```python
import torch

def _softmax(x, axis=-1):
    return torch.softmax(x, dim=axis)

def _gelu(x):
    return torch.nn.functional.gelu(x, approximate='tanh')

def _silu(x):
    return torch.nn.functional.silu(x)

def _sigmoid(x):
    return torch.sigmoid(x)

def _layernorm(x, axis=-1, eps=1e-05):
    m = x.mean(dim=axis, keepdim=True)
    v = x.var(dim=axis, keepdim=True, unbiased=False)
    return (x - m) / torch.sqrt(v + eps)

def _scatter_add(tgt, idx, src, axis=0):
    return tgt.clone().index_add_(axis, idx, src)

def _segment_sum(src, seg, n):
    out = torch.zeros((n,) + src.shape[1:], dtype=src.dtype)
    return out.index_add_(0, seg, src)

def _pad(x, pw):
    flat = tuple((v for pair in reversed(pw) for v in pair))
    return torch.nn.functional.pad(x, flat)
kernel_name = 'gated_mix__sliding_local_dilated__memory_aug_recurrent_mem_tr__prompt'

def setup_inputs():

    _w = lambda a: (lambda t: t.to(torch.bfloat16) if t.is_floating_point() else t)(torch.as_tensor(a))

    def _A_setup():
        B, S, D = (1, 2048, 576)
        return {'x': _w((lambda *s: torch.randn(*s, dtype=torch.bfloat16) * 0.05)(B, S, D)), 'wqkv': _w((lambda *s: torch.randn(*s, dtype=torch.bfloat16) * 0.8)(D, 3 * D)), 'wo': _w((lambda *s: torch.randn(*s, dtype=torch.bfloat16) * 0.05)(D, D))}
    _A_in = _A_setup()

    def _B_setup():
        B, S, Dm = (1, 2048, 576)
        H, Dh = (32, 128)
        M, seg = (8, 32)
        seg = min(seg, S)
        S = S // seg * seg
        return {'x': _w((lambda *s: torch.randn(*s, dtype=torch.bfloat16) * 0.05)(B, S, Dm)), 'mem0': _w((lambda *s: torch.randn(*s, dtype=torch.bfloat16) * 1.6)(B, M, Dm)), 'Wq': _w((lambda *s: torch.randn(*s, dtype=torch.bfloat16) * 0.8)(Dm, H, Dh) * Dm ** (-0.5)), 'Wk': _w((lambda *s: torch.randn(*s, dtype=torch.bfloat16) * 0.8)(Dm, H, Dh) * Dm ** (-0.5)), 'Wv': _w((lambda *s: torch.randn(*s, dtype=torch.bfloat16) * 1.6)(Dm, H, Dh) * Dm ** (-0.5)), 'Wo': _w((lambda *s: torch.randn(*s, dtype=torch.bfloat16) * 1.6)(H, Dh, Dm) * (H * Dh) ** (-0.5)), 'seg_len': seg}
    _B_in = _B_setup()
    return {'A_x': _A_in['x'], 'A_wqkv': _A_in['wqkv'], 'A_wo': _A_in['wo'], 'B_x': _B_in['x'], 'B_mem0': _B_in['mem0'], 'B_Wq': _B_in['Wq'], 'B_Wk': _B_in['Wk'], 'B_Wv': _B_in['Wv'], 'B_Wo': _B_in['Wo'], 'B_seg_len': _B_in['seg_len'], 'gate_w': _w((lambda *s: torch.randn(*s, dtype=torch.bfloat16) * 0.05)(576) * 16.0)}

def reference(A_x, A_wqkv, A_wo, B_x, B_mem0, B_Wq, B_Wk, B_Wv, B_Wo, B_seg_len, gate_w):

    def _A_ref(x, wqkv, wo):
        B, S, D = x.shape
        H = 32
        Dh = D // H
        W, dil = (8, 2)
        qkv = (lambda x, *d: x.permute(*d))((x @ wqkv).reshape(B, S, 3, H, Dh), 2, 0, 3, 1, 4)
        q, k, v = (qkv[0], qkv[1], qkv[2])
        scale = Dh ** (-0.5)
        pos = torch.arange(S)
        off = torch.arange(W) * dil
        idx = pos[:, None] - off[None, :]
        mask = idx >= 0
        idx_c = torch.where(mask, idx, 0).reshape(-1)
        kg = k[:, :, idx_c, :].reshape(B, H, S, W, Dh)
        vg = v[:, :, idx_c, :].reshape(B, H, S, W, Dh)
        logits = torch.einsum('bhsd,bhswd->bhsw', q, kg) * scale
        logits = torch.where(mask[None, None, :, :], logits, -1000000000.0)
        attn = _softmax(logits, axis=-1)
        o = torch.einsum('bhsw,bhswd->bhsd', attn, vg)
        return (lambda x, *d: x.permute(*d))(o, 0, 2, 1, 3).reshape(B, S, D) @ wo

    def _B_ref(x, mem0, Wq, Wk, Wv, Wo, seg_len):
        B, S, Dm = x.shape
        H, Dh = (Wq.shape[1], Wq.shape[2])
        M = mem0.shape[1]
        scale = Dh ** (-0.5)
        n_seg = S // seg_len
        L = M + seg_len
        idx = torch.arange(L)
        mask = (idx[:, None] < M) | (idx[:, None] >= idx[None, :])
        mem = mem0
        outs = []
        for s in range(n_seg):
            xs = x[:, s * seg_len:(s + 1) * seg_len, :].clone()
            h = torch.concatenate([mem, xs], axis=1)
            q = torch.einsum('btd,dhe->bhte', h, Wq)
            k = torch.einsum('btd,dhe->bhte', h, Wk)
            v = torch.einsum('btd,dhe->bhte', h, Wv)
            scores = torch.einsum('bhqe,bhke->bhqk', q, k) * scale
            scores = torch.where(mask[None, None], scores, -1000000000.0)
            p = _softmax(scores, axis=-1)
            o = torch.einsum('bhqk,bhke->bhqe', p, v)
            o = torch.einsum('bhte,hed->btd', o, Wo)
            mem = o[:, :M, :].clone()
            outs.append(o[:, M:, :])
        return torch.concatenate(outs, axis=1)
    x = A_x
    g = _sigmoid((x * gate_w).sum(-1, keepdims=True))
    a = _A_ref(x, A_wqkv, A_wo)
    b = _B_ref(x, B_mem0, B_Wq, B_Wk, B_Wv, B_Wo, B_seg_len)
    return g * a + (1 - g) * b
```

```cpp
#include <cuda_runtime.h>
#include <cuda_bf16.h>
#include <cuda_fp16.h>
#include <cuda.h>
#include <stdint.h>

typedef __nv_bfloat16 bf16;

constexpr int S_LEN = 2048, DM = 576, NH = 32, DH = 128, NSEG = 64, KCAT = 4096 + 576;
#define RED_LINE(i) (((i) >> 2) * 4096 + ((i) & 1) * 256 + ((i) & 2) * 512)
#define RED_SLOT(s) (((s) & 1) * 128 + ((s) & 2) * 256)

#define POLL_NS 896
#define NII 18
#define W3PRE 4
#define W3MID 4
#define GF 0
#define B5POS 0
#define NUP 4
#define UPF 1
#define B3Q 9
#define B3F 0
#define GATE 7
#define NTL 2
#define B7R 1
#define EXPOS 0
#define VW2 1
#define CLR 1
#define RFW 0
#define NIC 0
#define LEAD 0
#define FIN16 1
#define VXG 0
#define RING 63
#define EXB 0
#define EXD 0
#define EXB2 8192
#define HDLY 0
#define F10 1
#define NPROBE 2
#define QM 0
#define N5 224
#define KP(i) (((i) >> 1) + 4 * ((i) & 1))
#define SPIN_LIMIT (1 << 14)
#define XP 0

__device__ __align__(1024) bf16 g_Ocat[S_LEN * KCAT];
__device__ __align__(1024) bf16 g_qkvA[S_LEN * 3 * DM];
__device__ __align__(1024) unsigned char g_red_raw[2 * 262144];
constexpr int HINT_OFF = 2048;
__device__ __align__(16) float g_gate[S_LEN];
__device__ __align__(128) uint4 g_stats[96 * 2];
__device__ unsigned g_epoch;
__device__ unsigned g_epoch2;
__device__ unsigned g_oflag[NH * 32];
__device__ unsigned g_abar[3 * 32];
__device__ unsigned g_pace[32];
__device__ unsigned g_sflag[96 * 8];
__device__ __align__(1024) unsigned char g_seg[NSEG * 96 * 8192];
__device__ __align__(1024) unsigned char g_km[NSEG * NH * 4096];
__device__ __align__(1024) uint2 g_part[8 * 9 * 4 * 8 * 128];
__device__ int g_err;
#define SSTAMP(seg, idx)
#define QSTAMP(idx)
#define PROF(idx)
#define PROFP(idx)
#define STAMP(idx)
#define ASTAMP(idx)
#define WSTAMP(idx)

#define CSTAMP(idx)
#define CDECL
#define CDUMP
#define DI __device__ __forceinline__
DI uint32_t smem_u32(const void* p) { return (uint32_t)__cvta_generic_to_shared(p); }
DI uint32_t clock32() { uint32_t c; asm volatile("mov.u32 %0, %%clock;" : "=r"(c) :: "memory"); return c; }
DI uint32_t gtime() { uint32_t c; asm volatile("mov.u32 %0, %%globaltimer_lo;" : "=r"(c) :: "memory"); return c; }
DI uint32_t ldg_relaxed32(const void* p) { uint32_t v; asm volatile("ld.relaxed.gpu.global.b32 %0, [%1];" : "=r"(v) : "l"(p) : "memory"); return v; }
DI uint32_t ldg_acquire32(const void* p) { uint32_t v; asm volatile("ld.acquire.gpu.global.b32 %0, [%1];" : "=r"(v) : "l"(p) : "memory"); return v; }
DI void stg_relaxed32(void* p, uint32_t v) { asm volatile("st.relaxed.gpu.global.b32 [%0], %1;" :: "l"(p), "r"(v) : "memory"); }
DI int head_id() { int c; asm volatile("mov.u32 %0, %%clusterid.x;" : "=r"(c)); return c; }
DI uint32_t mapa(uint32_t a, uint32_t r) { uint32_t o; asm("mapa.shared::cluster.u32 %0, %1, %2;" : "=r"(o) : "r"(a), "r"(r)); return o; }
DI void cluster_arrive() { asm volatile("barrier.cluster.arrive.relaxed.aligned;" ::: "memory"); }
DI void cluster_wait() { asm volatile("barrier.cluster.wait.aligned;" ::: "memory"); }
DI void cluster_sync() { asm volatile("barrier.cluster.arrive.release.aligned;\nbarrier.cluster.wait.acquire.aligned;" ::: "memory"); }
DI void mbar_init(uint32_t b, uint32_t c) { asm volatile("mbarrier.init.shared::cta.b64 [%0], %1;" :: "r"(b), "r"(c) : "memory"); }
DI void mbar_expect(uint32_t b, uint32_t tx) { asm volatile("mbarrier.arrive.expect_tx.shared::cta.b64 _, [%0], %1;" :: "r"(b), "r"(tx) : "memory"); }
DI void mbar_arrive(uint32_t b) { asm volatile("mbarrier.arrive.shared::cta.b64 _, [%0];" :: "r"(b) : "memory"); }
DI void mbar_wait(uint32_t b, uint32_t par) {
  asm volatile("{\n.reg .pred p;\n.reg .u32 n, q;\nmov.u32 n, 0;\n"
               "WL: add.u32 n, n, 1;\nshr.u32 q, n, 12;\nxor.b32 q, q, %1;\n"
               "mbarrier.try_wait.parity.shared::cta.b64 p, [%0], q;\n@!p bra.uni WL;\n}"
               :: "r"(b), "r"(par) : "memory");
}
DI void wait_until(uint32_t t) {
  const uint32_t now = gtime();
  t = min(t, now + 8192);
  asm volatile("{\n.reg .pred p;\n.reg .u32 c;\nTL: mov.u32 c, %%globaltimer_lo;\nsetp.lt.u32 p, c, %0;\n@p bra.uni TL;\n}" :: "r"(t) : "memory");
}
#define PIN(v) v = __shfl_xor_sync(0xffffffffu, v, 0)
#define SCHED_FENCE(k) asm volatile("{\n.reg .pred p;\nsetp.eq.u32 p, %0, %1;\n@p exit;\n}" :: "r"(fence_reg), "r"(k) : "memory")
#define MEM_ORDER(k) asm volatile("{\n.reg .pred p;\nsetp.eq.u32 p, %0, %1;\n@p st.shared.u32 [%0], %0;\n}" :: "r"(fence_reg), "r"(k + 64) : "memory")
DI void bar_sync(int id, int n) { asm volatile("bar.sync %0, %1;" :: "r"(id), "r"(n) : "memory"); }
DI void bar_arrive(int id, int n) { asm volatile("bar.arrive %0, %1;" :: "r"(id), "r"(n) : "memory"); }
DI void fence_async() { asm volatile("fence.proxy.async.shared::cta;" ::: "memory"); }
DI void st_async4(uint32_t a, uint32_t x, uint32_t y, uint32_t z, uint32_t w, uint32_t mb) {
  asm volatile("st.async.weak.shared::cluster.mbarrier::complete_tx::bytes.v4.b32 [%0], {%1,%2,%3,%4}, [%5];"
               :: "r"(a), "r"(x), "r"(y), "r"(z), "r"(w), "r"(mb) : "memory");
}
DI void st_async2(uint32_t a, uint32_t x, uint32_t y, uint32_t mb) {
  asm volatile("st.async.weak.shared::cluster.mbarrier::complete_tx::bytes.v2.b32 [%0], {%1,%2}, [%3];"
               :: "r"(a), "r"(x), "r"(y), "r"(mb) : "memory");
}
DI void sts32(uint32_t a, uint32_t x) { asm volatile("st.shared.b32 [%0], %1;" :: "r"(a), "r"(x) : "memory"); }
DI void sts64(uint32_t a, uint32_t x, uint32_t y) { asm volatile("st.shared.v2.b32 [%0], {%1,%2};" :: "r"(a), "r"(x), "r"(y) : "memory"); }
DI void sts128(uint32_t a, uint32_t x, uint32_t y, uint32_t z, uint32_t w) {
  asm volatile("st.shared.v4.b32 [%0], {%1,%2,%3,%4};" :: "r"(a), "r"(x), "r"(y), "r"(z), "r"(w) : "memory");
}
DI uint32_t lds32(uint32_t a) { uint32_t x; asm volatile("ld.shared.b32 %0, [%1];" : "=r"(x) : "r"(a) : "memory"); return x; }
DI void lds64(uint32_t a, uint32_t& x, uint32_t& y) { asm volatile("ld.shared.v2.b32 {%0,%1}, [%2];" : "=r"(x), "=r"(y) : "r"(a) : "memory"); }
DI void lds128(uint32_t a, uint32_t* r) {
  asm volatile("ld.shared.v4.b32 {%0,%1,%2,%3}, [%4];" : "=r"(r[0]), "=r"(r[1]), "=r"(r[2]), "=r"(r[3]) : "r"(a) : "memory");
}
DI void lds128f(uint32_t a, float* r) {
  asm volatile("ld.shared.v4.f32 {%0,%1,%2,%3}, [%4];" : "=f"(r[0]), "=f"(r[1]), "=f"(r[2]), "=f"(r[3]) : "r"(a) : "memory");
}
DI void lds64f(uint32_t a, float* r) { asm volatile("ld.shared.v2.f32 {%0,%1}, [%2];" : "=f"(r[0]), "=f"(r[1]) : "r"(a) : "memory"); }
DI void ldsm4t(uint32_t* r, uint32_t a) {
  asm volatile("ldmatrix.sync.aligned.m8n8.x4.trans.shared.b16 {%0,%1,%2,%3}, [%4];"
               : "=r"(r[0]), "=r"(r[1]), "=r"(r[2]), "=r"(r[3]) : "r"(a) : "memory");
}
DI void ldsm4t_in(uint32_t* r, uint32_t a, uint32_t t) {
  asm volatile("{\n.reg .pred p;\nsetp.ne.u32 p, %5, 0;\n@p ldmatrix.sync.aligned.m8n8.x4.trans.shared.b16 {%0,%1,%2,%3}, [%4];\n}"
               : "+r"(r[0]), "+r"(r[1]), "+r"(r[2]), "+r"(r[3]) : "r"(a), "r"(t) : "memory");
}
DI void lds128_in(uint32_t* r, uint32_t a, uint32_t t) {
  asm volatile("{\n.reg .pred p;\nsetp.ne.u32 p, %5, 0;\n@p ld.shared.v4.b32 {%0,%1,%2,%3}, [%4];\n}"
               : "+r"(r[0]), "+r"(r[1]), "+r"(r[2]), "+r"(r[3]) : "r"(a), "r"(t) : "memory");
}
DI void ldsm2t_in(uint32_t* r, uint32_t a, uint32_t t) {
  asm volatile("{\n.reg .pred p;\nsetp.ne.u32 p, %3, 0;\n@p ldmatrix.sync.aligned.m8n8.x2.trans.shared.b16 {%0,%1}, [%2];\n}" : "+r"(r[0]), "+r"(r[1]) : "r"(a), "r"(t) : "memory");
}
DI void reserve2(uint32_t* r) { asm volatile("{\n.reg .u64 t;\nmov.u64 t, %%clock64;\nmov.b64 {%0, %1}, t;\n}" : "=r"(r[0]), "=r"(r[1])); }
DI void scale_sum(float& x, float& y, float s, uint32_t t) {
  asm volatile("{\n.reg .pred p;\nsetp.ne.u32 p, %2, 0;\n@p mul.f32 %0, %0, %1;\n}" : "+f"(y) : "f"(s), "r"(t));
  asm volatile("{\n.reg .pred p;\nsetp.ne.u32 p, %3, 1;\n@p fma.rn.f32 %0, %0, %1, %2;\n}" : "+f"(x) : "f"(s), "f"(y), "r"(t));
}
DI void ldsm4(uint32_t* r, uint32_t a) {
  asm volatile("ldmatrix.sync.aligned.m8n8.x4.shared.b16 {%0,%1,%2,%3}, [%4];"
               : "=r"(r[0]), "=r"(r[1]), "=r"(r[2]), "=r"(r[3]) : "r"(a) : "memory");
}
DI void st_async1(uint32_t a, uint32_t x, uint32_t mb) {
  asm volatile("st.async.weak.shared::cluster.mbarrier::complete_tx::bytes.b32 [%0], %1, [%2];" :: "r"(a), "r"(x), "r"(mb) : "memory");
}
DI void stsm4(uint32_t a, uint32_t x, uint32_t y, uint32_t z, uint32_t w) {
  asm volatile("stmatrix.sync.aligned.m8n8.x4.shared.b16 [%0], {%1,%2,%3,%4};" :: "r"(a), "r"(x), "r"(y), "r"(z), "r"(w) : "memory");
}
DI void stsm4t(uint32_t a, uint32_t x, uint32_t y, uint32_t z, uint32_t w) {
  asm volatile("stmatrix.sync.aligned.m8n8.x4.trans.shared.b16 [%0], {%1,%2,%3,%4};" :: "r"(a), "r"(x), "r"(y), "r"(z), "r"(w) : "memory");
}
DI uint32_t pack_bf16(float lo, float hi) { uint32_t r; asm("cvt.rn.bf16x2.f32 %0, %1, %2;" : "=r"(r) : "f"(hi), "f"(lo)); return r; }
DI uint32_t pack_f16(float lo, float hi) { uint32_t r; asm("cvt.rn.f16x2.f32 %0, %1, %2;" : "=r"(r) : "f"(hi), "f"(lo)); return r; }
DI float ex2(float x) { float y; asm("ex2.approx.ftz.f32 %0, %1;" : "=f"(y) : "f"(x)); return y; }
DI float rcp(float x) { float y; asm("rcp.approx.ftz.f32 %0, %1;" : "=f"(y) : "f"(x)); return y; }
DI float bf_lo(uint32_t x) { return __uint_as_float(x << 16); }
DI float bf_hi(uint32_t x) { return __uint_as_float(x & 0xffff0000u); }
DI void mma16816(float* d, const uint32_t* a, uint32_t b0, uint32_t b1) {
  asm volatile("mma.sync.aligned.m16n8k16.row.col.f32.bf16.bf16.f32 {%0,%1,%2,%3}, {%4,%5,%6,%7}, {%8,%9}, {%0,%1,%2,%3};"
               : "+f"(d[0]), "+f"(d[1]), "+f"(d[2]), "+f"(d[3]) : "r"(a[0]), "r"(a[1]), "r"(a[2]), "r"(a[3]), "r"(b0), "r"(b1));
}
DI void mma16816z(float* d, const uint32_t* a, uint32_t b0, uint32_t b1) {
  asm volatile("mma.sync.aligned.m16n8k16.row.col.f32.bf16.bf16.f32 {%0,%1,%2,%3}, {%4,%5,%6,%7}, {%8,%9}, {%10,%10,%10,%10};"
               : "=f"(d[0]), "=f"(d[1]), "=f"(d[2]), "=f"(d[3]) : "r"(a[0]), "r"(a[1]), "r"(a[2]), "r"(a[3]), "r"(b0), "r"(b1), "f"(0.f));
}
DI void mma1688z(float* d, uint32_t a0, uint32_t a1, uint32_t b0) {
  asm volatile("mma.sync.aligned.m16n8k8.row.col.f32.bf16.bf16.f32 {%0,%1,%2,%3}, {%4,%5}, {%6}, {%7,%7,%7,%7};"
               : "=f"(d[0]), "=f"(d[1]), "=f"(d[2]), "=f"(d[3]) : "r"(a0), "r"(a1), "r"(b0), "f"(0.f));
}
DI void mma1688(float* d, uint32_t a0, uint32_t a1, uint32_t b0) {
  asm volatile("mma.sync.aligned.m16n8k8.row.col.f32.bf16.bf16.f32 {%0,%1,%2,%3}, {%4,%5}, {%6}, {%0,%1,%2,%3};"
               : "+f"(d[0]), "+f"(d[1]), "+f"(d[2]), "+f"(d[3]) : "r"(a0), "r"(a1), "r"(b0));
}
DI void ldsm2t(uint32_t* r, uint32_t a) {
  asm volatile("ldmatrix.sync.aligned.m8n8.x2.trans.shared.b16 {%0,%1}, [%2];" : "=r"(r[0]), "=r"(r[1]) : "r"(a) : "memory");
}
DI uint32_t add_bf16(uint32_t a, uint32_t b) { uint32_t r; asm("add.rn.bf16x2 %0, %1, %2;" : "=r"(r) : "r"(a), "r"(b)); return r; }
DI uint32_t mul_bf16(uint32_t a, uint32_t b) { uint32_t r; asm("mul.rn.bf16x2 %0, %1, %2;" : "=r"(r) : "r"(a), "r"(b)); return r; }
DI uint64_t make_desc(uint32_t addr, uint32_t lbo, uint32_t sbo, uint32_t swz) {
  return (uint64_t)((addr & 0x3FFFF) >> 4) | ((uint64_t)(lbo >> 4) << 16) | ((uint64_t)(sbo >> 4) << 32) | ((uint64_t)swz << 62);
}
#define WG_FENCE() asm volatile("wgmma.fence.sync.aligned;" ::: "memory")
#define WG_COMMIT() asm volatile("wgmma.commit_group.sync.aligned;" ::: "memory")
#define WG_WAIT(n) asm volatile("wgmma.wait_group.sync.aligned %0;" :: "n"(n) : "memory")
#define ACC8(d, o) "+f"(d[o]), "+f"(d[o + 1]), "+f"(d[o + 2]), "+f"(d[o + 3]), "+f"(d[o + 4]), "+f"(d[o + 5]), "+f"(d[o + 6]), "+f"(d[o + 7])
DI void wgmma_n32_rs(float* d, uint32_t a0, uint32_t a1, uint32_t a2, uint32_t a3, uint64_t db, int acc) {
  asm volatile("{\n.reg .pred p;\nsetp.ne.b32 p, %21, 0;\n"
               "wgmma.mma_async.sync.aligned.m64n32k16.f32.bf16.bf16 {%0,%1,%2,%3,%4,%5,%6,%7,%8,%9,%10,%11,%12,%13,%14,%15}, "
               "{%16,%17,%18,%19}, %20, p, 1, 1, 0;\n}\n"
               : ACC8(d, 0), ACC8(d, 8) : "r"(a0), "r"(a1), "r"(a2), "r"(a3), "l"(db), "r"(acc));
}
template <int TA>
DI void wgmma_n32_ss(float* d, uint64_t da, uint64_t db, int acc) {
  asm volatile("{\n.reg .pred p;\nsetp.ne.b32 p, %18, 0;\n"
               "wgmma.mma_async.sync.aligned.m64n32k16.f32.bf16.bf16 {%0,%1,%2,%3,%4,%5,%6,%7,%8,%9,%10,%11,%12,%13,%14,%15}, "
               "%16, %17, p, 1, 1, %19, 1;\n}\n"
               : ACC8(d, 0), ACC8(d, 8) : "l"(da), "l"(db), "r"(acc), "n"(TA));
}
DI void tma_load(uint32_t dst, const CUtensorMap* m, int c0, int c1, uint32_t mb) {
  asm volatile("cp.async.bulk.tensor.2d.shared::cluster.global.mbarrier::complete_tx::bytes [%0], [%1, {%3, %4}], [%2];"
               :: "r"(dst), "l"(m), "r"(mb), "r"(c0), "r"(c1) : "memory");
}
DI void tma_load3(uint32_t dst, const CUtensorMap* m, int row, uint32_t mb) {
  asm volatile("cp.async.bulk.tensor.3d.shared::cluster.global.mbarrier::complete_tx::bytes [%0], [%1, {%3, %4, %3}], [%2];"
               :: "r"(dst), "l"(m), "r"(mb), "r"(0), "r"(row) : "memory");
}
DI bool elect_one() {
  uint32_t p;
  asm volatile("{\n.reg .pred p;\nelect.sync _|p, 0xffffffff;\nselp.u32 %0, 1, 0, p;\n}" : "=r"(p));
  return p;
}
DI void bulk_s2s(uint32_t dst, uint32_t src, uint32_t bytes, uint32_t mb) {
  asm volatile("cp.async.bulk.shared::cluster.shared::cta.mbarrier::complete_tx::bytes [%0], [%1], %2, [%3];"
               :: "r"(dst), "r"(src), "r"(bytes), "r"(mb) : "memory");
}
DI void bulk_load(uint32_t dst, const void* src, uint32_t bytes, uint32_t mb) {
  asm volatile("cp.async.bulk.shared::cluster.global.mbarrier::complete_tx::bytes [%0], [%1], %2, [%3];" :: "r"(dst), "l"(src), "r"(bytes), "r"(mb) : "memory");
}
DI void tma_prefetch(const CUtensorMap* m, int c0, int c1) {
  asm volatile("cp.async.bulk.prefetch.tensor.2d.L2.global.tile [%0, {%1, %2}];" :: "l"(m), "r"(c0), "r"(c1) : "memory");
}
DI void tma_store(const CUtensorMap* m, uint32_t src, int c0, int c1) {
  asm volatile("cp.async.bulk.tensor.2d.global.shared::cta.bulk_group [%0, {%2, %3}], [%1];" :: "l"(m), "r"(src), "r"(c0), "r"(c1) : "memory");
}
DI uint4 ldg_relaxed(const void* p) {
  uint4 v;
  asm volatile("ld.relaxed.gpu.global.v4.b32 {%0,%1,%2,%3}, [%4];" : "=r"(v.x), "=r"(v.y), "=r"(v.z), "=r"(v.w) : "l"(p) : "memory");
  return v;
}
DI void stg_relaxed(void* p, uint32_t x, uint32_t y, uint32_t z, uint32_t w) {
  asm volatile("st.relaxed.gpu.global.v4.b32 [%0], {%1,%2,%3,%4};" :: "l"(p), "r"(x), "r"(y), "r"(z), "r"(w) : "memory");
}
DI void red_f16x8(void* p, uint32_t x, uint32_t y, uint32_t z, uint32_t w) {
  asm volatile("red.relaxed.gpu.global.add.noftz.v4.f16x2 [%0], {%1,%2,%3,%4};" :: "l"(p), "r"(x), "r"(y), "r"(z), "r"(w) : "memory");
}
DI void sq_acc(uint32_t& a, uint32_t x) { asm("fma.rn.bf16x2 %0, %1, %1, %0;" : "+r"(a) : "r"(x)); }
DI __half2 amax4(__half2 h, const uint32_t* v) {
  h = __hmax2_nan(__hmax2_nan(h, __habs2(*(const __half2*)&v[0])), __habs2(*(const __half2*)&v[1]));
  return __hmax2_nan(__hmax2_nan(h, __habs2(*(const __half2*)&v[2])), __habs2(*(const __half2*)&v[3]));
}
DI uint32_t wexp(__half2 h) { const uint32_t u = *(const uint32_t*)&h; return __reduce_max_sync(0xffffffffu, max((u >> 16) & 0x7fffu, u & 0x7fffu)) >> 7; }
DI float max10(const float* a) {
  return fmaxf(fmaxf(fmaxf(fmaxf(a[0], a[1]), fmaxf(a[2], a[3])), fmaxf(fmaxf(a[4], a[5]), fmaxf(a[6], a[7]))), fmaxf(a[8], a[9]));
}
DI float quad_max(float m) {
  return fmaxf(fmaxf(m, __shfl_xor_sync(0xffffffffu, m, 1)), fmaxf(__shfl_xor_sync(0xffffffffu, m, 2), __shfl_xor_sync(0xffffffffu, m, 3)));
}
DI float warp_sum(float v) {
#pragma unroll
  for (int o = 16; o; o >>= 1) v += __shfl_xor_sync(0xffffffffu, v, o);
  return v;
}

constexpr int SM_WO3 = 0;
constexpr int SM_X = 16384;
constexpr int XT = 36864;
constexpr int SM_EXP = 126976;
constexpr int SEGB = 10240;
constexpr int SM_BLK = SM_EXP + 8192;
constexpr int SM_VC = SM_BLK + 4 * SEGB;
constexpr int SM_PART = SM_VC + 16384;
constexpr int SM_QM = SM_PART + 4096;
constexpr int SM_E = SM_QM + 1024;
constexpr int SM_VM = SM_E + 1536;
constexpr int SM_OB = SM_VM + 2048;
constexpr int SM_FB = SM_OB + 2048;
constexpr int SM_STAGE = SM_X + XT;
constexpr int SM_MISC = 210944;
constexpr int SM_WOST = 212992;
constexpr int SM_MEM = SM_WOST;
constexpr int SM_MAX = SM_MEM + 11264;
#define MEM_BLK(q) ((q) / 3 * 4096 + (q) % 3 * 1024)
constexpr int SM_TOTAL = 229376;
constexpr int MB_W = SM_MISC;
constexpr int MB_WO = SM_MISC + 24;
constexpr int MB_WO3 = SM_MISC + 32;
constexpr int MB_X = SM_MISC + 40;
constexpr int MB_S = SM_MISC + 64;
constexpr int MB_F = SM_MISC + 72;
constexpr int MB_VX = SM_MISC + 80;
constexpr int SC_FPAR = SM_MISC + 136;
constexpr int SC_DEAD = SM_MISC + 96;
constexpr int SC_UNSC = SM_MISC + 112;
constexpr int SC_EXPW = SM_MISC + 132;
constexpr int SC_ONES = SM_MISC + 144;
constexpr int SC_SS = SM_MISC + 160;
constexpr int SC_LAT = SM_MISC + 224;
constexpr int SC_EPO = SM_MISC + 240;
constexpr int SC_XMAX = SM_MISC + 256;
constexpr int SC_PROF = 229376;

constexpr float SM_SCALE = 0.08838834764831845f;
constexpr float LOG2E = 1.4426950408889634f;
constexpr float E_LIM = 20.f;

template <bool B> struct BoolC { static constexpr bool value = B; };
struct RMaps { CUtensorMap x, wq, wk, wv, wo; unsigned char* red; uint32_t poll; const unsigned char* w[4]; };

DI uint32_t latest_hint(uint32_t h, uint32_t d, int s) {
  const uint32_t x = (((h | 0xc0c0c0c0u) - ((d >> 5) & 63) * 0x01010101u) & 0x3f3f3f3fu) | ((h ^ (((s >> 2) + 1) & 3) * 0x40404040u) & 0xc0c0c0c0u);
  const uint32_t y = __vmaxu2(x & 0x00ff00ffu, (x >> 8) & 0x00ff00ffu);
  return __reduce_max_sync(0xffffffffu, max(y & 0xffffu, y >> 16));
}
DI uint32_t near_half(uint32_t sb) {
  uint32_t a, b; lds64(sb + SC_LAT, a, b);
  return a > b;
}

template <int RT, int K0, int K1, bool D32 = false>
DI void xproj(float* acc, const uint32_t (&wa)[2][18][4], uint64_t xd) {
  if (XP & 1) return;
  WG_FENCE();
#pragma unroll
  for (int k = K0; k < ((XP & 128) ? K0 + 1 : K1); k++)
  {
    uint64_t d = xd + (uint64_t)(((k >> 1) * 4096 + (k & 1) * 32) >> 4);
    if (D32) asm("mov.b64 %0, {%1, %2};" : "=l"(d) : "r"((uint32_t)xd + (((k >> 1) * 4096 + (k & 1) * 32) >> 4)), "r"((uint32_t)(xd >> 32)));
    wgmma_n32_rs(acc, wa[RT][k][0], wa[RT][k][1], wa[RT][k][2], wa[RT][k][3], d, k != 0);
  }
  WG_COMMIT();
}

DI void seg_store(int seg, uint32_t sb) {
  fence_async();
  asm volatile("cp.async.bulk.global.shared::cta.bulk_group [%0], [%1], 8192;"
               :: "l"(g_seg + ((size_t)(seg & RING) * 96 + blockIdx.x) * 8192), "r"(sb + SM_BLK + (seg & 3) * SEGB) : "memory");
  asm volatile("cp.async.bulk.commit_group;" ::: "memory");
}
DI void seg_publish(int seg, uint32_t sb) {
  const uint32_t v = lds32(sb + SC_EPO) + seg;
  asm volatile("cp.async.bulk.wait_group 0;" ::: "memory");
  stg_relaxed32(&g_sflag[blockIdx.x * 8], v);
}

DI void proj_role(const uint32_t sb, const RMaps& tm, const uint32_t rank, const int wg, const int w, const int lane) {
  const bool qk = rank < 2;
  uint32_t wa[2][18][4];
  {
    const int rr = (lane & 7) + ((lane >> 4) << 3);
    const uint32_t col = ((2 * w + ((lane >> 3) & 1)) ^ (lane & 7)) << 4;
    float ss = 0.f;
#pragma unroll
    for (int c = 0; c < 3; c++) {
      QSTAMP(2 + 2 * c);
      mbar_wait(sb + MB_W + 8 * c, 0);
      QSTAMP(3 + 2 * c);
#pragma unroll
      for (int rt = 0; rt < 2; rt++)
#pragma unroll
        for (int k = 0; k < 6; k++)
          ldsm4t(wa[rt][c * 6 + k], sb + SM_STAGE + c * 49152 + (rt ^ wg) * 24576 + (64 * (k >> 1) + 32 * wg + 16 * (k & 1) + rr) * 128 + col);
      if (c < 2) {
        fence_async();
        bar_sync(3, 256);
        if (threadIdx.x == 0) {
          if (c == 0) tma_load3(sb + SM_X + XT, &tm.x, 32, sb + MB_X + 8);
          else tma_load(sb + SM_X + 2 * XT, &tm.wo, rank * 192, (blockIdx.x / 3) * DH, sb + MB_WO);
        }
        __syncwarp();
      }
      uint32_t q[4] = {0, 0, 0, 0};
#pragma unroll
      for (int rt = 0; rt < 2; rt++)
#pragma unroll
        for (int k = 0; k < 6; k++)
#pragma unroll
          for (int i = 0; i < 4; i++) sq_acc(q[i], wa[rt][c * 6 + k][i]);
#pragma unroll
      for (int i = 0; i < 4; i++) ss += bf_lo(q[i]) + bf_hi(q[i]);
    }
    ss = warp_sum(ss);
    fence_async();
    cluster_arrive();
    if (lane == 0) sts32(sb + SC_SS + 4 * (wg * 4 + w), qk ? 0 : __float_as_uint(ss));
    bar_arrive(11, 384);
  }
  STAMP(1);
  QSTAMP(8);
  mbar_wait(sb + MB_X, 0);
  STAMP(2);
  QSTAMP(9);

  uint32_t t16 = sb + (w * 32 + lane) * 16;
  uint32_t mem_a = sb + SM_MEM + wg * 512 + lane * 16;
  uint32_t fin_a = sb + (lane & 7) * 16 + SM_BLK + (qk ? (wg ^ 1) * 4096 + w * 256 + (lane & 8) * 16 + (lane & 16) * 64
                                              : wg * 4096 + w * 1024 + (lane & 8) * 64 + (lane & 16) * 8);
  PIN(t16); PIN(mem_a); PIN(fin_a);
  const uint32_t fence_reg = mem_a;
  const uint32_t fin2 = qk ? 2048 : 256;
  float acc[16];
  const uint64_t xd0 = make_desc(sb + SM_X + wg * 64, 16, 1024, 1);
  auto do_export = [&]() {
    WG_WAIT(0);
#pragma unroll
    for (int i = 0; i < 2; i++)
      sts128(t16 + SM_EXP + wg * 4096 + i * 2048, pack_bf16(acc[8 * i], acc[8 * i + 1]), pack_bf16(acc[8 * i + 2], acc[8 * i + 3]),
             pack_bf16(acc[8 * i + 4], acc[8 * i + 5]), pack_bf16(acc[8 * i + 6], acc[8 * i + 7]));
  };
  uint32_t o[8];
  auto import = [&]() { lds128(t16 + SM_EXP + (wg ^ 1) * 4096, o); lds128(t16 + SM_EXP + (wg ^ 1) * 4096 + 2048, o + 4); };
  auto finish = [&](int seg) {
    const uint32_t a = fin_a + (seg & 3) * SEGB;
    WG_WAIT(0);
#pragma unroll
    for (int i = 0; i < 8; i++) o[i] = FIN16 ? add_bf16(pack_bf16(acc[2 * i], acc[2 * i + 1]), o[i]) : pack_bf16(acc[2 * i] + bf_lo(o[i]), acc[2 * i + 1] + bf_hi(o[i]));
    stsm4(a, o[0], o[1], o[2], o[3]);
    stsm4(a + fin2, o[4], o[5], o[6], o[7]);
  };
  auto send_v = [&](int seg, int dst) {
    fence_async();
    if (seg < NSEG - 1 && !(XP & 2) && elect_one())
      bulk_s2s(mapa(sb + SM_VC + (seg & 1) * 8192, dst), sb + SM_BLK + (seg & 3) * SEGB, 8192, mapa(sb + MB_VX + (seg & 1) * 8, dst));
    __syncwarp();
  };
  auto wait_v = [&](int seg) {
    if (seg < NSEG - 1 && !(XP & 2)) {
      mbar_wait(sb + MB_VX + (seg & 1) * 8, (seg >> 1) & 1);
      if (elect_one()) mbar_expect(sb + MB_VX + (seg & 1) * 8, 8192);
      __syncwarp();
    }
  };
  bar_sync(3, 256);
  xproj<1, 0, 18>(acc, wa, xd0);
  do_export();
  SCHED_FENCE(11);
  xproj<0, 0, 18>(acc, wa, xd0);
  bar_sync(3, 256);
  QSTAMP(10);
  cluster_wait();
  QSTAMP(11);
  mbar_wait(sb + MB_X + 8, 0);
  QSTAMP(12);
  import();
  finish(0);
  SCHED_FENCE(12);
  bar_sync(3, 256);
  uint64_t dA = xd0 + (XT >> 4);
  xproj<1, 0, 18>(acc, wa, dA);
  if (!qk && wg == 0 && w < 2) send_v(0, w);
  do_export();
  QSTAMP(13);
  if (qk && wg == 0 && w == 0) wait_v(0);
  QSTAMP(14);
  bar_arrive(13, 384);
  if (!qk) {
    SCHED_FENCE(15);
    xproj<0, 0, 18>(acc, wa, dA);
    if (threadIdx.x == 0 && !(XP & 8)) { mbar_expect(sb + MB_X, XT); tma_load3(sb + SM_X, &tm.x, 96, sb + MB_X); }
    bar_sync(3, 256);
    mbar_wait(sb + MB_X + 16, 0);
    import();
    finish(1);
    SCHED_FENCE(16);
    bar_sync(3, 256);
    dA += XT >> 4;
    xproj<1, 0, 18>(acc, wa, dA);
    if (wg == 0 && w < VW2) send_v(1, w);
    do_export();
  }
  QSTAMP(15);
  bar_sync(0, 384);
  QSTAMP(16);
  const int ro = __shfl_sync(0xffffffffu, near_half(sb) ^ wg, 0);
  STAMP(5);
  const uint32_t always = __shfl_sync(0xffffffffu, lds32(sb + SC_DEAD + 12), 0);
  const int ah = qk ? 1 : 2;
  int b2 = qk ? 2 : 0;
  int s = 0;
  uint32_t hint_lo = (uint32_t)(uint64_t)tm.red + HINT_OFF + blockIdx.x + (lane & 1) * 4096 + (lane >> 1) * 16384;
  PIN(hint_lo);
  auto post_hint = [&]() {
    asm volatile("{\n.reg .pred p;\n.reg .b64 a;\n.reg .u32 t;\nsetp.lt.u32 p, %0, %1;\nmov.b64 a, {%2, %3};\nmov.u32 t, %%globaltimer_lo;\n"
                 "bfe.u32 t, t, 5, 6;\nor.b32 t, t, %4;\n@p st.relaxed.gpu.global.u8 [a], t;\n}"
                 :: "r"(t16), "r"(sb + 128), "r"(hint_lo + RED_SLOT(s)), "r"((uint32_t)((uint64_t)tm.red >> 32)), "r"(((s >> 2) + 1) << 6) : "memory");
  };
  auto memproj = [&](auto second, int id, float u0, float u1, float* r) {
    constexpr bool R1 = decltype(second)::value;
    uint32_t b[NUP][4], b0[4];
    SCHED_FENCE(id);
    bar_sync(R1 ? 2 : 1, 256);
    PROF(0);
    ldsm4t(b0, mem_a);
#pragma unroll
    for (int q = 0; q < NUP; q++) {
      if (R1 && q == 2) {
        bar_sync(11, 256);
        SCHED_FENCE(id + 1);
      }
      ldsm4t(b[q], mem_a + MEM_BLK(q + 1));
    }
    mma16816z(&acc[0], wa[0][0], b0[0], b0[1]);
    mma16816z(&acc[4], wa[1][0], b0[0], b0[1]);
    mma16816z(&acc[8], wa[0][1], b0[2], b0[3]);
    mma16816z(&acc[12], wa[1][1], b0[2], b0[3]);
#pragma unroll
    for (int q = 1; q < 9; q++) {
      uint32_t* const c = b[(q - 1) % NUP];
      mma16816(&acc[0], wa[0][2 * q], c[0], c[1]);
      mma16816(&acc[4], wa[1][2 * q], c[0], c[1]);
      mma16816(&acc[8], wa[0][2 * q + 1], c[2], c[3]);
      mma16816(&acc[12], wa[1][2 * q + 1], c[2], c[3]);
      if (R1 && q + NUP == B3Q) bar_sync(3, 256);
      if (q + NUP < 9) ldsm4t_in(c, mem_a + MEM_BLK(q + NUP), always);
      else if (R1 && q + NUP < 11) lds128_in(c, t16 + SM_PART + (10 - q - NUP) * 2048, always);
      else if (!R1 && GATE && q == GATE) { bar_arrive(11, 256); lds128_in(c, sb + SC_DEAD, always); u0 = u1 = __uint_as_float(c[3]); }
    }
#pragma unroll
    for (int i = 0; i < 8; i++) {
      const float u = i < 4 ? u0 : u1;
      r[i] = R1 ? fmaf(acc[8 + i], u, (acc[i] + __uint_as_float(b[(8 + i / 4) % NUP][i & 3])) * u) : (GATE ? fmaf(acc[i], u, acc[8 + i]) : acc[i] + acc[8 + i]);
    }
  };
  if (ro == 0) {
#pragma unroll 1
    while (true) {
      if (s == 8) STAMP(6);
      float r[8];
      memproj(BoolC<false>(), 30, 0.f, 0.f, r);
      sts128(t16 + SM_PART, __float_as_uint(r[0]), __float_as_uint(r[1]), __float_as_uint(r[2]), __float_as_uint(r[3]));
      sts128(t16 + SM_PART + 2048, __float_as_uint(r[4]), __float_as_uint(r[5]), __float_as_uint(r[6]), __float_as_uint(r[7]));
      bar_arrive(3, 256);
      PROF(1);
      bar_sync(9, 256);
      if (s == NSEG - 1) break;
      post_hint();
      if (w == 1) {
        uint32_t m[8];
        lds128(t16 + SM_MAX - 512, m); lds128(t16 + SM_MAX, m + 4);
        const int em = (wexp(amax4(amax4(*(const __half2*)&m[0], m), m + 4)) >> 3) + (int)(lds32(sb + SC_UNSC + (s & 1) * 8) >> 23) - 15;
        const int ex = max(s ? em : 0, (int)lds32(sb + SC_XMAX + 4 * s)) - 127 + (int)lds32(sb + SC_EXPW);
        sts32(sb + SC_UNSC + (~s & 1) * 8, (127 + min(max(ex, -120), 120)) << 23);
        __syncwarp();
        if (elect_one()) mbar_arrive(sb + MB_S);
      }
      SCHED_FENCE(9);
      bar_sync(5, qk ? N5 : 256);
      PROF(2);
      import();
      xproj<0, 0, NII>(acc, wa, dA);
      if (NII < 18) {
        if (qk) bar_sync(7, 384);
        xproj<0, NII, 18>(acc, wa, dA);
        if (!qk) bar_sync(7, 384);
      } else {
        if (F10) WG_WAIT(0);
        bar_sync(10, 256);
        if (F10) SCHED_FENCE(17);
      }
      dA += (int64_t)(b2 ? XT >> 4 : -(XT >> 3));
      finish(s + ah);
      if (qk || w >= VW2) bar_arrive(13, 384);
      PROF(6);
      SCHED_FENCE(14);
      bar_sync(12, 256);
      PROF(7);
      xproj<1, 0, 18, true>(acc, wa, dA);
      bar_arrive(14, 256);
      b2 = b2 == 2 ? 0 : b2 + 1;
      s++;
      if (!qk && w < VW2) { bar_sync(13, 384); send_v(s + 1, w); }
      PROFP(8);
      do_export();
      PROFP(3);
    }
    if (!qk) bar_arrive(5, 256);
  } else {
#pragma unroll 1
    while (true) {
      if (s == 8) STAMP(6);
      const uint32_t tl = ((t16 >> 8) ^ wg) & 1, am = (t16 & ~256u) - w * 256;
      const float un = __uint_as_float(lds32(sb + SC_UNSC + (s & 1) * 8));
      float r[8];
      if (qk) {
        uint32_t a0 = am + (tl ? SM_QM : SM_BLK + 8192 + (s & 3) * SEGB);
        float u0 = wg ? un * (SM_SCALE * LOG2E) : un, u1 = wg ? un : un * (SM_SCALE * LOG2E);
        PIN(a0); PIN(u0); PIN(u1);
        memproj(BoolC<true>(), 32, u0, u1, r);
        const uint32_t p0 = pack_bf16(r[0], r[1]), p1 = pack_bf16(r[2], r[3]), p2 = pack_bf16(r[4], r[5]), p3 = pack_bf16(r[6], r[7]);
        stsm4(a0, p0, p1, p2, p3);
        bar_arrive(4, 256);
        SCHED_FENCE(18);
        if (!(XP & 4))
          asm volatile("st.relaxed.gpu.global.v2.b32 [%0], {%1,%2};" :: "l"(g_km + (size_t)(s * NH + head_id()) * 4096 + (rank * 1024 + ((t16 - sb) >> 1))),
                       "r"(((wg ? p2 : p0) & ~1u) | lds32(sb + SC_EPO + 4)), "r"(wg ? p3 : p1) : "memory");
      } else {
        const uint32_t d0 = s < NSEG - 1 ? 0 : 2, d1 = s < NSEG - 1 ? 1 : 2;
        uint32_t r0 = mapa(t16 + SM_VM, d0), r1 = mapa(t16 + SM_VM, d1);
        PIN(r0); PIN(r1);
        memproj(BoolC<true>(), 34, un, un, r);
        const uint32_t p0 = pack_bf16(r[0], r[1]), p1 = pack_bf16(r[2], r[3]), p2 = pack_bf16(r[4], r[5]), p3 = pack_bf16(r[6], r[7]);
        const uint32_t v0 = wg ? p2 : p0, v1 = wg ? p3 : p1, v2 = wg ? p0 : p2, v3 = wg ? p1 : p3;
        st_async4(r0, v0, v1, v2, v3, mapa(sb + MB_S, d0));
        st_async4(r1, v0, v1, v2, v3, mapa(sb + MB_S, d1));
        bar_arrive(5, 256);
        sts128(t16 + SM_VM, v0, v1, v2, v3);
        __syncwarp();
        if (elect_one()) mbar_arrive(sb + MB_S);
        SCHED_FENCE(19);
        if (!(XP & 4)) stg_relaxed(g_km + (size_t)(s * NH + head_id()) * 4096 + (2048 + t16 - sb), (v0 & ~1u) | lds32(sb + SC_EPO + 4), v1, v2, v3);
      }
      if (s == NSEG - 1) break;
      PROF(1);
      auto rearm = [&]() { mbar_wait(sb + MB_S, s & 1); if (elect_one()) mbar_expect(sb + MB_S, qk ? 640 + 2048 : 1280); __syncwarp(); };
      if (w == 1) {
        if ((t16 & 384) == 0) stg_relaxed(tm.red + (RED_SLOT(s + 2) + RED_LINE(blockIdx.x)) + (t16 & 112), 0, 0, 0, 0);
      } else if (w == 0) {
        const int tn = s + ah + 1;
        if (RFW) mbar_wait(sb + MB_S, s & 1);
        if (tn + 1 < NSEG && !(XP & 8) && elect_one()) {
          const int b0 = b2 == 2 ? 0 : b2 + 1;
          mbar_expect(sb + MB_X + 8 * b0, XT);
          tma_load3(sb + SM_X + b0 * XT, &tm.x, (tn + 1) * 32, sb + MB_X + 8 * b0);
        }
        if (tn < NSEG && (!(XP & 8) || tn < 3)) mbar_wait(sb + MB_X + 8 * b2, (tn / 3) & 1);
      } else if (w == 2) {
        if (!qk) { if (VW2 < 1) send_v(s + 1, 0); if (VW2 < 2) send_v(s + 1, 1); }
      } else if (qk || !NIC) {
        rearm();
      }
      __syncwarp();
      import();
      PROF(4);
      SCHED_FENCE(10);
      if (NIC) {
        if (qk) bar_sync(7, NII < 18 ? 384 : 256);
        xproj<0, 0, NIC>(acc, wa, dA);
        if (!qk) { if (w == 3) rearm(); bar_sync(7, NII < 18 ? 384 : 256); }
      } else {
        bar_sync(7, NII < 18 ? 384 : 256);
      }
      xproj<0, NIC, 18>(acc, wa, dA);
      bar_arrive(12, 256);
      dA += (int64_t)(b2 ? XT >> 4 : -(XT >> 3));
      finish(s + ah);
      if (qk && w == 0) wait_v(s + 1);
      bar_arrive(13, 384);
      PROF(6);
      SCHED_FENCE(13);
      bar_sync(14, 256);
      PROF(7);
      xproj<1, 0, 18>(acc, wa, dA);
      b2 = b2 == 2 ? 0 : b2 + 1;
      s++;
      PROFP(8);
      do_export();
      PROFP(3);
    }
  }
  bar_arrive(0, 384);
  STAMP(3);
  cluster_sync();
  STAMP(4);
}

DI void attn_role(const uint32_t sb, unsigned char* smem_raw, const RMaps& tm, const uint32_t RANK, const bf16* __restrict__ x, const bf16* __restrict__ mem0,
                  const int w, const int lane) {
  const int t2 = w * 32 + lane;
  uint32_t wo[8][4], w1[8][4];
  const uint32_t wo_lane = sb + ((lane & 7) + ((lane >> 4) << 3)) * 128 + (((w + 4 * ((lane >> 3) & 1)) ^ (lane & 7)) << 4);
  unsigned char* const g_red = tm.red;
  {
    const uint32_t tag = *(volatile unsigned*)&g_epoch + 1;
    if (w == 0) {
      stg_relaxed(g_red + RED_SLOT(t2 >> 3) + RED_LINE(blockIdx.x) + (t2 & 7) * 16, 0, 0, 0, 0);
      asm volatile("st.relaxed.gpu.global.u8 [%0], 0;" :: "l"(g_red + RED_SLOT(t2) + HINT_OFF + (t2 & 4) * 1024 + (t2 >> 3) * 16384 + blockIdx.x) : "memory");
    }
    uint4 mv[5], xv[18];
#pragma unroll
    for (int i = 0; i < 5; i++) mv[i] = t2 + 128 * i < DM ? ((const uint4*)mem0)[t2 + 128 * i] : make_uint4(0, 0, 0, 0);
#pragma unroll
    for (int i = 0; i < 18; i++) xv[i] = blockIdx.x < NSEG ? ((const uint4*)(x + blockIdx.x * 32 * DM))[t2 + 128 * i] : make_uint4(0, 0, 0, 0);
    QSTAMP(0);
    bar_sync(0, 384);
    QSTAMP(1);
    cluster_arrive();
    __half2 hx = __float2half2_rn(0.f);
#pragma unroll
    for (int i = 0; i < 18; i++) hx = amax4(hx, &xv[i].x);
    if (blockIdx.x == 0)
#pragma unroll
      for (int i = 0; i < 5; i++) hx = amax4(hx, &mv[i].x);
    sts32(sb + SC_SS + 4 * (12 + w), wexp(hx));
    if (t2 == 0) { sts64(sb + SC_EPO, (tag - 1) * NSEG + 1, tag & 1); sts32(sb + SC_UNSC, __float_as_uint(1.f)); sts128(sb + SC_DEAD, 0, 0, 0, 0x3f800000u); sts64(sb + SC_FPAR, 0, 0); sts128(sb + SC_ONES, 0x3f803f80u, 0x3f803f80u, 0x3f803f80u, 0x3f803f80u); }
    WSTAMP(27);
    if (w == 0) __threadfence();
    uint32_t q[8] = {0, 0, 0, 0, 0, 0, 0, 0};
    QSTAMP(2);
    mbar_wait(sb + MB_WO3, 0);
    QSTAMP(3);
#pragma unroll
    for (int k = 0; k < 8; k++) {
      ldsm4t(wo[k], wo_lane + SM_WO3 + k * 2048); ldsm4t(w1[k], wo_lane + SM_WOST + k * 2048);
#pragma unroll
      for (int i = 0; i < 4; i++) { sq_acc(q[i], wo[k][i]); sq_acc(q[i], w1[k][i]); }
    }
    bar_sync(6, 128);
#pragma unroll
    for (int k = 0; k < 8; k++) sts128(sb + SM_WO3 + t2 * 16 + k * 2048, wo[k][0], wo[k][1], wo[k][2], wo[k][3]);
#pragma unroll
    for (int i = 0; i < 5; i++) {
      const int e = t2 + 128 * i, tok = e / 72, c = (e - tok * 72) * 8;
      const uint32_t u[4] = {mv[i].x, mv[i].y, mv[i].z, mv[i].w};
      if (e < DM)
#pragma unroll
        for (int j = 0; j < 8; j++) *(unsigned short*)(smem_raw + SM_MEM + (c + c / 192 * 64 + j) * 16 + tok * 2) = (unsigned short)(u[j >> 1] >> (16 * (j & 1)));
    }
    bar_arrive(1, 256); bar_arrive(2, 256); bar_arrive(9, 256);
    QSTAMP(4);
    mbar_wait(sb + MB_WO, 0);
    QSTAMP(5);
#pragma unroll
    for (int k = 0; k < 8; k++) ldsm4t(wo[k], wo_lane + SM_X + 2 * XT + k * 2048);
    fence_async();
    bar_sync(6, 128);
    if (t2 == 32) tma_load3(sb + SM_X + 2 * XT, &tm.x, 64, sb + MB_X + 16);
    __syncwarp();
#pragma unroll
    for (int k = 0; k < 8; k++)
#pragma unroll
      for (int i = 0; i < 4; i++) sq_acc(q[4 + i], wo[k][i]);
    float ss = 0.f;
#pragma unroll
    for (int i = 0; i < 8; i++) ss += bf_lo(q[i]) + bf_hi(q[i]);
    ss = warp_sum(ss);
    if (lane == 0) sts32(sb + SC_SS + 4 * (8 + w), __float_as_uint(ss));
    QSTAMP(6);
    bar_sync(11, 384);
    QSTAMP(7);
    if (t2 == 0) {
      float a[16];
#pragma unroll
      for (int i = 0; i < 4; i++) lds128f(sb + SC_SS + 16 * i, &a[4 * i]);
      stg_relaxed(&g_stats[blockIdx.x * 2], __float_as_uint(((a[0] + a[1]) + (a[2] + a[3])) + ((a[4] + a[5]) + (a[6] + a[7]))),
                  __float_as_uint((a[8] + a[9]) + (a[10] + a[11])),
                  max(max(__float_as_uint(a[12]), __float_as_uint(a[13])), max(__float_as_uint(a[14]), __float_as_uint(a[15]))), tag);
    }
    __syncwarp();
    WSTAMP(24);
    QSTAMP(8);
    cluster_wait();
    QSTAMP(9);
    if (w == 0) {
      uint4 v[3];
      int n = 0;
      while (true) {
#pragma unroll
        for (int i = 0; i < 3; i++) v[i] = ldg_relaxed(&g_stats[(i * 32 + lane) * 2]);
        if (__all_sync(0xffffffffu, v[0].w == tag && v[1].w == tag && v[2].w == tag) || ++n > SPIN_LIMIT) break;
        __nanosleep(100);
      }
      WSTAMP(25);
      QSTAMP(10);
      const float sv = warp_sum(__uint_as_float(v[0].x) + __uint_as_float(v[1].x) + __uint_as_float(v[2].x));
      const float so = warp_sum(__uint_as_float(v[0].y) + __uint_as_float(v[1].y) + __uint_as_float(v[2].y));
      const int expW = ((int)(__float_as_uint(sv) >> 23) + (int)(__float_as_uint(so) >> 23) - 254 + 2 + 10 + 1) >> 1;
      sts32(sb + SC_XMAX + 4 * lane, v[0].z); sts32(sb + SC_XMAX + 128 + 4 * lane, v[1].z);
      sts32(sb + SC_EXPW, expW + 1 - 15);
      if (blockIdx.x == 0 && lane == 0) *(volatile unsigned*)&g_epoch = tag;
      sts32(sb + SC_FPAR + 4, 1);
    } else if (w < 3) {
      const uint32_t u = blockIdx.x >> 4;
      unsigned char* const z = g_red + 98304 + (blockIdx.x & 15) * 128 + (u & 1) * 2048 + (u & 6) * 4096 + (((u >> 1) ^ w) & 1) * 4096 + lane * 4;
      stg_relaxed32(z, 0);
      uint32_t best = 0xffffffffu;
#pragma unroll 1
      for (int i = 0; i < 64; i++) {
        uint32_t last, dt;
        asm volatile("{\n.reg .pred p;\n.reg .u32 c, v;\nld.volatile.shared.u32 %0, [%3];\nmov.u32 c, %%clock;\n"
                     "atom.relaxed.gpu.global.exch.b32 v, [%2], 0;\nsetp.eq.u32 p, v, 0;\nmov.u32 %1, 0;\n@p mov.u32 %1, %%clock;\nsub.u32 %1, %1, c;\n}"
                     : "=r"(last), "=r"(dt) : "l"(z), "r"(sb + SC_FPAR + 4) : "memory");
        best = min(best, dt);
        if (last && i >= NPROBE - 1) break;
      }
      sts32(sb + SC_LAT + (w - 1) * 4, best);
    }
    QSTAMP(11);
    bar_sync(13, 384);
    bar_arrive(0, 384);
    QSTAMP(12);
    WSTAMP(26);
  }

  const uint32_t nh = __shfl_sync(0xffffffffu, near_half(sb), 0);
  uint32_t l16 = sb + lane * 16;
  PIN(l16);
#define LV ((l16 >> 4) & 31)
#define fence_reg l16
  const uint32_t red_lo = (uint32_t)(uint64_t)g_red, red_hi = (uint32_t)((uint64_t)g_red >> 32);
  uint32_t lp;
  auto slot = [&](int s, uint32_t c, uint32_t ofs) {
    const uint32_t lo = lp | (red_lo + ((w >> 1) * 4 + (w & 1) * 2 + ((w ^ c) & 1)) * 4096 + RED_SLOT(s) + ofs);
    uint64_t a; asm("mov.b64 %0, {%1, %2};" : "=l"(a) : "r"(lo), "r"(red_hi));
    return (unsigned char*)a;
  };
  const uint32_t always = __shfl_sync(0xffffffffu, lds32(sb + SC_DEAD + 12), 0);
  const int mode0 = RANK < 2 ? w : w | 4;
  auto hint_addr = [&](int s) { return min(LV, 23u) * 4 + (red_lo + HINT_OFF + nh * 4096 + w * 16384 + RED_SLOT(s)); };
  auto load_hints = [&](uint32_t lo) {
    uint64_t a; asm("mov.b64 %0, {%1, %2};" : "=l"(a) : "r"(lo), "r"(red_hi));
    return ldg_relaxed32((const void*)a);
  };
  auto export_seg = [&](int seg) { if (!(XP & 4) && elect_one()) seg_store(seg, sb); __syncwarp(); };
  auto publish = [&](int seg) { if (!(XP & 4) && elect_one()) seg_publish(seg, sb); __syncwarp(); };
  uint32_t dl = __shfl_sync(0xffffffffu, gtime() - 768, 0);
  int s = 0;
  bool bad = false;
#pragma unroll 1
  while (true) {
    const uint32_t par = s & 1;
    uint32_t vx[4][4], hints;
    auto load_vx = [&]() {
      const uint32_t va = l16 + (RANK < 2 ? SM_VC + par * 8192 : SM_BLK + (s & 3) * SEGB) + w * 1024 + ((LV >> 3) & 1) * 384 - (LV >> 4) * 128;
#pragma unroll
      for (int i = 0; i < 4; i++) ldsm4(vx[i], va + (i & 1) * 4096 + (i >> 1) * 256);
    };
    auto retire = [&](uint32_t x) {
      asm volatile("{\n.reg .pred p;\nsetp.eq.u32 p, %0, 0;\n@p exit;\n}" :: "r"(vx[0][0] | vx[1][0] | vx[2][0] | vx[3][0] | x) : "memory");
    };
    auto scores = [&](auto memkeys, auto first, float* sc) {
      constexpr bool MK = decltype(memkeys)::value, FIRST = decltype(first)::value;
      uint32_t kb[4][4], qb[2][4];
      const uint32_t m = LV >> 3;
      uint32_t kaddr = l16 + SM_BLK + 4096 + (s & 3) * SEGB + w * 2048 + (m & 1) * (MK ? 128 : 896) - (m >> 1) * 128;
      if (MK) { PIN(kaddr); }
      else {
#pragma unroll
        for (int k = 0; k < 4; k++) ldsm4t(kb[k], kaddr + k * 256);
      }
      if (FIRST) { load_vx(); retire(MK ? kaddr : kb[0][0] | kb[1][0] | kb[2][0] | kb[3][0] | l16); bar_sync(4, 256); PROF(4); }
      ldsm4t(qb[0], l16 + SM_QM);
      if (MK) ldsm4t(kb[0], kaddr);
      ldsm4t(qb[1], l16 + SM_QM + 512);
      if (MK) ldsm4t(kb[2], kaddr + 512);
      float c[4][4];
      mma16816z(c[0], kb[0], qb[0][0], qb[0][1]); mma16816z(c[1], kb[MK ? 0 : 1], qb[0][2], qb[0][3]);
      mma16816z(c[2], kb[2], qb[1][0], qb[1][1]); mma16816z(c[3], kb[MK ? 2 : 3], qb[1][2], qb[1][3]);
      if (FIRST && B5POS == 0) bar_arrive(5, N5);
#pragma unroll
      for (int i = 0; i < (MK ? 2 : 4); i++) sc[i] = ((c[0][i] + c[1][MK ? i + 2 : i]) + c[2][i]) + c[3][MK ? i + 2 : i];
    };
    auto send = [&](auto memkeys) {
      constexpr bool MK = decltype(memkeys)::value;
      constexpr int N = MK ? 1 : 2;
      const uint32_t sa = sb + LV * 4 + SM_E + (MK ? 1024 + RANK * 128 : RANK * 512 + w * 256);
      uint32_t ra[N][2], mb[N][2];
#pragma unroll
      for (int i = 0; i < N; i++)
#pragma unroll
        for (int j = 0; j < 2; j++) {
          ra[i][j] = mapa(sa + i * 128, j ? 2 : RANK ^ 1); mb[i][j] = mapa(sb + MB_S, j ? 2 : RANK ^ 1);
          PIN(ra[i][j]);
        }
      float sc[4];
      scores(memkeys, BoolC<true>(), sc);
      uint32_t e[N];
#pragma unroll
      for (int i = 0; i < N; i++) {
        e[i] = pack_bf16(ex2(sc[2 * i]), ex2(sc[2 * i + 1]));
        if (!(fmaxf(fabsf(sc[2 * i]), fabsf(sc[2 * i + 1])) <= E_LIM)) e[i] = 0x7fff7fffu;
        st_async1(ra[i][0], e[i], mb[i][0]);
        st_async1(ra[i][1], e[i], mb[i][1]);
      }
#pragma unroll
      for (int i = 0; i < N; i++) sts32(sa + i * 128, e[i]);
      __syncwarp();
      if (l16 == sb) mbar_arrive(sb + MB_S);
      PROF(5);
    };
    const int mode = bad ? 8 : mode0;
    if (mode < 2) {
      send(BoolC<false>());
    } else if (mode == 2) {
      send(BoolC<true>());
    } else if (mode == 8) {
      load_vx();
      retire(l16);
      const uint32_t fp = lds32(sb + SC_FPAR);
      bar_sync(6, 128);
      if (w == 0 && l16 == sb) { sts32(sb + SC_FPAR, fp ^ 1); mbar_expect(sb + MB_F, 3072); }
      if (RANK < 2 && w < 3) {
        float sc[4] = {0.f, 0.f, 0.f, 0.f};
        if (w < 2) scores(BoolC<false>(), BoolC<false>(), sc); else scores(BoolC<true>(), BoolC<false>(), sc);
#pragma unroll 1
        for (int r = 0; r < 3; r++)
          st_async4(mapa(l16 + SM_FB + RANK * 1536 + w * 512, r), __float_as_uint(sc[0]), __float_as_uint(sc[1]), __float_as_uint(sc[2]), __float_as_uint(sc[3]), mapa(sb + MB_F, r));
      }
      mbar_wait(sb + MB_F, fp);
      float a[12];
#pragma unroll
      for (int j = 0; j < 3; j++) {
        float b[4];
        lds128f(l16 + SM_FB + j * 512, a + 4 * j); lds128f(l16 + SM_FB + 1536 + j * 512, b);
#pragma unroll
        for (int i = 0; i < 4; i++) a[4 * j + i] += b[i];
      }
      float m0 = fmaxf(fmaxf(fmaxf(a[0], a[2]), fmaxf(a[4], a[6])), a[8]), m1 = fmaxf(fmaxf(fmaxf(a[1], a[3]), fmaxf(a[5], a[7])), a[9]);
#pragma unroll
      for (int o = 4; o < 32; o <<= 1) { m0 = fmaxf(m0, __shfl_xor_sync(0xffffffffu, m0, o)); m1 = fmaxf(m1, __shfl_xor_sync(0xffffffffu, m1, o)); }
#pragma unroll
      for (int i = 0; i < 5; i++) {
        const uint32_t ea = sb + SM_E + LV * 4 + (i < 4 ? i * 128 : 1024);
        sts32(ea, pack_bf16(ex2(a[2 * i] - m0), ex2(a[2 * i + 1] - m1)));
        sts32(ea + (i < 4 ? 512 : 128), 0x3f803f80u);
      }
      __syncwarp();
    } else {
      load_vx();
      if (mode == 3) bar_arrive(4, 256);
      retire(l16 + 1);
      if (w == 3) export_seg(s);
    }
    {
      uint32_t wa[4], wb[4], oc[4];
      constexpr int WS = 2048;
      const uint32_t w3a = l16 + SM_WO3 + w * 512;
      lds128(w3a + KP(0) * WS, wa); lds128(w3a + KP(1) * WS, wb); lds128(sb + SC_ONES, oc);
      if (B5POS == 1 && mode < 3) bar_arrive(5, N5);
      uint32_t e[10], p[5], vm[4], ob[4];
      float o0[4], o1[4], f[3][2][4], rs[4];
      reserve2(vm); reserve2(vm + 2); reserve2(e + 8);
      hints = hint_addr(s);
      PIN(hints);
      if (CLR & 2) asm volatile("{\n.reg .pred p;\nsetp.eq.u32 p, %0, 0;\n@p exit;\n}" :: "r"(wa[0] | wb[0] | oc[0] | hints) : "memory");
      mbar_wait(sb + MB_S, par);
      PROF(6);
      ldsm4t(e, l16 + SM_E); ldsm2t_in(e + 8, l16 + SM_E + 1024, always); ldsm4t(e + 4, l16 + SM_E + 512);
      lds128_in(vm, l16 + w * 512 + SM_VM, always);
      const float scl = __uint_as_float(lds32(sb + SC_UNSC + 8 - par * 8));
      hints = load_hints(hints);
      if (GF & 1) SCHED_FENCE(4);
#pragma unroll
      for (int i = 0; i < 4; i++) p[i] = mul_bf16(e[i], e[4 + i]);
      p[4] = mul_bf16(e[8], e[9]);
      mma16816z(o0, vx[0], p[0], p[1]); mma16816z(o1, vx[1], p[0], p[1]); mma16816z(rs, oc, p[0], p[1]);
      mma16816(o0, vx[2], p[2], p[3]); lds128_in(vx[2], w3a + KP(2) * WS, always);
      mma16816(o1, vx[3], p[2], p[3]); lds128_in(vx[3], w3a + KP(3) * WS, always);
      mma16816(rs, oc, p[2], p[3]);
      mma1688(o0, vm[0], vm[1], p[4]); mma1688(o1, vm[2], vm[3], p[4]); mma1688(rs, oc[0], oc[1], p[4]);
      stsm4(l16 + w * 512 + SM_OB, pack_bf16(o0[0], o0[1]), pack_bf16(o0[2], o0[3]), pack_bf16(o1[0], o1[1]), pack_bf16(o1[2], o1[3]));
      bar_sync(6, 128);
      PROF(7);
      ldsm4t_in(oc, l16 + SM_OB, always);
      bad = __any_sync(0xffffffffu, !(rs[0] + rs[1] > 0.f) && !bad);
      rs[0] *= scl; rs[1] *= scl;
      asm volatile("{\n.reg .pred p;\nsetp.ne.u32 p, %1, 0;\n@p rcp.approx.ftz.f32 %0, %0;\n}" : "+f"(rs[0]) : "r"(always));
      asm volatile("{\n.reg .pred p;\nsetp.ne.u32 p, %1, 1;\n@p rcp.approx.ftz.f32 %0, %0;\n}" : "+f"(rs[1]) : "r"(always));
      asm volatile("lop3.b32 %0, %1, %2, %3, 0xfe;" : "=r"(lp) : "r"((l16 & 128) * 2), "r"((l16 & 256) * 4), "r"(l16 & 112));
      if (bad) continue;
      ldsm4t(ob, l16 + SM_OB + 512);
      mma16816z(f[2][0], wa, oc[0], oc[1]); mma16816z(f[2][1], wb, oc[2], oc[3]);
      mma16816z(f[0][0], wo[0], oc[0], oc[1]); mma16816z(f[0][1], wo[4], oc[2], oc[3]);
      mma16816z(f[1][0], w1[0], oc[0], oc[1]); mma16816z(f[1][1], w1[4], oc[2], oc[3]);
      ldsm4t_in(oc, l16 + SM_OB + 1024, always);
      mma16816(f[2][0], vx[2], ob[0], ob[1]); lds128_in(vx[2], w3a + KP(4) * WS, always);
      mma16816(f[2][1], vx[3], ob[2], ob[3]); lds128_in(vx[3], w3a + KP(5) * WS, always);
      mma16816(f[0][0], wo[1], ob[0], ob[1]); mma16816(f[0][1], wo[5], ob[2], ob[3]);
      mma16816(f[1][0], w1[1], ob[0], ob[1]); mma16816(f[1][1], w1[5], ob[2], ob[3]);
      ldsm4t_in(ob, l16 + SM_OB + 1536, always);
      mma16816(f[0][0], wo[2], oc[0], oc[1]); mma16816(f[0][1], wo[6], oc[2], oc[3]);
      mma16816(f[2][0], vx[2], oc[0], oc[1]); lds128_in(vx[2], w3a + KP(6) * WS, always);
      mma16816(f[2][1], vx[3], oc[2], oc[3]); lds128_in(vx[3], w3a + KP(7) * WS, always);
      mma16816(f[1][0], w1[2], oc[0], oc[1]); mma16816(f[1][1], w1[6], oc[2], oc[3]);
      mma16816(f[0][0], wo[3], ob[0], ob[1]); mma16816(f[0][1], wo[7], ob[2], ob[3]);
      mma16816(f[1][0], w1[3], ob[0], ob[1]); mma16816(f[1][1], w1[7], ob[2], ob[3]);
      mma16816(f[2][0], vx[2], ob[0], ob[1]); mma16816(f[2][1], vx[3], ob[2], ob[3]);
      bar_arrive(7, NII < 18 ? 384 : 256);
      lds128_in(ob, sb + SC_DEAD, always);
      uint32_t h[3][2];
#pragma unroll
      for (int j = 0; j < 3; j++)
#pragma unroll
        for (int i = 0; i < 2; i++)
        {
          scale_sum(f[j][1][2 * i], f[j][0][2 * i], rs[0], always); scale_sum(f[j][1][2 * i + 1], f[j][0][2 * i + 1], rs[1], always);
          h[j][i] = pack_f16(f[j][1][2 * i], f[j][1][2 * i + 1]);
        }
      const uint32_t rofs = RANK * 32768;
      red_f16x8(slot(s, RANK >> 1, rofs), h[0][0], h[1][0], h[2][0], 0x3c00u);
      red_f16x8(slot(s, (RANK >> 1) ^ 1, rofs), h[0][1], h[1][1], h[2][1], 0x3c00u);
      if (NII == 18) bar_arrive(10, 256);
      SCHED_FENCE(5);
      l16 += ob[B7R];
    }
    {
    PROF(8);
    const uint32_t ma0 = l16 + SM_MEM + w * 128 + (LV >> 3) * 896 + nh * 512;
    const unsigned char* const sl[2] = {slot(s, nh, 0), slot(s, nh ^ 1, 0)};
    uint32_t late = latest_hint(hints, dl, s);
    if (late >= 64) {
      int n = 0;
#pragma unroll 1
      do {
        late = latest_hint(load_hints(hint_addr(s)), dl, s);
      } while (late >= 64 && ++n < SPIN_LIMIT);
    }
    dl += late * 32 + tm.poll;
    if (w == 3) publish(s);
    if (QM && blockIdx.x == 0 && l16 == sb && w == 0) stg_relaxed32(g_pace, dl);
    PROF(9);
    {
      auto wait_until = [&](uint32_t t) {
        asm volatile("{\n.reg .pred p;\n.reg .s32 c;\n.reg .u64 t;\nTL: mov.u64 t, %%globaltimer;\ncvt.u32.u64 c, t;\nsub.s32 c, c, %0;\nsetp.lt.s32 p, c, 0;\n@p bra.uni TL;\n}" :: "r"(t + (l16 & 15)) : "memory");
      };
      uint4 v[2][3];
      auto load = [&](int c) {
#pragma unroll
        for (int r = 0; r < 3; r++) v[c][r] = ldg_relaxed(sl[c ^ (r >> 1)] + r * 32768);
      };
      auto decode = [&](int c, int n) {
        uint32_t q[9];
        __half2 hm;
        const uint32_t ma = ma0 ^ (c * 512);
#pragma unroll
        for (int i = 0; i < 9; i++) {
          const uint32_t h = i % 3 == 0 ? v[c][i / 3].x : (i % 3 == 1 ? v[c][i / 3].y : v[c][i / 3].z);
          const float2 f = __half22float2(*(const __half2*)&h);
          q[i] = pack_bf16(f.x, f.y);
          hm = i ? __hmax2(hm, __habs2(*(const __half2*)&h)) : __habs2(*(const __half2*)&h);
        }
#pragma unroll
        for (int r = 0; r < 3; r++) stsm4(ma + r * 4096, q[3 * r], q[3 * r + 1], q[3 * r + 2], r < 2 ? v[c][r].w : *(const uint32_t*)&hm);
        const bool done = __all_sync(0xffffffffu, v[c][0].w == 0x5000u && v[c][1].w == 0x5000u && v[c][2].w == 0x5000u) || n > SPIN_LIMIT;
        asm volatile("{\n.reg .pred p;\nsetp.ne.u32 p, %0, 0;\n@p bar.arrive %1, 256;\n}" :: "r"((int)done), "r"(1 + c) : "memory");
        return done;
      };
      if (LEAD) { wait_until(dl - LEAD); load(1); }
      wait_until(dl);
      PROF(10);
      int n = 0;
#pragma unroll 1
      do {
        load(0);
        if (!LEAD) load(1);
        asm volatile("{\n.reg .pred p;\nsetp.eq.u32 p, %0, 0;\n@p bar.sync 13, 384;\n}" :: "r"(n) : "memory");
      } while (!decode(0, n++));
      PROF(11);
#pragma unroll 1
      while (!decode(1, n++)) load(1);
      bar_arrive(9, 256);
      PROF(12);
    }
    PROF(13);
    if (++s == NSEG - 1) break;
    }
  }
#undef fence_reg
  if (RANK < 2) bar_arrive(4, 256);
  if (w == 3) { export_seg(NSEG - 1); publish(NSEG - 1); }
  bar_sync(0, 384);
  cluster_sync();
}

__global__ void __cluster_dims__(3, 1, 1) __launch_bounds__(384, 1)
rec_kernel(const __grid_constant__ RMaps tm, const bf16* __restrict__ x, const bf16* __restrict__ mem0) {
  extern __shared__ __align__(1024) unsigned char smem_raw[];
  const uint32_t sb = smem_u32(smem_raw);
  const int tid = threadIdx.x, lane = tid & 31;
  const int wg = __shfl_sync(0xffffffffu, tid >> 7, 0);
  const int w = __shfl_sync(0xffffffffu, (tid >> 5) & 3, 0);
  uint32_t rank; asm("mov.u32 %0, %%cluster_ctarank;" : "=r"(rank));
  STAMP(0);
  asm volatile("griddepcontrol.launch_dependents;" ::: "memory");

  if (wg < 2) {
    asm volatile("setmaxnreg.inc.sync.aligned.u32 192;");
    if (tid == 0) {
      for (int i = 0; i < 3; i++) { mbar_init(sb + MB_W + 8 * i, 1); mbar_init(sb + MB_X + 8 * i, 1); }
      mbar_init(sb + MB_WO, 1); mbar_init(sb + MB_WO3, 1);
      mbar_init(sb + MB_S, rank < 2 ? 5 : 6);
      mbar_init(sb + MB_F, 1);
      mbar_init(sb + MB_VX, 1); mbar_init(sb + MB_VX + 8, 1);
      asm volatile("fence.mbarrier_init.release.cluster;" ::: "memory");
      fence_async();
      const int h = blockIdx.x / 3;
      const CUtensorMap* m0 = rank < 2 ? &tm.wk : &tm.wv;
      const CUtensorMap* m1 = rank < 2 ? &tm.wq : &tm.wv;
      const int c0 = h * DH + (rank == 1 ? 64 : 0), c1 = h * DH + (rank == 0 ? 0 : 64);
      for (int c = 0; c < 3; c++) {
        mbar_expect(sb + MB_W + 8 * c, 49152);
        tma_load(sb + SM_STAGE + c * 49152, m0, c0, c * 192, sb + MB_W + 8 * c);
        tma_load(sb + SM_STAGE + c * 49152 + 24576, m1, c1, c * 192, sb + MB_W + 8 * c);
      }
      for (int i = 0; i < 3; i++) mbar_expect(sb + MB_X + 8 * i, XT);
      tma_load3(sb + SM_X, &tm.x, 0, sb + MB_X);
      tma_prefetch(&tm.wo, rank * 192, h * DH);
      mbar_expect(sb + MB_WO, 16384);
      mbar_expect(sb + MB_WO3, 32768);
      tma_load(sb + SM_WOST, &tm.wo, rank * 192 + 64, h * DH, sb + MB_WO3);
      tma_load(sb + SM_WO3, &tm.wo, rank * 192 + 128, h * DH, sb + MB_WO3);
      mbar_expect(sb + MB_S, rank < 2 ? 640 + 2048 : 1280);
      mbar_expect(sb + MB_VX, 8192); mbar_expect(sb + MB_VX + 8, 8192);
    }
    __syncwarp();
    QSTAMP(0);
    bar_sync(0, 384);
    QSTAMP(1);
    proj_role(sb, tm, rank, wg, w, lane);
  } else {
    asm volatile("setmaxnreg.dec.sync.aligned.u32 120;");
    attn_role(sb, smem_raw, tm, rank, x, mem0, w, lane);
  }
}

constexpr int NAUX = 36;
constexpr int A_ST = 3, A_STAGE = 16384 + 24576, A_STG = A_ST * A_STAGE;
constexpr int A_KV = 2 * DM * 2, A_Q = 30 * A_KV, A_CHUNK = A_Q + 16 * DM * 2;
constexpr int A_XW = 4 * XT, A_XT = A_XW + 16384, A_NR = 4;
constexpr int A_IN = A_XT + 16384, A_OST = A_IN + 3 * SEGB, A_P = A_OST + 8192, A_G = A_P + 3072;
constexpr int A_BAR = 229376;
constexpr int A_TOTAL = A_BAR + 512;
struct AMaps { CUtensorMap x, wa, qst, o, o3, wob, woa; };

DI void wgmma_n192_ss_nt(float* d, uint64_t da, uint64_t db, int acc) {
  asm volatile("{\n.reg .pred p;\nsetp.ne.b32 p, %98, 0;\n"
               "wgmma.mma_async.sync.aligned.m64n192k16.f32.bf16.bf16 {"
               "%0,%1,%2,%3,%4,%5,%6,%7,%8,%9,%10,%11,%12,%13,%14,%15,%16,%17,%18,%19,%20,%21,%22,%23,%24,%25,%26,%27,%28,%29,%30,%31,"
               "%32,%33,%34,%35,%36,%37,%38,%39,%40,%41,%42,%43,%44,%45,%46,%47,%48,%49,%50,%51,%52,%53,%54,%55,%56,%57,%58,%59,%60,%61,%62,%63,"
               "%64,%65,%66,%67,%68,%69,%70,%71,%72,%73,%74,%75,%76,%77,%78,%79,%80,%81,%82,%83,%84,%85,%86,%87,%88,%89,%90,%91,%92,%93,%94,%95"
               "}, %96, %97, p, 1, 1, 0, 1;\n}\n"
               : ACC8(d, 0), ACC8(d, 8), ACC8(d, 16), ACC8(d, 24), ACC8(d, 32), ACC8(d, 40), ACC8(d, 48), ACC8(d, 56),
                 ACC8(d, 64), ACC8(d, 72), ACC8(d, 80), ACC8(d, 88) : "l"(da), "l"(db), "r"(acc));
}
DI void wgmma_n32_ss_tn(float* d, uint64_t da, uint64_t db, int on) {
  asm volatile("{\n.reg .pred p;\nsetp.ne.b32 p, %18, 0;\n"
               "@p wgmma.mma_async.sync.aligned.m64n32k16.f32.bf16.bf16 {%0,%1,%2,%3,%4,%5,%6,%7,%8,%9,%10,%11,%12,%13,%14,%15}, "
               "%16, %17, 1, 1, 1, 1, 0;\n}\n"
               : ACC8(d, 0), ACC8(d, 8) : "l"(da), "l"(db), "r"(on));
}
DI void wgmma_n40_ss(float* d, uint64_t da, uint64_t db, int acc) {
  asm volatile("{\n.reg .pred p;\nsetp.ne.b32 p, %22, 0;\n"
               "wgmma.mma_async.sync.aligned.m64n40k16.f32.bf16.bf16 {%0,%1,%2,%3,%4,%5,%6,%7,%8,%9,%10,%11,%12,%13,%14,%15,%16,%17,%18,%19}, "
               "%20, %21, p, 1, 1, 1, 1;\n}\n"
               : ACC8(d, 0), ACC8(d, 8), "+f"(d[16]), "+f"(d[17]), "+f"(d[18]), "+f"(d[19]) : "l"(da), "l"(db), "r"(acc));
}
DI uint2 ldg_relaxed64(const void* p) {
  uint2 v; asm volatile("ld.relaxed.gpu.global.v2.b32 {%0,%1}, [%2];" : "=r"(v.x), "=r"(v.y) : "l"(p) : "memory"); return v;
}
template <int ST> DI void ldg8x64(uint32_t* m, const void* p) {
  asm volatile("ld.relaxed.gpu.global.v2.b32 {%0,%1}, [%16];\nld.relaxed.gpu.global.v2.b32 {%2,%3}, [%16 + %17];\n"
               "ld.relaxed.gpu.global.v2.b32 {%4,%5}, [%16 + %18];\nld.relaxed.gpu.global.v2.b32 {%6,%7}, [%16 + %19];\n"
               "ld.relaxed.gpu.global.v2.b32 {%8,%9}, [%16 + %20];\nld.relaxed.gpu.global.v2.b32 {%10,%11}, [%16 + %21];\n"
               "ld.relaxed.gpu.global.v2.b32 {%12,%13}, [%16 + %22];\nld.relaxed.gpu.global.v2.b32 {%14,%15}, [%16 + %23];"
               : "=r"(m[0]), "=r"(m[1]), "=r"(m[2]), "=r"(m[3]), "=r"(m[4]), "=r"(m[5]), "=r"(m[6]), "=r"(m[7]),
                 "=r"(m[8]), "=r"(m[9]), "=r"(m[10]), "=r"(m[11]), "=r"(m[12]), "=r"(m[13]), "=r"(m[14]), "=r"(m[15])
               : "l"(p), "n"(ST), "n"(2 * ST), "n"(3 * ST), "n"(4 * ST), "n"(5 * ST), "n"(6 * ST), "n"(7 * ST) : "memory");
}
template <int ST> DI void ldg4x128(uint32_t* m, const void* p) {
  asm volatile("ld.relaxed.gpu.global.v4.b32 {%0,%1,%2,%3}, [%16];\nld.relaxed.gpu.global.v4.b32 {%4,%5,%6,%7}, [%16 + %17];\n"
               "ld.relaxed.gpu.global.v4.b32 {%8,%9,%10,%11}, [%16 + %18];\nld.relaxed.gpu.global.v4.b32 {%12,%13,%14,%15}, [%16 + %19];"
               : "=r"(m[0]), "=r"(m[1]), "=r"(m[2]), "=r"(m[3]), "=r"(m[4]), "=r"(m[5]), "=r"(m[6]), "=r"(m[7]),
                 "=r"(m[8]), "=r"(m[9]), "=r"(m[10]), "=r"(m[11]), "=r"(m[12]), "=r"(m[13]), "=r"(m[14]), "=r"(m[15])
               : "l"(p), "n"(ST), "n"(2 * ST), "n"(3 * ST) : "memory");
}
template <int N, int ST> DI bool stale(const uint32_t* m, uint32_t tag) {
  uint32_t x = m[0] ^ tag;
#pragma unroll
  for (int i = 1; i < N; i++) asm("lop3.b32 %0, %0, %1, %2, 0xf6;" : "+r"(x) : "r"(m[i * ST]), "r"(tag));
  return __any_sync(0xffffffffu, x & 1);
}
DI bool mbar_test(uint32_t b, uint32_t par) {
  uint32_t r; asm volatile("{\n.reg .pred p;\nmbarrier.test_wait.parity.shared::cta.b64 p, [%1], %2;\nselp.u32 %0, 1, 0, p;\n}" : "=r"(r) : "r"(b), "r"(par) : "memory");
  return r;
}
DI int wait_flags(const unsigned* p, bool active, unsigned base, int seg) {
  int n = 0, m;
  while (true) {
    m = __reduce_min_sync(0xffffffffu, active ? (int)(ldg_acquire32(p) - base) : NSEG);
    if (m > seg || ++n > SPIN_LIMIT) break;
    __nanosleep(40);
  }
  return max(m, seg + 1);
}
DI void wait_count(const unsigned* p, unsigned target) {
  int n = 0;
  unsigned v;
  while (true) {
    asm volatile("ld.acquire.gpu.global.b32 %0, [%1];" : "=r"(v) : "l"(p) : "memory");
    if ((int)(v - target) >= 0 || ++n > SPIN_LIMIT) break;
    __nanosleep(64);
  }
}
#define PING 1
#define FLAG 2
#define FPOS 1
#define QB 2
#define Q_LO 320
#define Q_HI 1056
DI void quiet_wait(uint32_t& dl) {
  if (XP & 32) return;
  for (int n = 0; n < 64; n++) {
    const int d = gtime() - dl;
    if (d <= Q_HI && d > -4096) { wait_until(dl + Q_LO); return; }
    const uint32_t v = ldg_relaxed32(g_pace);
    if (v == dl && (d > 3072 || d < 0)) return;
    dl = v;
  }
}
DI void aux_barrier(int i, unsigned epoch) {
  asm volatile("fence.proxy.async;" ::: "memory");
  asm volatile("red.release.gpu.global.add.u32 [%0], 1;" :: "l"(&g_abar[i * 32]) : "memory");
  wait_count(&g_abar[i * 32], NAUX * (epoch + 1));
  asm volatile("fence.proxy.async;" ::: "memory");
}

__global__ void __launch_bounds__(512, 1)
aux_kernel(const __grid_constant__ AMaps tm, const bf16* __restrict__ x, const bf16* __restrict__ gate_w, bf16* __restrict__ out) {
  extern __shared__ __align__(1024) unsigned char smem_raw[];
  const uint32_t sb = smem_u32(smem_raw);
  const uint32_t full1 = sb + A_BAR, empty1 = full1 + 8 * A_ST, full2 = empty1 + 8 * A_ST, fullw = full2 + 16, full3 = fullw + 8, empty3 = full3 + 8 * A_NR,
                 fullq = empty3 + 8 * A_NR, fullv = fullq + 8, emptyq = fullv + 8, emptyv = emptyq + 8;
  const int tid = threadIdx.x, lane = tid & 31, cta = blockIdx.x;
  const int wg = __shfl_sync(0xffffffffu, tid >> 7, 0), w = __shfl_sync(0xffffffffu, (tid >> 5) & 3, 0);
  ASTAMP(14);
  const unsigned epoch = *(volatile unsigned*)&g_epoch2;
  if (tid == 0) {
    for (int i = 0; i < A_ST; i++) { mbar_init(full1 + 8 * i, 1); mbar_init(empty1 + 8 * i, 8); }
    mbar_init(full2, 1); mbar_init(full2 + 8, 1); mbar_init(fullw, 1); mbar_init(fullq, 2); mbar_init(fullv, 2);
    mbar_init(emptyq, 4); mbar_init(emptyv, 4);
    for (int i = 0; i < A_NR; i++) { mbar_init(full3 + 8 * i, 1); mbar_init(empty3 + 8 * i, cta < NH ? 8 : 4); }
    fence_async();
  }
  __syncthreads();
  ASTAMP(0);
  const bool wide = cta < NH;
  auto p3_ks = [&](int g) { return wide ? cta >> 2 : 2 * (cta - NH) + g; };
  auto p3_mt = [&](int g) { return wide ? 2 * (cta & 3) + g : 8; };
  const unsigned fbase = epoch * NSEG;
  if (wg == 3) {
    asm volatile("setmaxnreg.dec.sync.aligned.u32 40;");
    if (w == 1 && cta < NH) {
#pragma unroll 1
      for (int seg = 0; seg < ((XP & 2048) ? 0 : NSEG); seg++) {
        bar_arrive(5, 160);
        if (seg > 0 && lane == 0) {
          asm volatile("cp.async.bulk.wait_group 0;" ::: "memory");
          stg_relaxed32(&g_oflag[cta * 32], fbase + seg);
        }
        __syncwarp();
        bar_sync(4, 160);
        if (lane == 0) {
          fence_async();
          tma_store(&tm.o, sb + A_OST, cta * DH, seg * 32);
          tma_store(&tm.o, sb + A_OST + 4096, cta * DH + 64, seg * 32);
          asm volatile("cp.async.bulk.commit_group;" ::: "memory");
          asm volatile("cp.async.bulk.wait_group.read 0;" ::: "memory");
        }
        __syncwarp();
      }
      if (lane == 0) {
        asm volatile("cp.async.bulk.wait_group 0;" ::: "memory");
        stg_relaxed32(&g_oflag[cta * 32], fbase + NSEG);
      }
    }
    if (w >= 2 && cta < NH) {
      const bool qk = w == 2;
      const uint32_t full = qk ? fullq : fullv, ktag = (epoch + 1) & 1;
      const uint32_t ma = sb + A_IN + 8192 + (qk ? lane * 16 : 2 * SEGB + (lane >> 4) * 1024 + (lane & 15) * 16);
      int avail = 0;
      uint32_t pace = 0;
      if (qk) bar_sync(10, 64);
#pragma unroll 1
      for (int seg = 0; seg < ((XP & 2048) ? 0 : NSEG); seg++) {
        if (seg >= avail) avail = wait_flags(&g_sflag[(cta * 3 + (qk ? lane & 1 : 2)) * 8], true, fbase, seg);
        if ((QM & 8) && seg < NSEG - 2 && avail <= seg + QB) quiet_wait(pace);
        const unsigned char* km = g_km + (size_t)(seg * NH + cta) * 4096 + (qk ? lane * 8 : 2048 + lane * 16);
        uint32_t m[16];
        auto fetch = [&]() { if (qk) ldg8x64<256>(m, km); else ldg4x128<512>(m, km); };
        const float g = qk ? __ldcg(&g_gate[seg * 32 + lane]) : 0.f;
        fetch();
        mbar_wait(qk ? emptyq : emptyv, (seg & 1) ^ 1);
        const unsigned char* src = g_seg + ((size_t)(seg & RING) * 96 + cta * 3) * 8192;
        if (lane == 0) mbar_expect(full, qk ? 16384 : 8192);
        __syncwarp();
        if (lane < (qk ? 2 : 1)) bulk_load(sb + A_IN + (qk ? lane : 2) * SEGB, src + (qk ? lane : 2) * 8192, 8192, full);
        int n = 0;
#pragma unroll 1
        while ((qk ? stale<8, 2>(m, ktag) : stale<4, 4>(m, ktag)) && ++n < SPIN_LIMIT) fetch();
#pragma unroll
        for (int i = 0; i < 4; i++) stsm4(ma + (qk ? (i >> 1) * SEGB + (i & 1) * 512 : i * 256), m[4 * i], m[4 * i + 1], m[4 * i + 2], m[4 * i + 3]);
        if (qk) sts32(sb + A_G + lane * 4, __float_as_uint(1.f - g));
        fence_async();
        __syncwarp();
        if (lane == 0) mbar_arrive(full);
      }
    }
    if (w != 0) return;
    const bool lead = lane == 0;
    uint32_t pace = 0;
    if (lead) {
      for (int it = 0; it < ((XP & 256) ? 0 : 36); it++) {
        const int st = it % A_ST, tile = (it / 9) * NAUX + cta, k = it % 9;
        if (it >= A_ST) mbar_wait(empty1 + 8 * st, (it / A_ST - 1) & 1);
        if (QM & 1) quiet_wait(pace);
        mbar_expect(full1 + 8 * st, A_STAGE);
        tma_load(sb + st * A_STAGE, &tm.x, k * 64, (tile / 9) * 128, full1 + 8 * st);
        for (int j = 0; j < 3; j++) tma_load(sb + st * A_STAGE + 16384 + j * 8192, &tm.wa, (tile % 9) * 192 + j * 64, k * 64, full1 + 8 * st);
      }
    }
    __syncwarp(); bar_sync(6, 288);
    bar_sync(8, 64);
    if (lead) { aux_barrier(0, epoch); if (cta == 0) *(volatile unsigned*)&g_epoch2 = epoch + 1; }
    __syncwarp(); bar_sync(6, 288);
    __syncwarp(); bar_sync(6, 288);
    if (lead) mbar_expect(fullw, (18 + (p3_ks(0) == 7) + (p3_ks(1) == 7)) * 8192);
    __syncwarp();
    if (lane < 20) {
      const int g = lane >= 10, k = lane - 10 * g, kb = p3_ks(g) * 9 + k;
      if (k < 9 || kb == 72) {
        const uint32_t dst = sb + (k < 9 ? (g * 9 + k) * 8192 : A_XW + g * 8192);
        if (kb < 64) tma_load(dst, &tm.wob, p3_mt(g) * 64, kb * 64, fullw);
        else tma_load(dst, &tm.woa, p3_mt(g) * 64, (kb - 64) * 64, fullw);
      }
    }
    __syncwarp();
    if (lead) aux_barrier(1, epoch);
    __syncwarp(); bar_sync(6, 288);
    {
      int avail = 0;
      const int h = (9 * p3_ks(0) >> 1) + lane;
#pragma unroll 1
      for (int seg = 0; seg < ((XP & 2048) ? 0 : NSEG); seg++) {
        if (seg >= avail) avail = wait_flags(&g_oflag[min(h, NH - 1) * 32], lane < (wide ? 5 : 9), fbase, seg);
        SSTAMP(seg, 4);
        for (int g = 0; g < (wide ? 1 : 2); g++) {
          const int sl = wide ? seg & 3 : (seg & 1) * 2 + g, ks = p3_ks(g);
          mbar_wait(empty3 + 8 * sl, ((seg >> (wide ? 2 : 1)) & 1) ^ 1);
          if ((QM & 4) && seg < NSEG - 3 && avail <= seg + QB) quiet_wait(pace);
          if (lead) {
            mbar_expect(full3 + 8 * sl, XT + (ks == 7 ? 4096 : 0));
            asm volatile("cp.async.bulk.tensor.3d.shared::cluster.global.mbarrier::complete_tx::bytes [%0], [%1, {%3, %4, %5}], [%2];"
                         :: "r"(sb + sl * XT), "l"(&tm.o3), "r"(full3 + 8 * sl), "r"(0), "r"(seg * 32), "r"(ks * 9) : "memory");
            if (ks == 7) tma_load(sb + A_XT + sl * 4096, &tm.o, 72 * 64, seg * 32, full3 + 8 * sl);
          }
          __syncwarp();
        }
      }
    }
    __syncwarp(); bar_sync(6, 288);
    asm volatile("griddepcontrol.wait;" ::: "memory");
  } else if (wg == 2) {
    asm volatile("setmaxnreg.dec.sync.aligned.u32 72;");
    if (cta < NH) {
#pragma unroll 4
      for (int u = 0; u < 16; u++) {
        const int tok = cta * 64 + w * 16 + u;
        float dot = 0.f;
#pragma unroll
        for (int j = 0; j < 9; j++) {
          const uint32_t a = ((const uint32_t*)x)[tok * (DM / 2) + j * 32 + lane], g = ((const uint32_t*)gate_w)[j * 32 + lane];
          dot += bf_lo(a) * bf_lo(g) + bf_hi(a) * bf_hi(g);
        }
        dot = warp_sum(dot);
        if (lane == 0) g_gate[tok] = 1.f / (1.f + __expf(-dot));
      }
    }
    bar_sync(3, 128);
    if (tid == 256) aux_barrier(2, epoch);
    __syncwarp();
    bar_sync(3, 128);
    if (w == 0) bar_arrive(8, 64);
    if (w == 1 && cta < NH) bar_arrive(10, 64);
    if (cta < NH) {
      const uint64_t qd = make_desc(sb + A_IN, 128, 1024, 0);
      CDECL;
#pragma unroll 1
      for (int seg = 0; seg < ((XP & 2048) ? 0 : NSEG); seg++) {
        CSTAMP(0);
        mbar_wait(fullq, seg & 1);
        CSTAMP(3);
        SSTAMP(seg, 0);
        float d[2][16];
        {
          float a[20];
          WG_FENCE();
#pragma unroll
          for (int k = 0; k < 8; k++) wgmma_n40_ss(a, qd + ((k >> 2) * SEGB + (k & 3) * 256 >> 4), qd + ((k >> 2) * SEGB + (k & 3) * 256 + 4096 >> 4), k > 0);
          const uint32_t ga = sb + A_G + (w & 1) * 64 + (lane >> 2) * 4;
          const float f0 = __uint_as_float(lds32(ga)), f1 = __uint_as_float(lds32(ga + 32));
          WG_COMMIT();
          WG_WAIT(0);
          CSTAMP(5);
          if (lane == 0 && f0 + f1 != 4.f) mbar_arrive(emptyq);
          SSTAMP(seg, 1);
          if (w < 2) {
            const int lim = w * 16 + (lane >> 2) - 2 * (lane & 3);
            float m0 = -3.0e38f, m1 = -3.0e38f;
#pragma unroll
            for (int i = 0; i < 20; i++) {
              a[i] *= SM_SCALE * LOG2E;
              if (i < 16 && (i >> 2) * 8 + (i & 1) - (i & 2) * 4 > lim) a[i] = -1.0e9f * LOG2E;
              if (i & 2) m1 = fmaxf(m1, a[i]); else m0 = fmaxf(m0, a[i]);
            }
#pragma unroll
            for (int o = 1; o < 4; o <<= 1) { m0 = fmaxf(m0, __shfl_xor_sync(0xffffffffu, m0, o)); m1 = fmaxf(m1, __shfl_xor_sync(0xffffffffu, m1, o)); }
            float s0 = 0.f, s1 = 0.f;
#pragma unroll
            for (int i = 0; i < 20; i++) { a[i] = ex2(a[i] - (i & 2 ? m1 : m0)); if (i & 2) s1 += a[i]; else s0 += a[i]; }
#pragma unroll
            for (int o = 1; o < 4; o <<= 1) { s0 += __shfl_xor_sync(0xffffffffu, s0, o); s1 += __shfl_xor_sync(0xffffffffu, s1, o); }
            s0 = f0 * rcp(s0); s1 = f1 * rcp(s1);
            uint32_t p[10];
#pragma unroll
            for (int i = 0; i < 10; i++) p[i] = pack_bf16(a[2 * i] * (i & 1 ? s1 : s0), a[2 * i + 1] * (i & 1 ? s1 : s0));
            const uint32_t pa = sb + A_P + (2 * w + ((lane >> 3) & 1)) * 768 + (lane >> 4) * 128 + (lane & 7) * 16;
            stsm4t(pa, p[0], p[1], p[2], p[3]); stsm4t(pa + 256, p[4], p[5], p[6], p[7]); stsm4t(pa + 512, p[8], p[9], 0, 0);
            CSTAMP(6);
            fence_async();
            CSTAMP(7);
          }
        }
        CSTAMP(8);
        mbar_wait(fullv, seg & 1);
        CSTAMP(9);
        bar_sync(5, 160);
        CSTAMP(10);
        SSTAMP(seg, 2);
        const uint64_t pd = make_desc(sb + A_P, 128, 768, 0), vd = make_desc(sb + A_IN + 2 * SEGB, 128, 512, 0), md = make_desc(sb + A_IN + 2 * SEGB + 8192, 0, 128, 0);
        WG_FENCE();
#pragma unroll
        for (int i = 0; i < 2; i++) {
          wgmma_n32_ss<0>(d[i], vd + i * 256, pd, 0);
          wgmma_n32_ss<0>(d[i], vd + i * 256 + 16, pd + 16, 1);
          wgmma_n32_ss<0>(d[i], md + i * 64, pd + 32, 1);
        }
        WG_COMMIT();
        WG_WAIT(0);
        CSTAMP(11);
        if (lane == 0) mbar_arrive(emptyv);
#pragma unroll
        for (int i = 0; i < 2; i++) {
          const uint32_t oa = sb + A_OST + i * 4096 + ((lane & 7) + ((lane >> 4) << 3)) * 128 + (((2 * w + ((lane >> 3) & 1)) ^ (lane & 7)) << 4);
          stsm4t(oa, pack_bf16(d[i][0], d[i][1]), pack_bf16(d[i][2], d[i][3]), pack_bf16(d[i][4], d[i][5]), pack_bf16(d[i][6], d[i][7]));
          stsm4t(oa + 2048, pack_bf16(d[i][8], d[i][9]), pack_bf16(d[i][10], d[i][11]), pack_bf16(d[i][12], d[i][13]), pack_bf16(d[i][14], d[i][15]));
        }
        CSTAMP(12);
        bar_sync(4, 160);
        SSTAMP(seg, 3);
      }
      CDUMP;
    }
  } else {
    asm volatile("setmaxnreg.inc.sync.aligned.u32 200;");
    {
    float acc[96];
#pragma unroll 1
    for (int t = 0; t < ((XP & 256) ? 0 : 4); t++) {
#pragma unroll 1
      for (int k = 0; k < 9; k++) {
        const int it = t * 9 + k, st = it % A_ST;
        mbar_wait(full1 + 8 * st, (it / A_ST) & 1);
        const uint64_t da = make_desc(sb + st * A_STAGE + wg * 8192, 16, 1024, 1);
        const uint64_t db = make_desc(sb + st * A_STAGE + 16384, 8192, 1024, 1);
        WG_FENCE();
#pragma unroll
        for (int j = 0; j < 4; j++) wgmma_n192_ss_nt(acc, da + j * 2, db + j * 128, (k | j) != 0);
        WG_COMMIT();
        WG_WAIT(1);
        if (k > 0 && lane == 0) mbar_arrive(empty1 + 8 * ((it - 1) % A_ST));
      }
      WG_WAIT(0);
      ASTAMP(16 + t);
      if (lane == 0) mbar_arrive(empty1 + 8 * ((t * 9 + 8) % A_ST));
      if ((tid & 127) == 0) asm volatile("cp.async.bulk.wait_group.read 0;" ::: "memory");
      bar_sync(1 + wg, 128);
      const uint32_t sa = sb + A_STG + wg * 24576 + (w * 16 + (lane & 15)) * 128;
#pragma unroll
      for (int n = 0; n < 12; n++)
        stsm4(sa + (n >> 2) * 8192 + ((((n & 3) * 2 + (lane >> 4)) ^ (lane & 7)) << 4), pack_bf16(acc[8 * n], acc[8 * n + 1]),
              pack_bf16(acc[8 * n + 2], acc[8 * n + 3]), pack_bf16(acc[8 * n + 4], acc[8 * n + 5]), pack_bf16(acc[8 * n + 6], acc[8 * n + 7]));
      fence_async();
      bar_sync(1 + wg, 128);
      if ((tid & 127) == 0) {
        const int tile = t * NAUX + cta;
        for (int j = 0; j < 3; j++) tma_store(&tm.qst, sb + A_STG + wg * 24576 + j * 8192, (tile % 9) * 192 + j * 64, (tile / 9) * 128 + wg * 64);
        asm volatile("cp.async.bulk.commit_group;" ::: "memory");
      }
    }
    if ((tid & 127) == 0) { asm volatile("cp.async.bulk.wait_group 0;" ::: "memory"); asm volatile("fence.proxy.async;" ::: "memory"); }
    }
    ASTAMP(1);
    bar_sync(6, 288);
    bar_sync(6, 288);
    {
    const uint32_t buf = sb + wg * A_CHUNK;
#pragma unroll 1
    for (int i = 0; i < 2; i++) {
      const int c = (2 * i + wg) * NAUX + cta;
      if (c >= S_LEN / 16 || (XP & 256)) break;
      const int r0 = max(c * 16 - 14, 0);
      if (w < 2) {
        uint32_t pace = 0;
        if (QM & 2) quiet_wait(pace);
        const int nkv = c * 16 + 16 - r0;
        if ((tid & 127) == 0) mbar_expect(full2 + 8 * wg, nkv * A_KV + 16 * DM * 2);
        if (lane < (w ? 16 : nkv))
          asm volatile("cp.async.bulk.shared::cluster.global.mbarrier::complete_tx::bytes [%0], [%1], %2, [%3];"
                       :: "r"(buf + (w ? A_Q + lane * DM * 2 : lane * A_KV)), "l"(g_qkvA + (size_t)((w ? c * 16 : r0) + lane) * 3 * DM + (w ? 0 : DM)),
                          "r"(w ? DM * 2 : A_KV), "r"(full2 + 8 * wg) : "memory");
        __syncwarp();
      }
      const int tok0 = c * 16 + (w >> 1) * 8 + (w & 1);
      const uint32_t qa = buf + A_Q + lane * 36 + (tok0 - c * 16) * DM * 2;
      uint32_t ra[11];
#pragma unroll
      for (int r = 0; r < 11; r++) ra[r] = buf + lane * 36 + (max(tok0 - 14 + 2 * r, 0) - r0) * A_KV;
      float l[4][8];
#pragma unroll
      for (int u = 0; u < 4; u++)
#pragma unroll
        for (int k = 0; k < 8; k++) l[u][k] = 0.f;
      mbar_wait(full2 + 8 * wg, i);
      if (i == 0) ASTAMP(2);
      const unsigned char* const sp = smem_raw - sb;
#pragma unroll 1
      for (int j = 0; j < 36; j += 4) {
        uint32_t qw[4], kw[11];
#pragma unroll
        for (int u = 0; u < 4; u++) qw[u] = *(const uint32_t*)(sp + qa + u * A_KV + j);
#pragma unroll
        for (int r = 0; r < 11; r++) kw[r] = *(const uint32_t*)(sp + ra[r] + j);
#pragma unroll
        for (int u = 0; u < 4; u++)
#pragma unroll
          for (int k = 0; k < 8; k++) l[u][k] = fmaf(bf_hi(qw[u]), bf_hi(kw[u + k]), fmaf(bf_lo(qw[u]), bf_lo(kw[u + k]), l[u][k]));
      }
#pragma unroll
      for (int u = 0; u < 4; u++) {
        float m = -3.0e38f, sum = 0.f;
#pragma unroll
        for (int k = 0; k < 8; k++) { l[u][k] = tok0 - 14 + 2 * (u + k) >= 0 ? l[u][k] * 0.23570226039551584f : -1.0e9f; m = fmaxf(m, l[u][k]); }
#pragma unroll
        for (int k = 0; k < 8; k++) { l[u][k] = ex2((l[u][k] - m) * LOG2E); sum += l[u][k]; }
        const float f = __ldcg(&g_gate[tok0 + 2 * u]) * rcp(sum);
#pragma unroll
        for (int k = 0; k < 8; k++) l[u][k] *= f;
      }
#pragma unroll 1
      for (int j = 0; j < 36; j += 4) {
        uint32_t vw[11];
#pragma unroll
        for (int r = 0; r < 11; r++) vw[r] = *(const uint32_t*)(sp + ra[r] + DM * 2 + j);
#pragma unroll
        for (int u = 0; u < 4; u++) {
          float o0 = 0.f, o1 = 0.f;
#pragma unroll
          for (int k = 0; k < 8; k++) { o0 = fmaf(l[u][k], bf_lo(vw[u + k]), o0); o1 = fmaf(l[u][k], bf_hi(vw[u + k]), o1); }
          sts32(qa + u * A_KV + j, pack_bf16(o0, o1));
        }
      }
      fence_async();
      __syncwarp();
      if (lane < 4) {
        asm volatile("cp.async.bulk.global.shared::cta.bulk_group [%0], [%1], %2;"
                     :: "l"(g_Ocat + (size_t)(tok0 + 2 * lane) * KCAT + 4096), "r"(buf + A_Q + (tok0 + 2 * lane - c * 16) * DM * 2), "r"(DM * 2) : "memory");
        asm volatile("cp.async.bulk.commit_group;" ::: "memory");
        asm volatile("cp.async.bulk.wait_group.read 0;" ::: "memory");
      }
      bar_sync(1 + wg, 128);
    }
    asm volatile("cp.async.bulk.wait_group 0;" ::: "memory");
    }
    ASTAMP(3);
    bar_sync(6, 288);
    uint32_t wa[36][4];
    mbar_wait(fullw, 0);
    const uint32_t la = sb + wg * 73728 + ((lane & 7) + ((lane >> 4) << 3)) * 128 + (((2 * w + ((lane >> 3) & 1)) ^ (lane & 7)) << 4);
#pragma unroll
    for (int k = 0; k < 36; k++) ldsm4t(wa[k], la + k * 2048);
    fence_async();
    bar_sync(6, 288);
    ASTAMP(4);
    const int ks = p3_ks(wg), mt = p3_mt(wg);
    uint32_t v[16];
    auto fetch = [&](int seg) { ldg8x64<1024>(v, g_part + (((seg & 7) * 9 + mt) * 4 + (ks & 3)) * 1024 + (tid & 127)); };
    auto finish = [&](int seg) {
      const uint32_t tagv = (~seg >> 3) & 1;
      int n = 0;
#pragma unroll 1
      while (stale<8, 2>(v, tagv) && ++n < SPIN_LIMIT) {
        if (seg < NSEG - 2) __nanosleep(100);
        fetch(seg);
      }
      float own[4] = {bf_lo(v[0]), bf_hi(v[0]), bf_lo(v[1]), bf_hi(v[1])};
#pragma unroll
      for (int j = 1; j < 8; j++) { own[0] += bf_lo(v[2 * j]); own[1] += bf_hi(v[2 * j]); own[2] += bf_lo(v[2 * j + 1]); own[3] += bf_hi(v[2 * j + 1]); }
      uint32_t p0 = pack_bf16(own[0], own[1]), p1 = pack_bf16(own[2], own[3]);
      asm volatile("movmatrix.sync.aligned.m8n8.trans.b16 %0, %0;" : "+r"(p0));
      asm volatile("movmatrix.sync.aligned.m8n8.trans.b16 %0, %0;" : "+r"(p1));
      uint32_t* o = (uint32_t*)(out + (size_t)(seg * 32 + (ks & 3) * 8 + (lane >> 2)) * DM + mt * 64 + w * 16) + (lane & 3);
      o[0] = p0; o[4] = p1;
      SSTAMP(seg, 7);
    };
    float acc[16];
#pragma unroll
    for (int i = 0; i < 16; i++) acc[i] = 0.f;
    int pend = -1;
    if (PING && wg) bar_arrive(1, 256);
    CDECL;
#pragma unroll 1
    for (int seg = 0; seg < ((XP & 2048) ? 0 : NSEG); seg++) {
      const int sl = wide ? seg & 3 : (seg & 1) * 2 + wg;
      CSTAMP(0);
      const bool fin = pend >= 0 && seg - pend >= FLAG;
      if (FPOS == 0 && fin) fetch(pend);
      mbar_wait(full3 + 8 * sl, (seg >> (wide ? 2 : 1)) & 1);
      if (FPOS == 1 && fin) fetch(pend);
      CSTAMP(1);
      if (wg) SSTAMP(seg, 5);
      if (PING) bar_sync(1 + wg, 256);
      const uint64_t db = make_desc(sb + sl * XT, 16, 1024, 1);
      WG_FENCE();
#pragma unroll
      for (int k = 0; k < ((XP & 1024) ? 1 : 36); k++) wgmma_n32_rs(acc, wa[k][0], wa[k][1], wa[k][2], wa[k][3], db + (k >> 2) * 256 + (k & 3) * 2, k);
      {
        const uint64_t da = make_desc(sb + A_XW + wg * 8192, 8192, 1024, 1), de = make_desc(sb + A_XT + sl * 4096, 16, 1024, 1);
#pragma unroll
        for (int j = 0; j < 4; j++) wgmma_n32_ss_tn(acc, da + j * 128, de + j * 2, ks == 7);
      }
      WG_COMMIT();
      if (PING) bar_arrive(2 - wg, 256);
      CSTAMP(2);
      if (FPOS == 2 && fin) fetch(pend);
      CSTAMP(3);
      WG_WAIT(0);
      CSTAMP(4);
      if (wg) SSTAMP(seg, 6);
      if (lane == 0) mbar_arrive(empty3 + 8 * sl);
      uint2* dst = g_part + (((seg & 7) * 9 + mt) * 32 + ks) * 128 + (tid & 127);
      uint32_t q[8];
#pragma unroll
      for (int j = 0; j < 8; j++) q[j] = j & 1 ? pack_bf16(acc[2 * j], acc[2 * j + 1]) : (pack_bf16(acc[2 * j], acc[2 * j + 1]) & ~1u) | ((~seg >> 3) & 1);
      asm volatile("st.relaxed.gpu.global.v2.b32 [%0], {%1,%2};\nst.relaxed.gpu.global.v2.b32 [%0 + 8192], {%3,%4};\n"
                   "st.relaxed.gpu.global.v2.b32 [%0 + 16384], {%5,%6};\nst.relaxed.gpu.global.v2.b32 [%0 + 24576], {%7,%8};"
                   :: "l"(dst), "r"(q[0]), "r"(q[1]), "r"(q[2]), "r"(q[3]), "r"(q[4]), "r"(q[5]), "r"(q[6]), "r"(q[7]) : "memory");
      CSTAMP(5);
      if (fin) { finish(pend); pend = -1; }
      CSTAMP(6);
      if ((seg & 1) == ks >> 2) pend = seg;
      if (wg && (seg & 7) == 6) ASTAMP(5 + (seg >> 3));
    }
    if (PING && !wg) bar_sync(1, 256);
    if (pend >= 0) { fetch(pend); finish(pend); }
    CDUMP;
    ASTAMP(13);
    bar_sync(6, 288);
  }
}

typedef CUresult (*EncodeFn)(CUtensorMap*, CUtensorMapDataType, cuuint32_t, void*, const cuuint64_t*, const cuuint64_t*,
                             const cuuint32_t*, const cuuint32_t*, CUtensorMapInterleave, CUtensorMapSwizzle,
                             CUtensorMapL2promotion, CUtensorMapFloatOOBfill);
#define PROMO 2
static void make_map(EncodeFn enc, CUtensorMap* m, const void* p, int rows, int cols, int box_rows) {
  cuuint64_t dims[2] = {(cuuint64_t)cols, (cuuint64_t)rows};
  cuuint64_t strides[1] = {(cuuint64_t)cols * 2};
  cuuint32_t box[2] = {64, (cuuint32_t)box_rows};
  cuuint32_t es[2] = {1, 1};
  enc(m, CU_TENSOR_MAP_DATA_TYPE_BFLOAT16, 2, (void*)p, dims, strides, box, es, CU_TENSOR_MAP_INTERLEAVE_NONE,
      CU_TENSOR_MAP_SWIZZLE_128B, (CUtensorMapL2promotion)PROMO, CU_TENSOR_MAP_FLOAT_OOB_FILL_NONE);
}

constexpr int g_poll = POLL_NS;
extern "C" void kernel_launch(void* const* d_in, const int* in_sizes, int n_in, void* d_out, int out_size) {
  const bf16* x = (const bf16*)d_in[0];
  const bf16* wqkvA = (const bf16*)d_in[1];
  const bf16* woA = (const bf16*)d_in[2];
  const bf16* mem0 = (const bf16*)d_in[4];
  const bf16* Wq = (const bf16*)d_in[5];
  const bf16* Wk = (const bf16*)d_in[6];
  const bf16* Wv = (const bf16*)d_in[7];
  const bf16* Wo = (const bf16*)d_in[8];
  const bf16* gate_w = (const bf16*)d_in[10];
  static EncodeFn enc = nullptr;
  static void *pO = nullptr, *pQ = nullptr, *pR = nullptr;
  if (!enc) {
    cudaDriverEntryPointQueryResult qr;
    cudaGetDriverEntryPoint("cuTensorMapEncodeTiled", (void**)&enc, cudaEnableDefault, &qr);
    cudaGetSymbolAddress(&pO, g_Ocat);
    cudaGetSymbolAddress(&pQ, g_qkvA);
    cudaGetSymbolAddress(&pR, g_red_raw);
    cudaFuncSetAttribute(rec_kernel, cudaFuncAttributeMaxDynamicSharedMemorySize, SM_TOTAL);
    cudaFuncSetAttribute(aux_kernel, cudaFuncAttributeMaxDynamicSharedMemorySize, A_TOTAL);
  }
  RMaps rm;
  rm.poll = g_poll;
  rm.w[0] = (const unsigned char*)Wk; rm.w[1] = (const unsigned char*)Wq; rm.w[2] = (const unsigned char*)Wv; rm.w[3] = (const unsigned char*)Wo;
  rm.red = (unsigned char*)(((uintptr_t)pR + 262143) & ~(uintptr_t)262143);
  {
    cuuint64_t dims[3] = {64, S_LEN, 9}, strides[2] = {DM * 2, 128};
    cuuint32_t box[3] = {64, 32, 9}, es[3] = {1, 1, 1};
    enc(&rm.x, CU_TENSOR_MAP_DATA_TYPE_BFLOAT16, 3, (void*)x, dims, strides, box, es, CU_TENSOR_MAP_INTERLEAVE_NONE,
        CU_TENSOR_MAP_SWIZZLE_128B, CU_TENSOR_MAP_L2_PROMOTION_L2_128B, CU_TENSOR_MAP_FLOAT_OOB_FILL_NONE);
  }
  make_map(enc, &rm.wq, Wq, DM, 4096, 192);
  make_map(enc, &rm.wk, Wk, DM, 4096, 192);
  make_map(enc, &rm.wv, Wv, DM, 4096, 192);
  make_map(enc, &rm.wo, Wo, 4096, DM, 128);
  AMaps am;
  make_map(enc, &am.x, x, S_LEN, DM, 128);
  make_map(enc, &am.wa, wqkvA, DM, 3 * DM, 64);
  make_map(enc, &am.qst, pQ, S_LEN, 3 * DM, 64);
  {
    cuuint64_t dims[3] = {64, S_LEN, KCAT / 64}, strides[2] = {KCAT * 2, 128};
    cuuint32_t box[3] = {64, 32, 9}, es[3] = {1, 1, 1};
    make_map(enc, &am.o, pO, S_LEN, KCAT, 32);
    enc(&am.o3, CU_TENSOR_MAP_DATA_TYPE_BFLOAT16, 3, pO, dims, strides, box, es, CU_TENSOR_MAP_INTERLEAVE_NONE,
        CU_TENSOR_MAP_SWIZZLE_128B, CU_TENSOR_MAP_L2_PROMOTION_L2_128B, CU_TENSOR_MAP_FLOAT_OOB_FILL_NONE);
  }
  make_map(enc, &am.wob, Wo, 4096, DM, 64);
  make_map(enc, &am.woa, woA, DM, DM, 64);

  rec_kernel<<<96, 384, SM_TOTAL, cudaStreamPerThread>>>(rm, x, mem0);
  cudaLaunchConfig_t cfg = {};
  cfg.gridDim = dim3(NAUX); cfg.blockDim = dim3(512); cfg.dynamicSmemBytes = A_TOTAL; cfg.stream = cudaStreamPerThread;
  cudaLaunchAttribute at[1];
  at[0].id = cudaLaunchAttributeProgrammaticStreamSerialization; at[0].val.programmaticStreamSerializationAllowed = 1;
  cfg.attrs = at; cfg.numAttrs = 1;
  if (XP & 16) cfg.numAttrs = 0;
  if (!(XP & 64)) cudaLaunchKernelEx(&cfg, aux_kernel, am, x, gate_w, (bf16*)d_out);
}
```

```cpp
#include <cuda_runtime.h>
#include <cuda_bf16.h>
#include <cuda_fp16.h>
#include <cuda.h>
#include <stdint.h>

typedef __nv_bfloat16 bf16;

constexpr int S_LEN = 2048, DM = 576, NH = 32, DH = 128, NSEG = 64, KCAT = 4096 + 576;
#define RED_LINE(i) (((i) >> 2) * 4096 + ((i) & 1) * 256 + ((i) & 2) * 512)
#define RED_SLOT(s) (((s) & 1) * 128 + ((s) & 2) * 256)

#define POLL_NS 896
#define NII 18
#define W3PRE 4
#define W3MID 4
#define GF 0
#define B5POS 0
#define NUP 4
#define UPF 1
#define B3Q 9
#define B3F 0
#define GATE 7
#define NTL 2
#define B7R 1
#define EXPOS 0
#define VW2 1
#define CLR 1
#define RFW 0
#define NIC 0
#define LEAD 0
#define FIN16 1
#define VXG 0
#define RING 63
#define EXB 0
#define EXD 0
#define EXB2 8192
#define HDLY 0
#define F10 1
#define NPROBE 2
#define NPROBE2 5
#define WPOS 2
#define WARM 0
#define QM 0
#define N5 224
#define KP(i) (((i) >> 1) + 4 * ((i) & 1))
#define SPIN_LIMIT (1 << 14)
#define XP 0

__device__ __align__(1024) bf16 g_Ocat[S_LEN * KCAT];
__device__ __align__(1024) bf16 g_qkvA[S_LEN * 3 * DM];
__device__ __align__(1024) unsigned char g_red_raw[2 * 262144];
constexpr int HINT_OFF = 2048;
__device__ __align__(16) float g_gate[S_LEN];
__device__ __align__(128) uint4 g_stats[96 * 2];
__device__ unsigned g_epoch;
__device__ unsigned g_epoch2;
__device__ unsigned g_oflag[NH * 32];
__device__ unsigned g_abar[3 * 32];
__device__ unsigned g_pace[32];
__device__ unsigned g_sflag[96 * 8];
__device__ __align__(1024) unsigned char g_seg[NSEG * 96 * 8192];
__device__ __align__(1024) unsigned char g_km[NSEG * NH * 4096];
__device__ __align__(1024) uint2 g_part[8 * 9 * 4 * 8 * 128];
__device__ int g_err;
#define SSTAMP(seg, idx)
#define QSTAMP(idx)
#define PROF(idx)
#define PROFP(idx)
#define STAMP(idx)
#define ASTAMP(idx)
#define WSTAMP(idx)

#define CSTAMP(idx)
#define CDECL
#define CDUMP
#define DI __device__ __forceinline__
DI uint32_t smem_u32(const void* p) { return (uint32_t)__cvta_generic_to_shared(p); }
DI uint32_t clock32() { uint32_t c; asm volatile("mov.u32 %0, %%clock;" : "=r"(c) :: "memory"); return c; }
DI uint32_t gtime() { uint32_t c; asm volatile("mov.u32 %0, %%globaltimer_lo;" : "=r"(c) :: "memory"); return c; }
DI uint32_t ldg_relaxed32(const void* p) { uint32_t v; asm volatile("ld.relaxed.gpu.global.b32 %0, [%1];" : "=r"(v) : "l"(p) : "memory"); return v; }
DI uint32_t ldg_acquire32(const void* p) { uint32_t v; asm volatile("ld.acquire.gpu.global.b32 %0, [%1];" : "=r"(v) : "l"(p) : "memory"); return v; }
DI void stg_relaxed32(void* p, uint32_t v) { asm volatile("st.relaxed.gpu.global.b32 [%0], %1;" :: "l"(p), "r"(v) : "memory"); }
DI int head_id() { int c; asm volatile("mov.u32 %0, %%clusterid.x;" : "=r"(c)); return c; }
DI uint32_t mapa(uint32_t a, uint32_t r) { uint32_t o; asm("mapa.shared::cluster.u32 %0, %1, %2;" : "=r"(o) : "r"(a), "r"(r)); return o; }
DI void cluster_arrive() { asm volatile("barrier.cluster.arrive.relaxed.aligned;" ::: "memory"); }
DI void cluster_wait() { asm volatile("barrier.cluster.wait.aligned;" ::: "memory"); }
DI void cluster_sync() { asm volatile("barrier.cluster.arrive.release.aligned;\nbarrier.cluster.wait.acquire.aligned;" ::: "memory"); }
DI void mbar_init(uint32_t b, uint32_t c) { asm volatile("mbarrier.init.shared::cta.b64 [%0], %1;" :: "r"(b), "r"(c) : "memory"); }
DI void mbar_expect(uint32_t b, uint32_t tx) { asm volatile("mbarrier.arrive.expect_tx.shared::cta.b64 _, [%0], %1;" :: "r"(b), "r"(tx) : "memory"); }
DI void mbar_arrive(uint32_t b) { asm volatile("mbarrier.arrive.shared::cta.b64 _, [%0];" :: "r"(b) : "memory"); }
DI void mbar_wait(uint32_t b, uint32_t par) {
  asm volatile("{\n.reg .pred p;\n.reg .u32 n, q;\nmov.u32 n, 0;\n"
               "WL: add.u32 n, n, 1;\nshr.u32 q, n, 12;\nxor.b32 q, q, %1;\n"
               "mbarrier.try_wait.parity.shared::cta.b64 p, [%0], q;\n@!p bra.uni WL;\n}"
               :: "r"(b), "r"(par) : "memory");
}
DI void wait_until(uint32_t t) {
  const uint32_t now = gtime();
  t = min(t, now + 8192);
  asm volatile("{\n.reg .pred p;\n.reg .u32 c;\nTL: mov.u32 c, %%globaltimer_lo;\nsetp.lt.u32 p, c, %0;\n@p bra.uni TL;\n}" :: "r"(t) : "memory");
}
#define PIN(v) v = __shfl_xor_sync(0xffffffffu, v, 0)
#define SCHED_FENCE(k) asm volatile("{\n.reg .pred p;\nsetp.eq.u32 p, %0, %1;\n@p exit;\n}" :: "r"(fence_reg), "r"(k) : "memory")
#define MEM_ORDER(k) asm volatile("{\n.reg .pred p;\nsetp.eq.u32 p, %0, %1;\n@p st.shared.u32 [%0], %0;\n}" :: "r"(fence_reg), "r"(k + 64) : "memory")
DI void bar_sync(int id, int n) { asm volatile("bar.sync %0, %1;" :: "r"(id), "r"(n) : "memory"); }
DI void bar_arrive(int id, int n) { asm volatile("bar.arrive %0, %1;" :: "r"(id), "r"(n) : "memory"); }
DI void fence_async() { asm volatile("fence.proxy.async.shared::cta;" ::: "memory"); }
DI void st_async4(uint32_t a, uint32_t x, uint32_t y, uint32_t z, uint32_t w, uint32_t mb) {
  asm volatile("st.async.weak.shared::cluster.mbarrier::complete_tx::bytes.v4.b32 [%0], {%1,%2,%3,%4}, [%5];"
               :: "r"(a), "r"(x), "r"(y), "r"(z), "r"(w), "r"(mb) : "memory");
}
DI void st_async2(uint32_t a, uint32_t x, uint32_t y, uint32_t mb) {
  asm volatile("st.async.weak.shared::cluster.mbarrier::complete_tx::bytes.v2.b32 [%0], {%1,%2}, [%3];"
               :: "r"(a), "r"(x), "r"(y), "r"(mb) : "memory");
}
DI void sts32(uint32_t a, uint32_t x) { asm volatile("st.shared.b32 [%0], %1;" :: "r"(a), "r"(x) : "memory"); }
DI void sts64(uint32_t a, uint32_t x, uint32_t y) { asm volatile("st.shared.v2.b32 [%0], {%1,%2};" :: "r"(a), "r"(x), "r"(y) : "memory"); }
DI void sts128(uint32_t a, uint32_t x, uint32_t y, uint32_t z, uint32_t w) {
  asm volatile("st.shared.v4.b32 [%0], {%1,%2,%3,%4};" :: "r"(a), "r"(x), "r"(y), "r"(z), "r"(w) : "memory");
}
DI uint32_t lds32(uint32_t a) { uint32_t x; asm volatile("ld.shared.b32 %0, [%1];" : "=r"(x) : "r"(a) : "memory"); return x; }
DI void lds64(uint32_t a, uint32_t& x, uint32_t& y) { asm volatile("ld.shared.v2.b32 {%0,%1}, [%2];" : "=r"(x), "=r"(y) : "r"(a) : "memory"); }
DI void lds128(uint32_t a, uint32_t* r) {
  asm volatile("ld.shared.v4.b32 {%0,%1,%2,%3}, [%4];" : "=r"(r[0]), "=r"(r[1]), "=r"(r[2]), "=r"(r[3]) : "r"(a) : "memory");
}
DI void lds128f(uint32_t a, float* r) {
  asm volatile("ld.shared.v4.f32 {%0,%1,%2,%3}, [%4];" : "=f"(r[0]), "=f"(r[1]), "=f"(r[2]), "=f"(r[3]) : "r"(a) : "memory");
}
DI void lds64f(uint32_t a, float* r) { asm volatile("ld.shared.v2.f32 {%0,%1}, [%2];" : "=f"(r[0]), "=f"(r[1]) : "r"(a) : "memory"); }
DI void ldsm4t(uint32_t* r, uint32_t a) {
  asm volatile("ldmatrix.sync.aligned.m8n8.x4.trans.shared.b16 {%0,%1,%2,%3}, [%4];"
               : "=r"(r[0]), "=r"(r[1]), "=r"(r[2]), "=r"(r[3]) : "r"(a) : "memory");
}
DI void ldsm4t_in(uint32_t* r, uint32_t a, uint32_t t) {
  asm volatile("{\n.reg .pred p;\nsetp.ne.u32 p, %5, 0;\n@p ldmatrix.sync.aligned.m8n8.x4.trans.shared.b16 {%0,%1,%2,%3}, [%4];\n}"
               : "+r"(r[0]), "+r"(r[1]), "+r"(r[2]), "+r"(r[3]) : "r"(a), "r"(t) : "memory");
}
DI void lds128_in(uint32_t* r, uint32_t a, uint32_t t) {
  asm volatile("{\n.reg .pred p;\nsetp.ne.u32 p, %5, 0;\n@p ld.shared.v4.b32 {%0,%1,%2,%3}, [%4];\n}"
               : "+r"(r[0]), "+r"(r[1]), "+r"(r[2]), "+r"(r[3]) : "r"(a), "r"(t) : "memory");
}
DI void ldsm2t_in(uint32_t* r, uint32_t a, uint32_t t) {
  asm volatile("{\n.reg .pred p;\nsetp.ne.u32 p, %3, 0;\n@p ldmatrix.sync.aligned.m8n8.x2.trans.shared.b16 {%0,%1}, [%2];\n}" : "+r"(r[0]), "+r"(r[1]) : "r"(a), "r"(t) : "memory");
}
DI void reserve2(uint32_t* r) { asm volatile("{\n.reg .u64 t;\nmov.u64 t, %%clock64;\nmov.b64 {%0, %1}, t;\n}" : "=r"(r[0]), "=r"(r[1])); }
DI void scale_sum(float& x, float& y, float s, uint32_t t) {
  asm volatile("{\n.reg .pred p;\nsetp.ne.u32 p, %2, 0;\n@p mul.f32 %0, %0, %1;\n}" : "+f"(y) : "f"(s), "r"(t));
  asm volatile("{\n.reg .pred p;\nsetp.ne.u32 p, %3, 1;\n@p fma.rn.f32 %0, %0, %1, %2;\n}" : "+f"(x) : "f"(s), "f"(y), "r"(t));
}
DI void ldsm4(uint32_t* r, uint32_t a) {
  asm volatile("ldmatrix.sync.aligned.m8n8.x4.shared.b16 {%0,%1,%2,%3}, [%4];"
               : "=r"(r[0]), "=r"(r[1]), "=r"(r[2]), "=r"(r[3]) : "r"(a) : "memory");
}
DI void st_async1(uint32_t a, uint32_t x, uint32_t mb) {
  asm volatile("st.async.weak.shared::cluster.mbarrier::complete_tx::bytes.b32 [%0], %1, [%2];" :: "r"(a), "r"(x), "r"(mb) : "memory");
}
DI void stsm4(uint32_t a, uint32_t x, uint32_t y, uint32_t z, uint32_t w) {
  asm volatile("stmatrix.sync.aligned.m8n8.x4.shared.b16 [%0], {%1,%2,%3,%4};" :: "r"(a), "r"(x), "r"(y), "r"(z), "r"(w) : "memory");
}
DI void stsm4t(uint32_t a, uint32_t x, uint32_t y, uint32_t z, uint32_t w) {
  asm volatile("stmatrix.sync.aligned.m8n8.x4.trans.shared.b16 [%0], {%1,%2,%3,%4};" :: "r"(a), "r"(x), "r"(y), "r"(z), "r"(w) : "memory");
}
DI uint32_t pack_bf16(float lo, float hi) { uint32_t r; asm("cvt.rn.bf16x2.f32 %0, %1, %2;" : "=r"(r) : "f"(hi), "f"(lo)); return r; }
DI uint32_t pack_f16(float lo, float hi) { uint32_t r; asm("cvt.rn.f16x2.f32 %0, %1, %2;" : "=r"(r) : "f"(hi), "f"(lo)); return r; }
DI float ex2(float x) { float y; asm("ex2.approx.ftz.f32 %0, %1;" : "=f"(y) : "f"(x)); return y; }
DI float rcp(float x) { float y; asm("rcp.approx.ftz.f32 %0, %1;" : "=f"(y) : "f"(x)); return y; }
DI float bf_lo(uint32_t x) { return __uint_as_float(x << 16); }
DI float bf_hi(uint32_t x) { return __uint_as_float(x & 0xffff0000u); }
DI void mma16816(float* d, const uint32_t* a, uint32_t b0, uint32_t b1) {
  asm volatile("mma.sync.aligned.m16n8k16.row.col.f32.bf16.bf16.f32 {%0,%1,%2,%3}, {%4,%5,%6,%7}, {%8,%9}, {%0,%1,%2,%3};"
               : "+f"(d[0]), "+f"(d[1]), "+f"(d[2]), "+f"(d[3]) : "r"(a[0]), "r"(a[1]), "r"(a[2]), "r"(a[3]), "r"(b0), "r"(b1));
}
DI void mma16816z(float* d, const uint32_t* a, uint32_t b0, uint32_t b1) {
  asm volatile("mma.sync.aligned.m16n8k16.row.col.f32.bf16.bf16.f32 {%0,%1,%2,%3}, {%4,%5,%6,%7}, {%8,%9}, {%10,%10,%10,%10};"
               : "=f"(d[0]), "=f"(d[1]), "=f"(d[2]), "=f"(d[3]) : "r"(a[0]), "r"(a[1]), "r"(a[2]), "r"(a[3]), "r"(b0), "r"(b1), "f"(0.f));
}
DI void mma1688z(float* d, uint32_t a0, uint32_t a1, uint32_t b0) {
  asm volatile("mma.sync.aligned.m16n8k8.row.col.f32.bf16.bf16.f32 {%0,%1,%2,%3}, {%4,%5}, {%6}, {%7,%7,%7,%7};"
               : "=f"(d[0]), "=f"(d[1]), "=f"(d[2]), "=f"(d[3]) : "r"(a0), "r"(a1), "r"(b0), "f"(0.f));
}
DI void mma1688(float* d, uint32_t a0, uint32_t a1, uint32_t b0) {
  asm volatile("mma.sync.aligned.m16n8k8.row.col.f32.bf16.bf16.f32 {%0,%1,%2,%3}, {%4,%5}, {%6}, {%0,%1,%2,%3};"
               : "+f"(d[0]), "+f"(d[1]), "+f"(d[2]), "+f"(d[3]) : "r"(a0), "r"(a1), "r"(b0));
}
DI void ldsm2t(uint32_t* r, uint32_t a) {
  asm volatile("ldmatrix.sync.aligned.m8n8.x2.trans.shared.b16 {%0,%1}, [%2];" : "=r"(r[0]), "=r"(r[1]) : "r"(a) : "memory");
}
DI uint32_t add_bf16(uint32_t a, uint32_t b) { uint32_t r; asm("add.rn.bf16x2 %0, %1, %2;" : "=r"(r) : "r"(a), "r"(b)); return r; }
DI uint32_t mul_bf16(uint32_t a, uint32_t b) { uint32_t r; asm("mul.rn.bf16x2 %0, %1, %2;" : "=r"(r) : "r"(a), "r"(b)); return r; }
DI uint64_t make_desc(uint32_t addr, uint32_t lbo, uint32_t sbo, uint32_t swz) {
  return (uint64_t)((addr & 0x3FFFF) >> 4) | ((uint64_t)(lbo >> 4) << 16) | ((uint64_t)(sbo >> 4) << 32) | ((uint64_t)swz << 62);
}
#define WG_FENCE() asm volatile("wgmma.fence.sync.aligned;" ::: "memory")
#define WG_COMMIT() asm volatile("wgmma.commit_group.sync.aligned;" ::: "memory")
#define WG_WAIT(n) asm volatile("wgmma.wait_group.sync.aligned %0;" :: "n"(n) : "memory")
#define ACC8(d, o) "+f"(d[o]), "+f"(d[o + 1]), "+f"(d[o + 2]), "+f"(d[o + 3]), "+f"(d[o + 4]), "+f"(d[o + 5]), "+f"(d[o + 6]), "+f"(d[o + 7])
DI void wgmma_n32_rs(float* d, uint32_t a0, uint32_t a1, uint32_t a2, uint32_t a3, uint64_t db, int acc) {
  asm volatile("{\n.reg .pred p;\nsetp.ne.b32 p, %21, 0;\n"
               "wgmma.mma_async.sync.aligned.m64n32k16.f32.bf16.bf16 {%0,%1,%2,%3,%4,%5,%6,%7,%8,%9,%10,%11,%12,%13,%14,%15}, "
               "{%16,%17,%18,%19}, %20, p, 1, 1, 0;\n}\n"
               : ACC8(d, 0), ACC8(d, 8) : "r"(a0), "r"(a1), "r"(a2), "r"(a3), "l"(db), "r"(acc));
}
template <int TA>
DI void wgmma_n32_ss(float* d, uint64_t da, uint64_t db, int acc) {
  asm volatile("{\n.reg .pred p;\nsetp.ne.b32 p, %18, 0;\n"
               "wgmma.mma_async.sync.aligned.m64n32k16.f32.bf16.bf16 {%0,%1,%2,%3,%4,%5,%6,%7,%8,%9,%10,%11,%12,%13,%14,%15}, "
               "%16, %17, p, 1, 1, %19, 1;\n}\n"
               : ACC8(d, 0), ACC8(d, 8) : "l"(da), "l"(db), "r"(acc), "n"(TA));
}
DI void tma_load(uint32_t dst, const CUtensorMap* m, int c0, int c1, uint32_t mb) {
  asm volatile("cp.async.bulk.tensor.2d.shared::cluster.global.mbarrier::complete_tx::bytes [%0], [%1, {%3, %4}], [%2];"
               :: "r"(dst), "l"(m), "r"(mb), "r"(c0), "r"(c1) : "memory");
}
DI void tma_load3(uint32_t dst, const CUtensorMap* m, int row, uint32_t mb) {
  asm volatile("cp.async.bulk.tensor.3d.shared::cluster.global.mbarrier::complete_tx::bytes [%0], [%1, {%3, %4, %3}], [%2];"
               :: "r"(dst), "l"(m), "r"(mb), "r"(0), "r"(row) : "memory");
}
DI bool elect_one() {
  uint32_t p;
  asm volatile("{\n.reg .pred p;\nelect.sync _|p, 0xffffffff;\nselp.u32 %0, 1, 0, p;\n}" : "=r"(p));
  return p;
}
DI void bulk_s2s(uint32_t dst, uint32_t src, uint32_t bytes, uint32_t mb) {
  asm volatile("cp.async.bulk.shared::cluster.shared::cta.mbarrier::complete_tx::bytes [%0], [%1], %2, [%3];"
               :: "r"(dst), "r"(src), "r"(bytes), "r"(mb) : "memory");
}
DI void bulk_load(uint32_t dst, const void* src, uint32_t bytes, uint32_t mb) {
  asm volatile("cp.async.bulk.shared::cluster.global.mbarrier::complete_tx::bytes [%0], [%1], %2, [%3];" :: "r"(dst), "l"(src), "r"(bytes), "r"(mb) : "memory");
}
DI void tma_prefetch(const CUtensorMap* m, int c0, int c1) {
  asm volatile("cp.async.bulk.prefetch.tensor.2d.L2.global.tile [%0, {%1, %2}];" :: "l"(m), "r"(c0), "r"(c1) : "memory");
}
DI void tma_store(const CUtensorMap* m, uint32_t src, int c0, int c1) {
  asm volatile("cp.async.bulk.tensor.2d.global.shared::cta.bulk_group [%0, {%2, %3}], [%1];" :: "l"(m), "r"(src), "r"(c0), "r"(c1) : "memory");
}
DI uint4 ldg_relaxed(const void* p) {
  uint4 v;
  asm volatile("ld.relaxed.gpu.global.v4.b32 {%0,%1,%2,%3}, [%4];" : "=r"(v.x), "=r"(v.y), "=r"(v.z), "=r"(v.w) : "l"(p) : "memory");
  return v;
}
DI void stg_relaxed(void* p, uint32_t x, uint32_t y, uint32_t z, uint32_t w) {
  asm volatile("st.relaxed.gpu.global.v4.b32 [%0], {%1,%2,%3,%4};" :: "l"(p), "r"(x), "r"(y), "r"(z), "r"(w) : "memory");
}
DI void red_f16x8(void* p, uint32_t x, uint32_t y, uint32_t z, uint32_t w) {
  asm volatile("red.relaxed.gpu.global.add.noftz.v4.f16x2 [%0], {%1,%2,%3,%4};" :: "l"(p), "r"(x), "r"(y), "r"(z), "r"(w) : "memory");
}
DI void sq_acc(uint32_t& a, uint32_t x) { asm("fma.rn.bf16x2 %0, %1, %1, %0;" : "+r"(a) : "r"(x)); }
DI __half2 amax4(__half2 h, const uint32_t* v) {
  h = __hmax2_nan(__hmax2_nan(h, __habs2(*(const __half2*)&v[0])), __habs2(*(const __half2*)&v[1]));
  return __hmax2_nan(__hmax2_nan(h, __habs2(*(const __half2*)&v[2])), __habs2(*(const __half2*)&v[3]));
}
DI uint32_t wexp(__half2 h) { const uint32_t u = *(const uint32_t*)&h; return __reduce_max_sync(0xffffffffu, max((u >> 16) & 0x7fffu, u & 0x7fffu)) >> 7; }
DI float max10(const float* a) {
  return fmaxf(fmaxf(fmaxf(fmaxf(a[0], a[1]), fmaxf(a[2], a[3])), fmaxf(fmaxf(a[4], a[5]), fmaxf(a[6], a[7]))), fmaxf(a[8], a[9]));
}
DI float quad_max(float m) {
  return fmaxf(fmaxf(m, __shfl_xor_sync(0xffffffffu, m, 1)), fmaxf(__shfl_xor_sync(0xffffffffu, m, 2), __shfl_xor_sync(0xffffffffu, m, 3)));
}
DI float warp_sum(float v) {
#pragma unroll
  for (int o = 16; o; o >>= 1) v += __shfl_xor_sync(0xffffffffu, v, o);
  return v;
}

constexpr int SM_WO3 = 0;
constexpr int SM_X = 16384;
constexpr int XT = 36864;
constexpr int SM_EXP = 126976;
constexpr int SEGB = 10240;
constexpr int SM_BLK = SM_EXP + 8192;
constexpr int SM_VC = SM_BLK + 4 * SEGB;
constexpr int SM_PART = SM_VC + 16384;
constexpr int SM_QM = SM_PART + 4096;
constexpr int SM_E = SM_QM + 1024;
constexpr int SM_VM = SM_E + 1536;
constexpr int SM_OB = SM_VM + 2048;
constexpr int SM_FB = SM_OB + 2048;
constexpr int SM_STAGE = SM_X + XT;
constexpr int SM_M0 = SM_STAGE + 3 * 49152;
constexpr int SM_MISC = 210944;
constexpr int SM_WOST = 212992;
constexpr int SM_MEM = SM_WOST;
constexpr int SM_MAX = SM_MEM + 11264;
#define MEM_BLK(q) ((q) / 3 * 4096 + (q) % 3 * 1024)
constexpr int SM_TOTAL = 229376;
constexpr int MB_W = SM_MISC;
constexpr int MB_WO = SM_MISC + 24;
constexpr int MB_WO3 = SM_MISC + 32;
constexpr int MB_X = SM_MISC + 40;
constexpr int MB_S = SM_MISC + 64;
constexpr int MB_F = SM_MISC + 72;
constexpr int MB_VX = SM_MISC + 80;
constexpr int SC_FPAR = SM_MISC + 136;
constexpr int SC_DEAD = SM_MISC + 96;
constexpr int SC_UNSC = SM_MISC + 112;
constexpr int SC_EXPW = SM_MISC + 132;
constexpr int SC_ONES = SM_MISC + 144;
constexpr int SC_SS = SM_MISC + 160;
constexpr int SC_LAT = SM_MISC + 224;
constexpr int SC_EPO = SM_MISC + 240;
constexpr int MB_XS = SM_MISC + 248;
constexpr int SC_XMAX = SM_MISC + 256;
constexpr int SC_PROF = 229376;

constexpr float SM_SCALE = 0.08838834764831845f;
constexpr float LOG2E = 1.4426950408889634f;
constexpr float E_LIM = 20.f;

template <bool B> struct BoolC { static constexpr bool value = B; };
struct RMaps { CUtensorMap x, wq, wk, wv, wo; unsigned char* red; uint32_t poll; const unsigned char* w[4]; };

DI uint32_t latest_hint(uint32_t h, uint32_t d, int s) {
  const uint32_t x = (((h | 0xc0c0c0c0u) - ((d >> 5) & 63) * 0x01010101u) & 0x3f3f3f3fu) | ((h ^ (((s >> 2) + 1) & 3) * 0x40404040u) & 0xc0c0c0c0u);
  const uint32_t y = __vmaxu2(x & 0x00ff00ffu, (x >> 8) & 0x00ff00ffu);
  return __reduce_max_sync(0xffffffffu, max(y & 0xffffu, y >> 16));
}
DI uint32_t near_half(uint32_t sb) {
  uint32_t a, b; lds64(sb + SC_LAT, a, b);
  return a > b;
}

template <int RT, int K0, int K1, bool D32 = false>
DI void xproj(float* acc, const uint32_t (&wa)[2][18][4], uint64_t xd) {
  if (XP & 1) return;
  WG_FENCE();
#pragma unroll
  for (int k = K0; k < ((XP & 128) ? K0 + 1 : K1); k++)
  {
    uint64_t d = xd + (uint64_t)(((k >> 1) * 4096 + (k & 1) * 32) >> 4);
    if (D32) asm("mov.b64 %0, {%1, %2};" : "=l"(d) : "r"((uint32_t)xd + (((k >> 1) * 4096 + (k & 1) * 32) >> 4)), "r"((uint32_t)(xd >> 32)));
    wgmma_n32_rs(acc, wa[RT][k][0], wa[RT][k][1], wa[RT][k][2], wa[RT][k][3], d, k != 0);
  }
  WG_COMMIT();
}

DI void seg_store(int seg, uint32_t sb) {
  fence_async();
  asm volatile("cp.async.bulk.global.shared::cta.bulk_group [%0], [%1], 8192;"
               :: "l"(g_seg + ((size_t)(seg & RING) * 96 + blockIdx.x) * 8192), "r"(sb + SM_BLK + (seg & 3) * SEGB) : "memory");
  asm volatile("cp.async.bulk.commit_group;" ::: "memory");
}
DI void seg_publish(int seg, uint32_t sb) {
  const uint32_t v = lds32(sb + SC_EPO) + seg;
  asm volatile("cp.async.bulk.wait_group 0;" ::: "memory");
  stg_relaxed32(&g_sflag[blockIdx.x * 8], v);
}

DI void proj_role(const uint32_t sb, const RMaps& tm, const uint32_t rank, const int wg, const int w, const int lane) {
  const bool qk = rank < 2;
  uint32_t wa[2][18][4];
  {
    const int rr = (lane & 7) + ((lane >> 4) << 3);
    const uint32_t col = ((2 * w + ((lane >> 3) & 1)) ^ (lane & 7)) << 4;
    float ss;
#pragma unroll 1
    for (int pass = WARM ? wg + w == 0 : 1; pass < 2; pass++) {
      ss = 0.f;
      if (pass) bar_sync(3, 256);
#pragma unroll
      for (int c = 0; c < 3; c++) {
        QSTAMP(2 + 2 * c);
        if (pass) mbar_wait(sb + MB_W + 8 * c, 0);
        QSTAMP(3 + 2 * c);
#pragma unroll
        for (int rt = 0; rt < 2; rt++)
#pragma unroll
          for (int k = 0; k < 6; k++)
            ldsm4t(wa[rt][c * 6 + k], sb + SM_STAGE + c * 49152 + (rt ^ wg) * 24576 + (64 * (k >> 1) + 32 * wg + 16 * (k & 1) + rr) * 128 + col);
        if (c < 2) {
          fence_async();
          if (pass) {
            bar_sync(3, 256);
            QSTAMP(17 + c);
            if (threadIdx.x == 0) {
              if (c == 0) tma_load3(sb + SM_X + XT, &tm.x, 32, sb + MB_X + 8);
              else tma_load(sb + SM_X + 2 * XT, &tm.wo, rank * 192, (blockIdx.x / 3) * DH, sb + MB_WO);
            }
            __syncwarp();
          }
        }
        uint32_t q[4] = {0, 0, 0, 0};
#pragma unroll
        for (int rt = 0; rt < 2; rt++)
#pragma unroll
          for (int k = 0; k < 6; k++)
#pragma unroll
            for (int i = 0; i < 4; i++) sq_acc(q[i], wa[rt][c * 6 + k][i]);
#pragma unroll
        for (int i = 0; i < 4; i++) ss += bf_lo(q[i]) + bf_hi(q[i]);
      }
      ss = warp_sum(ss);
    }
    fence_async();
    cluster_arrive();
    if (lane == 0) sts32(sb + SC_SS + 4 * (wg * 4 + w), qk ? 0 : __float_as_uint(ss));
    bar_arrive(11, 384);
  }
  STAMP(1);
  QSTAMP(8);
  mbar_wait(sb + MB_X, 0);
  STAMP(2);
  QSTAMP(9);

  uint32_t t16 = sb + (w * 32 + lane) * 16;
  uint32_t mem_a = sb + SM_MEM + wg * 512 + lane * 16;
  uint32_t fin_a = sb + (lane & 7) * 16 + SM_BLK + (qk ? (wg ^ 1) * 4096 + w * 256 + (lane & 8) * 16 + (lane & 16) * 64
                                              : wg * 4096 + w * 1024 + (lane & 8) * 64 + (lane & 16) * 8);
  PIN(t16); PIN(mem_a); PIN(fin_a);
  const uint32_t fence_reg = mem_a;
  const uint32_t fin2 = qk ? 2048 : 256;
  float acc[16];
  const uint64_t xd0 = make_desc(sb + SM_X + wg * 64, 16, 1024, 1);
  auto do_export = [&](auto retire, uint32_t always) {
    WG_WAIT(0);
    uint32_t p[2];
#pragma unroll
    for (int i = 0; i < 2; i++) {
      p[i] = pack_bf16(acc[8 * i], acc[8 * i + 1]);
      sts128(t16 + SM_EXP + wg * 4096 + i * 2048, p[i], pack_bf16(acc[8 * i + 2], acc[8 * i + 3]),
             pack_bf16(acc[8 * i + 4], acc[8 * i + 5]), pack_bf16(acc[8 * i + 6], acc[8 * i + 7]));
    }
    if (decltype(retire)::value)
      asm volatile("{\n.reg .pred p, q;\nsetp.ne.u32 p, %2, 0;\nsetp.ne.u32 q, %2, 1;\n@p ld.shared.b32 %0, [%3];\n@q ld.shared.b32 %1, [%3 + 4];\n"
                   "setp.ne.u32 p, %0, %1;\n@p exit;\n}" : "+r"(p[0]), "+r"(p[1]) : "r"(always), "r"(sb + SC_DEAD) : "memory");
  };
  uint32_t o[8];
  auto import = [&]() { lds128(t16 + SM_EXP + (wg ^ 1) * 4096, o); lds128(t16 + SM_EXP + (wg ^ 1) * 4096 + 2048, o + 4); };
  auto finish = [&](int seg) {
    const uint32_t a = fin_a + (seg & 3) * SEGB;
    WG_WAIT(0);
#pragma unroll
    for (int i = 0; i < 8; i++) o[i] = FIN16 ? add_bf16(pack_bf16(acc[2 * i], acc[2 * i + 1]), o[i]) : pack_bf16(acc[2 * i] + bf_lo(o[i]), acc[2 * i + 1] + bf_hi(o[i]));
    stsm4(a, o[0], o[1], o[2], o[3]);
    stsm4(a + fin2, o[4], o[5], o[6], o[7]);
  };
  auto send_v = [&](int seg, int dst) {
    fence_async();
    if (seg < NSEG - 1 && !(XP & 2) && elect_one())
      bulk_s2s(mapa(sb + SM_VC + (seg & 1) * 8192, dst), sb + SM_BLK + (seg & 3) * SEGB, 8192, mapa(sb + MB_VX + (seg & 1) * 8, dst));
    __syncwarp();
  };
  auto wait_v = [&](int seg) {
    if (seg < NSEG - 1 && !(XP & 2)) {
      mbar_wait(sb + MB_VX + (seg & 1) * 8, (seg >> 1) & 1);
      if (elect_one()) mbar_expect(sb + MB_VX + (seg & 1) * 8, 8192);
      __syncwarp();
    }
  };
  bar_sync(3, 256);
  xproj<1, 0, 18>(acc, wa, xd0);
  do_export(BoolC<false>(), 0);
  SCHED_FENCE(11);
  xproj<0, 0, 18>(acc, wa, xd0);
  bar_sync(3, 256);
  QSTAMP(10);
  cluster_wait();
  QSTAMP(11);
  mbar_wait(sb + MB_X + 8, 0);
  QSTAMP(12);
  import();
  finish(0);
  SCHED_FENCE(12);
  bar_sync(3, 256);
  uint64_t dA = xd0 + (XT >> 4);
  xproj<1, 0, 18>(acc, wa, dA);
  if (!qk && wg == 0 && w < 2) send_v(0, w);
  QSTAMP(13);
  if (qk && wg == 0 && w == 0) wait_v(0);
  QSTAMP(14);
  bar_arrive(13, 384);
  if (!qk) {
    do_export(BoolC<false>(), 0);
    SCHED_FENCE(15);
    xproj<0, 0, 18>(acc, wa, dA);
    if (threadIdx.x == 0 && !(XP & 8)) { mbar_expect(sb + MB_X, XT); tma_load3(sb + SM_X, &tm.x, 96, sb + MB_X); }
    bar_sync(3, 256);
    mbar_wait(sb + MB_X + 16, 0);
    import();
    finish(1);
    SCHED_FENCE(16);
    bar_sync(3, 256);
    dA += XT >> 4;
    xproj<1, 0, 18>(acc, wa, dA);
    if (wg == 0 && w < VW2) send_v(1, w);
  }
  QSTAMP(15);
  WG_WAIT(0);
  bar_sync(0, 384);
  QSTAMP(16);
  const int ro = __shfl_sync(0xffffffffu, near_half(sb) ^ wg, 0);
  STAMP(5);
  const uint32_t always = __shfl_sync(0xffffffffu, lds32(sb + SC_DEAD + 12), 0);
  const int ah = qk ? 1 : 2;
  int b2 = qk ? 2 : 0;
  int s = 0;
  uint32_t hint_lo = (uint32_t)(uint64_t)tm.red + HINT_OFF + blockIdx.x + (lane & 1) * 4096 + (lane >> 1) * 16384;
  PIN(hint_lo);
  auto post_hint = [&]() {
    asm volatile("{\n.reg .pred p;\n.reg .b64 a;\n.reg .u32 t;\nsetp.lt.u32 p, %0, %1;\nmov.b64 a, {%2, %3};\nmov.u32 t, %%globaltimer_lo;\n"
                 "bfe.u32 t, t, 5, 6;\nor.b32 t, t, %4;\n@p st.relaxed.gpu.global.u8 [a], t;\n}"
                 :: "r"(t16), "r"(sb + 128), "r"(hint_lo + RED_SLOT(s)), "r"((uint32_t)((uint64_t)tm.red >> 32)), "r"(((s >> 2) + 1) << 6) : "memory");
  };
  auto memproj = [&](auto second, int id, uint32_t dep, float u0, float u1, float* r) {
    constexpr bool R1 = decltype(second)::value;
    uint32_t b[NUP][4], b0[4];
    if (R1) asm volatile("{\n.reg .pred p;\nsetp.eq.u32 p, %0, %1;\n@p exit;\n}" :: "r"(dep), "r"(id) : "memory");
    bar_sync(R1 ? 2 : 1, 256);
    PROF(0);
    ldsm4t(b0, mem_a);
#pragma unroll
    for (int q = 0; q < NUP; q++) {
      if (R1 && q == 2) {
        bar_sync(11, 256);
        SCHED_FENCE(id + 1);
      }
      ldsm4t(b[q], mem_a + MEM_BLK(q + 1));
    }
    mma16816z(&acc[0], wa[0][0], b0[0], b0[1]);
    mma16816z(&acc[4], wa[1][0], b0[0], b0[1]);
    mma16816z(&acc[8], wa[0][1], b0[2], b0[3]);
    mma16816z(&acc[12], wa[1][1], b0[2], b0[3]);
#pragma unroll
    for (int q = 1; q < 9; q++) {
      uint32_t* const c = b[(q - 1) % NUP];
      mma16816(&acc[0], wa[0][2 * q], c[0], c[1]);
      mma16816(&acc[4], wa[1][2 * q], c[0], c[1]);
      mma16816(&acc[8], wa[0][2 * q + 1], c[2], c[3]);
      mma16816(&acc[12], wa[1][2 * q + 1], c[2], c[3]);
      if (R1 && q + NUP == B3Q) bar_sync(3, 256);
      if (q + NUP < 9) ldsm4t_in(c, mem_a + MEM_BLK(q + NUP), always);
      else if (R1 && q + NUP < 11) lds128_in(c, t16 + SM_PART + (10 - q - NUP) * 2048, always);
      else if (!R1 && GATE && q == GATE) { bar_arrive(11, 256); lds128_in(c, sb + SC_DEAD, always); u0 = u1 = __uint_as_float(c[3]); }
    }
#pragma unroll
    for (int i = 0; i < 8; i++) {
      const float u = i < 4 ? u0 : u1;
      r[i] = R1 ? fmaf(acc[8 + i], u, (acc[i] + __uint_as_float(b[(8 + i / 4) % NUP][i & 3])) * u) : (GATE ? fmaf(acc[i], u, acc[8 + i]) : acc[i] + acc[8 + i]);
    }
  };
  if (ro == 0) {
#pragma unroll 1
    while (true) {
      do_export(BoolC<true>(), always);
      PROFP(3);
      if (s == 8) STAMP(6);
      float r[8];
      memproj(BoolC<false>(), 30, 0, 0.f, 0.f, r);
      sts128(t16 + SM_PART, __float_as_uint(r[0]), __float_as_uint(r[1]), __float_as_uint(r[2]), __float_as_uint(r[3]));
      sts128(t16 + SM_PART + 2048, __float_as_uint(r[4]), __float_as_uint(r[5]), __float_as_uint(r[6]), __float_as_uint(r[7]));
      bar_arrive(3, 256);
      PROF(1);
      bar_sync(9, 256);
      if (s == NSEG - 1) break;
      post_hint();
      if (w == 1) {
        uint32_t m[8];
        lds128(t16 + SM_MAX - 512, m); lds128(t16 + SM_MAX, m + 4);
        const int em = (wexp(amax4(amax4(*(const __half2*)&m[0], m), m + 4)) >> 3) + (int)(lds32(sb + SC_UNSC + (s & 1) * 8) >> 23) - 15;
        const int ex = max(s ? em : 0, (int)lds32(sb + SC_XMAX + 4 * s)) - 127 + (int)lds32(sb + SC_EXPW);
        sts32(sb + SC_UNSC + (~s & 1) * 8, (127 + min(max(ex, -120), 120)) << 23);
        __syncwarp();
        if (elect_one()) mbar_arrive(sb + MB_S);
      }
      SCHED_FENCE(9);
      bar_sync(5, qk ? N5 : 256);
      PROF(2);
      import();
      xproj<0, 0, NII>(acc, wa, dA);
      if (NII < 18) {
        if (qk) bar_sync(7, 384);
        xproj<0, NII, 18>(acc, wa, dA);
        if (!qk) bar_sync(7, 384);
      } else {
        if (F10) WG_WAIT(0);
        bar_sync(10, 256);
        if (F10) SCHED_FENCE(17);
      }
      dA += (int64_t)(b2 ? XT >> 4 : -(XT >> 3));
      finish(s + ah);
      if (qk || w >= VW2) bar_arrive(13, 384);
      PROF(6);
      SCHED_FENCE(14);
      bar_sync(12, 256);
      PROF(7);
      xproj<1, 0, 18, true>(acc, wa, dA);
      bar_arrive(14, 256);
      b2 = b2 == 2 ? 0 : b2 + 1;
      s++;
      if (!qk && w < VW2) { bar_sync(13, 384); send_v(s + 1, w); }
      PROFP(8);
    }
    if (!qk) bar_arrive(5, 256);
  } else {
#pragma unroll 1
    while (true) {
      do_export(BoolC<true>(), always);
      PROFP(3);
      if (s == 8) STAMP(6);
      const uint32_t tl = ((t16 >> 8) ^ wg) & 1, am = (t16 & ~256u) - w * 256;
      const float un = __uint_as_float(lds32(sb + SC_UNSC + (s & 1) * 8));
      float r[8];
      if (qk) {
        uint32_t a0 = am + (tl ? SM_QM : SM_BLK + 8192 + (s & 3) * SEGB);
        float u0 = wg ? un * (SM_SCALE * LOG2E) : un, u1 = wg ? un : un * (SM_SCALE * LOG2E);
        PIN(a0); PIN(u0); PIN(u1);
        memproj(BoolC<true>(), 32, a0, u0, u1, r);
        const uint32_t p0 = pack_bf16(r[0], r[1]), p1 = pack_bf16(r[2], r[3]), p2 = pack_bf16(r[4], r[5]), p3 = pack_bf16(r[6], r[7]);
        stsm4(a0, p0, p1, p2, p3);
        bar_arrive(4, 256);
        SCHED_FENCE(18);
        if (!(XP & 4))
          asm volatile("st.relaxed.gpu.global.v2.b32 [%0], {%1,%2};" :: "l"(g_km + (size_t)(s * NH + head_id()) * 4096 + (rank * 1024 + ((t16 - sb) >> 1))),
                       "r"(((wg ? p2 : p0) & ~1u) | lds32(sb + SC_EPO + 4)), "r"(wg ? p3 : p1) : "memory");
      } else {
        const uint32_t d0 = s < NSEG - 1 ? 0 : 2, d1 = s < NSEG - 1 ? 1 : 2;
        uint32_t r0 = mapa(t16 + SM_VM, d0), r1 = mapa(t16 + SM_VM, d1);
        PIN(r0); PIN(r1);
        memproj(BoolC<true>(), 34, r0 | r1, un, un, r);
        const uint32_t p0 = pack_bf16(r[0], r[1]), p1 = pack_bf16(r[2], r[3]), p2 = pack_bf16(r[4], r[5]), p3 = pack_bf16(r[6], r[7]);
        const uint32_t v0 = wg ? p2 : p0, v1 = wg ? p3 : p1, v2 = wg ? p0 : p2, v3 = wg ? p1 : p3;
        st_async4(r0, v0, v1, v2, v3, mapa(sb + MB_S, d0));
        st_async4(r1, v0, v1, v2, v3, mapa(sb + MB_S, d1));
        bar_arrive(5, 256);
        sts128(t16 + SM_VM, v0, v1, v2, v3);
        __syncwarp();
        if (elect_one()) mbar_arrive(sb + MB_S);
        SCHED_FENCE(19);
        if (!(XP & 4)) stg_relaxed(g_km + (size_t)(s * NH + head_id()) * 4096 + (2048 + t16 - sb), (v0 & ~1u) | lds32(sb + SC_EPO + 4), v1, v2, v3);
      }
      if (s == NSEG - 1) break;
      PROF(1);
      auto rearm = [&]() { mbar_wait(sb + MB_S, s & 1); if (elect_one()) mbar_expect(sb + MB_S, qk ? 640 + 2048 : 1280); __syncwarp(); };
      if (w == 1) {
        if ((t16 & 384) == 0) stg_relaxed(tm.red + (RED_SLOT(s + 2) + RED_LINE(blockIdx.x)) + (t16 & 112), 0, 0, 0, 0);
      } else if (w == 0) {
        const int tn = s + ah + 1;
        if (RFW) mbar_wait(sb + MB_S, s & 1);
        if (tn + 1 < NSEG && !(XP & 8) && elect_one()) {
          const int b0 = b2 == 2 ? 0 : b2 + 1;
          mbar_expect(sb + MB_X + 8 * b0, XT);
          tma_load3(sb + SM_X + b0 * XT, &tm.x, (tn + 1) * 32, sb + MB_X + 8 * b0);
        }
        if (tn < NSEG && (!(XP & 8) || tn < 3)) mbar_wait(sb + MB_X + 8 * b2, (tn / 3) & 1);
      } else if (w == 2) {
        if (!qk) { if (VW2 < 1) send_v(s + 1, 0); if (VW2 < 2) send_v(s + 1, 1); }
      } else if (qk || !NIC) {
        rearm();
      }
      __syncwarp();
      import();
      PROF(4);
      SCHED_FENCE(10);
      if (NIC) {
        if (qk) bar_sync(7, NII < 18 ? 384 : 256);
        xproj<0, 0, NIC>(acc, wa, dA);
        if (!qk) { if (w == 3) rearm(); bar_sync(7, NII < 18 ? 384 : 256); }
      } else {
        bar_sync(7, NII < 18 ? 384 : 256);
      }
      xproj<0, NIC, 18>(acc, wa, dA);
      bar_arrive(12, 256);
      dA += (int64_t)(b2 ? XT >> 4 : -(XT >> 3));
      finish(s + ah);
      if (qk && w == 0) wait_v(s + 1);
      bar_arrive(13, 384);
      PROF(6);
      SCHED_FENCE(13);
      bar_sync(14, 256);
      PROF(7);
      xproj<1, 0, 18>(acc, wa, dA);
      b2 = b2 == 2 ? 0 : b2 + 1;
      s++;
      PROFP(8);
    }
    if (t16 - sb < 128) stg_relaxed(tm.red + (RED_SLOT(NSEG + 1) + RED_LINE(blockIdx.x)) + (t16 & 112), 0, 0, 0, 0);
  }
  bar_arrive(0, 384);
  STAMP(3);
  cluster_sync();
  STAMP(4);
}

DI void attn_role(const uint32_t sb, unsigned char* smem_raw, const RMaps& tm, const uint32_t RANK, const bf16* __restrict__ x, const bf16* __restrict__ mem0,
                  const int w, const int lane) {
  const int t2 = w * 32 + lane;
  uint32_t wo[8][4], w1[8][4];
  const uint32_t wo_lane = sb + ((lane & 7) + ((lane >> 4) << 3)) * 128 + (((w + 4 * ((lane >> 3) & 1)) ^ (lane & 7)) << 4);
  unsigned char* const g_red = tm.red;
  {
    const uint32_t tag = *(volatile unsigned*)&g_epoch + 1;
    QSTAMP(0);
    bar_sync(0, 160);
    QSTAMP(1);
    cluster_arrive();
    __half2 hx = __float2half2_rn(0.f);
    if (blockIdx.x < NSEG) {
      mbar_wait(sb + MB_XS, 0);
#pragma unroll
      for (int i = 0; i < 18; i++) { uint32_t v[4]; lds128(sb + SM_X + t2 * 16 + i * 2048, v); hx = amax4(hx, v); }
      fence_async();
      bar_sync(6, 128);
      if (t2 == 0) tma_load3(sb + SM_X, &tm.x, 0, sb + MB_X);
      __syncwarp();
    }
    if (t2 == 0) { sts64(sb + SC_EPO, (tag - 1) * NSEG + 1, tag & 1); sts32(sb + SC_UNSC, __float_as_uint(1.f)); sts128(sb + SC_DEAD, 0, 0, 0, 0x3f800000u); sts64(sb + SC_FPAR, 0, 0); sts128(sb + SC_ONES, 0x3f803f80u, 0x3f803f80u, 0x3f803f80u, 0x3f803f80u); }
    WSTAMP(27);
    uint32_t q[8] = {0, 0, 0, 0, 0, 0, 0, 0};
    QSTAMP(2);
    mbar_wait(sb + MB_WO3, 0);
    QSTAMP(3);
    uint32_t mv[5][4];
#pragma unroll
    for (int i = 0; i < 5; i++) {
      ldsm4(mv[i], sb + SM_M0 + (lane & 7) * (DM * 2) + min(w + 4 * i, 17) * 64 + (lane >> 3) * 16);
      if (blockIdx.x == 0) hx = amax4(hx, mv[i]);
    }
    sts32(sb + SC_SS + 4 * (12 + w), wexp(hx));
#pragma unroll
    for (int k = 0; k < 8; k++) {
      ldsm4t(wo[k], wo_lane + SM_WO3 + k * 2048); ldsm4t(w1[k], wo_lane + SM_WOST + k * 2048);
#pragma unroll
      for (int i = 0; i < 4; i++) { sq_acc(q[i], wo[k][i]); sq_acc(q[i], w1[k][i]); }
    }
    bar_sync(6, 128);
#pragma unroll
    for (int k = 0; k < 8; k++) sts128(sb + SM_WO3 + t2 * 16 + k * 2048, wo[k][0], wo[k][1], wo[k][2], wo[k][3]);
#pragma unroll
    for (int i = 0; i < 5; i++) {
      const int c = (w + 4 * i) * 32;
      if (c < DM) stsm4t(sb + SM_MEM + (c + c / 192 * 64 + lane) * 16, mv[i][0], mv[i][1], mv[i][2], mv[i][3]);
    }
    bar_arrive(1, 256); bar_arrive(2, 256); bar_arrive(9, 256);
    QSTAMP(4);
    mbar_wait(sb + MB_WO, 0);
    QSTAMP(5);
#pragma unroll
    for (int k = 0; k < 8; k++) ldsm4t(wo[k], wo_lane + SM_X + 2 * XT + k * 2048);
    fence_async();
    bar_sync(6, 128);
    if (t2 == 32) tma_load3(sb + SM_X + 2 * XT, &tm.x, 64, sb + MB_X + 16);
    __syncwarp();
#pragma unroll
    for (int k = 0; k < 8; k++)
#pragma unroll
      for (int i = 0; i < 4; i++) sq_acc(q[4 + i], wo[k][i]);
    float ss = 0.f;
#pragma unroll
    for (int i = 0; i < 8; i++) ss += bf_lo(q[i]) + bf_hi(q[i]);
    ss = warp_sum(ss);
    if (lane == 0) sts32(sb + SC_SS + 4 * (8 + w), __float_as_uint(ss));
    QSTAMP(6);
    bar_sync(11, 384);
    QSTAMP(7);
    if (t2 == 0) {
      float a[16];
#pragma unroll
      for (int i = 0; i < 4; i++) lds128f(sb + SC_SS + 16 * i, &a[4 * i]);
      stg_relaxed(&g_stats[blockIdx.x * 2], __float_as_uint(((a[0] + a[1]) + (a[2] + a[3])) + ((a[4] + a[5]) + (a[6] + a[7]))),
                  __float_as_uint((a[8] + a[9]) + (a[10] + a[11])),
                  max(max(__float_as_uint(a[12]), __float_as_uint(a[13])), max(__float_as_uint(a[14]), __float_as_uint(a[15]))), tag);
    }
    __syncwarp();
    WSTAMP(24);
    QSTAMP(8);
    cluster_wait();
    QSTAMP(9);
    if (w == 0) {
      uint4 v[3];
      int n = 0;
      while (true) {
#pragma unroll
        for (int i = 0; i < 3; i++) v[i] = ldg_relaxed(&g_stats[(i * 32 + lane) * 2]);
        if (__all_sync(0xffffffffu, v[0].w == tag && v[1].w == tag && v[2].w == tag) || ++n > SPIN_LIMIT) break;
        __nanosleep(100);
      }
      WSTAMP(25);
      QSTAMP(10);
      const float sv = warp_sum(__uint_as_float(v[0].x) + __uint_as_float(v[1].x) + __uint_as_float(v[2].x));
      const float so = warp_sum(__uint_as_float(v[0].y) + __uint_as_float(v[1].y) + __uint_as_float(v[2].y));
      const int expW = ((int)(__float_as_uint(sv) >> 23) + (int)(__float_as_uint(so) >> 23) - 254 + 2 + 10 + 1) >> 1;
      sts32(sb + SC_XMAX + 4 * lane, v[0].z); sts32(sb + SC_XMAX + 128 + 4 * lane, v[1].z);
      sts32(sb + SC_EXPW, expW + 1 - 15);
      if (blockIdx.x == 0 && lane == 0) *(volatile unsigned*)&g_epoch = tag;
      sts32(sb + SC_FPAR + 4, 1);
    } else if (w < 3) {
      const uint32_t u = blockIdx.x >> 4;
      unsigned char* const z = g_red + 98304 + (blockIdx.x & 15) * 128 + (u & 1) * 2048 + (u & 6) * 4096 + (((u >> 1) ^ w) & 1) * 4096 + lane * 4;
      stg_relaxed32(z, 0);
      uint32_t best = 0xffffffffu;
#pragma unroll 1
      for (int i = 0; i < 64; i++) {
        uint32_t last, dt;
        asm volatile("{\n.reg .pred p;\n.reg .u32 c, v;\nld.volatile.shared.u32 %0, [%3];\nmov.u32 c, %%clock;\n"
                     "atom.relaxed.gpu.global.exch.b32 v, [%2], 0;\nsetp.eq.u32 p, v, 0;\nmov.u32 %1, 0;\n@p mov.u32 %1, %%clock;\nsub.u32 %1, %1, c;\n}"
                     : "=r"(last), "=r"(dt) : "l"(z), "r"(sb + SC_FPAR + 4) : "memory");
        best = min(best, dt);
        if ((last && i >= NPROBE - 1) || i >= NPROBE2 - 1) break;
      }
      sts32(sb + SC_LAT + (w - 1) * 4, best);
    }
    QSTAMP(11);
    bar_sync(13, 384);
    bar_arrive(0, 384);
    QSTAMP(12);
    WSTAMP(26);
  }

  const uint32_t nh = __shfl_sync(0xffffffffu, near_half(sb), 0);
  uint32_t l16 = sb + lane * 16;
  PIN(l16);
#define LV ((l16 >> 4) & 31)
#define fence_reg l16
  const uint32_t red_lo = (uint32_t)(uint64_t)g_red, red_hi = (uint32_t)((uint64_t)g_red >> 32);
  uint32_t lp;
  auto slot = [&](int s, uint32_t c, uint32_t ofs) {
    const uint32_t lo = lp | (red_lo + ((w >> 1) * 4 + (w & 1) * 2 + ((w ^ c) & 1)) * 4096 + RED_SLOT(s) + ofs);
    uint64_t a; asm("mov.b64 %0, {%1, %2};" : "=l"(a) : "r"(lo), "r"(red_hi));
    return (unsigned char*)a;
  };
  const uint32_t always = __shfl_sync(0xffffffffu, lds32(sb + SC_DEAD + 12), 0);
  const int mode0 = RANK < 2 ? w : w | 4;
  auto hint_addr = [&](int s) { return min(LV, 23u) * 4 + (red_lo + HINT_OFF + nh * 4096 + w * 16384 + RED_SLOT(s)); };
  auto load_hints = [&](uint32_t lo) {
    uint64_t a; asm("mov.b64 %0, {%1, %2};" : "=l"(a) : "r"(lo), "r"(red_hi));
    return ldg_relaxed32((const void*)a);
  };
  auto export_seg = [&](int seg) { if (!(XP & 4) && elect_one()) seg_store(seg, sb); __syncwarp(); };
  auto publish = [&](int seg) { if (!(XP & 4) && elect_one()) seg_publish(seg, sb); __syncwarp(); };
  uint32_t dl = __shfl_sync(0xffffffffu, gtime() - 768, 0);
  int s = 0;
  bool bad = false;
#pragma unroll 1
  while (true) {
    const uint32_t par = s & 1;
    uint32_t vx[4][4], hints;
    auto load_vx = [&]() {
      const uint32_t va = l16 + (RANK < 2 ? SM_VC + par * 8192 : SM_BLK + (s & 3) * SEGB) + w * 1024 + ((LV >> 3) & 1) * 384 - (LV >> 4) * 128;
#pragma unroll
      for (int i = 0; i < 4; i++) ldsm4(vx[i], va + (i & 1) * 4096 + (i >> 1) * 256);
    };
    auto retire = [&](uint32_t x) {
      asm volatile("{\n.reg .pred p;\nsetp.eq.u32 p, %0, 0;\n@p exit;\n}" :: "r"(vx[0][0] | vx[1][0] | vx[2][0] | vx[3][0] | x) : "memory");
    };
    auto scores = [&](auto memkeys, auto first, float* sc) {
      constexpr bool MK = decltype(memkeys)::value, FIRST = decltype(first)::value;
      uint32_t kb[4][4], qb[2][4];
      const uint32_t m = LV >> 3;
      uint32_t kaddr = l16 + SM_BLK + 4096 + (s & 3) * SEGB + w * 2048 + (m & 1) * (MK ? 128 : 896) - (m >> 1) * 128;
      if (MK) { PIN(kaddr); }
      else {
#pragma unroll
        for (int k = 0; k < 4; k++) ldsm4t(kb[k], kaddr + k * 256);
      }
      if (FIRST) { load_vx(); retire(MK ? kaddr : kb[0][0] | kb[1][0] | kb[2][0] | kb[3][0] | l16); bar_sync(4, 256); PROF(4); }
      ldsm4t(qb[0], l16 + SM_QM);
      if (MK) ldsm4t(kb[0], kaddr);
      ldsm4t(qb[1], l16 + SM_QM + 512);
      if (MK) ldsm4t(kb[2], kaddr + 512);
      float c[4][4];
      mma16816z(c[0], kb[0], qb[0][0], qb[0][1]); mma16816z(c[1], kb[MK ? 0 : 1], qb[0][2], qb[0][3]);
      mma16816z(c[2], kb[2], qb[1][0], qb[1][1]); mma16816z(c[3], kb[MK ? 2 : 3], qb[1][2], qb[1][3]);
      if (FIRST && B5POS == 0) bar_arrive(5, N5);
#pragma unroll
      for (int i = 0; i < (MK ? 2 : 4); i++) sc[i] = ((c[0][i] + c[1][MK ? i + 2 : i]) + c[2][i]) + c[3][MK ? i + 2 : i];
    };
    auto send = [&](auto memkeys) {
      constexpr bool MK = decltype(memkeys)::value;
      constexpr int N = MK ? 1 : 2;
      const uint32_t sa = sb + LV * 4 + SM_E + (MK ? 1024 + RANK * 128 : RANK * 512 + w * 256);
      uint32_t ra[N][2], mb[N][2];
#pragma unroll
      for (int i = 0; i < N; i++)
#pragma unroll
        for (int j = 0; j < 2; j++) {
          ra[i][j] = mapa(sa + i * 128, j ? 2 : RANK ^ 1); mb[i][j] = mapa(sb + MB_S, j ? 2 : RANK ^ 1);
          PIN(ra[i][j]);
        }
      float sc[4];
      scores(memkeys, BoolC<true>(), sc);
      uint32_t e[N];
#pragma unroll
      for (int i = 0; i < N; i++) {
        e[i] = pack_bf16(ex2(sc[2 * i]), ex2(sc[2 * i + 1]));
        if (!(fmaxf(fabsf(sc[2 * i]), fabsf(sc[2 * i + 1])) <= E_LIM)) e[i] = 0x7fff7fffu;
        st_async1(ra[i][0], e[i], mb[i][0]);
        st_async1(ra[i][1], e[i], mb[i][1]);
      }
#pragma unroll
      for (int i = 0; i < N; i++) sts32(sa + i * 128, e[i]);
      __syncwarp();
      if (l16 == sb) mbar_arrive(sb + MB_S);
      PROF(5);
    };
    const int mode = bad ? 8 : mode0;
    if (mode < 2) {
      send(BoolC<false>());
    } else if (mode == 2) {
      send(BoolC<true>());
    } else if (mode == 8) {
      load_vx();
      retire(l16);
      const uint32_t fp = lds32(sb + SC_FPAR);
      bar_sync(6, 128);
      if (w == 0 && l16 == sb) { sts32(sb + SC_FPAR, fp ^ 1); mbar_expect(sb + MB_F, 3072); }
      if (RANK < 2 && w < 3) {
        float sc[4] = {0.f, 0.f, 0.f, 0.f};
        if (w < 2) scores(BoolC<false>(), BoolC<false>(), sc); else scores(BoolC<true>(), BoolC<false>(), sc);
#pragma unroll 1
        for (int r = 0; r < 3; r++)
          st_async4(mapa(l16 + SM_FB + RANK * 1536 + w * 512, r), __float_as_uint(sc[0]), __float_as_uint(sc[1]), __float_as_uint(sc[2]), __float_as_uint(sc[3]), mapa(sb + MB_F, r));
      }
      mbar_wait(sb + MB_F, fp);
      float a[12];
#pragma unroll
      for (int j = 0; j < 3; j++) {
        float b[4];
        lds128f(l16 + SM_FB + j * 512, a + 4 * j); lds128f(l16 + SM_FB + 1536 + j * 512, b);
#pragma unroll
        for (int i = 0; i < 4; i++) a[4 * j + i] += b[i];
      }
      float m0 = fmaxf(fmaxf(fmaxf(a[0], a[2]), fmaxf(a[4], a[6])), a[8]), m1 = fmaxf(fmaxf(fmaxf(a[1], a[3]), fmaxf(a[5], a[7])), a[9]);
#pragma unroll
      for (int o = 4; o < 32; o <<= 1) { m0 = fmaxf(m0, __shfl_xor_sync(0xffffffffu, m0, o)); m1 = fmaxf(m1, __shfl_xor_sync(0xffffffffu, m1, o)); }
#pragma unroll
      for (int i = 0; i < 5; i++) {
        const uint32_t ea = sb + SM_E + LV * 4 + (i < 4 ? i * 128 : 1024);
        sts32(ea, pack_bf16(ex2(a[2 * i] - m0), ex2(a[2 * i + 1] - m1)));
        sts32(ea + (i < 4 ? 512 : 128), 0x3f803f80u);
      }
      __syncwarp();
    } else {
      load_vx();
      if (mode == 3) bar_arrive(4, 256);
      retire(l16 + 1);
      if (w == 3) export_seg(s);
    }
    {
      uint32_t wa[4], wb[4], oc[4];
      constexpr int WS = 2048;
      const uint32_t w3a = l16 + SM_WO3 + w * 512;
      lds128(w3a + KP(0) * WS, wa); lds128(w3a + KP(1) * WS, wb); lds128(sb + SC_ONES, oc);
      if (B5POS == 1 && mode < 3) bar_arrive(5, N5);
      uint32_t e[10], p[5], vm[4], ob[4];
      float o0[4], o1[4], f[3][2][4], rs[4];
      reserve2(vm); reserve2(vm + 2); reserve2(e + 8);
      hints = hint_addr(s);
      PIN(hints);
      if (CLR & 2) asm volatile("{\n.reg .pred p;\nsetp.eq.u32 p, %0, 0;\n@p exit;\n}" :: "r"(wa[0] | wb[0] | oc[0] | hints) : "memory");
      mbar_wait(sb + MB_S, par);
      PROF(6);
      ldsm4t(e, l16 + SM_E); ldsm2t_in(e + 8, l16 + SM_E + 1024, always); ldsm4t(e + 4, l16 + SM_E + 512);
      lds128_in(vm, l16 + w * 512 + SM_VM, always);
      const float scl = __uint_as_float(lds32(sb + SC_UNSC + 8 - par * 8));
      hints = load_hints(hints);
      if (GF & 1) SCHED_FENCE(4);
#pragma unroll
      for (int i = 0; i < 4; i++) p[i] = mul_bf16(e[i], e[4 + i]);
      p[4] = mul_bf16(e[8], e[9]);
      mma16816z(o0, vx[0], p[0], p[1]); mma16816z(o1, vx[1], p[0], p[1]); mma16816z(rs, oc, p[0], p[1]);
      mma16816(o0, vx[2], p[2], p[3]); lds128_in(vx[2], w3a + KP(2) * WS, always);
      mma16816(o1, vx[3], p[2], p[3]); lds128_in(vx[3], w3a + KP(3) * WS, always);
      mma16816(rs, oc, p[2], p[3]);
      mma1688(o0, vm[0], vm[1], p[4]); mma1688(o1, vm[2], vm[3], p[4]); mma1688(rs, oc[0], oc[1], p[4]);
      stsm4(l16 + w * 512 + SM_OB, pack_bf16(o0[0], o0[1]), pack_bf16(o0[2], o0[3]), pack_bf16(o1[0], o1[1]), pack_bf16(o1[2], o1[3]));
      bar_sync(6, 128);
      PROF(7);
      ldsm4t_in(oc, l16 + SM_OB, always);
      bad = __any_sync(0xffffffffu, !(rs[0] + rs[1] > 0.f) && !bad);
      rs[0] *= scl; rs[1] *= scl;
      asm volatile("{\n.reg .pred p;\nsetp.ne.u32 p, %1, 0;\n@p rcp.approx.ftz.f32 %0, %0;\n}" : "+f"(rs[0]) : "r"(always));
      asm volatile("{\n.reg .pred p;\nsetp.ne.u32 p, %1, 1;\n@p rcp.approx.ftz.f32 %0, %0;\n}" : "+f"(rs[1]) : "r"(always));
      asm volatile("lop3.b32 %0, %1, %2, %3, 0xfe;" : "=r"(lp) : "r"((l16 & 128) * 2), "r"((l16 & 256) * 4), "r"(l16 & 112));
      if (bad) continue;
      ldsm4t(ob, l16 + SM_OB + 512);
      mma16816z(f[2][0], wa, oc[0], oc[1]); mma16816z(f[2][1], wb, oc[2], oc[3]);
      mma16816z(f[0][0], wo[0], oc[0], oc[1]); mma16816z(f[0][1], wo[4], oc[2], oc[3]);
      mma16816z(f[1][0], w1[0], oc[0], oc[1]); mma16816z(f[1][1], w1[4], oc[2], oc[3]);
      ldsm4t_in(oc, l16 + SM_OB + 1024, always);
      mma16816(f[2][0], vx[2], ob[0], ob[1]); lds128_in(vx[2], w3a + KP(4) * WS, always);
      mma16816(f[2][1], vx[3], ob[2], ob[3]); lds128_in(vx[3], w3a + KP(5) * WS, always);
      mma16816(f[0][0], wo[1], ob[0], ob[1]); mma16816(f[0][1], wo[5], ob[2], ob[3]);
      mma16816(f[1][0], w1[1], ob[0], ob[1]); mma16816(f[1][1], w1[5], ob[2], ob[3]);
      ldsm4t_in(ob, l16 + SM_OB + 1536, always);
      mma16816(f[0][0], wo[2], oc[0], oc[1]); mma16816(f[0][1], wo[6], oc[2], oc[3]);
      mma16816(f[2][0], vx[2], oc[0], oc[1]); lds128_in(vx[2], w3a + KP(6) * WS, always);
      mma16816(f[2][1], vx[3], oc[2], oc[3]); lds128_in(vx[3], w3a + KP(7) * WS, always);
      mma16816(f[1][0], w1[2], oc[0], oc[1]); mma16816(f[1][1], w1[6], oc[2], oc[3]);
      mma16816(f[0][0], wo[3], ob[0], ob[1]); mma16816(f[0][1], wo[7], ob[2], ob[3]);
      mma16816(f[1][0], w1[3], ob[0], ob[1]); mma16816(f[1][1], w1[7], ob[2], ob[3]);
      mma16816(f[2][0], vx[2], ob[0], ob[1]); mma16816(f[2][1], vx[3], ob[2], ob[3]);
      bar_arrive(7, NII < 18 ? 384 : 256);
      lds128_in(ob, sb + SC_DEAD, always);
      uint32_t h[3][2];
#pragma unroll
      for (int j = 0; j < 3; j++)
#pragma unroll
        for (int i = 0; i < 2; i++)
        {
          scale_sum(f[j][1][2 * i], f[j][0][2 * i], rs[0], always); scale_sum(f[j][1][2 * i + 1], f[j][0][2 * i + 1], rs[1], always);
          h[j][i] = pack_f16(f[j][1][2 * i], f[j][1][2 * i + 1]);
        }
      const uint32_t rofs = RANK * 32768;
      red_f16x8(slot(s, RANK >> 1, rofs), h[0][0], h[1][0], h[2][0], 0x3c00u);
      red_f16x8(slot(s, (RANK >> 1) ^ 1, rofs), h[0][1], h[1][1], h[2][1], 0x3c00u);
      if (NII == 18) bar_arrive(10, 256);
      SCHED_FENCE(5);
      l16 += ob[B7R];
    }
    {
    PROF(8);
    const uint32_t ma0 = l16 + SM_MEM + w * 128 + (LV >> 3) * 896 + nh * 512;
    const unsigned char* const sl[2] = {slot(s, nh, 0), slot(s, nh ^ 1, 0)};
    uint32_t late = latest_hint(hints, dl, s);
    if (late >= 64) {
      int n = 0;
#pragma unroll 1
      do {
        late = latest_hint(load_hints(hint_addr(s)), dl, s);
      } while (late >= 64 && ++n < SPIN_LIMIT);
    }
    dl += late * 32 + tm.poll;
    if (w == 3) publish(s);
    if (QM && blockIdx.x == 0 && l16 == sb && w == 0) stg_relaxed32(g_pace, dl);
    PROF(9);
    {
      auto wait_until = [&](uint32_t t) {
        asm volatile("{\n.reg .pred p;\n.reg .s32 c;\n.reg .u64 t;\nTL: mov.u64 t, %%globaltimer;\ncvt.u32.u64 c, t;\nsub.s32 c, c, %0;\nsetp.lt.s32 p, c, 0;\n@p bra.uni TL;\n}" :: "r"(t + (l16 & 15)) : "memory");
      };
      uint4 v[2][3];
      auto load = [&](int c) {
#pragma unroll
        for (int r = 0; r < 3; r++) v[c][r] = ldg_relaxed(sl[c ^ (r >> 1)] + r * 32768);
      };
      auto decode = [&](int c, int n) {
        uint32_t q[9];
        __half2 hm;
        const uint32_t ma = ma0 ^ (c * 512);
#pragma unroll
        for (int i = 0; i < 9; i++) {
          const uint32_t h = i % 3 == 0 ? v[c][i / 3].x : (i % 3 == 1 ? v[c][i / 3].y : v[c][i / 3].z);
          const float2 f = __half22float2(*(const __half2*)&h);
          q[i] = pack_bf16(f.x, f.y);
          hm = i ? __hmax2(hm, __habs2(*(const __half2*)&h)) : __habs2(*(const __half2*)&h);
        }
#pragma unroll
        for (int r = 0; r < 3; r++) stsm4(ma + r * 4096, q[3 * r], q[3 * r + 1], q[3 * r + 2], r < 2 ? v[c][r].w : *(const uint32_t*)&hm);
        const bool done = __all_sync(0xffffffffu, v[c][0].w == 0x5000u && v[c][1].w == 0x5000u && v[c][2].w == 0x5000u) || n > SPIN_LIMIT;
        asm volatile("{\n.reg .pred p;\nsetp.ne.u32 p, %0, 0;\n@p bar.arrive %1, 256;\n}" :: "r"((int)done), "r"(1 + c) : "memory");
        return done;
      };
      if (LEAD) { wait_until(dl - LEAD); load(1); }
      wait_until(dl);
      PROF(10);
      int n = 0;
#pragma unroll 1
      do {
        load(0);
        if (!LEAD) load(1);
        asm volatile("{\n.reg .pred p;\nsetp.eq.u32 p, %0, 0;\n@p bar.sync 13, 384;\n}" :: "r"(n) : "memory");
      } while (!decode(0, n++));
      PROF(11);
#pragma unroll 1
      while (!decode(1, n++)) load(1);
      bar_arrive(9, 256);
      PROF(12);
    }
    PROF(13);
    if (++s == NSEG - 1) break;
    }
  }
#undef fence_reg
  if (RANK < 2) bar_arrive(4, 256);
  if (w == 3) { export_seg(NSEG - 1); publish(NSEG - 1); }
  bar_sync(0, 384);
  cluster_sync();
}

__global__ void __cluster_dims__(3, 1, 1) __launch_bounds__(384, 1)
rec_kernel(const __grid_constant__ RMaps tm, const bf16* __restrict__ x, const bf16* __restrict__ mem0) {
  extern __shared__ __align__(1024) unsigned char smem_raw[];
  const uint32_t sb = smem_u32(smem_raw);
  const int tid = threadIdx.x, lane = tid & 31;
  const int wg = __shfl_sync(0xffffffffu, tid >> 7, 0);
  const int w = __shfl_sync(0xffffffffu, (tid >> 5) & 3, 0);
  uint32_t rank; asm("mov.u32 %0, %%cluster_ctarank;" : "=r"(rank));
  STAMP(0);
  asm volatile("griddepcontrol.launch_dependents;" ::: "memory");

  if (wg < 2) {
    asm volatile("setmaxnreg.inc.sync.aligned.u32 192;");
    if (tid == 0) {
      for (int i = 0; i < 3; i++) { mbar_init(sb + MB_W + 8 * i, 1); mbar_init(sb + MB_X + 8 * i, 1); }
      mbar_init(sb + MB_WO, 1); mbar_init(sb + MB_WO3, 1);
      mbar_init(sb + MB_S, rank < 2 ? 5 : 6);
      mbar_init(sb + MB_F, 1); mbar_init(sb + MB_XS, 1);
      mbar_init(sb + MB_VX, 1); mbar_init(sb + MB_VX + 8, 1);
      asm volatile("fence.mbarrier_init.release.cluster;" ::: "memory");
      fence_async();
      const int h = blockIdx.x / 3;
      const CUtensorMap* m0 = rank < 2 ? &tm.wk : &tm.wv;
      const CUtensorMap* m1 = rank < 2 ? &tm.wq : &tm.wv;
      const int c0 = h * DH + (rank == 1 ? 64 : 0), c1 = h * DH + (rank == 0 ? 0 : 64);
      auto load_w = [&](int c) {
        mbar_expect(sb + MB_W + 8 * c, 49152);
        tma_load(sb + SM_STAGE + c * 49152, m0, c0, c * 192, sb + MB_W + 8 * c);
        tma_load(sb + SM_STAGE + c * 49152 + 24576, m1, c1, c * 192, sb + MB_W + 8 * c);
      };
      for (int i = 0; i < 3; i++) mbar_expect(sb + MB_X + 8 * i, XT);
      if (blockIdx.x < NSEG) { mbar_expect(sb + MB_XS, XT); bulk_load(sb + SM_X, x + blockIdx.x * 32 * DM, XT, sb + MB_XS); }
      for (int c = 0; c < WPOS; c++) load_w(c);
      mbar_expect(sb + MB_WO3, 32768 + 8 * DM * 2);
      tma_load(sb + SM_WOST, &tm.wo, rank * 192 + 64, h * DH, sb + MB_WO3);
      tma_load(sb + SM_WO3, &tm.wo, rank * 192 + 128, h * DH, sb + MB_WO3);
      bulk_load(sb + SM_M0, mem0, 8 * DM * 2, sb + MB_WO3);
      tma_prefetch(&tm.wo, rank * 192, h * DH);
      if (blockIdx.x >= NSEG) tma_load3(sb + SM_X, &tm.x, 0, sb + MB_X);
      for (int c = WPOS; c < 3; c++) load_w(c);
      mbar_expect(sb + MB_WO, 16384);
      mbar_expect(sb + MB_S, rank < 2 ? 640 + 2048 : 1280);
      mbar_expect(sb + MB_VX, 8192); mbar_expect(sb + MB_VX + 8, 8192);
    }
    __syncwarp();
    QSTAMP(0);
    if (tid < 32) bar_arrive(0, 160);
    QSTAMP(1);
    proj_role(sb, tm, rank, wg, w, lane);
  } else {
    asm volatile("setmaxnreg.dec.sync.aligned.u32 120;");
    attn_role(sb, smem_raw, tm, rank, x, mem0, w, lane);
  }
}

constexpr int NAUX = 36;
constexpr int A_ST = 3, A_STAGE = 16384 + 24576, A_STG = A_ST * A_STAGE;
constexpr int A_KV = 2 * DM * 2, A_Q = 30 * A_KV, A_CHUNK = A_Q + 16 * DM * 2;
constexpr int A_XW = 4 * XT, A_XT = A_XW + 16384, A_NR = 4;
constexpr int A_IN = A_XT + 16384, A_OST = A_IN + 3 * SEGB, A_P = A_OST + 8192, A_G = A_P + 3072;
constexpr int A_BAR = 229376;
constexpr int A_TOTAL = A_BAR + 512;
struct AMaps { CUtensorMap x, wa, qst, o, o3, wob, woa; };

DI void wgmma_n192_ss_nt(float* d, uint64_t da, uint64_t db, int acc) {
  asm volatile("{\n.reg .pred p;\nsetp.ne.b32 p, %98, 0;\n"
               "wgmma.mma_async.sync.aligned.m64n192k16.f32.bf16.bf16 {"
               "%0,%1,%2,%3,%4,%5,%6,%7,%8,%9,%10,%11,%12,%13,%14,%15,%16,%17,%18,%19,%20,%21,%22,%23,%24,%25,%26,%27,%28,%29,%30,%31,"
               "%32,%33,%34,%35,%36,%37,%38,%39,%40,%41,%42,%43,%44,%45,%46,%47,%48,%49,%50,%51,%52,%53,%54,%55,%56,%57,%58,%59,%60,%61,%62,%63,"
               "%64,%65,%66,%67,%68,%69,%70,%71,%72,%73,%74,%75,%76,%77,%78,%79,%80,%81,%82,%83,%84,%85,%86,%87,%88,%89,%90,%91,%92,%93,%94,%95"
               "}, %96, %97, p, 1, 1, 0, 1;\n}\n"
               : ACC8(d, 0), ACC8(d, 8), ACC8(d, 16), ACC8(d, 24), ACC8(d, 32), ACC8(d, 40), ACC8(d, 48), ACC8(d, 56),
                 ACC8(d, 64), ACC8(d, 72), ACC8(d, 80), ACC8(d, 88) : "l"(da), "l"(db), "r"(acc));
}
DI void wgmma_n32_ss_tn(float* d, uint64_t da, uint64_t db, int on) {
  asm volatile("{\n.reg .pred p;\nsetp.ne.b32 p, %18, 0;\n"
               "@p wgmma.mma_async.sync.aligned.m64n32k16.f32.bf16.bf16 {%0,%1,%2,%3,%4,%5,%6,%7,%8,%9,%10,%11,%12,%13,%14,%15}, "
               "%16, %17, 1, 1, 1, 1, 0;\n}\n"
               : ACC8(d, 0), ACC8(d, 8) : "l"(da), "l"(db), "r"(on));
}
DI void wgmma_n40_ss(float* d, uint64_t da, uint64_t db, int acc) {
  asm volatile("{\n.reg .pred p;\nsetp.ne.b32 p, %22, 0;\n"
               "wgmma.mma_async.sync.aligned.m64n40k16.f32.bf16.bf16 {%0,%1,%2,%3,%4,%5,%6,%7,%8,%9,%10,%11,%12,%13,%14,%15,%16,%17,%18,%19}, "
               "%20, %21, p, 1, 1, 1, 1;\n}\n"
               : ACC8(d, 0), ACC8(d, 8), "+f"(d[16]), "+f"(d[17]), "+f"(d[18]), "+f"(d[19]) : "l"(da), "l"(db), "r"(acc));
}
DI uint2 ldg_relaxed64(const void* p) {
  uint2 v; asm volatile("ld.relaxed.gpu.global.v2.b32 {%0,%1}, [%2];" : "=r"(v.x), "=r"(v.y) : "l"(p) : "memory"); return v;
}
template <int ST> DI void ldg8x64(uint32_t* m, const void* p) {
  asm volatile("ld.relaxed.gpu.global.v2.b32 {%0,%1}, [%16];\nld.relaxed.gpu.global.v2.b32 {%2,%3}, [%16 + %17];\n"
               "ld.relaxed.gpu.global.v2.b32 {%4,%5}, [%16 + %18];\nld.relaxed.gpu.global.v2.b32 {%6,%7}, [%16 + %19];\n"
               "ld.relaxed.gpu.global.v2.b32 {%8,%9}, [%16 + %20];\nld.relaxed.gpu.global.v2.b32 {%10,%11}, [%16 + %21];\n"
               "ld.relaxed.gpu.global.v2.b32 {%12,%13}, [%16 + %22];\nld.relaxed.gpu.global.v2.b32 {%14,%15}, [%16 + %23];"
               : "=r"(m[0]), "=r"(m[1]), "=r"(m[2]), "=r"(m[3]), "=r"(m[4]), "=r"(m[5]), "=r"(m[6]), "=r"(m[7]),
                 "=r"(m[8]), "=r"(m[9]), "=r"(m[10]), "=r"(m[11]), "=r"(m[12]), "=r"(m[13]), "=r"(m[14]), "=r"(m[15])
               : "l"(p), "n"(ST), "n"(2 * ST), "n"(3 * ST), "n"(4 * ST), "n"(5 * ST), "n"(6 * ST), "n"(7 * ST) : "memory");
}
template <int ST> DI void ldg4x128(uint32_t* m, const void* p) {
  asm volatile("ld.relaxed.gpu.global.v4.b32 {%0,%1,%2,%3}, [%16];\nld.relaxed.gpu.global.v4.b32 {%4,%5,%6,%7}, [%16 + %17];\n"
               "ld.relaxed.gpu.global.v4.b32 {%8,%9,%10,%11}, [%16 + %18];\nld.relaxed.gpu.global.v4.b32 {%12,%13,%14,%15}, [%16 + %19];"
               : "=r"(m[0]), "=r"(m[1]), "=r"(m[2]), "=r"(m[3]), "=r"(m[4]), "=r"(m[5]), "=r"(m[6]), "=r"(m[7]),
                 "=r"(m[8]), "=r"(m[9]), "=r"(m[10]), "=r"(m[11]), "=r"(m[12]), "=r"(m[13]), "=r"(m[14]), "=r"(m[15])
               : "l"(p), "n"(ST), "n"(2 * ST), "n"(3 * ST) : "memory");
}
template <int N, int ST> DI bool stale(const uint32_t* m, uint32_t tag) {
  uint32_t x = m[0] ^ tag;
#pragma unroll
  for (int i = 1; i < N; i++) asm("lop3.b32 %0, %0, %1, %2, 0xf6;" : "+r"(x) : "r"(m[i * ST]), "r"(tag));
  return __any_sync(0xffffffffu, x & 1);
}
DI bool mbar_test(uint32_t b, uint32_t par) {
  uint32_t r; asm volatile("{\n.reg .pred p;\nmbarrier.test_wait.parity.shared::cta.b64 p, [%1], %2;\nselp.u32 %0, 1, 0, p;\n}" : "=r"(r) : "r"(b), "r"(par) : "memory");
  return r;
}
DI int wait_flags(const unsigned* p, bool active, unsigned base, int seg) {
  int n = 0, m;
  while (true) {
    m = __reduce_min_sync(0xffffffffu, active ? (int)(ldg_acquire32(p) - base) : NSEG);
    if (m > seg || ++n > SPIN_LIMIT) break;
    __nanosleep(40);
  }
  return max(m, seg + 1);
}
DI void wait_count(const unsigned* p, unsigned target) {
  int n = 0;
  unsigned v;
  while (true) {
    asm volatile("ld.acquire.gpu.global.b32 %0, [%1];" : "=r"(v) : "l"(p) : "memory");
    if ((int)(v - target) >= 0 || ++n > SPIN_LIMIT) break;
    __nanosleep(64);
  }
}
#define PING 1
#define FLAG 2
#define FPOS 1
#define QB 2
#define Q_LO 320
#define Q_HI 1056
DI void quiet_wait(uint32_t& dl) {
  if (XP & 32) return;
  for (int n = 0; n < 64; n++) {
    const int d = gtime() - dl;
    if (d <= Q_HI && d > -4096) { wait_until(dl + Q_LO); return; }
    const uint32_t v = ldg_relaxed32(g_pace);
    if (v == dl && (d > 3072 || d < 0)) return;
    dl = v;
  }
}
DI void aux_barrier(int i, unsigned epoch) {
  asm volatile("fence.proxy.async;" ::: "memory");
  asm volatile("red.release.gpu.global.add.u32 [%0], 1;" :: "l"(&g_abar[i * 32]) : "memory");
  wait_count(&g_abar[i * 32], NAUX * (epoch + 1));
  asm volatile("fence.proxy.async;" ::: "memory");
}

__global__ void __launch_bounds__(512, 1)
aux_kernel(const __grid_constant__ AMaps tm, const bf16* __restrict__ x, const bf16* __restrict__ gate_w, bf16* __restrict__ out) {
  extern __shared__ __align__(1024) unsigned char smem_raw[];
  const uint32_t sb = smem_u32(smem_raw);
  const uint32_t full1 = sb + A_BAR, empty1 = full1 + 8 * A_ST, full2 = empty1 + 8 * A_ST, fullw = full2 + 16, full3 = fullw + 8, empty3 = full3 + 8 * A_NR,
                 fullq = empty3 + 8 * A_NR, fullv = fullq + 8, emptyq = fullv + 8, emptyv = emptyq + 8;
  const int tid = threadIdx.x, lane = tid & 31, cta = blockIdx.x;
  const int wg = __shfl_sync(0xffffffffu, tid >> 7, 0), w = __shfl_sync(0xffffffffu, (tid >> 5) & 3, 0);
  ASTAMP(14);
  const unsigned epoch = *(volatile unsigned*)&g_epoch2;
  if (tid == 0) {
    for (int i = 0; i < A_ST; i++) { mbar_init(full1 + 8 * i, 1); mbar_init(empty1 + 8 * i, 8); }
    mbar_init(full2, 1); mbar_init(full2 + 8, 1); mbar_init(fullw, 1); mbar_init(fullq, 2); mbar_init(fullv, 2);
    mbar_init(emptyq, 4); mbar_init(emptyv, 4);
    for (int i = 0; i < A_NR; i++) { mbar_init(full3 + 8 * i, 1); mbar_init(empty3 + 8 * i, cta < NH ? 8 : 4); }
    fence_async();
  }
  __syncthreads();
  ASTAMP(0);
  const bool wide = cta < NH;
  auto p3_ks = [&](int g) { return wide ? cta >> 2 : 2 * (cta - NH) + g; };
  auto p3_mt = [&](int g) { return wide ? 2 * (cta & 3) + g : 8; };
  const unsigned fbase = epoch * NSEG;
  if (wg == 3) {
    asm volatile("setmaxnreg.dec.sync.aligned.u32 40;");
    if (w == 1 && cta < NH) {
#pragma unroll 1
      for (int seg = 0; seg < ((XP & 2048) ? 0 : NSEG); seg++) {
        bar_arrive(5, 160);
        if (seg > 0 && lane == 0) {
          asm volatile("cp.async.bulk.wait_group 0;" ::: "memory");
          stg_relaxed32(&g_oflag[cta * 32], fbase + seg);
        }
        __syncwarp();
        bar_sync(4, 160);
        if (lane == 0) {
          fence_async();
          tma_store(&tm.o, sb + A_OST, cta * DH, seg * 32);
          tma_store(&tm.o, sb + A_OST + 4096, cta * DH + 64, seg * 32);
          asm volatile("cp.async.bulk.commit_group;" ::: "memory");
          asm volatile("cp.async.bulk.wait_group.read 0;" ::: "memory");
        }
        __syncwarp();
      }
      if (lane == 0) {
        asm volatile("cp.async.bulk.wait_group 0;" ::: "memory");
        stg_relaxed32(&g_oflag[cta * 32], fbase + NSEG);
      }
    }
    if (w >= 2 && cta < NH) {
      const bool qk = w == 2;
      const uint32_t full = qk ? fullq : fullv, ktag = (epoch + 1) & 1;
      const uint32_t ma = sb + A_IN + 8192 + (qk ? lane * 16 : 2 * SEGB + (lane >> 4) * 1024 + (lane & 15) * 16);
      int avail = 0;
      uint32_t pace = 0;
      if (qk) bar_sync(10, 64);
#pragma unroll 1
      for (int seg = 0; seg < ((XP & 2048) ? 0 : NSEG); seg++) {
        if (seg >= avail) avail = wait_flags(&g_sflag[(cta * 3 + (qk ? lane & 1 : 2)) * 8], true, fbase, seg);
        if ((QM & 8) && seg < NSEG - 2 && avail <= seg + QB) quiet_wait(pace);
        const unsigned char* km = g_km + (size_t)(seg * NH + cta) * 4096 + (qk ? lane * 8 : 2048 + lane * 16);
        uint32_t m[16];
        auto fetch = [&]() { if (qk) ldg8x64<256>(m, km); else ldg4x128<512>(m, km); };
        const float g = qk ? __ldcg(&g_gate[seg * 32 + lane]) : 0.f;
        fetch();
        mbar_wait(qk ? emptyq : emptyv, (seg & 1) ^ 1);
        const unsigned char* src = g_seg + ((size_t)(seg & RING) * 96 + cta * 3) * 8192;
        if (lane == 0) mbar_expect(full, qk ? 16384 : 8192);
        __syncwarp();
        if (lane < (qk ? 2 : 1)) bulk_load(sb + A_IN + (qk ? lane : 2) * SEGB, src + (qk ? lane : 2) * 8192, 8192, full);
        int n = 0;
#pragma unroll 1
        while ((qk ? stale<8, 2>(m, ktag) : stale<4, 4>(m, ktag)) && ++n < SPIN_LIMIT) fetch();
#pragma unroll
        for (int i = 0; i < 4; i++) stsm4(ma + (qk ? (i >> 1) * SEGB + (i & 1) * 512 : i * 256), m[4 * i], m[4 * i + 1], m[4 * i + 2], m[4 * i + 3]);
        if (qk) sts32(sb + A_G + lane * 4, __float_as_uint(1.f - g));
        fence_async();
        __syncwarp();
        if (lane == 0) mbar_arrive(full);
      }
    }
    if (w != 0) return;
    const bool lead = lane == 0;
    uint32_t pace = 0;
    if (lead) {
      for (int it = 0; it < ((XP & 256) ? 0 : 36); it++) {
        const int st = it % A_ST, tile = (it / 9) * NAUX + cta, k = it % 9;
        if (it >= A_ST) mbar_wait(empty1 + 8 * st, (it / A_ST - 1) & 1);
        if (QM & 1) quiet_wait(pace);
        mbar_expect(full1 + 8 * st, A_STAGE);
        tma_load(sb + st * A_STAGE, &tm.x, k * 64, (tile / 9) * 128, full1 + 8 * st);
        for (int j = 0; j < 3; j++) tma_load(sb + st * A_STAGE + 16384 + j * 8192, &tm.wa, (tile % 9) * 192 + j * 64, k * 64, full1 + 8 * st);
      }
    }
    __syncwarp(); bar_sync(6, 288);
    bar_sync(8, 64);
    if (lead) { aux_barrier(0, epoch); if (cta == 0) *(volatile unsigned*)&g_epoch2 = epoch + 1; }
    __syncwarp(); bar_sync(6, 288);
    __syncwarp(); bar_sync(6, 288);
    if (lead) mbar_expect(fullw, (18 + (p3_ks(0) == 7) + (p3_ks(1) == 7)) * 8192);
    __syncwarp();
    if (lane < 20) {
      const int g = lane >= 10, k = lane - 10 * g, kb = p3_ks(g) * 9 + k;
      if (k < 9 || kb == 72) {
        const uint32_t dst = sb + (k < 9 ? (g * 9 + k) * 8192 : A_XW + g * 8192);
        if (kb < 64) tma_load(dst, &tm.wob, p3_mt(g) * 64, kb * 64, fullw);
        else tma_load(dst, &tm.woa, p3_mt(g) * 64, (kb - 64) * 64, fullw);
      }
    }
    __syncwarp();
    if (lead) aux_barrier(1, epoch);
    __syncwarp(); bar_sync(6, 288);
    {
      int avail = 0;
      const int h = (9 * p3_ks(0) >> 1) + lane;
#pragma unroll 1
      for (int seg = 0; seg < ((XP & 2048) ? 0 : NSEG); seg++) {
        if (seg >= avail) avail = wait_flags(&g_oflag[min(h, NH - 1) * 32], lane < (wide ? 5 : 9), fbase, seg);
        SSTAMP(seg, 4);
        for (int g = 0; g < (wide ? 1 : 2); g++) {
          const int sl = wide ? seg & 3 : (seg & 1) * 2 + g, ks = p3_ks(g);
          mbar_wait(empty3 + 8 * sl, ((seg >> (wide ? 2 : 1)) & 1) ^ 1);
          if ((QM & 4) && seg < NSEG - 3 && avail <= seg + QB) quiet_wait(pace);
          if (lead) {
            mbar_expect(full3 + 8 * sl, XT + (ks == 7 ? 4096 : 0));
            asm volatile("cp.async.bulk.tensor.3d.shared::cluster.global.mbarrier::complete_tx::bytes [%0], [%1, {%3, %4, %5}], [%2];"
                         :: "r"(sb + sl * XT), "l"(&tm.o3), "r"(full3 + 8 * sl), "r"(0), "r"(seg * 32), "r"(ks * 9) : "memory");
            if (ks == 7) tma_load(sb + A_XT + sl * 4096, &tm.o, 72 * 64, seg * 32, full3 + 8 * sl);
          }
          __syncwarp();
        }
      }
    }
    __syncwarp(); bar_sync(6, 288);
    asm volatile("griddepcontrol.wait;" ::: "memory");
  } else if (wg == 2) {
    asm volatile("setmaxnreg.dec.sync.aligned.u32 72;");
    if (cta < NH) {
#pragma unroll 4
      for (int u = 0; u < 16; u++) {
        const int tok = cta * 64 + w * 16 + u;
        float dot = 0.f;
#pragma unroll
        for (int j = 0; j < 9; j++) {
          const uint32_t a = ((const uint32_t*)x)[tok * (DM / 2) + j * 32 + lane], g = ((const uint32_t*)gate_w)[j * 32 + lane];
          dot += bf_lo(a) * bf_lo(g) + bf_hi(a) * bf_hi(g);
        }
        dot = warp_sum(dot);
        if (lane == 0) g_gate[tok] = 1.f / (1.f + __expf(-dot));
      }
    }
    bar_sync(3, 128);
    if (tid == 256) aux_barrier(2, epoch);
    __syncwarp();
    bar_sync(3, 128);
    if (w == 0) bar_arrive(8, 64);
    if (w == 1 && cta < NH) bar_arrive(10, 64);
    if (cta < NH) {
      const uint64_t qd = make_desc(sb + A_IN, 128, 1024, 0);
      CDECL;
#pragma unroll 1
      for (int seg = 0; seg < ((XP & 2048) ? 0 : NSEG); seg++) {
        CSTAMP(0);
        mbar_wait(fullq, seg & 1);
        CSTAMP(3);
        SSTAMP(seg, 0);
        float d[2][16];
        {
          float a[20];
          WG_FENCE();
#pragma unroll
          for (int k = 0; k < 8; k++) wgmma_n40_ss(a, qd + ((k >> 2) * SEGB + (k & 3) * 256 >> 4), qd + ((k >> 2) * SEGB + (k & 3) * 256 + 4096 >> 4), k > 0);
          const uint32_t ga = sb + A_G + (w & 1) * 64 + (lane >> 2) * 4;
          const float f0 = __uint_as_float(lds32(ga)), f1 = __uint_as_float(lds32(ga + 32));
          WG_COMMIT();
          WG_WAIT(0);
          CSTAMP(5);
          if (lane == 0 && f0 + f1 != 4.f) mbar_arrive(emptyq);
          SSTAMP(seg, 1);
          if (w < 2) {
            const int lim = w * 16 + (lane >> 2) - 2 * (lane & 3);
            float m0 = -3.0e38f, m1 = -3.0e38f;
#pragma unroll
            for (int i = 0; i < 20; i++) {
              a[i] *= SM_SCALE * LOG2E;
              if (i < 16 && (i >> 2) * 8 + (i & 1) - (i & 2) * 4 > lim) a[i] = -1.0e9f * LOG2E;
              if (i & 2) m1 = fmaxf(m1, a[i]); else m0 = fmaxf(m0, a[i]);
            }
#pragma unroll
            for (int o = 1; o < 4; o <<= 1) { m0 = fmaxf(m0, __shfl_xor_sync(0xffffffffu, m0, o)); m1 = fmaxf(m1, __shfl_xor_sync(0xffffffffu, m1, o)); }
            float s0 = 0.f, s1 = 0.f;
#pragma unroll
            for (int i = 0; i < 20; i++) { a[i] = ex2(a[i] - (i & 2 ? m1 : m0)); if (i & 2) s1 += a[i]; else s0 += a[i]; }
#pragma unroll
            for (int o = 1; o < 4; o <<= 1) { s0 += __shfl_xor_sync(0xffffffffu, s0, o); s1 += __shfl_xor_sync(0xffffffffu, s1, o); }
            s0 = f0 * rcp(s0); s1 = f1 * rcp(s1);
            uint32_t p[10];
#pragma unroll
            for (int i = 0; i < 10; i++) p[i] = pack_bf16(a[2 * i] * (i & 1 ? s1 : s0), a[2 * i + 1] * (i & 1 ? s1 : s0));
            const uint32_t pa = sb + A_P + (2 * w + ((lane >> 3) & 1)) * 768 + (lane >> 4) * 128 + (lane & 7) * 16;
            stsm4t(pa, p[0], p[1], p[2], p[3]); stsm4t(pa + 256, p[4], p[5], p[6], p[7]); stsm4t(pa + 512, p[8], p[9], 0, 0);
            CSTAMP(6);
            fence_async();
            CSTAMP(7);
          }
        }
        CSTAMP(8);
        mbar_wait(fullv, seg & 1);
        CSTAMP(9);
        bar_sync(5, 160);
        CSTAMP(10);
        SSTAMP(seg, 2);
        const uint64_t pd = make_desc(sb + A_P, 128, 768, 0), vd = make_desc(sb + A_IN + 2 * SEGB, 128, 512, 0), md = make_desc(sb + A_IN + 2 * SEGB + 8192, 0, 128, 0);
        WG_FENCE();
#pragma unroll
        for (int i = 0; i < 2; i++) {
          wgmma_n32_ss<0>(d[i], vd + i * 256, pd, 0);
          wgmma_n32_ss<0>(d[i], vd + i * 256 + 16, pd + 16, 1);
          wgmma_n32_ss<0>(d[i], md + i * 64, pd + 32, 1);
        }
        WG_COMMIT();
        WG_WAIT(0);
        CSTAMP(11);
        if (lane == 0) mbar_arrive(emptyv);
#pragma unroll
        for (int i = 0; i < 2; i++) {
          const uint32_t oa = sb + A_OST + i * 4096 + ((lane & 7) + ((lane >> 4) << 3)) * 128 + (((2 * w + ((lane >> 3) & 1)) ^ (lane & 7)) << 4);
          stsm4t(oa, pack_bf16(d[i][0], d[i][1]), pack_bf16(d[i][2], d[i][3]), pack_bf16(d[i][4], d[i][5]), pack_bf16(d[i][6], d[i][7]));
          stsm4t(oa + 2048, pack_bf16(d[i][8], d[i][9]), pack_bf16(d[i][10], d[i][11]), pack_bf16(d[i][12], d[i][13]), pack_bf16(d[i][14], d[i][15]));
        }
        CSTAMP(12);
        bar_sync(4, 160);
        SSTAMP(seg, 3);
      }
      CDUMP;
    }
  } else {
    asm volatile("setmaxnreg.inc.sync.aligned.u32 200;");
    {
    float acc[96];
#pragma unroll 1
    for (int t = 0; t < ((XP & 256) ? 0 : 4); t++) {
#pragma unroll 1
      for (int k = 0; k < 9; k++) {
        const int it = t * 9 + k, st = it % A_ST;
        mbar_wait(full1 + 8 * st, (it / A_ST) & 1);
        const uint64_t da = make_desc(sb + st * A_STAGE + wg * 8192, 16, 1024, 1);
        const uint64_t db = make_desc(sb + st * A_STAGE + 16384, 8192, 1024, 1);
        WG_FENCE();
#pragma unroll
        for (int j = 0; j < 4; j++) wgmma_n192_ss_nt(acc, da + j * 2, db + j * 128, (k | j) != 0);
        WG_COMMIT();
        WG_WAIT(1);
        if (k > 0 && lane == 0) mbar_arrive(empty1 + 8 * ((it - 1) % A_ST));
      }
      WG_WAIT(0);
      ASTAMP(16 + t);
      if (lane == 0) mbar_arrive(empty1 + 8 * ((t * 9 + 8) % A_ST));
      if ((tid & 127) == 0) asm volatile("cp.async.bulk.wait_group.read 0;" ::: "memory");
      bar_sync(1 + wg, 128);
      const uint32_t sa = sb + A_STG + wg * 24576 + (w * 16 + (lane & 15)) * 128;
#pragma unroll
      for (int n = 0; n < 12; n++)
        stsm4(sa + (n >> 2) * 8192 + ((((n & 3) * 2 + (lane >> 4)) ^ (lane & 7)) << 4), pack_bf16(acc[8 * n], acc[8 * n + 1]),
              pack_bf16(acc[8 * n + 2], acc[8 * n + 3]), pack_bf16(acc[8 * n + 4], acc[8 * n + 5]), pack_bf16(acc[8 * n + 6], acc[8 * n + 7]));
      fence_async();
      bar_sync(1 + wg, 128);
      if ((tid & 127) == 0) {
        const int tile = t * NAUX + cta;
        for (int j = 0; j < 3; j++) tma_store(&tm.qst, sb + A_STG + wg * 24576 + j * 8192, (tile % 9) * 192 + j * 64, (tile / 9) * 128 + wg * 64);
        asm volatile("cp.async.bulk.commit_group;" ::: "memory");
      }
    }
    if ((tid & 127) == 0) { asm volatile("cp.async.bulk.wait_group 0;" ::: "memory"); asm volatile("fence.proxy.async;" ::: "memory"); }
    }
    ASTAMP(1);
    bar_sync(6, 288);
    bar_sync(6, 288);
    {
    const uint32_t buf = sb + wg * A_CHUNK;
#pragma unroll 1
    for (int i = 0; i < 2; i++) {
      const int c = (2 * i + wg) * NAUX + cta;
      if (c >= S_LEN / 16 || (XP & 256)) break;
      const int r0 = max(c * 16 - 14, 0);
      if (w < 2) {
        uint32_t pace = 0;
        if (QM & 2) quiet_wait(pace);
        const int nkv = c * 16 + 16 - r0;
        if ((tid & 127) == 0) mbar_expect(full2 + 8 * wg, nkv * A_KV + 16 * DM * 2);
        if (lane < (w ? 16 : nkv))
          asm volatile("cp.async.bulk.shared::cluster.global.mbarrier::complete_tx::bytes [%0], [%1], %2, [%3];"
                       :: "r"(buf + (w ? A_Q + lane * DM * 2 : lane * A_KV)), "l"(g_qkvA + (size_t)((w ? c * 16 : r0) + lane) * 3 * DM + (w ? 0 : DM)),
                          "r"(w ? DM * 2 : A_KV), "r"(full2 + 8 * wg) : "memory");
        __syncwarp();
      }
      const int tok0 = c * 16 + (w >> 1) * 8 + (w & 1);
      const uint32_t qa = buf + A_Q + lane * 36 + (tok0 - c * 16) * DM * 2;
      uint32_t ra[11];
#pragma unroll
      for (int r = 0; r < 11; r++) ra[r] = buf + lane * 36 + (max(tok0 - 14 + 2 * r, 0) - r0) * A_KV;
      float l[4][8];
#pragma unroll
      for (int u = 0; u < 4; u++)
#pragma unroll
        for (int k = 0; k < 8; k++) l[u][k] = 0.f;
      mbar_wait(full2 + 8 * wg, i);
      if (i == 0) ASTAMP(2);
      const unsigned char* const sp = smem_raw - sb;
#pragma unroll 1
      for (int j = 0; j < 36; j += 4) {
        uint32_t qw[4], kw[11];
#pragma unroll
        for (int u = 0; u < 4; u++) qw[u] = *(const uint32_t*)(sp + qa + u * A_KV + j);
#pragma unroll
        for (int r = 0; r < 11; r++) kw[r] = *(const uint32_t*)(sp + ra[r] + j);
#pragma unroll
        for (int u = 0; u < 4; u++)
#pragma unroll
          for (int k = 0; k < 8; k++) l[u][k] = fmaf(bf_hi(qw[u]), bf_hi(kw[u + k]), fmaf(bf_lo(qw[u]), bf_lo(kw[u + k]), l[u][k]));
      }
#pragma unroll
      for (int u = 0; u < 4; u++) {
        float m = -3.0e38f, sum = 0.f;
#pragma unroll
        for (int k = 0; k < 8; k++) { l[u][k] = tok0 - 14 + 2 * (u + k) >= 0 ? l[u][k] * 0.23570226039551584f : -1.0e9f; m = fmaxf(m, l[u][k]); }
#pragma unroll
        for (int k = 0; k < 8; k++) { l[u][k] = ex2((l[u][k] - m) * LOG2E); sum += l[u][k]; }
        const float f = __ldcg(&g_gate[tok0 + 2 * u]) * rcp(sum);
#pragma unroll
        for (int k = 0; k < 8; k++) l[u][k] *= f;
      }
#pragma unroll 1
      for (int j = 0; j < 36; j += 4) {
        uint32_t vw[11];
#pragma unroll
        for (int r = 0; r < 11; r++) vw[r] = *(const uint32_t*)(sp + ra[r] + DM * 2 + j);
#pragma unroll
        for (int u = 0; u < 4; u++) {
          float o0 = 0.f, o1 = 0.f;
#pragma unroll
          for (int k = 0; k < 8; k++) { o0 = fmaf(l[u][k], bf_lo(vw[u + k]), o0); o1 = fmaf(l[u][k], bf_hi(vw[u + k]), o1); }
          sts32(qa + u * A_KV + j, pack_bf16(o0, o1));
        }
      }
      fence_async();
      __syncwarp();
      if (lane < 4) {
        asm volatile("cp.async.bulk.global.shared::cta.bulk_group [%0], [%1], %2;"
                     :: "l"(g_Ocat + (size_t)(tok0 + 2 * lane) * KCAT + 4096), "r"(buf + A_Q + (tok0 + 2 * lane - c * 16) * DM * 2), "r"(DM * 2) : "memory");
        asm volatile("cp.async.bulk.commit_group;" ::: "memory");
        asm volatile("cp.async.bulk.wait_group.read 0;" ::: "memory");
      }
      bar_sync(1 + wg, 128);
    }
    asm volatile("cp.async.bulk.wait_group 0;" ::: "memory");
    }
    ASTAMP(3);
    bar_sync(6, 288);
    uint32_t wa[36][4];
    mbar_wait(fullw, 0);
    const uint32_t la = sb + wg * 73728 + ((lane & 7) + ((lane >> 4) << 3)) * 128 + (((2 * w + ((lane >> 3) & 1)) ^ (lane & 7)) << 4);
#pragma unroll
    for (int k = 0; k < 36; k++) ldsm4t(wa[k], la + k * 2048);
    fence_async();
    bar_sync(6, 288);
    ASTAMP(4);
    const int ks = p3_ks(wg), mt = p3_mt(wg);
    uint32_t v[16];
    auto fetch = [&](int seg) { ldg8x64<1024>(v, g_part + (((seg & 7) * 9 + mt) * 4 + (ks & 3)) * 1024 + (tid & 127)); };
    auto finish = [&](int seg) {
      const uint32_t tagv = (~seg >> 3) & 1;
      int n = 0;
#pragma unroll 1
      while (stale<8, 2>(v, tagv) && ++n < SPIN_LIMIT) {
        if (seg < NSEG - 2) __nanosleep(100);
        fetch(seg);
      }
      float own[4] = {bf_lo(v[0]), bf_hi(v[0]), bf_lo(v[1]), bf_hi(v[1])};
#pragma unroll
      for (int j = 1; j < 8; j++) { own[0] += bf_lo(v[2 * j]); own[1] += bf_hi(v[2 * j]); own[2] += bf_lo(v[2 * j + 1]); own[3] += bf_hi(v[2 * j + 1]); }
      uint32_t p0 = pack_bf16(own[0], own[1]), p1 = pack_bf16(own[2], own[3]);
      asm volatile("movmatrix.sync.aligned.m8n8.trans.b16 %0, %0;" : "+r"(p0));
      asm volatile("movmatrix.sync.aligned.m8n8.trans.b16 %0, %0;" : "+r"(p1));
      uint32_t* o = (uint32_t*)(out + (size_t)(seg * 32 + (ks & 3) * 8 + (lane >> 2)) * DM + mt * 64 + w * 16) + (lane & 3);
      o[0] = p0; o[4] = p1;
      SSTAMP(seg, 7);
    };
    float acc[16];
#pragma unroll
    for (int i = 0; i < 16; i++) acc[i] = 0.f;
    int pend = -1;
    if (PING && wg) bar_arrive(1, 256);
    CDECL;
#pragma unroll 1
    for (int seg = 0; seg < ((XP & 2048) ? 0 : NSEG); seg++) {
      const int sl = wide ? seg & 3 : (seg & 1) * 2 + wg;
      CSTAMP(0);
      const bool fin = pend >= 0 && seg - pend >= FLAG;
      if (FPOS == 0 && fin) fetch(pend);
      mbar_wait(full3 + 8 * sl, (seg >> (wide ? 2 : 1)) & 1);
      if (FPOS == 1 && fin) fetch(pend);
      CSTAMP(1);
      if (wg) SSTAMP(seg, 5);
      if (PING) bar_sync(1 + wg, 256);
      const uint64_t db = make_desc(sb + sl * XT, 16, 1024, 1);
      WG_FENCE();
#pragma unroll
      for (int k = 0; k < ((XP & 1024) ? 1 : 36); k++) wgmma_n32_rs(acc, wa[k][0], wa[k][1], wa[k][2], wa[k][3], db + (k >> 2) * 256 + (k & 3) * 2, k);
      {
        const uint64_t da = make_desc(sb + A_XW + wg * 8192, 8192, 1024, 1), de = make_desc(sb + A_XT + sl * 4096, 16, 1024, 1);
#pragma unroll
        for (int j = 0; j < 4; j++) wgmma_n32_ss_tn(acc, da + j * 128, de + j * 2, ks == 7);
      }
      WG_COMMIT();
      if (PING) bar_arrive(2 - wg, 256);
      CSTAMP(2);
      if (FPOS == 2 && fin) fetch(pend);
      CSTAMP(3);
      WG_WAIT(0);
      CSTAMP(4);
      if (wg) SSTAMP(seg, 6);
      if (lane == 0) mbar_arrive(empty3 + 8 * sl);
      uint2* dst = g_part + (((seg & 7) * 9 + mt) * 32 + ks) * 128 + (tid & 127);
      uint32_t q[8];
#pragma unroll
      for (int j = 0; j < 8; j++) q[j] = j & 1 ? pack_bf16(acc[2 * j], acc[2 * j + 1]) : (pack_bf16(acc[2 * j], acc[2 * j + 1]) & ~1u) | ((~seg >> 3) & 1);
      asm volatile("st.relaxed.gpu.global.v2.b32 [%0], {%1,%2};\nst.relaxed.gpu.global.v2.b32 [%0 + 8192], {%3,%4};\n"
                   "st.relaxed.gpu.global.v2.b32 [%0 + 16384], {%5,%6};\nst.relaxed.gpu.global.v2.b32 [%0 + 24576], {%7,%8};"
                   :: "l"(dst), "r"(q[0]), "r"(q[1]), "r"(q[2]), "r"(q[3]), "r"(q[4]), "r"(q[5]), "r"(q[6]), "r"(q[7]) : "memory");
      CSTAMP(5);
      if (fin) { finish(pend); pend = -1; }
      CSTAMP(6);
      if ((seg & 1) == ks >> 2) pend = seg;
      if (wg && (seg & 7) == 6) ASTAMP(5 + (seg >> 3));
    }
    if (PING && !wg) bar_sync(1, 256);
    if (pend >= 0) { fetch(pend); finish(pend); }
    CDUMP;
    ASTAMP(13);
    bar_sync(6, 288);
  }
}

typedef CUresult (*EncodeFn)(CUtensorMap*, CUtensorMapDataType, cuuint32_t, void*, const cuuint64_t*, const cuuint64_t*,
                             const cuuint32_t*, const cuuint32_t*, CUtensorMapInterleave, CUtensorMapSwizzle,
                             CUtensorMapL2promotion, CUtensorMapFloatOOBfill);
#define PROMO 2
static void make_map(EncodeFn enc, CUtensorMap* m, const void* p, int rows, int cols, int box_rows) {
  cuuint64_t dims[2] = {(cuuint64_t)cols, (cuuint64_t)rows};
  cuuint64_t strides[1] = {(cuuint64_t)cols * 2};
  cuuint32_t box[2] = {64, (cuuint32_t)box_rows};
  cuuint32_t es[2] = {1, 1};
  enc(m, CU_TENSOR_MAP_DATA_TYPE_BFLOAT16, 2, (void*)p, dims, strides, box, es, CU_TENSOR_MAP_INTERLEAVE_NONE,
      CU_TENSOR_MAP_SWIZZLE_128B, (CUtensorMapL2promotion)PROMO, CU_TENSOR_MAP_FLOAT_OOB_FILL_NONE);
}

constexpr int g_poll = POLL_NS;
extern "C" void kernel_launch(void* const* d_in, const int* in_sizes, int n_in, void* d_out, int out_size) {
  const bf16* x = (const bf16*)d_in[0];
  const bf16* wqkvA = (const bf16*)d_in[1];
  const bf16* woA = (const bf16*)d_in[2];
  const bf16* mem0 = (const bf16*)d_in[4];
  const bf16* Wq = (const bf16*)d_in[5];
  const bf16* Wk = (const bf16*)d_in[6];
  const bf16* Wv = (const bf16*)d_in[7];
  const bf16* Wo = (const bf16*)d_in[8];
  const bf16* gate_w = (const bf16*)d_in[10];
  static EncodeFn enc = nullptr;
  static void *pO = nullptr, *pQ = nullptr, *pR = nullptr;
  if (!enc) {
    cudaDriverEntryPointQueryResult qr;
    cudaGetDriverEntryPoint("cuTensorMapEncodeTiled", (void**)&enc, cudaEnableDefault, &qr);
    cudaGetSymbolAddress(&pO, g_Ocat);
    cudaGetSymbolAddress(&pQ, g_qkvA);
    cudaGetSymbolAddress(&pR, g_red_raw);
    cudaFuncSetAttribute(rec_kernel, cudaFuncAttributeMaxDynamicSharedMemorySize, SM_TOTAL);
    cudaFuncSetAttribute(aux_kernel, cudaFuncAttributeMaxDynamicSharedMemorySize, A_TOTAL);
  }
  RMaps rm;
  rm.poll = g_poll;
  rm.w[0] = (const unsigned char*)Wk; rm.w[1] = (const unsigned char*)Wq; rm.w[2] = (const unsigned char*)Wv; rm.w[3] = (const unsigned char*)Wo;
  rm.red = (unsigned char*)(((uintptr_t)pR + 262143) & ~(uintptr_t)262143);
  {
    cuuint64_t dims[3] = {64, S_LEN, 9}, strides[2] = {DM * 2, 128};
    cuuint32_t box[3] = {64, 32, 9}, es[3] = {1, 1, 1};
    enc(&rm.x, CU_TENSOR_MAP_DATA_TYPE_BFLOAT16, 3, (void*)x, dims, strides, box, es, CU_TENSOR_MAP_INTERLEAVE_NONE,
        CU_TENSOR_MAP_SWIZZLE_128B, CU_TENSOR_MAP_L2_PROMOTION_L2_128B, CU_TENSOR_MAP_FLOAT_OOB_FILL_NONE);
  }
  make_map(enc, &rm.wq, Wq, DM, 4096, 192);
  make_map(enc, &rm.wk, Wk, DM, 4096, 192);
  make_map(enc, &rm.wv, Wv, DM, 4096, 192);
  make_map(enc, &rm.wo, Wo, 4096, DM, 128);
  AMaps am;
  make_map(enc, &am.x, x, S_LEN, DM, 128);
  make_map(enc, &am.wa, wqkvA, DM, 3 * DM, 64);
  make_map(enc, &am.qst, pQ, S_LEN, 3 * DM, 64);
  {
    cuuint64_t dims[3] = {64, S_LEN, KCAT / 64}, strides[2] = {KCAT * 2, 128};
    cuuint32_t box[3] = {64, 32, 9}, es[3] = {1, 1, 1};
    make_map(enc, &am.o, pO, S_LEN, KCAT, 32);
    enc(&am.o3, CU_TENSOR_MAP_DATA_TYPE_BFLOAT16, 3, pO, dims, strides, box, es, CU_TENSOR_MAP_INTERLEAVE_NONE,
        CU_TENSOR_MAP_SWIZZLE_128B, CU_TENSOR_MAP_L2_PROMOTION_L2_128B, CU_TENSOR_MAP_FLOAT_OOB_FILL_NONE);
  }
  make_map(enc, &am.wob, Wo, 4096, DM, 64);
  make_map(enc, &am.woa, woA, DM, DM, 64);

  rec_kernel<<<96, 384, SM_TOTAL, cudaStreamPerThread>>>(rm, x, mem0);
  cudaLaunchConfig_t cfg = {};
  cfg.gridDim = dim3(NAUX); cfg.blockDim = dim3(512); cfg.dynamicSmemBytes = A_TOTAL; cfg.stream = cudaStreamPerThread;
  cudaLaunchAttribute at[1];
  at[0].id = cudaLaunchAttributeProgrammaticStreamSerialization; at[0].val.programmaticStreamSerializationAllowed = 1;
  cfg.attrs = at; cfg.numAttrs = 1;
  if (XP & 16) cfg.numAttrs = 0;
  if (!(XP & 64)) cudaLaunchKernelEx(&cfg, aux_kernel, am, x, gate_w, (bf16*)d_out);
}
```

```cpp
#include <cuda_runtime.h>
#include <cuda_bf16.h>
#include <cuda_fp16.h>
#include <cuda.h>
#include <stdint.h>

typedef __nv_bfloat16 bf16;

constexpr int S_LEN = 2048, DM = 576, NH = 32, DH = 128, NSEG = 64, KCAT = 4096 + 576;
#define RED_LINE(i) (((i) >> 2) * 4096 + ((i) & 1) * 256 + ((i) & 2) * 512)
#define RED_SLOT(s) (((s) & 1) * 128 + ((s) & 2) * 256)

#define POLL_NS 896
#define NII 18
#define W3PRE 4
#define W3MID 4
#define GF 0
#define B5POS 0
#define NUP 4
#define UPF 1
#define B3Q 9
#define B3F 0
#define GATE 7
#define NTL 2
#define B7R 1
#define EXPOS 0
#define VW2 1
#define CLR 1
#define RFW 0
#define NIC 0
#define LEAD 0
#define FIN16 1
#define VXG 0
#define RING 63
#define EXB 0
#define EXD 0
#define EXB2 8192
#define HDLY 0
#define F10 1
#define NPROBE 2
#define NPROBE2 5
#define WPOS 2
#define WARM 0
#define YP 0
#define QM 60
#define N5 224
#define KP(i) (((i) >> 1) + 4 * ((i) & 1))
#define SPIN_LIMIT (1 << 14)
#define XP 0

__device__ __align__(1024) bf16 g_Ocat[S_LEN * KCAT];
__device__ __align__(1024) unsigned char g_red_raw[2 * 262144];
constexpr int HINT_OFF = 2048;
__device__ __align__(16) float g_gate[S_LEN];
__device__ __align__(128) uint4 g_stats[96 * 2];
__device__ unsigned g_epoch;
__device__ unsigned g_epoch2;
__device__ unsigned g_oflag[NH * 32];
__device__ unsigned g_abar[3 * 32];
__device__ unsigned g_sflag[96 * 8];
__device__ __align__(1024) unsigned char g_seg[NSEG * 96 * 8192];
__device__ __align__(1024) unsigned char g_km[NSEG * NH * 4096];
__device__ __align__(1024) uint2 g_part[8 * 9 * 4 * 8 * 128];
__device__ int g_err;
#define SSTAMP(seg, idx)
#define QSTAMP(idx)
#define PROF(idx)
#define PROFP(idx)
#define STAMP(idx)
#define ASTAMP(idx)
#define WSTAMP(idx)

#define CSTAMP(idx)
#define CDECL
#define CDUMP
#define DI __device__ __forceinline__
DI uint32_t smem_u32(const void* p) { return (uint32_t)__cvta_generic_to_shared(p); }
DI uint32_t clock32() { uint32_t c; asm volatile("mov.u32 %0, %%clock;" : "=r"(c) :: "memory"); return c; }
DI uint32_t gtime() { uint32_t c; asm volatile("mov.u32 %0, %%globaltimer_lo;" : "=r"(c) :: "memory"); return c; }
DI uint32_t ldg_relaxed32(const void* p) { uint32_t v; asm volatile("ld.relaxed.gpu.global.b32 %0, [%1];" : "=r"(v) : "l"(p) : "memory"); return v; }
DI uint32_t ldg_acquire32(const void* p) { uint32_t v; asm volatile("ld.acquire.gpu.global.b32 %0, [%1];" : "=r"(v) : "l"(p) : "memory"); return v; }
DI void stg_relaxed32(void* p, uint32_t v) { asm volatile("st.relaxed.gpu.global.b32 [%0], %1;" :: "l"(p), "r"(v) : "memory"); }
DI int head_id() { int c; asm volatile("mov.u32 %0, %%clusterid.x;" : "=r"(c)); return c; }
DI uint32_t mapa(uint32_t a, uint32_t r) { uint32_t o; asm("mapa.shared::cluster.u32 %0, %1, %2;" : "=r"(o) : "r"(a), "r"(r)); return o; }
DI void cluster_arrive() { asm volatile("barrier.cluster.arrive.relaxed.aligned;" ::: "memory"); }
DI void cluster_wait() { asm volatile("barrier.cluster.wait.aligned;" ::: "memory"); }
DI void cluster_sync() { asm volatile("barrier.cluster.arrive.release.aligned;\nbarrier.cluster.wait.acquire.aligned;" ::: "memory"); }
DI void mbar_init(uint32_t b, uint32_t c) { asm volatile("mbarrier.init.shared::cta.b64 [%0], %1;" :: "r"(b), "r"(c) : "memory"); }
DI void mbar_expect(uint32_t b, uint32_t tx) { asm volatile("mbarrier.arrive.expect_tx.shared::cta.b64 _, [%0], %1;" :: "r"(b), "r"(tx) : "memory"); }
DI void mbar_arrive(uint32_t b) { asm volatile("mbarrier.arrive.shared::cta.b64 _, [%0];" :: "r"(b) : "memory"); }
DI void mbar_wait(uint32_t b, uint32_t par) {
  asm volatile("{\n.reg .pred p;\n.reg .u32 n, q;\nmov.u32 n, 0;\n"
               "WL: add.u32 n, n, 1;\nshr.u32 q, n, 12;\nxor.b32 q, q, %1;\n"
               "mbarrier.try_wait.parity.shared::cta.b64 p, [%0], q;\n@!p bra.uni WL;\n}"
               :: "r"(b), "r"(par) : "memory");
}
DI void wait_until(uint32_t t) {
  const uint32_t now = gtime();
  t = min(t, now + 8192);
  asm volatile("{\n.reg .pred p;\n.reg .u32 c;\nTL: mov.u32 c, %%globaltimer_lo;\nsetp.lt.u32 p, c, %0;\n@p bra.uni TL;\n}" :: "r"(t) : "memory");
}
#define PIN(v) v = __shfl_xor_sync(0xffffffffu, v, 0)
#define SCHED_FENCE(k) asm volatile("{\n.reg .pred p;\nsetp.eq.u32 p, %0, %1;\n@p exit;\n}" :: "r"(fence_reg), "r"(k) : "memory")
#define MEM_ORDER(k) asm volatile("{\n.reg .pred p;\nsetp.eq.u32 p, %0, %1;\n@p st.shared.u32 [%0], %0;\n}" :: "r"(fence_reg), "r"(k + 64) : "memory")
DI void bar_sync(int id, int n) { asm volatile("bar.sync %0, %1;" :: "r"(id), "r"(n) : "memory"); }
DI void bar_arrive(int id, int n) { asm volatile("bar.arrive %0, %1;" :: "r"(id), "r"(n) : "memory"); }
DI void fence_async() { asm volatile("fence.proxy.async.shared::cta;" ::: "memory"); }
DI void st_async4(uint32_t a, uint32_t x, uint32_t y, uint32_t z, uint32_t w, uint32_t mb) {
  asm volatile("st.async.weak.shared::cluster.mbarrier::complete_tx::bytes.v4.b32 [%0], {%1,%2,%3,%4}, [%5];"
               :: "r"(a), "r"(x), "r"(y), "r"(z), "r"(w), "r"(mb) : "memory");
}
DI void st_async2(uint32_t a, uint32_t x, uint32_t y, uint32_t mb) {
  asm volatile("st.async.weak.shared::cluster.mbarrier::complete_tx::bytes.v2.b32 [%0], {%1,%2}, [%3];"
               :: "r"(a), "r"(x), "r"(y), "r"(mb) : "memory");
}
DI void sts32(uint32_t a, uint32_t x) { asm volatile("st.shared.b32 [%0], %1;" :: "r"(a), "r"(x) : "memory"); }
DI void sts64(uint32_t a, uint32_t x, uint32_t y) { asm volatile("st.shared.v2.b32 [%0], {%1,%2};" :: "r"(a), "r"(x), "r"(y) : "memory"); }
DI void sts128(uint32_t a, uint32_t x, uint32_t y, uint32_t z, uint32_t w) {
  asm volatile("st.shared.v4.b32 [%0], {%1,%2,%3,%4};" :: "r"(a), "r"(x), "r"(y), "r"(z), "r"(w) : "memory");
}
DI uint32_t lds32(uint32_t a) { uint32_t x; asm volatile("ld.shared.b32 %0, [%1];" : "=r"(x) : "r"(a) : "memory"); return x; }
DI void lds64(uint32_t a, uint32_t& x, uint32_t& y) { asm volatile("ld.shared.v2.b32 {%0,%1}, [%2];" : "=r"(x), "=r"(y) : "r"(a) : "memory"); }
DI void lds128(uint32_t a, uint32_t* r) {
  asm volatile("ld.shared.v4.b32 {%0,%1,%2,%3}, [%4];" : "=r"(r[0]), "=r"(r[1]), "=r"(r[2]), "=r"(r[3]) : "r"(a) : "memory");
}
DI void lds128f(uint32_t a, float* r) {
  asm volatile("ld.shared.v4.f32 {%0,%1,%2,%3}, [%4];" : "=f"(r[0]), "=f"(r[1]), "=f"(r[2]), "=f"(r[3]) : "r"(a) : "memory");
}
DI void lds64f(uint32_t a, float* r) { asm volatile("ld.shared.v2.f32 {%0,%1}, [%2];" : "=f"(r[0]), "=f"(r[1]) : "r"(a) : "memory"); }
DI void ldsm4t(uint32_t* r, uint32_t a) {
  asm volatile("ldmatrix.sync.aligned.m8n8.x4.trans.shared.b16 {%0,%1,%2,%3}, [%4];"
               : "=r"(r[0]), "=r"(r[1]), "=r"(r[2]), "=r"(r[3]) : "r"(a) : "memory");
}
DI void ldsm4t_in(uint32_t* r, uint32_t a, uint32_t t) {
  asm volatile("{\n.reg .pred p;\nsetp.ne.u32 p, %5, 0;\n@p ldmatrix.sync.aligned.m8n8.x4.trans.shared.b16 {%0,%1,%2,%3}, [%4];\n}"
               : "+r"(r[0]), "+r"(r[1]), "+r"(r[2]), "+r"(r[3]) : "r"(a), "r"(t) : "memory");
}
DI void lds128_in(uint32_t* r, uint32_t a, uint32_t t) {
  asm volatile("{\n.reg .pred p;\nsetp.ne.u32 p, %5, 0;\n@p ld.shared.v4.b32 {%0,%1,%2,%3}, [%4];\n}"
               : "+r"(r[0]), "+r"(r[1]), "+r"(r[2]), "+r"(r[3]) : "r"(a), "r"(t) : "memory");
}
DI void ldsm2t_in(uint32_t* r, uint32_t a, uint32_t t) {
  asm volatile("{\n.reg .pred p;\nsetp.ne.u32 p, %3, 0;\n@p ldmatrix.sync.aligned.m8n8.x2.trans.shared.b16 {%0,%1}, [%2];\n}" : "+r"(r[0]), "+r"(r[1]) : "r"(a), "r"(t) : "memory");
}
DI void reserve2(uint32_t* r) { asm volatile("{\n.reg .u64 t;\nmov.u64 t, %%clock64;\nmov.b64 {%0, %1}, t;\n}" : "=r"(r[0]), "=r"(r[1])); }
DI void scale_sum(float& x, float& y, float s, uint32_t t) {
  asm volatile("{\n.reg .pred p;\nsetp.ne.u32 p, %2, 0;\n@p mul.f32 %0, %0, %1;\n}" : "+f"(y) : "f"(s), "r"(t));
  asm volatile("{\n.reg .pred p;\nsetp.ne.u32 p, %3, 1;\n@p fma.rn.f32 %0, %0, %1, %2;\n}" : "+f"(x) : "f"(s), "f"(y), "r"(t));
}
DI void ldsm4(uint32_t* r, uint32_t a) {
  asm volatile("ldmatrix.sync.aligned.m8n8.x4.shared.b16 {%0,%1,%2,%3}, [%4];"
               : "=r"(r[0]), "=r"(r[1]), "=r"(r[2]), "=r"(r[3]) : "r"(a) : "memory");
}
DI void st_async1(uint32_t a, uint32_t x, uint32_t mb) {
  asm volatile("st.async.weak.shared::cluster.mbarrier::complete_tx::bytes.b32 [%0], %1, [%2];" :: "r"(a), "r"(x), "r"(mb) : "memory");
}
DI void stsm4(uint32_t a, uint32_t x, uint32_t y, uint32_t z, uint32_t w) {
  asm volatile("stmatrix.sync.aligned.m8n8.x4.shared.b16 [%0], {%1,%2,%3,%4};" :: "r"(a), "r"(x), "r"(y), "r"(z), "r"(w) : "memory");
}
DI void stsm4t(uint32_t a, uint32_t x, uint32_t y, uint32_t z, uint32_t w) {
  asm volatile("stmatrix.sync.aligned.m8n8.x4.trans.shared.b16 [%0], {%1,%2,%3,%4};" :: "r"(a), "r"(x), "r"(y), "r"(z), "r"(w) : "memory");
}
DI uint32_t pack_bf16(float lo, float hi) { uint32_t r; asm("cvt.rn.bf16x2.f32 %0, %1, %2;" : "=r"(r) : "f"(hi), "f"(lo)); return r; }
DI uint32_t pack_f16(float lo, float hi) { uint32_t r; asm("cvt.rn.f16x2.f32 %0, %1, %2;" : "=r"(r) : "f"(hi), "f"(lo)); return r; }
DI float ex2(float x) { float y; asm("ex2.approx.ftz.f32 %0, %1;" : "=f"(y) : "f"(x)); return y; }
DI float rcp(float x) { float y; asm("rcp.approx.ftz.f32 %0, %1;" : "=f"(y) : "f"(x)); return y; }
DI float bf_lo(uint32_t x) { return __uint_as_float(x << 16); }
DI float bf_hi(uint32_t x) { return __uint_as_float(x & 0xffff0000u); }
DI void mma16816(float* d, const uint32_t* a, uint32_t b0, uint32_t b1) {
  asm volatile("mma.sync.aligned.m16n8k16.row.col.f32.bf16.bf16.f32 {%0,%1,%2,%3}, {%4,%5,%6,%7}, {%8,%9}, {%0,%1,%2,%3};"
               : "+f"(d[0]), "+f"(d[1]), "+f"(d[2]), "+f"(d[3]) : "r"(a[0]), "r"(a[1]), "r"(a[2]), "r"(a[3]), "r"(b0), "r"(b1));
}
DI void mma16816z(float* d, const uint32_t* a, uint32_t b0, uint32_t b1) {
  asm volatile("mma.sync.aligned.m16n8k16.row.col.f32.bf16.bf16.f32 {%0,%1,%2,%3}, {%4,%5,%6,%7}, {%8,%9}, {%10,%10,%10,%10};"
               : "=f"(d[0]), "=f"(d[1]), "=f"(d[2]), "=f"(d[3]) : "r"(a[0]), "r"(a[1]), "r"(a[2]), "r"(a[3]), "r"(b0), "r"(b1), "f"(0.f));
}
DI void mma1688z(float* d, uint32_t a0, uint32_t a1, uint32_t b0) {
  asm volatile("mma.sync.aligned.m16n8k8.row.col.f32.bf16.bf16.f32 {%0,%1,%2,%3}, {%4,%5}, {%6}, {%7,%7,%7,%7};"
               : "=f"(d[0]), "=f"(d[1]), "=f"(d[2]), "=f"(d[3]) : "r"(a0), "r"(a1), "r"(b0), "f"(0.f));
}
DI void mma1688(float* d, uint32_t a0, uint32_t a1, uint32_t b0) {
  asm volatile("mma.sync.aligned.m16n8k8.row.col.f32.bf16.bf16.f32 {%0,%1,%2,%3}, {%4,%5}, {%6}, {%0,%1,%2,%3};"
               : "+f"(d[0]), "+f"(d[1]), "+f"(d[2]), "+f"(d[3]) : "r"(a0), "r"(a1), "r"(b0));
}
DI void ldsm2t(uint32_t* r, uint32_t a) {
  asm volatile("ldmatrix.sync.aligned.m8n8.x2.trans.shared.b16 {%0,%1}, [%2];" : "=r"(r[0]), "=r"(r[1]) : "r"(a) : "memory");
}
DI uint32_t add_bf16(uint32_t a, uint32_t b) { uint32_t r; asm("add.rn.bf16x2 %0, %1, %2;" : "=r"(r) : "r"(a), "r"(b)); return r; }
DI uint32_t mul_bf16(uint32_t a, uint32_t b) { uint32_t r; asm("mul.rn.bf16x2 %0, %1, %2;" : "=r"(r) : "r"(a), "r"(b)); return r; }
DI uint64_t make_desc(uint32_t addr, uint32_t lbo, uint32_t sbo, uint32_t swz) {
  return (uint64_t)((addr & 0x3FFFF) >> 4) | ((uint64_t)(lbo >> 4) << 16) | ((uint64_t)(sbo >> 4) << 32) | ((uint64_t)swz << 62);
}
#define WG_FENCE() asm volatile("wgmma.fence.sync.aligned;" ::: "memory")
#define WG_COMMIT() asm volatile("wgmma.commit_group.sync.aligned;" ::: "memory")
#define WG_WAIT(n) asm volatile("wgmma.wait_group.sync.aligned %0;" :: "n"(n) : "memory")
#define ACC8(d, o) "+f"(d[o]), "+f"(d[o + 1]), "+f"(d[o + 2]), "+f"(d[o + 3]), "+f"(d[o + 4]), "+f"(d[o + 5]), "+f"(d[o + 6]), "+f"(d[o + 7])
DI void wgmma_n32_rs(float* d, uint32_t a0, uint32_t a1, uint32_t a2, uint32_t a3, uint64_t db, int acc) {
  asm volatile("{\n.reg .pred p;\nsetp.ne.b32 p, %21, 0;\n"
               "wgmma.mma_async.sync.aligned.m64n32k16.f32.bf16.bf16 {%0,%1,%2,%3,%4,%5,%6,%7,%8,%9,%10,%11,%12,%13,%14,%15}, "
               "{%16,%17,%18,%19}, %20, p, 1, 1, 0;\n}\n"
               : ACC8(d, 0), ACC8(d, 8) : "r"(a0), "r"(a1), "r"(a2), "r"(a3), "l"(db), "r"(acc));
}
template <int TA>
DI void wgmma_n32_ss(float* d, uint64_t da, uint64_t db, int acc) {
  asm volatile("{\n.reg .pred p;\nsetp.ne.b32 p, %18, 0;\n"
               "wgmma.mma_async.sync.aligned.m64n32k16.f32.bf16.bf16 {%0,%1,%2,%3,%4,%5,%6,%7,%8,%9,%10,%11,%12,%13,%14,%15}, "
               "%16, %17, p, 1, 1, %19, 1;\n}\n"
               : ACC8(d, 0), ACC8(d, 8) : "l"(da), "l"(db), "r"(acc), "n"(TA));
}
DI void tma_load(uint32_t dst, const CUtensorMap* m, int c0, int c1, uint32_t mb) {
  asm volatile("cp.async.bulk.tensor.2d.shared::cluster.global.mbarrier::complete_tx::bytes [%0], [%1, {%3, %4}], [%2];"
               :: "r"(dst), "l"(m), "r"(mb), "r"(c0), "r"(c1) : "memory");
}
DI void tma_load3(uint32_t dst, const CUtensorMap* m, int row, uint32_t mb) {
  asm volatile("cp.async.bulk.tensor.3d.shared::cluster.global.mbarrier::complete_tx::bytes [%0], [%1, {%3, %4, %3}], [%2];"
               :: "r"(dst), "l"(m), "r"(mb), "r"(0), "r"(row) : "memory");
}
DI bool elect_one() {
  uint32_t p;
  asm volatile("{\n.reg .pred p;\nelect.sync _|p, 0xffffffff;\nselp.u32 %0, 1, 0, p;\n}" : "=r"(p));
  return p;
}
DI void bulk_s2s(uint32_t dst, uint32_t src, uint32_t bytes, uint32_t mb) {
  asm volatile("cp.async.bulk.shared::cluster.shared::cta.mbarrier::complete_tx::bytes [%0], [%1], %2, [%3];"
               :: "r"(dst), "r"(src), "r"(bytes), "r"(mb) : "memory");
}
DI void bulk_load(uint32_t dst, const void* src, uint32_t bytes, uint32_t mb) {
  asm volatile("cp.async.bulk.shared::cluster.global.mbarrier::complete_tx::bytes [%0], [%1], %2, [%3];" :: "r"(dst), "l"(src), "r"(bytes), "r"(mb) : "memory");
}
DI void tma_prefetch(const CUtensorMap* m, int c0, int c1) {
  asm volatile("cp.async.bulk.prefetch.tensor.2d.L2.global.tile [%0, {%1, %2}];" :: "l"(m), "r"(c0), "r"(c1) : "memory");
}
DI void tma_store(const CUtensorMap* m, uint32_t src, int c0, int c1) {
  asm volatile("cp.async.bulk.tensor.2d.global.shared::cta.bulk_group [%0, {%2, %3}], [%1];" :: "l"(m), "r"(src), "r"(c0), "r"(c1) : "memory");
}
DI uint4 ldg_relaxed(const void* p) {
  uint4 v;
  asm volatile("ld.relaxed.gpu.global.v4.b32 {%0,%1,%2,%3}, [%4];" : "=r"(v.x), "=r"(v.y), "=r"(v.z), "=r"(v.w) : "l"(p) : "memory");
  return v;
}
DI void stg_relaxed(void* p, uint32_t x, uint32_t y, uint32_t z, uint32_t w) {
  asm volatile("st.relaxed.gpu.global.v4.b32 [%0], {%1,%2,%3,%4};" :: "l"(p), "r"(x), "r"(y), "r"(z), "r"(w) : "memory");
}
DI void red_f16x8(void* p, uint32_t x, uint32_t y, uint32_t z, uint32_t w) {
  asm volatile("red.relaxed.gpu.global.add.noftz.v4.f16x2 [%0], {%1,%2,%3,%4};" :: "l"(p), "r"(x), "r"(y), "r"(z), "r"(w) : "memory");
}
DI void sq_acc(uint32_t& a, uint32_t x) { asm("fma.rn.bf16x2 %0, %1, %1, %0;" : "+r"(a) : "r"(x)); }
DI __half2 amax4(__half2 h, const uint32_t* v) {
  h = __hmax2_nan(__hmax2_nan(h, __habs2(*(const __half2*)&v[0])), __habs2(*(const __half2*)&v[1]));
  return __hmax2_nan(__hmax2_nan(h, __habs2(*(const __half2*)&v[2])), __habs2(*(const __half2*)&v[3]));
}
DI uint32_t wexp(__half2 h) { const uint32_t u = *(const uint32_t*)&h; return __reduce_max_sync(0xffffffffu, max((u >> 16) & 0x7fffu, u & 0x7fffu)) >> 7; }
DI float max10(const float* a) {
  return fmaxf(fmaxf(fmaxf(fmaxf(a[0], a[1]), fmaxf(a[2], a[3])), fmaxf(fmaxf(a[4], a[5]), fmaxf(a[6], a[7]))), fmaxf(a[8], a[9]));
}
DI float quad_max(float m) {
  return fmaxf(fmaxf(m, __shfl_xor_sync(0xffffffffu, m, 1)), fmaxf(__shfl_xor_sync(0xffffffffu, m, 2), __shfl_xor_sync(0xffffffffu, m, 3)));
}
DI float warp_sum(float v) {
#pragma unroll
  for (int o = 16; o; o >>= 1) v += __shfl_xor_sync(0xffffffffu, v, o);
  return v;
}

constexpr int SM_WO3 = 0;
constexpr int SM_X = 16384;
constexpr int XT = 36864;
constexpr int SM_EXP = 126976;
constexpr int SEGB = 10240;
constexpr int SM_BLK = SM_EXP + 8192;
constexpr int SM_VC = SM_BLK + 4 * SEGB;
constexpr int SM_PART = SM_VC + 16384;
constexpr int SM_QM = SM_PART + 4096;
constexpr int SM_E = SM_QM + 1024;
constexpr int SM_VM = SM_E + 1536;
constexpr int SM_OB = SM_VM + 2048;
constexpr int SM_FB = SM_OB + 2048;
constexpr int SM_STAGE = SM_X + XT;
constexpr int SM_M0 = SM_STAGE + 3 * 49152;
constexpr int SM_MISC = 210944;
constexpr int SM_WOST = 212992;
constexpr int SM_MEM = SM_WOST;
constexpr int SM_MAX = SM_MEM + 11264;
#define MEM_BLK(q) ((q) / 3 * 4096 + (q) % 3 * 1024)
constexpr int SM_TOTAL = 229376;
constexpr int MB_W = SM_MISC;
constexpr int MB_WO = SM_MISC + 24;
constexpr int MB_WO3 = SM_MISC + 32;
constexpr int MB_X = SM_MISC + 40;
constexpr int MB_S = SM_MISC + 64;
constexpr int MB_F = SM_MISC + 72;
constexpr int MB_VX = SM_MISC + 80;
constexpr int SC_FPAR = SM_MISC + 136;
constexpr int SC_DEAD = SM_MISC + 96;
constexpr int SC_UNSC = SM_MISC + 112;
constexpr int SC_EXPW = SM_MISC + 132;
constexpr int SC_ONES = SM_MISC + 144;
constexpr int SC_SS = SM_MISC + 160;
constexpr int SC_LAT = SM_MISC + 224;
constexpr int SC_EPO = SM_MISC + 240;
constexpr int MB_XS = SM_MISC + 248;
constexpr int SC_XMAX = SM_MISC + 256;
constexpr int SC_PROF = 229376;

constexpr float SM_SCALE = 0.08838834764831845f;
constexpr float LOG2E = 1.4426950408889634f;
constexpr float E_LIM = 20.f;

template <bool B> struct BoolC { static constexpr bool value = B; };
struct RMaps { CUtensorMap x, wq, wk, wv, wo; unsigned char* red; uint32_t poll; const unsigned char* w[4]; };

DI uint32_t latest_hint(uint32_t h, uint32_t d, int s) {
  const uint32_t x = (((h | 0xc0c0c0c0u) - ((d >> 5) & 63) * 0x01010101u) & 0x3f3f3f3fu) | ((h ^ (((s >> 2) + 1) & 3) * 0x40404040u) & 0xc0c0c0c0u);
  const uint32_t y = __vmaxu2(x & 0x00ff00ffu, (x >> 8) & 0x00ff00ffu);
  return __reduce_max_sync(0xffffffffu, max(y & 0xffffu, y >> 16));
}
DI uint32_t near_half(uint32_t sb) {
  uint32_t a, b; lds64(sb + SC_LAT, a, b);
  return a > b;
}

template <int RT, int K0, int K1, bool D32 = false>
DI void xproj(float* acc, const uint32_t (&wa)[2][18][4], uint64_t xd) {
  if (XP & 1) return;
  WG_FENCE();
#pragma unroll
  for (int k = K0; k < ((XP & 128) ? K0 + 1 : K1); k++)
  {
    uint64_t d = xd + (uint64_t)(((k >> 1) * 4096 + (k & 1) * 32) >> 4);
    if (D32) asm("mov.b64 %0, {%1, %2};" : "=l"(d) : "r"((uint32_t)xd + (((k >> 1) * 4096 + (k & 1) * 32) >> 4)), "r"((uint32_t)(xd >> 32)));
    wgmma_n32_rs(acc, wa[RT][k][0], wa[RT][k][1], wa[RT][k][2], wa[RT][k][3], d, k != 0);
  }
  WG_COMMIT();
}

DI void seg_store(int seg, uint32_t sb) {
  fence_async();
  asm volatile("cp.async.bulk.global.shared::cta.bulk_group [%0], [%1], 8192;"
               :: "l"(g_seg + ((size_t)(seg & RING) * 96 + blockIdx.x) * 8192), "r"(sb + SM_BLK + (seg & 3) * SEGB) : "memory");
  asm volatile("cp.async.bulk.commit_group;" ::: "memory");
}
DI void seg_publish(int seg, uint32_t sb) {
  const uint32_t v = lds32(sb + SC_EPO) + seg;
  asm volatile("cp.async.bulk.wait_group 0;" ::: "memory");
  stg_relaxed32(&g_sflag[blockIdx.x * 8], v);
}

DI void proj_role(const uint32_t sb, const RMaps& tm, const uint32_t rank, const int wg, const int w, const int lane) {
  const bool qk = rank < 2;
  uint32_t wa[2][18][4];
  {
    const int rr = (lane & 7) + ((lane >> 4) << 3);
    const uint32_t col = ((2 * w + ((lane >> 3) & 1)) ^ (lane & 7)) << 4;
    float ss;
#pragma unroll 1
    for (int pass = WARM ? wg + w == 0 : 1; pass < 2; pass++) {
      ss = 0.f;
      if (pass) bar_sync(3, 256);
#pragma unroll
      for (int c = 0; c < 3; c++) {
        QSTAMP(2 + 2 * c);
        if (pass) mbar_wait(sb + MB_W + 8 * c, 0);
        QSTAMP(3 + 2 * c);
#pragma unroll
        for (int rt = 0; rt < 2; rt++)
#pragma unroll
          for (int k = 0; k < 6; k++)
            ldsm4t(wa[rt][c * 6 + k], sb + SM_STAGE + c * 49152 + (rt ^ wg) * 24576 + (64 * (k >> 1) + 32 * wg + 16 * (k & 1) + rr) * 128 + col);
        if (c < 2) {
          fence_async();
          if (pass) {
            bar_sync(3, 256);
            QSTAMP(17 + c);
            if (threadIdx.x == 0) {
              if (c == 0) tma_load3(sb + SM_X + XT, &tm.x, 32, sb + MB_X + 8);
              else tma_load(sb + SM_X + 2 * XT, &tm.wo, rank * 192, (blockIdx.x / 3) * DH, sb + MB_WO);
            }
            __syncwarp();
          }
        }
        uint32_t q[4] = {0, 0, 0, 0};
#pragma unroll
        for (int rt = 0; rt < 2; rt++)
#pragma unroll
          for (int k = 0; k < 6; k++)
#pragma unroll
            for (int i = 0; i < 4; i++) sq_acc(q[i], wa[rt][c * 6 + k][i]);
#pragma unroll
        for (int i = 0; i < 4; i++) ss += bf_lo(q[i]) + bf_hi(q[i]);
      }
      ss = warp_sum(ss);
    }
    fence_async();
    cluster_arrive();
    if (lane == 0) sts32(sb + SC_SS + 4 * (wg * 4 + w), qk ? 0 : __float_as_uint(ss));
    bar_arrive(11, 384);
  }
  STAMP(1);
  QSTAMP(8);
  mbar_wait(sb + MB_X, 0);
  STAMP(2);
  QSTAMP(9);

  uint32_t t16 = sb + (w * 32 + lane) * 16;
  uint32_t mem_a = sb + SM_MEM + wg * 512 + lane * 16;
  uint32_t fin_a = sb + (lane & 7) * 16 + SM_BLK + (qk ? (wg ^ 1) * 4096 + w * 256 + (lane & 8) * 16 + (lane & 16) * 64
                                              : wg * 4096 + w * 1024 + (lane & 8) * 64 + (lane & 16) * 8);
  PIN(t16); PIN(mem_a); PIN(fin_a);
  const uint32_t fence_reg = mem_a;
  const uint32_t fin2 = qk ? 2048 : 256;
  float acc[16];
  const uint64_t xd0 = make_desc(sb + SM_X + wg * 64, 16, 1024, 1);
  auto do_export = [&](auto retire, uint32_t always) {
    WG_WAIT(0);
    uint32_t p[2];
#pragma unroll
    for (int i = 0; i < 2; i++) {
      p[i] = pack_bf16(acc[8 * i], acc[8 * i + 1]);
      sts128(t16 + SM_EXP + wg * 4096 + i * 2048, p[i], pack_bf16(acc[8 * i + 2], acc[8 * i + 3]),
             pack_bf16(acc[8 * i + 4], acc[8 * i + 5]), pack_bf16(acc[8 * i + 6], acc[8 * i + 7]));
    }
    if (decltype(retire)::value)
      asm volatile("{\n.reg .pred p, q;\nsetp.ne.u32 p, %2, 0;\nsetp.ne.u32 q, %2, 1;\n@p ld.shared.b32 %0, [%3];\n@q ld.shared.b32 %1, [%3 + 4];\n"
                   "setp.ne.u32 p, %0, %1;\n@p exit;\n}" : "+r"(p[0]), "+r"(p[1]) : "r"(always), "r"(sb + SC_DEAD) : "memory");
  };
  uint32_t o[8];
  auto import = [&]() { lds128(t16 + SM_EXP + (wg ^ 1) * 4096, o); lds128(t16 + SM_EXP + (wg ^ 1) * 4096 + 2048, o + 4); };
  auto finish = [&](int seg) {
    const uint32_t a = fin_a + (seg & 3) * SEGB;
    WG_WAIT(0);
#pragma unroll
    for (int i = 0; i < 8; i++) o[i] = FIN16 ? add_bf16(pack_bf16(acc[2 * i], acc[2 * i + 1]), o[i]) : pack_bf16(acc[2 * i] + bf_lo(o[i]), acc[2 * i + 1] + bf_hi(o[i]));
    stsm4(a, o[0], o[1], o[2], o[3]);
    stsm4(a + fin2, o[4], o[5], o[6], o[7]);
  };
  auto send_v = [&](int seg, int dst) {
    fence_async();
    if (seg < NSEG - 1 && !(XP & 2) && elect_one())
      bulk_s2s(mapa(sb + SM_VC + (seg & 1) * 8192, dst), sb + SM_BLK + (seg & 3) * SEGB, 8192, mapa(sb + MB_VX + (seg & 1) * 8, dst));
    __syncwarp();
  };
  auto wait_v = [&](int seg) {
    if (seg < NSEG - 1 && !(XP & 2)) {
      mbar_wait(sb + MB_VX + (seg & 1) * 8, (seg >> 1) & 1);
      if (elect_one()) mbar_expect(sb + MB_VX + (seg & 1) * 8, 8192);
      __syncwarp();
    }
  };
  auto export_seg = [&](int seg) { if (!(XP & (4 | 8192)) && elect_one()) seg_store(seg, sb); __syncwarp(); };
  auto publish = [&](int seg) { if (!(XP & (4 | 16384)) && elect_one()) seg_publish(seg, sb); __syncwarp(); };
  bar_sync(3, 256);
  xproj<1, 0, 18>(acc, wa, xd0);
  do_export(BoolC<false>(), 0);
  SCHED_FENCE(11);
  xproj<0, 0, 18>(acc, wa, xd0);
  bar_sync(3, 256);
  QSTAMP(10);
  cluster_wait();
  QSTAMP(11);
  mbar_wait(sb + MB_X + 8, 0);
  QSTAMP(12);
  import();
  finish(0);
  SCHED_FENCE(12);
  bar_sync(3, 256);
  uint64_t dA = xd0 + (XT >> 4);
  xproj<1, 0, 18>(acc, wa, dA);
  if (!qk && wg == 0 && w < 2) send_v(0, w);
  if (wg == 0 && w == 3) export_seg(0);
  QSTAMP(13);
  if (qk && wg == 0 && w == 0) wait_v(0);
  QSTAMP(14);
  bar_arrive(13, 384);
  if (!qk) {
    do_export(BoolC<false>(), 0);
    SCHED_FENCE(15);
    xproj<0, 0, 18>(acc, wa, dA);
    if (threadIdx.x == 0 && !(XP & 8)) { mbar_expect(sb + MB_X, XT); tma_load3(sb + SM_X, &tm.x, 96, sb + MB_X); }
    bar_sync(3, 256);
    mbar_wait(sb + MB_X + 16, 0);
    import();
    finish(1);
    SCHED_FENCE(16);
    bar_sync(3, 256);
    dA += XT >> 4;
    xproj<1, 0, 18>(acc, wa, dA);
    if (wg == 0 && w < VW2) send_v(1, w);
  }
  QSTAMP(15);
  WG_WAIT(0);
  bar_sync(0, 384);
  if (wg == 0 && w == 3) publish(0);
  QSTAMP(16);
  const int ro = __shfl_sync(0xffffffffu, near_half(sb) ^ wg, 0);
  STAMP(5);
  const uint32_t always = __shfl_sync(0xffffffffu, lds32(sb + SC_DEAD + 12), 0);
  const int ah = qk ? 1 : 2;
  int b2 = qk ? 2 : 0;
  int s = 0;
  uint32_t hint_lo = (uint32_t)(uint64_t)tm.red + HINT_OFF + blockIdx.x + (lane & 1) * 4096 + (lane >> 1) * 16384;
  PIN(hint_lo);
  auto post_hint = [&]() {
    asm volatile("{\n.reg .pred p;\n.reg .b64 a;\n.reg .u32 t;\nsetp.lt.u32 p, %0, %1;\nmov.b64 a, {%2, %3};\nmov.u32 t, %%globaltimer_lo;\n"
                 "bfe.u32 t, t, 5, 6;\nor.b32 t, t, %4;\n@p st.relaxed.gpu.global.u8 [a], t;\n}"
                 :: "r"(t16), "r"(sb + 160), "r"(hint_lo + RED_SLOT(s)), "r"((uint32_t)((uint64_t)tm.red >> 32)), "r"(((s >> 2) + 1) << 6) : "memory");
  };
  auto memproj = [&](auto second, int id, uint32_t dep, float u0, float u1, float* r) {
    constexpr bool R1 = decltype(second)::value;
    uint32_t b[NUP][4], b0[4];
    if (R1) asm volatile("{\n.reg .pred p;\nsetp.eq.u32 p, %0, %1;\n@p exit;\n}" :: "r"(dep), "r"(id) : "memory");
    bar_sync(R1 ? 2 : 1, 256);
    PROF(0);
    ldsm4t(b0, mem_a);
#pragma unroll
    for (int q = 0; q < NUP; q++) {
      if (R1 && q == 2) {
        bar_sync(11, 256);
        SCHED_FENCE(id + 1);
      }
      ldsm4t(b[q], mem_a + MEM_BLK(q + 1));
    }
    mma16816z(&acc[0], wa[0][0], b0[0], b0[1]);
    mma16816z(&acc[4], wa[1][0], b0[0], b0[1]);
    mma16816z(&acc[8], wa[0][1], b0[2], b0[3]);
    mma16816z(&acc[12], wa[1][1], b0[2], b0[3]);
#pragma unroll
    for (int q = 1; q < 9; q++) {
      uint32_t* const c = b[(q - 1) % NUP];
      mma16816(&acc[0], wa[0][2 * q], c[0], c[1]);
      mma16816(&acc[4], wa[1][2 * q], c[0], c[1]);
      mma16816(&acc[8], wa[0][2 * q + 1], c[2], c[3]);
      mma16816(&acc[12], wa[1][2 * q + 1], c[2], c[3]);
      if (R1 && q + NUP == B3Q) bar_sync(3, 256);
      if (q + NUP < 9) ldsm4t_in(c, mem_a + MEM_BLK(q + NUP), always);
      else if (R1 && q + NUP < 11) lds128_in(c, t16 + SM_PART + (10 - q - NUP) * 2048, always);
      else if (!R1 && GATE && q == GATE) { bar_arrive(11, 256); lds128_in(c, sb + SC_DEAD, always); u0 = u1 = __uint_as_float(c[3]); }
    }
#pragma unroll
    for (int i = 0; i < 8; i++) {
      const float u = i < 4 ? u0 : u1;
      r[i] = R1 ? fmaf(acc[8 + i], u, (acc[i] + __uint_as_float(b[(8 + i / 4) % NUP][i & 3])) * u) : (GATE ? fmaf(acc[i], u, acc[8 + i]) : acc[i] + acc[8 + i]);
    }
  };
  if (ro == 0) {
#pragma unroll 1
    while (true) {
      do_export(BoolC<true>(), always);
      PROFP(3);
      if (s == 8) STAMP(6);
      float r[8];
      memproj(BoolC<false>(), 30, 0, 0.f, 0.f, r);
      sts128(t16 + SM_PART, __float_as_uint(r[0]), __float_as_uint(r[1]), __float_as_uint(r[2]), __float_as_uint(r[3]));
      sts128(t16 + SM_PART + 2048, __float_as_uint(r[4]), __float_as_uint(r[5]), __float_as_uint(r[6]), __float_as_uint(r[7]));
      bar_arrive(3, 256);
      PROF(1);
      bar_sync(9, 256);
      if (s == NSEG - 1) break;
      post_hint();
      if (w == 3 && s) publish(s);
      if (w == 1) {
        uint32_t m[8];
        lds128(t16 + SM_MAX - 512, m); lds128(t16 + SM_MAX, m + 4);
        const int em = (wexp(amax4(amax4(*(const __half2*)&m[0], m), m + 4)) >> 3) + (int)(lds32(sb + SC_UNSC + (s & 1) * 8) >> 23) - 15;
        const int ex = max(s ? em : 0, (int)lds32(sb + SC_XMAX + 4 * s)) - 127 + (int)lds32(sb + SC_EXPW);
        sts32(sb + SC_UNSC + (~s & 1) * 8, (127 + min(max(ex, -120), 120)) << 23);
        __syncwarp();
        if (elect_one()) mbar_arrive(sb + MB_S);
      }
      SCHED_FENCE(9);
      bar_sync(5, qk ? N5 : 256);
      PROF(2);
      import();
      xproj<0, 0, NII>(acc, wa, dA);
      if (NII < 18) {
        if (qk) bar_sync(7, 384);
        xproj<0, NII, 18>(acc, wa, dA);
        if (!qk) bar_sync(7, 384);
      } else {
        if (F10) WG_WAIT(0);
        bar_sync(10, 256);
        if (F10) SCHED_FENCE(17);
      }
      dA += (int64_t)(b2 ? XT >> 4 : -(XT >> 3));
      finish(s + ah);
      if (w != 3 && (qk || w >= VW2)) bar_arrive(13, 384);
      PROF(6);
      SCHED_FENCE(14);
      bar_sync(12, 256);
      PROF(7);
      xproj<1, 0, 18, true>(acc, wa, dA);
      bar_arrive(14, 256);
      b2 = b2 == 2 ? 0 : b2 + 1;
      s++;
      if (w == 3 || (!qk && w < VW2)) {
        bar_sync(13, 384);
        if (w == 3) export_seg(s); else send_v(s + 1, w);
      }
      PROFP(8);
    }
    if (!qk) bar_arrive(5, 256);
    if (w == 3) publish(NSEG - 1);
  } else {
    uint32_t km[4];
    auto send_km = [&]() {
      if (XP & (4 | 4096)) return;
      const uint32_t t = (km[0] & ~1u) | lds32(sb + SC_EPO + 4), u = (s * NH + head_id()) * 4096;
      if (qk)
        asm volatile("{\n.reg .u32 o;\n.reg .u64 a;\nshr.u32 o, %0, 1;\nadd.u32 o, o, %1;\nmad.wide.u32 a, o, 1, %2;\nst.relaxed.gpu.global.v2.b32 [a], {%3,%4};\n}"
                     :: "r"(t16), "r"(u + rank * 1024 - (sb >> 1)), "l"(g_km), "r"(t), "r"(km[1]) : "memory");
      else
        asm volatile("{\n.reg .u32 o;\n.reg .u64 a;\nadd.u32 o, %0, %1;\nmad.wide.u32 a, o, 1, %2;\nst.relaxed.gpu.global.v4.b32 [a], {%3,%4,%5,%6};\n}"
                     :: "r"(t16), "r"(u + 2048 - sb), "l"(g_km), "r"(t), "r"(km[1]), "r"(km[2]), "r"(km[3]) : "memory");
    };
#pragma unroll 1
    while (true) {
      do_export(BoolC<true>(), always);
      PROFP(3);
      if (s == 8) STAMP(6);
      const uint32_t tl = ((t16 >> 8) ^ wg) & 1, am = (t16 & ~256u) - w * 256;
      const float un = __uint_as_float(lds32(sb + SC_UNSC + (s & 1) * 8));
      float r[8];
      if (qk) {
        uint32_t a0 = am + (tl ? SM_QM : SM_BLK + 8192 + (s & 3) * SEGB);
        float u0 = wg ? un * (SM_SCALE * LOG2E) : un, u1 = wg ? un : un * (SM_SCALE * LOG2E);
        PIN(a0); PIN(u0); PIN(u1);
        memproj(BoolC<true>(), 32, a0, u0, u1, r);
        const uint32_t p0 = pack_bf16(r[0], r[1]), p1 = pack_bf16(r[2], r[3]), p2 = pack_bf16(r[4], r[5]), p3 = pack_bf16(r[6], r[7]);
        stsm4(a0, p0, p1, p2, p3);
        bar_arrive(4, 256);
        km[0] = wg ? p2 : p0; km[1] = wg ? p3 : p1;
      } else {
        const uint32_t d0 = s < NSEG - 1 ? 0 : 2, d1 = s < NSEG - 1 ? 1 : 2;
        uint32_t r0 = mapa(t16 + SM_VM, d0), r1 = mapa(t16 + SM_VM, d1);
        PIN(r0); PIN(r1);
        memproj(BoolC<true>(), 34, r0 | r1, un, un, r);
        const uint32_t p0 = pack_bf16(r[0], r[1]), p1 = pack_bf16(r[2], r[3]), p2 = pack_bf16(r[4], r[5]), p3 = pack_bf16(r[6], r[7]);
        const uint32_t v0 = wg ? p2 : p0, v1 = wg ? p3 : p1, v2 = wg ? p0 : p2, v3 = wg ? p1 : p3;
        st_async4(r0, v0, v1, v2, v3, mapa(sb + MB_S, d0));
        st_async4(r1, v0, v1, v2, v3, mapa(sb + MB_S, d1));
        bar_arrive(5, 256);
        sts128(t16 + SM_VM, v0, v1, v2, v3);
        __syncwarp();
        if (elect_one()) mbar_arrive(sb + MB_S);
        km[0] = v0; km[1] = v1; km[2] = v2; km[3] = v3;
      }
      if (s == NSEG - 1) break;
      PROF(1);
      auto rearm = [&]() { mbar_wait(sb + MB_S, s & 1); if (elect_one()) mbar_expect(sb + MB_S, qk ? 640 + 2048 : 1280); __syncwarp(); };
      if (w == 1) {
        if ((t16 & 384) == 0) stg_relaxed(tm.red + (RED_SLOT(s + 2) + RED_LINE(blockIdx.x)) + (t16 & 112), 0, 0, 0, 0);
      } else if (w == 0) {
        const int tn = s + ah + 1;
        if (RFW) mbar_wait(sb + MB_S, s & 1);
        if (tn + 1 < NSEG && !(XP & 8) && elect_one()) {
          const int b0 = b2 == 2 ? 0 : b2 + 1;
          mbar_expect(sb + MB_X + 8 * b0, XT);
          tma_load3(sb + SM_X + b0 * XT, &tm.x, (tn + 1) * 32, sb + MB_X + 8 * b0);
        }
        if (tn < NSEG && (!(XP & 8) || tn < 3)) mbar_wait(sb + MB_X + 8 * b2, (tn / 3) & 1);
      } else if (w == 2) {
        if (!qk) { if (VW2 < 1) send_v(s + 1, 0); if (VW2 < 2) send_v(s + 1, 1); }
      } else if (qk || !NIC) {
        rearm();
      }
      __syncwarp();
      send_km();
      import();
      PROF(4);
      SCHED_FENCE(10);
      if (NIC) {
        if (qk) bar_sync(7, NII < 18 ? 384 : 256);
        xproj<0, 0, NIC>(acc, wa, dA);
        if (!qk) { if (w == 3) rearm(); bar_sync(7, NII < 18 ? 384 : 256); }
      } else {
        bar_sync(7, NII < 18 ? 384 : 256);
      }
      xproj<0, NIC, 18>(acc, wa, dA);
      bar_arrive(12, 256);
      dA += (int64_t)(b2 ? XT >> 4 : -(XT >> 3));
      finish(s + ah);
      if (qk && w == 0) wait_v(s + 1);
      bar_arrive(13, 384);
      PROF(6);
      SCHED_FENCE(13);
      bar_sync(14, 256);
      PROF(7);
      xproj<1, 0, 18>(acc, wa, dA);
      b2 = b2 == 2 ? 0 : b2 + 1;
      s++;
      PROFP(8);
    }
    send_km();
    PIN(t16);
    if (t16 - sb < 128) stg_relaxed(tm.red + (RED_SLOT(NSEG + 1) + RED_LINE(head_id() * 3 + rank)) + (t16 & 112), 0, 0, 0, 0);
  }
  bar_arrive(0, 384);
  STAMP(3);
  cluster_sync();
  STAMP(4);
}

DI void attn_role(const uint32_t sb, unsigned char* smem_raw, const RMaps& tm, const uint32_t RANK, const bf16* __restrict__ x, const bf16* __restrict__ mem0,
                  const int w, const int lane) {
  const int t2 = w * 32 + lane;
  uint32_t wo[8][4], w1[8][4];
  const uint32_t wo_lane = sb + ((lane & 7) + ((lane >> 4) << 3)) * 128 + (((w + 4 * ((lane >> 3) & 1)) ^ (lane & 7)) << 4);
  unsigned char* const g_red = tm.red;
  {
    const uint32_t tag = *(volatile unsigned*)&g_epoch + 1;
    QSTAMP(0);
    bar_sync(0, 160);
    QSTAMP(1);
    cluster_arrive();
    __half2 hx = __float2half2_rn(0.f);
    if (blockIdx.x < NSEG) {
      mbar_wait(sb + MB_XS, 0);
#pragma unroll
      for (int i = 0; i < 18; i++) { uint32_t v[4]; lds128(sb + SM_X + t2 * 16 + i * 2048, v); hx = amax4(hx, v); }
      fence_async();
      bar_sync(6, 128);
      if (t2 == 0) tma_load3(sb + SM_X, &tm.x, 0, sb + MB_X);
      __syncwarp();
    }
    if (t2 == 0) { sts64(sb + SC_EPO, (tag - 1) * NSEG + 1, tag & 1); sts32(sb + SC_UNSC, __float_as_uint(1.f)); sts128(sb + SC_DEAD, 0, 0, 0, 0x3f800000u); sts64(sb + SC_FPAR, 0, 0); sts128(sb + SC_ONES, 0x3f803f80u, 0x3f803f80u, 0x3f803f80u, 0x3f803f80u); }
    WSTAMP(27);
    uint32_t q[8] = {0, 0, 0, 0, 0, 0, 0, 0};
    QSTAMP(2);
    mbar_wait(sb + MB_WO3, 0);
    QSTAMP(3);
    uint32_t mv[5][4];
#pragma unroll
    for (int i = 0; i < 5; i++) {
      ldsm4(mv[i], sb + SM_M0 + (lane & 7) * (DM * 2) + min(w + 4 * i, 17) * 64 + (lane >> 3) * 16);
      if (blockIdx.x == 0) hx = amax4(hx, mv[i]);
    }
    sts32(sb + SC_SS + 4 * (12 + w), wexp(hx));
#pragma unroll
    for (int k = 0; k < 8; k++) {
      ldsm4t(wo[k], wo_lane + SM_WO3 + k * 2048); ldsm4t(w1[k], wo_lane + SM_WOST + k * 2048);
#pragma unroll
      for (int i = 0; i < 4; i++) { sq_acc(q[i], wo[k][i]); sq_acc(q[i], w1[k][i]); }
    }
    bar_sync(6, 128);
#pragma unroll
    for (int k = 0; k < 8; k++) sts128(sb + SM_WO3 + t2 * 16 + k * 2048, wo[k][0], wo[k][1], wo[k][2], wo[k][3]);
#pragma unroll
    for (int i = 0; i < 5; i++) {
      const int c = (w + 4 * i) * 32;
      if (c < DM) stsm4t(sb + SM_MEM + (c + c / 192 * 64 + lane) * 16, mv[i][0], mv[i][1], mv[i][2], mv[i][3]);
    }
    bar_arrive(1, 256); bar_arrive(2, 256); bar_arrive(9, 256);
    QSTAMP(4);
    mbar_wait(sb + MB_WO, 0);
    QSTAMP(5);
#pragma unroll
    for (int k = 0; k < 8; k++) ldsm4t(wo[k], wo_lane + SM_X + 2 * XT + k * 2048);
    fence_async();
    bar_sync(6, 128);
    if (t2 == 32) tma_load3(sb + SM_X + 2 * XT, &tm.x, 64, sb + MB_X + 16);
    __syncwarp();
#pragma unroll
    for (int k = 0; k < 8; k++)
#pragma unroll
      for (int i = 0; i < 4; i++) sq_acc(q[4 + i], wo[k][i]);
    float ss = 0.f;
#pragma unroll
    for (int i = 0; i < 8; i++) ss += bf_lo(q[i]) + bf_hi(q[i]);
    ss = warp_sum(ss);
    if (lane == 0) sts32(sb + SC_SS + 4 * (8 + w), __float_as_uint(ss));
    QSTAMP(6);
    bar_sync(11, 384);
    QSTAMP(7);
    if (t2 == 0) {
      float a[16];
#pragma unroll
      for (int i = 0; i < 4; i++) lds128f(sb + SC_SS + 16 * i, &a[4 * i]);
      stg_relaxed(&g_stats[blockIdx.x * 2], __float_as_uint(((a[0] + a[1]) + (a[2] + a[3])) + ((a[4] + a[5]) + (a[6] + a[7]))),
                  __float_as_uint((a[8] + a[9]) + (a[10] + a[11])),
                  max(max(__float_as_uint(a[12]), __float_as_uint(a[13])), max(__float_as_uint(a[14]), __float_as_uint(a[15]))), tag);
    }
    __syncwarp();
    WSTAMP(24);
    QSTAMP(8);
    cluster_wait();
    QSTAMP(9);
    if (w == 0) {
      uint4 v[3];
      int n = 0;
      while (true) {
#pragma unroll
        for (int i = 0; i < 3; i++) v[i] = ldg_relaxed(&g_stats[(i * 32 + lane) * 2]);
        if (__all_sync(0xffffffffu, v[0].w == tag && v[1].w == tag && v[2].w == tag) || ++n > SPIN_LIMIT) break;
        __nanosleep(100);
      }
      WSTAMP(25);
      QSTAMP(10);
      const float sv = warp_sum(__uint_as_float(v[0].x) + __uint_as_float(v[1].x) + __uint_as_float(v[2].x));
      const float so = warp_sum(__uint_as_float(v[0].y) + __uint_as_float(v[1].y) + __uint_as_float(v[2].y));
      const int expW = ((int)(__float_as_uint(sv) >> 23) + (int)(__float_as_uint(so) >> 23) - 254 + 2 + 10 + 1) >> 1;
      sts32(sb + SC_XMAX + 4 * lane, v[0].z); sts32(sb + SC_XMAX + 128 + 4 * lane, v[1].z);
      sts32(sb + SC_EXPW, expW + 1 - 15);
      if (blockIdx.x == 0 && lane == 0) *(volatile unsigned*)&g_epoch = tag;
      sts32(sb + SC_FPAR + 4, 1);
    } else if (w < 3) {
      const uint32_t u = blockIdx.x >> 4;
      unsigned char* const z = g_red + 98304 + (blockIdx.x & 15) * 128 + (u & 1) * 2048 + (u & 6) * 4096 + (((u >> 1) ^ w) & 1) * 4096 + lane * 4;
      stg_relaxed32(z, 0);
      uint32_t best = 0xffffffffu;
#pragma unroll 1
      for (int i = 0; i < 64; i++) {
        uint32_t last, dt;
        asm volatile("{\n.reg .pred p;\n.reg .u32 c, v;\nld.volatile.shared.u32 %0, [%3];\nmov.u32 c, %%clock;\n"
                     "atom.relaxed.gpu.global.exch.b32 v, [%2], 0;\nsetp.eq.u32 p, v, 0;\nmov.u32 %1, 0;\n@p mov.u32 %1, %%clock;\nsub.u32 %1, %1, c;\n}"
                     : "=r"(last), "=r"(dt) : "l"(z), "r"(sb + SC_FPAR + 4) : "memory");
        best = min(best, dt);
        if ((last && i >= NPROBE - 1) || i >= NPROBE2 - 1) break;
      }
      sts32(sb + SC_LAT + (w - 1) * 4, best);
    }
    QSTAMP(11);
    bar_sync(13, 384);
    bar_arrive(0, 384);
    QSTAMP(12);
    WSTAMP(26);
  }

  const uint32_t nh = __shfl_sync(0xffffffffu, near_half(sb), 0);
  uint32_t l16 = sb + lane * 16;
  PIN(l16);
#define LV ((l16 >> 4) & 31)
#define fence_reg l16
  const uint32_t red_lo = (uint32_t)(uint64_t)g_red, red_hi = (uint32_t)((uint64_t)g_red >> 32);
  uint32_t lp;
  auto slot = [&](int s, uint32_t c, uint32_t ofs) {
    const uint32_t lo = lp | (red_lo + ((w >> 1) * 4 + (w & 1) * 2 + ((w ^ c) & 1)) * 4096 + RED_SLOT(s) + ofs);
    uint64_t a; asm("mov.b64 %0, {%1, %2};" : "=l"(a) : "r"(lo), "r"(red_hi));
    return (unsigned char*)a;
  };
  const uint32_t always = __shfl_sync(0xffffffffu, lds32(sb + SC_DEAD + 12), 0);
  const int mode0 = RANK < 2 ? w : w | 4;
  auto hint_addr = [&](int s) { return min(LV, 23u) * 4 + (red_lo + HINT_OFF + nh * 4096 + w * 16384 + RED_SLOT(s)); };
  auto load_hints = [&](uint32_t lo) {
    uint64_t a; asm("mov.b64 %0, {%1, %2};" : "=l"(a) : "r"(lo), "r"(red_hi));
    return ldg_relaxed32((const void*)a);
  };
  int s = 0;
  bool bad = false;
#pragma unroll 1
  while (true) {
    const uint32_t par = s & 1;
    uint32_t vx[4][4], hints;
    auto load_vx = [&]() {
      const uint32_t va = l16 + (RANK < 2 ? SM_VC + par * 8192 : SM_BLK + (s & 3) * SEGB) + w * 1024 + ((LV >> 3) & 1) * 384 - (LV >> 4) * 128;
#pragma unroll
      for (int i = 0; i < 4; i++) ldsm4(vx[i], va + (i & 1) * 4096 + (i >> 1) * 256);
    };
    auto retire = [&](uint32_t x) {
      asm volatile("{\n.reg .pred p;\nsetp.eq.u32 p, %0, 0;\n@p exit;\n}" :: "r"(vx[0][0] | vx[1][0] | vx[2][0] | vx[3][0] | x) : "memory");
    };
    auto scores = [&](auto memkeys, auto first, float* sc) {
      constexpr bool MK = decltype(memkeys)::value, FIRST = decltype(first)::value;
      uint32_t kb[4][4], qb[2][4];
      const uint32_t m = LV >> 3;
      uint32_t kaddr = l16 + SM_BLK + 4096 + (s & 3) * SEGB + w * 2048 + (m & 1) * (MK ? 128 : 896) - (m >> 1) * 128;
      if (MK) { PIN(kaddr); }
      else {
#pragma unroll
        for (int k = 0; k < 4; k++) ldsm4t(kb[k], kaddr + k * 256);
      }
      if (FIRST) { load_vx(); retire(MK ? kaddr : kb[0][0] | kb[1][0] | kb[2][0] | kb[3][0] | l16); bar_sync(4, 256); PROF(4); }
      ldsm4t(qb[0], l16 + SM_QM);
      if (MK) ldsm4t(kb[0], kaddr);
      ldsm4t(qb[1], l16 + SM_QM + 512);
      if (MK) ldsm4t(kb[2], kaddr + 512);
      float c[4][4];
      mma16816z(c[0], kb[0], qb[0][0], qb[0][1]); mma16816z(c[1], kb[MK ? 0 : 1], qb[0][2], qb[0][3]);
      mma16816z(c[2], kb[2], qb[1][0], qb[1][1]); mma16816z(c[3], kb[MK ? 2 : 3], qb[1][2], qb[1][3]);
      if (FIRST && B5POS == 0) bar_arrive(5, N5);
#pragma unroll
      for (int i = 0; i < (MK ? 2 : 4); i++) sc[i] = ((c[0][i] + c[1][MK ? i + 2 : i]) + c[2][i]) + c[3][MK ? i + 2 : i];
    };
    auto send = [&](auto memkeys) {
      constexpr bool MK = decltype(memkeys)::value;
      constexpr int N = MK ? 1 : 2;
      const uint32_t sa = sb + LV * 4 + SM_E + (MK ? 1024 + RANK * 128 : RANK * 512 + w * 256);
      uint32_t ra[N][2], mb[N][2];
#pragma unroll
      for (int i = 0; i < N; i++)
#pragma unroll
        for (int j = 0; j < 2; j++) {
          ra[i][j] = mapa(sa + i * 128, j ? 2 : RANK ^ 1); mb[i][j] = mapa(sb + MB_S, j ? 2 : RANK ^ 1);
          PIN(ra[i][j]);
        }
      float sc[4];
      scores(memkeys, BoolC<true>(), sc);
      uint32_t e[N];
#pragma unroll
      for (int i = 0; i < N; i++) {
        e[i] = pack_bf16(ex2(sc[2 * i]), ex2(sc[2 * i + 1]));
        if (!(fmaxf(fabsf(sc[2 * i]), fabsf(sc[2 * i + 1])) <= E_LIM)) e[i] = 0x7fff7fffu;
        st_async1(ra[i][0], e[i], mb[i][0]);
        st_async1(ra[i][1], e[i], mb[i][1]);
      }
#pragma unroll
      for (int i = 0; i < N; i++) sts32(sa + i * 128, e[i]);
      __syncwarp();
      if (l16 == sb) mbar_arrive(sb + MB_S);
      PROF(5);
    };
    const int mode = bad ? 8 : mode0;
    if (mode < 2) {
      send(BoolC<false>());
    } else if (mode == 2) {
      send(BoolC<true>());
    } else if (mode == 8) {
      load_vx();
      retire(l16);
      const uint32_t fp = lds32(sb + SC_FPAR);
      bar_sync(6, 128);
      if (w == 0 && l16 == sb) { sts32(sb + SC_FPAR, fp ^ 1); mbar_expect(sb + MB_F, 3072); }
      if (RANK < 2 && w < 3) {
        float sc[4] = {0.f, 0.f, 0.f, 0.f};
        if (w < 2) scores(BoolC<false>(), BoolC<false>(), sc); else scores(BoolC<true>(), BoolC<false>(), sc);
#pragma unroll 1
        for (int r = 0; r < 3; r++)
          st_async4(mapa(l16 + SM_FB + RANK * 1536 + w * 512, r), __float_as_uint(sc[0]), __float_as_uint(sc[1]), __float_as_uint(sc[2]), __float_as_uint(sc[3]), mapa(sb + MB_F, r));
      }
      mbar_wait(sb + MB_F, fp);
      float a[12];
#pragma unroll
      for (int j = 0; j < 3; j++) {
        float b[4];
        lds128f(l16 + SM_FB + j * 512, a + 4 * j); lds128f(l16 + SM_FB + 1536 + j * 512, b);
#pragma unroll
        for (int i = 0; i < 4; i++) a[4 * j + i] += b[i];
      }
      float m0 = fmaxf(fmaxf(fmaxf(a[0], a[2]), fmaxf(a[4], a[6])), a[8]), m1 = fmaxf(fmaxf(fmaxf(a[1], a[3]), fmaxf(a[5], a[7])), a[9]);
#pragma unroll
      for (int o = 4; o < 32; o <<= 1) { m0 = fmaxf(m0, __shfl_xor_sync(0xffffffffu, m0, o)); m1 = fmaxf(m1, __shfl_xor_sync(0xffffffffu, m1, o)); }
#pragma unroll
      for (int i = 0; i < 5; i++) {
        const uint32_t ea = sb + SM_E + LV * 4 + (i < 4 ? i * 128 : 1024);
        sts32(ea, pack_bf16(ex2(a[2 * i] - m0), ex2(a[2 * i + 1] - m1)));
        sts32(ea + (i < 4 ? 512 : 128), 0x3f803f80u);
      }
      __syncwarp();
    } else {
      load_vx();
      if (mode == 3) bar_arrive(4, 256);
      retire(l16 + 1);
    }
    {
      uint32_t wa[4], wb[4], oc[4];
      constexpr int WS = 2048;
      const uint32_t w3a = l16 + SM_WO3 + w * 512;
      lds128(w3a + KP(0) * WS, wa); lds128(w3a + KP(1) * WS, wb); lds128(sb + SC_ONES, oc);
      if (B5POS == 1 && mode < 3) bar_arrive(5, N5);
      uint32_t e[10], p[5], vm[4], ob[4];
      float o0[4], o1[4], f[3][2][4], rs[4];
      reserve2(vm); reserve2(vm + 2); reserve2(e + 8);
      hints = hint_addr(s);
      PIN(hints);
      if (CLR & 2) asm volatile("{\n.reg .pred p;\nsetp.eq.u32 p, %0, 0;\n@p exit;\n}" :: "r"(wa[0] | wb[0] | oc[0] | hints) : "memory");
      mbar_wait(sb + MB_S, par);
      PROF(6);
      ldsm4t(e, l16 + SM_E); ldsm2t_in(e + 8, l16 + SM_E + 1024, always); ldsm4t(e + 4, l16 + SM_E + 512);
      lds128_in(vm, l16 + w * 512 + SM_VM, always);
      const float scl = __uint_as_float(lds32(sb + SC_UNSC + 8 - par * 8));
      hints = load_hints(hints);
      if (GF & 1) SCHED_FENCE(4);
#pragma unroll
      for (int i = 0; i < 4; i++) p[i] = mul_bf16(e[i], e[4 + i]);
      p[4] = mul_bf16(e[8], e[9]);
      mma16816z(o0, vx[0], p[0], p[1]); mma16816z(o1, vx[1], p[0], p[1]); mma16816z(rs, oc, p[0], p[1]);
      mma16816(o0, vx[2], p[2], p[3]); lds128_in(vx[2], w3a + KP(2) * WS, always);
      mma16816(o1, vx[3], p[2], p[3]); lds128_in(vx[3], w3a + KP(3) * WS, always);
      mma16816(rs, oc, p[2], p[3]);
      mma1688(o0, vm[0], vm[1], p[4]); mma1688(o1, vm[2], vm[3], p[4]); mma1688(rs, oc[0], oc[1], p[4]);
      stsm4(l16 + w * 512 + SM_OB, pack_bf16(o0[0], o0[1]), pack_bf16(o0[2], o0[3]), pack_bf16(o1[0], o1[1]), pack_bf16(o1[2], o1[3]));
      bar_sync(6, 128);
      PROF(7);
      ldsm4t_in(oc, l16 + SM_OB, always);
      bad = __any_sync(0xffffffffu, !(rs[0] + rs[1] > 0.f) && !bad);
      rs[0] *= scl; rs[1] *= scl;
      asm volatile("{\n.reg .pred p;\nsetp.ne.u32 p, %1, 0;\n@p rcp.approx.ftz.f32 %0, %0;\n}" : "+f"(rs[0]) : "r"(always));
      asm volatile("{\n.reg .pred p;\nsetp.ne.u32 p, %1, 1;\n@p rcp.approx.ftz.f32 %0, %0;\n}" : "+f"(rs[1]) : "r"(always));
      asm volatile("lop3.b32 %0, %1, %2, %3, 0xfe;" : "=r"(lp) : "r"((l16 & 128) * 2), "r"((l16 & 256) * 4), "r"(l16 & 112));
      if (bad) continue;
      ldsm4t(ob, l16 + SM_OB + 512);
      mma16816z(f[2][0], wa, oc[0], oc[1]); mma16816z(f[2][1], wb, oc[2], oc[3]);
      mma16816z(f[0][0], wo[0], oc[0], oc[1]); mma16816z(f[0][1], wo[4], oc[2], oc[3]);
      mma16816z(f[1][0], w1[0], oc[0], oc[1]); mma16816z(f[1][1], w1[4], oc[2], oc[3]);
      ldsm4t_in(oc, l16 + SM_OB + 1024, always);
      mma16816(f[2][0], vx[2], ob[0], ob[1]); lds128_in(vx[2], w3a + KP(4) * WS, always);
      mma16816(f[2][1], vx[3], ob[2], ob[3]); lds128_in(vx[3], w3a + KP(5) * WS, always);
      mma16816(f[0][0], wo[1], ob[0], ob[1]); mma16816(f[0][1], wo[5], ob[2], ob[3]);
      mma16816(f[1][0], w1[1], ob[0], ob[1]); mma16816(f[1][1], w1[5], ob[2], ob[3]);
      ldsm4t_in(ob, l16 + SM_OB + 1536, always);
      mma16816(f[0][0], wo[2], oc[0], oc[1]); mma16816(f[0][1], wo[6], oc[2], oc[3]);
      mma16816(f[2][0], vx[2], oc[0], oc[1]); lds128_in(vx[2], w3a + KP(6) * WS, always);
      mma16816(f[2][1], vx[3], oc[2], oc[3]); lds128_in(vx[3], w3a + KP(7) * WS, always);
      mma16816(f[1][0], w1[2], oc[0], oc[1]); mma16816(f[1][1], w1[6], oc[2], oc[3]);
      mma16816(f[0][0], wo[3], ob[0], ob[1]); mma16816(f[0][1], wo[7], ob[2], ob[3]);
      mma16816(f[1][0], w1[3], ob[0], ob[1]); mma16816(f[1][1], w1[7], ob[2], ob[3]);
      mma16816(f[2][0], vx[2], ob[0], ob[1]); mma16816(f[2][1], vx[3], ob[2], ob[3]);
      bar_arrive(7, NII < 18 ? 384 : 256);
      lds128_in(ob, sb + SC_DEAD, always);
      uint32_t h[3][2];
#pragma unroll
      for (int j = 0; j < 3; j++)
#pragma unroll
        for (int i = 0; i < 2; i++)
        {
          scale_sum(f[j][1][2 * i], f[j][0][2 * i], rs[0], always); scale_sum(f[j][1][2 * i + 1], f[j][0][2 * i + 1], rs[1], always);
          h[j][i] = pack_f16(f[j][1][2 * i], f[j][1][2 * i + 1]);
        }
      const uint32_t rofs = RANK * 32768;
      red_f16x8(slot(s, RANK >> 1, rofs), h[0][0], h[1][0], h[2][0], 0x3c00u);
      red_f16x8(slot(s, (RANK >> 1) ^ 1, rofs), h[0][1], h[1][1], h[2][1], 0x3c00u);
      if (NII == 18) bar_arrive(10, 256);
      SCHED_FENCE(5);
      l16 += ob[B7R];
    }
    {
    PROF(8);
    const uint32_t ma0 = l16 + SM_MEM + w * 128 + (LV >> 3) * 896 + nh * 512;
    const unsigned char* const sl[2] = {slot(s, nh, 0), slot(s, nh ^ 1, 0)};
    uint32_t dl = gtime() - 1984;
    uint32_t late = latest_hint(hints, dl, s);
    if (late >= 64) {
      int n = 0;
#pragma unroll 1
      do {
        hints = load_hints(hint_addr(s));
        dl = gtime() - 1984;
        late = latest_hint(hints, dl, s);
      } while (late >= 64 && ++n < SPIN_LIMIT);
    }
    dl += late * 32 + tm.poll;
    PROF(9);
    {
      auto wait_until = [&](uint32_t t) {
        asm volatile("{\n.reg .pred p;\n.reg .s32 c;\n.reg .u64 t;\nTL: mov.u64 t, %%globaltimer;\ncvt.u32.u64 c, t;\nsub.s32 c, c, %0;\nsetp.lt.s32 p, c, 0;\n@p bra.uni TL;\n}" :: "r"(t + (l16 & 15)) : "memory");
      };
      uint4 v[2][3];
      auto load = [&](int c) {
#pragma unroll
        for (int r = 0; r < 3; r++) v[c][r] = ldg_relaxed(sl[c ^ (r >> 1)] + r * 32768);
      };
      auto decode = [&](int c, int n) {
        uint32_t q[9];
        __half2 hm;
        const uint32_t ma = ma0 ^ (c * 512);
#pragma unroll
        for (int i = 0; i < 9; i++) {
          const uint32_t h = i % 3 == 0 ? v[c][i / 3].x : (i % 3 == 1 ? v[c][i / 3].y : v[c][i / 3].z);
          const float2 f = __half22float2(*(const __half2*)&h);
          q[i] = pack_bf16(f.x, f.y);
          hm = i ? __hmax2(hm, __habs2(*(const __half2*)&h)) : __habs2(*(const __half2*)&h);
        }
#pragma unroll
        for (int r = 0; r < 3; r++) stsm4(ma + r * 4096, q[3 * r], q[3 * r + 1], q[3 * r + 2], r < 2 ? v[c][r].w : *(const uint32_t*)&hm);
        const bool done = __all_sync(0xffffffffu, v[c][0].w == 0x5000u && v[c][1].w == 0x5000u && v[c][2].w == 0x5000u) || n > SPIN_LIMIT;
        asm volatile("{\n.reg .pred p;\nsetp.ne.u32 p, %0, 0;\n@p bar.arrive %1, 256;\n}" :: "r"((int)done), "r"(1 + c) : "memory");
        return done;
      };
      if (LEAD) { wait_until(dl - LEAD); load(1); }
      wait_until(dl);
      PROF(10);
      int n = 0;
#pragma unroll 1
      do {
        load(0);
        if (!LEAD) load(1);
        asm volatile("{\n.reg .pred p;\nsetp.eq.u32 p, %0, 0;\n@p bar.sync 13, 384;\n}" :: "r"(n) : "memory");
      } while (!decode(0, n++));
      PROF(11);
#pragma unroll 1
      while (!decode(1, n++)) load(1);
      bar_arrive(9, 256);
      PROF(12);
    }
    PROF(13);
    if (++s == NSEG - 1) break;
    }
  }
#undef fence_reg
  if (RANK < 2) bar_arrive(4, 256);
  bar_sync(0, 384);
  cluster_sync();
}

__global__ void __cluster_dims__(3, 1, 1) __launch_bounds__(384, 1)
rec_kernel(const __grid_constant__ RMaps tm, const bf16* __restrict__ x, const bf16* __restrict__ mem0) {
  extern __shared__ __align__(1024) unsigned char smem_raw[];
  const uint32_t sb = smem_u32(smem_raw);
  const int tid = threadIdx.x, lane = tid & 31;
  const int wg = __shfl_sync(0xffffffffu, tid >> 7, 0);
  const int w = __shfl_sync(0xffffffffu, (tid >> 5) & 3, 0);
  uint32_t rank; asm("mov.u32 %0, %%cluster_ctarank;" : "=r"(rank));
  STAMP(0);
  asm volatile("griddepcontrol.launch_dependents;" ::: "memory");

  if (wg < 2) {
    asm volatile("setmaxnreg.inc.sync.aligned.u32 192;");
    if (tid == 0) {
      for (int i = 0; i < 3; i++) { mbar_init(sb + MB_W + 8 * i, 1); mbar_init(sb + MB_X + 8 * i, 1); }
      mbar_init(sb + MB_WO, 1); mbar_init(sb + MB_WO3, 1);
      mbar_init(sb + MB_S, rank < 2 ? 5 : 6);
      mbar_init(sb + MB_F, 1); mbar_init(sb + MB_XS, 1);
      mbar_init(sb + MB_VX, 1); mbar_init(sb + MB_VX + 8, 1);
      asm volatile("fence.mbarrier_init.release.cluster;" ::: "memory");
      fence_async();
      const int h = blockIdx.x / 3;
      const CUtensorMap* m0 = rank < 2 ? &tm.wk : &tm.wv;
      const CUtensorMap* m1 = rank < 2 ? &tm.wq : &tm.wv;
      const int c0 = h * DH + (rank == 1 ? 64 : 0), c1 = h * DH + (rank == 0 ? 0 : 64);
      auto load_w = [&](int c) {
        mbar_expect(sb + MB_W + 8 * c, 49152);
        tma_load(sb + SM_STAGE + c * 49152, m0, c0, c * 192, sb + MB_W + 8 * c);
        tma_load(sb + SM_STAGE + c * 49152 + 24576, m1, c1, c * 192, sb + MB_W + 8 * c);
      };
      for (int i = 0; i < 3; i++) mbar_expect(sb + MB_X + 8 * i, XT);
      if (blockIdx.x < NSEG) { mbar_expect(sb + MB_XS, XT); bulk_load(sb + SM_X, x + blockIdx.x * 32 * DM, XT, sb + MB_XS); }
      for (int c = 0; c < WPOS; c++) load_w(c);
      mbar_expect(sb + MB_WO3, 32768 + 8 * DM * 2);
      tma_load(sb + SM_WOST, &tm.wo, rank * 192 + 64, h * DH, sb + MB_WO3);
      tma_load(sb + SM_WO3, &tm.wo, rank * 192 + 128, h * DH, sb + MB_WO3);
      bulk_load(sb + SM_M0, mem0, 8 * DM * 2, sb + MB_WO3);
      tma_prefetch(&tm.wo, rank * 192, h * DH);
      if (blockIdx.x >= NSEG) tma_load3(sb + SM_X, &tm.x, 0, sb + MB_X);
      for (int c = WPOS; c < 3; c++) load_w(c);
      mbar_expect(sb + MB_WO, 16384);
      mbar_expect(sb + MB_S, rank < 2 ? 640 + 2048 : 1280);
      mbar_expect(sb + MB_VX, 8192); mbar_expect(sb + MB_VX + 8, 8192);
    }
    __syncwarp();
    QSTAMP(0);
    if (tid < 32) bar_arrive(0, 160);
    QSTAMP(1);
    proj_role(sb, tm, rank, wg, w, lane);
  } else {
    asm volatile("setmaxnreg.dec.sync.aligned.u32 120;");
    attn_role(sb, smem_raw, tm, rank, x, mem0, w, lane);
  }
}

constexpr int NAUX = 36;
constexpr int A_ST = 6, A_STAGE = 8192 + 12288, A_W8 = A_ST * A_STAGE, A_EXC = A_W8 + A_ST * 1536, A_ROWS = 57;
constexpr int A_XT = 3 * XT, A_XW = A_XT + 3 * 4096;
constexpr int A_IN = A_EXC + 8 * 2304, A_INB = 3 * SEGB, A_OST = A_IN + 2 * A_INB, A_P = A_OST + 8192, A_G = A_P + 3072;
constexpr int A_BAR = A_G + 1024;
constexpr int A_TOTAL = A_BAR + 512;
static_assert(A_IN % 1024 == 0 && A_IN >= 4 * XT && A_IN + 64 * DM * 2 <= A_BAR && A_TOTAL <= 232448, "side kernel shared memory");
struct AMaps { CUtensorMap x, wa, wa8, o, o3, wob, woa; const unsigned char* red; uint32_t poll; };

DI void wgmma_n192_ss_nt(float* d, uint64_t da, uint64_t db, int acc) {
  asm volatile("{\n.reg .pred p;\nsetp.ne.b32 p, %98, 0;\n"
               "wgmma.mma_async.sync.aligned.m64n192k16.f32.bf16.bf16 {"
               "%0,%1,%2,%3,%4,%5,%6,%7,%8,%9,%10,%11,%12,%13,%14,%15,%16,%17,%18,%19,%20,%21,%22,%23,%24,%25,%26,%27,%28,%29,%30,%31,"
               "%32,%33,%34,%35,%36,%37,%38,%39,%40,%41,%42,%43,%44,%45,%46,%47,%48,%49,%50,%51,%52,%53,%54,%55,%56,%57,%58,%59,%60,%61,%62,%63,"
               "%64,%65,%66,%67,%68,%69,%70,%71,%72,%73,%74,%75,%76,%77,%78,%79,%80,%81,%82,%83,%84,%85,%86,%87,%88,%89,%90,%91,%92,%93,%94,%95"
               "}, %96, %97, p, 1, 1, 0, 1;\n}\n"
               : ACC8(d, 0), ACC8(d, 8), ACC8(d, 16), ACC8(d, 24), ACC8(d, 32), ACC8(d, 40), ACC8(d, 48), ACC8(d, 56),
                 ACC8(d, 64), ACC8(d, 72), ACC8(d, 80), ACC8(d, 88) : "l"(da), "l"(db), "r"(acc));
}
DI void wgmma_n24_ss_nt(float* d, uint64_t da, uint64_t db, int acc) {
  asm volatile("{\n.reg .pred p;\nsetp.ne.b32 p, %14, 0;\n"
               "wgmma.mma_async.sync.aligned.m64n24k16.f32.bf16.bf16 {%0,%1,%2,%3,%4,%5,%6,%7,%8,%9,%10,%11}, %12, %13, p, 1, 1, 0, 1;\n}\n"
               : ACC8(d, 0), "+f"(d[8]), "+f"(d[9]), "+f"(d[10]), "+f"(d[11]) : "l"(da), "l"(db), "r"(acc));
}
DI void tma_load3d(uint32_t dst, const CUtensorMap* m, int c0, int c1, int c2, uint32_t mb) {
  asm volatile("cp.async.bulk.tensor.3d.shared::cluster.global.mbarrier::complete_tx::bytes [%0], [%1, {%3, %4, %5}], [%2];"
               :: "r"(dst), "l"(m), "r"(mb), "r"(c0), "r"(c1), "r"(c2) : "memory");
}
DI uint32_t trans8(uint32_t x) { uint32_t r; asm("movmatrix.sync.aligned.m8n8.trans.b16 %0, %1;" : "=r"(r) : "r"(x)); return r; }
DI void wgmma_n32_ss_tn(float* d, uint64_t da, uint64_t db, int on) {
  asm volatile("{\n.reg .pred p;\nsetp.ne.b32 p, %18, 0;\n"
               "@p wgmma.mma_async.sync.aligned.m64n32k16.f32.bf16.bf16 {%0,%1,%2,%3,%4,%5,%6,%7,%8,%9,%10,%11,%12,%13,%14,%15}, "
               "%16, %17, 1, 1, 1, 1, 0;\n}\n"
               : ACC8(d, 0), ACC8(d, 8) : "l"(da), "l"(db), "r"(on));
}
DI void wgmma_n40_ss(float* d, uint64_t da, uint64_t db, int acc) {
  asm volatile("{\n.reg .pred p;\nsetp.ne.b32 p, %22, 0;\n"
               "wgmma.mma_async.sync.aligned.m64n40k16.f32.bf16.bf16 {%0,%1,%2,%3,%4,%5,%6,%7,%8,%9,%10,%11,%12,%13,%14,%15,%16,%17,%18,%19}, "
               "%20, %21, p, 1, 1, 1, 1;\n}\n"
               : ACC8(d, 0), ACC8(d, 8), "+f"(d[16]), "+f"(d[17]), "+f"(d[18]), "+f"(d[19]) : "l"(da), "l"(db), "r"(acc));
}
DI uint2 ldg_relaxed64(const void* p) {
  uint2 v; asm volatile("ld.relaxed.gpu.global.v2.b32 {%0,%1}, [%2];" : "=r"(v.x), "=r"(v.y) : "l"(p) : "memory"); return v;
}
template <int ST> DI void ldg8x64(uint32_t* m, const void* p) {
  asm volatile("ld.relaxed.gpu.global.v2.b32 {%0,%1}, [%16];\nld.relaxed.gpu.global.v2.b32 {%2,%3}, [%16 + %17];\n"
               "ld.relaxed.gpu.global.v2.b32 {%4,%5}, [%16 + %18];\nld.relaxed.gpu.global.v2.b32 {%6,%7}, [%16 + %19];\n"
               "ld.relaxed.gpu.global.v2.b32 {%8,%9}, [%16 + %20];\nld.relaxed.gpu.global.v2.b32 {%10,%11}, [%16 + %21];\n"
               "ld.relaxed.gpu.global.v2.b32 {%12,%13}, [%16 + %22];\nld.relaxed.gpu.global.v2.b32 {%14,%15}, [%16 + %23];"
               : "=r"(m[0]), "=r"(m[1]), "=r"(m[2]), "=r"(m[3]), "=r"(m[4]), "=r"(m[5]), "=r"(m[6]), "=r"(m[7]),
                 "=r"(m[8]), "=r"(m[9]), "=r"(m[10]), "=r"(m[11]), "=r"(m[12]), "=r"(m[13]), "=r"(m[14]), "=r"(m[15])
               : "l"(p), "n"(ST), "n"(2 * ST), "n"(3 * ST), "n"(4 * ST), "n"(5 * ST), "n"(6 * ST), "n"(7 * ST) : "memory");
}
template <int ST> DI void ldg4x128(uint32_t* m, const void* p) {
  asm volatile("ld.relaxed.gpu.global.v4.b32 {%0,%1,%2,%3}, [%16];\nld.relaxed.gpu.global.v4.b32 {%4,%5,%6,%7}, [%16 + %17];\n"
               "ld.relaxed.gpu.global.v4.b32 {%8,%9,%10,%11}, [%16 + %18];\nld.relaxed.gpu.global.v4.b32 {%12,%13,%14,%15}, [%16 + %19];"
               : "=r"(m[0]), "=r"(m[1]), "=r"(m[2]), "=r"(m[3]), "=r"(m[4]), "=r"(m[5]), "=r"(m[6]), "=r"(m[7]),
                 "=r"(m[8]), "=r"(m[9]), "=r"(m[10]), "=r"(m[11]), "=r"(m[12]), "=r"(m[13]), "=r"(m[14]), "=r"(m[15])
               : "l"(p), "n"(ST), "n"(2 * ST), "n"(3 * ST) : "memory");
}
template <int N, int ST> DI bool stale(const uint32_t* m, uint32_t tag) {
  uint32_t x = m[0] ^ tag;
#pragma unroll
  for (int i = 1; i < N; i++) asm("lop3.b32 %0, %0, %1, %2, 0xf6;" : "+r"(x) : "r"(m[i * ST]), "r"(tag));
  return __any_sync(0xffffffffu, x & 1);
}
DI bool mbar_test(uint32_t b, uint32_t par) {
  uint32_t r; asm volatile("{\n.reg .pred p;\nmbarrier.test_wait.parity.shared::cta.b64 p, [%1], %2;\nselp.u32 %0, 1, 0, p;\n}" : "=r"(r) : "r"(b), "r"(par) : "memory");
  return r;
}
DI int wait_flags(const unsigned* p, bool active, unsigned base, int seg) {
  int n = 0, m;
  while (true) {
    m = __reduce_min_sync(0xffffffffu, active ? (int)(ldg_acquire32(p) - base) : NSEG);
    if (m > seg || ++n > SPIN_LIMIT) break;
    __nanosleep((YP & 32) ? 400 : 40);
  }
  return max(m, seg + 1);
}
DI void wait_count(const unsigned* p, unsigned target) {
  int n = 0;
  unsigned v;
  while (true) {
    asm volatile("ld.acquire.gpu.global.b32 %0, [%1];" : "=r"(v) : "l"(p) : "memory");
    if ((int)(v - target) >= 0 || ++n > SPIN_LIMIT) break;
    __nanosleep(64);
  }
}
#define PACE_NEXT 800
#define PING 1
#define FLAG 2
#define FPOS 1
#define QB 1
#define Q_LO 0
#define Q_HI 320
DI void tick_wait(uint32_t pace, int step) {
  const int n = lds32(pace);
  if (n <= step) mbar_wait(pace + 8, n & 1);
}
DI void quiet_wait(uint32_t pace) {
  uint32_t n, d;
  lds64(pace, n, d);
  if (n - 1 < NSEG - 2 && (int)(gtime() - d) > Q_HI) mbar_wait(pace + 8, n & 1);
}
DI void sleep_until(uint32_t t) {
  for (int n = 0; n < 64; n++) {
    const int r = t - gtime();
    if (r <= 0) break;
    __nanosleep(r >> 1);
  }
}
DI void aux_barrier(int i, unsigned epoch) {
  asm volatile("fence.proxy.async;" ::: "memory");
  asm volatile("red.release.gpu.global.add.u32 [%0], 1;" :: "l"(&g_abar[i * 32]) : "memory");
  wait_count(&g_abar[i * 32], NAUX * (epoch + 1));
  asm volatile("fence.proxy.async;" ::: "memory");
}

__global__ void __launch_bounds__(512, 1)
aux_kernel(const __grid_constant__ AMaps tm, const bf16* __restrict__ x, const bf16* __restrict__ gate_w, bf16* __restrict__ out) {
  extern __shared__ __align__(1024) unsigned char smem_raw[];
  const uint32_t sb = smem_u32(smem_raw);
  const uint32_t full1 = sb + A_BAR, empty1 = full1 + 8 * A_ST, fullw = empty1 + 8 * A_ST, full3 = fullw + 8, empty3 = full3 + 32,
                 fulla = empty3 + 32, emptya = fulla + 16, fullg = emptya + 16, pace = fullg + 8;
  const int tid = threadIdx.x, lane = tid & 31, cta = blockIdx.x;
  const int wg = __shfl_sync(0xffffffffu, tid >> 7, 0), w = __shfl_sync(0xffffffffu, (tid >> 5) & 3, 0);
  ASTAMP(14);
  const unsigned epoch = *(volatile unsigned*)&g_epoch2;
  if (tid == 0) {
    for (int i = 0; i < A_ST; i++) { mbar_init(full1 + 8 * i, 1); mbar_init(empty1 + 8 * i, 8); }
    mbar_init(fullw, 1); mbar_init(fullg, 1);
    for (int i = 0; i < 2; i++) { mbar_init(fulla + 8 * i, 2); mbar_init(emptya + 8 * i, 4); }
    sts64(pace, 0, 0); mbar_init(pace + 8, 1); sts32(pace + 16, 0);
    for (int i = 0; i < 4; i++) { mbar_init(full3 + 8 * i, 1); mbar_init(empty3 + 8 * i, cta < NH ? 8 : 4); }
    fence_async();
  }
  __syncthreads();
  ASTAMP(0);
  const bool wide = cta < NH;
  auto p3_ks = [&](int g) { return wide ? cta >> 2 : 2 * (cta - NH) + g; };
  auto p3_mt = [&](int g) { return wide ? 2 * (cta & 3) + g : 8; };
  const uint32_t xt = sb + (wide ? A_XT : A_IN), xw = sb + (wide ? A_XW : A_IN + 16384);
  const unsigned fbase = epoch * NSEG;
  if (wg == 3) {
    asm volatile("setmaxnreg.dec.sync.aligned.u32 56;");
    if (w == 1 && cta < NH) {
#pragma unroll 1
      for (int seg = 0; seg < ((XP & 2048) ? 0 : NSEG); seg++) {
        bar_arrive(5, 160);
        if (seg > 0 && lane == 0) {
          asm volatile("cp.async.bulk.wait_group 0;" ::: "memory");
          stg_relaxed32(&g_oflag[cta * 32], fbase + seg);
        }
        __syncwarp();
        bar_sync(4, 160);
        if (QM & 16) tick_wait(pace, seg + 1);
        if (lane == 0) {
          fence_async();
          if (!(YP & 2)) {
          tma_store(&tm.o, sb + A_OST, cta * DH, seg * 32);
          tma_store(&tm.o, sb + A_OST + 4096, cta * DH + 64, seg * 32);
          }
          asm volatile("cp.async.bulk.commit_group;" ::: "memory");
          asm volatile("cp.async.bulk.wait_group.read 0;" ::: "memory");
        }
        __syncwarp();
      }
      if (lane == 0) {
        asm volatile("cp.async.bulk.wait_group 0;" ::: "memory");
        stg_relaxed32(&g_oflag[cta * 32], fbase + NSEG);
      }
    }
    if (w == 2 && cta < NH) {
      const uint32_t ktag = (epoch + 1) & 1, ma = sb + A_IN + 8192 + lane * 16;
      int avail = 0;
      bar_sync(10, 64);
#pragma unroll 1
      for (int seg = 0; seg < ((XP & 2048) ? 0 : NSEG); seg++) {
        if (avail <= seg) avail = wait_flags(&g_sflag[(cta * 3 + min(lane, 2)) * 8], true, fbase, seg);
        if (QM & 8) tick_wait(pace, seg);
        const unsigned char* km = g_km + (size_t)(seg * NH + cta) * 4096 + lane * 8;
        uint32_t k[16], v[16];
        auto fetch = [&]() { ldg8x64<256>(k, km); ldg4x128<512>(v, km + 2048 + lane * 8); };
        const float g = __ldcg(&g_gate[seg * 32 + lane]);
        fetch();
        const uint32_t b = seg & 1, full = fulla + 8 * b, mb = ma + b * A_INB;
        mbar_wait(emptya + 8 * b, (~seg >> 1) & 1);
        if (lane == 0) mbar_expect(full, (YP & 8) ? 0 : 24576);
        __syncwarp();
        if (lane < 3 && !(YP & 8)) bulk_load(sb + A_IN + b * A_INB + lane * SEGB, g_seg + ((size_t)(seg & RING) * 96 + cta * 3 + lane) * 8192, 8192, full);
        int n = 0;
#pragma unroll 1
        while ((stale<8, 2>(k, ktag) | stale<4, 4>(v, ktag)) && ++n < SPIN_LIMIT) { if (seg < NSEG - 1) __nanosleep(200); fetch(); }
#pragma unroll
        for (int i = 0; i < 4; i++) {
          stsm4(mb + (i >> 1) * SEGB + (i & 1) * 512, k[4 * i], k[4 * i + 1], k[4 * i + 2], k[4 * i + 3]);
          stsm4(mb + 2 * SEGB + (lane >> 4) * 768 + i * 256, v[4 * i], v[4 * i + 1], v[4 * i + 2], v[4 * i + 3]);
        }
        sts32(sb + A_G + b * 128 + lane * 4, __float_as_uint(1.f - g));
        fence_async();
        __syncwarp();
        if (lane == 0) mbar_arrive(full);
      }
    }
    if (w == 3 && QM) {
      const unsigned char* const hp = tm.red + HINT_OFF + 65536 + (cta & 1) * 4096 + min(lane, 23) * 4;
      uint32_t d = 0;
      int s = 0, n = 0;
#pragma unroll 1
      while (s < NSEG - 1) {
        const uint32_t h = ldg_relaxed32(hp + RED_SLOT(s)), t = (gtime() - 1984) & ~31u, late = latest_hint(h, t, s);
        if (late < 64) {
          d = t + late * 32 + tm.poll + Q_LO;
          sleep_until(d);
          s++; n = 0;
          if (lane == 0) { mbar_arrive(pace + 8); sts64(pace, s < NSEG - 1 ? s : 2 * NSEG, d); }
          sleep_until(d + PACE_NEXT);
        } else {
          if (++n > (s ? 16 : 256) || lds32(pace + 16)) break;
          if (!s) __nanosleep(100);
        }
      }
      if (s < NSEG - 1 && lane == 0) { mbar_arrive(pace + 8); sts64(pace, 2 * NSEG, d); }
    }
    if (w != 0) return;
    const bool lead = lane == 0;
    if (lead) {
#pragma unroll 1
      for (int it = 0, st = 0, ph = 1, k = 0, col = (cta & 1) * (DM / 2); it < ((XP & 256) ? 0 : 72); it++) {
        mbar_wait(empty1 + 8 * st, ph);
        if (QM & 1) quiet_wait(pace);
        mbar_expect(full1 + 8 * st, A_STAGE + 1536);
        tma_load3d(sb + st * A_STAGE, &tm.x, k, (cta >> 1) * A_ROWS - 7, 0, full1 + 8 * st);
        tma_load3d(sb + st * A_STAGE + 8192, &tm.wa, col, k, 0, full1 + 8 * st);
        tma_load3d(sb + A_W8 + st * 1536, &tm.wa8, col + 64, k, 0, full1 + 8 * st);
        if (++st == A_ST) { st = 0; ph ^= 1; }
        k += 32;
        if (k == DM) { k = 0; col += 72; }
      }
    }
    __syncwarp(); bar_sync(6, 288);
    auto load_wo = [&](uint32_t dst, int g, int kb, uint32_t mb) {
      if (kb < 64) tma_load(dst, &tm.wob, p3_mt(g) * 64, kb * 64, mb);
      else tma_load(dst, &tm.woa, p3_mt(g) * 64, (kb - 64) * 64, mb);
    };
    if (QM & 2) quiet_wait(pace);
    if (lead) mbar_expect(fullw, 18 * 8192);
    __syncwarp();
    if (lane < 18) load_wo(sb + lane * 8192, lane >= 9, p3_ks(lane >= 9) * 9 + lane % 9, fullw);
    __syncwarp();
    if (lead) aux_barrier(1, epoch);
    __syncwarp(); bar_sync(6, 288);
    {
      int avail = 0, sl = 0, ph = 1;
      const int h = (9 * p3_ks(0) >> 1) + lane;
#pragma unroll 1
      for (int seg = 0; seg < ((XP & 2048) ? 0 : NSEG); seg++) {
        if (avail <= seg) avail = wait_flags(&g_oflag[min(h, NH - 1) * 32], lane < (wide ? 5 : 9), fbase, seg);
        SSTAMP(seg, 4);
        for (int g = 0; g < (wide ? 1 : 2); g++) {
          const int ks = p3_ks(g);
          mbar_wait(empty3 + 8 * sl, ph);
          if (QM & 4) tick_wait(pace, seg + (QM >> 4 & 1) + 1);
          if (lead && (YP & 4)) mbar_arrive(full3 + 8 * sl);
          else if (lead) {
            mbar_expect(full3 + 8 * sl, XT + (ks == 7 ? (seg ? 4096 : wide ? 20480 : 12288) : 0));
            tma_load3d(sb + sl * XT, &tm.o3, 0, seg * 32, ks * 9, full3 + 8 * sl);
            if (ks == 7) {
              tma_load(xt + sl * 4096, &tm.o, 72 * 64, seg * 32, full3 + 8 * sl);
              if (seg == 0) { load_wo(xw + 8192, 1, 72, full3 + 8 * sl); if (wide) load_wo(xw, 0, 72, full3 + 8 * sl); }
            }
          }
          __syncwarp();
          if (++sl == (wide ? 3 : 4)) { sl = 0; ph ^= 1; }
        }
      }
    }
    sts32(pace + 16, 1);
    __syncwarp(); bar_sync(6, 288);
    asm volatile("griddepcontrol.wait;" ::: "memory");
  } else if (wg == 2) {
    asm volatile("setmaxnreg.dec.sync.aligned.u32 72;");
    if (cta < NH) {
      if (tid == 256) { mbar_expect(fullg, 64 * DM * 2); bulk_load(sb + A_IN, x + cta * 64 * DM, 64 * DM * 2, fullg); }
      uint32_t gw[9];
#pragma unroll
      for (int j = 0; j < 9; j++) gw[j] = ((const uint32_t*)gate_w)[j * 32 + lane];
      mbar_wait(fullg, 0);
      float mine = 0.f;
#pragma unroll 4
      for (int u = 0; u < 16; u++) {
        float d0 = 0.f, d1 = 0.f;
#pragma unroll
        for (int j = 0; j < 9; j++) {
          const uint32_t a = lds32(sb + A_IN + (w * 16 + u) * (DM * 2) + j * 128 + lane * 4);
          d0 = fmaf(bf_lo(a), bf_lo(gw[j]), d0); d1 = fmaf(bf_hi(a), bf_hi(gw[j]), d1);
        }
        d0 = warp_sum(d0 + d1);
        if (lane == u) mine = d0;
      }
      if (lane < 16) g_gate[cta * 64 + w * 16 + lane] = 1.f / (1.f + __expf(-mine));
      fence_async();
    }
    bar_sync(3, 128);
    if (tid == 256) { aux_barrier(0, epoch); if (cta == 0) *(volatile unsigned*)&g_epoch2 = epoch + 1; }
    __syncwarp();
    bar_sync(3, 128);
    if (w == 0) bar_arrive(8, 288);
    if (w == 1 && cta < NH) bar_arrive(10, 64);
    if (cta < NH) {
      CDECL;
#pragma unroll 1
      for (int seg = 0; seg < ((XP & 2048) ? 0 : NSEG); seg++) {
        CSTAMP(0);
        const uint32_t in = sb + A_IN + (seg & 1) * A_INB;
        const uint64_t qd = make_desc(in, 128, 1024, 0);
        mbar_wait(fulla + 8 * (seg & 1), (seg >> 1) & 1);
        CSTAMP(3);
        SSTAMP(seg, 0);
        float d[2][16];
        {
          float a[20];
          WG_FENCE();
#pragma unroll
          for (int k = 0; k < ((YP & 16) ? 1 : 8); k++) wgmma_n40_ss(a, qd + ((k >> 2) * SEGB + (k & 3) * 256 >> 4), qd + ((k >> 2) * SEGB + (k & 3) * 256 + 4096 >> 4), k > 0);
          const uint32_t ga = sb + A_G + (seg & 1) * 128 + (w & 1) * 64 + (lane >> 2) * 4;
          const float f0 = __uint_as_float(lds32(ga)), f1 = __uint_as_float(lds32(ga + 32));
          WG_COMMIT();
          WG_WAIT(0);
          CSTAMP(5);
          SSTAMP(seg, 1);
          if (w < 2) {
            const int lim = w * 16 + (lane >> 2) - 2 * (lane & 3);
            float m0 = -3.0e38f, m1 = -3.0e38f;
#pragma unroll
            for (int i = 0; i < 20; i++) {
              a[i] *= SM_SCALE * LOG2E;
              if (i < 16 && (i >> 2) * 8 + (i & 1) - (i & 2) * 4 > lim) a[i] = -1.0e9f * LOG2E;
              if (i & 2) m1 = fmaxf(m1, a[i]); else m0 = fmaxf(m0, a[i]);
            }
#pragma unroll
            for (int o = 1; o < 4; o <<= 1) { m0 = fmaxf(m0, __shfl_xor_sync(0xffffffffu, m0, o)); m1 = fmaxf(m1, __shfl_xor_sync(0xffffffffu, m1, o)); }
            float s0 = 0.f, s1 = 0.f;
#pragma unroll
            for (int i = 0; i < 20; i++) { a[i] = ex2(a[i] - (i & 2 ? m1 : m0)); if (i & 2) s1 += a[i]; else s0 += a[i]; }
#pragma unroll
            for (int o = 1; o < 4; o <<= 1) { s0 += __shfl_xor_sync(0xffffffffu, s0, o); s1 += __shfl_xor_sync(0xffffffffu, s1, o); }
            s0 = f0 * rcp(s0); s1 = f1 * rcp(s1);
            uint32_t p[10];
#pragma unroll
            for (int i = 0; i < 10; i++) p[i] = pack_bf16(a[2 * i] * (i & 1 ? s1 : s0), a[2 * i + 1] * (i & 1 ? s1 : s0));
            const uint32_t pa = sb + A_P + (2 * w + ((lane >> 3) & 1)) * 768 + (lane >> 4) * 128 + (lane & 7) * 16;
            stsm4t(pa, p[0], p[1], p[2], p[3]); stsm4t(pa + 256, p[4], p[5], p[6], p[7]); stsm4t(pa + 512, p[8], p[9], 0, 0);
            CSTAMP(6);
            fence_async();
            CSTAMP(7);
          }
        }
        CSTAMP(8);

        bar_sync(5, 160);
        CSTAMP(10);
        SSTAMP(seg, 2);
        const uint64_t pd = make_desc(sb + A_P, 128, 768, 0), vd = make_desc(in + 2 * SEGB, 128, 512, 0), md = make_desc(in + 2 * SEGB + 8192, 0, 128, 0);
        WG_FENCE();
#pragma unroll
        for (int i = 0; i < 2; i++) {
          wgmma_n32_ss<0>(d[i], vd + i * 256, pd, 0);
          wgmma_n32_ss<0>(d[i], vd + i * 256 + 16, pd + 16, 1);
          wgmma_n32_ss<0>(d[i], md + i * 64, pd + 32, 1);
        }
        WG_COMMIT();
        WG_WAIT(0);
        CSTAMP(11);
        if (lane == 0) mbar_arrive(emptya + 8 * (seg & 1));
#pragma unroll
        for (int i = 0; i < 2; i++) {
          const uint32_t oa = sb + A_OST + i * 4096 + ((lane & 7) + ((lane >> 4) << 3)) * 128 + (((2 * w + ((lane >> 3) & 1)) ^ (lane & 7)) << 4);
          stsm4t(oa, pack_bf16(d[i][0], d[i][1]), pack_bf16(d[i][2], d[i][3]), pack_bf16(d[i][4], d[i][5]), pack_bf16(d[i][6], d[i][7]));
          stsm4t(oa + 2048, pack_bf16(d[i][8], d[i][9]), pack_bf16(d[i][10], d[i][11]), pack_bf16(d[i][12], d[i][13]), pack_bf16(d[i][14], d[i][15]));
        }
        CSTAMP(12);
        bar_sync(4, 160);
        SSTAMP(seg, 3);
      }
      CDUMP;
    }
  } else {
    asm volatile("setmaxnreg.inc.sync.aligned.u32 192;");
    {
      const int g = lane >> 2, t = lane & 3, r0 = (cta >> 1) * A_ROWS - 7 + w * 16;
      const uint32_t prev = (2 * t > g ? 0xffffu : 0u) | (2 * t + 1 > g ? 0xffff0000u : 0u);
      const int k0 = r0 + 2 * t - (2 * t > g ? 8 : 0), k1 = r0 + 2 * t + 1 - (2 * t + 1 > g ? 8 : 0);
      const uint32_t slot = sb + A_EXC + (wg * 4 + w) * 2304;
      float gl = 0.f, gh = 0.f;
      int st = 0, ph = 0;
#pragma unroll 1
      for (int p = 0; p < ((XP & 256) ? 0 : 4); p++) {
        float big[96], sml[12];
#pragma unroll
        for (int i = 0; i < 96; i++) big[i] = 0.f;
#pragma unroll
        for (int i = 0; i < 12; i++) sml[i] = 0.f;
#pragma unroll 1
        for (int k = 0; k < 18; k++) {
          mbar_wait(full1 + 8 * st, ph);
          const uint64_t da = make_desc(sb + st * A_STAGE + wg * 4096, 16, 512, 2);
          const uint64_t db = make_desc(sb + st * A_STAGE + 8192, 4096, 1024, 1), dc = make_desc(sb + A_W8 + st * 1536, 128, 512, 0);
          WG_FENCE();
#pragma unroll
          for (int j = 0; j < 2; j++) { wgmma_n192_ss_nt(big, da + j * 2, db + j * 128, 1); wgmma_n24_ss_nt(sml, da + j * 2, dc + j * 16, 1); }
          WG_COMMIT();
          WG_WAIT(1);
          if (k > 0 && lane == 0) mbar_arrive(empty1 + 8 * (st ? st - 1 : A_ST - 1));
          if (++st == A_ST) { st = 0; ph ^= 1; }
        }
        WG_WAIT(0);
        ASTAMP(16 + p + wg * 16);
        if (lane == 0) mbar_arrive(empty1 + 8 * (st ? st - 1 : A_ST - 1));
        uint32_t f[3][9][2];
#pragma unroll
        for (int c = 0; c < 3; c++)
#pragma unroll
          for (int j = 0; j < 9; j++)
#pragma unroll
            for (int i = 0; i < 2; i++) {
              const float* a = j < 8 ? &big[(c * 8 + j) * 4 + 2 * i] : &sml[c * 4 + 2 * i];
              f[c][j][i] = c < 2 ? pack_bf16(a[0], a[1]) : trans8(pack_bf16(a[0], a[1]));
            }
        if (p == 0) {
          bar_sync(8, 288);
          gl = __ldcg(&g_gate[min(max(r0 + g, 0), S_LEN / 2 - 1) * 2 + wg]); gh = __ldcg(&g_gate[min(max(r0 + g + 8, 0), S_LEN / 2 - 1) * 2 + wg]);
        }
        asm volatile("cp.async.bulk.wait_group.read 0;" ::: "memory");
        __syncwarp();
#pragma unroll
        for (int j = 0; j < 8; j += 2) sts128(slot + j * 256 + lane * 16, f[1][j][1], f[2][j][1], f[1][j + 1][1], f[2][j + 1][1]);
        sts64(slot + 2048 + lane * 8, f[1][8][1], f[2][8][1]);
        bar_sync(1 + wg, 128);
        ASTAMP(24 + p + wg * 16);
        uint32_t pv[9][2];
#pragma unroll
        for (int j = 0; j < 9; j++) pv[j][0] = pv[j][1] = 0;
        if (w) {
#pragma unroll
          for (int j = 0; j < 8; j += 2) lds128(slot - 2304 + j * 256 + lane * 16, pv[j]);
          lds64(slot - 256 + lane * 8, pv[8][0], pv[8][1]);
        }
        uint32_t o[9][2];
#pragma unroll
        for (int h = 0; h < 4; h++) {
          const int j = 2 * h;
          const uint32_t qa[4] = {t >= h ? f[0][j][0] : 0, t >= h ? f[0][j][1] : 0, f[0][j + 1][0], f[0][j + 1][1]};
          const uint32_t qb0 = t <= h ? f[0][j + 2][0] : 0, qb1 = t <= h ? f[0][j + 2][1] : 0;
          float s0[4], s1[4], s2[4];
          mma16816z(s0, qa, pv[j][0], pv[j + 1][0]); mma16816z(s1, qa, f[1][j][0], f[1][j + 1][0]); mma16816z(s2, qa, f[1][j][1], f[1][j + 1][1]);
          mma1688(s0, qb0, qb1, pv[j + 2][0]); mma1688(s1, qb0, qb1, f[1][j + 2][0]); mma1688(s2, qb0, qb1, f[1][j + 2][1]);
          float a[4] = {2 * t > g ? s0[0] : s1[0], 2 * t + 1 > g ? s0[1] : s1[1], 2 * t > g ? s1[2] : s2[2], 2 * t + 1 > g ? s1[3] : s2[3]};
#pragma unroll
          for (int i = 0; i < 4; i++) a[i] = (i & 1 ? k1 : k0) + (i & 2) * 4 >= 0 ? a[i] * (0.23570226039551584f * LOG2E) : -1.0e9f * LOG2E;
          float m0 = fmaxf(a[0], a[1]), m1 = fmaxf(a[2], a[3]);
#pragma unroll
          for (int x = 1; x < 4; x <<= 1) { m0 = fmaxf(m0, __shfl_xor_sync(0xffffffffu, m0, x)); m1 = fmaxf(m1, __shfl_xor_sync(0xffffffffu, m1, x)); }
#pragma unroll
          for (int i = 0; i < 4; i++) a[i] = ex2(a[i] - (i & 2 ? m1 : m0));
          float z0 = a[0] + a[1], z1 = a[2] + a[3];
#pragma unroll
          for (int x = 1; x < 4; x <<= 1) { z0 += __shfl_xor_sync(0xffffffffu, z0, x); z1 += __shfl_xor_sync(0xffffffffu, z1, x); }
          z0 = gl * rcp(z0); z1 = gh * rcp(z1);
          const uint32_t pl = pack_bf16(a[0] * z0, a[1] * z0), ph = pack_bf16(a[2] * z1, a[3] * z1);
          const uint32_t pa[4] = {pl & prev, 0, pl & ~prev, ph & prev};
#pragma unroll
          for (int i = 0; i < 3; i++) {
            float d[4];
            mma16816z(d, pa, pv[j + i][1], f[2][j + i][0]);
            mma1688(d, 0, ph & ~prev, f[2][j + i][1]);
            const uint32_t d0 = pack_bf16(d[0], d[1]), d1 = pack_bf16(d[2], d[3]);
            o[j + i][0] = i == 0 && h > 0 && t < h ? o[j][0] : d0;
            o[j + i][1] = i == 0 && h > 0 && t < h ? o[j][1] : d1;
          }
        }
        ASTAMP(28 + p + wg * 16);
        bar_sync(1 + wg, 128);
        const uint32_t oa = slot + (lane & 15) * 144 + (lane >> 4) * 16;
#pragma unroll
        for (int j = 0; j < 8; j += 2) stsm4(oa + j * 16, o[j][0], o[j][1], o[j + 1][0], o[j + 1][1]);
        asm volatile("stmatrix.sync.aligned.m8n8.x2.shared.b16 [%0], {%1,%2};" :: "r"(oa + 128), "r"(o[8][0]), "r"(o[8][1]) : "memory");
        fence_async();
        __syncwarp();
        if (QM & 64) quiet_wait(pace);
        if (lane < 16 && w * 16 + lane >= 7 && r0 + lane < S_LEN / 2)
          asm volatile("cp.async.bulk.global.shared::cta.bulk_group [%0], [%1], 144;"
                       :: "l"(g_Ocat + (size_t)((r0 + lane) * 2 + wg) * KCAT + 4096 + (cta & 1) * (DM / 2) + p * 72), "r"(slot + lane * 144) : "memory");
        asm volatile("cp.async.bulk.commit_group;" ::: "memory");
        ASTAMP(20 + p + wg * 16);
      }
      if (XP & 256) bar_sync(8, 288);
      asm volatile("cp.async.bulk.wait_group 0;" ::: "memory");
    }
    ASTAMP(3);
    bar_sync(6, 288);
    uint32_t wa[36][4];
    mbar_wait(fullw, 0);
    const uint32_t la = sb + wg * 73728 + ((lane & 7) + ((lane >> 4) << 3)) * 128 + (((2 * w + ((lane >> 3) & 1)) ^ (lane & 7)) << 4);
#pragma unroll
    for (int k = 0; k < 36; k++) ldsm4t(wa[k], la + k * 2048);
    fence_async();
    bar_sync(6, 288);
    ASTAMP(4);
    const int ks = p3_ks(wg), mt = p3_mt(wg);
    uint32_t v[16];
    auto fetch = [&](int seg) { ldg8x64<1024>(v, g_part + (((seg & 7) * 9 + mt) * 4 + (ks & 3)) * 1024 + (tid & 127)); };
    auto finish = [&](int seg) {
      const uint32_t tagv = (~seg >> 3) & 1;
      int n = 0;
#pragma unroll 1
      while (stale<8, 2>(v, tagv) && ++n < SPIN_LIMIT) {
        if (seg < NSEG - 2) __nanosleep(100);
        fetch(seg);
      }
      float own[4] = {bf_lo(v[0]), bf_hi(v[0]), bf_lo(v[1]), bf_hi(v[1])};
#pragma unroll
      for (int j = 1; j < 8; j++) { own[0] += bf_lo(v[2 * j]); own[1] += bf_hi(v[2 * j]); own[2] += bf_lo(v[2 * j + 1]); own[3] += bf_hi(v[2 * j + 1]); }
      uint32_t p0 = pack_bf16(own[0], own[1]), p1 = pack_bf16(own[2], own[3]);
      asm volatile("movmatrix.sync.aligned.m8n8.trans.b16 %0, %0;" : "+r"(p0));
      asm volatile("movmatrix.sync.aligned.m8n8.trans.b16 %0, %0;" : "+r"(p1));
      uint32_t* o = (uint32_t*)(out + (size_t)(seg * 32 + (ks & 3) * 8 + (lane >> 2)) * DM + mt * 64 + w * 16) + (lane & 3);
      o[0] = p0; o[4] = p1;
      SSTAMP(seg, 7);
    };
    float acc[16];
#pragma unroll
    for (int i = 0; i < 16; i++) acc[i] = 0.f;
    int pend = -1, sl = wide ? 0 : wg, ph = 0;
    if (PING && wg) bar_arrive(1, 256);
    CDECL;
#pragma unroll 1
    for (int seg = 0; seg < ((XP & 2048) ? 0 : NSEG); seg++) {
      CSTAMP(0);
      const bool fin = pend >= 0 && seg - pend >= FLAG;
      if (FPOS == 0 && fin) fetch(pend);
      mbar_wait(full3 + 8 * sl, ph);
      if (FPOS == 1 && fin) fetch(pend);
      CSTAMP(1);
      if (wg) SSTAMP(seg, 5);
      if (PING) bar_sync(1 + wg, 256);
      CSTAMP(7);
      const uint64_t db = make_desc(sb + sl * XT, 16, 1024, 1);
      WG_FENCE();
#pragma unroll
      for (int k = 0; k < ((XP & 1024) ? 1 : 36); k++) wgmma_n32_rs(acc, wa[k][0], wa[k][1], wa[k][2], wa[k][3], db + (k >> 2) * 256 + (k & 3) * 2, k);
      {
        const uint64_t da = make_desc(xw + wg * 8192, 8192, 1024, 1), de = make_desc(xt + sl * 4096, 16, 1024, 1);
#pragma unroll
        for (int j = 0; j < 4; j++) wgmma_n32_ss_tn(acc, da + j * 128, de + j * 2, ks == 7);
      }
      WG_COMMIT();
      if (PING) bar_arrive(2 - wg, 256);
      CSTAMP(2);
      if (FPOS == 2 && fin) fetch(pend);
      CSTAMP(3);
      WG_WAIT(0);
      CSTAMP(4);
      if (wg) SSTAMP(seg, 6);
      if (lane == 0) mbar_arrive(empty3 + 8 * sl);
      sl += wide ? 1 : 2;
      if (sl >= (wide ? 3 : 4)) { sl -= wide ? 3 : 4; ph ^= 1; }
      uint2* dst = g_part + (((seg & 7) * 9 + mt) * 32 + ks) * 128 + (tid & 127);
      uint32_t q[8];
#pragma unroll
      for (int j = 0; j < 8; j++) q[j] = j & 1 ? pack_bf16(acc[2 * j], acc[2 * j + 1]) : (pack_bf16(acc[2 * j], acc[2 * j + 1]) & ~1u) | ((~seg >> 3) & 1);
      if (QM & 32) tick_wait(pace, seg + (QM >> 4 & 1) + 2);
      if (!(YP & 1) || q[0] == 0x12345678)
      asm volatile("st.relaxed.gpu.global.v2.b32 [%0], {%1,%2};\nst.relaxed.gpu.global.v2.b32 [%0 + 8192], {%3,%4};\n"
                   "st.relaxed.gpu.global.v2.b32 [%0 + 16384], {%5,%6};\nst.relaxed.gpu.global.v2.b32 [%0 + 24576], {%7,%8};"
                   :: "l"(dst), "r"(q[0]), "r"(q[1]), "r"(q[2]), "r"(q[3]), "r"(q[4]), "r"(q[5]), "r"(q[6]), "r"(q[7]) : "memory");
      CSTAMP(5);
      if (fin) { finish(pend); pend = -1; }
      CSTAMP(6);
      if ((seg & 1) == ks >> 2 && !(YP & 1)) pend = seg;
      if (wg && (seg & 7) == 6) ASTAMP(5 + (seg >> 3));
    }
    if (PING && !wg) bar_sync(1, 256);
    if (pend >= 0) { fetch(pend); finish(pend); }
    CDUMP;
    ASTAMP(13);
    bar_sync(6, 288);
  }
}

typedef CUresult (*EncodeFn)(CUtensorMap*, CUtensorMapDataType, cuuint32_t, void*, const cuuint64_t*, const cuuint64_t*,
                             const cuuint32_t*, const cuuint32_t*, CUtensorMapInterleave, CUtensorMapSwizzle,
                             CUtensorMapL2promotion, CUtensorMapFloatOOBfill);
#define PROMO 2
static void make_map(EncodeFn enc, CUtensorMap* m, const void* p, int rows, int cols, int box_rows) {
  cuuint64_t dims[2] = {(cuuint64_t)cols, (cuuint64_t)rows};
  cuuint64_t strides[1] = {(cuuint64_t)cols * 2};
  cuuint32_t box[2] = {64, (cuuint32_t)box_rows};
  cuuint32_t es[2] = {1, 1};
  enc(m, CU_TENSOR_MAP_DATA_TYPE_BFLOAT16, 2, (void*)p, dims, strides, box, es, CU_TENSOR_MAP_INTERLEAVE_NONE,
      CU_TENSOR_MAP_SWIZZLE_128B, (CUtensorMapL2promotion)PROMO, CU_TENSOR_MAP_FLOAT_OOB_FILL_NONE);
}

constexpr int g_poll = POLL_NS;
extern "C" void kernel_launch(void* const* d_in, const int* in_sizes, int n_in, void* d_out, int out_size) {
  const bf16* x = (const bf16*)d_in[0];
  const bf16* wqkvA = (const bf16*)d_in[1];
  const bf16* woA = (const bf16*)d_in[2];
  const bf16* mem0 = (const bf16*)d_in[4];
  const bf16* Wq = (const bf16*)d_in[5];
  const bf16* Wk = (const bf16*)d_in[6];
  const bf16* Wv = (const bf16*)d_in[7];
  const bf16* Wo = (const bf16*)d_in[8];
  const bf16* gate_w = (const bf16*)d_in[10];
  static EncodeFn enc = nullptr;
  static void *pO = nullptr, *pR = nullptr;
  if (!enc) {
    cudaDriverEntryPointQueryResult qr;
    cudaGetDriverEntryPoint("cuTensorMapEncodeTiled", (void**)&enc, cudaEnableDefault, &qr);
    cudaGetSymbolAddress(&pO, g_Ocat);
    cudaGetSymbolAddress(&pR, g_red_raw);
    cudaFuncSetAttribute(rec_kernel, cudaFuncAttributeMaxDynamicSharedMemorySize, SM_TOTAL);
    cudaFuncSetAttribute(aux_kernel, cudaFuncAttributeMaxDynamicSharedMemorySize, A_TOTAL);
  }
  RMaps rm;
  rm.poll = g_poll;
  rm.w[0] = (const unsigned char*)Wk; rm.w[1] = (const unsigned char*)Wq; rm.w[2] = (const unsigned char*)Wv; rm.w[3] = (const unsigned char*)Wo;
  rm.red = (unsigned char*)(((uintptr_t)pR + 262143) & ~(uintptr_t)262143);
  {
    cuuint64_t dims[3] = {64, S_LEN, 9}, strides[2] = {DM * 2, 128};
    cuuint32_t box[3] = {64, 32, 9}, es[3] = {1, 1, 1};
    enc(&rm.x, CU_TENSOR_MAP_DATA_TYPE_BFLOAT16, 3, (void*)x, dims, strides, box, es, CU_TENSOR_MAP_INTERLEAVE_NONE,
        CU_TENSOR_MAP_SWIZZLE_128B, CU_TENSOR_MAP_L2_PROMOTION_L2_128B, CU_TENSOR_MAP_FLOAT_OOB_FILL_NONE);
  }
  make_map(enc, &rm.wq, Wq, DM, 4096, 192);
  make_map(enc, &rm.wk, Wk, DM, 4096, 192);
  make_map(enc, &rm.wv, Wv, DM, 4096, 192);
  make_map(enc, &rm.wo, Wo, 4096, DM, 128);
  AMaps am;
  am.red = rm.red; am.poll = rm.poll;
  {
    cuuint64_t dims[3] = {DM, S_LEN / 2, 2}, strides[2] = {DM * 4, DM * 2};
    cuuint32_t box[3] = {32, 64, 2}, es[3] = {1, 1, 1};
    enc(&am.x, CU_TENSOR_MAP_DATA_TYPE_BFLOAT16, 3, (void*)x, dims, strides, box, es, CU_TENSOR_MAP_INTERLEAVE_NONE,
        CU_TENSOR_MAP_SWIZZLE_64B, CU_TENSOR_MAP_L2_PROMOTION_L2_128B, CU_TENSOR_MAP_FLOAT_OOB_FILL_NONE);
    cuuint64_t wdims[3] = {DM, DM, 3}, wstrides[2] = {DM * 6, DM * 2};
    cuuint32_t wbox[3] = {64, 32, 3}, wbox8[3] = {8, 32, 3};
    enc(&am.wa, CU_TENSOR_MAP_DATA_TYPE_BFLOAT16, 3, (void*)wqkvA, wdims, wstrides, wbox, es, CU_TENSOR_MAP_INTERLEAVE_NONE,
        CU_TENSOR_MAP_SWIZZLE_128B, CU_TENSOR_MAP_L2_PROMOTION_L2_128B, CU_TENSOR_MAP_FLOAT_OOB_FILL_NONE);
    enc(&am.wa8, CU_TENSOR_MAP_DATA_TYPE_BFLOAT16, 3, (void*)wqkvA, wdims, wstrides, wbox8, es, CU_TENSOR_MAP_INTERLEAVE_NONE,
        CU_TENSOR_MAP_SWIZZLE_NONE, CU_TENSOR_MAP_L2_PROMOTION_NONE, CU_TENSOR_MAP_FLOAT_OOB_FILL_NONE);
  }
  {
    cuuint64_t dims[3] = {64, S_LEN, KCAT / 64}, strides[2] = {KCAT * 2, 128};
    cuuint32_t box[3] = {64, 32, 9}, es[3] = {1, 1, 1};
    make_map(enc, &am.o, pO, S_LEN, KCAT, 32);
    enc(&am.o3, CU_TENSOR_MAP_DATA_TYPE_BFLOAT16, 3, pO, dims, strides, box, es, CU_TENSOR_MAP_INTERLEAVE_NONE,
        CU_TENSOR_MAP_SWIZZLE_128B, CU_TENSOR_MAP_L2_PROMOTION_L2_128B, CU_TENSOR_MAP_FLOAT_OOB_FILL_NONE);
  }
  make_map(enc, &am.wob, Wo, 4096, DM, 64);
  make_map(enc, &am.woa, woA, DM, DM, 64);

  rec_kernel<<<96, 384, SM_TOTAL, cudaStreamPerThread>>>(rm, x, mem0);
  cudaLaunchConfig_t cfg = {};
  cfg.gridDim = dim3(NAUX); cfg.blockDim = dim3(512); cfg.dynamicSmemBytes = A_TOTAL; cfg.stream = cudaStreamPerThread;
  cudaLaunchAttribute at[1];
  at[0].id = cudaLaunchAttributeProgrammaticStreamSerialization; at[0].val.programmaticStreamSerializationAllowed = 1;
  cfg.attrs = at; cfg.numAttrs = 1;
  if (XP & 16) cfg.numAttrs = 0;
  if (!(XP & 64)) cudaLaunchKernelEx(&cfg, aux_kernel, am, x, gate_w, (bf16*)d_out);
}
```

```cpp
#include <cuda_runtime.h>
#include <cuda_bf16.h>
#include <cuda_fp16.h>
#include <cuda.h>
#include <stdint.h>

typedef __nv_bfloat16 bf16;

constexpr int S_LEN = 2048, DM = 576, NH = 32, DH = 128, NSEG = 64, KCAT = 4096 + 576;
#define RED_LINE(i) (((i) >> 2) * 4096 + ((i) & 1) * 256 + ((i) & 2) * 512)
#define RED_SLOT(s) (((s) & 1) * 128 + ((s) & 2) * 256)

#define POLL_NS 896
#define NII 18
#define W3PRE 4
#define W3MID 4
#define GF 0
#define B5POS 0
#define NUP 4
#define UPF 1
#define B3Q 9
#define B3F 0
#define GATE 7
#define NTL 2
#define B7R 1
#define EXPOS 0
#define VW2 1
#define CLR 1
#define RFW 0
#define NIC 0
#define LEAD 0
#define FIN16 1
#define VXG 0
#define RING 63
#define EXB 0
#define EXD 0
#define EXB2 8192
#define HDLY 0
#define F10 1
#define NPROBE 2
#define NPROBE2 5
#define WPOS 2
#define WARM 0
#define YP 0
#define QM 60
#define N5 224
#define KP(i) (((i) >> 1) + 4 * ((i) & 1))
#define SPIN_LIMIT (1 << 14)
#define XP 0

__device__ __align__(1024) bf16 g_Ocat[S_LEN * KCAT];
__device__ __align__(1024) unsigned char g_red_raw[2 * 262144];
constexpr int HINT_OFF = 2048;
__device__ __align__(16) float g_gate[S_LEN];
__device__ __align__(128) uint4 g_stats[96 * 2];
__device__ unsigned g_epoch;
__device__ unsigned g_epoch2;
__device__ unsigned g_oflag[NH * 32];
__device__ unsigned g_abar[3 * 32];
__device__ unsigned g_sflag[96 * 8];
__device__ __align__(1024) unsigned char g_seg[NSEG * 96 * 8192];
__device__ __align__(1024) unsigned char g_km[NSEG * NH * 4096];
__device__ __align__(1024) uint2 g_part[8 * 9 * 4 * 8 * 128];
__device__ int g_err;
#define SSTAMP(seg, idx)
#define QSTAMP(idx)
#define PROF(idx)
#define PROFP(idx)
#define STAMP(idx)
#define ASTAMP(idx)
#define WSTAMP(idx)

#define CSTAMP(idx)
#define CDECL
#define CDUMP
#define DI __device__ __forceinline__
DI uint32_t smem_u32(const void* p) { return (uint32_t)__cvta_generic_to_shared(p); }
DI uint32_t clock32() { uint32_t c; asm volatile("mov.u32 %0, %%clock;" : "=r"(c) :: "memory"); return c; }
DI uint32_t gtime() { uint32_t c; asm volatile("mov.u32 %0, %%globaltimer_lo;" : "=r"(c) :: "memory"); return c; }
DI uint32_t ldg_relaxed32(const void* p) { uint32_t v; asm volatile("ld.relaxed.gpu.global.b32 %0, [%1];" : "=r"(v) : "l"(p) : "memory"); return v; }
DI uint32_t ldg_acquire32(const void* p) { uint32_t v; asm volatile("ld.acquire.gpu.global.b32 %0, [%1];" : "=r"(v) : "l"(p) : "memory"); return v; }
DI void stg_relaxed32(void* p, uint32_t v) { asm volatile("st.relaxed.gpu.global.b32 [%0], %1;" :: "l"(p), "r"(v) : "memory"); }
DI int head_id() { int c; asm volatile("mov.u32 %0, %%clusterid.x;" : "=r"(c)); return c; }
DI uint32_t mapa(uint32_t a, uint32_t r) { uint32_t o; asm("mapa.shared::cluster.u32 %0, %1, %2;" : "=r"(o) : "r"(a), "r"(r)); return o; }
DI void cluster_arrive() { asm volatile("barrier.cluster.arrive.relaxed.aligned;" ::: "memory"); }
DI void cluster_wait() { asm volatile("barrier.cluster.wait.aligned;" ::: "memory"); }
DI void cluster_sync() { asm volatile("barrier.cluster.arrive.release.aligned;\nbarrier.cluster.wait.acquire.aligned;" ::: "memory"); }
DI void mbar_init(uint32_t b, uint32_t c) { asm volatile("mbarrier.init.shared::cta.b64 [%0], %1;" :: "r"(b), "r"(c) : "memory"); }
DI void mbar_expect(uint32_t b, uint32_t tx) { asm volatile("mbarrier.arrive.expect_tx.shared::cta.b64 _, [%0], %1;" :: "r"(b), "r"(tx) : "memory"); }
DI void mbar_arrive(uint32_t b) { asm volatile("mbarrier.arrive.shared::cta.b64 _, [%0];" :: "r"(b) : "memory"); }
DI void mbar_wait(uint32_t b, uint32_t par) {
  asm volatile("{\n.reg .pred p;\n.reg .u32 n, q;\nmov.u32 n, 0;\n"
               "WL: add.u32 n, n, 1;\nshr.u32 q, n, 12;\nxor.b32 q, q, %1;\n"
               "mbarrier.try_wait.parity.shared::cta.b64 p, [%0], q;\n@!p bra.uni WL;\n}"
               :: "r"(b), "r"(par) : "memory");
}
DI void wait_until(uint32_t t) {
  const uint32_t now = gtime();
  t = min(t, now + 8192);
  asm volatile("{\n.reg .pred p;\n.reg .u32 c;\nTL: mov.u32 c, %%globaltimer_lo;\nsetp.lt.u32 p, c, %0;\n@p bra.uni TL;\n}" :: "r"(t) : "memory");
}
#define PIN(v) v = __shfl_xor_sync(0xffffffffu, v, 0)
#define SCHED_FENCE(k) asm volatile("{\n.reg .pred p;\nsetp.eq.u32 p, %0, %1;\n@p exit;\n}" :: "r"(fence_reg), "r"(k) : "memory")
#define MEM_ORDER(k) asm volatile("{\n.reg .pred p;\nsetp.eq.u32 p, %0, %1;\n@p st.shared.u32 [%0], %0;\n}" :: "r"(fence_reg), "r"(k + 64) : "memory")
DI void bar_sync(int id, int n) { asm volatile("bar.sync %0, %1;" :: "r"(id), "r"(n) : "memory"); }
DI void bar_arrive(int id, int n) { asm volatile("bar.arrive %0, %1;" :: "r"(id), "r"(n) : "memory"); }
DI void fence_async() { asm volatile("fence.proxy.async.shared::cta;" ::: "memory"); }
DI void st_async4(uint32_t a, uint32_t x, uint32_t y, uint32_t z, uint32_t w, uint32_t mb) {
  asm volatile("st.async.weak.shared::cluster.mbarrier::complete_tx::bytes.v4.b32 [%0], {%1,%2,%3,%4}, [%5];"
               :: "r"(a), "r"(x), "r"(y), "r"(z), "r"(w), "r"(mb) : "memory");
}
DI void st_async2(uint32_t a, uint32_t x, uint32_t y, uint32_t mb) {
  asm volatile("st.async.weak.shared::cluster.mbarrier::complete_tx::bytes.v2.b32 [%0], {%1,%2}, [%3];"
               :: "r"(a), "r"(x), "r"(y), "r"(mb) : "memory");
}
DI void sts32(uint32_t a, uint32_t x) { asm volatile("st.shared.b32 [%0], %1;" :: "r"(a), "r"(x) : "memory"); }
DI void sts64(uint32_t a, uint32_t x, uint32_t y) { asm volatile("st.shared.v2.b32 [%0], {%1,%2};" :: "r"(a), "r"(x), "r"(y) : "memory"); }
DI void sts128(uint32_t a, uint32_t x, uint32_t y, uint32_t z, uint32_t w) {
  asm volatile("st.shared.v4.b32 [%0], {%1,%2,%3,%4};" :: "r"(a), "r"(x), "r"(y), "r"(z), "r"(w) : "memory");
}
DI uint32_t lds32(uint32_t a) { uint32_t x; asm volatile("ld.shared.b32 %0, [%1];" : "=r"(x) : "r"(a) : "memory"); return x; }
DI void lds64(uint32_t a, uint32_t& x, uint32_t& y) { asm volatile("ld.shared.v2.b32 {%0,%1}, [%2];" : "=r"(x), "=r"(y) : "r"(a) : "memory"); }
DI void lds128(uint32_t a, uint32_t* r) {
  asm volatile("ld.shared.v4.b32 {%0,%1,%2,%3}, [%4];" : "=r"(r[0]), "=r"(r[1]), "=r"(r[2]), "=r"(r[3]) : "r"(a) : "memory");
}
DI void lds128f(uint32_t a, float* r) {
  asm volatile("ld.shared.v4.f32 {%0,%1,%2,%3}, [%4];" : "=f"(r[0]), "=f"(r[1]), "=f"(r[2]), "=f"(r[3]) : "r"(a) : "memory");
}
DI void lds64f(uint32_t a, float* r) { asm volatile("ld.shared.v2.f32 {%0,%1}, [%2];" : "=f"(r[0]), "=f"(r[1]) : "r"(a) : "memory"); }
DI void ldsm4t(uint32_t* r, uint32_t a) {
  asm volatile("ldmatrix.sync.aligned.m8n8.x4.trans.shared.b16 {%0,%1,%2,%3}, [%4];"
               : "=r"(r[0]), "=r"(r[1]), "=r"(r[2]), "=r"(r[3]) : "r"(a) : "memory");
}
DI void ldsm4t_in(uint32_t* r, uint32_t a, uint32_t t) {
  asm volatile("{\n.reg .pred p;\nsetp.ne.u32 p, %5, 0;\n@p ldmatrix.sync.aligned.m8n8.x4.trans.shared.b16 {%0,%1,%2,%3}, [%4];\n}"
               : "+r"(r[0]), "+r"(r[1]), "+r"(r[2]), "+r"(r[3]) : "r"(a), "r"(t) : "memory");
}
DI void lds128_in(uint32_t* r, uint32_t a, uint32_t t) {
  asm volatile("{\n.reg .pred p;\nsetp.ne.u32 p, %5, 0;\n@p ld.shared.v4.b32 {%0,%1,%2,%3}, [%4];\n}"
               : "+r"(r[0]), "+r"(r[1]), "+r"(r[2]), "+r"(r[3]) : "r"(a), "r"(t) : "memory");
}
DI void ldsm2t_in(uint32_t* r, uint32_t a, uint32_t t) {
  asm volatile("{\n.reg .pred p;\nsetp.ne.u32 p, %3, 0;\n@p ldmatrix.sync.aligned.m8n8.x2.trans.shared.b16 {%0,%1}, [%2];\n}" : "+r"(r[0]), "+r"(r[1]) : "r"(a), "r"(t) : "memory");
}
DI void reserve2(uint32_t* r) { asm volatile("{\n.reg .u64 t;\nmov.u64 t, %%clock64;\nmov.b64 {%0, %1}, t;\n}" : "=r"(r[0]), "=r"(r[1])); }
DI void scale_sum(float& x, float& y, float s, uint32_t t) {
  asm volatile("{\n.reg .pred p;\nsetp.ne.u32 p, %2, 0;\n@p mul.f32 %0, %0, %1;\n}" : "+f"(y) : "f"(s), "r"(t));
  asm volatile("{\n.reg .pred p;\nsetp.ne.u32 p, %3, 1;\n@p fma.rn.f32 %0, %0, %1, %2;\n}" : "+f"(x) : "f"(s), "f"(y), "r"(t));
}
DI void ldsm4(uint32_t* r, uint32_t a) {
  asm volatile("ldmatrix.sync.aligned.m8n8.x4.shared.b16 {%0,%1,%2,%3}, [%4];"
               : "=r"(r[0]), "=r"(r[1]), "=r"(r[2]), "=r"(r[3]) : "r"(a) : "memory");
}
DI void st_async1(uint32_t a, uint32_t x, uint32_t mb) {
  asm volatile("st.async.weak.shared::cluster.mbarrier::complete_tx::bytes.b32 [%0], %1, [%2];" :: "r"(a), "r"(x), "r"(mb) : "memory");
}
DI void stsm4(uint32_t a, uint32_t x, uint32_t y, uint32_t z, uint32_t w) {
  asm volatile("stmatrix.sync.aligned.m8n8.x4.shared.b16 [%0], {%1,%2,%3,%4};" :: "r"(a), "r"(x), "r"(y), "r"(z), "r"(w) : "memory");
}
DI void stsm4t(uint32_t a, uint32_t x, uint32_t y, uint32_t z, uint32_t w) {
  asm volatile("stmatrix.sync.aligned.m8n8.x4.trans.shared.b16 [%0], {%1,%2,%3,%4};" :: "r"(a), "r"(x), "r"(y), "r"(z), "r"(w) : "memory");
}
DI uint32_t pack_bf16(float lo, float hi) { uint32_t r; asm("cvt.rn.bf16x2.f32 %0, %1, %2;" : "=r"(r) : "f"(hi), "f"(lo)); return r; }
DI uint32_t pack_f16(float lo, float hi) { uint32_t r; asm("cvt.rn.f16x2.f32 %0, %1, %2;" : "=r"(r) : "f"(hi), "f"(lo)); return r; }
DI float ex2(float x) { float y; asm("ex2.approx.ftz.f32 %0, %1;" : "=f"(y) : "f"(x)); return y; }
DI float rcp(float x) { float y; asm("rcp.approx.ftz.f32 %0, %1;" : "=f"(y) : "f"(x)); return y; }
DI float bf_lo(uint32_t x) { return __uint_as_float(x << 16); }
DI float bf_hi(uint32_t x) { return __uint_as_float(x & 0xffff0000u); }
DI void mma16816(float* d, const uint32_t* a, uint32_t b0, uint32_t b1) {
  asm volatile("mma.sync.aligned.m16n8k16.row.col.f32.bf16.bf16.f32 {%0,%1,%2,%3}, {%4,%5,%6,%7}, {%8,%9}, {%0,%1,%2,%3};"
               : "+f"(d[0]), "+f"(d[1]), "+f"(d[2]), "+f"(d[3]) : "r"(a[0]), "r"(a[1]), "r"(a[2]), "r"(a[3]), "r"(b0), "r"(b1));
}
DI void mma16816z(float* d, const uint32_t* a, uint32_t b0, uint32_t b1) {
  asm volatile("mma.sync.aligned.m16n8k16.row.col.f32.bf16.bf16.f32 {%0,%1,%2,%3}, {%4,%5,%6,%7}, {%8,%9}, {%10,%10,%10,%10};"
               : "=f"(d[0]), "=f"(d[1]), "=f"(d[2]), "=f"(d[3]) : "r"(a[0]), "r"(a[1]), "r"(a[2]), "r"(a[3]), "r"(b0), "r"(b1), "f"(0.f));
}
DI void mma1688z(float* d, uint32_t a0, uint32_t a1, uint32_t b0) {
  asm volatile("mma.sync.aligned.m16n8k8.row.col.f32.bf16.bf16.f32 {%0,%1,%2,%3}, {%4,%5}, {%6}, {%7,%7,%7,%7};"
               : "=f"(d[0]), "=f"(d[1]), "=f"(d[2]), "=f"(d[3]) : "r"(a0), "r"(a1), "r"(b0), "f"(0.f));
}
DI void mma1688(float* d, uint32_t a0, uint32_t a1, uint32_t b0) {
  asm volatile("mma.sync.aligned.m16n8k8.row.col.f32.bf16.bf16.f32 {%0,%1,%2,%3}, {%4,%5}, {%6}, {%0,%1,%2,%3};"
               : "+f"(d[0]), "+f"(d[1]), "+f"(d[2]), "+f"(d[3]) : "r"(a0), "r"(a1), "r"(b0));
}
DI void ldsm2t(uint32_t* r, uint32_t a) {
  asm volatile("ldmatrix.sync.aligned.m8n8.x2.trans.shared.b16 {%0,%1}, [%2];" : "=r"(r[0]), "=r"(r[1]) : "r"(a) : "memory");
}
DI uint32_t add_bf16(uint32_t a, uint32_t b) { uint32_t r; asm("add.rn.bf16x2 %0, %1, %2;" : "=r"(r) : "r"(a), "r"(b)); return r; }
DI uint32_t mul_bf16(uint32_t a, uint32_t b) { uint32_t r; asm("mul.rn.bf16x2 %0, %1, %2;" : "=r"(r) : "r"(a), "r"(b)); return r; }
DI uint64_t make_desc(uint32_t addr, uint32_t lbo, uint32_t sbo, uint32_t swz) {
  return (uint64_t)((addr & 0x3FFFF) >> 4) | ((uint64_t)(lbo >> 4) << 16) | ((uint64_t)(sbo >> 4) << 32) | ((uint64_t)swz << 62);
}
#define WG_FENCE() asm volatile("wgmma.fence.sync.aligned;" ::: "memory")
#define WG_COMMIT() asm volatile("wgmma.commit_group.sync.aligned;" ::: "memory")
#define WG_WAIT(n) asm volatile("wgmma.wait_group.sync.aligned %0;" :: "n"(n) : "memory")
#define ACC8(d, o) "+f"(d[o]), "+f"(d[o + 1]), "+f"(d[o + 2]), "+f"(d[o + 3]), "+f"(d[o + 4]), "+f"(d[o + 5]), "+f"(d[o + 6]), "+f"(d[o + 7])
DI void wgmma_n32_rs(float* d, uint32_t a0, uint32_t a1, uint32_t a2, uint32_t a3, uint64_t db, int acc) {
  asm volatile("{\n.reg .pred p;\nsetp.ne.b32 p, %21, 0;\n"
               "wgmma.mma_async.sync.aligned.m64n32k16.f32.bf16.bf16 {%0,%1,%2,%3,%4,%5,%6,%7,%8,%9,%10,%11,%12,%13,%14,%15}, "
               "{%16,%17,%18,%19}, %20, p, 1, 1, 0;\n}\n"
               : ACC8(d, 0), ACC8(d, 8) : "r"(a0), "r"(a1), "r"(a2), "r"(a3), "l"(db), "r"(acc));
}
template <int TA>
DI void wgmma_n32_ss(float* d, uint64_t da, uint64_t db, int acc) {
  asm volatile("{\n.reg .pred p;\nsetp.ne.b32 p, %18, 0;\n"
               "wgmma.mma_async.sync.aligned.m64n32k16.f32.bf16.bf16 {%0,%1,%2,%3,%4,%5,%6,%7,%8,%9,%10,%11,%12,%13,%14,%15}, "
               "%16, %17, p, 1, 1, %19, 1;\n}\n"
               : ACC8(d, 0), ACC8(d, 8) : "l"(da), "l"(db), "r"(acc), "n"(TA));
}
DI void tma_load(uint32_t dst, const CUtensorMap* m, int c0, int c1, uint32_t mb) {
  asm volatile("cp.async.bulk.tensor.2d.shared::cluster.global.mbarrier::complete_tx::bytes [%0], [%1, {%3, %4}], [%2];"
               :: "r"(dst), "l"(m), "r"(mb), "r"(c0), "r"(c1) : "memory");
}
DI void tma_load3(uint32_t dst, const CUtensorMap* m, int row, uint32_t mb) {
  asm volatile("cp.async.bulk.tensor.3d.shared::cluster.global.mbarrier::complete_tx::bytes [%0], [%1, {%3, %4, %3}], [%2];"
               :: "r"(dst), "l"(m), "r"(mb), "r"(0), "r"(row) : "memory");
}
DI bool elect_one() {
  uint32_t p;
  asm volatile("{\n.reg .pred p;\nelect.sync _|p, 0xffffffff;\nselp.u32 %0, 1, 0, p;\n}" : "=r"(p));
  return p;
}
DI void bulk_s2s(uint32_t dst, uint32_t src, uint32_t bytes, uint32_t mb) {
  asm volatile("cp.async.bulk.shared::cluster.shared::cta.mbarrier::complete_tx::bytes [%0], [%1], %2, [%3];"
               :: "r"(dst), "r"(src), "r"(bytes), "r"(mb) : "memory");
}
DI void bulk_load(uint32_t dst, const void* src, uint32_t bytes, uint32_t mb) {
  asm volatile("cp.async.bulk.shared::cluster.global.mbarrier::complete_tx::bytes [%0], [%1], %2, [%3];" :: "r"(dst), "l"(src), "r"(bytes), "r"(mb) : "memory");
}
DI void tma_prefetch(const CUtensorMap* m, int c0, int c1) {
  asm volatile("cp.async.bulk.prefetch.tensor.2d.L2.global.tile [%0, {%1, %2}];" :: "l"(m), "r"(c0), "r"(c1) : "memory");
}
DI void tma_store(const CUtensorMap* m, uint32_t src, int c0, int c1) {
  asm volatile("cp.async.bulk.tensor.2d.global.shared::cta.bulk_group [%0, {%2, %3}], [%1];" :: "l"(m), "r"(src), "r"(c0), "r"(c1) : "memory");
}
DI uint4 ldg_relaxed(const void* p) {
  uint4 v;
  asm volatile("ld.relaxed.gpu.global.v4.b32 {%0,%1,%2,%3}, [%4];" : "=r"(v.x), "=r"(v.y), "=r"(v.z), "=r"(v.w) : "l"(p) : "memory");
  return v;
}
DI void stg_relaxed(void* p, uint32_t x, uint32_t y, uint32_t z, uint32_t w) {
  asm volatile("st.relaxed.gpu.global.v4.b32 [%0], {%1,%2,%3,%4};" :: "l"(p), "r"(x), "r"(y), "r"(z), "r"(w) : "memory");
}
DI void red_f16x8(void* p, uint32_t x, uint32_t y, uint32_t z, uint32_t w) {
  asm volatile("red.relaxed.gpu.global.add.noftz.v4.f16x2 [%0], {%1,%2,%3,%4};" :: "l"(p), "r"(x), "r"(y), "r"(z), "r"(w) : "memory");
}
DI void sq_acc(uint32_t& a, uint32_t x) { asm("fma.rn.bf16x2 %0, %1, %1, %0;" : "+r"(a) : "r"(x)); }
DI __half2 amax4(__half2 h, const uint32_t* v) {
  h = __hmax2_nan(__hmax2_nan(h, __habs2(*(const __half2*)&v[0])), __habs2(*(const __half2*)&v[1]));
  return __hmax2_nan(__hmax2_nan(h, __habs2(*(const __half2*)&v[2])), __habs2(*(const __half2*)&v[3]));
}
DI uint32_t wexp(__half2 h) { const uint32_t u = *(const uint32_t*)&h; return __reduce_max_sync(0xffffffffu, max((u >> 16) & 0x7fffu, u & 0x7fffu)) >> 7; }
DI float max10(const float* a) {
  return fmaxf(fmaxf(fmaxf(fmaxf(a[0], a[1]), fmaxf(a[2], a[3])), fmaxf(fmaxf(a[4], a[5]), fmaxf(a[6], a[7]))), fmaxf(a[8], a[9]));
}
DI float quad_max(float m) {
  return fmaxf(fmaxf(m, __shfl_xor_sync(0xffffffffu, m, 1)), fmaxf(__shfl_xor_sync(0xffffffffu, m, 2), __shfl_xor_sync(0xffffffffu, m, 3)));
}
DI float warp_sum(float v) {
#pragma unroll
  for (int o = 16; o; o >>= 1) v += __shfl_xor_sync(0xffffffffu, v, o);
  return v;
}

constexpr int SM_WO3 = 0;
constexpr int SM_X = 16384;
constexpr int XT = 36864;
constexpr int SM_EXP = 126976;
constexpr int SEGB = 10240;
constexpr int SM_BLK = SM_EXP + 8192;
constexpr int SM_VC = SM_BLK + 4 * SEGB;
constexpr int SM_PART = SM_VC + 16384;
constexpr int SM_QM = SM_PART + 4096;
constexpr int SM_E = SM_QM + 1024;
constexpr int SM_VM = SM_E + 1536;
constexpr int SM_OB = SM_VM + 2048;
constexpr int SM_FB = SM_OB + 2048;
constexpr int SM_STAGE = SM_X + XT;
constexpr int SM_M0 = SM_STAGE + 3 * 49152;
constexpr int SM_MISC = 210944;
constexpr int SM_WOST = 212992;
constexpr int SM_MEM = SM_WOST;
constexpr int SM_MAX = SM_MEM + 11264;
#define MEM_BLK(q) ((q) / 3 * 4096 + (q) % 3 * 1024)
constexpr int SM_TOTAL = 229376;
constexpr int MB_W = SM_MISC;
constexpr int MB_WO = SM_MISC + 24;
constexpr int MB_WO3 = SM_MISC + 32;
constexpr int MB_X = SM_MISC + 40;
constexpr int MB_S = SM_MISC + 64;
constexpr int MB_F = SM_MISC + 72;
constexpr int MB_VX = SM_MISC + 80;
constexpr int SC_FPAR = SM_MISC + 136;
constexpr int SC_DEAD = SM_MISC + 96;
constexpr int SC_UNSC = SM_MISC + 112;
constexpr int SC_EXPW = SM_MISC + 132;
constexpr int SC_ONES = SM_MISC + 144;
constexpr int SC_SS = SM_MISC + 160;
constexpr int SC_LAT = SM_MISC + 224;
constexpr int SC_EPO = SM_MISC + 240;
constexpr int MB_XS = SM_MISC + 248;
constexpr int SC_XMAX = SM_MISC + 256;
constexpr int SC_PROF = 229376;

constexpr float SM_SCALE = 0.08838834764831845f;
constexpr float LOG2E = 1.4426950408889634f;
constexpr float E_LIM = 20.f;

template <bool B> struct BoolC { static constexpr bool value = B; };
struct RMaps { CUtensorMap x, wq, wk, wv, wo; unsigned char* red; uint32_t poll; const unsigned char* w[4]; };

DI uint32_t latest_hint(uint32_t h, uint32_t d, int s) {
  const uint32_t x = (((h | 0xc0c0c0c0u) - ((d >> 5) & 63) * 0x01010101u) & 0x3f3f3f3fu) | ((h ^ (((s >> 2) + 1) & 3) * 0x40404040u) & 0xc0c0c0c0u);
  const uint32_t y = __vmaxu2(x & 0x00ff00ffu, (x >> 8) & 0x00ff00ffu);
  return __reduce_max_sync(0xffffffffu, max(y & 0xffffu, y >> 16));
}
DI uint32_t near_half(uint32_t sb) {
  uint32_t a, b; lds64(sb + SC_LAT, a, b);
  return a > b;
}

template <int RT, int K0, int K1, bool D32 = false>
DI void xproj(float* acc, const uint32_t (&wa)[2][18][4], uint64_t xd) {
  if (XP & 1) return;
  WG_FENCE();
#pragma unroll
  for (int k = K0; k < ((XP & 128) ? K0 + 1 : K1); k++)
  {
    uint64_t d = xd + (uint64_t)(((k >> 1) * 4096 + (k & 1) * 32) >> 4);
    if (D32) asm("mov.b64 %0, {%1, %2};" : "=l"(d) : "r"((uint32_t)xd + (((k >> 1) * 4096 + (k & 1) * 32) >> 4)), "r"((uint32_t)(xd >> 32)));
    wgmma_n32_rs(acc, wa[RT][k][0], wa[RT][k][1], wa[RT][k][2], wa[RT][k][3], d, k != 0);
  }
  WG_COMMIT();
}

DI void seg_store(int seg, uint32_t sb) {
  fence_async();
  asm volatile("cp.async.bulk.global.shared::cta.bulk_group [%0], [%1], 8192;"
               :: "l"(g_seg + ((size_t)(seg & RING) * 96 + blockIdx.x) * 8192), "r"(sb + SM_BLK + (seg & 3) * SEGB) : "memory");
  asm volatile("cp.async.bulk.commit_group;" ::: "memory");
}
DI void seg_publish(int seg, uint32_t sb) {
  const uint32_t v = lds32(sb + SC_EPO) + seg;
  asm volatile("cp.async.bulk.wait_group 0;" ::: "memory");
  stg_relaxed32(&g_sflag[blockIdx.x * 8], v);
}

DI void proj_role(const uint32_t sb, const RMaps& tm, const uint32_t rank, const int wg, const int w, const int lane) {
  const bool qk = rank < 2;
  uint32_t wa[2][18][4];
  {
    const int rr = (lane & 7) + ((lane >> 4) << 3);
    const uint32_t col = ((2 * w + ((lane >> 3) & 1)) ^ (lane & 7)) << 4;
    float ss;
#pragma unroll 1
    for (int pass = WARM ? wg + w == 0 : 1; pass < 2; pass++) {
      ss = 0.f;
      if (pass) bar_sync(3, 256);
#pragma unroll
      for (int c = 0; c < 3; c++) {
        QSTAMP(2 + 2 * c);
        if (pass) mbar_wait(sb + MB_W + 8 * c, 0);
        QSTAMP(3 + 2 * c);
#pragma unroll
        for (int rt = 0; rt < 2; rt++)
#pragma unroll
          for (int k = 0; k < 6; k++)
            ldsm4t(wa[rt][c * 6 + k], sb + SM_STAGE + c * 49152 + (rt ^ wg) * 24576 + (64 * (k >> 1) + 32 * wg + 16 * (k & 1) + rr) * 128 + col);
        if (c < 2) {
          fence_async();
          if (pass) {
            bar_sync(3, 256);
            QSTAMP(17 + c);
            if (threadIdx.x == 0) {
              if (c == 0) tma_load3(sb + SM_X + XT, &tm.x, 32, sb + MB_X + 8);
              else tma_load(sb + SM_X + 2 * XT, &tm.wo, rank * 192, (blockIdx.x / 3) * DH, sb + MB_WO);
            }
            __syncwarp();
          }
        }
        uint32_t q[4] = {0, 0, 0, 0};
#pragma unroll
        for (int rt = 0; rt < 2; rt++)
#pragma unroll
          for (int k = 0; k < 6; k++)
#pragma unroll
            for (int i = 0; i < 4; i++) sq_acc(q[i], wa[rt][c * 6 + k][i]);
#pragma unroll
        for (int i = 0; i < 4; i++) ss += bf_lo(q[i]) + bf_hi(q[i]);
      }
      ss = warp_sum(ss);
    }
    fence_async();
    cluster_arrive();
    if (lane == 0) sts32(sb + SC_SS + 4 * (wg * 4 + w), qk ? 0 : __float_as_uint(ss));
    bar_arrive(11, 384);
  }
  STAMP(1);
  QSTAMP(8);
  mbar_wait(sb + MB_X, 0);
  STAMP(2);
  QSTAMP(9);

  uint32_t t16 = sb + (w * 32 + lane) * 16;
  uint32_t mem_a = sb + SM_MEM + wg * 512 + lane * 16;
  uint32_t fin_a = sb + (lane & 7) * 16 + SM_BLK + (qk ? (wg ^ 1) * 4096 + w * 256 + (lane & 8) * 16 + (lane & 16) * 64
                                              : wg * 4096 + w * 1024 + (lane & 8) * 64 + (lane & 16) * 8);
  PIN(t16); PIN(mem_a); PIN(fin_a);
  const uint32_t fence_reg = mem_a;
  const uint32_t fin2 = qk ? 2048 : 256;
  float acc[16];
  const uint64_t xd0 = make_desc(sb + SM_X + wg * 64, 16, 1024, 1);
  auto do_export = [&](auto retire, uint32_t always) {
    WG_WAIT(0);
    uint32_t p[2];
#pragma unroll
    for (int i = 0; i < 2; i++) {
      p[i] = pack_bf16(acc[8 * i], acc[8 * i + 1]);
      sts128(t16 + SM_EXP + wg * 4096 + i * 2048, p[i], pack_bf16(acc[8 * i + 2], acc[8 * i + 3]),
             pack_bf16(acc[8 * i + 4], acc[8 * i + 5]), pack_bf16(acc[8 * i + 6], acc[8 * i + 7]));
    }
    if (decltype(retire)::value)
      asm volatile("{\n.reg .pred p, q;\nsetp.ne.u32 p, %2, 0;\nsetp.ne.u32 q, %2, 1;\n@p ld.shared.b32 %0, [%3];\n@q ld.shared.b32 %1, [%3 + 4];\n"
                   "setp.ne.u32 p, %0, %1;\n@p exit;\n}" : "+r"(p[0]), "+r"(p[1]) : "r"(always), "r"(sb + SC_DEAD) : "memory");
  };
  uint32_t o[8];
  auto import = [&]() { lds128(t16 + SM_EXP + (wg ^ 1) * 4096, o); lds128(t16 + SM_EXP + (wg ^ 1) * 4096 + 2048, o + 4); };
  auto finish = [&](int seg) {
    const uint32_t a = fin_a + (seg & 3) * SEGB;
    WG_WAIT(0);
#pragma unroll
    for (int i = 0; i < 8; i++) o[i] = FIN16 ? add_bf16(pack_bf16(acc[2 * i], acc[2 * i + 1]), o[i]) : pack_bf16(acc[2 * i] + bf_lo(o[i]), acc[2 * i + 1] + bf_hi(o[i]));
    stsm4(a, o[0], o[1], o[2], o[3]);
    stsm4(a + fin2, o[4], o[5], o[6], o[7]);
  };
  auto send_v = [&](int seg, int dst) {
    fence_async();
    if (seg < NSEG - 1 && !(XP & 2) && elect_one())
      bulk_s2s(mapa(sb + SM_VC + (seg & 1) * 8192, dst), sb + SM_BLK + (seg & 3) * SEGB, 8192, mapa(sb + MB_VX + (seg & 1) * 8, dst));
    __syncwarp();
  };
  auto wait_v = [&](int seg) {
    if (seg < NSEG - 1 && !(XP & 2)) {
      mbar_wait(sb + MB_VX + (seg & 1) * 8, (seg >> 1) & 1);
      if (elect_one()) mbar_expect(sb + MB_VX + (seg & 1) * 8, 8192);
      __syncwarp();
    }
  };
  auto export_seg = [&](int seg) { if (!(XP & (4 | 8192)) && elect_one()) seg_store(seg, sb); __syncwarp(); };
  auto publish = [&](int seg) { if (!(XP & (4 | 16384)) && elect_one()) seg_publish(seg, sb); __syncwarp(); };
  bar_sync(3, 256);
  xproj<1, 0, 18>(acc, wa, xd0);
  do_export(BoolC<false>(), 0);
  SCHED_FENCE(11);
  xproj<0, 0, 18>(acc, wa, xd0);
  bar_sync(3, 256);
  QSTAMP(10);
  cluster_wait();
  QSTAMP(11);
  mbar_wait(sb + MB_X + 8, 0);
  QSTAMP(12);
  import();
  finish(0);
  SCHED_FENCE(12);
  bar_sync(3, 256);
  uint64_t dA = xd0 + (XT >> 4);
  xproj<1, 0, 18>(acc, wa, dA);
  if (!qk && wg == 0 && w < 2) send_v(0, w);
  if (wg == 0 && w == 3) export_seg(0);
  QSTAMP(13);
  if (qk && wg == 0 && w == 0) wait_v(0);
  QSTAMP(14);
  bar_arrive(13, 384);
  if (!qk) {
    do_export(BoolC<false>(), 0);
    SCHED_FENCE(15);
    xproj<0, 0, 18>(acc, wa, dA);
    if (threadIdx.x == 0 && !(XP & 8)) { mbar_expect(sb + MB_X, XT); tma_load3(sb + SM_X, &tm.x, 96, sb + MB_X); }
    bar_sync(3, 256);
    mbar_wait(sb + MB_X + 16, 0);
    import();
    finish(1);
    SCHED_FENCE(16);
    bar_sync(3, 256);
    dA += XT >> 4;
    xproj<1, 0, 18>(acc, wa, dA);
    if (wg == 0 && w < VW2) send_v(1, w);
  }
  QSTAMP(15);
  WG_WAIT(0);
  bar_sync(0, 384);
  if (wg == 0 && w == 3) publish(0);
  QSTAMP(16);
  const int ro = __shfl_sync(0xffffffffu, near_half(sb) ^ wg, 0);
  STAMP(5);
  const uint32_t always = __shfl_sync(0xffffffffu, lds32(sb + SC_DEAD + 12), 0);
  const int ah = qk ? 1 : 2;
  int b2 = qk ? 2 : 0;
  int s = 0;
  uint32_t hint_lo = (uint32_t)(uint64_t)tm.red + HINT_OFF + blockIdx.x + (lane & 1) * 4096 + (lane >> 1) * 16384;
  PIN(hint_lo);
  auto post_hint = [&]() {
    asm volatile("{\n.reg .pred p;\n.reg .b64 a;\n.reg .u32 t;\nsetp.lt.u32 p, %0, %1;\nmov.b64 a, {%2, %3};\nmov.u32 t, %%globaltimer_lo;\n"
                 "bfe.u32 t, t, 5, 6;\nor.b32 t, t, %4;\n@p st.relaxed.gpu.global.u8 [a], t;\n}"
                 :: "r"(t16), "r"(sb + 160), "r"(hint_lo + RED_SLOT(s)), "r"((uint32_t)((uint64_t)tm.red >> 32)), "r"(((s >> 2) + 1) << 6) : "memory");
  };
  auto memproj = [&](auto second, int id, uint32_t dep, float u0, float u1, float* r) {
    constexpr bool R1 = decltype(second)::value;
    uint32_t b[NUP][4], b0[4];
    if (R1) asm volatile("{\n.reg .pred p;\nsetp.eq.u32 p, %0, %1;\n@p exit;\n}" :: "r"(dep), "r"(id) : "memory");
    bar_sync(R1 ? 2 : 1, 256);
    PROF(0);
    ldsm4t(b0, mem_a);
#pragma unroll
    for (int q = 0; q < NUP; q++) {
      if (R1 && q == 2) {
        bar_sync(11, 256);
        SCHED_FENCE(id + 1);
      }
      ldsm4t(b[q], mem_a + MEM_BLK(q + 1));
    }
    mma16816z(&acc[0], wa[0][0], b0[0], b0[1]);
    mma16816z(&acc[4], wa[1][0], b0[0], b0[1]);
    mma16816z(&acc[8], wa[0][1], b0[2], b0[3]);
    mma16816z(&acc[12], wa[1][1], b0[2], b0[3]);
#pragma unroll
    for (int q = 1; q < 9; q++) {
      uint32_t* const c = b[(q - 1) % NUP];
      mma16816(&acc[0], wa[0][2 * q], c[0], c[1]);
      mma16816(&acc[4], wa[1][2 * q], c[0], c[1]);
      mma16816(&acc[8], wa[0][2 * q + 1], c[2], c[3]);
      mma16816(&acc[12], wa[1][2 * q + 1], c[2], c[3]);
      if (R1 && q + NUP == B3Q) bar_sync(3, 256);
      if (q + NUP < 9) ldsm4t_in(c, mem_a + MEM_BLK(q + NUP), always);
      else if (R1 && q + NUP < 11) lds128_in(c, t16 + SM_PART + (10 - q - NUP) * 2048, always);
      else if (!R1 && GATE && q == GATE) { bar_arrive(11, 256); lds128_in(c, sb + SC_DEAD, always); u0 = u1 = __uint_as_float(c[3]); }
    }
#pragma unroll
    for (int i = 0; i < 8; i++) {
      const float u = i < 4 ? u0 : u1;
      r[i] = R1 ? fmaf(acc[8 + i], u, (acc[i] + __uint_as_float(b[(8 + i / 4) % NUP][i & 3])) * u) : (GATE ? fmaf(acc[i], u, acc[8 + i]) : acc[i] + acc[8 + i]);
    }
  };
  if (ro == 0) {
#pragma unroll 1
    while (true) {
      do_export(BoolC<true>(), always);
      PROFP(3);
      if (s == 8) STAMP(6);
      float r[8];
      memproj(BoolC<false>(), 30, 0, 0.f, 0.f, r);
      sts128(t16 + SM_PART, __float_as_uint(r[0]), __float_as_uint(r[1]), __float_as_uint(r[2]), __float_as_uint(r[3]));
      sts128(t16 + SM_PART + 2048, __float_as_uint(r[4]), __float_as_uint(r[5]), __float_as_uint(r[6]), __float_as_uint(r[7]));
      bar_arrive(3, 256);
      PROF(1);
      bar_sync(9, 256);
      if (s == NSEG - 1) break;
      post_hint();
      if (w == 3 && s) publish(s);
      if (w == 1) {
        uint32_t m[8];
        lds128(t16 + SM_MAX - 512, m); lds128(t16 + SM_MAX, m + 4);
        const int em = (wexp(amax4(amax4(*(const __half2*)&m[0], m), m + 4)) >> 3) + (int)(lds32(sb + SC_UNSC + (s & 1) * 8) >> 23) - 15;
        const int ex = max(s ? em : 0, (int)lds32(sb + SC_XMAX + 4 * s)) - 127 + (int)lds32(sb + SC_EXPW);
        sts32(sb + SC_UNSC + (~s & 1) * 8, (127 + min(max(ex, -120), 120)) << 23);
        __syncwarp();
        if (elect_one()) mbar_arrive(sb + MB_S);
      }
      SCHED_FENCE(9);
      bar_sync(5, qk ? N5 : 256);
      PROF(2);
      import();
      xproj<0, 0, NII>(acc, wa, dA);
      if (NII < 18) {
        if (qk) bar_sync(7, 384);
        xproj<0, NII, 18>(acc, wa, dA);
        if (!qk) bar_sync(7, 384);
      } else {
        if (F10) WG_WAIT(0);
        bar_sync(10, 256);
        if (F10) SCHED_FENCE(17);
      }
      dA += (int64_t)(b2 ? XT >> 4 : -(XT >> 3));
      finish(s + ah);
      if (w != 3 && (qk || w >= VW2)) bar_arrive(13, 384);
      PROF(6);
      SCHED_FENCE(14);
      bar_sync(12, 256);
      PROF(7);
      xproj<1, 0, 18, true>(acc, wa, dA);
      bar_arrive(14, 256);
      b2 = b2 == 2 ? 0 : b2 + 1;
      s++;
      if (w == 3 || (!qk && w < VW2)) {
        bar_sync(13, 384);
        if (w == 3) export_seg(s); else send_v(s + 1, w);
      }
      PROFP(8);
    }
    if (!qk) bar_arrive(5, 256);
    if (w == 3) publish(NSEG - 1);
  } else {
    uint32_t km[4];
    auto send_km = [&]() {
      if (XP & (4 | 4096)) return;
      const uint32_t t = (km[0] & ~1u) | lds32(sb + SC_EPO + 4), u = (s * NH + head_id()) * 4096;
      if (qk)
        asm volatile("{\n.reg .u32 o;\n.reg .u64 a;\nshr.u32 o, %0, 1;\nadd.u32 o, o, %1;\nmad.wide.u32 a, o, 1, %2;\nst.relaxed.gpu.global.v2.b32 [a], {%3,%4};\n}"
                     :: "r"(t16), "r"(u + rank * 1024 - (sb >> 1)), "l"(g_km), "r"(t), "r"(km[1]) : "memory");
      else
        asm volatile("{\n.reg .u32 o;\n.reg .u64 a;\nadd.u32 o, %0, %1;\nmad.wide.u32 a, o, 1, %2;\nst.relaxed.gpu.global.v4.b32 [a], {%3,%4,%5,%6};\n}"
                     :: "r"(t16), "r"(u + 2048 - sb), "l"(g_km), "r"(t), "r"(km[1]), "r"(km[2]), "r"(km[3]) : "memory");
    };
#pragma unroll 1
    while (true) {
      do_export(BoolC<true>(), always);
      PROFP(3);
      if (s == 8) STAMP(6);
      const uint32_t tl = ((t16 >> 8) ^ wg) & 1, am = (t16 & ~256u) - w * 256;
      const float un = __uint_as_float(lds32(sb + SC_UNSC + (s & 1) * 8));
      float r[8];
      if (qk) {
        uint32_t a0 = am + (tl ? SM_QM : SM_BLK + 8192 + (s & 3) * SEGB);
        float u0 = wg ? un * (SM_SCALE * LOG2E) : un, u1 = wg ? un : un * (SM_SCALE * LOG2E);
        PIN(a0); PIN(u0); PIN(u1);
        memproj(BoolC<true>(), 32, a0, u0, u1, r);
        const uint32_t p0 = pack_bf16(r[0], r[1]), p1 = pack_bf16(r[2], r[3]), p2 = pack_bf16(r[4], r[5]), p3 = pack_bf16(r[6], r[7]);
        stsm4(a0, p0, p1, p2, p3);
        bar_arrive(4, 256);
        km[0] = wg ? p2 : p0; km[1] = wg ? p3 : p1;
      } else {
        const uint32_t d0 = s < NSEG - 1 ? 0 : 2, d1 = s < NSEG - 1 ? 1 : 2;
        uint32_t r0 = mapa(t16 + SM_VM, d0), r1 = mapa(t16 + SM_VM, d1);
        PIN(r0); PIN(r1);
        memproj(BoolC<true>(), 34, r0 | r1, un, un, r);
        const uint32_t p0 = pack_bf16(r[0], r[1]), p1 = pack_bf16(r[2], r[3]), p2 = pack_bf16(r[4], r[5]), p3 = pack_bf16(r[6], r[7]);
        const uint32_t v0 = wg ? p2 : p0, v1 = wg ? p3 : p1, v2 = wg ? p0 : p2, v3 = wg ? p1 : p3;
        st_async4(r0, v0, v1, v2, v3, mapa(sb + MB_S, d0));
        st_async4(r1, v0, v1, v2, v3, mapa(sb + MB_S, d1));
        bar_arrive(5, 256);
        sts128(t16 + SM_VM, v0, v1, v2, v3);
        __syncwarp();
        if (elect_one()) mbar_arrive(sb + MB_S);
        km[0] = v0; km[1] = v1; km[2] = v2; km[3] = v3;
      }
      if (s == NSEG - 1) break;
      PROF(1);
      auto rearm = [&]() { mbar_wait(sb + MB_S, s & 1); if (elect_one()) mbar_expect(sb + MB_S, qk ? 640 + 2048 : 1280); __syncwarp(); };
      if (w == 1) {
        if ((t16 & 384) == 0) stg_relaxed(tm.red + (RED_SLOT(s + 2) + RED_LINE(blockIdx.x)) + (t16 & 112), 0, 0, 0, 0);
      } else if (w == 0) {
        const int tn = s + ah + 1;
        if (RFW) mbar_wait(sb + MB_S, s & 1);
        if (tn + 1 < NSEG && !(XP & 8) && elect_one()) {
          const int b0 = b2 == 2 ? 0 : b2 + 1;
          mbar_expect(sb + MB_X + 8 * b0, XT);
          tma_load3(sb + SM_X + b0 * XT, &tm.x, (tn + 1) * 32, sb + MB_X + 8 * b0);
        }
        if (tn < NSEG && (!(XP & 8) || tn < 3)) mbar_wait(sb + MB_X + 8 * b2, (tn / 3) & 1);
      } else if (w == 2) {
        if (!qk) { if (VW2 < 1) send_v(s + 1, 0); if (VW2 < 2) send_v(s + 1, 1); }
      } else if (qk || !NIC) {
        rearm();
      }
      __syncwarp();
      send_km();
      import();
      PROF(4);
      SCHED_FENCE(10);
      if (NIC) {
        if (qk) bar_sync(7, NII < 18 ? 384 : 256);
        xproj<0, 0, NIC>(acc, wa, dA);
        if (!qk) { if (w == 3) rearm(); bar_sync(7, NII < 18 ? 384 : 256); }
      } else {
        bar_sync(7, NII < 18 ? 384 : 256);
      }
      xproj<0, NIC, 18>(acc, wa, dA);
      bar_arrive(12, 256);
      dA += (int64_t)(b2 ? XT >> 4 : -(XT >> 3));
      finish(s + ah);
      if (qk && w == 0) wait_v(s + 1);
      bar_arrive(13, 384);
      PROF(6);
      SCHED_FENCE(13);
      bar_sync(14, 256);
      PROF(7);
      xproj<1, 0, 18>(acc, wa, dA);
      b2 = b2 == 2 ? 0 : b2 + 1;
      s++;
      PROFP(8);
    }
    send_km();
    PIN(t16);
    if (t16 - sb < 128) stg_relaxed(tm.red + (RED_SLOT(NSEG + 1) + RED_LINE(head_id() * 3 + rank)) + (t16 & 112), 0, 0, 0, 0);
  }
  bar_arrive(0, 384);
  STAMP(3);
  cluster_sync();
  STAMP(4);
}

DI void attn_role(const uint32_t sb, unsigned char* smem_raw, const RMaps& tm, const uint32_t RANK, const bf16* __restrict__ x, const bf16* __restrict__ mem0,
                  const int w, const int lane) {
  const int t2 = w * 32 + lane;
  uint32_t wo[8][4], w1[8][4];
  const uint32_t wo_lane = sb + ((lane & 7) + ((lane >> 4) << 3)) * 128 + (((w + 4 * ((lane >> 3) & 1)) ^ (lane & 7)) << 4);
  unsigned char* const g_red = tm.red;
  {
    const uint32_t tag = *(volatile unsigned*)&g_epoch + 1;
    QSTAMP(0);
    bar_sync(0, 160);
    QSTAMP(1);
    cluster_arrive();
    __half2 hx = __float2half2_rn(0.f);
    if (blockIdx.x < NSEG) {
      mbar_wait(sb + MB_XS, 0);
#pragma unroll
      for (int i = 0; i < 18; i++) { uint32_t v[4]; lds128(sb + SM_X + t2 * 16 + i * 2048, v); hx = amax4(hx, v); }
      fence_async();
      bar_sync(6, 128);
      if (t2 == 0) tma_load3(sb + SM_X, &tm.x, 0, sb + MB_X);
      __syncwarp();
    }
    if (t2 == 0) { sts64(sb + SC_EPO, (tag - 1) * NSEG + 1, tag & 1); sts32(sb + SC_UNSC, __float_as_uint(1.f)); sts128(sb + SC_DEAD, 0, 0, 0, 0x3f800000u); sts64(sb + SC_FPAR, 0, 0); sts128(sb + SC_ONES, 0x3f803f80u, 0x3f803f80u, 0x3f803f80u, 0x3f803f80u); }
    WSTAMP(27);
    uint32_t q[8] = {0, 0, 0, 0, 0, 0, 0, 0};
    QSTAMP(2);
    mbar_wait(sb + MB_WO3, 0);
    QSTAMP(3);
    uint32_t mv[5][4];
#pragma unroll
    for (int i = 0; i < 5; i++) {
      ldsm4(mv[i], sb + SM_M0 + (lane & 7) * (DM * 2) + min(w + 4 * i, 17) * 64 + (lane >> 3) * 16);
      if (blockIdx.x == 0) hx = amax4(hx, mv[i]);
    }
    sts32(sb + SC_SS + 4 * (12 + w), wexp(hx));
#pragma unroll
    for (int k = 0; k < 8; k++) {
      ldsm4t(wo[k], wo_lane + SM_WO3 + k * 2048); ldsm4t(w1[k], wo_lane + SM_WOST + k * 2048);
#pragma unroll
      for (int i = 0; i < 4; i++) { sq_acc(q[i], wo[k][i]); sq_acc(q[i], w1[k][i]); }
    }
    bar_sync(6, 128);
#pragma unroll
    for (int k = 0; k < 8; k++) sts128(sb + SM_WO3 + t2 * 16 + k * 2048, wo[k][0], wo[k][1], wo[k][2], wo[k][3]);
#pragma unroll
    for (int i = 0; i < 5; i++) {
      const int c = (w + 4 * i) * 32;
      if (c < DM) stsm4t(sb + SM_MEM + (c + c / 192 * 64 + lane) * 16, mv[i][0], mv[i][1], mv[i][2], mv[i][3]);
    }
    bar_arrive(1, 256); bar_arrive(2, 256); bar_arrive(9, 256);
    QSTAMP(4);
    mbar_wait(sb + MB_WO, 0);
    QSTAMP(5);
#pragma unroll
    for (int k = 0; k < 8; k++) ldsm4t(wo[k], wo_lane + SM_X + 2 * XT + k * 2048);
    fence_async();
    bar_sync(6, 128);
    if (t2 == 32) tma_load3(sb + SM_X + 2 * XT, &tm.x, 64, sb + MB_X + 16);
    __syncwarp();
#pragma unroll
    for (int k = 0; k < 8; k++)
#pragma unroll
      for (int i = 0; i < 4; i++) sq_acc(q[4 + i], wo[k][i]);
    float ss = 0.f;
#pragma unroll
    for (int i = 0; i < 8; i++) ss += bf_lo(q[i]) + bf_hi(q[i]);
    ss = warp_sum(ss);
    if (lane == 0) sts32(sb + SC_SS + 4 * (8 + w), __float_as_uint(ss));
    QSTAMP(6);
    bar_sync(11, 384);
    QSTAMP(7);
    if (t2 == 0) {
      float a[16];
#pragma unroll
      for (int i = 0; i < 4; i++) lds128f(sb + SC_SS + 16 * i, &a[4 * i]);
      stg_relaxed(&g_stats[blockIdx.x * 2], __float_as_uint(((a[0] + a[1]) + (a[2] + a[3])) + ((a[4] + a[5]) + (a[6] + a[7]))),
                  __float_as_uint((a[8] + a[9]) + (a[10] + a[11])),
                  max(max(__float_as_uint(a[12]), __float_as_uint(a[13])), max(__float_as_uint(a[14]), __float_as_uint(a[15]))), tag);
    }
    __syncwarp();
    WSTAMP(24);
    QSTAMP(8);
    cluster_wait();
    QSTAMP(9);
    if (w == 0) {
      uint4 v[3];
      int n = 0;
      while (true) {
#pragma unroll
        for (int i = 0; i < 3; i++) v[i] = ldg_relaxed(&g_stats[(i * 32 + lane) * 2]);
        if (__all_sync(0xffffffffu, v[0].w == tag && v[1].w == tag && v[2].w == tag) || ++n > SPIN_LIMIT) break;
        __nanosleep(100);
      }
      WSTAMP(25);
      QSTAMP(10);
      const float sv = warp_sum(__uint_as_float(v[0].x) + __uint_as_float(v[1].x) + __uint_as_float(v[2].x));
      const float so = warp_sum(__uint_as_float(v[0].y) + __uint_as_float(v[1].y) + __uint_as_float(v[2].y));
      const int expW = ((int)(__float_as_uint(sv) >> 23) + (int)(__float_as_uint(so) >> 23) - 254 + 2 + 10 + 1) >> 1;
      sts32(sb + SC_XMAX + 4 * lane, v[0].z); sts32(sb + SC_XMAX + 128 + 4 * lane, v[1].z);
      sts32(sb + SC_EXPW, expW + 1 - 15);
      if (blockIdx.x == 0 && lane == 0) *(volatile unsigned*)&g_epoch = tag;
      sts32(sb + SC_FPAR + 4, 1);
    } else if (w < 3) {
      const uint32_t u = blockIdx.x >> 4;
      unsigned char* const z = g_red + 98304 + (blockIdx.x & 15) * 128 + (u & 1) * 2048 + (u & 6) * 4096 + (((u >> 1) ^ w) & 1) * 4096 + lane * 4;
      stg_relaxed32(z, 0);
      uint32_t best = 0xffffffffu;
#pragma unroll 1
      for (int i = 0; i < 64; i++) {
        uint32_t last, dt;
        asm volatile("{\n.reg .pred p;\n.reg .u32 c, v;\nld.volatile.shared.u32 %0, [%3];\nmov.u32 c, %%clock;\n"
                     "atom.relaxed.gpu.global.exch.b32 v, [%2], 0;\nsetp.eq.u32 p, v, 0;\nmov.u32 %1, 0;\n@p mov.u32 %1, %%clock;\nsub.u32 %1, %1, c;\n}"
                     : "=r"(last), "=r"(dt) : "l"(z), "r"(sb + SC_FPAR + 4) : "memory");
        best = min(best, dt);
        if ((last && i >= NPROBE - 1) || i >= NPROBE2 - 1) break;
      }
      sts32(sb + SC_LAT + (w - 1) * 4, best);
    }
    QSTAMP(11);
    bar_sync(13, 384);
    bar_arrive(0, 384);
    QSTAMP(12);
    WSTAMP(26);
  }

  const uint32_t nh = __shfl_sync(0xffffffffu, near_half(sb), 0);
  uint32_t l16 = sb + lane * 16;
  PIN(l16);
#define LV ((l16 >> 4) & 31)
#define fence_reg l16
  const uint32_t red_lo = (uint32_t)(uint64_t)g_red, red_hi = (uint32_t)((uint64_t)g_red >> 32);
  uint32_t lp;
  auto slot = [&](int s, uint32_t c, uint32_t ofs) {
    const uint32_t lo = lp | (red_lo + ((w >> 1) * 4 + (w & 1) * 2 + ((w ^ c) & 1)) * 4096 + RED_SLOT(s) + ofs);
    uint64_t a; asm("mov.b64 %0, {%1, %2};" : "=l"(a) : "r"(lo), "r"(red_hi));
    return (unsigned char*)a;
  };
  const uint32_t always = __shfl_sync(0xffffffffu, lds32(sb + SC_DEAD + 12), 0);
  const int mode0 = RANK < 2 ? w : w | 4;
  auto hint_addr = [&](int s) { return min(LV, 23u) * 4 + (red_lo + HINT_OFF + nh * 4096 + w * 16384 + RED_SLOT(s)); };
  auto load_hints = [&](uint32_t lo) {
    uint64_t a; asm("mov.b64 %0, {%1, %2};" : "=l"(a) : "r"(lo), "r"(red_hi));
    return ldg_relaxed32((const void*)a);
  };
  int s = 0;
  bool bad = false;
#pragma unroll 1
  while (true) {
    const uint32_t par = s & 1;
    uint32_t vx[4][4], hints;
    auto load_vx = [&]() {
      const uint32_t va = l16 + (RANK < 2 ? SM_VC + par * 8192 : SM_BLK + (s & 3) * SEGB) + w * 1024 + ((LV >> 3) & 1) * 384 - (LV >> 4) * 128;
#pragma unroll
      for (int i = 0; i < 4; i++) ldsm4(vx[i], va + (i & 1) * 4096 + (i >> 1) * 256);
    };
    auto retire = [&](uint32_t x) {
      asm volatile("{\n.reg .pred p;\nsetp.eq.u32 p, %0, 0;\n@p exit;\n}" :: "r"(vx[0][0] | vx[1][0] | vx[2][0] | vx[3][0] | x) : "memory");
    };
    auto scores = [&](auto memkeys, auto first, float* sc) {
      constexpr bool MK = decltype(memkeys)::value, FIRST = decltype(first)::value;
      uint32_t kb[4][4], qb[2][4];
      const uint32_t m = LV >> 3;
      uint32_t kaddr = l16 + SM_BLK + 4096 + (s & 3) * SEGB + w * 2048 + (m & 1) * (MK ? 128 : 896) - (m >> 1) * 128;
      if (MK) { PIN(kaddr); }
      else {
#pragma unroll
        for (int k = 0; k < 4; k++) ldsm4t(kb[k], kaddr + k * 256);
      }
      if (FIRST) { load_vx(); retire(MK ? kaddr : kb[0][0] | kb[1][0] | kb[2][0] | kb[3][0] | l16); bar_sync(4, 256); PROF(4); }
      ldsm4t(qb[0], l16 + SM_QM);
      if (MK) ldsm4t(kb[0], kaddr);
      ldsm4t(qb[1], l16 + SM_QM + 512);
      if (MK) ldsm4t(kb[2], kaddr + 512);
      float c[4][4];
      mma16816z(c[0], kb[0], qb[0][0], qb[0][1]); mma16816z(c[1], kb[MK ? 0 : 1], qb[0][2], qb[0][3]);
      mma16816z(c[2], kb[2], qb[1][0], qb[1][1]); mma16816z(c[3], kb[MK ? 2 : 3], qb[1][2], qb[1][3]);
      if (FIRST && B5POS == 0) bar_arrive(5, N5);
#pragma unroll
      for (int i = 0; i < (MK ? 2 : 4); i++) sc[i] = ((c[0][i] + c[1][MK ? i + 2 : i]) + c[2][i]) + c[3][MK ? i + 2 : i];
    };
    auto send = [&](auto memkeys) {
      constexpr bool MK = decltype(memkeys)::value;
      constexpr int N = MK ? 1 : 2;
      const uint32_t sa = sb + LV * 4 + SM_E + (MK ? 1024 + RANK * 128 : RANK * 512 + w * 256);
      uint32_t ra[N][2], mb[N][2];
#pragma unroll
      for (int i = 0; i < N; i++)
#pragma unroll
        for (int j = 0; j < 2; j++) {
          ra[i][j] = mapa(sa + i * 128, j ? 2 : RANK ^ 1); mb[i][j] = mapa(sb + MB_S, j ? 2 : RANK ^ 1);
          PIN(ra[i][j]);
        }
      float sc[4];
      scores(memkeys, BoolC<true>(), sc);
      uint32_t e[N];
#pragma unroll
      for (int i = 0; i < N; i++) {
        e[i] = pack_bf16(ex2(sc[2 * i]), ex2(sc[2 * i + 1]));
        if (!(fmaxf(fabsf(sc[2 * i]), fabsf(sc[2 * i + 1])) <= E_LIM)) e[i] = 0x7fff7fffu;
        st_async1(ra[i][0], e[i], mb[i][0]);
        st_async1(ra[i][1], e[i], mb[i][1]);
      }
#pragma unroll
      for (int i = 0; i < N; i++) sts32(sa + i * 128, e[i]);
      __syncwarp();
      if (l16 == sb) mbar_arrive(sb + MB_S);
      PROF(5);
    };
    const int mode = bad ? 8 : mode0;
    if (mode < 2) {
      send(BoolC<false>());
    } else if (mode == 2) {
      send(BoolC<true>());
    } else if (mode == 8) {
      load_vx();
      retire(l16);
      const uint32_t fp = lds32(sb + SC_FPAR);
      bar_sync(6, 128);
      if (w == 0 && l16 == sb) { sts32(sb + SC_FPAR, fp ^ 1); mbar_expect(sb + MB_F, 3072); }
      if (RANK < 2 && w < 3) {
        float sc[4] = {0.f, 0.f, 0.f, 0.f};
        if (w < 2) scores(BoolC<false>(), BoolC<false>(), sc); else scores(BoolC<true>(), BoolC<false>(), sc);
#pragma unroll 1
        for (int r = 0; r < 3; r++)
          st_async4(mapa(l16 + SM_FB + RANK * 1536 + w * 512, r), __float_as_uint(sc[0]), __float_as_uint(sc[1]), __float_as_uint(sc[2]), __float_as_uint(sc[3]), mapa(sb + MB_F, r));
      }
      mbar_wait(sb + MB_F, fp);
      float a[12];
#pragma unroll
      for (int j = 0; j < 3; j++) {
        float b[4];
        lds128f(l16 + SM_FB + j * 512, a + 4 * j); lds128f(l16 + SM_FB + 1536 + j * 512, b);
#pragma unroll
        for (int i = 0; i < 4; i++) a[4 * j + i] += b[i];
      }
      float m0 = fmaxf(fmaxf(fmaxf(a[0], a[2]), fmaxf(a[4], a[6])), a[8]), m1 = fmaxf(fmaxf(fmaxf(a[1], a[3]), fmaxf(a[5], a[7])), a[9]);
#pragma unroll
      for (int o = 4; o < 32; o <<= 1) { m0 = fmaxf(m0, __shfl_xor_sync(0xffffffffu, m0, o)); m1 = fmaxf(m1, __shfl_xor_sync(0xffffffffu, m1, o)); }
#pragma unroll
      for (int i = 0; i < 5; i++) {
        const uint32_t ea = sb + SM_E + LV * 4 + (i < 4 ? i * 128 : 1024);
        sts32(ea, pack_bf16(ex2(a[2 * i] - m0), ex2(a[2 * i + 1] - m1)));
        sts32(ea + (i < 4 ? 512 : 128), 0x3f803f80u);
      }
      __syncwarp();
    } else {
      load_vx();
      if (mode == 3) bar_arrive(4, 256);
      retire(l16 + 1);
    }
    {
      uint32_t wa[4], wb[4], oc[4];
      constexpr int WS = 2048;
      const uint32_t w3a = l16 + SM_WO3 + w * 512;
      lds128(w3a + KP(0) * WS, wa); lds128(w3a + KP(1) * WS, wb); lds128(sb + SC_ONES, oc);
      if (B5POS == 1 && mode < 3) bar_arrive(5, N5);
      uint32_t e[10], p[5], vm[4], ob[4];
      float o0[4], o1[4], f[3][2][4], rs[4];
      reserve2(vm); reserve2(vm + 2); reserve2(e + 8);
      hints = hint_addr(s);
      PIN(hints);
      if (CLR & 2) asm volatile("{\n.reg .pred p;\nsetp.eq.u32 p, %0, 0;\n@p exit;\n}" :: "r"(wa[0] | wb[0] | oc[0] | hints) : "memory");
      mbar_wait(sb + MB_S, par);
      PROF(6);
      ldsm4t(e, l16 + SM_E); ldsm2t_in(e + 8, l16 + SM_E + 1024, always); ldsm4t(e + 4, l16 + SM_E + 512);
      lds128_in(vm, l16 + w * 512 + SM_VM, always);
      const float scl = __uint_as_float(lds32(sb + SC_UNSC + 8 - par * 8));
      hints = load_hints(hints);
      if (GF & 1) SCHED_FENCE(4);
#pragma unroll
      for (int i = 0; i < 4; i++) p[i] = mul_bf16(e[i], e[4 + i]);
      p[4] = mul_bf16(e[8], e[9]);
      mma16816z(o0, vx[0], p[0], p[1]); mma16816z(o1, vx[1], p[0], p[1]); mma16816z(rs, oc, p[0], p[1]);
      mma16816(o0, vx[2], p[2], p[3]); lds128_in(vx[2], w3a + KP(2) * WS, always);
      mma16816(o1, vx[3], p[2], p[3]); lds128_in(vx[3], w3a + KP(3) * WS, always);
      mma16816(rs, oc, p[2], p[3]);
      mma1688(o0, vm[0], vm[1], p[4]); mma1688(o1, vm[2], vm[3], p[4]); mma1688(rs, oc[0], oc[1], p[4]);
      stsm4(l16 + w * 512 + SM_OB, pack_bf16(o0[0], o0[1]), pack_bf16(o0[2], o0[3]), pack_bf16(o1[0], o1[1]), pack_bf16(o1[2], o1[3]));
      bar_sync(6, 128);
      PROF(7);
      ldsm4t_in(oc, l16 + SM_OB, always);
      bad = __any_sync(0xffffffffu, !(rs[0] + rs[1] > 0.f) && !bad);
      rs[0] *= scl; rs[1] *= scl;
      asm volatile("{\n.reg .pred p;\nsetp.ne.u32 p, %1, 0;\n@p rcp.approx.ftz.f32 %0, %0;\n}" : "+f"(rs[0]) : "r"(always));
      asm volatile("{\n.reg .pred p;\nsetp.ne.u32 p, %1, 1;\n@p rcp.approx.ftz.f32 %0, %0;\n}" : "+f"(rs[1]) : "r"(always));
      asm volatile("lop3.b32 %0, %1, %2, %3, 0xfe;" : "=r"(lp) : "r"((l16 & 128) * 2), "r"((l16 & 256) * 4), "r"(l16 & 112));
      if (bad) continue;
      ldsm4t(ob, l16 + SM_OB + 512);
      mma16816z(f[2][0], wa, oc[0], oc[1]); mma16816z(f[2][1], wb, oc[2], oc[3]);
      mma16816z(f[0][0], wo[0], oc[0], oc[1]); mma16816z(f[0][1], wo[4], oc[2], oc[3]);
      mma16816z(f[1][0], w1[0], oc[0], oc[1]); mma16816z(f[1][1], w1[4], oc[2], oc[3]);
      ldsm4t_in(oc, l16 + SM_OB + 1024, always);
      mma16816(f[2][0], vx[2], ob[0], ob[1]); lds128_in(vx[2], w3a + KP(4) * WS, always);
      mma16816(f[2][1], vx[3], ob[2], ob[3]); lds128_in(vx[3], w3a + KP(5) * WS, always);
      mma16816(f[0][0], wo[1], ob[0], ob[1]); mma16816(f[0][1], wo[5], ob[2], ob[3]);
      mma16816(f[1][0], w1[1], ob[0], ob[1]); mma16816(f[1][1], w1[5], ob[2], ob[3]);
      ldsm4t_in(ob, l16 + SM_OB + 1536, always);
      mma16816(f[0][0], wo[2], oc[0], oc[1]); mma16816(f[0][1], wo[6], oc[2], oc[3]);
      mma16816(f[2][0], vx[2], oc[0], oc[1]); lds128_in(vx[2], w3a + KP(6) * WS, always);
      mma16816(f[2][1], vx[3], oc[2], oc[3]); lds128_in(vx[3], w3a + KP(7) * WS, always);
      mma16816(f[1][0], w1[2], oc[0], oc[1]); mma16816(f[1][1], w1[6], oc[2], oc[3]);
      mma16816(f[0][0], wo[3], ob[0], ob[1]); mma16816(f[0][1], wo[7], ob[2], ob[3]);
      mma16816(f[1][0], w1[3], ob[0], ob[1]); mma16816(f[1][1], w1[7], ob[2], ob[3]);
      mma16816(f[2][0], vx[2], ob[0], ob[1]); mma16816(f[2][1], vx[3], ob[2], ob[3]);
      bar_arrive(7, NII < 18 ? 384 : 256);
      lds128_in(ob, sb + SC_DEAD, always);
      uint32_t h[3][2];
#pragma unroll
      for (int j = 0; j < 3; j++)
#pragma unroll
        for (int i = 0; i < 2; i++)
        {
          scale_sum(f[j][1][2 * i], f[j][0][2 * i], rs[0], always); scale_sum(f[j][1][2 * i + 1], f[j][0][2 * i + 1], rs[1], always);
          h[j][i] = pack_f16(f[j][1][2 * i], f[j][1][2 * i + 1]);
        }
      const uint32_t rofs = RANK * 32768;
      red_f16x8(slot(s, RANK >> 1, rofs), h[0][0], h[1][0], h[2][0], 0x3c00u);
      red_f16x8(slot(s, (RANK >> 1) ^ 1, rofs), h[0][1], h[1][1], h[2][1], 0x3c00u);
      if (NII == 18) bar_arrive(10, 256);
      SCHED_FENCE(5);
      l16 += ob[B7R];
    }
    {
    PROF(8);
    const uint32_t ma0 = l16 + SM_MEM + w * 128 + (LV >> 3) * 896 + nh * 512;
    const unsigned char* const sl[2] = {slot(s, nh, 0), slot(s, nh ^ 1, 0)};
    uint32_t dl = gtime() - 1984;
    uint32_t late = latest_hint(hints, dl, s);
    if (late >= 64) {
      int n = 0;
#pragma unroll 1
      do {
        hints = load_hints(hint_addr(s));
        dl = gtime() - 1984;
        late = latest_hint(hints, dl, s);
      } while (late >= 64 && ++n < SPIN_LIMIT);
    }
    dl += late * 32 + tm.poll;
    PROF(9);
    {
      auto wait_until = [&](uint32_t t) {
        asm volatile("{\n.reg .pred p;\n.reg .s32 c;\n.reg .u64 t;\nTL: mov.u64 t, %%globaltimer;\ncvt.u32.u64 c, t;\nsub.s32 c, c, %0;\nsetp.lt.s32 p, c, 0;\n@p bra.uni TL;\n}" :: "r"(t + (l16 & 15)) : "memory");
      };
      uint4 v[2][3];
      auto load = [&](int c) {
#pragma unroll
        for (int r = 0; r < 3; r++) v[c][r] = ldg_relaxed(sl[c ^ (r >> 1)] + r * 32768);
      };
      auto decode = [&](int c, int n) {
        uint32_t q[9];
        __half2 hm;
        const uint32_t ma = ma0 ^ (c * 512);
#pragma unroll
        for (int i = 0; i < 9; i++) {
          const uint32_t h = i % 3 == 0 ? v[c][i / 3].x : (i % 3 == 1 ? v[c][i / 3].y : v[c][i / 3].z);
          const float2 f = __half22float2(*(const __half2*)&h);
          q[i] = pack_bf16(f.x, f.y);
          hm = i ? __hmax2(hm, __habs2(*(const __half2*)&h)) : __habs2(*(const __half2*)&h);
        }
#pragma unroll
        for (int r = 0; r < 3; r++) stsm4(ma + r * 4096, q[3 * r], q[3 * r + 1], q[3 * r + 2], r < 2 ? v[c][r].w : *(const uint32_t*)&hm);
        const bool done = __all_sync(0xffffffffu, v[c][0].w == 0x5000u && v[c][1].w == 0x5000u && v[c][2].w == 0x5000u) || n > SPIN_LIMIT;
        asm volatile("{\n.reg .pred p;\nsetp.ne.u32 p, %0, 0;\n@p bar.arrive %1, 256;\n}" :: "r"((int)done), "r"(1 + c) : "memory");
        return done;
      };
      if (LEAD) { wait_until(dl - LEAD); load(1); }
      wait_until(dl);
      PROF(10);
      int n = 0;
#pragma unroll 1
      do {
        load(0);
        if (!LEAD) load(1);
        asm volatile("{\n.reg .pred p;\nsetp.eq.u32 p, %0, 0;\n@p bar.sync 13, 384;\n}" :: "r"(n) : "memory");
      } while (!decode(0, n++));
      PROF(11);
#pragma unroll 1
      while (!decode(1, n++)) load(1);
      bar_arrive(9, 256);
      PROF(12);
    }
    PROF(13);
    if (++s == NSEG - 1) break;
    }
  }
#undef fence_reg
  if (RANK < 2) bar_arrive(4, 256);
  bar_sync(0, 384);
  cluster_sync();
}

__global__ void __cluster_dims__(3, 1, 1) __launch_bounds__(384, 1)
rec_kernel(const __grid_constant__ RMaps tm, const bf16* __restrict__ x, const bf16* __restrict__ mem0) {
  extern __shared__ __align__(1024) unsigned char smem_raw[];
  const uint32_t sb = smem_u32(smem_raw);
  const int tid = threadIdx.x, lane = tid & 31;
  const int wg = __shfl_sync(0xffffffffu, tid >> 7, 0);
  const int w = __shfl_sync(0xffffffffu, (tid >> 5) & 3, 0);
  uint32_t rank; asm("mov.u32 %0, %%cluster_ctarank;" : "=r"(rank));
  STAMP(0);
  asm volatile("griddepcontrol.launch_dependents;" ::: "memory");

  if (wg < 2) {
    asm volatile("setmaxnreg.inc.sync.aligned.u32 192;");
    if (tid == 0) {
      for (int i = 0; i < 3; i++) { mbar_init(sb + MB_W + 8 * i, 1); mbar_init(sb + MB_X + 8 * i, 1); }
      mbar_init(sb + MB_WO, 1); mbar_init(sb + MB_WO3, 1);
      mbar_init(sb + MB_S, rank < 2 ? 5 : 6);
      mbar_init(sb + MB_F, 1); mbar_init(sb + MB_XS, 1);
      mbar_init(sb + MB_VX, 1); mbar_init(sb + MB_VX + 8, 1);
      asm volatile("fence.mbarrier_init.release.cluster;" ::: "memory");
      fence_async();
      const int h = blockIdx.x / 3;
      const CUtensorMap* m0 = rank < 2 ? &tm.wk : &tm.wv;
      const CUtensorMap* m1 = rank < 2 ? &tm.wq : &tm.wv;
      const int c0 = h * DH + (rank == 1 ? 64 : 0), c1 = h * DH + (rank == 0 ? 0 : 64);
      auto load_w = [&](int c) {
        mbar_expect(sb + MB_W + 8 * c, 49152);
        tma_load(sb + SM_STAGE + c * 49152, m0, c0, c * 192, sb + MB_W + 8 * c);
        tma_load(sb + SM_STAGE + c * 49152 + 24576, m1, c1, c * 192, sb + MB_W + 8 * c);
      };
      for (int i = 0; i < 3; i++) mbar_expect(sb + MB_X + 8 * i, XT);
      if (blockIdx.x < NSEG) { mbar_expect(sb + MB_XS, XT); bulk_load(sb + SM_X, x + blockIdx.x * 32 * DM, XT, sb + MB_XS); }
      for (int c = 0; c < WPOS; c++) load_w(c);
      mbar_expect(sb + MB_WO3, 32768 + 8 * DM * 2);
      tma_load(sb + SM_WOST, &tm.wo, rank * 192 + 64, h * DH, sb + MB_WO3);
      tma_load(sb + SM_WO3, &tm.wo, rank * 192 + 128, h * DH, sb + MB_WO3);
      bulk_load(sb + SM_M0, mem0, 8 * DM * 2, sb + MB_WO3);
      tma_prefetch(&tm.wo, rank * 192, h * DH);
      if (blockIdx.x >= NSEG) tma_load3(sb + SM_X, &tm.x, 0, sb + MB_X);
      for (int c = WPOS; c < 3; c++) load_w(c);
      mbar_expect(sb + MB_WO, 16384);
      mbar_expect(sb + MB_S, rank < 2 ? 640 + 2048 : 1280);
      mbar_expect(sb + MB_VX, 8192); mbar_expect(sb + MB_VX + 8, 8192);
    }
    __syncwarp();
    QSTAMP(0);
    if (tid < 32) bar_arrive(0, 160);
    QSTAMP(1);
    proj_role(sb, tm, rank, wg, w, lane);
  } else {
    asm volatile("setmaxnreg.dec.sync.aligned.u32 120;");
    attn_role(sb, smem_raw, tm, rank, x, mem0, w, lane);
  }
}

constexpr int NAUX = 36;
constexpr int A_ST = 6, A_STAGE = 8192 + 12288, A_W8 = A_ST * A_STAGE, A_EXC = A_W8 + A_ST * 1536, A_ROWS = 57;
constexpr int A_XT = 3 * XT, A_XW = A_XT + 3 * 4096;
constexpr int A_IN = A_EXC + 8 * 2304, A_INB = 3 * SEGB, A_OST = A_IN + 2 * A_INB, A_P = A_OST + 8192, A_G = A_P + 3072;
constexpr int A_BAR = A_G + 1024;
constexpr int A_TOTAL = A_BAR + 512;
static_assert(A_IN % 1024 == 0 && A_IN >= 4 * XT && A_IN + 64 * DM * 2 <= A_BAR && A_TOTAL <= 232448, "side kernel shared memory");
struct AMaps { CUtensorMap x, wa, wa8, o, o3, wob, woa; const unsigned char* red; uint32_t poll; };

DI void wgmma_n192_ss_nt(float* d, uint64_t da, uint64_t db, int acc) {
  asm volatile("{\n.reg .pred p;\nsetp.ne.b32 p, %98, 0;\n"
               "wgmma.mma_async.sync.aligned.m64n192k16.f32.bf16.bf16 {"
               "%0,%1,%2,%3,%4,%5,%6,%7,%8,%9,%10,%11,%12,%13,%14,%15,%16,%17,%18,%19,%20,%21,%22,%23,%24,%25,%26,%27,%28,%29,%30,%31,"
               "%32,%33,%34,%35,%36,%37,%38,%39,%40,%41,%42,%43,%44,%45,%46,%47,%48,%49,%50,%51,%52,%53,%54,%55,%56,%57,%58,%59,%60,%61,%62,%63,"
               "%64,%65,%66,%67,%68,%69,%70,%71,%72,%73,%74,%75,%76,%77,%78,%79,%80,%81,%82,%83,%84,%85,%86,%87,%88,%89,%90,%91,%92,%93,%94,%95"
               "}, %96, %97, p, 1, 1, 0, 1;\n}\n"
               : ACC8(d, 0), ACC8(d, 8), ACC8(d, 16), ACC8(d, 24), ACC8(d, 32), ACC8(d, 40), ACC8(d, 48), ACC8(d, 56),
                 ACC8(d, 64), ACC8(d, 72), ACC8(d, 80), ACC8(d, 88) : "l"(da), "l"(db), "r"(acc));
}
DI void wgmma_n24_ss_nt(float* d, uint64_t da, uint64_t db, int acc) {
  asm volatile("{\n.reg .pred p;\nsetp.ne.b32 p, %14, 0;\n"
               "wgmma.mma_async.sync.aligned.m64n24k16.f32.bf16.bf16 {%0,%1,%2,%3,%4,%5,%6,%7,%8,%9,%10,%11}, %12, %13, p, 1, 1, 0, 1;\n}\n"
               : ACC8(d, 0), "+f"(d[8]), "+f"(d[9]), "+f"(d[10]), "+f"(d[11]) : "l"(da), "l"(db), "r"(acc));
}
DI void tma_load3d(uint32_t dst, const CUtensorMap* m, int c0, int c1, int c2, uint32_t mb) {
  asm volatile("cp.async.bulk.tensor.3d.shared::cluster.global.mbarrier::complete_tx::bytes [%0], [%1, {%3, %4, %5}], [%2];"
               :: "r"(dst), "l"(m), "r"(mb), "r"(c0), "r"(c1), "r"(c2) : "memory");
}
DI uint32_t trans8(uint32_t x) { uint32_t r; asm("movmatrix.sync.aligned.m8n8.trans.b16 %0, %1;" : "=r"(r) : "r"(x)); return r; }
DI void wgmma_n32_ss_tn(float* d, uint64_t da, uint64_t db) {
  asm volatile("wgmma.mma_async.sync.aligned.m64n32k16.f32.bf16.bf16 {%0,%1,%2,%3,%4,%5,%6,%7,%8,%9,%10,%11,%12,%13,%14,%15}, "
               "%16, %17, 1, 1, 1, 1, 0;"
               : ACC8(d, 0), ACC8(d, 8) : "l"(da), "l"(db));
}
DI void wgmma_n40_ss(float* d, uint64_t da, uint64_t db, int acc) {
  asm volatile("{\n.reg .pred p;\nsetp.ne.b32 p, %22, 0;\n"
               "wgmma.mma_async.sync.aligned.m64n40k16.f32.bf16.bf16 {%0,%1,%2,%3,%4,%5,%6,%7,%8,%9,%10,%11,%12,%13,%14,%15,%16,%17,%18,%19}, "
               "%20, %21, p, 1, 1, 1, 1;\n}\n"
               : ACC8(d, 0), ACC8(d, 8), "+f"(d[16]), "+f"(d[17]), "+f"(d[18]), "+f"(d[19]) : "l"(da), "l"(db), "r"(acc));
}
DI uint2 ldg_relaxed64(const void* p) {
  uint2 v; asm volatile("ld.relaxed.gpu.global.v2.b32 {%0,%1}, [%2];" : "=r"(v.x), "=r"(v.y) : "l"(p) : "memory"); return v;
}
template <int ST> DI void ldg8x64(uint32_t* m, const void* p) {
  asm volatile("ld.relaxed.gpu.global.v2.b32 {%0,%1}, [%16];\nld.relaxed.gpu.global.v2.b32 {%2,%3}, [%16 + %17];\n"
               "ld.relaxed.gpu.global.v2.b32 {%4,%5}, [%16 + %18];\nld.relaxed.gpu.global.v2.b32 {%6,%7}, [%16 + %19];\n"
               "ld.relaxed.gpu.global.v2.b32 {%8,%9}, [%16 + %20];\nld.relaxed.gpu.global.v2.b32 {%10,%11}, [%16 + %21];\n"
               "ld.relaxed.gpu.global.v2.b32 {%12,%13}, [%16 + %22];\nld.relaxed.gpu.global.v2.b32 {%14,%15}, [%16 + %23];"
               : "=r"(m[0]), "=r"(m[1]), "=r"(m[2]), "=r"(m[3]), "=r"(m[4]), "=r"(m[5]), "=r"(m[6]), "=r"(m[7]),
                 "=r"(m[8]), "=r"(m[9]), "=r"(m[10]), "=r"(m[11]), "=r"(m[12]), "=r"(m[13]), "=r"(m[14]), "=r"(m[15])
               : "l"(p), "n"(ST), "n"(2 * ST), "n"(3 * ST), "n"(4 * ST), "n"(5 * ST), "n"(6 * ST), "n"(7 * ST) : "memory");
}
template <int ST> DI void ldg4x128(uint32_t* m, const void* p) {
  asm volatile("ld.relaxed.gpu.global.v4.b32 {%0,%1,%2,%3}, [%16];\nld.relaxed.gpu.global.v4.b32 {%4,%5,%6,%7}, [%16 + %17];\n"
               "ld.relaxed.gpu.global.v4.b32 {%8,%9,%10,%11}, [%16 + %18];\nld.relaxed.gpu.global.v4.b32 {%12,%13,%14,%15}, [%16 + %19];"
               : "=r"(m[0]), "=r"(m[1]), "=r"(m[2]), "=r"(m[3]), "=r"(m[4]), "=r"(m[5]), "=r"(m[6]), "=r"(m[7]),
                 "=r"(m[8]), "=r"(m[9]), "=r"(m[10]), "=r"(m[11]), "=r"(m[12]), "=r"(m[13]), "=r"(m[14]), "=r"(m[15])
               : "l"(p), "n"(ST), "n"(2 * ST), "n"(3 * ST) : "memory");
}
template <int N, int ST> DI bool stale(const uint32_t* m, uint32_t tag) {
  uint32_t x = m[0] ^ tag;
#pragma unroll
  for (int i = 1; i < N; i++) asm("lop3.b32 %0, %0, %1, %2, 0xf6;" : "+r"(x) : "r"(m[i * ST]), "r"(tag));
  return __any_sync(0xffffffffu, x & 1);
}
DI bool mbar_test(uint32_t b, uint32_t par) {
  uint32_t r; asm volatile("{\n.reg .pred p;\nmbarrier.test_wait.parity.shared::cta.b64 p, [%1], %2;\nselp.u32 %0, 1, 0, p;\n}" : "=r"(r) : "r"(b), "r"(par) : "memory");
  return r;
}
DI int wait_flags(const unsigned* p, bool active, unsigned base, int seg) {
  int n = 0, m;
  while (true) {
    m = __reduce_min_sync(0xffffffffu, active ? (int)(ldg_acquire32(p) - base) : NSEG);
    if (m > seg || ++n > SPIN_LIMIT) break;
    __nanosleep((YP & 32) ? 400 : 40);
  }
  return max(m, seg + 1);
}
DI void wait_count(const unsigned* p, unsigned target) {
  int n = 0;
  unsigned v;
  while (true) {
    asm volatile("ld.acquire.gpu.global.b32 %0, [%1];" : "=r"(v) : "l"(p) : "memory");
    if ((int)(v - target) >= 0 || ++n > SPIN_LIMIT) break;
    __nanosleep(64);
  }
}
#define PACE_NEXT 800
#define AWARM 0
#define PING 1
#define FLAG 2
#define FPOS 1
#define QB 1
#define Q_LO 0
#define Q_HI 320
DI void tick_wait(uint32_t pace, int step) {
  const int n = lds32(pace);
  if (n <= step) mbar_wait(pace + 8, n & 1);
}
DI void quiet_wait(uint32_t pace) {
  uint32_t n, d;
  lds64(pace, n, d);
  if (n - 1 < NSEG - 2 && (int)(gtime() - d) > Q_HI) mbar_wait(pace + 8, n & 1);
}
DI void sleep_until(uint32_t t) {
  for (int n = 0; n < 64; n++) {
    const int r = t - gtime();
    if (r <= 0) break;
    __nanosleep(r >> 1);
  }
}
DI void aux_barrier(int i, unsigned epoch, bool wait = true) {
  asm volatile("fence.proxy.async;" ::: "memory");
  asm volatile("red.release.gpu.global.add.u32 [%0], 1;" :: "l"(&g_abar[i * 32]) : "memory");
  if (!wait) return;
  wait_count(&g_abar[i * 32], NAUX * (epoch + 1));
  asm volatile("fence.proxy.async;" ::: "memory");
}

__global__ void __launch_bounds__(512, 1)
aux_kernel(const __grid_constant__ AMaps tm, const bf16* __restrict__ x, const bf16* __restrict__ gate_w, bf16* __restrict__ out) {
  extern __shared__ __align__(1024) unsigned char smem_raw[];
  const uint32_t sb = smem_u32(smem_raw);
  const uint32_t full1 = sb + A_BAR, empty1 = full1 + 8 * A_ST, fullw = empty1 + 8 * A_ST, full3 = fullw + 16, empty3 = full3 + 32,
                 fulla = empty3 + 32, emptya = fulla + 32, fullg = emptya + 16, pace = fullg + 8;
  const int tid = threadIdx.x, lane = tid & 31, cta = blockIdx.x;
  const int wg = __shfl_sync(0xffffffffu, tid >> 7, 0), w = __shfl_sync(0xffffffffu, (tid >> 5) & 3, 0);
  ASTAMP(14);
  const unsigned epoch = *(volatile unsigned*)&g_epoch2;
  if (tid == 0) {
    for (int i = 0; i < A_ST; i++) { mbar_init(full1 + 8 * i, 1); mbar_init(empty1 + 8 * i, 8); }
    mbar_init(fullw, 1); mbar_init(fullw + 8, 1); mbar_init(fullg, 1);
    for (int i = 0; i < 2; i++) { mbar_init(fulla + 16 * i, 2); mbar_init(fulla + 16 * i + 8, 2); mbar_init(emptya + 8 * i, 4); }
    sts64(pace, 0, 0); mbar_init(pace + 8, 1); sts32(pace + 16, 0); sts64(pace + 24, 65536, 0xffff0000u);
    for (int i = 0; i < 4; i++) { mbar_init(full3 + 8 * i, 1); mbar_init(empty3 + 8 * i, cta < NH ? 8 : 4); }
    fence_async();
  }
  __syncthreads();
  ASTAMP(0);
  const bool wide = cta < NH;
  auto p3_ks = [&](int g) { return wide ? cta >> 2 : 2 * (cta - NH) + g; };
  auto p3_mt = [&](int g) { return wide ? 2 * (cta & 3) + g : 8; };
  const uint32_t xt = sb + (wide ? A_XT : A_IN), xw = sb + (wide ? A_XW : A_IN + 16384);
  const unsigned fbase = epoch * NSEG;
  if (wg == 3) {
    asm volatile("setmaxnreg.dec.sync.aligned.u32 48;");
    if (w == 1 && cta < NH) {
#pragma unroll 1
      for (int seg = 0; seg < ((XP & 2048) ? 0 : NSEG); seg++) {
        bar_arrive(5, 160);
        if (seg > 0 && lane == 0) {
          asm volatile("cp.async.bulk.wait_group 0;" ::: "memory");
          stg_relaxed32(&g_oflag[cta * 32], fbase + seg);
        }
        __syncwarp();
        bar_sync(4, 160);
        if (QM & 16) tick_wait(pace, seg + 1);
        if (lane == 0) {
          fence_async();
          if (!(YP & 2)) {
          tma_store(&tm.o, sb + A_OST, cta * DH, seg * 32);
          tma_store(&tm.o, sb + A_OST + 4096, cta * DH + 64, seg * 32);
          }
          asm volatile("cp.async.bulk.commit_group;" ::: "memory");
          asm volatile("cp.async.bulk.wait_group.read 0;" ::: "memory");
        }
        __syncwarp();
      }
      if (lane == 0) {
        asm volatile("cp.async.bulk.wait_group 0;" ::: "memory");
        stg_relaxed32(&g_oflag[cta * 32], fbase + NSEG);
      }
    }
    if (w == 2 && cta < NH) {
      const uint32_t ktag = (epoch + 1) & 1, ma = sb + A_IN + 8192 + lane * 16;
      int avail = 0;
      bar_sync(10, 64);
#pragma unroll 1
      for (int seg = 0; seg < ((XP & 2048) ? 0 : NSEG); seg++) {
        if (avail <= seg) avail = wait_flags(&g_sflag[(cta * 3 + min(lane, 2)) * 8], true, fbase, seg);
        if (QM & 8) tick_wait(pace, seg);
        const unsigned char* km = g_km + (size_t)(seg * NH + cta) * 4096 + lane * 8;
        uint32_t m[16];
        const float g = __ldcg(&g_gate[seg * 32 + lane]);
        ldg8x64<256>(m, km);
        const uint32_t b = seg & 1, full = fulla + 16 * b, mb = ma + b * A_INB;
        mbar_wait(emptya + 8 * b, (~seg >> 1) & 1);
        if (lane < 2) mbar_expect(full + 8 * lane, (YP & 8) ? 0 : 16384 >> lane);
        __syncwarp();
        if (lane < 3 && !(YP & 8)) bulk_load(sb + A_IN + b * A_INB + lane * SEGB, g_seg + ((size_t)(seg & RING) * 96 + cta * 3 + lane) * 8192, 8192, full + (lane & 2) * 4);
        int n = 0;
#pragma unroll 1
        while (stale<8, 2>(m, ktag) && ++n < SPIN_LIMIT) { if (seg < NSEG - 1) __nanosleep(200); ldg8x64<256>(m, km); }
#pragma unroll
        for (int i = 0; i < 4; i++) stsm4(mb + (i >> 1) * SEGB + (i & 1) * 512, m[4 * i], m[4 * i + 1], m[4 * i + 2], m[4 * i + 3]);
        sts32(sb + A_G + b * 128 + lane * 4, __float_as_uint(1.f - g));
        fence_async();
        __syncwarp();
        if (lane == 0) mbar_arrive(full);
#pragma unroll 1
        do ldg4x128<512>(m, km + 2048 + lane * 8); while (stale<4, 4>(m, ktag) && ++n < SPIN_LIMIT);
#pragma unroll
        for (int i = 0; i < 4; i++) stsm4(mb + 2 * SEGB + (lane >> 4) * 768 + i * 256, m[4 * i], m[4 * i + 1], m[4 * i + 2], m[4 * i + 3]);
        fence_async();
        __syncwarp();
        if (lane == 0) mbar_arrive(full + 8);
      }
    }
    if (w == 3 && QM) {
      const unsigned char* const hp = tm.red + HINT_OFF + 65536 + (cta & 1) * 4096 + min(lane, 23) * 4;
      uint32_t d = 0;
      int s = 0, n = 0;
#pragma unroll 1
      while (s < NSEG - 1) {
        const uint32_t h = ldg_relaxed32(hp + RED_SLOT(s)), t = (gtime() - 1984) & ~31u, late = latest_hint(h, t, s);
        if (late < 64) {
          d = t + late * 32 + tm.poll + Q_LO;
          sleep_until(d);
          s++; n = 0;
          if (lane == 0) { mbar_arrive(pace + 8); sts64(pace, s < NSEG - 1 ? s : 2 * NSEG, d); }
          sleep_until(d + PACE_NEXT);
        } else {
          if (++n > (s ? 16 : 256) || lds32(pace + 16)) break;
          if (!s) __nanosleep(100);
        }
      }
      if (s < NSEG - 1 && lane == 0) { mbar_arrive(pace + 8); sts64(pace, 2 * NSEG, d); }
    }
    if (w != 0) return;
    const bool lead = lane == 0;
    if (lead) {
#pragma unroll 1
      for (int it = 0, st = 0, ph = 1, k = 0, col = (cta & 1) * (DM / 2); it < ((XP & 256) ? 0 : 72); it++) {
        mbar_wait(empty1 + 8 * st, ph);
        if (QM & 1) quiet_wait(pace);
        mbar_expect(full1 + 8 * st, A_STAGE + 1536);
        tma_load3d(sb + st * A_STAGE, &tm.x, k, (cta >> 1) * A_ROWS - 7, 0, full1 + 8 * st);
        tma_load3d(sb + st * A_STAGE + 8192, &tm.wa, col, k, 0, full1 + 8 * st);
        tma_load3d(sb + A_W8 + st * 1536, &tm.wa8, col + 64, k, 0, full1 + 8 * st);
        if (++st == A_ST) { st = 0; ph ^= 1; }
        k += 32;
        if (k == DM) { k = 0; col += 72; }
      }
    }
    __syncwarp();
    auto load_wo = [&](uint32_t dst, int g, int kb, uint32_t mb) {
      if (kb < 64) tma_load(dst, &tm.wob, p3_mt(g) * 64, kb * 64, mb);
      else tma_load(dst, &tm.woa, p3_mt(g) * 64, (kb - 64) * 64, mb);
    };
    if (!(XP & 256)) for (int st = 0; st < A_ST; st++) mbar_wait(empty1 + 8 * st, 1);
    if (QM & 2) quiet_wait(pace);
    if (lead) mbar_expect(fullw, 16 * 8192);
    __syncwarp();
    if (lane < 16) load_wo(sb + lane * 8192, lane >> 3, p3_ks(lane >> 3) * 9 + (lane & 7), fullw);
    __syncwarp(); bar_sync(6, 288);
    if (lead) mbar_expect(fullw + 8, 2 * 8192);
    __syncwarp();
    if (lane < 2) load_wo(sb + (16 + lane) * 8192, lane, p3_ks(lane) * 9 + 8, fullw + 8);
    __syncwarp();
    if (lead) aux_barrier(1, epoch, p3_ks(1) == 7);
    __syncwarp(); bar_sync(6, 288);
    {
      int avail = 0, sl = 0, ph = 1;
      const int h = (9 * p3_ks(0) >> 1) + lane;
#pragma unroll 1
      for (int seg = 0; seg < ((XP & 2048) ? 0 : NSEG); seg++) {
        if (avail <= seg) avail = wait_flags(&g_oflag[min(h, NH - 1) * 32], lane < (wide ? 5 : 9), fbase, seg);
        SSTAMP(seg, 4);
        for (int g = 0; g < (wide ? 1 : 2); g++) {
          const int ks = p3_ks(g);
          mbar_wait(empty3 + 8 * sl, ph);
          if (QM & 4) tick_wait(pace, seg + (QM >> 4 & 1) + 1);
          if (lead && (YP & 4)) mbar_arrive(full3 + 8 * sl);
          else if (lead) {
            mbar_expect(full3 + 8 * sl, XT + (ks == 7 ? (seg ? 4096 : wide ? 20480 : 12288) : 0));
            tma_load3d(sb + sl * XT, &tm.o3, 0, seg * 32, ks * 9, full3 + 8 * sl);
            if (ks == 7) {
              tma_load(xt + sl * 4096, &tm.o, 72 * 64, seg * 32, full3 + 8 * sl);
              if (seg == 0) { load_wo(xw + 8192, 1, 72, full3 + 8 * sl); if (wide) load_wo(xw, 0, 72, full3 + 8 * sl); }
            }
          }
          __syncwarp();
          if (++sl == (wide ? 3 : 4)) { sl = 0; ph ^= 1; }
        }
      }
    }
    sts32(pace + 16, 1);
    __syncwarp(); bar_sync(6, 288);
    asm volatile("griddepcontrol.wait;" ::: "memory");
  } else if (wg == 2) {
    asm volatile("setmaxnreg.dec.sync.aligned.u32 64;");
    if (cta < NH) {
      if (tid == 256) { mbar_expect(fullg, 64 * DM * 2); bulk_load(sb + A_IN, x + cta * 64 * DM, 64 * DM * 2, fullg); }
      uint32_t gw[9];
#pragma unroll
      for (int j = 0; j < 9; j++) gw[j] = ((const uint32_t*)gate_w)[j * 32 + lane];
      mbar_wait(fullg, 0);
      float mine = 0.f;
#pragma unroll 4
      for (int u = 0; u < 16; u++) {
        float d0 = 0.f, d1 = 0.f;
#pragma unroll
        for (int j = 0; j < 9; j++) {
          const uint32_t a = lds32(sb + A_IN + (w * 16 + u) * (DM * 2) + j * 128 + lane * 4);
          d0 = fmaf(bf_lo(a), bf_lo(gw[j]), d0); d1 = fmaf(bf_hi(a), bf_hi(gw[j]), d1);
        }
        d0 = warp_sum(d0 + d1);
        if (lane == u) mine = d0;
      }
      if (lane < 16) g_gate[cta * 64 + w * 16 + lane] = 1.f / (1.f + __expf(-mine));
      fence_async();
    }
    bar_sync(3, 128);
    if (tid == 256) { aux_barrier(0, epoch); if (cta == 0) *(volatile unsigned*)&g_epoch2 = epoch + 1; }
    __syncwarp();
    bar_sync(3, 128);
    if (w == 0) bar_arrive(8, 288);
    if (w == 1 && cta < NH) bar_arrive(10, 64);
    if (cta < NH) {
      CDECL;
#pragma unroll 1
      for (int seg = 0; seg < ((XP & 2048) ? 0 : NSEG); seg++) {
        CSTAMP(0);
        const uint32_t in = sb + A_IN + (seg & 1) * A_INB;
        const uint64_t qd = make_desc(in, 128, 1024, 0);
        mbar_wait(fulla + 16 * (seg & 1), (seg >> 1) & 1);
        CSTAMP(3);
        SSTAMP(seg, 0);
        float d[2][16];
        {
          float a[20];
          WG_FENCE();
#pragma unroll
          for (int k = 0; k < ((YP & 16) ? 1 : 8); k++) wgmma_n40_ss(a, qd + ((k >> 2) * SEGB + (k & 3) * 256 >> 4), qd + ((k >> 2) * SEGB + (k & 3) * 256 + 4096 >> 4), k > 0);
          const uint32_t ga = sb + A_G + (seg & 1) * 128 + (w & 1) * 64 + (lane >> 2) * 4;
          const float f0 = __uint_as_float(lds32(ga)), f1 = __uint_as_float(lds32(ga + 32));
          WG_COMMIT();
          WG_WAIT(0);
          CSTAMP(5);
          SSTAMP(seg, 1);
          if (w < 2) {
            const int lim = w * 16 + (lane >> 2) - 2 * (lane & 3);
            float m0 = -3.0e38f, m1 = -3.0e38f;
#pragma unroll
            for (int i = 0; i < 20; i++) {
              a[i] *= SM_SCALE * LOG2E;
              if (i < 16 && (i >> 2) * 8 + (i & 1) - (i & 2) * 4 > lim) a[i] = -1.0e9f * LOG2E;
              if (i & 2) m1 = fmaxf(m1, a[i]); else m0 = fmaxf(m0, a[i]);
            }
#pragma unroll
            for (int o = 1; o < 4; o <<= 1) { m0 = fmaxf(m0, __shfl_xor_sync(0xffffffffu, m0, o)); m1 = fmaxf(m1, __shfl_xor_sync(0xffffffffu, m1, o)); }
            float s0 = 0.f, s1 = 0.f;
#pragma unroll
            for (int i = 0; i < 20; i++) { a[i] = ex2(a[i] - (i & 2 ? m1 : m0)); if (i & 2) s1 += a[i]; else s0 += a[i]; }
#pragma unroll
            for (int o = 1; o < 4; o <<= 1) { s0 += __shfl_xor_sync(0xffffffffu, s0, o); s1 += __shfl_xor_sync(0xffffffffu, s1, o); }
            s0 = f0 * rcp(s0); s1 = f1 * rcp(s1);
            uint32_t p[10];
#pragma unroll
            for (int i = 0; i < 10; i++) p[i] = pack_bf16(a[2 * i] * (i & 1 ? s1 : s0), a[2 * i + 1] * (i & 1 ? s1 : s0));
            const uint32_t pa = sb + A_P + (2 * w + ((lane >> 3) & 1)) * 768 + (lane >> 4) * 128 + (lane & 7) * 16;
            stsm4t(pa, p[0], p[1], p[2], p[3]); stsm4t(pa + 256, p[4], p[5], p[6], p[7]); stsm4t(pa + 512, p[8], p[9], 0, 0);
            CSTAMP(6);
            fence_async();
            CSTAMP(7);
          }
        }
        CSTAMP(8);

        if (w == 3) mbar_wait(fulla + 16 * (seg & 1) + 8, (seg >> 1) & 1);
        bar_sync(5, 160);
        CSTAMP(10);
        SSTAMP(seg, 2);
        const uint64_t pd = make_desc(sb + A_P, 128, 768, 0), vd = make_desc(in + 2 * SEGB, 128, 512, 0), md = make_desc(in + 2 * SEGB + 8192, 0, 128, 0);
        WG_FENCE();
#pragma unroll
        for (int i = 0; i < 2; i++) {
          wgmma_n32_ss<0>(d[i], vd + i * 256, pd, 0);
          wgmma_n32_ss<0>(d[i], vd + i * 256 + 16, pd + 16, 1);
          wgmma_n32_ss<0>(d[i], md + i * 64, pd + 32, 1);
        }
        WG_COMMIT();
        WG_WAIT(0);
        CSTAMP(11);
        if (lane == 0) mbar_arrive(emptya + 8 * (seg & 1));
#pragma unroll
        for (int i = 0; i < 2; i++) {
          const uint32_t oa = sb + A_OST + i * 4096 + ((lane & 7) + ((lane >> 4) << 3)) * 128 + (((2 * w + ((lane >> 3) & 1)) ^ (lane & 7)) << 4);
          stsm4t(oa, pack_bf16(d[i][0], d[i][1]), pack_bf16(d[i][2], d[i][3]), pack_bf16(d[i][4], d[i][5]), pack_bf16(d[i][6], d[i][7]));
          stsm4t(oa + 2048, pack_bf16(d[i][8], d[i][9]), pack_bf16(d[i][10], d[i][11]), pack_bf16(d[i][12], d[i][13]), pack_bf16(d[i][14], d[i][15]));
        }
        CSTAMP(12);
        bar_sync(4, 160);
        SSTAMP(seg, 3);
      }
      CDUMP;
    }
  } else {
    asm volatile("setmaxnreg.inc.sync.aligned.u32 200;");
    {
      const int g = lane >> 2, t = lane & 3, r0 = (cta >> 1) * A_ROWS - 7 + w * 16;
      const uint32_t prev = (2 * t > g ? 0xffffu : 0u) | (2 * t + 1 > g ? 0xffff0000u : 0u);
      const int k0 = r0 + 2 * t - (2 * t > g ? 8 : 0), k1 = r0 + 2 * t + 1 - (2 * t + 1 > g ? 8 : 0);
      const uint32_t slot = sb + A_EXC + (wg * 4 + w) * 2304;
      float gl = 0.f, gh = 0.f;
      int st = 0, ph = 0;
#pragma unroll 1
      for (int p = -AWARM; p < ((XP & 256) ? 0 : 4); p++) {
        float big[96], sml[12];
        if (p == 3 && tid < 18) {
          const int kb = p3_ks(tid >= 9) * 9 + tid % 9;
          tma_prefetch(kb < 64 ? &tm.wob : &tm.woa, p3_mt(tid >= 9) * 64, (kb & 63) * 64);
        }
        __syncwarp();
#pragma unroll
        for (int i = 0; i < 96; i++) big[i] = 0.f;
#pragma unroll
        for (int i = 0; i < 12; i++) sml[i] = 0.f;
#pragma unroll 1
        for (int k = p < 0 ? 18 : 0; k < 18; k++) {
          mbar_wait(full1 + 8 * st, ph);
          const uint64_t da = make_desc(sb + st * A_STAGE + wg * 4096, 16, 512, 2);
          const uint64_t db = make_desc(sb + st * A_STAGE + 8192, 4096, 1024, 1), dc = make_desc(sb + A_W8 + st * 1536, 128, 512, 0);
          WG_FENCE();
#pragma unroll
          for (int j = 0; j < 2; j++) { wgmma_n192_ss_nt(big, da + j * 2, db + j * 128, 1); wgmma_n24_ss_nt(sml, da + j * 2, dc + j * 16, 1); }
          WG_COMMIT();
          WG_WAIT(1);
          if (k > 0 && lane == 0) mbar_arrive(empty1 + 8 * (st ? st - 1 : A_ST - 1));
          if (++st == A_ST) { st = 0; ph ^= 1; }
        }
        WG_WAIT(0);
        ASTAMP(16 + max(p, 0) + wg * 16);
        if (lane == 0 && p >= 0) mbar_arrive(empty1 + 8 * (st ? st - 1 : A_ST - 1));
        uint32_t f[3][9][2];
#pragma unroll
        for (int c = 0; c < 3; c++)
#pragma unroll
          for (int j = 0; j < 9; j++)
#pragma unroll
            for (int i = 0; i < 2; i++) {
              const float* a = j < 8 ? &big[(c * 8 + j) * 4 + 2 * i] : &sml[c * 4 + 2 * i];
              f[c][j][i] = c < 2 ? pack_bf16(a[0], a[1]) : trans8(pack_bf16(a[0], a[1]));
            }
        if (p == 0) {
          bar_sync(8, 288);
          gl = __ldcg(&g_gate[min(max(r0 + g, 0), S_LEN / 2 - 1) * 2 + wg]); gh = __ldcg(&g_gate[min(max(r0 + g + 8, 0), S_LEN / 2 - 1) * 2 + wg]);
        }
        asm volatile("cp.async.bulk.wait_group.read 0;" ::: "memory");
        __syncwarp();
#pragma unroll
        for (int j = 0; j < 8; j += 2) sts128(slot + j * 256 + lane * 16, f[1][j][1], f[2][j][1], f[1][j + 1][1], f[2][j + 1][1]);
        sts64(slot + 2048 + lane * 8, f[1][8][1], f[2][8][1]);
        bar_sync(1 + wg, 128);
        ASTAMP(24 + max(p, 0) + wg * 16);
        uint32_t pv[9][2];
#pragma unroll
        for (int j = 0; j < 9; j++) pv[j][0] = pv[j][1] = 0;
        if (w) {
#pragma unroll
          for (int j = 0; j < 8; j += 2) lds128(slot - 2304 + j * 256 + lane * 16, pv[j]);
          lds64(slot - 256 + lane * 8, pv[8][0], pv[8][1]);
        }
        float a[4][4], m[4][2];
#pragma unroll
        for (int h = 0; h < 4; h++) {
          const int j = 2 * h;
          const uint32_t qa[4] = {t >= h ? f[0][j][0] : 0, t >= h ? f[0][j][1] : 0, f[0][j + 1][0], f[0][j + 1][1]};
          const uint32_t qb0 = t <= h ? f[0][j + 2][0] : 0, qb1 = t <= h ? f[0][j + 2][1] : 0;
          float s0[4], s1[4], s2[4];
          mma16816z(s1, qa, f[1][j][0], f[1][j + 1][0]); mma16816z(s2, qa, f[1][j][1], f[1][j + 1][1]); mma16816z(s0, qa, pv[j][0], pv[j + 1][0]);
          mma1688(s1, qb0, qb1, f[1][j + 2][0]); mma1688(s2, qb0, qb1, f[1][j + 2][1]); mma1688(s0, qb0, qb1, pv[j + 2][0]);
          a[h][0] = 2 * t > g ? s0[0] : s1[0]; a[h][1] = 2 * t + 1 > g ? s0[1] : s1[1]; a[h][2] = 2 * t > g ? s1[2] : s2[2]; a[h][3] = 2 * t + 1 > g ? s1[3] : s2[3];
        }
#pragma unroll
        for (int h = 0; h < 4; h++) {
#pragma unroll
          for (int i = 0; i < 4; i++) a[h][i] = (i & 1 ? k1 : k0) + (i & 2) * 4 >= 0 ? a[h][i] * (0.23570226039551584f * LOG2E) : -1.0e9f * LOG2E;
          m[h][0] = fmaxf(a[h][0], a[h][1]); m[h][1] = fmaxf(a[h][2], a[h][3]);
        }
#pragma unroll
        for (int x = 1; x < 4; x <<= 1)
#pragma unroll
          for (int i = 0; i < 8; i++) m[i >> 1][i & 1] = fmaxf(m[i >> 1][i & 1], __shfl_xor_sync(0xffffffffu, m[i >> 1][i & 1], x));
#pragma unroll
        for (int h = 0; h < 4; h++) {
#pragma unroll
          for (int i = 0; i < 4; i++) a[h][i] = ex2(a[h][i] - m[h][i >> 1]);
          m[h][0] = a[h][0] + a[h][1]; m[h][1] = a[h][2] + a[h][3];
        }
#pragma unroll
        for (int x = 1; x < 4; x <<= 1)
#pragma unroll
          for (int i = 0; i < 8; i++) m[i >> 1][i & 1] += __shfl_xor_sync(0xffffffffu, m[i >> 1][i & 1], x);
        uint32_t o[9][2];
#pragma unroll
        for (int h = 0; h < 4; h++) {
          const int j = 2 * h;
          const float z0 = gl * rcp(m[h][0]), z1 = gh * rcp(m[h][1]);
          const uint32_t pl = pack_bf16(a[h][0] * z0, a[h][1] * z0), pu = pack_bf16(a[h][2] * z1, a[h][3] * z1);
          const uint32_t pa[4] = {pl & prev, 0, pl & ~prev, pu & prev};
          float d[3][4];
#pragma unroll
          for (int i = 0; i < 3; i++) mma16816z(d[i], pa, pv[j + i][1], f[2][j + i][0]);
#pragma unroll
          for (int i = 0; i < 3; i++) mma1688(d[i], 0, pu & ~prev, f[2][j + i][1]);
#pragma unroll
          for (int i = 0; i < 3; i++) {
            const uint32_t d0 = pack_bf16(d[i][0], d[i][1]), d1 = pack_bf16(d[i][2], d[i][3]);
            o[j + i][0] = i == 0 && h > 0 && t < h ? o[j][0] : d0;
            o[j + i][1] = i == 0 && h > 0 && t < h ? o[j][1] : d1;
          }
        }
        ASTAMP(28 + max(p, 0) + wg * 16);
        bar_sync(1 + wg, 128);
        const uint32_t oa = slot + (lane & 15) * 144 + (lane >> 4) * 16;
#pragma unroll
        for (int j = 0; j < 8; j += 2) stsm4(oa + j * 16, o[j][0], o[j][1], o[j + 1][0], o[j + 1][1]);
        asm volatile("stmatrix.sync.aligned.m8n8.x2.shared.b16 [%0], {%1,%2};" :: "r"(oa + 128), "r"(o[8][0]), "r"(o[8][1]) : "memory");
        fence_async();
        __syncwarp();
        if (QM & 64) quiet_wait(pace);
        if (lane < 16 && w * 16 + lane >= 7 && r0 + lane < S_LEN / 2 && p >= 0)
          asm volatile("cp.async.bulk.global.shared::cta.bulk_group [%0], [%1], 144;"
                       :: "l"(g_Ocat + (size_t)((r0 + lane) * 2 + wg) * KCAT + 4096 + (cta & 1) * (DM / 2) + p * 72), "r"(slot + lane * 144) : "memory");
        asm volatile("cp.async.bulk.commit_group;" ::: "memory");
        ASTAMP(20 + max(p, 0) + wg * 16);
      }
      if (XP & 256) bar_sync(8, 288);
      asm volatile("cp.async.bulk.wait_group 0;" ::: "memory");
    }
    ASTAMP(3);
    bar_arrive(6, 288);
    uint32_t wa[36][4];
    mbar_wait(fullw, 0);
    const uint32_t la = sb + ((lane & 7) + ((lane >> 4) << 3)) * 128 + (((2 * w + ((lane >> 3) & 1)) ^ (lane & 7)) << 4);
#pragma unroll
    for (int k = 0; k < 32; k++) ldsm4t(wa[k], la + wg * 65536 + k * 2048);
    mbar_wait(fullw + 8, 0);
#pragma unroll
    for (int k = 32; k < 36; k++) ldsm4t(wa[k], la + wg * 8192 + 65536 + k * 2048);
    fence_async();
    if (XP & 2048) bar_sync(6, 288); else bar_arrive(6, 288);
    ASTAMP(4);
    const int ks = p3_ks(wg), mt = p3_mt(wg);
    uint32_t v[16];
    auto fetch = [&](int seg) { ldg8x64<1024>(v, g_part + (((seg & 7) * 9 + mt) * 4 + (ks & 3)) * 1024 + (tid & 127)); };
    auto finish = [&](int seg) {
      const uint32_t tagv = (~seg >> 3) & 1;
      int n = 0;
#pragma unroll 1
      while (stale<8, 2>(v, tagv) && ++n < SPIN_LIMIT) {
        if (seg < NSEG - 2) __nanosleep(100);
        fetch(seg);
      }
      float own[4] = {bf_lo(v[0]), bf_hi(v[0]), bf_lo(v[1]), bf_hi(v[1])};
#pragma unroll
      for (int j = 1; j < 8; j++) { own[0] += bf_lo(v[2 * j]); own[1] += bf_hi(v[2 * j]); own[2] += bf_lo(v[2 * j + 1]); own[3] += bf_hi(v[2 * j + 1]); }
      uint32_t p0 = pack_bf16(own[0], own[1]), p1 = pack_bf16(own[2], own[3]);
      asm volatile("movmatrix.sync.aligned.m8n8.trans.b16 %0, %0;" : "+r"(p0));
      asm volatile("movmatrix.sync.aligned.m8n8.trans.b16 %0, %0;" : "+r"(p1));
      uint32_t* o = (uint32_t*)(out + (size_t)(seg * 32 + (ks & 3) * 8 + (lane >> 2)) * DM + mt * 64 + w * 16) + (lane & 3);
      o[0] = p0; o[4] = p1;
      SSTAMP(seg, 7);
    };
    float acc[16];
#pragma unroll
    for (int i = 0; i < 16; i++) acc[i] = 0.f;
    int pend = -1, sl = wide ? 0 : wg, ph = 0;
    if (PING && wg) bar_arrive(1, 256);
    CDECL;
    auto run = [&](auto extra) {
#pragma unroll 1
    for (int seg = 0; seg < ((XP & 2048) ? 0 : NSEG); seg++) {
      CSTAMP(0);
      const bool fin = pend >= 0 && seg - pend >= FLAG;
      if (FPOS == 0 && fin) fetch(pend);
      mbar_wait(full3 + 8 * sl, ph);
      if (FPOS == 1 && fin) fetch(pend);
      CSTAMP(1);
      if (wg) SSTAMP(seg, 5);
      if (PING) bar_sync(1 + wg, 256);
      CSTAMP(7);
      const uint64_t db = make_desc(sb + sl * XT, 16, 1024, 1);
      WG_FENCE();
#pragma unroll
      for (int k = 0; k < ((XP & 1024) ? 1 : 36); k++) wgmma_n32_rs(acc, wa[k][0], wa[k][1], wa[k][2], wa[k][3], db + (k >> 2) * 256 + (k & 3) * 2, k);
      if (decltype(extra)::value) {
        const uint64_t da = make_desc(xw + wg * 8192, 8192, 1024, 1), de = make_desc(xt + sl * 4096, 16, 1024, 1);
#pragma unroll
        for (int j = 0; j < 4; j++) wgmma_n32_ss_tn(acc, da + j * 128, de + j * 2);
      }
      WG_COMMIT();
      if (PING) bar_arrive(2 - wg, 256);
      CSTAMP(2);
      if (FPOS == 2 && fin) fetch(pend);
      CSTAMP(3);
      WG_WAIT(0);
      CSTAMP(4);
      if (wg) SSTAMP(seg, 6);
      if (lane == 0) mbar_arrive(empty3 + 8 * sl);
      sl += wide ? 1 : 2;
      if (sl >= (wide ? 3 : 4)) { sl -= wide ? 3 : 4; ph ^= 1; }
      uint2* dst = g_part + (((seg & 7) * 9 + mt) * 32 + ks) * 128 + (tid & 127);
      uint32_t q[8];
#pragma unroll
      for (int j = 0; j < 8; j++) q[j] = j & 1 ? pack_bf16(acc[2 * j], acc[2 * j + 1]) : (pack_bf16(acc[2 * j], acc[2 * j + 1]) & ~1u) | ((~seg >> 3) & 1);
      if (QM & 32) tick_wait(pace, seg + (QM >> 4 & 1) + 2);
      if (!(YP & 1) || q[0] == 0x12345678)
      asm volatile("st.relaxed.gpu.global.v2.b32 [%0], {%1,%2};\nst.relaxed.gpu.global.v2.b32 [%0 + 8192], {%3,%4};\n"
                   "st.relaxed.gpu.global.v2.b32 [%0 + 16384], {%5,%6};\nst.relaxed.gpu.global.v2.b32 [%0 + 24576], {%7,%8};"
                   :: "l"(dst), "r"(q[0]), "r"(q[1]), "r"(q[2]), "r"(q[3]), "r"(q[4]), "r"(q[5]), "r"(q[6]), "r"(q[7]) : "memory");
      CSTAMP(5);
      if (fin) { finish(pend); pend = -1; }
      CSTAMP(6);
      if ((seg & 1) == ks >> 2 && !(YP & 1)) pend = seg;
      if (wg && (seg & 7) == 6) ASTAMP(5 + (seg >> 3));
    }
    };
    if (ks == 7) run(BoolC<true>()); else run(BoolC<false>());
    if (PING && !wg) bar_sync(1, 256);
    if (pend >= 0) { fetch(pend); finish(pend); }
    CDUMP;
    ASTAMP(13);
    bar_sync(6, 288);
  }
}

typedef CUresult (*EncodeFn)(CUtensorMap*, CUtensorMapDataType, cuuint32_t, void*, const cuuint64_t*, const cuuint64_t*,
                             const cuuint32_t*, const cuuint32_t*, CUtensorMapInterleave, CUtensorMapSwizzle,
                             CUtensorMapL2promotion, CUtensorMapFloatOOBfill);
#define PROMO 2
static void make_map(EncodeFn enc, CUtensorMap* m, const void* p, int rows, int cols, int box_rows) {
  cuuint64_t dims[2] = {(cuuint64_t)cols, (cuuint64_t)rows};
  cuuint64_t strides[1] = {(cuuint64_t)cols * 2};
  cuuint32_t box[2] = {64, (cuuint32_t)box_rows};
  cuuint32_t es[2] = {1, 1};
  enc(m, CU_TENSOR_MAP_DATA_TYPE_BFLOAT16, 2, (void*)p, dims, strides, box, es, CU_TENSOR_MAP_INTERLEAVE_NONE,
      CU_TENSOR_MAP_SWIZZLE_128B, (CUtensorMapL2promotion)PROMO, CU_TENSOR_MAP_FLOAT_OOB_FILL_NONE);
}

constexpr int g_poll = POLL_NS;
extern "C" void kernel_launch(void* const* d_in, const int* in_sizes, int n_in, void* d_out, int out_size) {
  const bf16* x = (const bf16*)d_in[0];
  const bf16* wqkvA = (const bf16*)d_in[1];
  const bf16* woA = (const bf16*)d_in[2];
  const bf16* mem0 = (const bf16*)d_in[4];
  const bf16* Wq = (const bf16*)d_in[5];
  const bf16* Wk = (const bf16*)d_in[6];
  const bf16* Wv = (const bf16*)d_in[7];
  const bf16* Wo = (const bf16*)d_in[8];
  const bf16* gate_w = (const bf16*)d_in[10];
  static EncodeFn enc = nullptr;
  static void *pO = nullptr, *pR = nullptr;
  if (!enc) {
    cudaDriverEntryPointQueryResult qr;
    cudaGetDriverEntryPoint("cuTensorMapEncodeTiled", (void**)&enc, cudaEnableDefault, &qr);
    cudaGetSymbolAddress(&pO, g_Ocat);
    cudaGetSymbolAddress(&pR, g_red_raw);
    cudaFuncSetAttribute(rec_kernel, cudaFuncAttributeMaxDynamicSharedMemorySize, SM_TOTAL);
    cudaFuncSetAttribute(aux_kernel, cudaFuncAttributeMaxDynamicSharedMemorySize, A_TOTAL);
  }
  RMaps rm;
  rm.poll = g_poll;
  rm.w[0] = (const unsigned char*)Wk; rm.w[1] = (const unsigned char*)Wq; rm.w[2] = (const unsigned char*)Wv; rm.w[3] = (const unsigned char*)Wo;
  rm.red = (unsigned char*)(((uintptr_t)pR + 262143) & ~(uintptr_t)262143);
  {
    cuuint64_t dims[3] = {64, S_LEN, 9}, strides[2] = {DM * 2, 128};
    cuuint32_t box[3] = {64, 32, 9}, es[3] = {1, 1, 1};
    enc(&rm.x, CU_TENSOR_MAP_DATA_TYPE_BFLOAT16, 3, (void*)x, dims, strides, box, es, CU_TENSOR_MAP_INTERLEAVE_NONE,
        CU_TENSOR_MAP_SWIZZLE_128B, CU_TENSOR_MAP_L2_PROMOTION_L2_128B, CU_TENSOR_MAP_FLOAT_OOB_FILL_NONE);
  }
  make_map(enc, &rm.wq, Wq, DM, 4096, 192);
  make_map(enc, &rm.wk, Wk, DM, 4096, 192);
  make_map(enc, &rm.wv, Wv, DM, 4096, 192);
  make_map(enc, &rm.wo, Wo, 4096, DM, 128);
  AMaps am;
  am.red = rm.red; am.poll = rm.poll;
  {
    cuuint64_t dims[3] = {DM, S_LEN / 2, 2}, strides[2] = {DM * 4, DM * 2};
    cuuint32_t box[3] = {32, 64, 2}, es[3] = {1, 1, 1};
    enc(&am.x, CU_TENSOR_MAP_DATA_TYPE_BFLOAT16, 3, (void*)x, dims, strides, box, es, CU_TENSOR_MAP_INTERLEAVE_NONE,
        CU_TENSOR_MAP_SWIZZLE_64B, CU_TENSOR_MAP_L2_PROMOTION_L2_128B, CU_TENSOR_MAP_FLOAT_OOB_FILL_NONE);
    cuuint64_t wdims[3] = {DM, DM, 3}, wstrides[2] = {DM * 6, DM * 2};
    cuuint32_t wbox[3] = {64, 32, 3}, wbox8[3] = {8, 32, 3};
    enc(&am.wa, CU_TENSOR_MAP_DATA_TYPE_BFLOAT16, 3, (void*)wqkvA, wdims, wstrides, wbox, es, CU_TENSOR_MAP_INTERLEAVE_NONE,
        CU_TENSOR_MAP_SWIZZLE_128B, CU_TENSOR_MAP_L2_PROMOTION_L2_128B, CU_TENSOR_MAP_FLOAT_OOB_FILL_NONE);
    enc(&am.wa8, CU_TENSOR_MAP_DATA_TYPE_BFLOAT16, 3, (void*)wqkvA, wdims, wstrides, wbox8, es, CU_TENSOR_MAP_INTERLEAVE_NONE,
        CU_TENSOR_MAP_SWIZZLE_NONE, CU_TENSOR_MAP_L2_PROMOTION_NONE, CU_TENSOR_MAP_FLOAT_OOB_FILL_NONE);
  }
  {
    cuuint64_t dims[3] = {64, S_LEN, KCAT / 64}, strides[2] = {KCAT * 2, 128};
    cuuint32_t box[3] = {64, 32, 9}, es[3] = {1, 1, 1};
    make_map(enc, &am.o, pO, S_LEN, KCAT, 32);
    enc(&am.o3, CU_TENSOR_MAP_DATA_TYPE_BFLOAT16, 3, pO, dims, strides, box, es, CU_TENSOR_MAP_INTERLEAVE_NONE,
        CU_TENSOR_MAP_SWIZZLE_128B, CU_TENSOR_MAP_L2_PROMOTION_L2_128B, CU_TENSOR_MAP_FLOAT_OOB_FILL_NONE);
  }
  make_map(enc, &am.wob, Wo, 4096, DM, 64);
  make_map(enc, &am.woa, woA, DM, DM, 64);

  rec_kernel<<<96, 384, SM_TOTAL, cudaStreamPerThread>>>(rm, x, mem0);
  cudaLaunchConfig_t cfg = {};
  cfg.gridDim = dim3(NAUX); cfg.blockDim = dim3(512); cfg.dynamicSmemBytes = A_TOTAL; cfg.stream = cudaStreamPerThread;
  cudaLaunchAttribute at[1];
  at[0].id = cudaLaunchAttributeProgrammaticStreamSerialization; at[0].val.programmaticStreamSerializationAllowed = 1;
  cfg.attrs = at; cfg.numAttrs = 1;
  if (XP & 16) cfg.numAttrs = 0;
  if (!(XP & 64)) cudaLaunchKernelEx(&cfg, aux_kernel, am, x, gate_w, (bf16*)d_out);
}
```

```cpp
#include <cuda_runtime.h>
#include <cuda_bf16.h>
#include <cuda_fp16.h>
#include <cuda.h>
#include <stdint.h>

typedef __nv_bfloat16 bf16;

constexpr int S_LEN = 2048, DM = 576, NH = 32, DH = 128, NSEG = 64, KCAT = 4096 + 576;
#define RED_LINE(i) (((i) >> 2) * 4096 + ((i) & 1) * 256 + ((i) & 2) * 512)
#define RED_SLOT(s) (((s) & 1) * 128 + ((s) & 2) * 256)

#define POLL_NS 832
#define NII 18
#define W3PRE 4
#define W3MID 4
#define GF 0
#define B5POS 0
#define NUP 4
#define UPF 1
#define B3Q 9
#define B3F 0
#define GATE 7
#define NTL 2
#define B7R 1
#define EXPOS 0
#define VW2 1
#define CLR 1
#define RFW 0
#define NIC 0
#define LEAD 0
#define FIN16 1
#define VXG 0
#define RING 63
#define EXB 0
#define EXD 0
#define EXB2 8192
#define HDLY 0
#define F10 1
#define NPROBE 2
#define NPROBE2 5
#define WPOS 2
#define WARM 0
#define YP 0
#define EXV 2
#define NOB 0
#define QM 60
#define N5 224
#define KP(i) (((i) >> 1) + 4 * ((i) & 1))
#define SPIN_LIMIT (1 << 14)
#define XP 0

__device__ __align__(1024) bf16 g_Ocat[S_LEN * KCAT];
__device__ __align__(1024) unsigned char g_red_raw[2 * 262144];
constexpr int HINT_OFF = 2048;
__device__ __align__(16) float g_gate[S_LEN];
__device__ __align__(128) uint4 g_stats[96 * 2];
__device__ unsigned g_epoch;
__device__ unsigned g_epoch2;
__device__ unsigned g_oflag[NH * 32];
__device__ unsigned g_abar[3 * 32];
__device__ unsigned g_sflag[96 * 8];
__device__ __align__(1024) unsigned char g_seg[NSEG * 96 * 8192];
__device__ __align__(1024) unsigned char g_km[NSEG * NH * 4096];
__device__ __align__(1024) uint2 g_part[8 * 9 * 4 * 8 * 128];
__device__ int g_err;
#define SSTAMP(seg, idx)
#define QSTAMP(idx)
#define PROF(idx)
#define PROFP(idx)
#define STAMP(idx)
#define ASTAMP(idx)
#define WSTAMP(idx)

#define CSTAMP(idx)
#define CDECL
#define CDUMP
#define DI __device__ __forceinline__
DI uint32_t smem_u32(const void* p) { return (uint32_t)__cvta_generic_to_shared(p); }
DI uint32_t clock32() { uint32_t c; asm volatile("mov.u32 %0, %%clock;" : "=r"(c) :: "memory"); return c; }
DI uint32_t gtime() { uint32_t c; asm volatile("mov.u32 %0, %%globaltimer_lo;" : "=r"(c) :: "memory"); return c; }
DI uint32_t ldg_relaxed32(const void* p) { uint32_t v; asm volatile("ld.relaxed.gpu.global.b32 %0, [%1];" : "=r"(v) : "l"(p) : "memory"); return v; }
DI uint32_t ldg_acquire32(const void* p) { uint32_t v; asm volatile("ld.acquire.gpu.global.b32 %0, [%1];" : "=r"(v) : "l"(p) : "memory"); return v; }
DI void stg_relaxed32(void* p, uint32_t v) { asm volatile("st.relaxed.gpu.global.b32 [%0], %1;" :: "l"(p), "r"(v) : "memory"); }
DI int head_id() { int c; asm volatile("mov.u32 %0, %%clusterid.x;" : "=r"(c)); return c; }
DI uint32_t mapa(uint32_t a, uint32_t r) { uint32_t o; asm("mapa.shared::cluster.u32 %0, %1, %2;" : "=r"(o) : "r"(a), "r"(r)); return o; }
DI void cluster_arrive() { asm volatile("barrier.cluster.arrive.relaxed.aligned;" ::: "memory"); }
DI void cluster_wait() { asm volatile("barrier.cluster.wait.aligned;" ::: "memory"); }
DI void cluster_sync() { asm volatile("barrier.cluster.arrive.release.aligned;\nbarrier.cluster.wait.acquire.aligned;" ::: "memory"); }
DI void mbar_init(uint32_t b, uint32_t c) { asm volatile("mbarrier.init.shared::cta.b64 [%0], %1;" :: "r"(b), "r"(c) : "memory"); }
DI void mbar_expect(uint32_t b, uint32_t tx) { asm volatile("mbarrier.arrive.expect_tx.shared::cta.b64 _, [%0], %1;" :: "r"(b), "r"(tx) : "memory"); }
DI void mbar_arrive(uint32_t b) { asm volatile("mbarrier.arrive.shared::cta.b64 _, [%0];" :: "r"(b) : "memory"); }
DI void mbar_wait(uint32_t b, uint32_t par) {
  asm volatile("{\n.reg .pred p;\n.reg .u32 n, q;\nmov.u32 n, 0;\n"
               "WL: add.u32 n, n, 1;\nshr.u32 q, n, 12;\nxor.b32 q, q, %1;\n"
               "mbarrier.try_wait.parity.shared::cta.b64 p, [%0], q;\n@!p bra.uni WL;\n}"
               :: "r"(b), "r"(par) : "memory");
}
DI void wait_until(uint32_t t) {
  const uint32_t now = gtime();
  t = min(t, now + 8192);
  asm volatile("{\n.reg .pred p;\n.reg .u32 c;\nTL: mov.u32 c, %%globaltimer_lo;\nsetp.lt.u32 p, c, %0;\n@p bra.uni TL;\n}" :: "r"(t) : "memory");
}
#define PIN(v) v = __shfl_xor_sync(0xffffffffu, v, 0)
#define SCHED_FENCE(k) asm volatile("{\n.reg .pred p;\nsetp.eq.u32 p, %0, %1;\n@p exit;\n}" :: "r"(fence_reg), "r"(k) : "memory")
#define MEM_ORDER(k) asm volatile("{\n.reg .pred p;\nsetp.eq.u32 p, %0, %1;\n@p st.shared.u32 [%0], %0;\n}" :: "r"(fence_reg), "r"(k + 64) : "memory")
DI void bar_sync(int id, int n) { asm volatile("bar.sync %0, %1;" :: "r"(id), "r"(n) : "memory"); }
DI void bar_arrive(int id, int n) { asm volatile("bar.arrive %0, %1;" :: "r"(id), "r"(n) : "memory"); }
DI void fence_async() { asm volatile("fence.proxy.async.shared::cta;" ::: "memory"); }
DI void st_async4(uint32_t a, uint32_t x, uint32_t y, uint32_t z, uint32_t w, uint32_t mb) {
  asm volatile("st.async.weak.shared::cluster.mbarrier::complete_tx::bytes.v4.b32 [%0], {%1,%2,%3,%4}, [%5];"
               :: "r"(a), "r"(x), "r"(y), "r"(z), "r"(w), "r"(mb) : "memory");
}
DI void st_async2(uint32_t a, uint32_t x, uint32_t y, uint32_t mb) {
  asm volatile("st.async.weak.shared::cluster.mbarrier::complete_tx::bytes.v2.b32 [%0], {%1,%2}, [%3];"
               :: "r"(a), "r"(x), "r"(y), "r"(mb) : "memory");
}
DI void sts32(uint32_t a, uint32_t x) { asm volatile("st.shared.b32 [%0], %1;" :: "r"(a), "r"(x) : "memory"); }
DI void sts64(uint32_t a, uint32_t x, uint32_t y) { asm volatile("st.shared.v2.b32 [%0], {%1,%2};" :: "r"(a), "r"(x), "r"(y) : "memory"); }
DI void sts128(uint32_t a, uint32_t x, uint32_t y, uint32_t z, uint32_t w) {
  asm volatile("st.shared.v4.b32 [%0], {%1,%2,%3,%4};" :: "r"(a), "r"(x), "r"(y), "r"(z), "r"(w) : "memory");
}
DI uint32_t lds32(uint32_t a) { uint32_t x; asm volatile("ld.shared.b32 %0, [%1];" : "=r"(x) : "r"(a) : "memory"); return x; }
DI void lds64(uint32_t a, uint32_t& x, uint32_t& y) { asm volatile("ld.shared.v2.b32 {%0,%1}, [%2];" : "=r"(x), "=r"(y) : "r"(a) : "memory"); }
DI void lds128(uint32_t a, uint32_t* r) {
  asm volatile("ld.shared.v4.b32 {%0,%1,%2,%3}, [%4];" : "=r"(r[0]), "=r"(r[1]), "=r"(r[2]), "=r"(r[3]) : "r"(a) : "memory");
}
DI void lds128f(uint32_t a, float* r) {
  asm volatile("ld.shared.v4.f32 {%0,%1,%2,%3}, [%4];" : "=f"(r[0]), "=f"(r[1]), "=f"(r[2]), "=f"(r[3]) : "r"(a) : "memory");
}
DI void lds64f(uint32_t a, float* r) { asm volatile("ld.shared.v2.f32 {%0,%1}, [%2];" : "=f"(r[0]), "=f"(r[1]) : "r"(a) : "memory"); }
DI void ldsm4t(uint32_t* r, uint32_t a) {
  asm volatile("ldmatrix.sync.aligned.m8n8.x4.trans.shared.b16 {%0,%1,%2,%3}, [%4];"
               : "=r"(r[0]), "=r"(r[1]), "=r"(r[2]), "=r"(r[3]) : "r"(a) : "memory");
}
DI void ldsm4t_in(uint32_t* r, uint32_t a, uint32_t t) {
  asm volatile("{\n.reg .pred p;\nsetp.ne.u32 p, %5, 0;\n@p ldmatrix.sync.aligned.m8n8.x4.trans.shared.b16 {%0,%1,%2,%3}, [%4];\n}"
               : "+r"(r[0]), "+r"(r[1]), "+r"(r[2]), "+r"(r[3]) : "r"(a), "r"(t) : "memory");
}
DI void lds128_in(uint32_t* r, uint32_t a, uint32_t t) {
  asm volatile("{\n.reg .pred p;\nsetp.ne.u32 p, %5, 0;\n@p ld.shared.v4.b32 {%0,%1,%2,%3}, [%4];\n}"
               : "+r"(r[0]), "+r"(r[1]), "+r"(r[2]), "+r"(r[3]) : "r"(a), "r"(t) : "memory");
}
DI void ldsm2t_in(uint32_t* r, uint32_t a, uint32_t t) {
  asm volatile("{\n.reg .pred p;\nsetp.ne.u32 p, %3, 0;\n@p ldmatrix.sync.aligned.m8n8.x2.trans.shared.b16 {%0,%1}, [%2];\n}" : "+r"(r[0]), "+r"(r[1]) : "r"(a), "r"(t) : "memory");
}
DI void reserve2(uint32_t* r) { asm volatile("{\n.reg .u64 t;\nmov.u64 t, %%clock64;\nmov.b64 {%0, %1}, t;\n}" : "=r"(r[0]), "=r"(r[1])); }
DI void scale_sum(float& x, float& y, float s, uint32_t t) {
  asm volatile("{\n.reg .pred p;\nsetp.ne.u32 p, %2, 0;\n@p mul.f32 %0, %0, %1;\n}" : "+f"(y) : "f"(s), "r"(t));
  asm volatile("{\n.reg .pred p;\nsetp.ne.u32 p, %3, 1;\n@p fma.rn.f32 %0, %0, %1, %2;\n}" : "+f"(x) : "f"(s), "f"(y), "r"(t));
}
DI void ldsm4(uint32_t* r, uint32_t a) {
  asm volatile("ldmatrix.sync.aligned.m8n8.x4.shared.b16 {%0,%1,%2,%3}, [%4];"
               : "=r"(r[0]), "=r"(r[1]), "=r"(r[2]), "=r"(r[3]) : "r"(a) : "memory");
}
DI void st_async1(uint32_t a, uint32_t x, uint32_t mb) {
  asm volatile("st.async.weak.shared::cluster.mbarrier::complete_tx::bytes.b32 [%0], %1, [%2];" :: "r"(a), "r"(x), "r"(mb) : "memory");
}
DI void stsm4(uint32_t a, uint32_t x, uint32_t y, uint32_t z, uint32_t w) {
  asm volatile("stmatrix.sync.aligned.m8n8.x4.shared.b16 [%0], {%1,%2,%3,%4};" :: "r"(a), "r"(x), "r"(y), "r"(z), "r"(w) : "memory");
}
DI void stsm4t(uint32_t a, uint32_t x, uint32_t y, uint32_t z, uint32_t w) {
  asm volatile("stmatrix.sync.aligned.m8n8.x4.trans.shared.b16 [%0], {%1,%2,%3,%4};" :: "r"(a), "r"(x), "r"(y), "r"(z), "r"(w) : "memory");
}
DI uint32_t pack_bf16(float lo, float hi) { uint32_t r; asm("cvt.rn.bf16x2.f32 %0, %1, %2;" : "=r"(r) : "f"(hi), "f"(lo)); return r; }
DI uint32_t pack_f16(float lo, float hi) { uint32_t r; asm("cvt.rn.f16x2.f32 %0, %1, %2;" : "=r"(r) : "f"(hi), "f"(lo)); return r; }
DI float ex2(float x) { float y; asm("ex2.approx.ftz.f32 %0, %1;" : "=f"(y) : "f"(x)); return y; }
DI float rcp(float x) { float y; asm("rcp.approx.ftz.f32 %0, %1;" : "=f"(y) : "f"(x)); return y; }
DI float bf_lo(uint32_t x) { return __uint_as_float(x << 16); }
DI float bf_hi(uint32_t x) { return __uint_as_float(x & 0xffff0000u); }
DI void mma16816(float* d, const uint32_t* a, uint32_t b0, uint32_t b1) {
  asm volatile("mma.sync.aligned.m16n8k16.row.col.f32.bf16.bf16.f32 {%0,%1,%2,%3}, {%4,%5,%6,%7}, {%8,%9}, {%0,%1,%2,%3};"
               : "+f"(d[0]), "+f"(d[1]), "+f"(d[2]), "+f"(d[3]) : "r"(a[0]), "r"(a[1]), "r"(a[2]), "r"(a[3]), "r"(b0), "r"(b1));
}
DI void mma16816z(float* d, const uint32_t* a, uint32_t b0, uint32_t b1) {
  asm volatile("mma.sync.aligned.m16n8k16.row.col.f32.bf16.bf16.f32 {%0,%1,%2,%3}, {%4,%5,%6,%7}, {%8,%9}, {%10,%10,%10,%10};"
               : "=f"(d[0]), "=f"(d[1]), "=f"(d[2]), "=f"(d[3]) : "r"(a[0]), "r"(a[1]), "r"(a[2]), "r"(a[3]), "r"(b0), "r"(b1), "f"(0.f));
}
DI void mma1688z(float* d, uint32_t a0, uint32_t a1, uint32_t b0) {
  asm volatile("mma.sync.aligned.m16n8k8.row.col.f32.bf16.bf16.f32 {%0,%1,%2,%3}, {%4,%5}, {%6}, {%7,%7,%7,%7};"
               : "=f"(d[0]), "=f"(d[1]), "=f"(d[2]), "=f"(d[3]) : "r"(a0), "r"(a1), "r"(b0), "f"(0.f));
}
DI void mma1688(float* d, uint32_t a0, uint32_t a1, uint32_t b0) {
  asm volatile("mma.sync.aligned.m16n8k8.row.col.f32.bf16.bf16.f32 {%0,%1,%2,%3}, {%4,%5}, {%6}, {%0,%1,%2,%3};"
               : "+f"(d[0]), "+f"(d[1]), "+f"(d[2]), "+f"(d[3]) : "r"(a0), "r"(a1), "r"(b0));
}
DI void ldsm2t(uint32_t* r, uint32_t a) {
  asm volatile("ldmatrix.sync.aligned.m8n8.x2.trans.shared.b16 {%0,%1}, [%2];" : "=r"(r[0]), "=r"(r[1]) : "r"(a) : "memory");
}
DI uint32_t add_bf16(uint32_t a, uint32_t b) { uint32_t r; asm("add.rn.bf16x2 %0, %1, %2;" : "=r"(r) : "r"(a), "r"(b)); return r; }
DI uint32_t mul_bf16(uint32_t a, uint32_t b) { uint32_t r; asm("mul.rn.bf16x2 %0, %1, %2;" : "=r"(r) : "r"(a), "r"(b)); return r; }
DI uint64_t make_desc(uint32_t addr, uint32_t lbo, uint32_t sbo, uint32_t swz) {
  return (uint64_t)((addr & 0x3FFFF) >> 4) | ((uint64_t)(lbo >> 4) << 16) | ((uint64_t)(sbo >> 4) << 32) | ((uint64_t)swz << 62);
}
#define WG_FENCE() asm volatile("wgmma.fence.sync.aligned;" ::: "memory")
#define WG_COMMIT() asm volatile("wgmma.commit_group.sync.aligned;" ::: "memory")
#define WG_WAIT(n) asm volatile("wgmma.wait_group.sync.aligned %0;" :: "n"(n) : "memory")
#define ACC8(d, o) "+f"(d[o]), "+f"(d[o + 1]), "+f"(d[o + 2]), "+f"(d[o + 3]), "+f"(d[o + 4]), "+f"(d[o + 5]), "+f"(d[o + 6]), "+f"(d[o + 7])
DI void wgmma_n32_rs(float* d, uint32_t a0, uint32_t a1, uint32_t a2, uint32_t a3, uint64_t db, int acc) {
  asm volatile("{\n.reg .pred p;\nsetp.ne.b32 p, %21, 0;\n"
               "wgmma.mma_async.sync.aligned.m64n32k16.f32.bf16.bf16 {%0,%1,%2,%3,%4,%5,%6,%7,%8,%9,%10,%11,%12,%13,%14,%15}, "
               "{%16,%17,%18,%19}, %20, p, 1, 1, 0;\n}\n"
               : ACC8(d, 0), ACC8(d, 8) : "r"(a0), "r"(a1), "r"(a2), "r"(a3), "l"(db), "r"(acc));
}
template <int TA>
DI void wgmma_n32_ss(float* d, uint64_t da, uint64_t db, int acc) {
  asm volatile("{\n.reg .pred p;\nsetp.ne.b32 p, %18, 0;\n"
               "wgmma.mma_async.sync.aligned.m64n32k16.f32.bf16.bf16 {%0,%1,%2,%3,%4,%5,%6,%7,%8,%9,%10,%11,%12,%13,%14,%15}, "
               "%16, %17, p, 1, 1, %19, 1;\n}\n"
               : ACC8(d, 0), ACC8(d, 8) : "l"(da), "l"(db), "r"(acc), "n"(TA));
}
DI void tma_load(uint32_t dst, const CUtensorMap* m, int c0, int c1, uint32_t mb) {
  asm volatile("cp.async.bulk.tensor.2d.shared::cluster.global.mbarrier::complete_tx::bytes [%0], [%1, {%3, %4}], [%2];"
               :: "r"(dst), "l"(m), "r"(mb), "r"(c0), "r"(c1) : "memory");
}
DI void tma_load3(uint32_t dst, const CUtensorMap* m, int row, uint32_t mb) {
  asm volatile("cp.async.bulk.tensor.3d.shared::cluster.global.mbarrier::complete_tx::bytes [%0], [%1, {%3, %4, %3}], [%2];"
               :: "r"(dst), "l"(m), "r"(mb), "r"(0), "r"(row) : "memory");
}
DI bool elect_one() {
  uint32_t p;
  asm volatile("{\n.reg .pred p;\nelect.sync _|p, 0xffffffff;\nselp.u32 %0, 1, 0, p;\n}" : "=r"(p));
  return p;
}
DI void bulk_s2s(uint32_t dst, uint32_t src, uint32_t bytes, uint32_t mb) {
  asm volatile("cp.async.bulk.shared::cluster.shared::cta.mbarrier::complete_tx::bytes [%0], [%1], %2, [%3];"
               :: "r"(dst), "r"(src), "r"(bytes), "r"(mb) : "memory");
}
DI void bulk_load(uint32_t dst, const void* src, uint32_t bytes, uint32_t mb) {
  asm volatile("cp.async.bulk.shared::cluster.global.mbarrier::complete_tx::bytes [%0], [%1], %2, [%3];" :: "r"(dst), "l"(src), "r"(bytes), "r"(mb) : "memory");
}
DI void tma_prefetch(const CUtensorMap* m, int c0, int c1) {
  asm volatile("cp.async.bulk.prefetch.tensor.2d.L2.global.tile [%0, {%1, %2}];" :: "l"(m), "r"(c0), "r"(c1) : "memory");
}
DI void tma_store(const CUtensorMap* m, uint32_t src, int c0, int c1) {
  asm volatile("cp.async.bulk.tensor.2d.global.shared::cta.bulk_group [%0, {%2, %3}], [%1];" :: "l"(m), "r"(src), "r"(c0), "r"(c1) : "memory");
}
DI uint4 ldg_relaxed(const void* p) {
  uint4 v;
  asm volatile("ld.relaxed.gpu.global.v4.b32 {%0,%1,%2,%3}, [%4];" : "=r"(v.x), "=r"(v.y), "=r"(v.z), "=r"(v.w) : "l"(p) : "memory");
  return v;
}
DI void stg_relaxed(void* p, uint32_t x, uint32_t y, uint32_t z, uint32_t w) {
  asm volatile("st.relaxed.gpu.global.v4.b32 [%0], {%1,%2,%3,%4};" :: "l"(p), "r"(x), "r"(y), "r"(z), "r"(w) : "memory");
}
DI void red_f16x8(void* p, uint32_t x, uint32_t y, uint32_t z, uint32_t w) {
  asm volatile("red.relaxed.gpu.global.add.noftz.v4.f16x2 [%0], {%1,%2,%3,%4};" :: "l"(p), "r"(x), "r"(y), "r"(z), "r"(w) : "memory");
}
DI void sq_acc(uint32_t& a, uint32_t x) { asm("fma.rn.bf16x2 %0, %1, %1, %0;" : "+r"(a) : "r"(x)); }
DI __half2 amax4(__half2 h, const uint32_t* v) {
  h = __hmax2_nan(__hmax2_nan(h, __habs2(*(const __half2*)&v[0])), __habs2(*(const __half2*)&v[1]));
  return __hmax2_nan(__hmax2_nan(h, __habs2(*(const __half2*)&v[2])), __habs2(*(const __half2*)&v[3]));
}
DI uint32_t wexp(__half2 h) { const uint32_t u = *(const uint32_t*)&h; return __reduce_max_sync(0xffffffffu, max((u >> 16) & 0x7fffu, u & 0x7fffu)) >> 7; }
DI float max10(const float* a) {
  return fmaxf(fmaxf(fmaxf(fmaxf(a[0], a[1]), fmaxf(a[2], a[3])), fmaxf(fmaxf(a[4], a[5]), fmaxf(a[6], a[7]))), fmaxf(a[8], a[9]));
}
DI float quad_max(float m) {
  return fmaxf(fmaxf(m, __shfl_xor_sync(0xffffffffu, m, 1)), fmaxf(__shfl_xor_sync(0xffffffffu, m, 2), __shfl_xor_sync(0xffffffffu, m, 3)));
}
DI float warp_sum(float v) {
#pragma unroll
  for (int o = 16; o; o >>= 1) v += __shfl_xor_sync(0xffffffffu, v, o);
  return v;
}

constexpr int SM_WO3 = 0;
constexpr int SM_X = 16384;
constexpr int XT = 36864;
constexpr int SM_EXP = 126976;
constexpr int SEGB = 10240;
constexpr int SM_BLK = SM_EXP + 8192;
constexpr int SM_VC = SM_BLK + 4 * SEGB;
constexpr int SM_PART = SM_VC + 16384;
constexpr int SM_QM = SM_PART + 4096;
constexpr int SM_E = SM_QM + 1024;
constexpr int SM_VM = SM_E + 1536;
constexpr int SM_OB = SM_VM + 2048;
constexpr int SM_FB = SM_OB + 2048;
constexpr int SM_STAGE = SM_X + XT;
constexpr int SM_M0 = SM_STAGE + 3 * 49152;
constexpr int SM_MISC = 210944;
constexpr int SM_WOST = 212992;
constexpr int SM_MEM = SM_WOST;
constexpr int SM_MAX = SM_MEM + 11264;
#define MEM_BLK(q) ((q) / 3 * 4096 + (q) % 3 * 1024)
constexpr int SM_TOTAL = 229376;
constexpr int MB_W = SM_MISC;
constexpr int MB_WO = SM_MISC + 24;
constexpr int MB_WO3 = SM_MISC + 32;
constexpr int MB_X = SM_MISC + 40;
constexpr int MB_S = SM_MISC + 64;
constexpr int MB_F = SM_MISC + 72;
constexpr int MB_VX = SM_MISC + 80;
constexpr int SC_FPAR = SM_MISC + 136;
constexpr int SC_DEAD = SM_MISC + 96;
constexpr int SC_UNSC = SM_MISC + 112;
constexpr int SC_EXPW = SM_MISC + 132;
constexpr int SC_ONES = SM_MISC + 144;
constexpr int SC_SS = SM_MISC + 160;
constexpr int SC_LAT = SM_MISC + 224;
constexpr int SC_EPO = SM_MISC + 240;
constexpr int MB_XS = SM_MISC + 248;
constexpr int SC_XMAX = SM_MISC + 256;
constexpr int SC_PROF = 229376;

constexpr float SM_SCALE = 0.08838834764831845f;
constexpr float LOG2E = 1.4426950408889634f;
constexpr float E_LIM = 20.f;

template <bool B> struct BoolC { static constexpr bool value = B; };
struct RMaps { CUtensorMap x, wq, wk, wv, wo; unsigned char* red; uint32_t poll; const unsigned char* w[4]; };

DI uint32_t latest_hint(uint32_t h, uint32_t d, int s) {
  const uint32_t x = (((h | 0xc0c0c0c0u) - ((d >> 5) & 63) * 0x01010101u) & 0x3f3f3f3fu) | ((h ^ (((s >> 2) + 1) & 3) * 0x40404040u) & 0xc0c0c0c0u);
  const uint32_t y = __vmaxu2(x & 0x00ff00ffu, (x >> 8) & 0x00ff00ffu);
  return __reduce_max_sync(0xffffffffu, max(y & 0xffffu, y >> 16));
}
DI uint32_t near_half(uint32_t sb) {
  uint32_t a, b; lds64(sb + SC_LAT, a, b);
  return a > b;
}

template <int RT, int K0, int K1, bool D32 = false>
DI void xproj(float* acc, const uint32_t (&wa)[2][18][4], uint64_t xd) {
  if (XP & 1) return;
  WG_FENCE();
#pragma unroll
  for (int k = K0; k < ((XP & 128) ? K0 + 1 : K1); k++)
  {
    uint64_t d = xd + (uint64_t)(((k >> 1) * 4096 + (k & 1) * 32) >> 4);
    if (D32) asm("mov.b64 %0, {%1, %2};" : "=l"(d) : "r"((uint32_t)xd + (((k >> 1) * 4096 + (k & 1) * 32) >> 4)), "r"((uint32_t)(xd >> 32)));
    wgmma_n32_rs(acc, wa[RT][k][0], wa[RT][k][1], wa[RT][k][2], wa[RT][k][3], d, k != 0);
  }
  WG_COMMIT();
}

DI void seg_store(int seg, uint32_t sb) {
  fence_async();
  asm volatile("cp.async.bulk.global.shared::cta.bulk_group [%0], [%1], 8192;"
               :: "l"(g_seg + ((size_t)(seg & RING) * 96 + blockIdx.x) * 8192), "r"(sb + SM_BLK + (seg & 3) * SEGB) : "memory");
  asm volatile("cp.async.bulk.commit_group;" ::: "memory");
}
DI void seg_publish(int seg, uint32_t sb) {
  const uint32_t v = lds32(sb + SC_EPO) + seg;
  asm volatile("cp.async.bulk.wait_group 0;" ::: "memory");
  stg_relaxed32(&g_sflag[blockIdx.x * 8], v);
}

DI void proj_role(const uint32_t sb, const RMaps& tm, const uint32_t rank, const int wg, const int w, const int lane) {
  const bool qk = rank < 2;
  uint32_t wa[2][18][4];
  {
    const int rr = (lane & 7) + ((lane >> 4) << 3);
    const uint32_t col = ((2 * w + ((lane >> 3) & 1)) ^ (lane & 7)) << 4;
    float ss;
#pragma unroll 1
    for (int pass = WARM ? wg + w == 0 : 1; pass < 2; pass++) {
      ss = 0.f;
      if (pass) bar_sync(3, 256);
#pragma unroll
      for (int c = 0; c < 3; c++) {
        QSTAMP(2 + 2 * c);
        if (pass) mbar_wait(sb + MB_W + 8 * c, 0);
        QSTAMP(3 + 2 * c);
#pragma unroll
        for (int rt = 0; rt < 2; rt++)
#pragma unroll
          for (int k = 0; k < 6; k++)
            ldsm4t(wa[rt][c * 6 + k], sb + SM_STAGE + c * 49152 + (rt ^ wg) * 24576 + (64 * (k >> 1) + 32 * wg + 16 * (k & 1) + rr) * 128 + col);
        if (c < 2) {
          fence_async();
          if (pass) {
            bar_sync(3, 256);
            QSTAMP(17 + c);
            if (threadIdx.x == 0) {
              if (c == 0) tma_load3(sb + SM_X + XT, &tm.x, 32, sb + MB_X + 8);
              else tma_load(sb + SM_X + 2 * XT, &tm.wo, rank * 192, (blockIdx.x / 3) * DH, sb + MB_WO);
            }
            __syncwarp();
          }
        }
        uint32_t q[4] = {0, 0, 0, 0};
#pragma unroll
        for (int rt = 0; rt < 2; rt++)
#pragma unroll
          for (int k = 0; k < 6; k++)
#pragma unroll
            for (int i = 0; i < 4; i++) sq_acc(q[i], wa[rt][c * 6 + k][i]);
#pragma unroll
        for (int i = 0; i < 4; i++) ss += bf_lo(q[i]) + bf_hi(q[i]);
      }
      ss = warp_sum(ss);
    }
    fence_async();
    cluster_arrive();
    if (lane == 0) sts32(sb + SC_SS + 4 * (wg * 4 + w), qk ? 0 : __float_as_uint(ss));
    bar_arrive(11, 384);
  }
  STAMP(1);
  QSTAMP(8);
  mbar_wait(sb + MB_X, 0);
  STAMP(2);
  QSTAMP(9);

  uint32_t t16 = sb + (w * 32 + lane) * 16;
  uint32_t mem_a = sb + SM_MEM + wg * 512 + lane * 16;
  uint32_t fin_a = sb + (lane & 7) * 16 + SM_BLK + (qk ? (wg ^ 1) * 4096 + w * 256 + (lane & 8) * 16 + (lane & 16) * 64
                                              : wg * 4096 + w * 1024 + (lane & 8) * 64 + (lane & 16) * 8);
  PIN(t16); PIN(mem_a); PIN(fin_a);
  const uint32_t fence_reg = mem_a;
  const uint32_t fin2 = qk ? 2048 : 256;
  float acc[16];
  const uint64_t xd0 = make_desc(sb + SM_X + wg * 64, 16, 1024, 1);
  auto do_export = [&](auto retire, uint32_t always) {
    WG_WAIT(0);
    uint32_t p[2];
#pragma unroll
    for (int i = 0; i < 2; i++) {
      p[i] = pack_bf16(acc[8 * i], acc[8 * i + 1]);
      sts128(t16 + SM_EXP + wg * 4096 + i * 2048, p[i], pack_bf16(acc[8 * i + 2], acc[8 * i + 3]),
             pack_bf16(acc[8 * i + 4], acc[8 * i + 5]), pack_bf16(acc[8 * i + 6], acc[8 * i + 7]));
    }
    if (decltype(retire)::value)
      asm volatile("{\n.reg .pred p, q;\nsetp.ne.u32 p, %2, 0;\nsetp.ne.u32 q, %2, 1;\n@p ld.shared.b32 %0, [%3];\n@q ld.shared.b32 %1, [%3 + 4];\n"
                   "setp.ne.u32 p, %0, %1;\n@p exit;\n}" : "+r"(p[0]), "+r"(p[1]) : "r"(always), "r"(sb + SC_DEAD) : "memory");
  };
  uint32_t o[8];
  auto import = [&]() { lds128(t16 + SM_EXP + (wg ^ 1) * 4096, o); lds128(t16 + SM_EXP + (wg ^ 1) * 4096 + 2048, o + 4); };
  auto finish = [&](int seg) {
    const uint32_t a = fin_a + (seg & 3) * SEGB;
    WG_WAIT(0);
#pragma unroll
    for (int i = 0; i < 8; i++) o[i] = FIN16 ? add_bf16(pack_bf16(acc[2 * i], acc[2 * i + 1]), o[i]) : pack_bf16(acc[2 * i] + bf_lo(o[i]), acc[2 * i + 1] + bf_hi(o[i]));
    stsm4(a, o[0], o[1], o[2], o[3]);
    stsm4(a + fin2, o[4], o[5], o[6], o[7]);
  };
  auto send_v = [&](int seg, int dst) {
    fence_async();
    if (seg < NSEG - 1 && !(XP & 2) && elect_one())
      bulk_s2s(mapa(sb + SM_VC + (seg & 1) * 8192, dst), sb + SM_BLK + (seg & 3) * SEGB, 8192, mapa(sb + MB_VX + (seg & 1) * 8, dst));
    __syncwarp();
  };
  auto wait_v = [&](int seg) {
    if (seg < NSEG - 1 && !(XP & 2)) {
      mbar_wait(sb + MB_VX + (seg & 1) * 8, (seg >> 1) & 1);
      if (elect_one()) mbar_expect(sb + MB_VX + (seg & 1) * 8, 8192);
      __syncwarp();
    }
  };
  auto export_seg = [&](int seg) { if (!(XP & (4 | 8192)) && elect_one()) seg_store(seg, sb); __syncwarp(); };
  auto publish = [&](int seg) { if (!(XP & (4 | 16384)) && elect_one()) seg_publish(seg, sb); __syncwarp(); };
  bar_sync(3, 256);
  xproj<1, 0, 18>(acc, wa, xd0);
  do_export(BoolC<false>(), 0);
  SCHED_FENCE(11);
  xproj<0, 0, 18>(acc, wa, xd0);
  bar_sync(3, 256);
  QSTAMP(10);
  cluster_wait();
  QSTAMP(11);
  mbar_wait(sb + MB_X + 8, 0);
  QSTAMP(12);
  import();
  finish(0);
  SCHED_FENCE(12);
  bar_sync(3, 256);
  uint64_t dA = xd0 + (XT >> 4);
  xproj<1, 0, 18>(acc, wa, dA);
  if (!qk && wg == 0 && w < 2) send_v(0, w);
  if (!(EXV & 1) && wg == 0 && w == 3) export_seg(0);
  QSTAMP(13);
  if (qk && wg == 0 && w == 0) wait_v(0);
  QSTAMP(14);
  bar_arrive(13, 384);
  if (!qk) {
    do_export(BoolC<false>(), 0);
    SCHED_FENCE(15);
    xproj<0, 0, 18>(acc, wa, dA);
    if (threadIdx.x == 0 && !(XP & 8)) { mbar_expect(sb + MB_X, XT); tma_load3(sb + SM_X, &tm.x, 96, sb + MB_X); }
    bar_sync(3, 256);
    mbar_wait(sb + MB_X + 16, 0);
    import();
    finish(1);
    SCHED_FENCE(16);
    bar_sync(3, 256);
    dA += XT >> 4;
    xproj<1, 0, 18>(acc, wa, dA);
    if (!(EXV & 2) && wg == 0 && w < VW2) send_v(1, w);
  }
  QSTAMP(15);
  WG_WAIT(0);
  bar_sync(0, 384);
  if (!(EXV & 1) && wg == 0 && w == 3) publish(0);
  QSTAMP(16);
  const int ro = __shfl_sync(0xffffffffu, near_half(sb) ^ wg, 0);
  STAMP(5);
  const uint32_t always = __shfl_sync(0xffffffffu, lds32(sb + SC_DEAD + 12), 0);
  const int ah = qk ? 1 : 2;
  int b2 = qk ? 2 : 0;
  int s = 0;
  uint32_t hint_lo = (uint32_t)(uint64_t)tm.red + HINT_OFF + blockIdx.x + (lane & 1) * 4096 + (lane >> 1) * 16384;
  PIN(hint_lo);
  auto post_hint = [&]() {
    asm volatile("{\n.reg .pred p;\n.reg .b64 a;\n.reg .u32 t;\nsetp.lt.u32 p, %0, %1;\nmov.b64 a, {%2, %3};\nmov.u32 t, %%globaltimer_lo;\n"
                 "bfe.u32 t, t, 5, 6;\nor.b32 t, t, %4;\n@p st.relaxed.gpu.global.u8 [a], t;\n}"
                 :: "r"(t16), "r"(sb + 160), "r"(hint_lo + RED_SLOT(s)), "r"((uint32_t)((uint64_t)tm.red >> 32)), "r"(((s >> 2) + 1) << 6) : "memory");
  };
  auto memproj = [&](auto second, int id, uint32_t dep, float u0, float u1, float* r) {
    constexpr bool R1 = decltype(second)::value;
    uint32_t b[NUP][4], b0[4];
    if (R1) asm volatile("{\n.reg .pred p;\nsetp.eq.u32 p, %0, %1;\n@p exit;\n}" :: "r"(dep), "r"(id) : "memory");
    bar_sync(R1 ? 2 : 1, 256);
    PROF(0);
    ldsm4t(b0, mem_a);
#pragma unroll
    for (int q = 0; q < NUP; q++) {
      if (R1 && q == 2) {
        bar_sync(11, 256);
        SCHED_FENCE(id + 1);
      }
      ldsm4t(b[q], mem_a + MEM_BLK(q + 1));
    }
    mma16816z(&acc[0], wa[0][0], b0[0], b0[1]);
    mma16816z(&acc[4], wa[1][0], b0[0], b0[1]);
    mma16816z(&acc[8], wa[0][1], b0[2], b0[3]);
    mma16816z(&acc[12], wa[1][1], b0[2], b0[3]);
#pragma unroll
    for (int q = 1; q < 9; q++) {
      uint32_t* const c = b[(q - 1) % NUP];
      mma16816(&acc[0], wa[0][2 * q], c[0], c[1]);
      mma16816(&acc[4], wa[1][2 * q], c[0], c[1]);
      mma16816(&acc[8], wa[0][2 * q + 1], c[2], c[3]);
      mma16816(&acc[12], wa[1][2 * q + 1], c[2], c[3]);
      if (R1 && q + NUP == B3Q) bar_sync(3, 256);
      if (q + NUP < 9) ldsm4t_in(c, mem_a + MEM_BLK(q + NUP), always);
      else if (R1 && q + NUP < 11) lds128_in(c, t16 + SM_PART + (10 - q - NUP) * 2048, always);
      else if (!R1 && GATE && q == GATE) { bar_arrive(11, 256); lds128_in(c, sb + SC_DEAD, always); u0 = u1 = __uint_as_float(c[3]); }
    }
#pragma unroll
    for (int i = 0; i < 8; i++) {
      const float u = i < 4 ? u0 : u1;
      r[i] = R1 ? fmaf(acc[8 + i], u, (acc[i] + __uint_as_float(b[(8 + i / 4) % NUP][i & 3])) * u) : (GATE ? fmaf(acc[i], u, acc[8 + i]) : acc[i] + acc[8 + i]);
    }
  };
  if (ro == 0) {
#pragma unroll 1
    while (true) {
      do_export(BoolC<true>(), always);
      PROFP(3);
      if (s == 8) STAMP(6);
      float r[8];
      memproj(BoolC<false>(), 30, 0, 0.f, 0.f, r);
      sts128(t16 + SM_PART, __float_as_uint(r[0]), __float_as_uint(r[1]), __float_as_uint(r[2]), __float_as_uint(r[3]));
      sts128(t16 + SM_PART + 2048, __float_as_uint(r[4]), __float_as_uint(r[5]), __float_as_uint(r[6]), __float_as_uint(r[7]));
      bar_arrive(3, 256);
      PROF(1);
      bar_sync(9, 256);
      if (s == NSEG - 1) break;
      post_hint();
      if (!(EXV & 1) && w == 3 && s) publish(s);
      if (w == 1) {
        uint32_t m[8];
        lds128(t16 + SM_MAX - 512, m); lds128(t16 + SM_MAX, m + 4);
        const int em = (wexp(amax4(amax4(*(const __half2*)&m[0], m), m + 4)) >> 3) + (int)(lds32(sb + SC_UNSC + (s & 1) * 8) >> 23) - 15;
        const int ex = max(s ? em : 0, (int)lds32(sb + SC_XMAX + 4 * s)) - 127 + (int)lds32(sb + SC_EXPW);
        sts32(sb + SC_UNSC + (~s & 1) * 8, (127 + min(max(ex, -120), 120)) << 23);
        __syncwarp();
        if (elect_one()) mbar_arrive(sb + MB_S);
      }
      SCHED_FENCE(9);
      bar_sync(5, qk ? N5 : 256);
      PROF(2);
      import();
      xproj<0, 0, NII>(acc, wa, dA);
      if (NII < 18) {
        if (qk) bar_sync(7, 384);
        xproj<0, NII, 18>(acc, wa, dA);
        if (!qk) bar_sync(7, 384);
      } else {
        if (F10) WG_WAIT(0);
        bar_sync(10, 256);
        if (F10) SCHED_FENCE(17);
      }
      dA += (int64_t)(b2 ? XT >> 4 : -(XT >> 3));
      finish(s + ah);
      if (((EXV & 1) || w != 3) && ((EXV & 2) || qk || w >= VW2)) bar_arrive(13, 384);
      PROF(6);
      SCHED_FENCE(14);
      if (NOB & 2) bar_arrive(14, 256);
      bar_sync(12, 256);
      PROF(7);
      xproj<1, 0, 18, true>(acc, wa, dA);
      if (!(NOB & 2)) bar_arrive(14, 256);
      b2 = b2 == 2 ? 0 : b2 + 1;
      s++;
      if ((!(EXV & 1) && w == 3) || (!(EXV & 2) && !qk && w < VW2)) {
        bar_sync(13, 384);
        if (!(EXV & 1) && w == 3) export_seg(s); else send_v(s + 1, w);
      }
      PROFP(8);
    }
    if (!qk) bar_arrive(5, 256);
    if (!(EXV & 1) && w == 3) publish(NSEG - 1);
  } else {
    uint32_t km[4];
    auto send_km = [&]() {
      if (XP & (4 | 4096)) return;
      const uint32_t t = (km[0] & ~1u) | lds32(sb + SC_EPO + 4), u = (s * NH + head_id()) * 4096;
      if (qk)
        asm volatile("{\n.reg .u32 o;\n.reg .u64 a;\nshr.u32 o, %0, 1;\nadd.u32 o, o, %1;\nmad.wide.u32 a, o, 1, %2;\nst.relaxed.gpu.global.v2.b32 [a], {%3,%4};\n}"
                     :: "r"(t16), "r"(u + rank * 1024 - (sb >> 1)), "l"(g_km), "r"(t), "r"(km[1]) : "memory");
      else
        asm volatile("{\n.reg .u32 o;\n.reg .u64 a;\nadd.u32 o, %0, %1;\nmad.wide.u32 a, o, 1, %2;\nst.relaxed.gpu.global.v4.b32 [a], {%3,%4,%5,%6};\n}"
                     :: "r"(t16), "r"(u + 2048 - sb), "l"(g_km), "r"(t), "r"(km[1]), "r"(km[2]), "r"(km[3]) : "memory");
    };
#pragma unroll 1
    while (true) {
      do_export(BoolC<true>(), always);
      if ((EXV & 1) && w == 1) export_seg(s);
      if ((EXV & 2) && !qk && w == 2) send_v(s + 1, 0);
      PROFP(3);
      if (s == 8) STAMP(6);
      const uint32_t tl = ((t16 >> 8) ^ wg) & 1, am = (t16 & ~256u) - w * 256;
      const float un = __uint_as_float(lds32(sb + SC_UNSC + (s & 1) * 8));
      float r[8];
      if (qk) {
        uint32_t a0 = am + (tl ? SM_QM : SM_BLK + 8192 + (s & 3) * SEGB);
        float u0 = wg ? un * (SM_SCALE * LOG2E) : un, u1 = wg ? un : un * (SM_SCALE * LOG2E);
        PIN(a0); PIN(u0); PIN(u1);
        memproj(BoolC<true>(), 32, a0, u0, u1, r);
        const uint32_t p0 = pack_bf16(r[0], r[1]), p1 = pack_bf16(r[2], r[3]), p2 = pack_bf16(r[4], r[5]), p3 = pack_bf16(r[6], r[7]);
        stsm4(a0, p0, p1, p2, p3);
        bar_arrive(4, 256);
        km[0] = wg ? p2 : p0; km[1] = wg ? p3 : p1;
      } else {
        const uint32_t d0 = s < NSEG - 1 ? 0 : 2, d1 = s < NSEG - 1 ? 1 : 2;
        uint32_t r0 = mapa(t16 + SM_VM, d0), r1 = mapa(t16 + SM_VM, d1);
        PIN(r0); PIN(r1);
        memproj(BoolC<true>(), 34, r0 | r1, un, un, r);
        const uint32_t p0 = pack_bf16(r[0], r[1]), p1 = pack_bf16(r[2], r[3]), p2 = pack_bf16(r[4], r[5]), p3 = pack_bf16(r[6], r[7]);
        const uint32_t v0 = wg ? p2 : p0, v1 = wg ? p3 : p1, v2 = wg ? p0 : p2, v3 = wg ? p1 : p3;
        st_async4(r0, v0, v1, v2, v3, mapa(sb + MB_S, d0));
        st_async4(r1, v0, v1, v2, v3, mapa(sb + MB_S, d1));
        bar_arrive(5, 256);
        sts128(t16 + SM_VM, v0, v1, v2, v3);
        __syncwarp();
        if (elect_one()) mbar_arrive(sb + MB_S);
        km[0] = v0; km[1] = v1; km[2] = v2; km[3] = v3;
      }
      if (s == NSEG - 1) break;
      PROF(1);
      auto rearm = [&]() { mbar_wait(sb + MB_S, s & 1); if (elect_one()) mbar_expect(sb + MB_S, qk ? 640 + 2048 : 1280); __syncwarp(); };
      if (w == 1) {
        if ((t16 & 384) == 0) stg_relaxed(tm.red + (RED_SLOT(s + 2) + RED_LINE(blockIdx.x)) + (t16 & 112), 0, 0, 0, 0);
        if (EXV & 1) publish(s);
      } else if (w == 0) {
        const int tn = s + ah + 1;
        if (RFW) mbar_wait(sb + MB_S, s & 1);
        if (tn + 1 < NSEG && !(XP & 8) && elect_one()) {
          const int b0 = b2 == 2 ? 0 : b2 + 1;
          mbar_expect(sb + MB_X + 8 * b0, XT);
          tma_load3(sb + SM_X + b0 * XT, &tm.x, (tn + 1) * 32, sb + MB_X + 8 * b0);
        }
        if (tn < NSEG && (!(XP & 8) || tn < 3)) mbar_wait(sb + MB_X + 8 * b2, (tn / 3) & 1);
      } else if (w == 2) {
        if (!qk) { if (VW2 < 1) send_v(s + 1, 0); if (VW2 < 2) send_v(s + 1, 1); }
      } else if (qk || !NIC) {
        rearm();
      }
      __syncwarp();
      send_km();
      import();
      PROF(4);
      SCHED_FENCE(10);
      if (NIC) {
        if (qk) bar_sync(7, NII < 18 ? 384 : 256);
        xproj<0, 0, NIC>(acc, wa, dA);
        if (!qk) { if (w == 3) rearm(); bar_sync(7, NII < 18 ? 384 : 256); }
      } else {
        bar_sync(7, NII < 18 ? 384 : 256);
      }
      if (NOB & 1) bar_arrive(12, 256);
      xproj<0, NIC, 18>(acc, wa, dA);
      if (!(NOB & 1)) bar_arrive(12, 256);
      dA += (int64_t)(b2 ? XT >> 4 : -(XT >> 3));
      finish(s + ah);
      if (qk && w == 0) wait_v(s + 1);
      bar_arrive(13, 384);
      PROF(6);
      SCHED_FENCE(13);
      bar_sync(14, 256);
      PROF(7);
      xproj<1, 0, 18>(acc, wa, dA);
      b2 = b2 == 2 ? 0 : b2 + 1;
      s++;
      PROFP(8);
    }
    send_km();
    if ((EXV & 1) && w == 1) publish(NSEG - 1);
    PIN(t16);
    if (t16 - sb < 128) stg_relaxed(tm.red + (RED_SLOT(NSEG + 1) + RED_LINE(head_id() * 3 + rank)) + (t16 & 112), 0, 0, 0, 0);
  }
  bar_arrive(0, 384);
  STAMP(3);
  cluster_sync();
  STAMP(4);
}

DI void attn_role(const uint32_t sb, unsigned char* smem_raw, const RMaps& tm, const uint32_t RANK, const bf16* __restrict__ x, const bf16* __restrict__ mem0,
                  const int w, const int lane) {
  const int t2 = w * 32 + lane;
  uint32_t wo[8][4], w1[8][4];
  const uint32_t wo_lane = sb + ((lane & 7) + ((lane >> 4) << 3)) * 128 + (((w + 4 * ((lane >> 3) & 1)) ^ (lane & 7)) << 4);
  unsigned char* const g_red = tm.red;
  {
    const uint32_t tag = *(volatile unsigned*)&g_epoch + 1;
    QSTAMP(0);
    bar_sync(0, 160);
    QSTAMP(1);
    cluster_arrive();
    __half2 hx = __float2half2_rn(0.f);
    if (blockIdx.x < NSEG) {
      mbar_wait(sb + MB_XS, 0);
#pragma unroll
      for (int i = 0; i < 18; i++) { uint32_t v[4]; lds128(sb + SM_X + t2 * 16 + i * 2048, v); hx = amax4(hx, v); }
      fence_async();
      bar_sync(6, 128);
      if (t2 == 0) tma_load3(sb + SM_X, &tm.x, 0, sb + MB_X);
      __syncwarp();
    }
    if (t2 == 0) { sts64(sb + SC_EPO, (tag - 1) * NSEG + 1, tag & 1); sts32(sb + SC_UNSC, __float_as_uint(1.f)); sts128(sb + SC_DEAD, 0, 0, 0, 0x3f800000u); sts64(sb + SC_FPAR, 0, 0); sts128(sb + SC_ONES, 0x3f803f80u, 0x3f803f80u, 0x3f803f80u, 0x3f803f80u); }
    WSTAMP(27);
    uint32_t q[8] = {0, 0, 0, 0, 0, 0, 0, 0};
    QSTAMP(2);
    mbar_wait(sb + MB_WO3, 0);
    QSTAMP(3);
    uint32_t mv[5][4];
#pragma unroll
    for (int i = 0; i < 5; i++) {
      ldsm4(mv[i], sb + SM_M0 + (lane & 7) * (DM * 2) + min(w + 4 * i, 17) * 64 + (lane >> 3) * 16);
      if (blockIdx.x == 0) hx = amax4(hx, mv[i]);
    }
    sts32(sb + SC_SS + 4 * (12 + w), wexp(hx));
#pragma unroll
    for (int k = 0; k < 8; k++) {
      ldsm4t(wo[k], wo_lane + SM_WO3 + k * 2048); ldsm4t(w1[k], wo_lane + SM_WOST + k * 2048);
#pragma unroll
      for (int i = 0; i < 4; i++) { sq_acc(q[i], wo[k][i]); sq_acc(q[i], w1[k][i]); }
    }
    bar_sync(6, 128);
#pragma unroll
    for (int k = 0; k < 8; k++) sts128(sb + SM_WO3 + t2 * 16 + k * 2048, wo[k][0], wo[k][1], wo[k][2], wo[k][3]);
#pragma unroll
    for (int i = 0; i < 5; i++) {
      const int c = (w + 4 * i) * 32;
      if (c < DM) stsm4t(sb + SM_MEM + (c + c / 192 * 64 + lane) * 16, mv[i][0], mv[i][1], mv[i][2], mv[i][3]);
    }
    bar_arrive(1, 256); bar_arrive(2, 256); bar_arrive(9, 256);
    QSTAMP(4);
    mbar_wait(sb + MB_WO, 0);
    QSTAMP(5);
#pragma unroll
    for (int k = 0; k < 8; k++) ldsm4t(wo[k], wo_lane + SM_X + 2 * XT + k * 2048);
    fence_async();
    bar_sync(6, 128);
    if (t2 == 32) tma_load3(sb + SM_X + 2 * XT, &tm.x, 64, sb + MB_X + 16);
    __syncwarp();
#pragma unroll
    for (int k = 0; k < 8; k++)
#pragma unroll
      for (int i = 0; i < 4; i++) sq_acc(q[4 + i], wo[k][i]);
    float ss = 0.f;
#pragma unroll
    for (int i = 0; i < 8; i++) ss += bf_lo(q[i]) + bf_hi(q[i]);
    ss = warp_sum(ss);
    if (lane == 0) sts32(sb + SC_SS + 4 * (8 + w), __float_as_uint(ss));
    QSTAMP(6);
    bar_sync(11, 384);
    QSTAMP(7);
    if (t2 == 0) {
      float a[16];
#pragma unroll
      for (int i = 0; i < 4; i++) lds128f(sb + SC_SS + 16 * i, &a[4 * i]);
      stg_relaxed(&g_stats[blockIdx.x * 2], __float_as_uint(((a[0] + a[1]) + (a[2] + a[3])) + ((a[4] + a[5]) + (a[6] + a[7]))),
                  __float_as_uint((a[8] + a[9]) + (a[10] + a[11])),
                  max(max(__float_as_uint(a[12]), __float_as_uint(a[13])), max(__float_as_uint(a[14]), __float_as_uint(a[15]))), tag);
    }
    __syncwarp();
    WSTAMP(24);
    QSTAMP(8);
    cluster_wait();
    QSTAMP(9);
    if (w == 0) {
      uint4 v[3];
      int n = 0;
      while (true) {
#pragma unroll
        for (int i = 0; i < 3; i++) v[i] = ldg_relaxed(&g_stats[(i * 32 + lane) * 2]);
        if (__all_sync(0xffffffffu, v[0].w == tag && v[1].w == tag && v[2].w == tag) || ++n > SPIN_LIMIT) break;
        __nanosleep(100);
      }
      WSTAMP(25);
      QSTAMP(10);
      const float sv = warp_sum(__uint_as_float(v[0].x) + __uint_as_float(v[1].x) + __uint_as_float(v[2].x));
      const float so = warp_sum(__uint_as_float(v[0].y) + __uint_as_float(v[1].y) + __uint_as_float(v[2].y));
      const int expW = ((int)(__float_as_uint(sv) >> 23) + (int)(__float_as_uint(so) >> 23) - 254 + 2 + 10 + 1) >> 1;
      sts32(sb + SC_XMAX + 4 * lane, v[0].z); sts32(sb + SC_XMAX + 128 + 4 * lane, v[1].z);
      sts32(sb + SC_EXPW, expW + 1 - 15);
      if (blockIdx.x == 0 && lane == 0) *(volatile unsigned*)&g_epoch = tag;
      sts32(sb + SC_FPAR + 4, 1);
    } else if (w < 3) {
      const uint32_t u = blockIdx.x >> 4;
      unsigned char* const z = g_red + 98304 + (blockIdx.x & 15) * 128 + (u & 1) * 2048 + (u & 6) * 4096 + (((u >> 1) ^ w) & 1) * 4096 + lane * 4;
      stg_relaxed32(z, 0);
      uint32_t best = 0xffffffffu;
#pragma unroll 1
      for (int i = 0; i < 64; i++) {
        uint32_t last, dt;
        asm volatile("{\n.reg .pred p;\n.reg .u32 c, v;\nld.volatile.shared.u32 %0, [%3];\nmov.u32 c, %%clock;\n"
                     "atom.relaxed.gpu.global.exch.b32 v, [%2], 0;\nsetp.eq.u32 p, v, 0;\nmov.u32 %1, 0;\n@p mov.u32 %1, %%clock;\nsub.u32 %1, %1, c;\n}"
                     : "=r"(last), "=r"(dt) : "l"(z), "r"(sb + SC_FPAR + 4) : "memory");
        best = min(best, dt);
        if ((last && i >= NPROBE - 1) || i >= NPROBE2 - 1) break;
      }
      sts32(sb + SC_LAT + (w - 1) * 4, best);
    }
    QSTAMP(11);
    bar_sync(13, 384);
    bar_arrive(0, 384);
    QSTAMP(12);
    WSTAMP(26);
  }

  const uint32_t nh = __shfl_sync(0xffffffffu, near_half(sb), 0);
  uint32_t l16 = sb + lane * 16;
  PIN(l16);
#define LV ((l16 >> 4) & 31)
#define fence_reg l16
  const uint32_t red_lo = (uint32_t)(uint64_t)g_red, red_hi = (uint32_t)((uint64_t)g_red >> 32);
  uint32_t lp;
  auto slot = [&](int s, uint32_t c, uint32_t ofs) {
    const uint32_t lo = lp | (red_lo + ((w >> 1) * 4 + (w & 1) * 2 + ((w ^ c) & 1)) * 4096 + RED_SLOT(s) + ofs);
    uint64_t a; asm("mov.b64 %0, {%1, %2};" : "=l"(a) : "r"(lo), "r"(red_hi));
    return (unsigned char*)a;
  };
  const uint32_t always = __shfl_sync(0xffffffffu, lds32(sb + SC_DEAD + 12), 0);
  const int mode0 = RANK < 2 ? w : w | 4;
  auto hint_addr = [&](int s) { return min(LV, 23u) * 4 + (red_lo + HINT_OFF + nh * 4096 + w * 16384 + RED_SLOT(s)); };
  auto load_hints = [&](uint32_t lo) {
    uint64_t a; asm("mov.b64 %0, {%1, %2};" : "=l"(a) : "r"(lo), "r"(red_hi));
    return ldg_relaxed32((const void*)a);
  };
  int s = 0;
  bool bad = false;
#pragma unroll 1
  while (true) {
    const uint32_t par = s & 1;
    uint32_t vx[4][4], hints;
    auto load_vx = [&]() {
      const uint32_t va = l16 + (RANK < 2 ? SM_VC + par * 8192 : SM_BLK + (s & 3) * SEGB) + w * 1024 + ((LV >> 3) & 1) * 384 - (LV >> 4) * 128;
#pragma unroll
      for (int i = 0; i < 4; i++) ldsm4(vx[i], va + (i & 1) * 4096 + (i >> 1) * 256);
    };
    auto retire = [&](uint32_t x) {
      asm volatile("{\n.reg .pred p;\nsetp.eq.u32 p, %0, 0;\n@p exit;\n}" :: "r"(vx[0][0] | vx[1][0] | vx[2][0] | vx[3][0] | x) : "memory");
    };
    auto scores = [&](auto memkeys, auto first, float* sc) {
      constexpr bool MK = decltype(memkeys)::value, FIRST = decltype(first)::value;
      uint32_t kb[4][4], qb[2][4];
      const uint32_t m = LV >> 3;
      uint32_t kaddr = l16 + SM_BLK + 4096 + (s & 3) * SEGB + w * 2048 + (m & 1) * (MK ? 128 : 896) - (m >> 1) * 128;
      if (MK) { PIN(kaddr); }
      else {
#pragma unroll
        for (int k = 0; k < 4; k++) ldsm4t(kb[k], kaddr + k * 256);
      }
      if (FIRST) { load_vx(); retire(MK ? kaddr : kb[0][0] | kb[1][0] | kb[2][0] | kb[3][0] | l16); bar_sync(4, 256); PROF(4); }
      ldsm4t(qb[0], l16 + SM_QM);
      if (MK) ldsm4t(kb[0], kaddr);
      ldsm4t(qb[1], l16 + SM_QM + 512);
      if (MK) ldsm4t(kb[2], kaddr + 512);
      float c[4][4];
      mma16816z(c[0], kb[0], qb[0][0], qb[0][1]); mma16816z(c[1], kb[MK ? 0 : 1], qb[0][2], qb[0][3]);
      mma16816z(c[2], kb[2], qb[1][0], qb[1][1]); mma16816z(c[3], kb[MK ? 2 : 3], qb[1][2], qb[1][3]);
      if (FIRST && B5POS == 0) bar_arrive(5, N5);
#pragma unroll
      for (int i = 0; i < (MK ? 2 : 4); i++) sc[i] = ((c[0][i] + c[1][MK ? i + 2 : i]) + c[2][i]) + c[3][MK ? i + 2 : i];
    };
    auto send = [&](auto memkeys) {
      constexpr bool MK = decltype(memkeys)::value;
      constexpr int N = MK ? 1 : 2;
      const uint32_t sa = sb + LV * 4 + SM_E + (MK ? 1024 + RANK * 128 : RANK * 512 + w * 256);
      uint32_t ra[N][2], mb[N][2];
#pragma unroll
      for (int i = 0; i < N; i++)
#pragma unroll
        for (int j = 0; j < 2; j++) {
          ra[i][j] = mapa(sa + i * 128, j ? 2 : RANK ^ 1); mb[i][j] = mapa(sb + MB_S, j ? 2 : RANK ^ 1);
          PIN(ra[i][j]);
        }
      float sc[4];
      scores(memkeys, BoolC<true>(), sc);
      uint32_t e[N];
#pragma unroll
      for (int i = 0; i < N; i++) {
        e[i] = pack_bf16(ex2(sc[2 * i]), ex2(sc[2 * i + 1]));
        if (!(fmaxf(fabsf(sc[2 * i]), fabsf(sc[2 * i + 1])) <= E_LIM)) e[i] = 0x7fff7fffu;
        st_async1(ra[i][0], e[i], mb[i][0]);
        st_async1(ra[i][1], e[i], mb[i][1]);
      }
#pragma unroll
      for (int i = 0; i < N; i++) sts32(sa + i * 128, e[i]);
      __syncwarp();
      if (l16 == sb) mbar_arrive(sb + MB_S);
      PROF(5);
    };
    const int mode = bad ? 8 : mode0;
    if (mode < 2) {
      send(BoolC<false>());
    } else if (mode == 2) {
      send(BoolC<true>());
    } else if (mode == 8) {
      load_vx();
      retire(l16);
      const uint32_t fp = lds32(sb + SC_FPAR);
      bar_sync(6, 128);
      if (w == 0 && l16 == sb) { sts32(sb + SC_FPAR, fp ^ 1); mbar_expect(sb + MB_F, 3072); }
      if (RANK < 2 && w < 3) {
        float sc[4] = {0.f, 0.f, 0.f, 0.f};
        if (w < 2) scores(BoolC<false>(), BoolC<false>(), sc); else scores(BoolC<true>(), BoolC<false>(), sc);
#pragma unroll 1
        for (int r = 0; r < 3; r++)
          st_async4(mapa(l16 + SM_FB + RANK * 1536 + w * 512, r), __float_as_uint(sc[0]), __float_as_uint(sc[1]), __float_as_uint(sc[2]), __float_as_uint(sc[3]), mapa(sb + MB_F, r));
      }
      mbar_wait(sb + MB_F, fp);
      float a[12];
#pragma unroll
      for (int j = 0; j < 3; j++) {
        float b[4];
        lds128f(l16 + SM_FB + j * 512, a + 4 * j); lds128f(l16 + SM_FB + 1536 + j * 512, b);
#pragma unroll
        for (int i = 0; i < 4; i++) a[4 * j + i] += b[i];
      }
      float m0 = fmaxf(fmaxf(fmaxf(a[0], a[2]), fmaxf(a[4], a[6])), a[8]), m1 = fmaxf(fmaxf(fmaxf(a[1], a[3]), fmaxf(a[5], a[7])), a[9]);
#pragma unroll
      for (int o = 4; o < 32; o <<= 1) { m0 = fmaxf(m0, __shfl_xor_sync(0xffffffffu, m0, o)); m1 = fmaxf(m1, __shfl_xor_sync(0xffffffffu, m1, o)); }
#pragma unroll
      for (int i = 0; i < 5; i++) {
        const uint32_t ea = sb + SM_E + LV * 4 + (i < 4 ? i * 128 : 1024);
        sts32(ea, pack_bf16(ex2(a[2 * i] - m0), ex2(a[2 * i + 1] - m1)));
        sts32(ea + (i < 4 ? 512 : 128), 0x3f803f80u);
      }
      __syncwarp();
    } else {
      load_vx();
      if (mode == 3) bar_arrive(4, 256);
      retire(l16 + 1);
    }
    {
      uint32_t wa[4], wb[4], oc[4];
      constexpr int WS = 2048;
      const uint32_t w3a = l16 + SM_WO3 + w * 512;
      lds128(w3a + KP(0) * WS, wa); lds128(w3a + KP(1) * WS, wb); lds128(sb + SC_ONES, oc);
      if (B5POS == 1 && mode < 3) bar_arrive(5, N5);
      uint32_t e[10], p[5], vm[4], ob[4];
      float o0[4], o1[4], f[3][2][4], rs[4];
      reserve2(vm); reserve2(vm + 2); reserve2(e + 8);
      hints = hint_addr(s);
      PIN(hints);
      if (CLR & 2) asm volatile("{\n.reg .pred p;\nsetp.eq.u32 p, %0, 0;\n@p exit;\n}" :: "r"(wa[0] | wb[0] | oc[0] | hints) : "memory");
      mbar_wait(sb + MB_S, par);
      PROF(6);
      ldsm4t(e, l16 + SM_E); ldsm2t_in(e + 8, l16 + SM_E + 1024, always); ldsm4t(e + 4, l16 + SM_E + 512);
      lds128_in(vm, l16 + w * 512 + SM_VM, always);
      const float scl = __uint_as_float(lds32(sb + SC_UNSC + 8 - par * 8));
      hints = load_hints(hints);
      if (GF & 1) SCHED_FENCE(4);
#pragma unroll
      for (int i = 0; i < 4; i++) p[i] = mul_bf16(e[i], e[4 + i]);
      p[4] = mul_bf16(e[8], e[9]);
      mma16816z(o0, vx[0], p[0], p[1]); mma16816z(o1, vx[1], p[0], p[1]); mma16816z(rs, oc, p[0], p[1]);
      mma16816(o0, vx[2], p[2], p[3]); lds128_in(vx[2], w3a + KP(2) * WS, always);
      mma16816(o1, vx[3], p[2], p[3]); lds128_in(vx[3], w3a + KP(3) * WS, always);
      mma16816(rs, oc, p[2], p[3]);
      mma1688(o0, vm[0], vm[1], p[4]); mma1688(o1, vm[2], vm[3], p[4]); mma1688(rs, oc[0], oc[1], p[4]);
      stsm4(l16 + w * 512 + SM_OB, pack_bf16(o0[0], o0[1]), pack_bf16(o0[2], o0[3]), pack_bf16(o1[0], o1[1]), pack_bf16(o1[2], o1[3]));
      bar_sync(6, 128);
      PROF(7);
      ldsm4t_in(oc, l16 + SM_OB, always);
      bad = __any_sync(0xffffffffu, !(rs[0] + rs[1] > 0.f) && !bad);
      rs[0] *= scl; rs[1] *= scl;
      asm volatile("{\n.reg .pred p;\nsetp.ne.u32 p, %1, 0;\n@p rcp.approx.ftz.f32 %0, %0;\n}" : "+f"(rs[0]) : "r"(always));
      asm volatile("{\n.reg .pred p;\nsetp.ne.u32 p, %1, 1;\n@p rcp.approx.ftz.f32 %0, %0;\n}" : "+f"(rs[1]) : "r"(always));
      asm volatile("lop3.b32 %0, %1, %2, %3, 0xfe;" : "=r"(lp) : "r"((l16 & 128) * 2), "r"((l16 & 256) * 4), "r"(l16 & 112));
      if (bad) continue;
      ldsm4t(ob, l16 + SM_OB + 512);
      mma16816z(f[2][0], wa, oc[0], oc[1]); mma16816z(f[2][1], wb, oc[2], oc[3]);
      mma16816z(f[0][0], wo[0], oc[0], oc[1]); mma16816z(f[0][1], wo[4], oc[2], oc[3]);
      mma16816z(f[1][0], w1[0], oc[0], oc[1]); mma16816z(f[1][1], w1[4], oc[2], oc[3]);
      ldsm4t_in(oc, l16 + SM_OB + 1024, always);
      mma16816(f[2][0], vx[2], ob[0], ob[1]); lds128_in(vx[2], w3a + KP(4) * WS, always);
      mma16816(f[2][1], vx[3], ob[2], ob[3]); lds128_in(vx[3], w3a + KP(5) * WS, always);
      mma16816(f[0][0], wo[1], ob[0], ob[1]); mma16816(f[0][1], wo[5], ob[2], ob[3]);
      mma16816(f[1][0], w1[1], ob[0], ob[1]); mma16816(f[1][1], w1[5], ob[2], ob[3]);
      ldsm4t_in(ob, l16 + SM_OB + 1536, always);
      mma16816(f[0][0], wo[2], oc[0], oc[1]); mma16816(f[0][1], wo[6], oc[2], oc[3]);
      mma16816(f[2][0], vx[2], oc[0], oc[1]); lds128_in(vx[2], w3a + KP(6) * WS, always);
      mma16816(f[2][1], vx[3], oc[2], oc[3]); lds128_in(vx[3], w3a + KP(7) * WS, always);
      mma16816(f[1][0], w1[2], oc[0], oc[1]); mma16816(f[1][1], w1[6], oc[2], oc[3]);
      mma16816(f[0][0], wo[3], ob[0], ob[1]); mma16816(f[0][1], wo[7], ob[2], ob[3]);
      mma16816(f[1][0], w1[3], ob[0], ob[1]); mma16816(f[1][1], w1[7], ob[2], ob[3]);
      mma16816(f[2][0], vx[2], ob[0], ob[1]); mma16816(f[2][1], vx[3], ob[2], ob[3]);
      bar_arrive(7, NII < 18 ? 384 : 256);
      lds128_in(ob, sb + SC_DEAD, always);
      uint32_t h[3][2];
#pragma unroll
      for (int j = 0; j < 3; j++)
#pragma unroll
        for (int i = 0; i < 2; i++)
        {
          scale_sum(f[j][1][2 * i], f[j][0][2 * i], rs[0], always); scale_sum(f[j][1][2 * i + 1], f[j][0][2 * i + 1], rs[1], always);
          h[j][i] = pack_f16(f[j][1][2 * i], f[j][1][2 * i + 1]);
        }
      const uint32_t rofs = RANK * 32768;
      red_f16x8(slot(s, RANK >> 1, rofs), h[0][0], h[1][0], h[2][0], 0x3c00u);
      red_f16x8(slot(s, (RANK >> 1) ^ 1, rofs), h[0][1], h[1][1], h[2][1], 0x3c00u);
      if (NII == 18) bar_arrive(10, 256);
      SCHED_FENCE(5);
      l16 += ob[B7R];
    }
    {
    PROF(8);
    const uint32_t ma0 = l16 + SM_MEM + w * 128 + (LV >> 3) * 896 + nh * 512;
    const unsigned char* const sl[2] = {slot(s, nh, 0), slot(s, nh ^ 1, 0)};
    uint32_t dl = gtime() - 1984;
    uint32_t late = latest_hint(hints, dl, s);
    if (late >= 64) {
      int n = 0;
#pragma unroll 1
      do {
        hints = load_hints(hint_addr(s));
        dl = gtime() - 1984;
        late = latest_hint(hints, dl, s);
      } while (late >= 64 && ++n < SPIN_LIMIT);
    }
    dl += late * 32 + tm.poll;
    PROF(9);
    {
      auto wait_until = [&](uint32_t t) {
        asm volatile("{\n.reg .pred p;\n.reg .s32 c;\n.reg .u64 t;\nTL: mov.u64 t, %%globaltimer;\ncvt.u32.u64 c, t;\nsub.s32 c, c, %0;\nsetp.lt.s32 p, c, 0;\n@p bra.uni TL;\n}" :: "r"(t + (l16 & 15)) : "memory");
      };
      uint4 v[2][3];
      auto load = [&](int c) {
#pragma unroll
        for (int r = 0; r < 3; r++) v[c][r] = ldg_relaxed(sl[c ^ (r >> 1)] + r * 32768);
      };
      auto decode = [&](int c, int n) {
        uint32_t q[9];
        __half2 hm;
        const uint32_t ma = ma0 ^ (c * 512);
#pragma unroll
        for (int i = 0; i < 9; i++) {
          const uint32_t h = i % 3 == 0 ? v[c][i / 3].x : (i % 3 == 1 ? v[c][i / 3].y : v[c][i / 3].z);
          const float2 f = __half22float2(*(const __half2*)&h);
          q[i] = pack_bf16(f.x, f.y);
          hm = i ? __hmax2(hm, __habs2(*(const __half2*)&h)) : __habs2(*(const __half2*)&h);
        }
#pragma unroll
        for (int r = 0; r < 3; r++) stsm4(ma + r * 4096, q[3 * r], q[3 * r + 1], q[3 * r + 2], r < 2 ? v[c][r].w : *(const uint32_t*)&hm);
        const bool done = __all_sync(0xffffffffu, v[c][0].w == 0x5000u && v[c][1].w == 0x5000u && v[c][2].w == 0x5000u) || n > SPIN_LIMIT;
        asm volatile("{\n.reg .pred p;\nsetp.ne.u32 p, %0, 0;\n@p bar.arrive %1, 256;\n}" :: "r"((int)done), "r"(1 + c) : "memory");
        return done;
      };
      if (LEAD) { wait_until(dl - LEAD); load(1); }
      wait_until(dl);
      PROF(10);
      int n = 0;
#pragma unroll 1
      do {
        load(0);
        if (!LEAD) load(1);
        asm volatile("{\n.reg .pred p;\nsetp.eq.u32 p, %0, 0;\n@p bar.sync 13, 384;\n}" :: "r"(n) : "memory");
      } while (!decode(0, n++));
      PROF(11);
#pragma unroll 1
      while (!decode(1, n++)) load(1);
      bar_arrive(9, 256);
      PROF(12);
    }
    PROF(13);
    if (++s == NSEG - 1) break;
    }
  }
#undef fence_reg
  if (RANK < 2) bar_arrive(4, 256);
  bar_sync(0, 384);
  cluster_sync();
}

__global__ void __cluster_dims__(3, 1, 1) __launch_bounds__(384, 1)
rec_kernel(const __grid_constant__ RMaps tm, const bf16* __restrict__ x, const bf16* __restrict__ mem0) {
  extern __shared__ __align__(1024) unsigned char smem_raw[];
  const uint32_t sb = smem_u32(smem_raw);
  const int tid = threadIdx.x, lane = tid & 31;
  const int wg = __shfl_sync(0xffffffffu, tid >> 7, 0);
  const int w = __shfl_sync(0xffffffffu, (tid >> 5) & 3, 0);
  uint32_t rank; asm("mov.u32 %0, %%cluster_ctarank;" : "=r"(rank));
  STAMP(0);
  asm volatile("griddepcontrol.launch_dependents;" ::: "memory");

  if (wg < 2) {
    asm volatile("setmaxnreg.inc.sync.aligned.u32 192;");
    if (tid == 0) {
      for (int i = 0; i < 3; i++) { mbar_init(sb + MB_W + 8 * i, 1); mbar_init(sb + MB_X + 8 * i, 1); }
      mbar_init(sb + MB_WO, 1); mbar_init(sb + MB_WO3, 1);
      mbar_init(sb + MB_S, rank < 2 ? 5 : 6);
      mbar_init(sb + MB_F, 1); mbar_init(sb + MB_XS, 1);
      mbar_init(sb + MB_VX, 1); mbar_init(sb + MB_VX + 8, 1);
      asm volatile("fence.mbarrier_init.release.cluster;" ::: "memory");
      fence_async();
      const int h = blockIdx.x / 3;
      const CUtensorMap* m0 = rank < 2 ? &tm.wk : &tm.wv;
      const CUtensorMap* m1 = rank < 2 ? &tm.wq : &tm.wv;
      const int c0 = h * DH + (rank == 1 ? 64 : 0), c1 = h * DH + (rank == 0 ? 0 : 64);
      auto load_w = [&](int c) {
        mbar_expect(sb + MB_W + 8 * c, 49152);
        tma_load(sb + SM_STAGE + c * 49152, m0, c0, c * 192, sb + MB_W + 8 * c);
        tma_load(sb + SM_STAGE + c * 49152 + 24576, m1, c1, c * 192, sb + MB_W + 8 * c);
      };
      for (int i = 0; i < 3; i++) mbar_expect(sb + MB_X + 8 * i, XT);
      if (blockIdx.x < NSEG) { mbar_expect(sb + MB_XS, XT); bulk_load(sb + SM_X, x + blockIdx.x * 32 * DM, XT, sb + MB_XS); }
      for (int c = 0; c < WPOS; c++) load_w(c);
      mbar_expect(sb + MB_WO3, 32768 + 8 * DM * 2);
      tma_load(sb + SM_WOST, &tm.wo, rank * 192 + 64, h * DH, sb + MB_WO3);
      tma_load(sb + SM_WO3, &tm.wo, rank * 192 + 128, h * DH, sb + MB_WO3);
      bulk_load(sb + SM_M0, mem0, 8 * DM * 2, sb + MB_WO3);
      tma_prefetch(&tm.wo, rank * 192, h * DH);
      if (blockIdx.x >= NSEG) tma_load3(sb + SM_X, &tm.x, 0, sb + MB_X);
      for (int c = WPOS; c < 3; c++) load_w(c);
      mbar_expect(sb + MB_WO, 16384);
      mbar_expect(sb + MB_S, rank < 2 ? 640 + 2048 : 1280);
      mbar_expect(sb + MB_VX, 8192); mbar_expect(sb + MB_VX + 8, 8192);
    }
    __syncwarp();
    QSTAMP(0);
    if (tid < 32) bar_arrive(0, 160);
    QSTAMP(1);
    proj_role(sb, tm, rank, wg, w, lane);
  } else {
    asm volatile("setmaxnreg.dec.sync.aligned.u32 120;");
    attn_role(sb, smem_raw, tm, rank, x, mem0, w, lane);
  }
}

constexpr int NAUX = 36;
constexpr int A_ST = 6, A_STAGE = 8192 + 12288, A_W8 = A_ST * A_STAGE, A_EXC = A_W8 + A_ST * 1536, A_ROWS = 57;
constexpr int A_XT = 3 * XT, A_XW = A_XT + 3 * 4096;
constexpr int A_IN = A_EXC + 8 * 2304, A_INB = 3 * SEGB, A_OST = A_IN + 2 * A_INB, A_P = A_OST + 8192, A_G = A_P + 3072;
constexpr int A_BAR = A_G + 1024;
constexpr int A_TOTAL = A_BAR + 512;
static_assert(A_IN % 1024 == 0 && A_IN >= 4 * XT && A_IN + 64 * DM * 2 <= A_BAR && A_TOTAL <= 232448, "side kernel shared memory");
struct AMaps { CUtensorMap x, wa, wa8, o, o3, wob, woa; const unsigned char* red; uint32_t poll; };

DI void wgmma_n192_ss_nt(float* d, uint64_t da, uint64_t db, int acc) {
  asm volatile("{\n.reg .pred p;\nsetp.ne.b32 p, %98, 0;\n"
               "wgmma.mma_async.sync.aligned.m64n192k16.f32.bf16.bf16 {"
               "%0,%1,%2,%3,%4,%5,%6,%7,%8,%9,%10,%11,%12,%13,%14,%15,%16,%17,%18,%19,%20,%21,%22,%23,%24,%25,%26,%27,%28,%29,%30,%31,"
               "%32,%33,%34,%35,%36,%37,%38,%39,%40,%41,%42,%43,%44,%45,%46,%47,%48,%49,%50,%51,%52,%53,%54,%55,%56,%57,%58,%59,%60,%61,%62,%63,"
               "%64,%65,%66,%67,%68,%69,%70,%71,%72,%73,%74,%75,%76,%77,%78,%79,%80,%81,%82,%83,%84,%85,%86,%87,%88,%89,%90,%91,%92,%93,%94,%95"
               "}, %96, %97, p, 1, 1, 0, 1;\n}\n"
               : ACC8(d, 0), ACC8(d, 8), ACC8(d, 16), ACC8(d, 24), ACC8(d, 32), ACC8(d, 40), ACC8(d, 48), ACC8(d, 56),
                 ACC8(d, 64), ACC8(d, 72), ACC8(d, 80), ACC8(d, 88) : "l"(da), "l"(db), "r"(acc));
}
DI void wgmma_n24_ss_nt(float* d, uint64_t da, uint64_t db, int acc) {
  asm volatile("{\n.reg .pred p;\nsetp.ne.b32 p, %14, 0;\n"
               "wgmma.mma_async.sync.aligned.m64n24k16.f32.bf16.bf16 {%0,%1,%2,%3,%4,%5,%6,%7,%8,%9,%10,%11}, %12, %13, p, 1, 1, 0, 1;\n}\n"
               : ACC8(d, 0), "+f"(d[8]), "+f"(d[9]), "+f"(d[10]), "+f"(d[11]) : "l"(da), "l"(db), "r"(acc));
}
DI void tma_load3d(uint32_t dst, const CUtensorMap* m, int c0, int c1, int c2, uint32_t mb) {
  asm volatile("cp.async.bulk.tensor.3d.shared::cluster.global.mbarrier::complete_tx::bytes [%0], [%1, {%3, %4, %5}], [%2];"
               :: "r"(dst), "l"(m), "r"(mb), "r"(c0), "r"(c1), "r"(c2) : "memory");
}
DI uint32_t trans8(uint32_t x) { uint32_t r; asm("movmatrix.sync.aligned.m8n8.trans.b16 %0, %1;" : "=r"(r) : "r"(x)); return r; }
DI void wgmma_n32_ss_tn(float* d, uint64_t da, uint64_t db) {
  asm volatile("wgmma.mma_async.sync.aligned.m64n32k16.f32.bf16.bf16 {%0,%1,%2,%3,%4,%5,%6,%7,%8,%9,%10,%11,%12,%13,%14,%15}, "
               "%16, %17, 1, 1, 1, 1, 0;"
               : ACC8(d, 0), ACC8(d, 8) : "l"(da), "l"(db));
}
DI void wgmma_n40_ss(float* d, uint64_t da, uint64_t db, int acc) {
  asm volatile("{\n.reg .pred p;\nsetp.ne.b32 p, %22, 0;\n"
               "wgmma.mma_async.sync.aligned.m64n40k16.f32.bf16.bf16 {%0,%1,%2,%3,%4,%5,%6,%7,%8,%9,%10,%11,%12,%13,%14,%15,%16,%17,%18,%19}, "
               "%20, %21, p, 1, 1, 1, 1;\n}\n"
               : ACC8(d, 0), ACC8(d, 8), "+f"(d[16]), "+f"(d[17]), "+f"(d[18]), "+f"(d[19]) : "l"(da), "l"(db), "r"(acc));
}
DI uint2 ldg_relaxed64(const void* p) {
  uint2 v; asm volatile("ld.relaxed.gpu.global.v2.b32 {%0,%1}, [%2];" : "=r"(v.x), "=r"(v.y) : "l"(p) : "memory"); return v;
}
template <int ST> DI void ldg8x64(uint32_t* m, const void* p) {
  asm volatile("ld.relaxed.gpu.global.v2.b32 {%0,%1}, [%16];\nld.relaxed.gpu.global.v2.b32 {%2,%3}, [%16 + %17];\n"
               "ld.relaxed.gpu.global.v2.b32 {%4,%5}, [%16 + %18];\nld.relaxed.gpu.global.v2.b32 {%6,%7}, [%16 + %19];\n"
               "ld.relaxed.gpu.global.v2.b32 {%8,%9}, [%16 + %20];\nld.relaxed.gpu.global.v2.b32 {%10,%11}, [%16 + %21];\n"
               "ld.relaxed.gpu.global.v2.b32 {%12,%13}, [%16 + %22];\nld.relaxed.gpu.global.v2.b32 {%14,%15}, [%16 + %23];"
               : "=r"(m[0]), "=r"(m[1]), "=r"(m[2]), "=r"(m[3]), "=r"(m[4]), "=r"(m[5]), "=r"(m[6]), "=r"(m[7]),
                 "=r"(m[8]), "=r"(m[9]), "=r"(m[10]), "=r"(m[11]), "=r"(m[12]), "=r"(m[13]), "=r"(m[14]), "=r"(m[15])
               : "l"(p), "n"(ST), "n"(2 * ST), "n"(3 * ST), "n"(4 * ST), "n"(5 * ST), "n"(6 * ST), "n"(7 * ST) : "memory");
}
template <int ST> DI void ldg4x128(uint32_t* m, const void* p) {
  asm volatile("ld.relaxed.gpu.global.v4.b32 {%0,%1,%2,%3}, [%16];\nld.relaxed.gpu.global.v4.b32 {%4,%5,%6,%7}, [%16 + %17];\n"
               "ld.relaxed.gpu.global.v4.b32 {%8,%9,%10,%11}, [%16 + %18];\nld.relaxed.gpu.global.v4.b32 {%12,%13,%14,%15}, [%16 + %19];"
               : "=r"(m[0]), "=r"(m[1]), "=r"(m[2]), "=r"(m[3]), "=r"(m[4]), "=r"(m[5]), "=r"(m[6]), "=r"(m[7]),
                 "=r"(m[8]), "=r"(m[9]), "=r"(m[10]), "=r"(m[11]), "=r"(m[12]), "=r"(m[13]), "=r"(m[14]), "=r"(m[15])
               : "l"(p), "n"(ST), "n"(2 * ST), "n"(3 * ST) : "memory");
}
template <int N, int ST> DI bool stale(const uint32_t* m, uint32_t tag) {
  uint32_t x = m[0] ^ tag;
#pragma unroll
  for (int i = 1; i < N; i++) asm("lop3.b32 %0, %0, %1, %2, 0xf6;" : "+r"(x) : "r"(m[i * ST]), "r"(tag));
  return __any_sync(0xffffffffu, x & 1);
}
DI bool mbar_test(uint32_t b, uint32_t par) {
  uint32_t r; asm volatile("{\n.reg .pred p;\nmbarrier.test_wait.parity.shared::cta.b64 p, [%1], %2;\nselp.u32 %0, 1, 0, p;\n}" : "=r"(r) : "r"(b), "r"(par) : "memory");
  return r;
}
DI int wait_flags(const unsigned* p, bool active, unsigned base, int seg) {
  int n = 0, m;
  while (true) {
    m = __reduce_min_sync(0xffffffffu, active ? (int)(ldg_acquire32(p) - base) : NSEG);
    if (m > seg || ++n > SPIN_LIMIT) break;
    __nanosleep((YP & 32) ? 400 : 40);
  }
  return max(m, seg + 1);
}
DI void wait_count(const unsigned* p, unsigned target) {
  int n = 0;
  unsigned v;
  while (true) {
    asm volatile("ld.acquire.gpu.global.b32 %0, [%1];" : "=r"(v) : "l"(p) : "memory");
    if ((int)(v - target) >= 0 || ++n > SPIN_LIMIT) break;
    __nanosleep(64);
  }
}
#define PACE_NEXT 800
#define AWARM 0
#define PING 1
#define FLAG 2
#define FPOS 1
#define QB 1
#define Q_LO 0
#define Q_HI 320
DI void tick_wait(uint32_t pace, int step) {
  const int n = lds32(pace);
  if (n <= step) mbar_wait(pace + 8, n & 1);
}
DI void quiet_wait(uint32_t pace) {
  uint32_t n, d;
  lds64(pace, n, d);
  if (n - 1 < NSEG - 2 && (int)(gtime() - d) > Q_HI) mbar_wait(pace + 8, n & 1);
}
DI void sleep_until(uint32_t t) {
  for (int n = 0; n < 64; n++) {
    const int r = t - gtime();
    if (r <= 0) break;
    __nanosleep(r >> 1);
  }
}
DI void aux_barrier(int i, unsigned epoch, bool wait = true) {
  asm volatile("fence.proxy.async;" ::: "memory");
  asm volatile("red.release.gpu.global.add.u32 [%0], 1;" :: "l"(&g_abar[i * 32]) : "memory");
  if (!wait) return;
  wait_count(&g_abar[i * 32], NAUX * (epoch + 1));
  asm volatile("fence.proxy.async;" ::: "memory");
}

__global__ void __launch_bounds__(512, 1)
aux_kernel(const __grid_constant__ AMaps tm, const bf16* __restrict__ x, const bf16* __restrict__ gate_w, bf16* __restrict__ out) {
  extern __shared__ __align__(1024) unsigned char smem_raw[];
  const uint32_t sb = smem_u32(smem_raw);
  const uint32_t full1 = sb + A_BAR, empty1 = full1 + 8 * A_ST, fullw = empty1 + 8 * A_ST, full3 = fullw + 16, empty3 = full3 + 32,
                 fulla = empty3 + 32, emptya = fulla + 32, fullg = emptya + 16, pace = fullg + 8;
  const int tid = threadIdx.x, lane = tid & 31, cta = blockIdx.x;
  const int wg = __shfl_sync(0xffffffffu, tid >> 7, 0), w = __shfl_sync(0xffffffffu, (tid >> 5) & 3, 0);
  ASTAMP(14);
  const unsigned epoch = *(volatile unsigned*)&g_epoch2;
  if (tid == 0) {
    for (int i = 0; i < A_ST; i++) { mbar_init(full1 + 8 * i, 1); mbar_init(empty1 + 8 * i, 8); }
    mbar_init(fullw, 1); mbar_init(fullw + 8, 1); mbar_init(fullg, 1);
    for (int i = 0; i < 2; i++) { mbar_init(fulla + 16 * i, 2); mbar_init(fulla + 16 * i + 8, 2); mbar_init(emptya + 8 * i, 4); }
    sts64(pace, 0, 0); mbar_init(pace + 8, 1); sts32(pace + 16, 0); sts64(pace + 24, 65536, 0xffff0000u);
    for (int i = 0; i < 4; i++) { mbar_init(full3 + 8 * i, 1); mbar_init(empty3 + 8 * i, cta < NH ? 8 : 4); }
    fence_async();
  }
  __syncthreads();
  ASTAMP(0);
  const bool wide = cta < NH;
  auto p3_ks = [&](int g) { return wide ? cta >> 2 : 2 * (cta - NH) + g; };
  auto p3_mt = [&](int g) { return wide ? 2 * (cta & 3) + g : 8; };
  const uint32_t xt = sb + (wide ? A_XT : A_IN), xw = sb + (wide ? A_XW : A_IN + 16384);
  const unsigned fbase = epoch * NSEG;
  if (wg == 3) {
    asm volatile("setmaxnreg.dec.sync.aligned.u32 48;");
    if (w == 1 && cta < NH) {
#pragma unroll 1
      for (int seg = 0; seg < ((XP & 2048) ? 0 : NSEG); seg++) {
        bar_arrive(5, 160);
        if (seg > 0 && lane == 0) {
          asm volatile("cp.async.bulk.wait_group 0;" ::: "memory");
          stg_relaxed32(&g_oflag[cta * 32], fbase + seg);
        }
        __syncwarp();
        bar_sync(4, 160);
        if (QM & 16) tick_wait(pace, seg + 1);
        if (lane == 0) {
          fence_async();
          if (!(YP & 2)) {
          tma_store(&tm.o, sb + A_OST, cta * DH, seg * 32);
          tma_store(&tm.o, sb + A_OST + 4096, cta * DH + 64, seg * 32);
          }
          asm volatile("cp.async.bulk.commit_group;" ::: "memory");
          asm volatile("cp.async.bulk.wait_group.read 0;" ::: "memory");
        }
        __syncwarp();
      }
      if (lane == 0) {
        asm volatile("cp.async.bulk.wait_group 0;" ::: "memory");
        stg_relaxed32(&g_oflag[cta * 32], fbase + NSEG);
      }
    }
    if (w == 2 && cta < NH) {
      const uint32_t ktag = (epoch + 1) & 1, ma = sb + A_IN + 8192 + lane * 16;
      int avail = 0;
      bar_sync(10, 64);
#pragma unroll 1
      for (int seg = 0; seg < ((XP & 2048) ? 0 : NSEG); seg++) {
        if (avail <= seg) avail = wait_flags(&g_sflag[(cta * 3 + min(lane, 2)) * 8], true, fbase, seg);
        if (QM & 8) tick_wait(pace, seg);
        const unsigned char* km = g_km + (size_t)(seg * NH + cta) * 4096 + lane * 8;
        uint32_t m[16];
        const float g = __ldcg(&g_gate[seg * 32 + lane]);
        ldg8x64<256>(m, km);
        const uint32_t b = seg & 1, full = fulla + 16 * b, mb = ma + b * A_INB;
        mbar_wait(emptya + 8 * b, (~seg >> 1) & 1);
        if (lane < 2) mbar_expect(full + 8 * lane, (YP & 8) ? 0 : 16384 >> lane);
        __syncwarp();
        if (lane < 3 && !(YP & 8)) bulk_load(sb + A_IN + b * A_INB + lane * SEGB, g_seg + ((size_t)(seg & RING) * 96 + cta * 3 + lane) * 8192, 8192, full + (lane & 2) * 4);
        int n = 0;
#pragma unroll 1
        while (stale<8, 2>(m, ktag) && ++n < SPIN_LIMIT) { if (seg < NSEG - 1) __nanosleep(200); ldg8x64<256>(m, km); }
#pragma unroll
        for (int i = 0; i < 4; i++) stsm4(mb + (i >> 1) * SEGB + (i & 1) * 512, m[4 * i], m[4 * i + 1], m[4 * i + 2], m[4 * i + 3]);
        sts32(sb + A_G + b * 128 + lane * 4, __float_as_uint(1.f - g));
        fence_async();
        __syncwarp();
        if (lane == 0) mbar_arrive(full);
#pragma unroll 1
        do ldg4x128<512>(m, km + 2048 + lane * 8); while (stale<4, 4>(m, ktag) && ++n < SPIN_LIMIT);
#pragma unroll
        for (int i = 0; i < 4; i++) stsm4(mb + 2 * SEGB + (lane >> 4) * 768 + i * 256, m[4 * i], m[4 * i + 1], m[4 * i + 2], m[4 * i + 3]);
        fence_async();
        __syncwarp();
        if (lane == 0) mbar_arrive(full + 8);
      }
    }
    if (w == 3 && QM) {
      const unsigned char* const hp = tm.red + HINT_OFF + 65536 + (cta & 1) * 4096 + min(lane, 23) * 4;
      uint32_t d = 0;
      int s = 0, n = 0;
#pragma unroll 1
      while (s < NSEG - 1) {
        const uint32_t h = ldg_relaxed32(hp + RED_SLOT(s)), t = (gtime() - 1984) & ~31u, late = latest_hint(h, t, s);
        if (late < 64) {
          d = t + late * 32 + tm.poll + Q_LO;
          sleep_until(d);
          s++; n = 0;
          if (lane == 0) { mbar_arrive(pace + 8); sts64(pace, s < NSEG - 1 ? s : 2 * NSEG, d); }
          sleep_until(d + PACE_NEXT);
        } else {
          if (++n > (s ? 16 : 256) || lds32(pace + 16)) break;
          if (!s) __nanosleep(100);
        }
      }
      if (s < NSEG - 1 && lane == 0) { mbar_arrive(pace + 8); sts64(pace, 2 * NSEG, d); }
    }
    if (w != 0) return;
    const bool lead = lane == 0;
    if (lead) {
#pragma unroll 1
      for (int it = 0, st = 0, ph = 1, k = 0, col = (cta & 1) * (DM / 2); it < ((XP & 256) ? 0 : 72); it++) {
        mbar_wait(empty1 + 8 * st, ph);
        if (QM & 1) quiet_wait(pace);
        mbar_expect(full1 + 8 * st, A_STAGE + 1536);
        tma_load3d(sb + st * A_STAGE, &tm.x, k, (cta >> 1) * A_ROWS - 7, 0, full1 + 8 * st);
        tma_load3d(sb + st * A_STAGE + 8192, &tm.wa, col, k, 0, full1 + 8 * st);
        tma_load3d(sb + A_W8 + st * 1536, &tm.wa8, col + 64, k, 0, full1 + 8 * st);
        if (++st == A_ST) { st = 0; ph ^= 1; }
        k += 32;
        if (k == DM) { k = 0; col += 72; }
      }
    }
    __syncwarp();
    auto load_wo = [&](uint32_t dst, int g, int kb, uint32_t mb) {
      if (kb < 64) tma_load(dst, &tm.wob, p3_mt(g) * 64, kb * 64, mb);
      else tma_load(dst, &tm.woa, p3_mt(g) * 64, (kb - 64) * 64, mb);
    };
    if (!(XP & 256)) for (int st = 0; st < A_ST; st++) mbar_wait(empty1 + 8 * st, 1);
    if (QM & 2) quiet_wait(pace);
    if (lead) mbar_expect(fullw, 16 * 8192);
    __syncwarp();
    if (lane < 16) load_wo(sb + lane * 8192, lane >> 3, p3_ks(lane >> 3) * 9 + (lane & 7), fullw);
    __syncwarp(); bar_sync(6, 288);
    if (lead) mbar_expect(fullw + 8, 2 * 8192);
    __syncwarp();
    if (lane < 2) load_wo(sb + (16 + lane) * 8192, lane, p3_ks(lane) * 9 + 8, fullw + 8);
    __syncwarp();
    if (lead) aux_barrier(1, epoch, p3_ks(1) == 7);
    __syncwarp(); bar_sync(6, 288);
    {
      int avail = 0, sl = 0, ph = 1;
      const int h = (9 * p3_ks(0) >> 1) + lane;
#pragma unroll 1
      for (int seg = 0; seg < ((XP & 2048) ? 0 : NSEG); seg++) {
        if (avail <= seg) avail = wait_flags(&g_oflag[min(h, NH - 1) * 32], lane < (wide ? 5 : 9), fbase, seg);
        SSTAMP(seg, 4);
        for (int g = 0; g < (wide ? 1 : 2); g++) {
          const int ks = p3_ks(g);
          mbar_wait(empty3 + 8 * sl, ph);
          if (QM & 4) tick_wait(pace, seg + (QM >> 4 & 1) + 1);
          if (lead && (YP & 4)) mbar_arrive(full3 + 8 * sl);
          else if (lead) {
            mbar_expect(full3 + 8 * sl, XT + (ks == 7 ? (seg ? 4096 : wide ? 20480 : 12288) : 0));
            tma_load3d(sb + sl * XT, &tm.o3, 0, seg * 32, ks * 9, full3 + 8 * sl);
            if (ks == 7) {
              tma_load(xt + sl * 4096, &tm.o, 72 * 64, seg * 32, full3 + 8 * sl);
              if (seg == 0) { load_wo(xw + 8192, 1, 72, full3 + 8 * sl); if (wide) load_wo(xw, 0, 72, full3 + 8 * sl); }
            }
          }
          __syncwarp();
          if (++sl == (wide ? 3 : 4)) { sl = 0; ph ^= 1; }
        }
      }
    }
    sts32(pace + 16, 1);
    __syncwarp(); bar_sync(6, 288);
    asm volatile("griddepcontrol.wait;" ::: "memory");
  } else if (wg == 2) {
    asm volatile("setmaxnreg.dec.sync.aligned.u32 64;");
    if (cta < NH) {
      if (tid == 256) { mbar_expect(fullg, 64 * DM * 2); bulk_load(sb + A_IN, x + cta * 64 * DM, 64 * DM * 2, fullg); }
      uint32_t gw[9];
#pragma unroll
      for (int j = 0; j < 9; j++) gw[j] = ((const uint32_t*)gate_w)[j * 32 + lane];
      mbar_wait(fullg, 0);
      float mine = 0.f;
#pragma unroll 4
      for (int u = 0; u < 16; u++) {
        float d0 = 0.f, d1 = 0.f;
#pragma unroll
        for (int j = 0; j < 9; j++) {
          const uint32_t a = lds32(sb + A_IN + (w * 16 + u) * (DM * 2) + j * 128 + lane * 4);
          d0 = fmaf(bf_lo(a), bf_lo(gw[j]), d0); d1 = fmaf(bf_hi(a), bf_hi(gw[j]), d1);
        }
        d0 = warp_sum(d0 + d1);
        if (lane == u) mine = d0;
      }
      if (lane < 16) g_gate[cta * 64 + w * 16 + lane] = 1.f / (1.f + __expf(-mine));
      fence_async();
    }
    bar_sync(3, 128);
    if (tid == 256) { aux_barrier(0, epoch); if (cta == 0) *(volatile unsigned*)&g_epoch2 = epoch + 1; }
    __syncwarp();
    bar_sync(3, 128);
    if (w == 0) bar_arrive(8, 288);
    if (w == 1 && cta < NH) bar_arrive(10, 64);
    if (cta < NH) {
      CDECL;
#pragma unroll 1
      for (int seg = 0; seg < ((XP & 2048) ? 0 : NSEG); seg++) {
        CSTAMP(0);
        const uint32_t in = sb + A_IN + (seg & 1) * A_INB;
        const uint64_t qd = make_desc(in, 128, 1024, 0);
        mbar_wait(fulla + 16 * (seg & 1), (seg >> 1) & 1);
        CSTAMP(3);
        SSTAMP(seg, 0);
        float d[2][16];
        {
          float a[20];
          WG_FENCE();
#pragma unroll
          for (int k = 0; k < ((YP & 16) ? 1 : 8); k++) wgmma_n40_ss(a, qd + ((k >> 2) * SEGB + (k & 3) * 256 >> 4), qd + ((k >> 2) * SEGB + (k & 3) * 256 + 4096 >> 4), k > 0);
          const uint32_t ga = sb + A_G + (seg & 1) * 128 + (w & 1) * 64 + (lane >> 2) * 4;
          const float f0 = __uint_as_float(lds32(ga)), f1 = __uint_as_float(lds32(ga + 32));
          WG_COMMIT();
          WG_WAIT(0);
          CSTAMP(5);
          SSTAMP(seg, 1);
          if (w < 2) {
            const int lim = w * 16 + (lane >> 2) - 2 * (lane & 3);
            float m0 = -3.0e38f, m1 = -3.0e38f;
#pragma unroll
            for (int i = 0; i < 20; i++) {
              a[i] *= SM_SCALE * LOG2E;
              if (i < 16 && (i >> 2) * 8 + (i & 1) - (i & 2) * 4 > lim) a[i] = -1.0e9f * LOG2E;
              if (i & 2) m1 = fmaxf(m1, a[i]); else m0 = fmaxf(m0, a[i]);
            }
#pragma unroll
            for (int o = 1; o < 4; o <<= 1) { m0 = fmaxf(m0, __shfl_xor_sync(0xffffffffu, m0, o)); m1 = fmaxf(m1, __shfl_xor_sync(0xffffffffu, m1, o)); }
            float s0 = 0.f, s1 = 0.f;
#pragma unroll
            for (int i = 0; i < 20; i++) { a[i] = ex2(a[i] - (i & 2 ? m1 : m0)); if (i & 2) s1 += a[i]; else s0 += a[i]; }
#pragma unroll
            for (int o = 1; o < 4; o <<= 1) { s0 += __shfl_xor_sync(0xffffffffu, s0, o); s1 += __shfl_xor_sync(0xffffffffu, s1, o); }
            s0 = f0 * rcp(s0); s1 = f1 * rcp(s1);
            uint32_t p[10];
#pragma unroll
            for (int i = 0; i < 10; i++) p[i] = pack_bf16(a[2 * i] * (i & 1 ? s1 : s0), a[2 * i + 1] * (i & 1 ? s1 : s0));
            const uint32_t pa = sb + A_P + (2 * w + ((lane >> 3) & 1)) * 768 + (lane >> 4) * 128 + (lane & 7) * 16;
            stsm4t(pa, p[0], p[1], p[2], p[3]); stsm4t(pa + 256, p[4], p[5], p[6], p[7]); stsm4t(pa + 512, p[8], p[9], 0, 0);
            CSTAMP(6);
            fence_async();
            CSTAMP(7);
          }
        }
        CSTAMP(8);

        if (w == 3) mbar_wait(fulla + 16 * (seg & 1) + 8, (seg >> 1) & 1);
        bar_sync(5, 160);
        CSTAMP(10);
        SSTAMP(seg, 2);
        const uint64_t pd = make_desc(sb + A_P, 128, 768, 0), vd = make_desc(in + 2 * SEGB, 128, 512, 0), md = make_desc(in + 2 * SEGB + 8192, 0, 128, 0);
        WG_FENCE();
#pragma unroll
        for (int i = 0; i < 2; i++) {
          wgmma_n32_ss<0>(d[i], vd + i * 256, pd, 0);
          wgmma_n32_ss<0>(d[i], vd + i * 256 + 16, pd + 16, 1);
          wgmma_n32_ss<0>(d[i], md + i * 64, pd + 32, 1);
        }
        WG_COMMIT();
        WG_WAIT(0);
        CSTAMP(11);
        if (lane == 0) mbar_arrive(emptya + 8 * (seg & 1));
#pragma unroll
        for (int i = 0; i < 2; i++) {
          const uint32_t oa = sb + A_OST + i * 4096 + ((lane & 7) + ((lane >> 4) << 3)) * 128 + (((2 * w + ((lane >> 3) & 1)) ^ (lane & 7)) << 4);
          stsm4t(oa, pack_bf16(d[i][0], d[i][1]), pack_bf16(d[i][2], d[i][3]), pack_bf16(d[i][4], d[i][5]), pack_bf16(d[i][6], d[i][7]));
          stsm4t(oa + 2048, pack_bf16(d[i][8], d[i][9]), pack_bf16(d[i][10], d[i][11]), pack_bf16(d[i][12], d[i][13]), pack_bf16(d[i][14], d[i][15]));
        }
        CSTAMP(12);
        bar_sync(4, 160);
        SSTAMP(seg, 3);
      }
      CDUMP;
    }
  } else {
    asm volatile("setmaxnreg.inc.sync.aligned.u32 200;");
    {
      const int g = lane >> 2, t = lane & 3, r0 = (cta >> 1) * A_ROWS - 7 + w * 16;
      const uint32_t prev = (2 * t > g ? 0xffffu : 0u) | (2 * t + 1 > g ? 0xffff0000u : 0u);
      const int k0 = r0 + 2 * t - (2 * t > g ? 8 : 0), k1 = r0 + 2 * t + 1 - (2 * t + 1 > g ? 8 : 0);
      const uint32_t slot = sb + A_EXC + (wg * 4 + w) * 2304;
      float gl = 0.f, gh = 0.f;
      int st = 0, ph = 0;
#pragma unroll 1
      for (int p = -AWARM; p < ((XP & 256) ? 0 : 4); p++) {
        float big[96], sml[12];
        if (p == 3 && tid < 18) {
          const int kb = p3_ks(tid >= 9) * 9 + tid % 9;
          tma_prefetch(kb < 64 ? &tm.wob : &tm.woa, p3_mt(tid >= 9) * 64, (kb & 63) * 64);
        }
        __syncwarp();
#pragma unroll
        for (int i = 0; i < 96; i++) big[i] = 0.f;
#pragma unroll
        for (int i = 0; i < 12; i++) sml[i] = 0.f;
#pragma unroll 1
        for (int k = p < 0 ? 18 : 0; k < 18; k++) {
          mbar_wait(full1 + 8 * st, ph);
          const uint64_t da = make_desc(sb + st * A_STAGE + wg * 4096, 16, 512, 2);
          const uint64_t db = make_desc(sb + st * A_STAGE + 8192, 4096, 1024, 1), dc = make_desc(sb + A_W8 + st * 1536, 128, 512, 0);
          WG_FENCE();
#pragma unroll
          for (int j = 0; j < 2; j++) { wgmma_n192_ss_nt(big, da + j * 2, db + j * 128, 1); wgmma_n24_ss_nt(sml, da + j * 2, dc + j * 16, 1); }
          WG_COMMIT();
          WG_WAIT(1);
          if (k > 0 && lane == 0) mbar_arrive(empty1 + 8 * (st ? st - 1 : A_ST - 1));
          if (++st == A_ST) { st = 0; ph ^= 1; }
        }
        WG_WAIT(0);
        ASTAMP(16 + max(p, 0) + wg * 16);
        if (lane == 0 && p >= 0) mbar_arrive(empty1 + 8 * (st ? st - 1 : A_ST - 1));
        uint32_t f[3][9][2];
#pragma unroll
        for (int c = 0; c < 3; c++)
#pragma unroll
          for (int j = 0; j < 9; j++)
#pragma unroll
            for (int i = 0; i < 2; i++) {
              const float* a = j < 8 ? &big[(c * 8 + j) * 4 + 2 * i] : &sml[c * 4 + 2 * i];
              f[c][j][i] = c < 2 ? pack_bf16(a[0], a[1]) : trans8(pack_bf16(a[0], a[1]));
            }
        if (p == 0) {
          bar_sync(8, 288);
          gl = __ldcg(&g_gate[min(max(r0 + g, 0), S_LEN / 2 - 1) * 2 + wg]); gh = __ldcg(&g_gate[min(max(r0 + g + 8, 0), S_LEN / 2 - 1) * 2 + wg]);
        }
        asm volatile("cp.async.bulk.wait_group.read 0;" ::: "memory");
        __syncwarp();
#pragma unroll
        for (int j = 0; j < 8; j += 2) sts128(slot + j * 256 + lane * 16, f[1][j][1], f[2][j][1], f[1][j + 1][1], f[2][j + 1][1]);
        sts64(slot + 2048 + lane * 8, f[1][8][1], f[2][8][1]);
        bar_sync(1 + wg, 128);
        ASTAMP(24 + max(p, 0) + wg * 16);
        uint32_t pv[9][2];
#pragma unroll
        for (int j = 0; j < 9; j++) pv[j][0] = pv[j][1] = 0;
        if (w) {
#pragma unroll
          for (int j = 0; j < 8; j += 2) lds128(slot - 2304 + j * 256 + lane * 16, pv[j]);
          lds64(slot - 256 + lane * 8, pv[8][0], pv[8][1]);
        }
        float a[4][4], m[4][2];
#pragma unroll
        for (int h = 0; h < 4; h++) {
          const int j = 2 * h;
          const uint32_t qa[4] = {t >= h ? f[0][j][0] : 0, t >= h ? f[0][j][1] : 0, f[0][j + 1][0], f[0][j + 1][1]};
          const uint32_t qb0 = t <= h ? f[0][j + 2][0] : 0, qb1 = t <= h ? f[0][j + 2][1] : 0;
          float s0[4], s1[4], s2[4];
          mma16816z(s1, qa, f[1][j][0], f[1][j + 1][0]); mma16816z(s2, qa, f[1][j][1], f[1][j + 1][1]); mma16816z(s0, qa, pv[j][0], pv[j + 1][0]);
          mma1688(s1, qb0, qb1, f[1][j + 2][0]); mma1688(s2, qb0, qb1, f[1][j + 2][1]); mma1688(s0, qb0, qb1, pv[j + 2][0]);
          a[h][0] = 2 * t > g ? s0[0] : s1[0]; a[h][1] = 2 * t + 1 > g ? s0[1] : s1[1]; a[h][2] = 2 * t > g ? s1[2] : s2[2]; a[h][3] = 2 * t + 1 > g ? s1[3] : s2[3];
        }
#pragma unroll
        for (int h = 0; h < 4; h++) {
#pragma unroll
          for (int i = 0; i < 4; i++) a[h][i] = (i & 1 ? k1 : k0) + (i & 2) * 4 >= 0 ? a[h][i] * (0.23570226039551584f * LOG2E) : -1.0e9f * LOG2E;
          m[h][0] = fmaxf(a[h][0], a[h][1]); m[h][1] = fmaxf(a[h][2], a[h][3]);
        }
#pragma unroll
        for (int x = 1; x < 4; x <<= 1)
#pragma unroll
          for (int i = 0; i < 8; i++) m[i >> 1][i & 1] = fmaxf(m[i >> 1][i & 1], __shfl_xor_sync(0xffffffffu, m[i >> 1][i & 1], x));
#pragma unroll
        for (int h = 0; h < 4; h++) {
#pragma unroll
          for (int i = 0; i < 4; i++) a[h][i] = ex2(a[h][i] - m[h][i >> 1]);
          m[h][0] = a[h][0] + a[h][1]; m[h][1] = a[h][2] + a[h][3];
        }
#pragma unroll
        for (int x = 1; x < 4; x <<= 1)
#pragma unroll
          for (int i = 0; i < 8; i++) m[i >> 1][i & 1] += __shfl_xor_sync(0xffffffffu, m[i >> 1][i & 1], x);
        uint32_t o[9][2];
#pragma unroll
        for (int h = 0; h < 4; h++) {
          const int j = 2 * h;
          const float z0 = gl * rcp(m[h][0]), z1 = gh * rcp(m[h][1]);
          const uint32_t pl = pack_bf16(a[h][0] * z0, a[h][1] * z0), pu = pack_bf16(a[h][2] * z1, a[h][3] * z1);
          const uint32_t pa[4] = {pl & prev, 0, pl & ~prev, pu & prev};
          float d[3][4];
#pragma unroll
          for (int i = 0; i < 3; i++) mma16816z(d[i], pa, pv[j + i][1], f[2][j + i][0]);
#pragma unroll
          for (int i = 0; i < 3; i++) mma1688(d[i], 0, pu & ~prev, f[2][j + i][1]);
#pragma unroll
          for (int i = 0; i < 3; i++) {
            const uint32_t d0 = pack_bf16(d[i][0], d[i][1]), d1 = pack_bf16(d[i][2], d[i][3]);
            o[j + i][0] = i == 0 && h > 0 && t < h ? o[j][0] : d0;
            o[j + i][1] = i == 0 && h > 0 && t < h ? o[j][1] : d1;
          }
        }
        ASTAMP(28 + max(p, 0) + wg * 16);
        bar_sync(1 + wg, 128);
        const uint32_t oa = slot + (lane & 15) * 144 + (lane >> 4) * 16;
#pragma unroll
        for (int j = 0; j < 8; j += 2) stsm4(oa + j * 16, o[j][0], o[j][1], o[j + 1][0], o[j + 1][1]);
        asm volatile("stmatrix.sync.aligned.m8n8.x2.shared.b16 [%0], {%1,%2};" :: "r"(oa + 128), "r"(o[8][0]), "r"(o[8][1]) : "memory");
        fence_async();
        __syncwarp();
        if (QM & 64) quiet_wait(pace);
        if (lane < 16 && w * 16 + lane >= 7 && r0 + lane < S_LEN / 2 && p >= 0)
          asm volatile("cp.async.bulk.global.shared::cta.bulk_group [%0], [%1], 144;"
                       :: "l"(g_Ocat + (size_t)((r0 + lane) * 2 + wg) * KCAT + 4096 + (cta & 1) * (DM / 2) + p * 72), "r"(slot + lane * 144) : "memory");
        asm volatile("cp.async.bulk.commit_group;" ::: "memory");
        ASTAMP(20 + max(p, 0) + wg * 16);
      }
      if (XP & 256) bar_sync(8, 288);
      asm volatile("cp.async.bulk.wait_group 0;" ::: "memory");
    }
    ASTAMP(3);
    bar_arrive(6, 288);
    uint32_t wa[36][4];
    mbar_wait(fullw, 0);
    const uint32_t la = sb + ((lane & 7) + ((lane >> 4) << 3)) * 128 + (((2 * w + ((lane >> 3) & 1)) ^ (lane & 7)) << 4);
#pragma unroll
    for (int k = 0; k < 32; k++) ldsm4t(wa[k], la + wg * 65536 + k * 2048);
    mbar_wait(fullw + 8, 0);
#pragma unroll
    for (int k = 32; k < 36; k++) ldsm4t(wa[k], la + wg * 8192 + 65536 + k * 2048);
    fence_async();
    if (XP & 2048) bar_sync(6, 288); else bar_arrive(6, 288);
    ASTAMP(4);
    const int ks = p3_ks(wg), mt = p3_mt(wg);
    uint32_t v[16];
    auto fetch = [&](int seg) { ldg8x64<1024>(v, g_part + (((seg & 7) * 9 + mt) * 4 + (ks & 3)) * 1024 + (tid & 127)); };
    auto finish = [&](int seg) {
      const uint32_t tagv = (~seg >> 3) & 1;
      int n = 0;
#pragma unroll 1
      while (stale<8, 2>(v, tagv) && ++n < SPIN_LIMIT) {
        if (seg < NSEG - 2) __nanosleep(100);
        fetch(seg);
      }
      float own[4] = {bf_lo(v[0]), bf_hi(v[0]), bf_lo(v[1]), bf_hi(v[1])};
#pragma unroll
      for (int j = 1; j < 8; j++) { own[0] += bf_lo(v[2 * j]); own[1] += bf_hi(v[2 * j]); own[2] += bf_lo(v[2 * j + 1]); own[3] += bf_hi(v[2 * j + 1]); }
      uint32_t p0 = pack_bf16(own[0], own[1]), p1 = pack_bf16(own[2], own[3]);
      asm volatile("movmatrix.sync.aligned.m8n8.trans.b16 %0, %0;" : "+r"(p0));
      asm volatile("movmatrix.sync.aligned.m8n8.trans.b16 %0, %0;" : "+r"(p1));
      uint32_t* o = (uint32_t*)(out + (size_t)(seg * 32 + (ks & 3) * 8 + (lane >> 2)) * DM + mt * 64 + w * 16) + (lane & 3);
      o[0] = p0; o[4] = p1;
      SSTAMP(seg, 7);
    };
    float acc[16];
#pragma unroll
    for (int i = 0; i < 16; i++) acc[i] = 0.f;
    int pend = -1, sl = wide ? 0 : wg, ph = 0;
    if (PING && wg) bar_arrive(1, 256);
    CDECL;
    auto run = [&](auto extra) {
#pragma unroll 1
    for (int seg = 0; seg < ((XP & 2048) ? 0 : NSEG); seg++) {
      CSTAMP(0);
      const bool fin = pend >= 0 && seg - pend >= FLAG;
      if (FPOS == 0 && fin) fetch(pend);
      mbar_wait(full3 + 8 * sl, ph);
      if (FPOS == 1 && fin) fetch(pend);
      CSTAMP(1);
      if (wg) SSTAMP(seg, 5);
      if (PING) bar_sync(1 + wg, 256);
      CSTAMP(7);
      const uint64_t db = make_desc(sb + sl * XT, 16, 1024, 1);
      WG_FENCE();
#pragma unroll
      for (int k = 0; k < ((XP & 1024) ? 1 : 36); k++) wgmma_n32_rs(acc, wa[k][0], wa[k][1], wa[k][2], wa[k][3], db + (k >> 2) * 256 + (k & 3) * 2, k);
      if (decltype(extra)::value) {
        const uint64_t da = make_desc(xw + wg * 8192, 8192, 1024, 1), de = make_desc(xt + sl * 4096, 16, 1024, 1);
#pragma unroll
        for (int j = 0; j < 4; j++) wgmma_n32_ss_tn(acc, da + j * 128, de + j * 2);
      }
      WG_COMMIT();
      if (PING) bar_arrive(2 - wg, 256);
      CSTAMP(2);
      if (FPOS == 2 && fin) fetch(pend);
      CSTAMP(3);
      WG_WAIT(0);
      CSTAMP(4);
      if (wg) SSTAMP(seg, 6);
      if (lane == 0) mbar_arrive(empty3 + 8 * sl);
      sl += wide ? 1 : 2;
      if (sl >= (wide ? 3 : 4)) { sl -= wide ? 3 : 4; ph ^= 1; }
      uint2* dst = g_part + (((seg & 7) * 9 + mt) * 32 + ks) * 128 + (tid & 127);
      uint32_t q[8];
#pragma unroll
      for (int j = 0; j < 8; j++) q[j] = j & 1 ? pack_bf16(acc[2 * j], acc[2 * j + 1]) : (pack_bf16(acc[2 * j], acc[2 * j + 1]) & ~1u) | ((~seg >> 3) & 1);
      if (QM & 32) tick_wait(pace, seg + (QM >> 4 & 1) + 2);
      if (!(YP & 1) || q[0] == 0x12345678)
      asm volatile("st.relaxed.gpu.global.v2.b32 [%0], {%1,%2};\nst.relaxed.gpu.global.v2.b32 [%0 + 8192], {%3,%4};\n"
                   "st.relaxed.gpu.global.v2.b32 [%0 + 16384], {%5,%6};\nst.relaxed.gpu.global.v2.b32 [%0 + 24576], {%7,%8};"
                   :: "l"(dst), "r"(q[0]), "r"(q[1]), "r"(q[2]), "r"(q[3]), "r"(q[4]), "r"(q[5]), "r"(q[6]), "r"(q[7]) : "memory");
      CSTAMP(5);
      if (fin) { finish(pend); pend = -1; }
      CSTAMP(6);
      if ((seg & 1) == ks >> 2 && !(YP & 1)) pend = seg;
      if (wg && (seg & 7) == 6) ASTAMP(5 + (seg >> 3));
    }
    };
    if (ks == 7) run(BoolC<true>()); else run(BoolC<false>());
    if (PING && !wg) bar_sync(1, 256);
    if (pend >= 0) { fetch(pend); finish(pend); }
    CDUMP;
    ASTAMP(13);
    bar_sync(6, 288);
  }
}

typedef CUresult (*EncodeFn)(CUtensorMap*, CUtensorMapDataType, cuuint32_t, void*, const cuuint64_t*, const cuuint64_t*,
                             const cuuint32_t*, const cuuint32_t*, CUtensorMapInterleave, CUtensorMapSwizzle,
                             CUtensorMapL2promotion, CUtensorMapFloatOOBfill);
#define PROMO 2
static void make_map(EncodeFn enc, CUtensorMap* m, const void* p, int rows, int cols, int box_rows) {
  cuuint64_t dims[2] = {(cuuint64_t)cols, (cuuint64_t)rows};
  cuuint64_t strides[1] = {(cuuint64_t)cols * 2};
  cuuint32_t box[2] = {64, (cuuint32_t)box_rows};
  cuuint32_t es[2] = {1, 1};
  enc(m, CU_TENSOR_MAP_DATA_TYPE_BFLOAT16, 2, (void*)p, dims, strides, box, es, CU_TENSOR_MAP_INTERLEAVE_NONE,
      CU_TENSOR_MAP_SWIZZLE_128B, (CUtensorMapL2promotion)PROMO, CU_TENSOR_MAP_FLOAT_OOB_FILL_NONE);
}

constexpr int g_poll = POLL_NS;
extern "C" void kernel_launch(void* const* d_in, const int* in_sizes, int n_in, void* d_out, int out_size) {
  const bf16* x = (const bf16*)d_in[0];
  const bf16* wqkvA = (const bf16*)d_in[1];
  const bf16* woA = (const bf16*)d_in[2];
  const bf16* mem0 = (const bf16*)d_in[4];
  const bf16* Wq = (const bf16*)d_in[5];
  const bf16* Wk = (const bf16*)d_in[6];
  const bf16* Wv = (const bf16*)d_in[7];
  const bf16* Wo = (const bf16*)d_in[8];
  const bf16* gate_w = (const bf16*)d_in[10];
  static EncodeFn enc = nullptr;
  static void *pO = nullptr, *pR = nullptr;
  if (!enc) {
    cudaDriverEntryPointQueryResult qr;
    cudaGetDriverEntryPoint("cuTensorMapEncodeTiled", (void**)&enc, cudaEnableDefault, &qr);
    cudaGetSymbolAddress(&pO, g_Ocat);
    cudaGetSymbolAddress(&pR, g_red_raw);
    cudaFuncSetAttribute(rec_kernel, cudaFuncAttributeMaxDynamicSharedMemorySize, SM_TOTAL);
    cudaFuncSetAttribute(aux_kernel, cudaFuncAttributeMaxDynamicSharedMemorySize, A_TOTAL);
  }
  RMaps rm;
  rm.poll = g_poll;
  rm.w[0] = (const unsigned char*)Wk; rm.w[1] = (const unsigned char*)Wq; rm.w[2] = (const unsigned char*)Wv; rm.w[3] = (const unsigned char*)Wo;
  rm.red = (unsigned char*)(((uintptr_t)pR + 262143) & ~(uintptr_t)262143);
  {
    cuuint64_t dims[3] = {64, S_LEN, 9}, strides[2] = {DM * 2, 128};
    cuuint32_t box[3] = {64, 32, 9}, es[3] = {1, 1, 1};
    enc(&rm.x, CU_TENSOR_MAP_DATA_TYPE_BFLOAT16, 3, (void*)x, dims, strides, box, es, CU_TENSOR_MAP_INTERLEAVE_NONE,
        CU_TENSOR_MAP_SWIZZLE_128B, CU_TENSOR_MAP_L2_PROMOTION_L2_128B, CU_TENSOR_MAP_FLOAT_OOB_FILL_NONE);
  }
  make_map(enc, &rm.wq, Wq, DM, 4096, 192);
  make_map(enc, &rm.wk, Wk, DM, 4096, 192);
  make_map(enc, &rm.wv, Wv, DM, 4096, 192);
  make_map(enc, &rm.wo, Wo, 4096, DM, 128);
  AMaps am;
  am.red = rm.red; am.poll = rm.poll;
  {
    cuuint64_t dims[3] = {DM, S_LEN / 2, 2}, strides[2] = {DM * 4, DM * 2};
    cuuint32_t box[3] = {32, 64, 2}, es[3] = {1, 1, 1};
    enc(&am.x, CU_TENSOR_MAP_DATA_TYPE_BFLOAT16, 3, (void*)x, dims, strides, box, es, CU_TENSOR_MAP_INTERLEAVE_NONE,
        CU_TENSOR_MAP_SWIZZLE_64B, CU_TENSOR_MAP_L2_PROMOTION_L2_128B, CU_TENSOR_MAP_FLOAT_OOB_FILL_NONE);
    cuuint64_t wdims[3] = {DM, DM, 3}, wstrides[2] = {DM * 6, DM * 2};
    cuuint32_t wbox[3] = {64, 32, 3}, wbox8[3] = {8, 32, 3};
    enc(&am.wa, CU_TENSOR_MAP_DATA_TYPE_BFLOAT16, 3, (void*)wqkvA, wdims, wstrides, wbox, es, CU_TENSOR_MAP_INTERLEAVE_NONE,
        CU_TENSOR_MAP_SWIZZLE_128B, CU_TENSOR_MAP_L2_PROMOTION_L2_128B, CU_TENSOR_MAP_FLOAT_OOB_FILL_NONE);
    enc(&am.wa8, CU_TENSOR_MAP_DATA_TYPE_BFLOAT16, 3, (void*)wqkvA, wdims, wstrides, wbox8, es, CU_TENSOR_MAP_INTERLEAVE_NONE,
        CU_TENSOR_MAP_SWIZZLE_NONE, CU_TENSOR_MAP_L2_PROMOTION_NONE, CU_TENSOR_MAP_FLOAT_OOB_FILL_NONE);
  }
  {
    cuuint64_t dims[3] = {64, S_LEN, KCAT / 64}, strides[2] = {KCAT * 2, 128};
    cuuint32_t box[3] = {64, 32, 9}, es[3] = {1, 1, 1};
    make_map(enc, &am.o, pO, S_LEN, KCAT, 32);
    enc(&am.o3, CU_TENSOR_MAP_DATA_TYPE_BFLOAT16, 3, pO, dims, strides, box, es, CU_TENSOR_MAP_INTERLEAVE_NONE,
        CU_TENSOR_MAP_SWIZZLE_128B, CU_TENSOR_MAP_L2_PROMOTION_L2_128B, CU_TENSOR_MAP_FLOAT_OOB_FILL_NONE);
  }
  make_map(enc, &am.wob, Wo, 4096, DM, 64);
  make_map(enc, &am.woa, woA, DM, DM, 64);

  rec_kernel<<<96, 384, SM_TOTAL, cudaStreamPerThread>>>(rm, x, mem0);
  cudaLaunchConfig_t cfg = {};
  cfg.gridDim = dim3(NAUX); cfg.blockDim = dim3(512); cfg.dynamicSmemBytes = A_TOTAL; cfg.stream = cudaStreamPerThread;
  cudaLaunchAttribute at[1];
  at[0].id = cudaLaunchAttributeProgrammaticStreamSerialization; at[0].val.programmaticStreamSerializationAllowed = 1;
  cfg.attrs = at; cfg.numAttrs = 1;
  if (XP & 16) cfg.numAttrs = 0;
  if (!(XP & 64)) cudaLaunchKernelEx(&cfg, aux_kernel, am, x, gate_w, (bf16*)d_out);
}
```

```cpp
#include <cuda_runtime.h>
#include <cuda_bf16.h>
#include <cuda_fp16.h>
#include <cuda.h>
#include <stdint.h>

typedef __nv_bfloat16 bf16;

constexpr int S_LEN = 2048, DM = 576, NH = 32, DH = 128, NSEG = 64, KCAT = 4096 + 576;
#define RED_LINE(i) (((i) >> 2) * 4096 + ((i) & 1) * 256 + ((i) & 2) * 512)
#define RED_SLOT(s) (((s) & 1) * 128 + ((s) & 2) * 256)

#define POLL_NS 832
#define NII 18
#define W3PRE 4
#define W3MID 4
#define GF 0
#define B5POS 0
#define NUP 4
#define UPF 1
#define B3Q 9
#define B3F 0
#define GATE 7
#define NTL 2
#define B7R 1
#define EXPOS 0
#define VW2 1
#define CLR 1
#define RFW 0
#define NIC 0
#define LEAD 0
#define FIN16 1
#define VXG 0
#define RING 63
#define EXB 0
#define EXD 0
#define EXB2 8192
#define HDLY 0
#define F10 1
#define NPROBE 2
#define NPROBE2 5
#define WPOS 2
#define WARM 0
#define YP 0
#define EF 7
#define KME 0
#define EXV 2
#define NOB 0
#define QM 60
#define N5 224
#define KP(i) (((i) >> 1) + 4 * ((i) & 1))
#define SPIN_LIMIT (1 << 14)
#define XP 0

__device__ __align__(1024) bf16 g_Ocat[S_LEN * KCAT];
__device__ __align__(1024) unsigned char g_red_raw[2 * 262144];
constexpr int HINT_OFF = 2048;
__device__ __align__(16) float g_gate[S_LEN];
__device__ __align__(128) uint4 g_stats[96 * 2];
__device__ unsigned g_epoch;
__device__ unsigned g_epoch2;
__device__ unsigned g_oflag[NH * 32];
__device__ unsigned g_abar[3 * 32];
__device__ unsigned g_sflag[96 * 8];
__device__ __align__(1024) unsigned char g_seg[NSEG * 96 * 8192];
__device__ __align__(1024) unsigned char g_km[NSEG * NH * 4096];
__device__ __align__(1024) uint2 g_part[8 * 9 * 4 * 8 * 128];
__device__ int g_err;
#define SSTAMP(seg, idx)
#define TSTAMP(idx)
#define QSTAMP(idx)
#define PROF(idx)
#define PROFP(idx)
#define STAMP(idx)
#define ASTAMP(idx)
#define WSTAMP(idx)

#define CSTAMP(idx)
#define CDECL
#define CDUMP
#define DI __device__ __forceinline__
DI uint32_t smem_u32(const void* p) { return (uint32_t)__cvta_generic_to_shared(p); }
DI uint32_t clock32() { uint32_t c; asm volatile("mov.u32 %0, %%clock;" : "=r"(c) :: "memory"); return c; }
DI uint32_t gtime() { uint32_t c; asm volatile("mov.u32 %0, %%globaltimer_lo;" : "=r"(c) :: "memory"); return c; }
DI uint32_t ldg_relaxed32(const void* p) { uint32_t v; asm volatile("ld.relaxed.gpu.global.b32 %0, [%1];" : "=r"(v) : "l"(p) : "memory"); return v; }
DI uint32_t ldg_acquire32(const void* p) { uint32_t v; asm volatile("ld.acquire.gpu.global.b32 %0, [%1];" : "=r"(v) : "l"(p) : "memory"); return v; }
DI void stg_relaxed32(void* p, uint32_t v) { asm volatile("st.relaxed.gpu.global.b32 [%0], %1;" :: "l"(p), "r"(v) : "memory"); }
DI int head_id() { int c; asm volatile("mov.u32 %0, %%clusterid.x;" : "=r"(c)); return c; }
DI uint32_t mapa(uint32_t a, uint32_t r) { uint32_t o; asm("mapa.shared::cluster.u32 %0, %1, %2;" : "=r"(o) : "r"(a), "r"(r)); return o; }
DI void cluster_arrive() { asm volatile("barrier.cluster.arrive.relaxed.aligned;" ::: "memory"); }
DI void cluster_wait() { asm volatile("barrier.cluster.wait.aligned;" ::: "memory"); }
DI void cluster_sync() { asm volatile("barrier.cluster.arrive.release.aligned;\nbarrier.cluster.wait.acquire.aligned;" ::: "memory"); }
DI void mbar_init(uint32_t b, uint32_t c) { asm volatile("mbarrier.init.shared::cta.b64 [%0], %1;" :: "r"(b), "r"(c) : "memory"); }
DI void mbar_expect(uint32_t b, uint32_t tx) { asm volatile("mbarrier.arrive.expect_tx.shared::cta.b64 _, [%0], %1;" :: "r"(b), "r"(tx) : "memory"); }
DI void mbar_arrive(uint32_t b) { asm volatile("mbarrier.arrive.shared::cta.b64 _, [%0];" :: "r"(b) : "memory"); }
DI void mbar_wait(uint32_t b, uint32_t par) {
  asm volatile("{\n.reg .pred p;\n.reg .u32 n, q;\nmov.u32 n, 0;\n"
               "WL: add.u32 n, n, 1;\nshr.u32 q, n, 12;\nxor.b32 q, q, %1;\n"
               "mbarrier.try_wait.parity.shared::cta.b64 p, [%0], q;\n@!p bra.uni WL;\n}"
               :: "r"(b), "r"(par) : "memory");
}
DI void wait_until(uint32_t t) {
  const uint32_t now = gtime();
  t = min(t, now + 8192);
  asm volatile("{\n.reg .pred p;\n.reg .u32 c;\nTL: mov.u32 c, %%globaltimer_lo;\nsetp.lt.u32 p, c, %0;\n@p bra.uni TL;\n}" :: "r"(t) : "memory");
}
#define PIN(v) v = __shfl_xor_sync(0xffffffffu, v, 0)
#define SCHED_FENCE(k) asm volatile("{\n.reg .pred p;\nsetp.eq.u32 p, %0, %1;\n@p exit;\n}" :: "r"(fence_reg), "r"(k) : "memory")
#define MEM_ORDER(k) asm volatile("{\n.reg .pred p;\nsetp.eq.u32 p, %0, %1;\n@p st.shared.u32 [%0], %0;\n}" :: "r"(fence_reg), "r"(k + 64) : "memory")
DI void bar_sync(int id, int n) { asm volatile("bar.sync %0, %1;" :: "r"(id), "r"(n) : "memory"); }
DI void bar_arrive(int id, int n) { asm volatile("bar.arrive %0, %1;" :: "r"(id), "r"(n) : "memory"); }
DI void fence_async() { asm volatile("fence.proxy.async.shared::cta;" ::: "memory"); }
DI void st_async4(uint32_t a, uint32_t x, uint32_t y, uint32_t z, uint32_t w, uint32_t mb) {
  asm volatile("st.async.weak.shared::cluster.mbarrier::complete_tx::bytes.v4.b32 [%0], {%1,%2,%3,%4}, [%5];"
               :: "r"(a), "r"(x), "r"(y), "r"(z), "r"(w), "r"(mb) : "memory");
}
DI void st_async2(uint32_t a, uint32_t x, uint32_t y, uint32_t mb) {
  asm volatile("st.async.weak.shared::cluster.mbarrier::complete_tx::bytes.v2.b32 [%0], {%1,%2}, [%3];"
               :: "r"(a), "r"(x), "r"(y), "r"(mb) : "memory");
}
DI void sts32(uint32_t a, uint32_t x) { asm volatile("st.shared.b32 [%0], %1;" :: "r"(a), "r"(x) : "memory"); }
DI void sts64(uint32_t a, uint32_t x, uint32_t y) { asm volatile("st.shared.v2.b32 [%0], {%1,%2};" :: "r"(a), "r"(x), "r"(y) : "memory"); }
DI void sts128(uint32_t a, uint32_t x, uint32_t y, uint32_t z, uint32_t w) {
  asm volatile("st.shared.v4.b32 [%0], {%1,%2,%3,%4};" :: "r"(a), "r"(x), "r"(y), "r"(z), "r"(w) : "memory");
}
DI uint32_t lds32(uint32_t a) { uint32_t x; asm volatile("ld.shared.b32 %0, [%1];" : "=r"(x) : "r"(a) : "memory"); return x; }
DI void lds64(uint32_t a, uint32_t& x, uint32_t& y) { asm volatile("ld.shared.v2.b32 {%0,%1}, [%2];" : "=r"(x), "=r"(y) : "r"(a) : "memory"); }
DI void lds128(uint32_t a, uint32_t* r) {
  asm volatile("ld.shared.v4.b32 {%0,%1,%2,%3}, [%4];" : "=r"(r[0]), "=r"(r[1]), "=r"(r[2]), "=r"(r[3]) : "r"(a) : "memory");
}
DI void lds128f(uint32_t a, float* r) {
  asm volatile("ld.shared.v4.f32 {%0,%1,%2,%3}, [%4];" : "=f"(r[0]), "=f"(r[1]), "=f"(r[2]), "=f"(r[3]) : "r"(a) : "memory");
}
DI void lds64f(uint32_t a, float* r) { asm volatile("ld.shared.v2.f32 {%0,%1}, [%2];" : "=f"(r[0]), "=f"(r[1]) : "r"(a) : "memory"); }
DI void ldsm4t(uint32_t* r, uint32_t a) {
  asm volatile("ldmatrix.sync.aligned.m8n8.x4.trans.shared.b16 {%0,%1,%2,%3}, [%4];"
               : "=r"(r[0]), "=r"(r[1]), "=r"(r[2]), "=r"(r[3]) : "r"(a) : "memory");
}
DI void ldsm4t_in(uint32_t* r, uint32_t a, uint32_t t) {
  asm volatile("{\n.reg .pred p;\nsetp.ne.u32 p, %5, 0;\n@p ldmatrix.sync.aligned.m8n8.x4.trans.shared.b16 {%0,%1,%2,%3}, [%4];\n}"
               : "+r"(r[0]), "+r"(r[1]), "+r"(r[2]), "+r"(r[3]) : "r"(a), "r"(t) : "memory");
}
DI void lds128_in(uint32_t* r, uint32_t a, uint32_t t) {
  asm volatile("{\n.reg .pred p;\nsetp.ne.u32 p, %5, 0;\n@p ld.shared.v4.b32 {%0,%1,%2,%3}, [%4];\n}"
               : "+r"(r[0]), "+r"(r[1]), "+r"(r[2]), "+r"(r[3]) : "r"(a), "r"(t) : "memory");
}
DI void ldsm2t_in(uint32_t* r, uint32_t a, uint32_t t) {
  asm volatile("{\n.reg .pred p;\nsetp.ne.u32 p, %3, 0;\n@p ldmatrix.sync.aligned.m8n8.x2.trans.shared.b16 {%0,%1}, [%2];\n}" : "+r"(r[0]), "+r"(r[1]) : "r"(a), "r"(t) : "memory");
}
DI void reserve2(uint32_t* r) { asm volatile("{\n.reg .u64 t;\nmov.u64 t, %%clock64;\nmov.b64 {%0, %1}, t;\n}" : "=r"(r[0]), "=r"(r[1])); }
DI void scale_sum(float& x, float& y, float s, uint32_t t) {
  asm volatile("{\n.reg .pred p;\nsetp.ne.u32 p, %2, 0;\n@p mul.f32 %0, %0, %1;\n}" : "+f"(y) : "f"(s), "r"(t));
  asm volatile("{\n.reg .pred p;\nsetp.ne.u32 p, %3, 1;\n@p fma.rn.f32 %0, %0, %1, %2;\n}" : "+f"(x) : "f"(s), "f"(y), "r"(t));
}
DI void ldsm4(uint32_t* r, uint32_t a) {
  asm volatile("ldmatrix.sync.aligned.m8n8.x4.shared.b16 {%0,%1,%2,%3}, [%4];"
               : "=r"(r[0]), "=r"(r[1]), "=r"(r[2]), "=r"(r[3]) : "r"(a) : "memory");
}
DI void st_async1(uint32_t a, uint32_t x, uint32_t mb) {
  asm volatile("st.async.weak.shared::cluster.mbarrier::complete_tx::bytes.b32 [%0], %1, [%2];" :: "r"(a), "r"(x), "r"(mb) : "memory");
}
DI void stsm4(uint32_t a, uint32_t x, uint32_t y, uint32_t z, uint32_t w) {
  asm volatile("stmatrix.sync.aligned.m8n8.x4.shared.b16 [%0], {%1,%2,%3,%4};" :: "r"(a), "r"(x), "r"(y), "r"(z), "r"(w) : "memory");
}
DI void stsm4t(uint32_t a, uint32_t x, uint32_t y, uint32_t z, uint32_t w) {
  asm volatile("stmatrix.sync.aligned.m8n8.x4.trans.shared.b16 [%0], {%1,%2,%3,%4};" :: "r"(a), "r"(x), "r"(y), "r"(z), "r"(w) : "memory");
}
DI uint32_t pack_bf16(float lo, float hi) { uint32_t r; asm("cvt.rn.bf16x2.f32 %0, %1, %2;" : "=r"(r) : "f"(hi), "f"(lo)); return r; }
DI uint32_t pack_f16(float lo, float hi) { uint32_t r; asm("cvt.rn.f16x2.f32 %0, %1, %2;" : "=r"(r) : "f"(hi), "f"(lo)); return r; }
DI float ex2(float x) { float y; asm("ex2.approx.ftz.f32 %0, %1;" : "=f"(y) : "f"(x)); return y; }
DI float rcp(float x) { float y; asm("rcp.approx.ftz.f32 %0, %1;" : "=f"(y) : "f"(x)); return y; }
DI float bf_lo(uint32_t x) { return __uint_as_float(x << 16); }
DI float bf_hi(uint32_t x) { return __uint_as_float(x & 0xffff0000u); }
DI void mma16816(float* d, const uint32_t* a, uint32_t b0, uint32_t b1) {
  asm volatile("mma.sync.aligned.m16n8k16.row.col.f32.bf16.bf16.f32 {%0,%1,%2,%3}, {%4,%5,%6,%7}, {%8,%9}, {%0,%1,%2,%3};"
               : "+f"(d[0]), "+f"(d[1]), "+f"(d[2]), "+f"(d[3]) : "r"(a[0]), "r"(a[1]), "r"(a[2]), "r"(a[3]), "r"(b0), "r"(b1));
}
DI void mma16816z(float* d, const uint32_t* a, uint32_t b0, uint32_t b1) {
  asm volatile("mma.sync.aligned.m16n8k16.row.col.f32.bf16.bf16.f32 {%0,%1,%2,%3}, {%4,%5,%6,%7}, {%8,%9}, {%10,%10,%10,%10};"
               : "=f"(d[0]), "=f"(d[1]), "=f"(d[2]), "=f"(d[3]) : "r"(a[0]), "r"(a[1]), "r"(a[2]), "r"(a[3]), "r"(b0), "r"(b1), "f"(0.f));
}
DI void mma1688z(float* d, uint32_t a0, uint32_t a1, uint32_t b0) {
  asm volatile("mma.sync.aligned.m16n8k8.row.col.f32.bf16.bf16.f32 {%0,%1,%2,%3}, {%4,%5}, {%6}, {%7,%7,%7,%7};"
               : "=f"(d[0]), "=f"(d[1]), "=f"(d[2]), "=f"(d[3]) : "r"(a0), "r"(a1), "r"(b0), "f"(0.f));
}
DI void mma1688(float* d, uint32_t a0, uint32_t a1, uint32_t b0) {
  asm volatile("mma.sync.aligned.m16n8k8.row.col.f32.bf16.bf16.f32 {%0,%1,%2,%3}, {%4,%5}, {%6}, {%0,%1,%2,%3};"
               : "+f"(d[0]), "+f"(d[1]), "+f"(d[2]), "+f"(d[3]) : "r"(a0), "r"(a1), "r"(b0));
}
DI void ldsm2t(uint32_t* r, uint32_t a) {
  asm volatile("ldmatrix.sync.aligned.m8n8.x2.trans.shared.b16 {%0,%1}, [%2];" : "=r"(r[0]), "=r"(r[1]) : "r"(a) : "memory");
}
DI uint32_t add_bf16(uint32_t a, uint32_t b) { uint32_t r; asm("add.rn.bf16x2 %0, %1, %2;" : "=r"(r) : "r"(a), "r"(b)); return r; }
DI uint32_t mul_bf16(uint32_t a, uint32_t b) { uint32_t r; asm("mul.rn.bf16x2 %0, %1, %2;" : "=r"(r) : "r"(a), "r"(b)); return r; }
DI uint64_t make_desc(uint32_t addr, uint32_t lbo, uint32_t sbo, uint32_t swz) {
  return (uint64_t)((addr & 0x3FFFF) >> 4) | ((uint64_t)(lbo >> 4) << 16) | ((uint64_t)(sbo >> 4) << 32) | ((uint64_t)swz << 62);
}
#define WG_FENCE() asm volatile("wgmma.fence.sync.aligned;" ::: "memory")
#define WG_COMMIT() asm volatile("wgmma.commit_group.sync.aligned;" ::: "memory")
#define WG_WAIT(n) asm volatile("wgmma.wait_group.sync.aligned %0;" :: "n"(n) : "memory")
#define ACC8(d, o) "+f"(d[o]), "+f"(d[o + 1]), "+f"(d[o + 2]), "+f"(d[o + 3]), "+f"(d[o + 4]), "+f"(d[o + 5]), "+f"(d[o + 6]), "+f"(d[o + 7])
DI void wgmma_n32_rs(float* d, uint32_t a0, uint32_t a1, uint32_t a2, uint32_t a3, uint64_t db, int acc) {
  asm volatile("{\n.reg .pred p;\nsetp.ne.b32 p, %21, 0;\n"
               "wgmma.mma_async.sync.aligned.m64n32k16.f32.bf16.bf16 {%0,%1,%2,%3,%4,%5,%6,%7,%8,%9,%10,%11,%12,%13,%14,%15}, "
               "{%16,%17,%18,%19}, %20, p, 1, 1, 0;\n}\n"
               : ACC8(d, 0), ACC8(d, 8) : "r"(a0), "r"(a1), "r"(a2), "r"(a3), "l"(db), "r"(acc));
}
template <int TA>
DI void wgmma_n32_ss(float* d, uint64_t da, uint64_t db, int acc) {
  asm volatile("{\n.reg .pred p;\nsetp.ne.b32 p, %18, 0;\n"
               "wgmma.mma_async.sync.aligned.m64n32k16.f32.bf16.bf16 {%0,%1,%2,%3,%4,%5,%6,%7,%8,%9,%10,%11,%12,%13,%14,%15}, "
               "%16, %17, p, 1, 1, %19, 1;\n}\n"
               : ACC8(d, 0), ACC8(d, 8) : "l"(da), "l"(db), "r"(acc), "n"(TA));
}
DI void tma_load(uint32_t dst, const CUtensorMap* m, int c0, int c1, uint32_t mb) {
  asm volatile("cp.async.bulk.tensor.2d.shared::cluster.global.mbarrier::complete_tx::bytes [%0], [%1, {%3, %4}], [%2];"
               :: "r"(dst), "l"(m), "r"(mb), "r"(c0), "r"(c1) : "memory");
}
DI void tma_load3(uint32_t dst, const CUtensorMap* m, int row, uint32_t mb) {
  asm volatile("cp.async.bulk.tensor.3d.shared::cluster.global.mbarrier::complete_tx::bytes [%0], [%1, {%3, %4, %3}], [%2];"
               :: "r"(dst), "l"(m), "r"(mb), "r"(0), "r"(row) : "memory");
}
DI bool elect_one() {
  uint32_t p;
  asm volatile("{\n.reg .pred p;\nelect.sync _|p, 0xffffffff;\nselp.u32 %0, 1, 0, p;\n}" : "=r"(p));
  return p;
}
DI void bulk_s2s(uint32_t dst, uint32_t src, uint32_t bytes, uint32_t mb) {
  asm volatile("cp.async.bulk.shared::cluster.shared::cta.mbarrier::complete_tx::bytes [%0], [%1], %2, [%3];"
               :: "r"(dst), "r"(src), "r"(bytes), "r"(mb) : "memory");
}
DI void bulk_load(uint32_t dst, const void* src, uint32_t bytes, uint32_t mb) {
  asm volatile("cp.async.bulk.shared::cluster.global.mbarrier::complete_tx::bytes [%0], [%1], %2, [%3];" :: "r"(dst), "l"(src), "r"(bytes), "r"(mb) : "memory");
}
#define EVICT_FIRST ".reg .b64 pol;\ncreatepolicy.fractional.L2::evict_first.b64 pol, 1.0;\n"
DI void bulk_load_ef(uint32_t dst, const void* src, uint32_t bytes, uint32_t mb) {
  asm volatile("{\n" EVICT_FIRST "cp.async.bulk.shared::cluster.global.mbarrier::complete_tx::bytes.L2::cache_hint [%0], [%1], %2, [%3], pol;\n}"
               :: "r"(dst), "l"(src), "r"(bytes), "r"(mb) : "memory");
}
DI void tma_load_ef(uint32_t dst, const CUtensorMap* m, int c0, int c1, uint32_t mb) {
  asm volatile("{\n" EVICT_FIRST "cp.async.bulk.tensor.2d.shared::cluster.global.mbarrier::complete_tx::bytes.L2::cache_hint [%0], [%1, {%3, %4}], [%2], pol;\n}"
               :: "r"(dst), "l"(m), "r"(mb), "r"(c0), "r"(c1) : "memory");
}
DI void tma_prefetch(const CUtensorMap* m, int c0, int c1) {
  asm volatile("cp.async.bulk.prefetch.tensor.2d.L2.global.tile [%0, {%1, %2}];" :: "l"(m), "r"(c0), "r"(c1) : "memory");
}
DI void tma_store(const CUtensorMap* m, uint32_t src, int c0, int c1) {
  asm volatile("cp.async.bulk.tensor.2d.global.shared::cta.bulk_group [%0, {%2, %3}], [%1];" :: "l"(m), "r"(src), "r"(c0), "r"(c1) : "memory");
}
DI uint4 ldg_relaxed(const void* p) {
  uint4 v;
  asm volatile("ld.relaxed.gpu.global.v4.b32 {%0,%1,%2,%3}, [%4];" : "=r"(v.x), "=r"(v.y), "=r"(v.z), "=r"(v.w) : "l"(p) : "memory");
  return v;
}
DI void stg_relaxed(void* p, uint32_t x, uint32_t y, uint32_t z, uint32_t w) {
  asm volatile("st.relaxed.gpu.global.v4.b32 [%0], {%1,%2,%3,%4};" :: "l"(p), "r"(x), "r"(y), "r"(z), "r"(w) : "memory");
}
DI void red_f16x8(void* p, uint32_t x, uint32_t y, uint32_t z, uint32_t w) {
  asm volatile("red.relaxed.gpu.global.add.noftz.v4.f16x2 [%0], {%1,%2,%3,%4};" :: "l"(p), "r"(x), "r"(y), "r"(z), "r"(w) : "memory");
}
DI void sq_acc(uint32_t& a, uint32_t x) { asm("fma.rn.bf16x2 %0, %1, %1, %0;" : "+r"(a) : "r"(x)); }
DI __half2 amax4(__half2 h, const uint32_t* v) {
  h = __hmax2_nan(__hmax2_nan(h, __habs2(*(const __half2*)&v[0])), __habs2(*(const __half2*)&v[1]));
  return __hmax2_nan(__hmax2_nan(h, __habs2(*(const __half2*)&v[2])), __habs2(*(const __half2*)&v[3]));
}
DI uint32_t wexp(__half2 h) { const uint32_t u = *(const uint32_t*)&h; return __reduce_max_sync(0xffffffffu, max((u >> 16) & 0x7fffu, u & 0x7fffu)) >> 7; }
DI float max10(const float* a) {
  return fmaxf(fmaxf(fmaxf(fmaxf(a[0], a[1]), fmaxf(a[2], a[3])), fmaxf(fmaxf(a[4], a[5]), fmaxf(a[6], a[7]))), fmaxf(a[8], a[9]));
}
DI float quad_max(float m) {
  return fmaxf(fmaxf(m, __shfl_xor_sync(0xffffffffu, m, 1)), fmaxf(__shfl_xor_sync(0xffffffffu, m, 2), __shfl_xor_sync(0xffffffffu, m, 3)));
}
DI float warp_sum(float v) {
#pragma unroll
  for (int o = 16; o; o >>= 1) v += __shfl_xor_sync(0xffffffffu, v, o);
  return v;
}

constexpr int SM_WO3 = 0;
constexpr int SM_X = 16384;
constexpr int XT = 36864;
constexpr int SM_EXP = 126976;
constexpr int SEGB = 10240;
constexpr int SM_BLK = SM_EXP + 8192;
constexpr int SM_VC = SM_BLK + 4 * SEGB;
constexpr int SM_PART = SM_VC + 16384;
constexpr int SM_QM = SM_PART + 4096;
constexpr int SM_E = SM_QM + 1024;
constexpr int SM_VM = SM_E + 1536;
constexpr int SM_OB = SM_VM + 2048;
constexpr int SM_FB = SM_OB + 2048;
constexpr int SM_STAGE = SM_X + XT;
constexpr int SM_M0 = SM_STAGE + 3 * 49152;
constexpr int SM_MISC = 210944;
constexpr int SM_WOST = 212992;
constexpr int SM_MEM = SM_WOST;
constexpr int SM_MAX = SM_MEM + 11264;
#define MEM_BLK(q) ((q) / 3 * 4096 + (q) % 3 * 1024)
constexpr int SM_TOTAL = 229376;
constexpr int MB_W = SM_MISC;
constexpr int MB_WO = SM_MISC + 24;
constexpr int MB_WO3 = SM_MISC + 32;
constexpr int MB_X = SM_MISC + 40;
constexpr int MB_S = SM_MISC + 64;
constexpr int MB_F = SM_MISC + 72;
constexpr int MB_VX = SM_MISC + 80;
constexpr int SC_FPAR = SM_MISC + 136;
constexpr int SC_DEAD = SM_MISC + 96;
constexpr int SC_UNSC = SM_MISC + 112;
constexpr int SC_EXPW = SM_MISC + 132;
constexpr int SC_ONES = SM_MISC + 144;
constexpr int SC_SS = SM_MISC + 160;
constexpr int SC_LAT = SM_MISC + 224;
constexpr int SC_EPO = SM_MISC + 240;
constexpr int MB_XS = SM_MISC + 248;
constexpr int SC_XMAX = SM_MISC + 256;
constexpr int SC_PROF = 229376;

constexpr float SM_SCALE = 0.08838834764831845f;
constexpr float LOG2E = 1.4426950408889634f;
constexpr float E_LIM = 20.f;

template <bool B> struct BoolC { static constexpr bool value = B; };
struct RMaps { CUtensorMap x, wq, wk, wv, wo; unsigned char* red; uint32_t poll; const unsigned char* w[4]; };

DI uint32_t latest_hint(uint32_t h, uint32_t d, int s) {
  const uint32_t x = (((h | 0xc0c0c0c0u) - ((d >> 5) & 63) * 0x01010101u) & 0x3f3f3f3fu) | ((h ^ (((s >> 2) + 1) & 3) * 0x40404040u) & 0xc0c0c0c0u);
  const uint32_t y = __vmaxu2(x & 0x00ff00ffu, (x >> 8) & 0x00ff00ffu);
  return __reduce_max_sync(0xffffffffu, max(y & 0xffffu, y >> 16));
}
DI uint32_t near_half(uint32_t sb) {
  uint32_t a, b; lds64(sb + SC_LAT, a, b);
  return a > b;
}

template <int RT, int K0, int K1, bool D32 = false>
DI void xproj(float* acc, const uint32_t (&wa)[2][18][4], uint64_t xd) {
  if (XP & 1) return;
  WG_FENCE();
#pragma unroll
  for (int k = K0; k < ((XP & 128) ? K0 + 1 : K1); k++)
  {
    uint64_t d = xd + (uint64_t)(((k >> 1) * 4096 + (k & 1) * 32) >> 4);
    if (D32) asm("mov.b64 %0, {%1, %2};" : "=l"(d) : "r"((uint32_t)xd + (((k >> 1) * 4096 + (k & 1) * 32) >> 4)), "r"((uint32_t)(xd >> 32)));
    wgmma_n32_rs(acc, wa[RT][k][0], wa[RT][k][1], wa[RT][k][2], wa[RT][k][3], d, k != 0);
  }
  WG_COMMIT();
}

DI void seg_store(int seg, uint32_t sb) {
  fence_async();
  if (EF & 1)
    asm volatile("{\n" EVICT_FIRST "cp.async.bulk.global.shared::cta.bulk_group.L2::cache_hint [%0], [%1], 8192, pol;\n}"
                 :: "l"(g_seg + ((size_t)(seg & RING) * 96 + blockIdx.x) * 8192), "r"(sb + SM_BLK + (seg & 3) * SEGB) : "memory");
  else
  asm volatile("cp.async.bulk.global.shared::cta.bulk_group [%0], [%1], 8192;"
               :: "l"(g_seg + ((size_t)(seg & RING) * 96 + blockIdx.x) * 8192), "r"(sb + SM_BLK + (seg & 3) * SEGB) : "memory");
  asm volatile("cp.async.bulk.commit_group;" ::: "memory");
}
DI void seg_publish(int seg, uint32_t sb) {
  const uint32_t v = lds32(sb + SC_EPO) + seg;
  asm volatile("cp.async.bulk.wait_group 0;" ::: "memory");
  stg_relaxed32(&g_sflag[blockIdx.x * 8], v);
}

DI void proj_role(const uint32_t sb, const RMaps& tm, const uint32_t rank, const int wg, const int w, const int lane) {
  const bool qk = rank < 2;
  uint32_t wa[2][18][4];
  {
    const int rr = (lane & 7) + ((lane >> 4) << 3);
    const uint32_t col = ((2 * w + ((lane >> 3) & 1)) ^ (lane & 7)) << 4;
    float ss;
#pragma unroll 1
    for (int pass = WARM ? wg + w == 0 : 1; pass < 2; pass++) {
      ss = 0.f;
      if (pass) bar_sync(3, 256);
#pragma unroll
      for (int c = 0; c < 3; c++) {
        QSTAMP(2 + 2 * c);
        if (pass) mbar_wait(sb + MB_W + 8 * c, 0);
        QSTAMP(3 + 2 * c);
#pragma unroll
        for (int rt = 0; rt < 2; rt++)
#pragma unroll
          for (int k = 0; k < 6; k++)
            ldsm4t(wa[rt][c * 6 + k], sb + SM_STAGE + c * 49152 + (rt ^ wg) * 24576 + (64 * (k >> 1) + 32 * wg + 16 * (k & 1) + rr) * 128 + col);
        if (c < 2) {
          fence_async();
          if (pass) {
            bar_sync(3, 256);
            QSTAMP(17 + c);
            if (threadIdx.x == 0) {
              if (c == 0) tma_load3(sb + SM_X + XT, &tm.x, 32, sb + MB_X + 8);
              else tma_load(sb + SM_X + 2 * XT, &tm.wo, rank * 192, (blockIdx.x / 3) * DH, sb + MB_WO);
            }
            __syncwarp();
          }
        }
        uint32_t q[4] = {0, 0, 0, 0};
#pragma unroll
        for (int rt = 0; rt < 2; rt++)
#pragma unroll
          for (int k = 0; k < 6; k++)
#pragma unroll
            for (int i = 0; i < 4; i++) sq_acc(q[i], wa[rt][c * 6 + k][i]);
#pragma unroll
        for (int i = 0; i < 4; i++) ss += bf_lo(q[i]) + bf_hi(q[i]);
      }
      ss = warp_sum(ss);
    }
    fence_async();
    cluster_arrive();
    if (lane == 0) sts32(sb + SC_SS + 4 * (wg * 4 + w), qk ? 0 : __float_as_uint(ss));
    bar_arrive(11, 384);
  }
  STAMP(1);
  QSTAMP(8);
  mbar_wait(sb + MB_X, 0);
  STAMP(2);
  QSTAMP(9);

  uint32_t t16 = sb + (w * 32 + lane) * 16;
  uint32_t mem_a = sb + SM_MEM + wg * 512 + lane * 16;
  uint32_t fin_a = sb + (lane & 7) * 16 + SM_BLK + (qk ? (wg ^ 1) * 4096 + w * 256 + (lane & 8) * 16 + (lane & 16) * 64
                                              : wg * 4096 + w * 1024 + (lane & 8) * 64 + (lane & 16) * 8);
  PIN(t16); PIN(mem_a); PIN(fin_a);
  const uint32_t fence_reg = mem_a;
  const uint32_t fin2 = qk ? 2048 : 256;
  float acc[16];
  const uint64_t xd0 = make_desc(sb + SM_X + wg * 64, 16, 1024, 1);
  auto do_export = [&](auto retire, uint32_t always) {
    WG_WAIT(0);
    uint32_t p[2];
#pragma unroll
    for (int i = 0; i < 2; i++) {
      p[i] = pack_bf16(acc[8 * i], acc[8 * i + 1]);
      sts128(t16 + SM_EXP + wg * 4096 + i * 2048, p[i], pack_bf16(acc[8 * i + 2], acc[8 * i + 3]),
             pack_bf16(acc[8 * i + 4], acc[8 * i + 5]), pack_bf16(acc[8 * i + 6], acc[8 * i + 7]));
    }
    if (decltype(retire)::value)
      asm volatile("{\n.reg .pred p, q;\nsetp.ne.u32 p, %2, 0;\nsetp.ne.u32 q, %2, 1;\n@p ld.shared.b32 %0, [%3];\n@q ld.shared.b32 %1, [%3 + 4];\n"
                   "setp.ne.u32 p, %0, %1;\n@p exit;\n}" : "+r"(p[0]), "+r"(p[1]) : "r"(always), "r"(sb + SC_DEAD) : "memory");
  };
  uint32_t o[8];
  auto import = [&]() { lds128(t16 + SM_EXP + (wg ^ 1) * 4096, o); lds128(t16 + SM_EXP + (wg ^ 1) * 4096 + 2048, o + 4); };
  auto finish = [&](int seg) {
    const uint32_t a = fin_a + (seg & 3) * SEGB;
    WG_WAIT(0);
#pragma unroll
    for (int i = 0; i < 8; i++) o[i] = FIN16 ? add_bf16(pack_bf16(acc[2 * i], acc[2 * i + 1]), o[i]) : pack_bf16(acc[2 * i] + bf_lo(o[i]), acc[2 * i + 1] + bf_hi(o[i]));
    stsm4(a, o[0], o[1], o[2], o[3]);
    stsm4(a + fin2, o[4], o[5], o[6], o[7]);
  };
  auto send_v = [&](int seg, int dst) {
    fence_async();
    if (seg < NSEG - 1 && !(XP & 2) && elect_one())
      bulk_s2s(mapa(sb + SM_VC + (seg & 1) * 8192, dst), sb + SM_BLK + (seg & 3) * SEGB, 8192, mapa(sb + MB_VX + (seg & 1) * 8, dst));
    __syncwarp();
  };
  auto wait_v = [&](int seg) {
    if (seg < NSEG - 1 && !(XP & 2)) {
      mbar_wait(sb + MB_VX + (seg & 1) * 8, (seg >> 1) & 1);
      if (elect_one()) mbar_expect(sb + MB_VX + (seg & 1) * 8, 8192);
      __syncwarp();
    }
  };
  auto export_seg = [&](int seg) { if (!(XP & (4 | 8192)) && elect_one()) seg_store(seg, sb); __syncwarp(); };
  auto publish = [&](int seg) { if (!(XP & (4 | 16384)) && elect_one()) seg_publish(seg, sb); __syncwarp(); };
  bar_sync(3, 256);
  xproj<1, 0, 18>(acc, wa, xd0);
  do_export(BoolC<false>(), 0);
  SCHED_FENCE(11);
  xproj<0, 0, 18>(acc, wa, xd0);
  bar_sync(3, 256);
  QSTAMP(10);
  cluster_wait();
  QSTAMP(11);
  mbar_wait(sb + MB_X + 8, 0);
  QSTAMP(12);
  import();
  finish(0);
  SCHED_FENCE(12);
  bar_sync(3, 256);
  uint64_t dA = xd0 + (XT >> 4);
  xproj<1, 0, 18>(acc, wa, dA);
  if (!qk && wg == 0 && w < 2) send_v(0, w);
  if (!(EXV & 1) && wg == 0 && w == 3) export_seg(0);
  QSTAMP(13);
  if (qk && wg == 0 && w == 0) wait_v(0);
  QSTAMP(14);
  bar_arrive(13, 384);
  if (!qk) {
    do_export(BoolC<false>(), 0);
    SCHED_FENCE(15);
    xproj<0, 0, 18>(acc, wa, dA);
    if (threadIdx.x == 0 && !(XP & 8)) { mbar_expect(sb + MB_X, XT); tma_load3(sb + SM_X, &tm.x, 96, sb + MB_X); }
    bar_sync(3, 256);
    mbar_wait(sb + MB_X + 16, 0);
    import();
    finish(1);
    SCHED_FENCE(16);
    bar_sync(3, 256);
    dA += XT >> 4;
    xproj<1, 0, 18>(acc, wa, dA);
    if (!(EXV & 2) && wg == 0 && w < VW2) send_v(1, w);
  }
  QSTAMP(15);
  WG_WAIT(0);
  bar_sync(0, 384);
  if (!(EXV & 1) && wg == 0 && w == 3) publish(0);
  QSTAMP(16);
  const int ro = __shfl_sync(0xffffffffu, near_half(sb) ^ wg, 0);
  STAMP(5);
  const uint32_t always = __shfl_sync(0xffffffffu, lds32(sb + SC_DEAD + 12), 0);
  const int ah = qk ? 1 : 2;
  int b2 = qk ? 2 : 0;
  int s = 0;
  uint32_t hint_lo = (uint32_t)(uint64_t)tm.red + HINT_OFF + blockIdx.x + (lane & 1) * 4096 + (lane >> 1) * 16384;
  PIN(hint_lo);
  auto post_hint = [&]() {
    asm volatile("{\n.reg .pred p;\n.reg .b64 a;\n.reg .u32 t;\nsetp.lt.u32 p, %0, %1;\nmov.b64 a, {%2, %3};\nmov.u32 t, %%globaltimer_lo;\n"
                 "bfe.u32 t, t, 5, 6;\nor.b32 t, t, %4;\n@p st.relaxed.gpu.global.u8 [a], t;\n}"
                 :: "r"(t16), "r"(sb + 160), "r"(hint_lo + RED_SLOT(s)), "r"((uint32_t)((uint64_t)tm.red >> 32)), "r"(((s >> 2) + 1) << 6) : "memory");
  };
  auto memproj = [&](auto second, int id, uint32_t dep, float u0, float u1, float* r) {
    constexpr bool R1 = decltype(second)::value;
    uint32_t b[NUP][4], b0[4];
    if (R1) asm volatile("{\n.reg .pred p;\nsetp.eq.u32 p, %0, %1;\n@p exit;\n}" :: "r"(dep), "r"(id) : "memory");
    bar_sync(R1 ? 2 : 1, 256);
    PROF(0);
    ldsm4t(b0, mem_a);
#pragma unroll
    for (int q = 0; q < NUP; q++) {
      if (R1 && q == 2) {
        bar_sync(11, 256);
        SCHED_FENCE(id + 1);
      }
      ldsm4t(b[q], mem_a + MEM_BLK(q + 1));
    }
    mma16816z(&acc[0], wa[0][0], b0[0], b0[1]);
    mma16816z(&acc[4], wa[1][0], b0[0], b0[1]);
    mma16816z(&acc[8], wa[0][1], b0[2], b0[3]);
    mma16816z(&acc[12], wa[1][1], b0[2], b0[3]);
#pragma unroll
    for (int q = 1; q < 9; q++) {
      uint32_t* const c = b[(q - 1) % NUP];
      mma16816(&acc[0], wa[0][2 * q], c[0], c[1]);
      mma16816(&acc[4], wa[1][2 * q], c[0], c[1]);
      mma16816(&acc[8], wa[0][2 * q + 1], c[2], c[3]);
      mma16816(&acc[12], wa[1][2 * q + 1], c[2], c[3]);
      if (R1 && q + NUP == B3Q) bar_sync(3, 256);
      if (q + NUP < 9) ldsm4t_in(c, mem_a + MEM_BLK(q + NUP), always);
      else if (R1 && q + NUP < 11) lds128_in(c, t16 + SM_PART + (10 - q - NUP) * 2048, always);
      else if (!R1 && GATE && q == GATE) { bar_arrive(11, 256); lds128_in(c, sb + SC_DEAD, always); u0 = u1 = __uint_as_float(c[3]); }
    }
#pragma unroll
    for (int i = 0; i < 8; i++) {
      const float u = i < 4 ? u0 : u1;
      r[i] = R1 ? fmaf(acc[8 + i], u, (acc[i] + __uint_as_float(b[(8 + i / 4) % NUP][i & 3])) * u) : (GATE ? fmaf(acc[i], u, acc[8 + i]) : acc[i] + acc[8 + i]);
    }
  };
  if (ro == 0) {
#pragma unroll 1
    while (true) {
      do_export(BoolC<true>(), always);
      PROFP(3);
      if (s == 8) STAMP(6);
      float r[8];
      memproj(BoolC<false>(), 30, 0, 0.f, 0.f, r);
      sts128(t16 + SM_PART, __float_as_uint(r[0]), __float_as_uint(r[1]), __float_as_uint(r[2]), __float_as_uint(r[3]));
      sts128(t16 + SM_PART + 2048, __float_as_uint(r[4]), __float_as_uint(r[5]), __float_as_uint(r[6]), __float_as_uint(r[7]));
      bar_arrive(3, 256);
      PROF(1);
      bar_sync(9, 256);
      if (s == NSEG - 1) break;
      post_hint();
      if (!(EXV & 1) && w == 3 && s) publish(s);
      if (w == 1) {
        uint32_t m[8];
        lds128(t16 + SM_MAX - 512, m); lds128(t16 + SM_MAX, m + 4);
        const int em = (wexp(amax4(amax4(*(const __half2*)&m[0], m), m + 4)) >> 3) + (int)(lds32(sb + SC_UNSC + (s & 1) * 8) >> 23) - 15;
        const int ex = max(s ? em : 0, (int)lds32(sb + SC_XMAX + 4 * s)) - 127 + (int)lds32(sb + SC_EXPW);
        sts32(sb + SC_UNSC + (~s & 1) * 8, (127 + min(max(ex, -120), 120)) << 23);
        __syncwarp();
        if (elect_one()) mbar_arrive(sb + MB_S);
      }
      SCHED_FENCE(9);
      bar_sync(5, qk ? N5 : 256);
      PROF(2);
      import();
      xproj<0, 0, NII>(acc, wa, dA);
      if (NII < 18) {
        if (qk) bar_sync(7, 384);
        xproj<0, NII, 18>(acc, wa, dA);
        if (!qk) bar_sync(7, 384);
      } else {
        if (F10) WG_WAIT(0);
        bar_sync(10, 256);
        if (F10) SCHED_FENCE(17);
      }
      dA += (int64_t)(b2 ? XT >> 4 : -(XT >> 3));
      finish(s + ah);
      if (((EXV & 1) || w != 3) && ((EXV & 2) || qk || w >= VW2)) bar_arrive(13, 384);
      PROF(6);
      SCHED_FENCE(14);
      if (NOB & 2) bar_arrive(14, 256);
      bar_sync(12, 256);
      PROF(7);
      xproj<1, 0, 18, true>(acc, wa, dA);
      if (!(NOB & 2)) bar_arrive(14, 256);
      b2 = b2 == 2 ? 0 : b2 + 1;
      s++;
      if ((!(EXV & 1) && w == 3) || (!(EXV & 2) && !qk && w < VW2)) {
        bar_sync(13, 384);
        if (!(EXV & 1) && w == 3) export_seg(s); else send_v(s + 1, w);
      }
      PROFP(8);
    }
    if (!qk) bar_arrive(5, 256);
    if (!(EXV & 1) && w == 3) publish(NSEG - 1);
  } else {
    uint32_t km[4];
    auto send_km = [&]() {
      if (XP & (4 | 4096)) return;
      const uint32_t t = (km[0] & ~1u) | lds32(sb + SC_EPO + 4), u = (s * NH + head_id()) * 4096;
      if (qk)
        asm volatile("{\n.reg .u32 o;\n.reg .u64 a;\nshr.u32 o, %0, 1;\nadd.u32 o, o, %1;\nmad.wide.u32 a, o, 1, %2;\nst.relaxed.gpu.global.v2.b32 [a], {%3,%4};\n}"
                     :: "r"(t16), "r"(u + rank * 1024 - (sb >> 1)), "l"(g_km), "r"(t), "r"(km[1]) : "memory");
      else
        asm volatile("{\n.reg .u32 o;\n.reg .u64 a;\nadd.u32 o, %0, %1;\nmad.wide.u32 a, o, 1, %2;\nst.relaxed.gpu.global.v4.b32 [a], {%3,%4,%5,%6};\n}"
                     :: "r"(t16), "r"(u + 2048 - sb), "l"(g_km), "r"(t), "r"(km[1]), "r"(km[2]), "r"(km[3]) : "memory");
    };
#pragma unroll 1
    while (true) {
      do_export(BoolC<true>(), always);
      if ((EXV & 1) && w == 1) export_seg(s);
      if ((EXV & 2) && !qk && w == 2) send_v(s + 1, 0);
      PROFP(3);
      if (s == 8) STAMP(6);
      const uint32_t tl = ((t16 >> 8) ^ wg) & 1, am = (t16 & ~256u) - w * 256;
      const float un = __uint_as_float(lds32(sb + SC_UNSC + (s & 1) * 8));
      float r[8];
      if (qk) {
        uint32_t a0 = am + (tl ? SM_QM : SM_BLK + 8192 + (s & 3) * SEGB);
        float u0 = wg ? un * (SM_SCALE * LOG2E) : un, u1 = wg ? un : un * (SM_SCALE * LOG2E);
        PIN(a0); PIN(u0); PIN(u1);
        memproj(BoolC<true>(), 32, a0, u0, u1, r);
        const uint32_t p0 = pack_bf16(r[0], r[1]), p1 = pack_bf16(r[2], r[3]), p2 = pack_bf16(r[4], r[5]), p3 = pack_bf16(r[6], r[7]);
        stsm4(a0, p0, p1, p2, p3);
        bar_arrive(4, 256);
        km[0] = wg ? p2 : p0; km[1] = wg ? p3 : p1;
      } else {
        const uint32_t d0 = s < NSEG - 1 ? 0 : 2, d1 = s < NSEG - 1 ? 1 : 2;
        uint32_t r0 = mapa(t16 + SM_VM, d0), r1 = mapa(t16 + SM_VM, d1);
        PIN(r0); PIN(r1);
        memproj(BoolC<true>(), 34, r0 | r1, un, un, r);
        const uint32_t p0 = pack_bf16(r[0], r[1]), p1 = pack_bf16(r[2], r[3]), p2 = pack_bf16(r[4], r[5]), p3 = pack_bf16(r[6], r[7]);
        const uint32_t v0 = wg ? p2 : p0, v1 = wg ? p3 : p1, v2 = wg ? p0 : p2, v3 = wg ? p1 : p3;
        st_async4(r0, v0, v1, v2, v3, mapa(sb + MB_S, d0));
        st_async4(r1, v0, v1, v2, v3, mapa(sb + MB_S, d1));
        bar_arrive(5, 256);
        sts128(t16 + SM_VM, v0, v1, v2, v3);
        __syncwarp();
        if (elect_one()) mbar_arrive(sb + MB_S);
        km[0] = v0; km[1] = v1; km[2] = v2; km[3] = v3;
      }
      if (s == NSEG - 1) break;
      PROF(1);
      if (KME && (qk || w != 2)) send_km();
      auto rearm = [&]() { mbar_wait(sb + MB_S, s & 1); if (elect_one()) mbar_expect(sb + MB_S, qk ? 640 + 2048 : 1280); __syncwarp(); };
      if (w == 1) {
        if ((t16 & 384) == 0) stg_relaxed(tm.red + (RED_SLOT(s + 2) + RED_LINE(blockIdx.x)) + (t16 & 112), 0, 0, 0, 0);
        if (EXV & 1) publish(s);
      } else if (w == 0) {
        const int tn = s + ah + 1;
        if (RFW) mbar_wait(sb + MB_S, s & 1);
        if (tn + 1 < NSEG && !(XP & 8) && elect_one()) {
          const int b0 = b2 == 2 ? 0 : b2 + 1;
          mbar_expect(sb + MB_X + 8 * b0, XT);
          tma_load3(sb + SM_X + b0 * XT, &tm.x, (tn + 1) * 32, sb + MB_X + 8 * b0);
        }
        if (tn < NSEG && (!(XP & 8) || tn < 3)) mbar_wait(sb + MB_X + 8 * b2, (tn / 3) & 1);
      } else if (w == 2) {
        if (!qk) { if (VW2 < 1) send_v(s + 1, 0); if (VW2 < 2) send_v(s + 1, 1); }
      } else if (qk || !NIC) {
        rearm();
      }
      __syncwarp();
      if (!KME || (!qk && w == 2)) send_km();
      import();
      PROF(4);
      SCHED_FENCE(10);
      if (NIC) {
        if (qk) bar_sync(7, NII < 18 ? 384 : 256);
        xproj<0, 0, NIC>(acc, wa, dA);
        if (!qk) { if (w == 3) rearm(); bar_sync(7, NII < 18 ? 384 : 256); }
      } else {
        bar_sync(7, NII < 18 ? 384 : 256);
      }
      if (NOB & 1) bar_arrive(12, 256);
      xproj<0, NIC, 18>(acc, wa, dA);
      if (!(NOB & 1)) bar_arrive(12, 256);
      dA += (int64_t)(b2 ? XT >> 4 : -(XT >> 3));
      finish(s + ah);
      if (qk && w == 0) wait_v(s + 1);
      bar_arrive(13, 384);
      PROF(6);
      SCHED_FENCE(13);
      bar_sync(14, 256);
      PROF(7);
      xproj<1, 0, 18>(acc, wa, dA);
      b2 = b2 == 2 ? 0 : b2 + 1;
      s++;
      PROFP(8);
    }
    send_km();
    if ((EXV & 1) && w == 1) publish(NSEG - 1);
    PIN(t16);
    if (t16 - sb < 128) stg_relaxed(tm.red + (RED_SLOT(NSEG + 1) + RED_LINE(head_id() * 3 + rank)) + (t16 & 112), 0, 0, 0, 0);
  }
  bar_arrive(0, 384);
  STAMP(3);
  cluster_sync();
  STAMP(4);
}

DI void attn_role(const uint32_t sb, unsigned char* smem_raw, const RMaps& tm, const uint32_t RANK, const bf16* __restrict__ x, const bf16* __restrict__ mem0,
                  const int w, const int lane) {
  const int t2 = w * 32 + lane;
  uint32_t wo[8][4], w1[8][4];
  const uint32_t wo_lane = sb + ((lane & 7) + ((lane >> 4) << 3)) * 128 + (((w + 4 * ((lane >> 3) & 1)) ^ (lane & 7)) << 4);
  unsigned char* const g_red = tm.red;
  {
    const uint32_t tag = *(volatile unsigned*)&g_epoch + 1;
    QSTAMP(0);
    bar_sync(0, 160);
    QSTAMP(1);
    cluster_arrive();
    __half2 hx = __float2half2_rn(0.f);
    if (blockIdx.x < NSEG) {
      mbar_wait(sb + MB_XS, 0);
#pragma unroll
      for (int i = 0; i < 18; i++) { uint32_t v[4]; lds128(sb + SM_X + t2 * 16 + i * 2048, v); hx = amax4(hx, v); }
      fence_async();
      bar_sync(6, 128);
      if (t2 == 0) tma_load3(sb + SM_X, &tm.x, 0, sb + MB_X);
      __syncwarp();
    }
    if (t2 == 0) { sts64(sb + SC_EPO, (tag - 1) * NSEG + 1, tag & 1); sts32(sb + SC_UNSC, __float_as_uint(1.f)); sts128(sb + SC_DEAD, 0, 0, 0, 0x3f800000u); sts64(sb + SC_FPAR, 0, 0); sts128(sb + SC_ONES, 0x3f803f80u, 0x3f803f80u, 0x3f803f80u, 0x3f803f80u); }
    WSTAMP(27);
    uint32_t q[8] = {0, 0, 0, 0, 0, 0, 0, 0};
    QSTAMP(2);
    mbar_wait(sb + MB_WO3, 0);
    QSTAMP(3);
    uint32_t mv[5][4];
#pragma unroll
    for (int i = 0; i < 5; i++) {
      ldsm4(mv[i], sb + SM_M0 + (lane & 7) * (DM * 2) + min(w + 4 * i, 17) * 64 + (lane >> 3) * 16);
      if (blockIdx.x == 0) hx = amax4(hx, mv[i]);
    }
    sts32(sb + SC_SS + 4 * (12 + w), wexp(hx));
#pragma unroll
    for (int k = 0; k < 8; k++) {
      ldsm4t(wo[k], wo_lane + SM_WO3 + k * 2048); ldsm4t(w1[k], wo_lane + SM_WOST + k * 2048);
#pragma unroll
      for (int i = 0; i < 4; i++) { sq_acc(q[i], wo[k][i]); sq_acc(q[i], w1[k][i]); }
    }
    bar_sync(6, 128);
#pragma unroll
    for (int k = 0; k < 8; k++) sts128(sb + SM_WO3 + t2 * 16 + k * 2048, wo[k][0], wo[k][1], wo[k][2], wo[k][3]);
#pragma unroll
    for (int i = 0; i < 5; i++) {
      const int c = (w + 4 * i) * 32;
      if (c < DM) stsm4t(sb + SM_MEM + (c + c / 192 * 64 + lane) * 16, mv[i][0], mv[i][1], mv[i][2], mv[i][3]);
    }
    bar_arrive(1, 256); bar_arrive(2, 256); bar_arrive(9, 256);
    QSTAMP(4);
    mbar_wait(sb + MB_WO, 0);
    QSTAMP(5);
#pragma unroll
    for (int k = 0; k < 8; k++) ldsm4t(wo[k], wo_lane + SM_X + 2 * XT + k * 2048);
    fence_async();
    bar_sync(6, 128);
    if (t2 == 32) tma_load3(sb + SM_X + 2 * XT, &tm.x, 64, sb + MB_X + 16);
    __syncwarp();
#pragma unroll
    for (int k = 0; k < 8; k++)
#pragma unroll
      for (int i = 0; i < 4; i++) sq_acc(q[4 + i], wo[k][i]);
    float ss = 0.f;
#pragma unroll
    for (int i = 0; i < 8; i++) ss += bf_lo(q[i]) + bf_hi(q[i]);
    ss = warp_sum(ss);
    if (lane == 0) sts32(sb + SC_SS + 4 * (8 + w), __float_as_uint(ss));
    QSTAMP(6);
    bar_sync(11, 384);
    QSTAMP(7);
    if (t2 == 0) {
      float a[16];
#pragma unroll
      for (int i = 0; i < 4; i++) lds128f(sb + SC_SS + 16 * i, &a[4 * i]);
      stg_relaxed(&g_stats[blockIdx.x * 2], __float_as_uint(((a[0] + a[1]) + (a[2] + a[3])) + ((a[4] + a[5]) + (a[6] + a[7]))),
                  __float_as_uint((a[8] + a[9]) + (a[10] + a[11])),
                  max(max(__float_as_uint(a[12]), __float_as_uint(a[13])), max(__float_as_uint(a[14]), __float_as_uint(a[15]))), tag);
    }
    __syncwarp();
    WSTAMP(24);
    QSTAMP(8);
    cluster_wait();
    QSTAMP(9);
    if (w == 0) {
      uint4 v[3];
      int n = 0;
      while (true) {
#pragma unroll
        for (int i = 0; i < 3; i++) v[i] = ldg_relaxed(&g_stats[(i * 32 + lane) * 2]);
        if (__all_sync(0xffffffffu, v[0].w == tag && v[1].w == tag && v[2].w == tag) || ++n > SPIN_LIMIT) break;
        __nanosleep(100);
      }
      WSTAMP(25);
      QSTAMP(10);
      const float sv = warp_sum(__uint_as_float(v[0].x) + __uint_as_float(v[1].x) + __uint_as_float(v[2].x));
      const float so = warp_sum(__uint_as_float(v[0].y) + __uint_as_float(v[1].y) + __uint_as_float(v[2].y));
      const int expW = ((int)(__float_as_uint(sv) >> 23) + (int)(__float_as_uint(so) >> 23) - 254 + 2 + 10 + 1) >> 1;
      sts32(sb + SC_XMAX + 4 * lane, v[0].z); sts32(sb + SC_XMAX + 128 + 4 * lane, v[1].z);
      sts32(sb + SC_EXPW, expW + 1 - 15);
      if (blockIdx.x == 0 && lane == 0) *(volatile unsigned*)&g_epoch = tag;
      sts32(sb + SC_FPAR + 4, 1);
    } else if (w < 3) {
      const uint32_t u = blockIdx.x >> 4;
      unsigned char* const z = g_red + 98304 + (blockIdx.x & 15) * 128 + (u & 1) * 2048 + (u & 6) * 4096 + (((u >> 1) ^ w) & 1) * 4096 + lane * 4;
      stg_relaxed32(z, 0);
      uint32_t best = 0xffffffffu;
#pragma unroll 1
      for (int i = 0; i < 64; i++) {
        uint32_t last, dt;
        asm volatile("{\n.reg .pred p;\n.reg .u32 c, v;\nld.volatile.shared.u32 %0, [%3];\nmov.u32 c, %%clock;\n"
                     "atom.relaxed.gpu.global.exch.b32 v, [%2], 0;\nsetp.eq.u32 p, v, 0;\nmov.u32 %1, 0;\n@p mov.u32 %1, %%clock;\nsub.u32 %1, %1, c;\n}"
                     : "=r"(last), "=r"(dt) : "l"(z), "r"(sb + SC_FPAR + 4) : "memory");
        best = min(best, dt);
        if ((last && i >= NPROBE - 1) || i >= NPROBE2 - 1) break;
      }
      sts32(sb + SC_LAT + (w - 1) * 4, best);
    }
    QSTAMP(11);
    bar_sync(13, 384);
    bar_arrive(0, 384);
    QSTAMP(12);
    WSTAMP(26);
  }

  const uint32_t nh = __shfl_sync(0xffffffffu, near_half(sb), 0);
  uint32_t l16 = sb + lane * 16;
  PIN(l16);
#define LV ((l16 >> 4) & 31)
#define fence_reg l16
  const uint32_t red_lo = (uint32_t)(uint64_t)g_red, red_hi = (uint32_t)((uint64_t)g_red >> 32);
  uint32_t lp;
  auto slot = [&](int s, uint32_t c, uint32_t ofs) {
    const uint32_t lo = lp | (red_lo + ((w >> 1) * 4 + (w & 1) * 2 + ((w ^ c) & 1)) * 4096 + RED_SLOT(s) + ofs);
    uint64_t a; asm("mov.b64 %0, {%1, %2};" : "=l"(a) : "r"(lo), "r"(red_hi));
    return (unsigned char*)a;
  };
  const uint32_t always = __shfl_sync(0xffffffffu, lds32(sb + SC_DEAD + 12), 0);
  const int mode0 = RANK < 2 ? w : w | 4;
  auto hint_addr = [&](int s) { return min(LV, 23u) * 4 + (red_lo + HINT_OFF + nh * 4096 + w * 16384 + RED_SLOT(s)); };
  auto load_hints = [&](uint32_t lo) {
    uint64_t a; asm("mov.b64 %0, {%1, %2};" : "=l"(a) : "r"(lo), "r"(red_hi));
    return ldg_relaxed32((const void*)a);
  };
  int s = 0;
  bool bad = false;
#pragma unroll 1
  while (true) {
    const uint32_t par = s & 1;
    uint32_t vx[4][4], hints;
    auto load_vx = [&]() {
      const uint32_t va = l16 + (RANK < 2 ? SM_VC + par * 8192 : SM_BLK + (s & 3) * SEGB) + w * 1024 + ((LV >> 3) & 1) * 384 - (LV >> 4) * 128;
#pragma unroll
      for (int i = 0; i < 4; i++) ldsm4(vx[i], va + (i & 1) * 4096 + (i >> 1) * 256);
    };
    auto retire = [&](uint32_t x) {
      asm volatile("{\n.reg .pred p;\nsetp.eq.u32 p, %0, 0;\n@p exit;\n}" :: "r"(vx[0][0] | vx[1][0] | vx[2][0] | vx[3][0] | x) : "memory");
    };
    auto scores = [&](auto memkeys, auto first, float* sc) {
      constexpr bool MK = decltype(memkeys)::value, FIRST = decltype(first)::value;
      uint32_t kb[4][4], qb[2][4];
      const uint32_t m = LV >> 3;
      uint32_t kaddr = l16 + SM_BLK + 4096 + (s & 3) * SEGB + w * 2048 + (m & 1) * (MK ? 128 : 896) - (m >> 1) * 128;
      if (MK) { PIN(kaddr); }
      else {
#pragma unroll
        for (int k = 0; k < 4; k++) ldsm4t(kb[k], kaddr + k * 256);
      }
      if (FIRST) { load_vx(); retire(MK ? kaddr : kb[0][0] | kb[1][0] | kb[2][0] | kb[3][0] | l16); bar_sync(4, 256); PROF(4); }
      ldsm4t(qb[0], l16 + SM_QM);
      if (MK) ldsm4t(kb[0], kaddr);
      ldsm4t(qb[1], l16 + SM_QM + 512);
      if (MK) ldsm4t(kb[2], kaddr + 512);
      float c[4][4];
      mma16816z(c[0], kb[0], qb[0][0], qb[0][1]); mma16816z(c[1], kb[MK ? 0 : 1], qb[0][2], qb[0][3]);
      mma16816z(c[2], kb[2], qb[1][0], qb[1][1]); mma16816z(c[3], kb[MK ? 2 : 3], qb[1][2], qb[1][3]);
      if (FIRST && B5POS == 0) bar_arrive(5, N5);
#pragma unroll
      for (int i = 0; i < (MK ? 2 : 4); i++) sc[i] = ((c[0][i] + c[1][MK ? i + 2 : i]) + c[2][i]) + c[3][MK ? i + 2 : i];
    };
    auto send = [&](auto memkeys) {
      constexpr bool MK = decltype(memkeys)::value;
      constexpr int N = MK ? 1 : 2;
      const uint32_t sa = sb + LV * 4 + SM_E + (MK ? 1024 + RANK * 128 : RANK * 512 + w * 256);
      uint32_t ra[N][2], mb[N][2];
#pragma unroll
      for (int i = 0; i < N; i++)
#pragma unroll
        for (int j = 0; j < 2; j++) {
          ra[i][j] = mapa(sa + i * 128, j ? 2 : RANK ^ 1); mb[i][j] = mapa(sb + MB_S, j ? 2 : RANK ^ 1);
          PIN(ra[i][j]);
        }
      float sc[4];
      scores(memkeys, BoolC<true>(), sc);
      uint32_t e[N];
#pragma unroll
      for (int i = 0; i < N; i++) {
        e[i] = pack_bf16(ex2(sc[2 * i]), ex2(sc[2 * i + 1]));
        if (!(fmaxf(fabsf(sc[2 * i]), fabsf(sc[2 * i + 1])) <= E_LIM)) e[i] = 0x7fff7fffu;
        st_async1(ra[i][0], e[i], mb[i][0]);
        st_async1(ra[i][1], e[i], mb[i][1]);
      }
#pragma unroll
      for (int i = 0; i < N; i++) sts32(sa + i * 128, e[i]);
      __syncwarp();
      if (l16 == sb) mbar_arrive(sb + MB_S);
      PROF(5);
    };
    const int mode = bad ? 8 : mode0;
    if (mode < 2) {
      send(BoolC<false>());
    } else if (mode == 2) {
      send(BoolC<true>());
    } else if (mode == 8) {
      load_vx();
      retire(l16);
      const uint32_t fp = lds32(sb + SC_FPAR);
      bar_sync(6, 128);
      if (w == 0 && l16 == sb) { sts32(sb + SC_FPAR, fp ^ 1); mbar_expect(sb + MB_F, 3072); }
      if (RANK < 2 && w < 3) {
        float sc[4] = {0.f, 0.f, 0.f, 0.f};
        if (w < 2) scores(BoolC<false>(), BoolC<false>(), sc); else scores(BoolC<true>(), BoolC<false>(), sc);
#pragma unroll 1
        for (int r = 0; r < 3; r++)
          st_async4(mapa(l16 + SM_FB + RANK * 1536 + w * 512, r), __float_as_uint(sc[0]), __float_as_uint(sc[1]), __float_as_uint(sc[2]), __float_as_uint(sc[3]), mapa(sb + MB_F, r));
      }
      mbar_wait(sb + MB_F, fp);
      float a[12];
#pragma unroll
      for (int j = 0; j < 3; j++) {
        float b[4];
        lds128f(l16 + SM_FB + j * 512, a + 4 * j); lds128f(l16 + SM_FB + 1536 + j * 512, b);
#pragma unroll
        for (int i = 0; i < 4; i++) a[4 * j + i] += b[i];
      }
      float m0 = fmaxf(fmaxf(fmaxf(a[0], a[2]), fmaxf(a[4], a[6])), a[8]), m1 = fmaxf(fmaxf(fmaxf(a[1], a[3]), fmaxf(a[5], a[7])), a[9]);
#pragma unroll
      for (int o = 4; o < 32; o <<= 1) { m0 = fmaxf(m0, __shfl_xor_sync(0xffffffffu, m0, o)); m1 = fmaxf(m1, __shfl_xor_sync(0xffffffffu, m1, o)); }
#pragma unroll
      for (int i = 0; i < 5; i++) {
        const uint32_t ea = sb + SM_E + LV * 4 + (i < 4 ? i * 128 : 1024);
        sts32(ea, pack_bf16(ex2(a[2 * i] - m0), ex2(a[2 * i + 1] - m1)));
        sts32(ea + (i < 4 ? 512 : 128), 0x3f803f80u);
      }
      __syncwarp();
    } else {
      load_vx();
      if (mode == 3) bar_arrive(4, 256);
      retire(l16 + 1);
    }
    {
      uint32_t wa[4], wb[4], oc[4];
      constexpr int WS = 2048;
      const uint32_t w3a = l16 + SM_WO3 + w * 512;
      lds128(w3a + KP(0) * WS, wa); lds128(w3a + KP(1) * WS, wb); lds128(sb + SC_ONES, oc);
      if (B5POS == 1 && mode < 3) bar_arrive(5, N5);
      uint32_t e[10], p[5], vm[4], ob[4];
      float o0[4], o1[4], f[3][2][4], rs[4];
      reserve2(vm); reserve2(vm + 2); reserve2(e + 8);
      hints = hint_addr(s);
      PIN(hints);
      if (CLR & 2) asm volatile("{\n.reg .pred p;\nsetp.eq.u32 p, %0, 0;\n@p exit;\n}" :: "r"(wa[0] | wb[0] | oc[0] | hints) : "memory");
      mbar_wait(sb + MB_S, par);
      PROF(6);
      ldsm4t(e, l16 + SM_E); ldsm2t_in(e + 8, l16 + SM_E + 1024, always); ldsm4t(e + 4, l16 + SM_E + 512);
      lds128_in(vm, l16 + w * 512 + SM_VM, always);
      const float scl = __uint_as_float(lds32(sb + SC_UNSC + 8 - par * 8));
      hints = load_hints(hints);
      if (GF & 1) SCHED_FENCE(4);
#pragma unroll
      for (int i = 0; i < 4; i++) p[i] = mul_bf16(e[i], e[4 + i]);
      p[4] = mul_bf16(e[8], e[9]);
      mma16816z(o0, vx[0], p[0], p[1]); mma16816z(o1, vx[1], p[0], p[1]); mma16816z(rs, oc, p[0], p[1]);
      mma16816(o0, vx[2], p[2], p[3]); lds128_in(vx[2], w3a + KP(2) * WS, always);
      mma16816(o1, vx[3], p[2], p[3]); lds128_in(vx[3], w3a + KP(3) * WS, always);
      mma16816(rs, oc, p[2], p[3]);
      mma1688(o0, vm[0], vm[1], p[4]); mma1688(o1, vm[2], vm[3], p[4]); mma1688(rs, oc[0], oc[1], p[4]);
      stsm4(l16 + w * 512 + SM_OB, pack_bf16(o0[0], o0[1]), pack_bf16(o0[2], o0[3]), pack_bf16(o1[0], o1[1]), pack_bf16(o1[2], o1[3]));
      bar_sync(6, 128);
      PROF(7);
      ldsm4t_in(oc, l16 + SM_OB, always);
      bad = __any_sync(0xffffffffu, !(rs[0] + rs[1] > 0.f) && !bad);
      rs[0] *= scl; rs[1] *= scl;
      asm volatile("{\n.reg .pred p;\nsetp.ne.u32 p, %1, 0;\n@p rcp.approx.ftz.f32 %0, %0;\n}" : "+f"(rs[0]) : "r"(always));
      asm volatile("{\n.reg .pred p;\nsetp.ne.u32 p, %1, 1;\n@p rcp.approx.ftz.f32 %0, %0;\n}" : "+f"(rs[1]) : "r"(always));
      asm volatile("lop3.b32 %0, %1, %2, %3, 0xfe;" : "=r"(lp) : "r"((l16 & 128) * 2), "r"((l16 & 256) * 4), "r"(l16 & 112));
      if (bad) continue;
      ldsm4t(ob, l16 + SM_OB + 512);
      mma16816z(f[2][0], wa, oc[0], oc[1]); mma16816z(f[2][1], wb, oc[2], oc[3]);
      mma16816z(f[0][0], wo[0], oc[0], oc[1]); mma16816z(f[0][1], wo[4], oc[2], oc[3]);
      mma16816z(f[1][0], w1[0], oc[0], oc[1]); mma16816z(f[1][1], w1[4], oc[2], oc[3]);
      ldsm4t_in(oc, l16 + SM_OB + 1024, always);
      mma16816(f[2][0], vx[2], ob[0], ob[1]); lds128_in(vx[2], w3a + KP(4) * WS, always);
      mma16816(f[2][1], vx[3], ob[2], ob[3]); lds128_in(vx[3], w3a + KP(5) * WS, always);
      mma16816(f[0][0], wo[1], ob[0], ob[1]); mma16816(f[0][1], wo[5], ob[2], ob[3]);
      mma16816(f[1][0], w1[1], ob[0], ob[1]); mma16816(f[1][1], w1[5], ob[2], ob[3]);
      ldsm4t_in(ob, l16 + SM_OB + 1536, always);
      mma16816(f[0][0], wo[2], oc[0], oc[1]); mma16816(f[0][1], wo[6], oc[2], oc[3]);
      mma16816(f[2][0], vx[2], oc[0], oc[1]); lds128_in(vx[2], w3a + KP(6) * WS, always);
      mma16816(f[2][1], vx[3], oc[2], oc[3]); lds128_in(vx[3], w3a + KP(7) * WS, always);
      mma16816(f[1][0], w1[2], oc[0], oc[1]); mma16816(f[1][1], w1[6], oc[2], oc[3]);
      mma16816(f[0][0], wo[3], ob[0], ob[1]); mma16816(f[0][1], wo[7], ob[2], ob[3]);
      mma16816(f[1][0], w1[3], ob[0], ob[1]); mma16816(f[1][1], w1[7], ob[2], ob[3]);
      mma16816(f[2][0], vx[2], ob[0], ob[1]); mma16816(f[2][1], vx[3], ob[2], ob[3]);
      bar_arrive(7, NII < 18 ? 384 : 256);
      lds128_in(ob, sb + SC_DEAD, always);
      uint32_t h[3][2];
#pragma unroll
      for (int j = 0; j < 3; j++)
#pragma unroll
        for (int i = 0; i < 2; i++)
        {
          scale_sum(f[j][1][2 * i], f[j][0][2 * i], rs[0], always); scale_sum(f[j][1][2 * i + 1], f[j][0][2 * i + 1], rs[1], always);
          h[j][i] = pack_f16(f[j][1][2 * i], f[j][1][2 * i + 1]);
        }
      const uint32_t rofs = RANK * 32768;
      red_f16x8(slot(s, RANK >> 1, rofs), h[0][0], h[1][0], h[2][0], 0x3c00u);
      red_f16x8(slot(s, (RANK >> 1) ^ 1, rofs), h[0][1], h[1][1], h[2][1], 0x3c00u);
      if (NII == 18) bar_arrive(10, 256);
      SCHED_FENCE(5);
      l16 += ob[B7R];
    }
    {
    PROF(8);
    const uint32_t ma0 = l16 + SM_MEM + w * 128 + (LV >> 3) * 896 + nh * 512;
    const unsigned char* const sl[2] = {slot(s, nh, 0), slot(s, nh ^ 1, 0)};
    uint32_t dl = gtime() - 1984;
    uint32_t late = latest_hint(hints, dl, s);
    if (late >= 64) {
      int n = 0;
#pragma unroll 1
      do {
        hints = load_hints(hint_addr(s));
        dl = gtime() - 1984;
        late = latest_hint(hints, dl, s);
      } while (late >= 64 && ++n < SPIN_LIMIT);
    }
    dl += late * 32 + tm.poll;
    PROF(9);
    {
      auto wait_until = [&](uint32_t t) {
        asm volatile("{\n.reg .pred p;\n.reg .s32 c;\n.reg .u64 t;\nTL: mov.u64 t, %%globaltimer;\ncvt.u32.u64 c, t;\nsub.s32 c, c, %0;\nsetp.lt.s32 p, c, 0;\n@p bra.uni TL;\n}" :: "r"(t + (l16 & 15)) : "memory");
      };
      uint4 v[2][3];
      auto load = [&](int c) {
#pragma unroll
        for (int r = 0; r < 3; r++) v[c][r] = ldg_relaxed(sl[c ^ (r >> 1)] + r * 32768);
      };
      auto decode = [&](int c, int n) {
        uint32_t q[9];
        __half2 hm;
        const uint32_t ma = ma0 ^ (c * 512);
#pragma unroll
        for (int i = 0; i < 9; i++) {
          const uint32_t h = i % 3 == 0 ? v[c][i / 3].x : (i % 3 == 1 ? v[c][i / 3].y : v[c][i / 3].z);
          const float2 f = __half22float2(*(const __half2*)&h);
          q[i] = pack_bf16(f.x, f.y);
          hm = i ? __hmax2(hm, __habs2(*(const __half2*)&h)) : __habs2(*(const __half2*)&h);
        }
#pragma unroll
        for (int r = 0; r < 3; r++) stsm4(ma + r * 4096, q[3 * r], q[3 * r + 1], q[3 * r + 2], r < 2 ? v[c][r].w : *(const uint32_t*)&hm);
        const bool done = __all_sync(0xffffffffu, v[c][0].w == 0x5000u && v[c][1].w == 0x5000u && v[c][2].w == 0x5000u) || n > SPIN_LIMIT;
        asm volatile("{\n.reg .pred p;\nsetp.ne.u32 p, %0, 0;\n@p bar.arrive %1, 256;\n}" :: "r"((int)done), "r"(1 + c) : "memory");
        return done;
      };
      if (LEAD) { wait_until(dl - LEAD); load(1); }
      wait_until(dl);
      PROF(10);
      int n = 0;
#pragma unroll 1
      do {
        load(0);
        if (!LEAD) load(1);
        asm volatile("{\n.reg .pred p;\nsetp.eq.u32 p, %0, 0;\n@p bar.sync 13, 384;\n}" :: "r"(n) : "memory");
      } while (!decode(0, n++));
      PROF(11);
#pragma unroll 1
      while (!decode(1, n++)) load(1);
      bar_arrive(9, 256);
      PROF(12);
    }
    PROF(13);
    if (++s == NSEG - 1) break;
    }
  }
#undef fence_reg
  if (RANK < 2) bar_arrive(4, 256);
  bar_sync(0, 384);
  cluster_sync();
}

__global__ void __cluster_dims__(3, 1, 1) __launch_bounds__(384, 1)
rec_kernel(const __grid_constant__ RMaps tm, const bf16* __restrict__ x, const bf16* __restrict__ mem0) {
  extern __shared__ __align__(1024) unsigned char smem_raw[];
  const uint32_t sb = smem_u32(smem_raw);
  const int tid = threadIdx.x, lane = tid & 31;
  const int wg = __shfl_sync(0xffffffffu, tid >> 7, 0);
  const int w = __shfl_sync(0xffffffffu, (tid >> 5) & 3, 0);
  uint32_t rank; asm("mov.u32 %0, %%cluster_ctarank;" : "=r"(rank));
  STAMP(0);
  asm volatile("griddepcontrol.launch_dependents;" ::: "memory");

  if (wg < 2) {
    asm volatile("setmaxnreg.inc.sync.aligned.u32 192;");
    if (tid == 0) {
      for (int i = 0; i < 3; i++) { mbar_init(sb + MB_W + 8 * i, 1); mbar_init(sb + MB_X + 8 * i, 1); }
      mbar_init(sb + MB_WO, 1); mbar_init(sb + MB_WO3, 1);
      mbar_init(sb + MB_S, rank < 2 ? 5 : 6);
      mbar_init(sb + MB_F, 1); mbar_init(sb + MB_XS, 1);
      mbar_init(sb + MB_VX, 1); mbar_init(sb + MB_VX + 8, 1);
      asm volatile("fence.mbarrier_init.release.cluster;" ::: "memory");
      fence_async();
      const int h = blockIdx.x / 3;
      const CUtensorMap* m0 = rank < 2 ? &tm.wk : &tm.wv;
      const CUtensorMap* m1 = rank < 2 ? &tm.wq : &tm.wv;
      const int c0 = h * DH + (rank == 1 ? 64 : 0), c1 = h * DH + (rank == 0 ? 0 : 64);
      auto load_w = [&](int c) {
        mbar_expect(sb + MB_W + 8 * c, 49152);
        ((EF & 4) ? tma_load_ef : tma_load)(sb + SM_STAGE + c * 49152, m0, c0, c * 192, sb + MB_W + 8 * c);
        ((EF & 4) ? tma_load_ef : tma_load)(sb + SM_STAGE + c * 49152 + 24576, m1, c1, c * 192, sb + MB_W + 8 * c);
      };
      for (int i = 0; i < 3; i++) mbar_expect(sb + MB_X + 8 * i, XT);
      if (blockIdx.x < NSEG) { mbar_expect(sb + MB_XS, XT); bulk_load(sb + SM_X, x + blockIdx.x * 32 * DM, XT, sb + MB_XS); }
      for (int c = 0; c < WPOS; c++) load_w(c);
      mbar_expect(sb + MB_WO3, 32768 + 8 * DM * 2);
      tma_load(sb + SM_WOST, &tm.wo, rank * 192 + 64, h * DH, sb + MB_WO3);
      tma_load(sb + SM_WO3, &tm.wo, rank * 192 + 128, h * DH, sb + MB_WO3);
      bulk_load(sb + SM_M0, mem0, 8 * DM * 2, sb + MB_WO3);
      tma_prefetch(&tm.wo, rank * 192, h * DH);
      if (blockIdx.x >= NSEG) tma_load3(sb + SM_X, &tm.x, 0, sb + MB_X);
      for (int c = WPOS; c < 3; c++) load_w(c);
      mbar_expect(sb + MB_WO, 16384);
      mbar_expect(sb + MB_S, rank < 2 ? 640 + 2048 : 1280);
      mbar_expect(sb + MB_VX, 8192); mbar_expect(sb + MB_VX + 8, 8192);
    }
    __syncwarp();
    QSTAMP(0);
    if (tid < 32) bar_arrive(0, 160);
    QSTAMP(1);
    proj_role(sb, tm, rank, wg, w, lane);
  } else {
    asm volatile("setmaxnreg.dec.sync.aligned.u32 120;");
    attn_role(sb, smem_raw, tm, rank, x, mem0, w, lane);
  }
}

constexpr int NAUX = 36;
constexpr int A_ST = 6, A_STAGE = 8192 + 12288, A_W8 = A_ST * A_STAGE, A_EXC = A_W8 + A_ST * 1536, A_ROWS = 57;
constexpr int A_XT = 3 * XT, A_XW = A_XT + 3 * 4096;
constexpr int A_IN = A_EXC + 8 * 2304, A_INB = 3 * SEGB, A_OST = A_IN + 2 * A_INB, A_P = A_OST + 8192, A_G = A_P + 3072;
constexpr int A_BAR = A_G + 1024;
constexpr int A_TOTAL = A_BAR + 512;
static_assert(A_IN % 1024 == 0 && A_IN >= 4 * XT && A_IN + 64 * DM * 2 <= A_BAR && A_TOTAL <= 232448, "side kernel shared memory");
struct AMaps { CUtensorMap x, wa, wa8, o, o3, wob, woa; const unsigned char* red; uint32_t poll; };

DI void wgmma_n192_ss_nt(float* d, uint64_t da, uint64_t db, int acc) {
  asm volatile("{\n.reg .pred p;\nsetp.ne.b32 p, %98, 0;\n"
               "wgmma.mma_async.sync.aligned.m64n192k16.f32.bf16.bf16 {"
               "%0,%1,%2,%3,%4,%5,%6,%7,%8,%9,%10,%11,%12,%13,%14,%15,%16,%17,%18,%19,%20,%21,%22,%23,%24,%25,%26,%27,%28,%29,%30,%31,"
               "%32,%33,%34,%35,%36,%37,%38,%39,%40,%41,%42,%43,%44,%45,%46,%47,%48,%49,%50,%51,%52,%53,%54,%55,%56,%57,%58,%59,%60,%61,%62,%63,"
               "%64,%65,%66,%67,%68,%69,%70,%71,%72,%73,%74,%75,%76,%77,%78,%79,%80,%81,%82,%83,%84,%85,%86,%87,%88,%89,%90,%91,%92,%93,%94,%95"
               "}, %96, %97, p, 1, 1, 0, 1;\n}\n"
               : ACC8(d, 0), ACC8(d, 8), ACC8(d, 16), ACC8(d, 24), ACC8(d, 32), ACC8(d, 40), ACC8(d, 48), ACC8(d, 56),
                 ACC8(d, 64), ACC8(d, 72), ACC8(d, 80), ACC8(d, 88) : "l"(da), "l"(db), "r"(acc));
}
DI void wgmma_n24_ss_nt(float* d, uint64_t da, uint64_t db, int acc) {
  asm volatile("{\n.reg .pred p;\nsetp.ne.b32 p, %14, 0;\n"
               "wgmma.mma_async.sync.aligned.m64n24k16.f32.bf16.bf16 {%0,%1,%2,%3,%4,%5,%6,%7,%8,%9,%10,%11}, %12, %13, p, 1, 1, 0, 1;\n}\n"
               : ACC8(d, 0), "+f"(d[8]), "+f"(d[9]), "+f"(d[10]), "+f"(d[11]) : "l"(da), "l"(db), "r"(acc));
}
DI void tma_load3d(uint32_t dst, const CUtensorMap* m, int c0, int c1, int c2, uint32_t mb) {
  asm volatile("cp.async.bulk.tensor.3d.shared::cluster.global.mbarrier::complete_tx::bytes [%0], [%1, {%3, %4, %5}], [%2];"
               :: "r"(dst), "l"(m), "r"(mb), "r"(c0), "r"(c1), "r"(c2) : "memory");
}
DI uint32_t trans8(uint32_t x) { uint32_t r; asm("movmatrix.sync.aligned.m8n8.trans.b16 %0, %1;" : "=r"(r) : "r"(x)); return r; }
DI void wgmma_n32_ss_tn(float* d, uint64_t da, uint64_t db) {
  asm volatile("wgmma.mma_async.sync.aligned.m64n32k16.f32.bf16.bf16 {%0,%1,%2,%3,%4,%5,%6,%7,%8,%9,%10,%11,%12,%13,%14,%15}, "
               "%16, %17, 1, 1, 1, 1, 0;"
               : ACC8(d, 0), ACC8(d, 8) : "l"(da), "l"(db));
}
DI void wgmma_n40_ss(float* d, uint64_t da, uint64_t db, int acc) {
  asm volatile("{\n.reg .pred p;\nsetp.ne.b32 p, %22, 0;\n"
               "wgmma.mma_async.sync.aligned.m64n40k16.f32.bf16.bf16 {%0,%1,%2,%3,%4,%5,%6,%7,%8,%9,%10,%11,%12,%13,%14,%15,%16,%17,%18,%19}, "
               "%20, %21, p, 1, 1, 1, 1;\n}\n"
               : ACC8(d, 0), ACC8(d, 8), "+f"(d[16]), "+f"(d[17]), "+f"(d[18]), "+f"(d[19]) : "l"(da), "l"(db), "r"(acc));
}
DI uint2 ldg_relaxed64(const void* p) {
  uint2 v; asm volatile("ld.relaxed.gpu.global.v2.b32 {%0,%1}, [%2];" : "=r"(v.x), "=r"(v.y) : "l"(p) : "memory"); return v;
}
template <int ST> DI void ldg8x64(uint32_t* m, const void* p) {
  asm volatile("ld.relaxed.gpu.global.v2.b32 {%0,%1}, [%16];\nld.relaxed.gpu.global.v2.b32 {%2,%3}, [%16 + %17];\n"
               "ld.relaxed.gpu.global.v2.b32 {%4,%5}, [%16 + %18];\nld.relaxed.gpu.global.v2.b32 {%6,%7}, [%16 + %19];\n"
               "ld.relaxed.gpu.global.v2.b32 {%8,%9}, [%16 + %20];\nld.relaxed.gpu.global.v2.b32 {%10,%11}, [%16 + %21];\n"
               "ld.relaxed.gpu.global.v2.b32 {%12,%13}, [%16 + %22];\nld.relaxed.gpu.global.v2.b32 {%14,%15}, [%16 + %23];"
               : "=r"(m[0]), "=r"(m[1]), "=r"(m[2]), "=r"(m[3]), "=r"(m[4]), "=r"(m[5]), "=r"(m[6]), "=r"(m[7]),
                 "=r"(m[8]), "=r"(m[9]), "=r"(m[10]), "=r"(m[11]), "=r"(m[12]), "=r"(m[13]), "=r"(m[14]), "=r"(m[15])
               : "l"(p), "n"(ST), "n"(2 * ST), "n"(3 * ST), "n"(4 * ST), "n"(5 * ST), "n"(6 * ST), "n"(7 * ST) : "memory");
}
template <int ST> DI void ldg4x128(uint32_t* m, const void* p) {
  asm volatile("ld.relaxed.gpu.global.v4.b32 {%0,%1,%2,%3}, [%16];\nld.relaxed.gpu.global.v4.b32 {%4,%5,%6,%7}, [%16 + %17];\n"
               "ld.relaxed.gpu.global.v4.b32 {%8,%9,%10,%11}, [%16 + %18];\nld.relaxed.gpu.global.v4.b32 {%12,%13,%14,%15}, [%16 + %19];"
               : "=r"(m[0]), "=r"(m[1]), "=r"(m[2]), "=r"(m[3]), "=r"(m[4]), "=r"(m[5]), "=r"(m[6]), "=r"(m[7]),
                 "=r"(m[8]), "=r"(m[9]), "=r"(m[10]), "=r"(m[11]), "=r"(m[12]), "=r"(m[13]), "=r"(m[14]), "=r"(m[15])
               : "l"(p), "n"(ST), "n"(2 * ST), "n"(3 * ST) : "memory");
}
template <int N, int ST> DI bool stale(const uint32_t* m, uint32_t tag) {
  uint32_t x = m[0] ^ tag;
#pragma unroll
  for (int i = 1; i < N; i++) asm("lop3.b32 %0, %0, %1, %2, 0xf6;" : "+r"(x) : "r"(m[i * ST]), "r"(tag));
  return __any_sync(0xffffffffu, x & 1);
}
DI bool mbar_test(uint32_t b, uint32_t par) {
  uint32_t r; asm volatile("{\n.reg .pred p;\nmbarrier.test_wait.parity.shared::cta.b64 p, [%1], %2;\nselp.u32 %0, 1, 0, p;\n}" : "=r"(r) : "r"(b), "r"(par) : "memory");
  return r;
}
DI int wait_flags(const unsigned* p, bool active, unsigned base, int seg) {
  int n = 0, m;
  while (true) {
    m = __reduce_min_sync(0xffffffffu, active ? (int)(ldg_acquire32(p) - base) : NSEG);
    if (m > seg || ++n > SPIN_LIMIT) break;
    __nanosleep((YP & 32) ? 400 : 40);
  }
  return max(m, seg + 1);
}
DI void wait_count(const unsigned* p, unsigned target) {
  int n = 0;
  unsigned v;
  while (true) {
    asm volatile("ld.acquire.gpu.global.b32 %0, [%1];" : "=r"(v) : "l"(p) : "memory");
    if ((int)(v - target) >= 0 || ++n > SPIN_LIMIT) break;
    __nanosleep(64);
  }
}
#define PACE_NEXT 800
#define AWARM 0
#define WPF 3
#define UNP 64
#define ADLY 0
#define ODLY 100
#define PING 60
#define FLAG 2
#define FPOS 1
#define QB 1
#define Q_LO 0
#define Q_HI 320
DI bool tick_wait(uint32_t pace, int step) {
  const int n = lds32(pace);
  if (n <= step) mbar_wait(pace + 8, n & 1);
  return n <= step;
}
DI void quiet_wait(uint32_t pace) {
  uint32_t n, d;
  lds64(pace, n, d);
  if (n - 1 < NSEG - 2 && (int)(gtime() - d) > Q_HI) mbar_wait(pace + 8, n & 1);
}
DI void sleep_until(uint32_t t) {
  for (int n = 0; n < 64; n++) {
    const int r = t - gtime();
    if (r <= 0) break;
    __nanosleep(r >> 1);
  }
}
DI void aux_barrier(int i, unsigned epoch, bool wait = true) {
  asm volatile("fence.proxy.async;" ::: "memory");
  asm volatile("red.release.gpu.global.add.u32 [%0], 1;" :: "l"(&g_abar[i * 32]) : "memory");
  if (!wait) return;
  wait_count(&g_abar[i * 32], NAUX * (epoch + 1));
  asm volatile("fence.proxy.async;" ::: "memory");
}

__global__ void __launch_bounds__(512, 1)
aux_kernel(const __grid_constant__ AMaps tm, const bf16* __restrict__ x, const bf16* __restrict__ gate_w, bf16* __restrict__ out) {
  extern __shared__ __align__(1024) unsigned char smem_raw[];
  const uint32_t sb = smem_u32(smem_raw);
  const uint32_t full1 = sb + A_BAR, empty1 = full1 + 8 * A_ST, fullw = empty1 + 8 * A_ST, full3 = fullw + 16, empty3 = full3 + 32,
                 fulla = empty3 + 32, emptya = fulla + 32, fullg = emptya + 16, pace = fullg + 8;
  const int tid = threadIdx.x, lane = tid & 31, cta = blockIdx.x;
  const int wg = __shfl_sync(0xffffffffu, tid >> 7, 0), w = __shfl_sync(0xffffffffu, (tid >> 5) & 3, 0);
  ASTAMP(14);
  const unsigned epoch = *(volatile unsigned*)&g_epoch2;
  if (tid == 0) {
    for (int i = 0; i < A_ST; i++) { mbar_init(full1 + 8 * i, 1); mbar_init(empty1 + 8 * i, 8); }
    mbar_init(fullw, 1); mbar_init(fullw + 8, 1); mbar_init(fullg, 1);
    for (int i = 0; i < 2; i++) { mbar_init(fulla + 16 * i, 2); mbar_init(fulla + 16 * i + 8, 1); mbar_init(emptya + 8 * i, 4); }
    sts64(pace, 0, 0); mbar_init(pace + 8, 1); sts32(pace + 16, 0); sts64(pace + 24, 65536, 0xffff0000u);
    for (int i = 0; i < 4; i++) { mbar_init(full3 + 8 * i, 1); mbar_init(empty3 + 8 * i, cta < NH ? 8 : 4); }
    fence_async();
  }
  __syncthreads();
  ASTAMP(0);
  const bool wide = cta < NH;
  auto p3_ks = [&](int g) { return wide ? cta >> 2 : 2 * (cta - NH) + g; };
  auto p3_mt = [&](int g) { return wide ? 2 * (cta & 3) + g : 8; };
  const uint32_t xt = sb + (wide ? A_XT : A_IN), xw = sb + (wide ? A_XW : A_IN + 16384);
  const unsigned fbase = epoch * NSEG;
  if (wg == 3) {
    asm volatile("setmaxnreg.dec.sync.aligned.u32 48;");
    if (w == 1 && cta < NH) {
#pragma unroll 1
      for (int seg = 0; seg < ((XP & 2048) ? 0 : NSEG); seg++) {
        bar_arrive(5, 160);
        if (seg > 0 && lane == 0) {
          asm volatile("cp.async.bulk.wait_group 0;" ::: "memory");
          stg_relaxed32(&g_oflag[cta * 32], fbase + seg);
        }
        __syncwarp();
        bar_sync(4, 160);
        if (QM & 16) tick_wait(pace, seg + 1);
        if (lane == 0) {
          fence_async();
          if (!(YP & 2)) {
          tma_store(&tm.o, sb + A_OST, cta * DH, seg * 32);
          tma_store(&tm.o, sb + A_OST + 4096, cta * DH + 64, seg * 32);
          }
          asm volatile("cp.async.bulk.commit_group;" ::: "memory");
          asm volatile("cp.async.bulk.wait_group.read 0;" ::: "memory");
        }
        __syncwarp();
      }
      if (lane == 0) {
        asm volatile("cp.async.bulk.wait_group 0;" ::: "memory");
        { const int seg = NSEG - 1; TSTAMP(2); }
        stg_relaxed32(&g_oflag[cta * 32], fbase + NSEG);
      }
    }
    if (w == 2 && cta < NH) {
      const uint32_t ktag = (epoch + 1) & 1, ma = sb + A_IN + 8192 + lane * 16;
      int avail = 0;
      bar_sync(10, 64);
#pragma unroll 1
      for (int seg = 0; seg < ((XP & 2048) ? 0 : NSEG); seg++) {
        if (avail <= seg) avail = wait_flags(&g_sflag[(cta * 3 + min(lane, 2)) * 8], true, fbase, seg);
        if ((QM & 8) && seg < UNP) tick_wait(pace, seg);
        TSTAMP(0);
        const unsigned char* km = g_km + (size_t)(seg * NH + cta) * 4096 + lane * 8;
        uint32_t m[16];
        const float g = __ldcg(&g_gate[seg * 32 + lane]);
        ldg8x64<256>(m, km);
        const uint32_t b = seg & 1, full = fulla + 16 * b, mb = ma + b * A_INB;
        mbar_wait(emptya + 8 * b, (~seg >> 1) & 1);
        if (lane < 2) mbar_expect(full + 8 * lane, (YP & 8) ? 0 : 16384 >> lane);
        __syncwarp();
        if (lane < 3 && !(YP & 8)) ((EF & 2) ? bulk_load_ef : bulk_load)(sb + A_IN + b * A_INB + lane * SEGB, g_seg + ((size_t)(seg & RING) * 96 + cta * 3 + lane) * 8192, 8192, full + (lane & 2) * 4);
        int n = 0;
#pragma unroll 1
        while (stale<8, 2>(m, ktag) && ++n < SPIN_LIMIT) { if (seg < UNP - 1) __nanosleep(200); ldg8x64<256>(m, km); }
        TSTAMP(1);
#pragma unroll
        for (int i = 0; i < 4; i++) stsm4(mb + (i >> 1) * SEGB + (i & 1) * 512, m[4 * i], m[4 * i + 1], m[4 * i + 2], m[4 * i + 3]);
        sts32(sb + A_G + b * 128 + lane * 4, __float_as_uint(1.f - g));
        fence_async();
        __syncwarp();
        if (lane == 0) mbar_arrive(full);
      }
    }
    if (w == 3 && QM) {
      const unsigned char* const hp = tm.red + HINT_OFF + 65536 + (cta & 1) * 4096 + min(lane, 23) * 4;
      uint32_t d = 0;
      int s = 0, n = 0;
#pragma unroll 1
      while (s < NSEG - 1) {
        const uint32_t h = ldg_relaxed32(hp + RED_SLOT(s)), t = (gtime() - 1984) & ~31u, late = latest_hint(h, t, s);
        if (late < 64) {
          d = t + late * 32 + tm.poll + Q_LO;
          sleep_until(d);
          s++; n = 0;
          if (lane == 0) { mbar_arrive(pace + 8); sts64(pace, s < NSEG - 1 ? s : 2 * NSEG, d); }
          sleep_until(d + PACE_NEXT);
        } else {
          if (++n > (s ? 16 : 256) || lds32(pace + 16)) break;
          if (!s) __nanosleep(100);
        }
      }
      if (s < NSEG - 1 && lane == 0) { mbar_arrive(pace + 8); sts64(pace, 2 * NSEG, d); }
    }
    if (w != 0) return;
    const bool lead = lane == 0;
    if (ADLY) sleep_until(gtime() + ADLY);
    if (lead) {
#pragma unroll 1
      for (int it = 0, st = 0, ph = 1, k = 0, col = (cta & 1) * (DM / 2); it < ((XP & 256) ? 0 : 72); it++) {
        mbar_wait(empty1 + 8 * st, ph);
        if (QM & 1) quiet_wait(pace);
        mbar_expect(full1 + 8 * st, A_STAGE + 1536);
        tma_load3d(sb + st * A_STAGE, &tm.x, k, (cta >> 1) * A_ROWS - 7, 0, full1 + 8 * st);
        tma_load3d(sb + st * A_STAGE + 8192, &tm.wa, col, k, 0, full1 + 8 * st);
        tma_load3d(sb + A_W8 + st * 1536, &tm.wa8, col + 64, k, 0, full1 + 8 * st);
        if (++st == A_ST) { st = 0; ph ^= 1; }
        k += 32;
        if (k == DM) { k = 0; col += 72; }
      }
    }
    __syncwarp();
    auto load_wo = [&](uint32_t dst, int g, int kb, uint32_t mb) {
      if (kb < 64) tma_load(dst, &tm.wob, p3_mt(g) * 64, kb * 64, mb);
      else tma_load(dst, &tm.woa, p3_mt(g) * 64, (kb - 64) * 64, mb);
    };
    if (lead) mbar_expect(fullw, 16 * 8192);
#pragma unroll 1
    for (int st = 0; st < A_ST; st++) {
      if (!(XP & 256)) mbar_wait(empty1 + 8 * st, 1);
      if (lane < 16 && min(((lane + 1) * 8192 - 1) / A_STAGE, A_ST - 1) == st) load_wo(sb + lane * 8192, lane >> 3, p3_ks(lane >> 3) * 9 + (lane & 7), fullw);
      __syncwarp();
    }
    __syncwarp(); bar_sync(6, 288);
    if (lead) mbar_expect(fullw + 8, 2 * 8192);
    __syncwarp();
    if (lane < 2) load_wo(sb + (16 + lane) * 8192, lane, p3_ks(lane) * 9 + 8, fullw + 8);
    __syncwarp();
    if (lead) aux_barrier(1, epoch, p3_ks(1) == 7);
    __syncwarp(); bar_sync(6, 288);
    {
      int avail = 0, sl = 0, ph = 1;
      const int h = (9 * p3_ks(0) >> 1) + lane;
#pragma unroll 1
      for (int seg = 0; seg < ((XP & 2048) ? 0 : NSEG); seg++) {
        if (avail <= seg) avail = wait_flags(&g_oflag[min(h, NH - 1) * 32], lane < (wide ? 5 : 9), fbase, seg);
        SSTAMP(seg, 4);
        for (int g = 0; g < (wide ? 1 : 2); g++) {
          const int ks = p3_ks(g);
          mbar_wait(empty3 + 8 * sl, ph);
          if ((QM & 4) && tick_wait(pace, seg + (QM >> 4 & 1) + 1) && ODLY) __nanosleep(ODLY);
          if (lead && (YP & 4)) mbar_arrive(full3 + 8 * sl);
          else if (lead) {
            mbar_expect(full3 + 8 * sl, XT + (ks == 7 ? (seg ? 4096 : wide ? 20480 : 12288) : 0));
            tma_load3d(sb + sl * XT, &tm.o3, 0, seg * 32, ks * 9, full3 + 8 * sl);
            if (ks == 7) {
              tma_load(xt + sl * 4096, &tm.o, 72 * 64, seg * 32, full3 + 8 * sl);
              if (seg == 0) { load_wo(xw + 8192, 1, 72, full3 + 8 * sl); if (wide) load_wo(xw, 0, 72, full3 + 8 * sl); }
            }
          }
          __syncwarp();
          if (++sl == (wide ? 3 : 4)) { sl = 0; ph ^= 1; }
        }
      }
    }
    sts32(pace + 16, 1);
    __syncwarp(); bar_sync(6, 288);
    asm volatile("griddepcontrol.wait;" ::: "memory");
  } else if (wg == 2) {
    asm volatile("setmaxnreg.dec.sync.aligned.u32 64;");
    if (cta < NH) {
      if (tid == 256) { mbar_expect(fullg, 64 * DM * 2); bulk_load(sb + A_IN, x + cta * 64 * DM, 64 * DM * 2, fullg); }
      uint32_t gw[9];
#pragma unroll
      for (int j = 0; j < 9; j++) gw[j] = ((const uint32_t*)gate_w)[j * 32 + lane];
      mbar_wait(fullg, 0);
      float mine = 0.f;
#pragma unroll 4
      for (int u = 0; u < 16; u++) {
        float d0 = 0.f, d1 = 0.f;
#pragma unroll
        for (int j = 0; j < 9; j++) {
          const uint32_t a = lds32(sb + A_IN + (w * 16 + u) * (DM * 2) + j * 128 + lane * 4);
          d0 = fmaf(bf_lo(a), bf_lo(gw[j]), d0); d1 = fmaf(bf_hi(a), bf_hi(gw[j]), d1);
        }
        d0 = warp_sum(d0 + d1);
        if (lane == u) mine = d0;
      }
      if (lane < 16) g_gate[cta * 64 + w * 16 + lane] = 1.f / (1.f + __expf(-mine));
      fence_async();
    }
    bar_sync(3, 128);
    if (tid == 256) { aux_barrier(0, epoch); if (cta == 0) *(volatile unsigned*)&g_epoch2 = epoch + 1; }
    __syncwarp();
    bar_sync(3, 128);
    if (w == 0) bar_arrive(8, 288);
    if (w == 1 && cta < NH) bar_arrive(10, 64);
    if (cta < NH) {
      CDECL;
#pragma unroll 1
      for (int seg = 0; seg < ((XP & 2048) ? 0 : NSEG); seg++) {
        CSTAMP(0);
        const uint32_t in = sb + A_IN + (seg & 1) * A_INB;
        const uint64_t qd = make_desc(in, 128, 1024, 0);
        mbar_wait(fulla + 16 * (seg & 1), (seg >> 1) & 1);
        CSTAMP(3);
        SSTAMP(seg, 0);
        float d[2][16];
        {
          float a[20];
          uint32_t vm[16];
          const unsigned char* vp = g_km + (size_t)(seg * NH + cta) * 4096 + 2048 + lane * 16;
          if (w == 3) ldg4x128<512>(vm, vp);
          WG_FENCE();
#pragma unroll
          for (int k = 0; k < ((YP & 16) ? 1 : 8); k++) wgmma_n40_ss(a, qd + ((k >> 2) * SEGB + (k & 3) * 256 >> 4), qd + ((k >> 2) * SEGB + (k & 3) * 256 + 4096 >> 4), k > 0);
          const uint32_t ga = sb + A_G + (seg & 1) * 128 + (w & 1) * 64 + (lane >> 2) * 4;
          const float f0 = __uint_as_float(lds32(ga)), f1 = __uint_as_float(lds32(ga + 32));
          WG_COMMIT();
          WG_WAIT(0);
          CSTAMP(5);
          SSTAMP(seg, 1);
          if (w < 2) {
            const int lim = w * 16 + (lane >> 2) - 2 * (lane & 3);
            float m0 = -3.0e38f, m1 = -3.0e38f;
#pragma unroll
            for (int i = 0; i < 20; i++) {
              a[i] *= SM_SCALE * LOG2E;
              if (i < 16 && (i >> 2) * 8 + (i & 1) - (i & 2) * 4 > lim) a[i] = -1.0e9f * LOG2E;
              if (i & 2) m1 = fmaxf(m1, a[i]); else m0 = fmaxf(m0, a[i]);
            }
#pragma unroll
            for (int o = 1; o < 4; o <<= 1) { m0 = fmaxf(m0, __shfl_xor_sync(0xffffffffu, m0, o)); m1 = fmaxf(m1, __shfl_xor_sync(0xffffffffu, m1, o)); }
            float s0 = 0.f, s1 = 0.f;
#pragma unroll
            for (int i = 0; i < 20; i++) { a[i] = ex2(a[i] - (i & 2 ? m1 : m0)); if (i & 2) s1 += a[i]; else s0 += a[i]; }
#pragma unroll
            for (int o = 1; o < 4; o <<= 1) { s0 += __shfl_xor_sync(0xffffffffu, s0, o); s1 += __shfl_xor_sync(0xffffffffu, s1, o); }
            s0 = f0 * rcp(s0); s1 = f1 * rcp(s1);
            uint32_t p[10];
#pragma unroll
            for (int i = 0; i < 10; i++) p[i] = pack_bf16(a[2 * i] * (i & 1 ? s1 : s0), a[2 * i + 1] * (i & 1 ? s1 : s0));
            const uint32_t pa = sb + A_P + (2 * w + ((lane >> 3) & 1)) * 768 + (lane >> 4) * 128 + (lane & 7) * 16;
            stsm4t(pa, p[0], p[1], p[2], p[3]); stsm4t(pa + 256, p[4], p[5], p[6], p[7]); stsm4t(pa + 512, p[8], p[9], 0, 0);
            CSTAMP(6);
            fence_async();
            CSTAMP(7);
          } else if (w == 3) {
            int n = 0;
#pragma unroll 1
            while (stale<4, 4>(vm, (epoch + 1) & 1) && ++n < SPIN_LIMIT) ldg4x128<512>(vm, vp);
#pragma unroll
            for (int i = 0; i < 4; i++) stsm4(in + 2 * SEGB + 8192 + (lane >> 4) * 1024 + (lane & 15) * 16 + i * 256, vm[4 * i], vm[4 * i + 1], vm[4 * i + 2], vm[4 * i + 3]);
            fence_async();
            mbar_wait(fulla + 16 * (seg & 1) + 8, (seg >> 1) & 1);
          }
        }
        CSTAMP(8);

        bar_sync(5, 160);
        CSTAMP(10);
        SSTAMP(seg, 2);
        const uint64_t pd = make_desc(sb + A_P, 128, 768, 0), vd = make_desc(in + 2 * SEGB, 128, 512, 0), md = make_desc(in + 2 * SEGB + 8192, 0, 128, 0);
        WG_FENCE();
#pragma unroll
        for (int i = 0; i < 2; i++) {
          wgmma_n32_ss<0>(d[i], vd + i * 256, pd, 0);
          wgmma_n32_ss<0>(d[i], vd + i * 256 + 16, pd + 16, 1);
          wgmma_n32_ss<0>(d[i], md + i * 64, pd + 32, 1);
        }
        WG_COMMIT();
        WG_WAIT(0);
        CSTAMP(11);
        if (lane == 0) mbar_arrive(emptya + 8 * (seg & 1));
#pragma unroll
        for (int i = 0; i < 2; i++) {
          const uint32_t oa = sb + A_OST + i * 4096 + ((lane & 7) + ((lane >> 4) << 3)) * 128 + (((2 * w + ((lane >> 3) & 1)) ^ (lane & 7)) << 4);
          stsm4t(oa, pack_bf16(d[i][0], d[i][1]), pack_bf16(d[i][2], d[i][3]), pack_bf16(d[i][4], d[i][5]), pack_bf16(d[i][6], d[i][7]));
          stsm4t(oa + 2048, pack_bf16(d[i][8], d[i][9]), pack_bf16(d[i][10], d[i][11]), pack_bf16(d[i][12], d[i][13]), pack_bf16(d[i][14], d[i][15]));
        }
        CSTAMP(12);
        bar_sync(4, 160);
        SSTAMP(seg, 3);
      }
      CDUMP;
    }
  } else {
    asm volatile("setmaxnreg.inc.sync.aligned.u32 200;");
    {
      const int g = lane >> 2, t = lane & 3, r0 = (cta >> 1) * A_ROWS - 7 + w * 16;
      const uint32_t prev = (2 * t > g ? 0xffffu : 0u) | (2 * t + 1 > g ? 0xffff0000u : 0u);
      const int k0 = r0 + 2 * t - (2 * t > g ? 8 : 0), k1 = r0 + 2 * t + 1 - (2 * t + 1 > g ? 8 : 0);
      const uint32_t slot = sb + A_EXC + (wg * 4 + w) * 2304;
      float gl = 0.f, gh = 0.f;
      int st = 0, ph = 0;
#pragma unroll 1
      for (int p = -AWARM; p < ((XP & 256) ? 0 : 4); p++) {
        float big[96], sml[12];
        if (p == WPF && tid < 18) {
          const int kb = p3_ks(tid >= 9) * 9 + tid % 9;
          tma_prefetch(kb < 64 ? &tm.wob : &tm.woa, p3_mt(tid >= 9) * 64, (kb & 63) * 64);
        }
        __syncwarp();
#pragma unroll
        for (int i = 0; i < 96; i++) big[i] = 0.f;
#pragma unroll
        for (int i = 0; i < 12; i++) sml[i] = 0.f;
#pragma unroll 1
        for (int k = p < 0 ? 18 : 0; k < 18; k++) {
          mbar_wait(full1 + 8 * st, ph);
          const uint64_t da = make_desc(sb + st * A_STAGE + wg * 4096, 16, 512, 2);
          const uint64_t db = make_desc(sb + st * A_STAGE + 8192, 4096, 1024, 1), dc = make_desc(sb + A_W8 + st * 1536, 128, 512, 0);
          WG_FENCE();
#pragma unroll
          for (int j = 0; j < 2; j++) { wgmma_n192_ss_nt(big, da + j * 2, db + j * 128, 1); wgmma_n24_ss_nt(sml, da + j * 2, dc + j * 16, 1); }
          WG_COMMIT();
          WG_WAIT(1);
          if (k > 0 && lane == 0) mbar_arrive(empty1 + 8 * (st ? st - 1 : A_ST - 1));
          if (++st == A_ST) { st = 0; ph ^= 1; }
        }
        WG_WAIT(0);
        ASTAMP(16 + max(p, 0) + wg * 16);
        if (lane == 0 && p >= 0) mbar_arrive(empty1 + 8 * (st ? st - 1 : A_ST - 1));
        uint32_t f[3][9][2];
#pragma unroll
        for (int c = 0; c < 3; c++)
#pragma unroll
          for (int j = 0; j < 9; j++)
#pragma unroll
            for (int i = 0; i < 2; i++) {
              const float* a = j < 8 ? &big[(c * 8 + j) * 4 + 2 * i] : &sml[c * 4 + 2 * i];
              f[c][j][i] = c < 2 ? pack_bf16(a[0], a[1]) : trans8(pack_bf16(a[0], a[1]));
            }
        if (p == 0) {
          bar_sync(8, 288);
          gl = __ldcg(&g_gate[min(max(r0 + g, 0), S_LEN / 2 - 1) * 2 + wg]); gh = __ldcg(&g_gate[min(max(r0 + g + 8, 0), S_LEN / 2 - 1) * 2 + wg]);
        }
        asm volatile("cp.async.bulk.wait_group.read 0;" ::: "memory");
        __syncwarp();
#pragma unroll
        for (int j = 0; j < 8; j += 2) sts128(slot + j * 256 + lane * 16, f[1][j][1], f[2][j][1], f[1][j + 1][1], f[2][j + 1][1]);
        sts64(slot + 2048 + lane * 8, f[1][8][1], f[2][8][1]);
        bar_sync(1 + wg, 128);
        ASTAMP(24 + max(p, 0) + wg * 16);
        uint32_t pv[9][2];
#pragma unroll
        for (int j = 0; j < 9; j++) pv[j][0] = pv[j][1] = 0;
        if (w) {
#pragma unroll
          for (int j = 0; j < 8; j += 2) lds128(slot - 2304 + j * 256 + lane * 16, pv[j]);
          lds64(slot - 256 + lane * 8, pv[8][0], pv[8][1]);
        }
        float a[4][4], m[4][2];
#pragma unroll
        for (int h = 0; h < 4; h++) {
          const int j = 2 * h;
          const uint32_t qa[4] = {t >= h ? f[0][j][0] : 0, t >= h ? f[0][j][1] : 0, f[0][j + 1][0], f[0][j + 1][1]};
          const uint32_t qb0 = t <= h ? f[0][j + 2][0] : 0, qb1 = t <= h ? f[0][j + 2][1] : 0;
          float s0[4], s1[4], s2[4];
          mma16816z(s1, qa, f[1][j][0], f[1][j + 1][0]); mma16816z(s2, qa, f[1][j][1], f[1][j + 1][1]); mma16816z(s0, qa, pv[j][0], pv[j + 1][0]);
          mma1688(s1, qb0, qb1, f[1][j + 2][0]); mma1688(s2, qb0, qb1, f[1][j + 2][1]); mma1688(s0, qb0, qb1, pv[j + 2][0]);
          a[h][0] = 2 * t > g ? s0[0] : s1[0]; a[h][1] = 2 * t + 1 > g ? s0[1] : s1[1]; a[h][2] = 2 * t > g ? s1[2] : s2[2]; a[h][3] = 2 * t + 1 > g ? s1[3] : s2[3];
        }
#pragma unroll
        for (int h = 0; h < 4; h++) {
#pragma unroll
          for (int i = 0; i < 4; i++) a[h][i] = (i & 1 ? k1 : k0) + (i & 2) * 4 >= 0 ? a[h][i] * (0.23570226039551584f * LOG2E) : -1.0e9f * LOG2E;
          m[h][0] = fmaxf(a[h][0], a[h][1]); m[h][1] = fmaxf(a[h][2], a[h][3]);
        }
#pragma unroll
        for (int x = 1; x < 4; x <<= 1)
#pragma unroll
          for (int i = 0; i < 8; i++) m[i >> 1][i & 1] = fmaxf(m[i >> 1][i & 1], __shfl_xor_sync(0xffffffffu, m[i >> 1][i & 1], x));
#pragma unroll
        for (int h = 0; h < 4; h++) {
#pragma unroll
          for (int i = 0; i < 4; i++) a[h][i] = ex2(a[h][i] - m[h][i >> 1]);
          m[h][0] = a[h][0] + a[h][1]; m[h][1] = a[h][2] + a[h][3];
        }
#pragma unroll
        for (int x = 1; x < 4; x <<= 1)
#pragma unroll
          for (int i = 0; i < 8; i++) m[i >> 1][i & 1] += __shfl_xor_sync(0xffffffffu, m[i >> 1][i & 1], x);
        uint32_t o[9][2];
#pragma unroll
        for (int h = 0; h < 4; h++) {
          const int j = 2 * h;
          const float z0 = gl * rcp(m[h][0]), z1 = gh * rcp(m[h][1]);
          const uint32_t pl = pack_bf16(a[h][0] * z0, a[h][1] * z0), pu = pack_bf16(a[h][2] * z1, a[h][3] * z1);
          const uint32_t pa[4] = {pl & prev, 0, pl & ~prev, pu & prev};
          float d[3][4];
#pragma unroll
          for (int i = 0; i < 3; i++) mma16816z(d[i], pa, pv[j + i][1], f[2][j + i][0]);
#pragma unroll
          for (int i = 0; i < 3; i++) mma1688(d[i], 0, pu & ~prev, f[2][j + i][1]);
#pragma unroll
          for (int i = 0; i < 3; i++) {
            const uint32_t d0 = pack_bf16(d[i][0], d[i][1]), d1 = pack_bf16(d[i][2], d[i][3]);
            o[j + i][0] = i == 0 && h > 0 && t < h ? o[j][0] : d0;
            o[j + i][1] = i == 0 && h > 0 && t < h ? o[j][1] : d1;
          }
        }
        ASTAMP(28 + max(p, 0) + wg * 16);
        bar_sync(1 + wg, 128);
        const uint32_t oa = slot + (lane & 15) * 144 + (lane >> 4) * 16;
#pragma unroll
        for (int j = 0; j < 8; j += 2) stsm4(oa + j * 16, o[j][0], o[j][1], o[j + 1][0], o[j + 1][1]);
        asm volatile("stmatrix.sync.aligned.m8n8.x2.shared.b16 [%0], {%1,%2};" :: "r"(oa + 128), "r"(o[8][0]), "r"(o[8][1]) : "memory");
        fence_async();
        __syncwarp();
        if (QM & 64) quiet_wait(pace);
        if (lane < 16 && w * 16 + lane >= 7 && r0 + lane < S_LEN / 2 && p >= 0)
          asm volatile("cp.async.bulk.global.shared::cta.bulk_group [%0], [%1], 144;"
                       :: "l"(g_Ocat + (size_t)((r0 + lane) * 2 + wg) * KCAT + 4096 + (cta & 1) * (DM / 2) + p * 72), "r"(slot + lane * 144) : "memory");
        asm volatile("cp.async.bulk.commit_group;" ::: "memory");
        ASTAMP(20 + max(p, 0) + wg * 16);
      }
      if (XP & 256) bar_sync(8, 288);
      asm volatile("cp.async.bulk.wait_group 0;" ::: "memory");
    }
    ASTAMP(3);
    bar_arrive(6, 288);
    uint32_t wa[36][4];
    mbar_wait(fullw, 0);
    const uint32_t la = sb + ((lane & 7) + ((lane >> 4) << 3)) * 128 + (((2 * w + ((lane >> 3) & 1)) ^ (lane & 7)) << 4);
#pragma unroll
    for (int k = 0; k < 32; k++) ldsm4t(wa[k], la + wg * 65536 + k * 2048);
    mbar_wait(fullw + 8, 0);
#pragma unroll
    for (int k = 32; k < 36; k++) ldsm4t(wa[k], la + wg * 8192 + 65536 + k * 2048);
    fence_async();
    if (XP & 2048) bar_sync(6, 288); else bar_arrive(6, 288);
    ASTAMP(4);
    const int ks = p3_ks(wg), mt = p3_mt(wg);
    uint32_t v[16];
    auto fetch = [&](int seg) { ldg8x64<1024>(v, g_part + (((seg & 7) * 9 + mt) * 4 + (ks & 3)) * 1024 + (tid & 127)); };
    auto finish = [&](int seg) {
      const uint32_t tagv = (~seg >> 3) & 1;
      int n = 0;
#pragma unroll 1
      while (stale<8, 2>(v, tagv) && ++n < SPIN_LIMIT) {
        if (seg < NSEG - 2) __nanosleep(100);
        fetch(seg);
      }
      float own[4] = {bf_lo(v[0]), bf_hi(v[0]), bf_lo(v[1]), bf_hi(v[1])};
#pragma unroll
      for (int j = 1; j < 8; j++) { own[0] += bf_lo(v[2 * j]); own[1] += bf_hi(v[2 * j]); own[2] += bf_lo(v[2 * j + 1]); own[3] += bf_hi(v[2 * j + 1]); }
      uint32_t p0 = pack_bf16(own[0], own[1]), p1 = pack_bf16(own[2], own[3]);
      asm volatile("movmatrix.sync.aligned.m8n8.trans.b16 %0, %0;" : "+r"(p0));
      asm volatile("movmatrix.sync.aligned.m8n8.trans.b16 %0, %0;" : "+r"(p1));
      uint32_t* o = (uint32_t*)(out + (size_t)(seg * 32 + (ks & 3) * 8 + (lane >> 2)) * DM + mt * 64 + w * 16) + (lane & 3);
      o[0] = p0; o[4] = p1;
      SSTAMP(seg, 7);
    };
    float acc[16];
#pragma unroll
    for (int i = 0; i < 16; i++) acc[i] = 0.f;
    int pend = -1, sl = wide ? 0 : wg, ph = 0;
    if (PING && wg) bar_arrive(1, 256);
    CDECL;
    auto run = [&](auto extra) {
#pragma unroll 1
    for (int seg = 0; seg < ((XP & 2048) ? 0 : NSEG); seg++) {
      CSTAMP(0);
      const bool fin = pend >= 0 && seg - pend >= FLAG;
      if (FPOS == 0 && fin) fetch(pend);
      mbar_wait(full3 + 8 * sl, ph);
      if (FPOS == 1 && fin) fetch(pend);
      CSTAMP(1);
      if (wg) SSTAMP(seg, 5);
      if (seg < PING) bar_sync(1 + wg, 256);
      CSTAMP(7);
      const uint64_t db = make_desc(sb + sl * XT, 16, 1024, 1);
      WG_FENCE();
#pragma unroll
      for (int k = 0; k < ((XP & 1024) ? 1 : 36); k++) wgmma_n32_rs(acc, wa[k][0], wa[k][1], wa[k][2], wa[k][3], db + (k >> 2) * 256 + (k & 3) * 2, k);
      if (decltype(extra)::value) {
        const uint64_t da = make_desc(xw + wg * 8192, 8192, 1024, 1), de = make_desc(xt + sl * 4096, 16, 1024, 1);
#pragma unroll
        for (int j = 0; j < 4; j++) wgmma_n32_ss_tn(acc, da + j * 128, de + j * 2);
      }
      WG_COMMIT();
      if (seg < PING) bar_arrive(2 - wg, 256);
      CSTAMP(2);
      if (FPOS == 2 && fin) fetch(pend);
      CSTAMP(3);
      WG_WAIT(0);
      CSTAMP(4);
      if (wg) SSTAMP(seg, 6);
      if (lane == 0) mbar_arrive(empty3 + 8 * sl);
      sl += wide ? 1 : 2;
      if (sl >= (wide ? 3 : 4)) { sl -= wide ? 3 : 4; ph ^= 1; }
      uint2* dst = g_part + (((seg & 7) * 9 + mt) * 32 + ks) * 128 + (tid & 127);
      uint32_t q[8];
#pragma unroll
      for (int j = 0; j < 8; j++) q[j] = j & 1 ? pack_bf16(acc[2 * j], acc[2 * j + 1]) : (pack_bf16(acc[2 * j], acc[2 * j + 1]) & ~1u) | ((~seg >> 3) & 1);
      if (QM & 32) tick_wait(pace, seg + (QM >> 4 & 1) + 2);
      if (!(YP & 1) || q[0] == 0x12345678)
      asm volatile("st.relaxed.gpu.global.v2.b32 [%0], {%1,%2};\nst.relaxed.gpu.global.v2.b32 [%0 + 8192], {%3,%4};\n"
                   "st.relaxed.gpu.global.v2.b32 [%0 + 16384], {%5,%6};\nst.relaxed.gpu.global.v2.b32 [%0 + 24576], {%7,%8};"
                   :: "l"(dst), "r"(q[0]), "r"(q[1]), "r"(q[2]), "r"(q[3]), "r"(q[4]), "r"(q[5]), "r"(q[6]), "r"(q[7]) : "memory");
      CSTAMP(5);
      if (fin) { finish(pend); pend = -1; }
      CSTAMP(6);
      if ((seg & 1) == ks >> 2 && !(YP & 1)) pend = seg;
      if (wg && (seg & 7) == 6) ASTAMP(5 + (seg >> 3));
    }
    };
    if (ks == 7) run(BoolC<true>()); else run(BoolC<false>());
    if (PING && !wg) bar_sync(1, 256);
    if (pend >= 0) { fetch(pend); finish(pend); }
    CDUMP;
    ASTAMP(13);
    bar_sync(6, 288);
  }
}

typedef CUresult (*EncodeFn)(CUtensorMap*, CUtensorMapDataType, cuuint32_t, void*, const cuuint64_t*, const cuuint64_t*,
                             const cuuint32_t*, const cuuint32_t*, CUtensorMapInterleave, CUtensorMapSwizzle,
                             CUtensorMapL2promotion, CUtensorMapFloatOOBfill);
#define PROMO 2
static void make_map(EncodeFn enc, CUtensorMap* m, const void* p, int rows, int cols, int box_rows) {
  cuuint64_t dims[2] = {(cuuint64_t)cols, (cuuint64_t)rows};
  cuuint64_t strides[1] = {(cuuint64_t)cols * 2};
  cuuint32_t box[2] = {64, (cuuint32_t)box_rows};
  cuuint32_t es[2] = {1, 1};
  enc(m, CU_TENSOR_MAP_DATA_TYPE_BFLOAT16, 2, (void*)p, dims, strides, box, es, CU_TENSOR_MAP_INTERLEAVE_NONE,
      CU_TENSOR_MAP_SWIZZLE_128B, (CUtensorMapL2promotion)PROMO, CU_TENSOR_MAP_FLOAT_OOB_FILL_NONE);
}

constexpr int g_poll = POLL_NS;
extern "C" void kernel_launch(void* const* d_in, const int* in_sizes, int n_in, void* d_out, int out_size) {
  const bf16* x = (const bf16*)d_in[0];
  const bf16* wqkvA = (const bf16*)d_in[1];
  const bf16* woA = (const bf16*)d_in[2];
  const bf16* mem0 = (const bf16*)d_in[4];
  const bf16* Wq = (const bf16*)d_in[5];
  const bf16* Wk = (const bf16*)d_in[6];
  const bf16* Wv = (const bf16*)d_in[7];
  const bf16* Wo = (const bf16*)d_in[8];
  const bf16* gate_w = (const bf16*)d_in[10];
  static EncodeFn enc = nullptr;
  static void *pO = nullptr, *pR = nullptr;
  if (!enc) {
    cudaDriverEntryPointQueryResult qr;
    cudaGetDriverEntryPoint("cuTensorMapEncodeTiled", (void**)&enc, cudaEnableDefault, &qr);
    cudaGetSymbolAddress(&pO, g_Ocat);
    cudaGetSymbolAddress(&pR, g_red_raw);
    cudaFuncSetAttribute(rec_kernel, cudaFuncAttributeMaxDynamicSharedMemorySize, SM_TOTAL);
    cudaFuncSetAttribute(aux_kernel, cudaFuncAttributeMaxDynamicSharedMemorySize, A_TOTAL);
  }
  RMaps rm;
  rm.poll = g_poll;
  rm.w[0] = (const unsigned char*)Wk; rm.w[1] = (const unsigned char*)Wq; rm.w[2] = (const unsigned char*)Wv; rm.w[3] = (const unsigned char*)Wo;
  rm.red = (unsigned char*)(((uintptr_t)pR + 262143) & ~(uintptr_t)262143);
  {
    cuuint64_t dims[3] = {64, S_LEN, 9}, strides[2] = {DM * 2, 128};
    cuuint32_t box[3] = {64, 32, 9}, es[3] = {1, 1, 1};
    enc(&rm.x, CU_TENSOR_MAP_DATA_TYPE_BFLOAT16, 3, (void*)x, dims, strides, box, es, CU_TENSOR_MAP_INTERLEAVE_NONE,
        CU_TENSOR_MAP_SWIZZLE_128B, CU_TENSOR_MAP_L2_PROMOTION_L2_128B, CU_TENSOR_MAP_FLOAT_OOB_FILL_NONE);
  }
  make_map(enc, &rm.wq, Wq, DM, 4096, 192);
  make_map(enc, &rm.wk, Wk, DM, 4096, 192);
  make_map(enc, &rm.wv, Wv, DM, 4096, 192);
  make_map(enc, &rm.wo, Wo, 4096, DM, 128);
  AMaps am;
  am.red = rm.red; am.poll = rm.poll;
  {
    cuuint64_t dims[3] = {DM, S_LEN / 2, 2}, strides[2] = {DM * 4, DM * 2};
    cuuint32_t box[3] = {32, 64, 2}, es[3] = {1, 1, 1};
    enc(&am.x, CU_TENSOR_MAP_DATA_TYPE_BFLOAT16, 3, (void*)x, dims, strides, box, es, CU_TENSOR_MAP_INTERLEAVE_NONE,
        CU_TENSOR_MAP_SWIZZLE_64B, CU_TENSOR_MAP_L2_PROMOTION_L2_128B, CU_TENSOR_MAP_FLOAT_OOB_FILL_NONE);
    cuuint64_t wdims[3] = {DM, DM, 3}, wstrides[2] = {DM * 6, DM * 2};
    cuuint32_t wbox[3] = {64, 32, 3}, wbox8[3] = {8, 32, 3};
    enc(&am.wa, CU_TENSOR_MAP_DATA_TYPE_BFLOAT16, 3, (void*)wqkvA, wdims, wstrides, wbox, es, CU_TENSOR_MAP_INTERLEAVE_NONE,
        CU_TENSOR_MAP_SWIZZLE_128B, CU_TENSOR_MAP_L2_PROMOTION_L2_128B, CU_TENSOR_MAP_FLOAT_OOB_FILL_NONE);
    enc(&am.wa8, CU_TENSOR_MAP_DATA_TYPE_BFLOAT16, 3, (void*)wqkvA, wdims, wstrides, wbox8, es, CU_TENSOR_MAP_INTERLEAVE_NONE,
        CU_TENSOR_MAP_SWIZZLE_NONE, CU_TENSOR_MAP_L2_PROMOTION_NONE, CU_TENSOR_MAP_FLOAT_OOB_FILL_NONE);
  }
  {
    cuuint64_t dims[3] = {64, S_LEN, KCAT / 64}, strides[2] = {KCAT * 2, 128};
    cuuint32_t box[3] = {64, 32, 9}, es[3] = {1, 1, 1};
    make_map(enc, &am.o, pO, S_LEN, KCAT, 32);
    enc(&am.o3, CU_TENSOR_MAP_DATA_TYPE_BFLOAT16, 3, pO, dims, strides, box, es, CU_TENSOR_MAP_INTERLEAVE_NONE,
        CU_TENSOR_MAP_SWIZZLE_128B, CU_TENSOR_MAP_L2_PROMOTION_L2_128B, CU_TENSOR_MAP_FLOAT_OOB_FILL_NONE);
  }
  make_map(enc, &am.wob, Wo, 4096, DM, 64);
  make_map(enc, &am.woa, woA, DM, DM, 64);

  rec_kernel<<<96, 384, SM_TOTAL, cudaStreamPerThread>>>(rm, x, mem0);
  cudaLaunchConfig_t cfg = {};
  cfg.gridDim = dim3(NAUX); cfg.blockDim = dim3(512); cfg.dynamicSmemBytes = A_TOTAL; cfg.stream = cudaStreamPerThread;
  cudaLaunchAttribute at[1];
  at[0].id = cudaLaunchAttributeProgrammaticStreamSerialization; at[0].val.programmaticStreamSerializationAllowed = 1;
  cfg.attrs = at; cfg.numAttrs = 1;
  if (XP & 16) cfg.numAttrs = 0;
  if (!(XP & 64)) cudaLaunchKernelEx(&cfg, aux_kernel, am, x, gate_w, (bf16*)d_out);
}
```

```cpp
#include <cuda_runtime.h>
#include <cuda_bf16.h>
#include <cuda_fp16.h>
#include <cuda.h>
#include <stdint.h>

typedef __nv_bfloat16 bf16;

constexpr int S_LEN = 2048, DM = 576, NH = 32, DH = 128, NSEG = 64, KCAT = 4096 + 576;
#define RED_LINE(i) (((i) >> 2) * 4096 + ((i) & 1) * 256 + ((i) & 2) * 512)
#define RED_SLOT(s) (((s) & 1) * 128 + ((s) & 2) * 256)

#define POLL_NS 832
#define NII 18
#define W3PRE 4
#define W3MID 4
#define GF 0
#define B5POS 0
#define NUP 4
#define UPF 1
#define B3Q 9
#define B3F 0
#define GATE 8
#define NTL 2
#define B7R 1
#define EXPOS 0
#define VW2 1
#define CLR 1
#define RFW 0
#define NIC 0
#define LEAD 0
#define FIN16 1
#define VXG 0
#define RING 63
#define EXB 0
#define EXD 0
#define EXB2 8192
#define HDLY 0
#define F10 1
#define NPROBE 2
#define WPOS 1
#define CW 0
#define WOPF 0
#define YP 0
#define EF 7
#define KME 0
#define MO 0
#define EXV 2
#define NOB 0
#define QM 60
#define N5 224
#define KP(i) (((i) >> 1) + 4 * ((i) & 1))
#define SPIN_LIMIT (1 << 14)
#define XP 0

__device__ __align__(1024) bf16 g_Ocat[S_LEN * KCAT];
__device__ __align__(1024) unsigned char g_red_raw[2 * 262144];
constexpr int HINT_OFF = 2048;
__device__ __align__(16) float g_gate[S_LEN];
__device__ __align__(128) uint4 g_stats[96 * 2];
__device__ unsigned g_epoch;
__device__ unsigned g_epoch2;
__device__ unsigned g_oflag[NH * 32];
__device__ unsigned g_abar[3 * 32];
__device__ unsigned g_sflag[96 * 8];
__device__ __align__(1024) unsigned char g_seg[NSEG * 96 * 8192];
__device__ __align__(1024) unsigned char g_km[NSEG * NH * 4096];
__device__ __align__(1024) uint2 g_part[8 * 9 * 4 * 8 * 128];
__device__ int g_err;
#define SSTAMP(seg, idx)
#define TSTAMP(idx)
#define QSTAMP(idx)
#define PROF(idx)
#define PROFP(idx)
#define STAMP(idx)
#define ASTAMP(idx)
#define WSTAMP(idx)

#define CSTAMP(idx)
#define CDECL
#define CDUMP
#define DI __device__ __forceinline__
DI uint32_t smem_u32(const void* p) { return (uint32_t)__cvta_generic_to_shared(p); }
DI uint32_t clock32() { uint32_t c; asm volatile("mov.u32 %0, %%clock;" : "=r"(c) :: "memory"); return c; }
DI uint32_t gtime() { uint32_t c; asm volatile("mov.u32 %0, %%globaltimer_lo;" : "=r"(c) :: "memory"); return c; }
DI uint32_t ldg_relaxed32(const void* p) { uint32_t v; asm volatile("ld.relaxed.gpu.global.b32 %0, [%1];" : "=r"(v) : "l"(p) : "memory"); return v; }
DI uint32_t ldg_acquire32(const void* p) { uint32_t v; asm volatile("ld.acquire.gpu.global.b32 %0, [%1];" : "=r"(v) : "l"(p) : "memory"); return v; }
DI void stg_relaxed32(void* p, uint32_t v) { asm volatile("st.relaxed.gpu.global.b32 [%0], %1;" :: "l"(p), "r"(v) : "memory"); }
DI int head_id() { int c; asm volatile("mov.u32 %0, %%clusterid.x;" : "=r"(c)); return c; }
DI uint32_t mapa(uint32_t a, uint32_t r) { uint32_t o; asm("mapa.shared::cluster.u32 %0, %1, %2;" : "=r"(o) : "r"(a), "r"(r)); return o; }
DI void cluster_arrive() { asm volatile("barrier.cluster.arrive.relaxed.aligned;" ::: "memory"); }
DI void cluster_wait() { asm volatile("barrier.cluster.wait.aligned;" ::: "memory"); }
DI void cluster_sync() { asm volatile("barrier.cluster.arrive.release.aligned;\nbarrier.cluster.wait.acquire.aligned;" ::: "memory"); }
DI void mbar_init(uint32_t b, uint32_t c) { asm volatile("mbarrier.init.shared::cta.b64 [%0], %1;" :: "r"(b), "r"(c) : "memory"); }
DI void mbar_expect(uint32_t b, uint32_t tx) { asm volatile("mbarrier.arrive.expect_tx.shared::cta.b64 _, [%0], %1;" :: "r"(b), "r"(tx) : "memory"); }
DI void mbar_arrive(uint32_t b) { asm volatile("mbarrier.arrive.shared::cta.b64 _, [%0];" :: "r"(b) : "memory"); }
DI void mbar_wait(uint32_t b, uint32_t par) {
  asm volatile("{\n.reg .pred p;\n.reg .u32 n, q;\nmov.u32 n, 0;\n"
               "WL: add.u32 n, n, 1;\nshr.u32 q, n, 12;\nxor.b32 q, q, %1;\n"
               "mbarrier.try_wait.parity.shared::cta.b64 p, [%0], q;\n@!p bra.uni WL;\n}"
               :: "r"(b), "r"(par) : "memory");
}
DI void wait_until(uint32_t t) {
  const uint32_t now = gtime();
  t = min(t, now + 8192);
  asm volatile("{\n.reg .pred p;\n.reg .u32 c;\nTL: mov.u32 c, %%globaltimer_lo;\nsetp.lt.u32 p, c, %0;\n@p bra.uni TL;\n}" :: "r"(t) : "memory");
}
#define PIN(v) v = __shfl_xor_sync(0xffffffffu, v, 0)
#define SCHED_FENCE(k) asm volatile("{\n.reg .pred p;\nsetp.eq.u32 p, %0, %1;\n@p exit;\n}" :: "r"(fence_reg), "r"(k) : "memory")
#define MEM_ORDER(k) asm volatile("{\n.reg .pred p;\nsetp.eq.u32 p, %0, %1;\n@p st.shared.u32 [%0], %0;\n}" :: "r"(fence_reg), "r"(k + 64) : "memory")
DI void bar_sync(int id, int n) { asm volatile("bar.sync %0, %1;" :: "r"(id), "r"(n) : "memory"); }
DI void bar_arrive(int id, int n) { asm volatile("bar.arrive %0, %1;" :: "r"(id), "r"(n) : "memory"); }
DI void fence_async() { asm volatile("fence.proxy.async.shared::cta;" ::: "memory"); }
DI void st_async4(uint32_t a, uint32_t x, uint32_t y, uint32_t z, uint32_t w, uint32_t mb) {
  asm volatile("st.async.weak.shared::cluster.mbarrier::complete_tx::bytes.v4.b32 [%0], {%1,%2,%3,%4}, [%5];"
               :: "r"(a), "r"(x), "r"(y), "r"(z), "r"(w), "r"(mb) : "memory");
}
DI void st_async2(uint32_t a, uint32_t x, uint32_t y, uint32_t mb) {
  asm volatile("st.async.weak.shared::cluster.mbarrier::complete_tx::bytes.v2.b32 [%0], {%1,%2}, [%3];"
               :: "r"(a), "r"(x), "r"(y), "r"(mb) : "memory");
}
DI void sts32(uint32_t a, uint32_t x) { asm volatile("st.shared.b32 [%0], %1;" :: "r"(a), "r"(x) : "memory"); }
DI void sts64(uint32_t a, uint32_t x, uint32_t y) { asm volatile("st.shared.v2.b32 [%0], {%1,%2};" :: "r"(a), "r"(x), "r"(y) : "memory"); }
DI void sts128(uint32_t a, uint32_t x, uint32_t y, uint32_t z, uint32_t w) {
  asm volatile("st.shared.v4.b32 [%0], {%1,%2,%3,%4};" :: "r"(a), "r"(x), "r"(y), "r"(z), "r"(w) : "memory");
}
DI uint32_t lds32(uint32_t a) { uint32_t x; asm volatile("ld.shared.b32 %0, [%1];" : "=r"(x) : "r"(a) : "memory"); return x; }
DI uint32_t lds32v(uint32_t a) { uint32_t x; asm volatile("ld.volatile.shared.b32 %0, [%1];" : "=r"(x) : "r"(a) : "memory"); return x; }
DI void lds64(uint32_t a, uint32_t& x, uint32_t& y) { asm volatile("ld.shared.v2.b32 {%0,%1}, [%2];" : "=r"(x), "=r"(y) : "r"(a) : "memory"); }
DI void lds128(uint32_t a, uint32_t* r) {
  asm volatile("ld.shared.v4.b32 {%0,%1,%2,%3}, [%4];" : "=r"(r[0]), "=r"(r[1]), "=r"(r[2]), "=r"(r[3]) : "r"(a) : "memory");
}
DI void lds128f(uint32_t a, float* r) {
  asm volatile("ld.shared.v4.f32 {%0,%1,%2,%3}, [%4];" : "=f"(r[0]), "=f"(r[1]), "=f"(r[2]), "=f"(r[3]) : "r"(a) : "memory");
}
DI void lds64f(uint32_t a, float* r) { asm volatile("ld.shared.v2.f32 {%0,%1}, [%2];" : "=f"(r[0]), "=f"(r[1]) : "r"(a) : "memory"); }
DI void ldsm4t(uint32_t* r, uint32_t a) {
  asm volatile("ldmatrix.sync.aligned.m8n8.x4.trans.shared.b16 {%0,%1,%2,%3}, [%4];"
               : "=r"(r[0]), "=r"(r[1]), "=r"(r[2]), "=r"(r[3]) : "r"(a) : "memory");
}
DI void ldsm4t_in(uint32_t* r, uint32_t a, uint32_t t) {
  asm volatile("{\n.reg .pred p;\nsetp.ne.u32 p, %5, 0;\n@p ldmatrix.sync.aligned.m8n8.x4.trans.shared.b16 {%0,%1,%2,%3}, [%4];\n}"
               : "+r"(r[0]), "+r"(r[1]), "+r"(r[2]), "+r"(r[3]) : "r"(a), "r"(t) : "memory");
}
DI void lds128_in(uint32_t* r, uint32_t a, uint32_t t) {
  asm volatile("{\n.reg .pred p;\nsetp.ne.u32 p, %5, 0;\n@p ld.shared.v4.b32 {%0,%1,%2,%3}, [%4];\n}"
               : "+r"(r[0]), "+r"(r[1]), "+r"(r[2]), "+r"(r[3]) : "r"(a), "r"(t) : "memory");
}
DI void ldsm2t_in(uint32_t* r, uint32_t a, uint32_t t) {
  asm volatile("{\n.reg .pred p;\nsetp.ne.u32 p, %3, 0;\n@p ldmatrix.sync.aligned.m8n8.x2.trans.shared.b16 {%0,%1}, [%2];\n}" : "+r"(r[0]), "+r"(r[1]) : "r"(a), "r"(t) : "memory");
}
DI void reserve2(uint32_t* r) { asm volatile("{\n.reg .u64 t;\nmov.u64 t, %%clock64;\nmov.b64 {%0, %1}, t;\n}" : "=r"(r[0]), "=r"(r[1])); }
DI void scale_sum(float& x, float& y, float s, uint32_t t) {
  asm volatile("{\n.reg .pred p;\nsetp.ne.u32 p, %2, 0;\n@p mul.f32 %0, %0, %1;\n}" : "+f"(y) : "f"(s), "r"(t));
  asm volatile("{\n.reg .pred p;\nsetp.ne.u32 p, %3, 1;\n@p fma.rn.f32 %0, %0, %1, %2;\n}" : "+f"(x) : "f"(s), "f"(y), "r"(t));
}
DI void ldsm4(uint32_t* r, uint32_t a) {
  asm volatile("ldmatrix.sync.aligned.m8n8.x4.shared.b16 {%0,%1,%2,%3}, [%4];"
               : "=r"(r[0]), "=r"(r[1]), "=r"(r[2]), "=r"(r[3]) : "r"(a) : "memory");
}
DI void st_async1(uint32_t a, uint32_t x, uint32_t mb) {
  asm volatile("st.async.weak.shared::cluster.mbarrier::complete_tx::bytes.b32 [%0], %1, [%2];" :: "r"(a), "r"(x), "r"(mb) : "memory");
}
DI void stsm4(uint32_t a, uint32_t x, uint32_t y, uint32_t z, uint32_t w) {
  asm volatile("stmatrix.sync.aligned.m8n8.x4.shared.b16 [%0], {%1,%2,%3,%4};" :: "r"(a), "r"(x), "r"(y), "r"(z), "r"(w) : "memory");
}
DI void stsm4t(uint32_t a, uint32_t x, uint32_t y, uint32_t z, uint32_t w) {
  asm volatile("stmatrix.sync.aligned.m8n8.x4.trans.shared.b16 [%0], {%1,%2,%3,%4};" :: "r"(a), "r"(x), "r"(y), "r"(z), "r"(w) : "memory");
}
DI uint32_t pack_bf16(float lo, float hi) { uint32_t r; asm("cvt.rn.bf16x2.f32 %0, %1, %2;" : "=r"(r) : "f"(hi), "f"(lo)); return r; }
DI uint32_t pack_f16(float lo, float hi) { uint32_t r; asm("cvt.rn.f16x2.f32 %0, %1, %2;" : "=r"(r) : "f"(hi), "f"(lo)); return r; }
DI float ex2(float x) { float y; asm("ex2.approx.ftz.f32 %0, %1;" : "=f"(y) : "f"(x)); return y; }
DI float rcp(float x) { float y; asm("rcp.approx.ftz.f32 %0, %1;" : "=f"(y) : "f"(x)); return y; }
DI float bf_lo(uint32_t x) { return __uint_as_float(x << 16); }
DI float bf_hi(uint32_t x) { return __uint_as_float(x & 0xffff0000u); }
DI void mma16816(float* d, const uint32_t* a, uint32_t b0, uint32_t b1) {
  asm volatile("mma.sync.aligned.m16n8k16.row.col.f32.bf16.bf16.f32 {%0,%1,%2,%3}, {%4,%5,%6,%7}, {%8,%9}, {%0,%1,%2,%3};"
               : "+f"(d[0]), "+f"(d[1]), "+f"(d[2]), "+f"(d[3]) : "r"(a[0]), "r"(a[1]), "r"(a[2]), "r"(a[3]), "r"(b0), "r"(b1));
}
DI void mma16816z(float* d, const uint32_t* a, uint32_t b0, uint32_t b1) {
  asm volatile("mma.sync.aligned.m16n8k16.row.col.f32.bf16.bf16.f32 {%0,%1,%2,%3}, {%4,%5,%6,%7}, {%8,%9}, {%10,%10,%10,%10};"
               : "=f"(d[0]), "=f"(d[1]), "=f"(d[2]), "=f"(d[3]) : "r"(a[0]), "r"(a[1]), "r"(a[2]), "r"(a[3]), "r"(b0), "r"(b1), "f"(0.f));
}
DI void mma1688z(float* d, uint32_t a0, uint32_t a1, uint32_t b0) {
  asm volatile("mma.sync.aligned.m16n8k8.row.col.f32.bf16.bf16.f32 {%0,%1,%2,%3}, {%4,%5}, {%6}, {%7,%7,%7,%7};"
               : "=f"(d[0]), "=f"(d[1]), "=f"(d[2]), "=f"(d[3]) : "r"(a0), "r"(a1), "r"(b0), "f"(0.f));
}
DI void mma1688(float* d, uint32_t a0, uint32_t a1, uint32_t b0) {
  asm volatile("mma.sync.aligned.m16n8k8.row.col.f32.bf16.bf16.f32 {%0,%1,%2,%3}, {%4,%5}, {%6}, {%0,%1,%2,%3};"
               : "+f"(d[0]), "+f"(d[1]), "+f"(d[2]), "+f"(d[3]) : "r"(a0), "r"(a1), "r"(b0));
}
DI void ldsm2t(uint32_t* r, uint32_t a) {
  asm volatile("ldmatrix.sync.aligned.m8n8.x2.trans.shared.b16 {%0,%1}, [%2];" : "=r"(r[0]), "=r"(r[1]) : "r"(a) : "memory");
}
DI uint32_t add_bf16(uint32_t a, uint32_t b) { uint32_t r; asm("add.rn.bf16x2 %0, %1, %2;" : "=r"(r) : "r"(a), "r"(b)); return r; }
DI uint32_t mul_bf16(uint32_t a, uint32_t b) { uint32_t r; asm("mul.rn.bf16x2 %0, %1, %2;" : "=r"(r) : "r"(a), "r"(b)); return r; }
DI uint64_t make_desc(uint32_t addr, uint32_t lbo, uint32_t sbo, uint32_t swz) {
  return (uint64_t)((addr & 0x3FFFF) >> 4) | ((uint64_t)(lbo >> 4) << 16) | ((uint64_t)(sbo >> 4) << 32) | ((uint64_t)swz << 62);
}
#define WG_FENCE() asm volatile("wgmma.fence.sync.aligned;" ::: "memory")
#define WG_COMMIT() asm volatile("wgmma.commit_group.sync.aligned;" ::: "memory")
#define WG_WAIT(n) asm volatile("wgmma.wait_group.sync.aligned %0;" :: "n"(n) : "memory")
#define ACC8(d, o) "+f"(d[o]), "+f"(d[o + 1]), "+f"(d[o + 2]), "+f"(d[o + 3]), "+f"(d[o + 4]), "+f"(d[o + 5]), "+f"(d[o + 6]), "+f"(d[o + 7])
DI void wgmma_n32_rs(float* d, uint32_t a0, uint32_t a1, uint32_t a2, uint32_t a3, uint64_t db, int acc) {
  asm volatile("{\n.reg .pred p;\nsetp.ne.b32 p, %21, 0;\n"
               "wgmma.mma_async.sync.aligned.m64n32k16.f32.bf16.bf16 {%0,%1,%2,%3,%4,%5,%6,%7,%8,%9,%10,%11,%12,%13,%14,%15}, "
               "{%16,%17,%18,%19}, %20, p, 1, 1, 0;\n}\n"
               : ACC8(d, 0), ACC8(d, 8) : "r"(a0), "r"(a1), "r"(a2), "r"(a3), "l"(db), "r"(acc));
}
template <int TA>
DI void wgmma_n32_ss(float* d, uint64_t da, uint64_t db, int acc) {
  asm volatile("{\n.reg .pred p;\nsetp.ne.b32 p, %18, 0;\n"
               "wgmma.mma_async.sync.aligned.m64n32k16.f32.bf16.bf16 {%0,%1,%2,%3,%4,%5,%6,%7,%8,%9,%10,%11,%12,%13,%14,%15}, "
               "%16, %17, p, 1, 1, %19, 1;\n}\n"
               : ACC8(d, 0), ACC8(d, 8) : "l"(da), "l"(db), "r"(acc), "n"(TA));
}
DI void tma_load(uint32_t dst, const CUtensorMap* m, int c0, int c1, uint32_t mb) {
  asm volatile("cp.async.bulk.tensor.2d.shared::cluster.global.mbarrier::complete_tx::bytes [%0], [%1, {%3, %4}], [%2];"
               :: "r"(dst), "l"(m), "r"(mb), "r"(c0), "r"(c1) : "memory");
}
DI void tma_load3(uint32_t dst, const CUtensorMap* m, int row, uint32_t mb) {
  asm volatile("cp.async.bulk.tensor.3d.shared::cluster.global.mbarrier::complete_tx::bytes [%0], [%1, {%3, %4, %3}], [%2];"
               :: "r"(dst), "l"(m), "r"(mb), "r"(0), "r"(row) : "memory");
}
DI bool elect_one() {
  uint32_t p;
  asm volatile("{\n.reg .pred p;\nelect.sync _|p, 0xffffffff;\nselp.u32 %0, 1, 0, p;\n}" : "=r"(p));
  return p;
}
DI void bulk_s2s(uint32_t dst, uint32_t src, uint32_t bytes, uint32_t mb) {
  asm volatile("cp.async.bulk.shared::cluster.shared::cta.mbarrier::complete_tx::bytes [%0], [%1], %2, [%3];"
               :: "r"(dst), "r"(src), "r"(bytes), "r"(mb) : "memory");
}
DI void bulk_load(uint32_t dst, const void* src, uint32_t bytes, uint32_t mb) {
  asm volatile("cp.async.bulk.shared::cluster.global.mbarrier::complete_tx::bytes [%0], [%1], %2, [%3];" :: "r"(dst), "l"(src), "r"(bytes), "r"(mb) : "memory");
}
#define EVICT_FIRST ".reg .b64 pol;\ncreatepolicy.fractional.L2::evict_first.b64 pol, 1.0;\n"
DI void bulk_load_ef(uint32_t dst, const void* src, uint32_t bytes, uint32_t mb) {
  asm volatile("{\n" EVICT_FIRST "cp.async.bulk.shared::cluster.global.mbarrier::complete_tx::bytes.L2::cache_hint [%0], [%1], %2, [%3], pol;\n}"
               :: "r"(dst), "l"(src), "r"(bytes), "r"(mb) : "memory");
}
DI void tma_load_ef(uint32_t dst, const CUtensorMap* m, int c0, int c1, uint32_t mb) {
  asm volatile("{\n" EVICT_FIRST "cp.async.bulk.tensor.2d.shared::cluster.global.mbarrier::complete_tx::bytes.L2::cache_hint [%0], [%1, {%3, %4}], [%2], pol;\n}"
               :: "r"(dst), "l"(m), "r"(mb), "r"(c0), "r"(c1) : "memory");
}
DI void tma_prefetch(const CUtensorMap* m, int c0, int c1) {
  asm volatile("cp.async.bulk.prefetch.tensor.2d.L2.global.tile [%0, {%1, %2}];" :: "l"(m), "r"(c0), "r"(c1) : "memory");
}
DI void tma_store(const CUtensorMap* m, uint32_t src, int c0, int c1) {
  asm volatile("cp.async.bulk.tensor.2d.global.shared::cta.bulk_group [%0, {%2, %3}], [%1];" :: "l"(m), "r"(src), "r"(c0), "r"(c1) : "memory");
}
DI uint4 ldg_relaxed(const void* p) {
  uint4 v;
  asm volatile("ld.relaxed.gpu.global.v4.b32 {%0,%1,%2,%3}, [%4];" : "=r"(v.x), "=r"(v.y), "=r"(v.z), "=r"(v.w) : "l"(p) : "memory");
  return v;
}
DI void stg_relaxed(void* p, uint32_t x, uint32_t y, uint32_t z, uint32_t w) {
  asm volatile("st.relaxed.gpu.global.v4.b32 [%0], {%1,%2,%3,%4};" :: "l"(p), "r"(x), "r"(y), "r"(z), "r"(w) : "memory");
}
DI void red_f16x8(void* p, uint32_t x, uint32_t y, uint32_t z, uint32_t w) {
  asm volatile("red.relaxed.gpu.global.add.noftz.v4.f16x2 [%0], {%1,%2,%3,%4};" :: "l"(p), "r"(x), "r"(y), "r"(z), "r"(w) : "memory");
}
DI void sq_acc(uint32_t& a, uint32_t x) { asm("fma.rn.bf16x2 %0, %1, %1, %0;" : "+r"(a) : "r"(x)); }
DI __half2 amax4(__half2 h, const uint32_t* v) {
  h = __hmax2_nan(__hmax2_nan(h, __habs2(*(const __half2*)&v[0])), __habs2(*(const __half2*)&v[1]));
  return __hmax2_nan(__hmax2_nan(h, __habs2(*(const __half2*)&v[2])), __habs2(*(const __half2*)&v[3]));
}
DI uint32_t wexp(__half2 h) { const uint32_t u = *(const uint32_t*)&h; return __reduce_max_sync(0xffffffffu, max((u >> 16) & 0x7fffu, u & 0x7fffu)) >> 7; }
DI float max10(const float* a) {
  return fmaxf(fmaxf(fmaxf(fmaxf(a[0], a[1]), fmaxf(a[2], a[3])), fmaxf(fmaxf(a[4], a[5]), fmaxf(a[6], a[7]))), fmaxf(a[8], a[9]));
}
DI float quad_max(float m) {
  return fmaxf(fmaxf(m, __shfl_xor_sync(0xffffffffu, m, 1)), fmaxf(__shfl_xor_sync(0xffffffffu, m, 2), __shfl_xor_sync(0xffffffffu, m, 3)));
}
DI float warp_sum(float v) {
#pragma unroll
  for (int o = 16; o; o >>= 1) v += __shfl_xor_sync(0xffffffffu, v, o);
  return v;
}

constexpr int SM_WO3 = 0;
constexpr int SM_X = 16384;
constexpr int XT = 36864;
constexpr int SM_EXP = 126976;
constexpr int SEGB = 10240;
constexpr int SM_BLK = SM_EXP + 8192;
constexpr int SM_VC = SM_BLK + 4 * SEGB;
constexpr int SM_PART = SM_VC + 16384;
constexpr int SM_QM = SM_PART + 4096;
constexpr int SM_E = SM_QM + 1024;
constexpr int SM_VM = SM_E + 1536;
constexpr int SM_OB = SM_VM + 2048;
constexpr int SM_FB = SM_OB + 2048;
constexpr int SM_STAGE = SM_X + XT;
constexpr int SM_M0 = SM_STAGE + 3 * 49152;
constexpr int SM_MISC = 210944;
constexpr int SM_WOST = 212992;
constexpr int SM_MEM = SM_WOST;
constexpr int SM_MAX = SM_MEM + 11264;
#define MEM_BLK(q) ((q) / 3 * 4096 + (q) % 3 * 1024)
constexpr int SM_TOTAL = 229376;
constexpr int MB_W = SM_MISC;
constexpr int MB_WO = SM_MISC + 24;
constexpr int MB_WO3 = SM_MISC + 32;
constexpr int MB_X = SM_MISC + 40;
constexpr int MB_S = SM_MISC + 64;
constexpr int MB_F = SM_MISC + 72;
constexpr int MB_VX = SM_MISC + 80;
constexpr int SC_FPAR = SM_MISC + 136;
constexpr int SC_DEAD = SM_MISC + 96;
constexpr int SC_UNSC = SM_MISC + 112;
constexpr int SC_EXPW = SM_MISC + 132;
constexpr int SC_ONES = SM_MISC + 144;
constexpr int SC_SS = SM_MISC + 160;
constexpr int SC_LAT = SM_MISC + 224;
constexpr int SC_EPO = SM_MISC + 240;
constexpr int MB_XS = SM_MISC + 248;
constexpr int SC_XMAX = SM_MISC + 256;
constexpr int SC_PROF = 229376;

constexpr float SM_SCALE = 0.08838834764831845f;
constexpr float LOG2E = 1.4426950408889634f;
constexpr float E_LIM = 20.f;

template <bool B> struct BoolC { static constexpr bool value = B; };
template <int I> struct IntC { static constexpr int value = I; };
struct RMaps { CUtensorMap x, wq, wk, wv, wo; unsigned char* red; uint32_t poll; const unsigned char* w[4]; };

DI uint32_t latest_hint(uint32_t h, uint32_t d, int s) {
  const uint32_t x = (((h | 0xc0c0c0c0u) - ((d >> 5) & 63) * 0x01010101u) & 0x3f3f3f3fu) | ((h ^ (((s >> 2) + 1) & 3) * 0x40404040u) & 0xc0c0c0c0u);
  const uint32_t y = __vmaxu2(x & 0x00ff00ffu, (x >> 8) & 0x00ff00ffu);
  return __reduce_max_sync(0xffffffffu, max(y & 0xffffu, y >> 16));
}
DI uint32_t near_half(uint32_t sb) {
  uint32_t a, b; lds64(sb + SC_LAT, a, b);
  return a > b;
}

template <int RT, int K0, int K1, bool D32 = false>
DI void xproj(float* acc, const uint32_t (&wa)[2][18][4], uint64_t xd) {
  if (XP & 1) return;
  WG_FENCE();
#pragma unroll
  for (int k = K0; k < ((XP & 128) ? K0 + 1 : K1); k++)
  {
    uint64_t d = xd + (uint64_t)(((k >> 1) * 4096 + (k & 1) * 32) >> 4);
    if (D32) asm("mov.b64 %0, {%1, %2};" : "=l"(d) : "r"((uint32_t)xd + (((k >> 1) * 4096 + (k & 1) * 32) >> 4)), "r"((uint32_t)(xd >> 32)));
    wgmma_n32_rs(acc, wa[RT][k][0], wa[RT][k][1], wa[RT][k][2], wa[RT][k][3], d, k != 0);
  }
  WG_COMMIT();
}

DI void load_w(uint32_t sb, const RMaps& tm, uint32_t rank, int c) {
  const int h = blockIdx.x / 3;
  mbar_expect(sb + MB_W + 8 * c, 49152);
  ((EF & 4) ? tma_load_ef : tma_load)(sb + SM_STAGE + c * 49152, rank < 2 ? &tm.wk : &tm.wv, h * DH + (rank == 1 ? 64 : 0), c * 192, sb + MB_W + 8 * c);
  ((EF & 4) ? tma_load_ef : tma_load)(sb + SM_STAGE + c * 49152 + 24576, rank < 2 ? &tm.wq : &tm.wv, h * DH + (rank == 0 ? 0 : 64), c * 192, sb + MB_W + 8 * c);
}
DI void seg_store(int seg, uint32_t sb) {
  fence_async();
  if (EF & 1)
    asm volatile("{\n" EVICT_FIRST "cp.async.bulk.global.shared::cta.bulk_group.L2::cache_hint [%0], [%1], 8192, pol;\n}"
                 :: "l"(g_seg + ((size_t)(seg & RING) * 96 + blockIdx.x) * 8192), "r"(sb + SM_BLK + (seg & 3) * SEGB) : "memory");
  else
  asm volatile("cp.async.bulk.global.shared::cta.bulk_group [%0], [%1], 8192;"
               :: "l"(g_seg + ((size_t)(seg & RING) * 96 + blockIdx.x) * 8192), "r"(sb + SM_BLK + (seg & 3) * SEGB) : "memory");
  asm volatile("cp.async.bulk.commit_group;" ::: "memory");
}
DI void seg_publish(int seg, uint32_t sb) {
  const uint32_t v = lds32(sb + SC_EPO) + seg;
  asm volatile("cp.async.bulk.wait_group 0;" ::: "memory");
  stg_relaxed32(&g_sflag[blockIdx.x * 8], v);
}

DI void proj_role(const uint32_t sb, const RMaps& tm, const uint32_t rank, const int wg, const int w, const int lane) {
  const bool qk = rank < 2;
  uint32_t wa[2][18][4];
  float acc[16];
  const uint64_t xd0 = make_desc(sb + SM_X + wg * 64, 16, 1024, 1);
  {
    const int rr = (lane & 7) + ((lane >> 4) << 3);
    const uint32_t col = ((2 * w + ((lane >> 3) & 1)) ^ (lane & 7)) << 4;
    float ss = 0.f;
    bar_sync(3, 256);
    mbar_wait(sb + MB_X, 0);
    auto chunk = [&](auto cc) {
      constexpr int c = decltype(cc)::value;
      QSTAMP(2 + 2 * c);
      mbar_wait(sb + MB_W + 8 * c, 0);
      QSTAMP(3 + 2 * c);
#pragma unroll
      for (int rt = 1; rt >= 0; rt--)
#pragma unroll
        for (int k = 0; k < 6; k++)
          ldsm4t(wa[rt][c * 6 + k], sb + SM_STAGE + c * 49152 + (rt ^ wg) * 24576 + (64 * (k >> 1) + 32 * wg + 16 * (k & 1) + rr) * 128 + col);
      fence_async();
      if (c < 2) {
        bar_sync(3, 256);
        QSTAMP(17 + c);
        if (threadIdx.x == 0) {
          if (c == 0) tma_load(sb + SM_X + XT, &tm.wo, rank * 192, (blockIdx.x / 3) * DH, sb + MB_WO);
          else tma_load3(sb + SM_X + 2 * XT, &tm.x, 64, sb + MB_X + 16);
        }
        __syncwarp();
      } else {
        cluster_arrive();
      }
      xproj<1, 6 * c, 6 * c + 6>(acc, wa, xd0);
      if (!qk) {
        uint32_t q[4] = {0, 0, 0, 0};
#pragma unroll
        for (int rt = 0; rt < 2; rt++)
#pragma unroll
          for (int k = 0; k < 6; k++)
#pragma unroll
            for (int i = 0; i < 4; i++) sq_acc(q[i], wa[rt][c * 6 + k][i]);
#pragma unroll
        for (int i = 0; i < 4; i++) ss += bf_lo(q[i]) + bf_hi(q[i]);
      }
      if (c < 2 && CW) WG_WAIT(0);
    };
    chunk(IntC<0>()); chunk(IntC<1>()); chunk(IntC<2>());
    ss = warp_sum(ss);
    if (lane == 0) sts32(sb + SC_SS + 4 * (wg * 4 + w), __float_as_uint(ss));
    bar_arrive(11, 384);
  }
  STAMP(1);
  QSTAMP(8);
  STAMP(2);

  uint32_t t16 = sb + (w * 32 + lane) * 16;
  uint32_t mem_a = sb + SM_MEM + wg * 512 + lane * 16;
  uint32_t fin_a = sb + (lane & 7) * 16 + SM_BLK + (qk ? (wg ^ 1) * 4096 + w * 256 + (lane & 8) * 16 + (lane & 16) * 64
                                              : wg * 4096 + w * 1024 + (lane & 8) * 64 + (lane & 16) * 8);
  PIN(t16); PIN(mem_a); PIN(fin_a);
  const uint32_t fence_reg = mem_a;
  const uint32_t fin2 = qk ? 2048 : 256;
  auto do_export = [&](auto retire, uint32_t always) {
    WG_WAIT(0);
    uint32_t p[2];
#pragma unroll
    for (int i = 0; i < 2; i++) {
      p[i] = pack_bf16(acc[8 * i], acc[8 * i + 1]);
      sts128(t16 + SM_EXP + wg * 4096 + i * 2048, p[i], pack_bf16(acc[8 * i + 2], acc[8 * i + 3]),
             pack_bf16(acc[8 * i + 4], acc[8 * i + 5]), pack_bf16(acc[8 * i + 6], acc[8 * i + 7]));
    }
    if (decltype(retire)::value)
      asm volatile("{\n.reg .pred p, q;\nsetp.ne.u32 p, %2, 0;\nsetp.ne.u32 q, %2, 1;\n@p ld.shared.b32 %0, [%3];\n@q ld.shared.b32 %1, [%3 + 4];\n"
                   "setp.ne.u32 p, %0, %1;\n@p exit;\n}" : "+r"(p[0]), "+r"(p[1]) : "r"(always), "r"(sb + SC_DEAD) : "memory");
  };
  uint32_t o[8];
  auto import = [&]() { lds128(t16 + SM_EXP + (wg ^ 1) * 4096, o); lds128(t16 + SM_EXP + (wg ^ 1) * 4096 + 2048, o + 4); };
  auto finish_from = [&](int seg, const float* d) {
    const uint32_t a = fin_a + (seg & 3) * SEGB;
#pragma unroll
    for (int i = 0; i < 8; i++) o[i] = add_bf16(pack_bf16(d[2 * i], d[2 * i + 1]), o[i]);
    stsm4(a, o[0], o[1], o[2], o[3]);
    stsm4(a + fin2, o[4], o[5], o[6], o[7]);
  };
  auto finish = [&](int seg) { WG_WAIT(0); finish_from(seg, acc); };
  auto send_v = [&](int seg, int dst) {
    fence_async();
    if (seg < NSEG - 1 && !(XP & 2) && elect_one())
      bulk_s2s(mapa(sb + SM_VC + (seg & 1) * 8192, dst), sb + SM_BLK + (seg & 3) * SEGB, 8192, mapa(sb + MB_VX + (seg & 1) * 8, dst));
    __syncwarp();
  };
  auto wait_v = [&](int seg) {
    if (seg < NSEG - 1 && !(XP & 2)) {
      mbar_wait(sb + MB_VX + (seg & 1) * 8, (seg >> 1) & 1);
      if (elect_one()) mbar_expect(sb + MB_VX + (seg & 1) * 8, 8192);
      __syncwarp();
    }
  };
  auto export_seg = [&](int seg) { if (!(XP & (4 | 8192)) && elect_one()) seg_store(seg, sb); __syncwarp(); };
  auto publish = [&](int seg) { if (!(XP & (4 | 16384)) && elect_one()) seg_publish(seg, sb); __syncwarp(); };
  do_export(BoolC<false>(), 0);
  QSTAMP(9);
  SCHED_FENCE(11);
  xproj<0, 0, 18>(acc, wa, xd0);
  bar_sync(3, 256);
  QSTAMP(10);
  cluster_wait();
  QSTAMP(11);
  mbar_wait(sb + MB_X + 8, 0);
  QSTAMP(12);
  import();
  finish(0);
  SCHED_FENCE(12);
  uint64_t dA = xd0 + (XT >> 4);
  xproj<1, 0, 18>(acc, wa, dA);
  bar_sync(3, 256);
  if (!qk && wg == 0 && w < 2) send_v(0, w);
  if (!(EXV & 1) && wg == 0 && w == 3) export_seg(0);
  QSTAMP(13);
  if (qk && wg == 0 && w == 0) wait_v(0);
  QSTAMP(14);
  bar_arrive(13, 384);
  if (!qk) {
    do_export(BoolC<false>(), 0);
    SCHED_FENCE(15);
    xproj<0, 0, 18>(acc, wa, dA);
    if (threadIdx.x == 0 && !(XP & 8)) { mbar_expect(sb + MB_X, XT); tma_load3(sb + SM_X, &tm.x, 96, sb + MB_X); }
    bar_sync(3, 256);
    mbar_wait(sb + MB_X + 16, 0);
    import();
    finish(1);
    SCHED_FENCE(16);
    dA += XT >> 4;
    xproj<1, 0, 18>(acc, wa, dA);
    if (!(EXV & 2)) bar_sync(3, 256);
    if (!(EXV & 2) && wg == 0 && w < VW2) send_v(1, w);
  }
  QSTAMP(15);
  WG_WAIT(0);
  bar_sync(0, 384);
  if (!(EXV & 1) && wg == 0 && w == 3) publish(0);
  QSTAMP(16);
  const int ro = __shfl_sync(0xffffffffu, near_half(sb) ^ wg, 0);
  STAMP(5);
  const uint32_t always = __shfl_sync(0xffffffffu, lds32(sb + SC_DEAD + 12), 0);
  const int ah = qk ? 1 : 2;
  int b2 = qk ? 2 : 0;
  int s = 0;
  uint32_t hint_lo = (uint32_t)(uint64_t)tm.red + HINT_OFF + blockIdx.x + (lane & 1) * 4096 + (lane >> 1) * 16384;
  PIN(hint_lo);
  auto post_hint = [&]() {
    asm volatile("{\n.reg .pred p;\n.reg .b64 a;\n.reg .u32 t;\nsetp.lt.u32 p, %0, %1;\nmov.b64 a, {%2, %3};\nmov.u32 t, %%globaltimer_lo;\n"
                 "bfe.u32 t, t, 5, 6;\nor.b32 t, t, %4;\n@p st.relaxed.gpu.global.u8 [a], t;\n}"
                 :: "r"(t16), "r"(sb + 160), "r"(hint_lo + RED_SLOT(s)), "r"((uint32_t)((uint64_t)tm.red >> 32)), "r"(((s >> 2) + 1) << 6) : "memory");
  };
  auto memproj = [&](auto second, int id, uint32_t dep, float u0, float u1, float* r) {
    constexpr bool R1 = decltype(second)::value;
    uint32_t b[NUP][4], b0[4];
    if (R1) asm volatile("{\n.reg .pred p;\nsetp.eq.u32 p, %0, %1;\n@p exit;\n}" :: "r"(dep), "r"(id) : "memory");
    bar_sync(R1 ? 2 : 1, 256);
    PROF(0);
    ldsm4t(b0, mem_a);
#pragma unroll
    for (int q = 0; q < NUP; q++) {
      if (R1 && q == 2) {
        bar_sync(11, 256);
        SCHED_FENCE(id + 1);
      }
      ldsm4t(b[q], mem_a + MEM_BLK(q + 1));
    }
    mma16816z(&acc[0], wa[0][0], b0[0], b0[1]);
    mma16816z(&acc[4], wa[1][0], b0[0], b0[1]);
    mma16816z(&acc[8], wa[0][1], b0[2], b0[3]);
    mma16816z(&acc[12], wa[1][1], b0[2], b0[3]);
#pragma unroll
    for (int q = 1; q < 9; q++) {
      uint32_t* const c = b[(q - 1) % NUP];
      mma16816(&acc[0], wa[0][2 * q], c[0], c[1]);
      mma16816(&acc[4], wa[1][2 * q], c[0], c[1]);
      mma16816(&acc[8], wa[0][2 * q + 1], c[2], c[3]);
      mma16816(&acc[12], wa[1][2 * q + 1], c[2], c[3]);
      if (R1 && q + NUP == B3Q) bar_sync(3, 256);
      if (q + NUP < 9) ldsm4t_in(c, mem_a + MEM_BLK(q + NUP), always);
      else if (R1 && q + NUP < 11) lds128_in(c, t16 + SM_PART + (10 - q - NUP) * 2048, always);
      else if (!R1 && GATE && q == GATE) { bar_arrive(11, 256); lds128_in(c, sb + SC_DEAD, always); u0 = u1 = __uint_as_float(c[3]); }
    }
#pragma unroll
    for (int i = 0; i < 8; i++) {
      const float u = i < 4 ? u0 : u1;
      r[i] = R1 ? fmaf(acc[8 + i], u, (acc[i] + __uint_as_float(b[(8 + i / 4) % NUP][i & 3])) * u) : (GATE ? fmaf(acc[i], u, acc[8 + i]) : acc[i] + acc[8 + i]);
    }
  };
  if (ro == 0) {
#pragma unroll 1
    while (true) {
      do_export(BoolC<true>(), always);
      PROFP(3);
      if (s == 8) STAMP(6);
      float r[8];
      memproj(BoolC<false>(), 30, 0, 0.f, 0.f, r);
      sts128(t16 + SM_PART, __float_as_uint(r[0]), __float_as_uint(r[1]), __float_as_uint(r[2]), __float_as_uint(r[3]));
      sts128(t16 + SM_PART + 2048, __float_as_uint(r[4]), __float_as_uint(r[5]), __float_as_uint(r[6]), __float_as_uint(r[7]));
      bar_arrive(3, 256);
      PROF(1);
      bar_sync(9, 256);
      if (s == NSEG - 1) break;
      post_hint();
      if (!(EXV & 1) && w == 3 && s) publish(s);
      if (w == 1) {
        uint32_t m[8];
        lds128(t16 + SM_MAX - 512, m); lds128(t16 + SM_MAX, m + 4);
        const int em = (wexp(amax4(amax4(*(const __half2*)&m[0], m), m + 4)) >> 3) + (int)(lds32(sb + SC_UNSC + (s & 1) * 8) >> 23) - 15;
        const int ex = max(s ? em : 0, (int)lds32(sb + SC_XMAX + 4 * s)) - 127 + (int)lds32(sb + SC_EXPW);
        sts32(sb + SC_UNSC + (~s & 1) * 8, (127 + min(max(ex, -120), 120)) << 23);
        __syncwarp();
        if (elect_one()) mbar_arrive(sb + MB_S);
      }
      SCHED_FENCE(9);
      bar_sync(5, qk ? N5 : 256);
      PROF(2);
      import();
      xproj<0, 0, NII>(acc, wa, dA);
      if (NII < 18) {
        if (qk) bar_sync(7, 384);
        xproj<0, NII, 18>(acc, wa, dA);
        if (!qk) bar_sync(7, 384);
      } else {
        if (F10) WG_WAIT(0);
        bar_sync(10, 256);
        if (F10) SCHED_FENCE(17);
      }
      dA += (int64_t)(b2 ? XT >> 4 : -(XT >> 3));
      finish(s + ah);
      if (((EXV & 1) || w != 3) && ((EXV & 2) || qk || w >= VW2)) bar_arrive(13, 384);
      PROF(6);
      SCHED_FENCE(14);
      if (NOB & 2) bar_arrive(14, 256);
      bar_sync(12, 256);
      PROF(7);
      xproj<1, 0, 18, true>(acc, wa, dA);
      if (!(NOB & 2)) bar_arrive(14, 256);
      b2 = b2 == 2 ? 0 : b2 + 1;
      s++;
      if ((!(EXV & 1) && w == 3) || (!(EXV & 2) && !qk && w < VW2)) {
        bar_sync(13, 384);
        if (!(EXV & 1) && w == 3) export_seg(s); else send_v(s + 1, w);
      }
      PROFP(8);
    }
    if (!qk) bar_arrive(5, 256);
    if (!(EXV & 1) && w == 3) publish(NSEG - 1);
  } else {
    uint32_t km[4];
    auto send_km = [&]() {
      if (XP & (4 | 4096)) return;
      const uint32_t t = (km[0] & ~1u) | lds32(sb + SC_EPO + 4), u = (s * NH + head_id()) * 4096;
      if (qk)
        asm volatile("{\n.reg .u32 o;\n.reg .u64 a;\nshr.u32 o, %0, 1;\nadd.u32 o, o, %1;\nmad.wide.u32 a, o, 1, %2;\nst.relaxed.gpu.global.v2.b32 [a], {%3,%4};\n}"
                     :: "r"(t16), "r"(u + rank * 1024 - (sb >> 1)), "l"(g_km), "r"(t), "r"(km[1]) : "memory");
      else
        asm volatile("{\n.reg .u32 o;\n.reg .u64 a;\nadd.u32 o, %0, %1;\nmad.wide.u32 a, o, 1, %2;\nst.relaxed.gpu.global.v4.b32 [a], {%3,%4,%5,%6};\n}"
                     :: "r"(t16), "r"(u + 2048 - sb), "l"(g_km), "r"(t), "r"(km[1]), "r"(km[2]), "r"(km[3]) : "memory");
    };
#pragma unroll 1
    while (true) {
      do_export(BoolC<true>(), always);
      if ((EXV & 1) && w == 1) export_seg(s);
      if ((EXV & 2) && !qk && w == 2) send_v(s + 1, 0);
      PROFP(3);
      if (s == 8) STAMP(6);
      const uint32_t tl = ((t16 >> 8) ^ wg) & 1, am = (t16 & ~256u) - w * 256;
      const float un = __uint_as_float(lds32(sb + SC_UNSC + (s & 1) * 8));
      float r[8];
      if (qk) {
        uint32_t a0 = am + (tl ? SM_QM : SM_BLK + 8192 + (s & 3) * SEGB);
        float u0 = wg ? un * (SM_SCALE * LOG2E) : un, u1 = wg ? un : un * (SM_SCALE * LOG2E);
        PIN(a0); PIN(u0); PIN(u1);
        memproj(BoolC<true>(), 32, a0, u0, u1, r);
        const uint32_t p0 = pack_bf16(r[0], r[1]), p1 = pack_bf16(r[2], r[3]), p2 = pack_bf16(r[4], r[5]), p3 = pack_bf16(r[6], r[7]);
        stsm4(a0, p0, p1, p2, p3);
        bar_arrive(4, 256);
        km[0] = wg ? p2 : p0; km[1] = wg ? p3 : p1;
      } else {
        const uint32_t d0 = s < NSEG - 1 ? 0 : 2, d1 = s < NSEG - 1 ? 1 : 2;
        uint32_t r0 = mapa(t16 + SM_VM, d0), r1 = mapa(t16 + SM_VM, d1);
        PIN(r0); PIN(r1);
        memproj(BoolC<true>(), 34, r0 | r1, un, un, r);
        const uint32_t p0 = pack_bf16(r[0], r[1]), p1 = pack_bf16(r[2], r[3]), p2 = pack_bf16(r[4], r[5]), p3 = pack_bf16(r[6], r[7]);
        const uint32_t v0 = wg ? p2 : p0, v1 = wg ? p3 : p1, v2 = wg ? p0 : p2, v3 = wg ? p1 : p3;
        st_async4(r0, v0, v1, v2, v3, mapa(sb + MB_S, d0));
        st_async4(r1, v0, v1, v2, v3, mapa(sb + MB_S, d1));
        bar_arrive(5, 256);
        sts128(t16 + SM_VM, v0, v1, v2, v3);
        __syncwarp();
        if (elect_one()) mbar_arrive(sb + MB_S);
        km[0] = v0; km[1] = v1; km[2] = v2; km[3] = v3;
      }
      if (s == NSEG - 1) break;
      PROF(1);
      if (KME && (qk || w != 2)) send_km();
      auto rearm = [&]() { mbar_wait(sb + MB_S, s & 1); if (elect_one()) mbar_expect(sb + MB_S, qk ? 640 + 2048 : 1280); __syncwarp(); };
      if (w == 1) {
        if ((t16 & 384) == 0) stg_relaxed(tm.red + (RED_SLOT(s + 2) + RED_LINE(blockIdx.x)) + (t16 & 112), 0, 0, 0, 0);
        if (EXV & 1) publish(s);
      } else if (w == 0) {
        const int tn = s + ah + 1;
        if (RFW) mbar_wait(sb + MB_S, s & 1);
        if (tn + 1 < NSEG && !(XP & 8) && elect_one()) {
          const int b0 = b2 == 2 ? 0 : b2 + 1;
          mbar_expect(sb + MB_X + 8 * b0, XT);
          tma_load3(sb + SM_X + b0 * XT, &tm.x, (tn + 1) * 32, sb + MB_X + 8 * b0);
        }
        if (tn < NSEG && (!(XP & 8) || tn < 3)) mbar_wait(sb + MB_X + 8 * b2, (tn / 3) & 1);
      } else if (w == 2) {
        if (!qk) { if (VW2 < 1) send_v(s + 1, 0); if (VW2 < 2) send_v(s + 1, 1); }
      } else if (qk || !NIC) {
        rearm();
      }
      __syncwarp();
      if (!KME || (!qk && w == 2)) send_km();
      import();
      PROF(4);
      SCHED_FENCE(10);
      if (NIC) {
        if (qk) bar_sync(7, NII < 18 ? 384 : 256);
        xproj<0, 0, NIC>(acc, wa, dA);
        if (!qk) { if (w == 3) rearm(); bar_sync(7, NII < 18 ? 384 : 256); }
      } else {
        bar_sync(7, NII < 18 ? 384 : 256);
      }
      if (NOB & 1) bar_arrive(12, 256);
      xproj<0, NIC, 18>(acc, wa, dA);
      if (!(NOB & 1)) bar_arrive(12, 256);
      dA += (int64_t)(b2 ? XT >> 4 : -(XT >> 3));
      finish(s + ah);
      if (qk && w == 0) wait_v(s + 1);
      bar_arrive(13, 384);
      PROF(6);
      SCHED_FENCE(13);
      bar_sync(14, 256);
      PROF(7);
      xproj<1, 0, 18>(acc, wa, dA);
      b2 = b2 == 2 ? 0 : b2 + 1;
      s++;
      PROFP(8);
    }
    send_km();
    if ((EXV & 1) && w == 1) publish(NSEG - 1);
    PIN(t16);
    if (t16 - sb < 128) stg_relaxed(tm.red + (RED_SLOT(NSEG + 1) + RED_LINE(head_id() * 3 + rank)) + (t16 & 112), 0, 0, 0, 0);
  }
  bar_arrive(0, 384);
  STAMP(3);
  cluster_sync();
  STAMP(4);
}

DI void attn_role(const uint32_t sb, unsigned char* smem_raw, const RMaps& tm, const uint32_t RANK, const bf16* __restrict__ x, const bf16* __restrict__ mem0,
                  const int w, const int lane) {
  const int t2 = w * 32 + lane;
  uint32_t wo[8][4], w1[8][4];
  const uint32_t wo_lane = sb + ((lane & 7) + ((lane >> 4) << 3)) * 128 + (((w + 4 * ((lane >> 3) & 1)) ^ (lane & 7)) << 4);
  unsigned char* const g_red = tm.red;
  {
    const uint32_t tag = *(volatile unsigned*)&g_epoch + 1;
    QSTAMP(0);
    bar_sync(0, 160);
    QSTAMP(1);
    cluster_arrive();
    __half2 hx = __float2half2_rn(0.f);
    if (blockIdx.x < NSEG) {
      mbar_wait(sb + MB_XS, 0);
#pragma unroll
      for (int i = 0; i < 18; i++) { uint32_t v[4]; lds128(sb + SM_STAGE + 2 * 49152 + t2 * 16 + i * 2048, v); hx = amax4(hx, v); }
      fence_async();
      bar_sync(6, 128);
      if (t2 == 0) load_w(sb, tm, RANK, 2);
      __syncwarp();
    }
    if (t2 == 0) { sts64(sb + SC_EPO, (tag - 1) * NSEG + 1, tag & 1); sts32(sb + SC_UNSC, __float_as_uint(1.f)); sts128(sb + SC_DEAD, 0, 0, 0, 0x3f800000u); sts64(sb + SC_FPAR, 0, 0); sts128(sb + SC_ONES, 0x3f803f80u, 0x3f803f80u, 0x3f803f80u, 0x3f803f80u); }
    WSTAMP(27);
    uint32_t q[8] = {0, 0, 0, 0, 0, 0, 0, 0};
    QSTAMP(2);
    mbar_wait(sb + MB_WO3, 0);
    QSTAMP(3);
    uint32_t mv[5][4];
#pragma unroll
    for (int i = 0; i < 5; i++) {
      ldsm4(mv[i], sb + SM_M0 + (lane & 7) * (DM * 2) + min(w + 4 * i, 17) * 64 + (lane >> 3) * 16);
      if (blockIdx.x == 0) hx = amax4(hx, mv[i]);
    }
    sts32(sb + SC_SS + 4 * (12 + w), wexp(hx));
#pragma unroll
    for (int k = 0; k < 8; k++) {
      ldsm4t(wo[k], wo_lane + SM_WO3 + k * 2048); ldsm4t(w1[k], wo_lane + SM_WOST + k * 2048);
#pragma unroll
      for (int i = 0; i < 4; i++) { sq_acc(q[i], wo[k][i]); sq_acc(q[i], w1[k][i]); }
    }
    bar_sync(6, 128);
#pragma unroll
    for (int k = 0; k < 8; k++) sts128(sb + SM_WO3 + t2 * 16 + k * 2048, wo[k][0], wo[k][1], wo[k][2], wo[k][3]);
#pragma unroll
    for (int i = 0; i < 5; i++) {
      const int c = (w + 4 * i) * 32;
      if (c < DM) stsm4t(sb + SM_MEM + (c + c / 192 * 64 + lane) * 16, mv[i][0], mv[i][1], mv[i][2], mv[i][3]);
    }
    bar_arrive(1, 256); bar_arrive(2, 256); bar_arrive(9, 256);
    QSTAMP(4);
    mbar_wait(sb + MB_WO, 0);
    QSTAMP(5);
#pragma unroll
    for (int k = 0; k < 8; k++) ldsm4t(wo[k], wo_lane + SM_X + XT + k * 2048);
    fence_async();
    bar_sync(6, 128);
    if (t2 == 32) tma_load3(sb + SM_X + XT, &tm.x, 32, sb + MB_X + 8);
    __syncwarp();
#pragma unroll
    for (int k = 0; k < 8; k++)
#pragma unroll
      for (int i = 0; i < 4; i++) sq_acc(q[4 + i], wo[k][i]);
    float ss = 0.f;
#pragma unroll
    for (int i = 0; i < 8; i++) ss += bf_lo(q[i]) + bf_hi(q[i]);
    ss = warp_sum(ss);
    if (lane == 0) sts32(sb + SC_SS + 4 * (8 + w), __float_as_uint(ss));
    QSTAMP(6);
    bar_sync(11, 384);
    QSTAMP(7);
    if (t2 == 0) {
      float a[16];
#pragma unroll
      for (int i = 0; i < 4; i++) lds128f(sb + SC_SS + 16 * i, &a[4 * i]);
      stg_relaxed(&g_stats[blockIdx.x * 2], __float_as_uint(((a[0] + a[1]) + (a[2] + a[3])) + ((a[4] + a[5]) + (a[6] + a[7]))),
                  __float_as_uint((a[8] + a[9]) + (a[10] + a[11])),
                  max(max(__float_as_uint(a[12]), __float_as_uint(a[13])), max(__float_as_uint(a[14]), __float_as_uint(a[15]))), tag);
    }
    __syncwarp();
    WSTAMP(24);
    QSTAMP(8);
    cluster_wait();
    QSTAMP(9);
    if (w == 0) {
      uint4 v[3];
      int n = 0;
      while (true) {
#pragma unroll
        for (int i = 0; i < 3; i++) v[i] = ldg_relaxed(&g_stats[(i * 32 + lane) * 2]);
        if (__all_sync(0xffffffffu, v[0].w == tag && v[1].w == tag && v[2].w == tag) || ++n > SPIN_LIMIT) break;
        __nanosleep(100);
      }
      WSTAMP(25);
      QSTAMP(10);
      const float sv = warp_sum(__uint_as_float(v[0].x) + __uint_as_float(v[1].x) + __uint_as_float(v[2].x));
      const float so = warp_sum(__uint_as_float(v[0].y) + __uint_as_float(v[1].y) + __uint_as_float(v[2].y));
      const int expW = ((int)(__float_as_uint(sv) >> 23) + (int)(__float_as_uint(so) >> 23) - 254 + 2 + 10 + 1) >> 1;
      sts32(sb + SC_XMAX + 4 * lane, v[0].z); sts32(sb + SC_XMAX + 128 + 4 * lane, v[1].z);
      sts32(sb + SC_EXPW, expW + 1 - 15);
      if (blockIdx.x == 0 && lane == 0) *(volatile unsigned*)&g_epoch = tag;
      sts32(sb + SC_FPAR + 4, 1);
    } else if (w < 3) {
      const uint32_t u = blockIdx.x >> 4;
      unsigned char* const z = g_red + 98304 + (blockIdx.x & 15) * 128 + (u & 1) * 2048 + (u & 6) * 4096 + (((u >> 1) ^ w) & 1) * 4096 + lane * 4;
      stg_relaxed32(z, 0);
      uint32_t best = 0xffffffffu;
#pragma unroll 1
      for (int i = 0; i < 64; i++) {
        uint32_t dt;
        asm volatile("{\n.reg .pred p;\n.reg .u32 c, v;\nmov.u32 c, %%clock;\n"
                     "atom.relaxed.gpu.global.exch.b32 v, [%1], 0;\nsetp.eq.u32 p, v, 0;\nmov.u32 %0, 0;\n@p mov.u32 %0, %%clock;\nsub.u32 %0, %0, c;\n}"
                     : "=r"(dt) : "l"(z) : "memory");
        best = min(best, dt);
        if (lds32v(sb + SC_FPAR + 4) && i >= NPROBE - 1) break;
      }
      sts32(sb + SC_LAT + (w - 1) * 4, best);
    }
    QSTAMP(11);
    bar_sync(13, 384);
    bar_arrive(0, 384);
    QSTAMP(12);
    WSTAMP(26);
  }

  const uint32_t nh = __shfl_sync(0xffffffffu, near_half(sb), 0);
  uint32_t l16 = sb + lane * 16;
  PIN(l16);
#define LV ((l16 >> 4) & 31)
#define fence_reg l16
  const uint32_t red_lo = (uint32_t)(uint64_t)g_red, red_hi = (uint32_t)((uint64_t)g_red >> 32);
  uint32_t lp;
  auto slot = [&](int s, uint32_t c, uint32_t ofs) {
    const uint32_t lo = lp | (red_lo + ((w >> 1) * 4 + (w & 1) * 2 + ((w ^ c) & 1)) * 4096 + RED_SLOT(s) + ofs);
    uint64_t a; asm("mov.b64 %0, {%1, %2};" : "=l"(a) : "r"(lo), "r"(red_hi));
    return (unsigned char*)a;
  };
  const uint32_t always = __shfl_sync(0xffffffffu, lds32(sb + SC_DEAD + 12), 0);
  const int mode0 = RANK < 2 ? w : w | 4;
  auto hint_addr = [&](int s) { return min(LV, 23u) * 4 + (red_lo + HINT_OFF + nh * 4096 + w * 16384 + RED_SLOT(s)); };
  auto load_hints = [&](uint32_t lo) {
    uint64_t a; asm("mov.b64 %0, {%1, %2};" : "=l"(a) : "r"(lo), "r"(red_hi));
    return ldg_relaxed32((const void*)a);
  };
  int s = 0;
  bool bad = false;
#pragma unroll 1
  while (true) {
    const uint32_t par = s & 1;
    uint32_t vx[4][4], hints;
    auto load_vx = [&]() {
      const uint32_t va = l16 + (RANK < 2 ? SM_VC + par * 8192 : SM_BLK + (s & 3) * SEGB) + w * 1024 + ((LV >> 3) & 1) * 384 - (LV >> 4) * 128;
#pragma unroll
      for (int i = 0; i < 4; i++) ldsm4(vx[i], va + (i & 1) * 4096 + (i >> 1) * 256);
    };
    auto retire = [&](uint32_t x) {
      asm volatile("{\n.reg .pred p;\nsetp.eq.u32 p, %0, 0;\n@p exit;\n}" :: "r"(vx[0][0] | vx[1][0] | vx[2][0] | vx[3][0] | x) : "memory");
    };
    auto scores = [&](auto memkeys, auto first, float* sc) {
      constexpr bool MK = decltype(memkeys)::value, FIRST = decltype(first)::value;
      uint32_t kb[4][4], qb[2][4];
      const uint32_t m = LV >> 3;
      uint32_t kaddr = l16 + SM_BLK + 4096 + (s & 3) * SEGB + w * 2048 + (m & 1) * (MK ? 128 : 896) - (m >> 1) * 128;
      if (MK) { PIN(kaddr); }
      else {
#pragma unroll
        for (int k = 0; k < 4; k++) ldsm4t(kb[k], kaddr + k * 256);
      }
      if (FIRST) { load_vx(); retire(MK ? kaddr : kb[0][0] | kb[1][0] | kb[2][0] | kb[3][0] | l16); bar_sync(4, 256); PROF(4); }
      ldsm4t(qb[0], l16 + SM_QM);
      if (MK) ldsm4t(kb[0], kaddr);
      ldsm4t(qb[1], l16 + SM_QM + 512);
      if (MK) ldsm4t(kb[2], kaddr + 512);
      float c[4][4];
      mma16816z(c[0], kb[0], qb[0][0], qb[0][1]); mma16816z(c[1], kb[MK ? 0 : 1], qb[0][2], qb[0][3]);
      mma16816z(c[2], kb[2], qb[1][0], qb[1][1]); mma16816z(c[3], kb[MK ? 2 : 3], qb[1][2], qb[1][3]);
      if (FIRST && B5POS == 0) bar_arrive(5, N5);
#pragma unroll
      for (int i = 0; i < (MK ? 2 : 4); i++) sc[i] = ((c[0][i] + c[1][MK ? i + 2 : i]) + c[2][i]) + c[3][MK ? i + 2 : i];
    };
    auto send = [&](auto memkeys) {
      constexpr bool MK = decltype(memkeys)::value;
      constexpr int N = MK ? 1 : 2;
      const uint32_t sa = sb + LV * 4 + SM_E + (MK ? 1024 + RANK * 128 : RANK * 512 + w * 256);
      uint32_t ra[N][2], mb[N][2];
#pragma unroll
      for (int i = 0; i < N; i++)
#pragma unroll
        for (int j = 0; j < 2; j++) {
          ra[i][j] = mapa(sa + i * 128, j ? 2 : RANK ^ 1); mb[i][j] = mapa(sb + MB_S, j ? 2 : RANK ^ 1);
          PIN(ra[i][j]);
        }
      float sc[4];
      scores(memkeys, BoolC<true>(), sc);
      uint32_t e[N];
#pragma unroll
      for (int i = 0; i < N; i++) {
        e[i] = pack_bf16(ex2(sc[2 * i]), ex2(sc[2 * i + 1]));
        if (!(fmaxf(fabsf(sc[2 * i]), fabsf(sc[2 * i + 1])) <= E_LIM)) e[i] = 0x7fff7fffu;
        st_async1(ra[i][0], e[i], mb[i][0]);
        st_async1(ra[i][1], e[i], mb[i][1]);
      }
#pragma unroll
      for (int i = 0; i < N; i++) sts32(sa + i * 128, e[i]);
      __syncwarp();
      if (l16 == sb) mbar_arrive(sb + MB_S);
      PROF(5);
    };
    const int mode = bad ? 8 : mode0;
    if (mode < 2) {
      send(BoolC<false>());
    } else if (mode == 2) {
      send(BoolC<true>());
    } else if (mode == 8) {
      load_vx();
      retire(l16);
      const uint32_t fp = lds32(sb + SC_FPAR);
      bar_sync(6, 128);
      if (w == 0 && l16 == sb) { sts32(sb + SC_FPAR, fp ^ 1); mbar_expect(sb + MB_F, 3072); }
      if (RANK < 2 && w < 3) {
        float sc[4] = {0.f, 0.f, 0.f, 0.f};
        if (w < 2) scores(BoolC<false>(), BoolC<false>(), sc); else scores(BoolC<true>(), BoolC<false>(), sc);
#pragma unroll 1
        for (int r = 0; r < 3; r++)
          st_async4(mapa(l16 + SM_FB + RANK * 1536 + w * 512, r), __float_as_uint(sc[0]), __float_as_uint(sc[1]), __float_as_uint(sc[2]), __float_as_uint(sc[3]), mapa(sb + MB_F, r));
      }
      mbar_wait(sb + MB_F, fp);
      float a[12];
#pragma unroll
      for (int j = 0; j < 3; j++) {
        float b[4];
        lds128f(l16 + SM_FB + j * 512, a + 4 * j); lds128f(l16 + SM_FB + 1536 + j * 512, b);
#pragma unroll
        for (int i = 0; i < 4; i++) a[4 * j + i] += b[i];
      }
      float m0 = fmaxf(fmaxf(fmaxf(a[0], a[2]), fmaxf(a[4], a[6])), a[8]), m1 = fmaxf(fmaxf(fmaxf(a[1], a[3]), fmaxf(a[5], a[7])), a[9]);
#pragma unroll
      for (int o = 4; o < 32; o <<= 1) { m0 = fmaxf(m0, __shfl_xor_sync(0xffffffffu, m0, o)); m1 = fmaxf(m1, __shfl_xor_sync(0xffffffffu, m1, o)); }
#pragma unroll
      for (int i = 0; i < 5; i++) {
        const uint32_t ea = sb + SM_E + LV * 4 + (i < 4 ? i * 128 : 1024);
        sts32(ea, pack_bf16(ex2(a[2 * i] - m0), ex2(a[2 * i + 1] - m1)));
        sts32(ea + (i < 4 ? 512 : 128), 0x3f803f80u);
      }
      __syncwarp();
    } else {
      load_vx();
      if (mode == 3) bar_arrive(4, 256);
      retire(l16 + 1);
    }
    {
      uint32_t wa[4], wb[4], oc[4];
      constexpr int WS = 2048;
      const uint32_t w3a = l16 + SM_WO3 + w * 512;
      lds128(w3a + KP(0) * WS, wa); lds128(w3a + KP(1) * WS, wb); lds128(sb + SC_ONES, oc);
      if (B5POS == 1 && mode < 3) bar_arrive(5, N5);
      uint32_t e[10], p[5], vm[4], ob[4];
      float o0[4], o1[4], f[3][2][4], rs[4];
      reserve2(vm); reserve2(vm + 2); reserve2(e + 8);
      hints = hint_addr(s);
      PIN(hints);
      if (CLR & 2) asm volatile("{\n.reg .pred p;\nsetp.eq.u32 p, %0, 0;\n@p exit;\n}" :: "r"(wa[0] | wb[0] | oc[0] | hints) : "memory");
      mbar_wait(sb + MB_S, par);
      PROF(6);
      ldsm4t(e, l16 + SM_E); ldsm2t_in(e + 8, l16 + SM_E + 1024, always); ldsm4t(e + 4, l16 + SM_E + 512);
      lds128_in(vm, l16 + w * 512 + SM_VM, always);
      const float scl = __uint_as_float(lds32(sb + SC_UNSC + 8 - par * 8));
      hints = load_hints(hints);
      if (GF & 1) SCHED_FENCE(4);
#pragma unroll
      for (int i = 0; i < 4; i++) p[i] = mul_bf16(e[i], e[4 + i]);
      p[4] = mul_bf16(e[8], e[9]);
      if (MO & 4) {
        float a0[4], a1[4];
        mma16816z(o0, vx[0], p[0], p[1]); mma16816z(o1, vx[1], p[0], p[1]);
        mma16816z(a0, vx[2], p[2], p[3]); lds128_in(vx[2], w3a + KP(2) * WS, always);
        mma16816z(a1, vx[3], p[2], p[3]); lds128_in(vx[3], w3a + KP(3) * WS, always);
        mma1688(o0, vm[0], vm[1], p[4]); mma1688(o1, vm[2], vm[3], p[4]);
        mma16816z(rs, oc, p[0], p[1]); mma16816(rs, oc, p[2], p[3]); mma1688(rs, oc[0], oc[1], p[4]);
#pragma unroll
        for (int i = 0; i < 4; i++) { o0[i] += a0[i]; o1[i] += a1[i]; }
      } else {
      mma16816z(o0, vx[0], p[0], p[1]); mma16816z(o1, vx[1], p[0], p[1]); mma16816z(rs, oc, p[0], p[1]);
      mma16816(o0, vx[2], p[2], p[3]); lds128_in(vx[2], w3a + KP(2) * WS, always);
      mma16816(o1, vx[3], p[2], p[3]); lds128_in(vx[3], w3a + KP(3) * WS, always);
      mma16816(rs, oc, p[2], p[3]);
      mma1688(o0, vm[0], vm[1], p[4]); mma1688(o1, vm[2], vm[3], p[4]); mma1688(rs, oc[0], oc[1], p[4]);
      }
      stsm4(l16 + w * 512 + SM_OB, pack_bf16(o0[0], o0[1]), pack_bf16(o0[2], o0[3]), pack_bf16(o1[0], o1[1]), pack_bf16(o1[2], o1[3]));
      bar_sync(6, 128);
      PROF(7);
      ldsm4t_in(oc, l16 + SM_OB, always);
      bad = __any_sync(0xffffffffu, !(rs[0] + rs[1] > 0.f) && !bad);
      rs[0] *= scl; rs[1] *= scl;
      asm volatile("{\n.reg .pred p;\nsetp.ne.u32 p, %1, 0;\n@p rcp.approx.ftz.f32 %0, %0;\n}" : "+f"(rs[0]) : "r"(always));
      asm volatile("{\n.reg .pred p;\nsetp.ne.u32 p, %1, 1;\n@p rcp.approx.ftz.f32 %0, %0;\n}" : "+f"(rs[1]) : "r"(always));
      asm volatile("lop3.b32 %0, %1, %2, %3, 0xfe;" : "=r"(lp) : "r"((l16 & 128) * 2), "r"((l16 & 256) * 4), "r"(l16 & 112));
      if (bad) continue;
      ldsm4t(ob, l16 + SM_OB + 512);
      mma16816z(f[2][0], wa, oc[0], oc[1]); mma16816z(f[2][1], wb, oc[2], oc[3]);
      mma16816z(f[0][0], wo[0], oc[0], oc[1]); mma16816z(f[0][1], wo[4], oc[2], oc[3]);
      mma16816z(f[1][0], w1[0], oc[0], oc[1]); mma16816z(f[1][1], w1[4], oc[2], oc[3]);
      ldsm4t_in(oc, l16 + SM_OB + 1024, always);
      mma16816(f[2][0], vx[2], ob[0], ob[1]); lds128_in(vx[2], w3a + KP(4) * WS, always);
      mma16816(f[2][1], vx[3], ob[2], ob[3]); lds128_in(vx[3], w3a + KP(5) * WS, always);
      mma16816(f[0][0], wo[1], ob[0], ob[1]); mma16816(f[0][1], wo[5], ob[2], ob[3]);
      mma16816(f[1][0], w1[1], ob[0], ob[1]); mma16816(f[1][1], w1[5], ob[2], ob[3]);
      ldsm4t_in(ob, l16 + SM_OB + 1536, always);
      mma16816(f[0][0], wo[2], oc[0], oc[1]); mma16816(f[0][1], wo[6], oc[2], oc[3]);
      mma16816(f[2][0], vx[2], oc[0], oc[1]); lds128_in(vx[2], w3a + KP(6) * WS, always);
      mma16816(f[2][1], vx[3], oc[2], oc[3]); lds128_in(vx[3], w3a + KP(7) * WS, always);
      mma16816(f[1][0], w1[2], oc[0], oc[1]); mma16816(f[1][1], w1[6], oc[2], oc[3]);
      mma16816(f[0][0], wo[3], ob[0], ob[1]); mma16816(f[0][1], wo[7], ob[2], ob[3]);
      mma16816(f[1][0], w1[3], ob[0], ob[1]); mma16816(f[1][1], w1[7], ob[2], ob[3]);
      mma16816(f[2][0], vx[2], ob[0], ob[1]); mma16816(f[2][1], vx[3], ob[2], ob[3]);
      bar_arrive(7, NII < 18 ? 384 : 256);
      lds128_in(ob, sb + SC_DEAD, always);
      uint32_t h[3][2];
#pragma unroll
      for (int j = 0; j < 3; j++)
#pragma unroll
        for (int i = 0; i < 2; i++)
        {
          scale_sum(f[j][1][2 * i], f[j][0][2 * i], rs[0], always); scale_sum(f[j][1][2 * i + 1], f[j][0][2 * i + 1], rs[1], always);
          h[j][i] = pack_f16(f[j][1][2 * i], f[j][1][2 * i + 1]);
        }
      const uint32_t rofs = RANK * 32768;
      red_f16x8(slot(s, RANK >> 1, rofs), h[0][0], h[1][0], h[2][0], 0x3c00u);
      red_f16x8(slot(s, (RANK >> 1) ^ 1, rofs), h[0][1], h[1][1], h[2][1], 0x3c00u);
      if (NII == 18) bar_arrive(10, 256);
      SCHED_FENCE(5);
      l16 += ob[B7R];
    }
    {
    PROF(8);
    const uint32_t ma0 = l16 + SM_MEM + w * 128 + (LV >> 3) * 896 + nh * 512;
    const unsigned char* const sl[2] = {slot(s, nh, 0), slot(s, nh ^ 1, 0)};
    uint32_t dl = gtime() - 1984;
    uint32_t late = latest_hint(hints, dl, s);
    if (late >= 64) {
      int n = 0;
#pragma unroll 1
      do {
        hints = load_hints(hint_addr(s));
        dl = gtime() - 1984;
        late = latest_hint(hints, dl, s);
      } while (late >= 64 && ++n < SPIN_LIMIT);
    }
    dl += late * 32 + tm.poll;
    PROF(9);
    {
      auto wait_until = [&](uint32_t t) {
        asm volatile("{\n.reg .pred p;\n.reg .s32 c;\n.reg .u64 t;\nTL: mov.u64 t, %%globaltimer;\ncvt.u32.u64 c, t;\nsub.s32 c, c, %0;\nsetp.lt.s32 p, c, 0;\n@p bra.uni TL;\n}" :: "r"(t + (l16 & 15)) : "memory");
      };
      uint4 v[2][3];
      auto load = [&](int c) {
#pragma unroll
        for (int r = 0; r < 3; r++) v[c][r] = ldg_relaxed(sl[c ^ (r >> 1)] + r * 32768);
      };
      auto decode = [&](int c, int n) {
        uint32_t q[9];
        __half2 hm;
        const uint32_t ma = ma0 ^ (c * 512);
#pragma unroll
        for (int i = 0; i < 9; i++) {
          const uint32_t h = i % 3 == 0 ? v[c][i / 3].x : (i % 3 == 1 ? v[c][i / 3].y : v[c][i / 3].z);
          const float2 f = __half22float2(*(const __half2*)&h);
          q[i] = pack_bf16(f.x, f.y);
          hm = i ? __hmax2(hm, __habs2(*(const __half2*)&h)) : __habs2(*(const __half2*)&h);
        }
#pragma unroll
        for (int r = 0; r < 3; r++) stsm4(ma + r * 4096, q[3 * r], q[3 * r + 1], q[3 * r + 2], r < 2 ? v[c][r].w : *(const uint32_t*)&hm);
        const bool done = __all_sync(0xffffffffu, v[c][0].w == 0x5000u && v[c][1].w == 0x5000u && v[c][2].w == 0x5000u) || n > SPIN_LIMIT;
        asm volatile("{\n.reg .pred p;\nsetp.ne.u32 p, %0, 0;\n@p bar.arrive %1, 256;\n}" :: "r"((int)done), "r"(1 + c) : "memory");
        return done;
      };
      if (LEAD) { wait_until(dl - LEAD); load(1); }
      int n = MO & 1 ? l16 & 15 : 0;
      if (MO & 1) PIN(n);
      if (MO & 2) {
        const uint32_t t = __shfl_sync(0xffffffffu, dl, 0);
        asm volatile("{\n.reg .pred p;\n.reg .s32 c;\nTL: mov.u32 c, %%globaltimer_lo;\nsub.s32 c, c, %0;\nsetp.lt.s32 p, c, 0;\n@p bra.uni TL;\n}" :: "r"(t) : "memory");
      } else wait_until(dl);
      PROF(10);
#pragma unroll 1
      do {
        load(0);
        if (!LEAD) load(1);
        asm volatile("{\n.reg .pred p;\nsetp.eq.u32 p, %0, 0;\n@p bar.sync 13, 384;\n}" :: "r"(n) : "memory");
      } while (!decode(0, n++));
      PROF(11);
#pragma unroll 1
      while (!decode(1, n++)) load(1);
      bar_arrive(9, 256);
      PROF(12);
    }
    PROF(13);
    if (++s == NSEG - 1) break;
    }
  }
#undef fence_reg
  if (RANK < 2) bar_arrive(4, 256);
  bar_sync(0, 384);
  cluster_sync();
}

__global__ void __cluster_dims__(3, 1, 1) __launch_bounds__(384, 1)
rec_kernel(const __grid_constant__ RMaps tm, const bf16* __restrict__ x, const bf16* __restrict__ mem0) {
  extern __shared__ __align__(1024) unsigned char smem_raw[];
  const uint32_t sb = smem_u32(smem_raw);
  const int tid = threadIdx.x, lane = tid & 31;
  const int wg = __shfl_sync(0xffffffffu, tid >> 7, 0);
  const int w = __shfl_sync(0xffffffffu, (tid >> 5) & 3, 0);
  uint32_t rank; asm("mov.u32 %0, %%cluster_ctarank;" : "=r"(rank));
  STAMP(0);
  asm volatile("griddepcontrol.launch_dependents;" ::: "memory");

  if (wg < 2) {
    if (tid == 0) {
      const int h = blockIdx.x / 3;
      mbar_init(sb + MB_XS, 1);
      for (int i = 0; i < 3; i++) { mbar_init(sb + MB_W + 8 * i, 1); mbar_init(sb + MB_X + 8 * i, 1); }
      mbar_init(sb + MB_WO3, 1);
      fence_async();
      if (blockIdx.x < NSEG) { mbar_expect(sb + MB_XS, XT); bulk_load(sb + SM_STAGE + 2 * 49152, x + blockIdx.x * 32 * DM, XT, sb + MB_XS); }
      load_w(sb, tm, rank, 0);
      mbar_expect(sb + MB_X, XT);
      tma_load3(sb + SM_X, &tm.x, 0, sb + MB_X);
      if (WPOS == 2) load_w(sb, tm, rank, 1);
      mbar_expect(sb + MB_WO3, 32768 + 8 * DM * 2);
      tma_load(sb + SM_WOST, &tm.wo, rank * 192 + 64, h * DH, sb + MB_WO3);
      tma_load(sb + SM_WO3, &tm.wo, rank * 192 + 128, h * DH, sb + MB_WO3);
      bulk_load(sb + SM_M0, mem0, 8 * DM * 2, sb + MB_WO3);
      if (WOPF) tma_prefetch(&tm.wo, rank * 192, h * DH);
      if (WPOS == 1) load_w(sb, tm, rank, 1);
      if (blockIdx.x >= NSEG) load_w(sb, tm, rank, 2);
      mbar_init(sb + MB_WO, 1);
      mbar_init(sb + MB_S, rank < 2 ? 5 : 6);
      mbar_init(sb + MB_F, 1);
      mbar_init(sb + MB_VX, 1); mbar_init(sb + MB_VX + 8, 1);
      asm volatile("fence.mbarrier_init.release.cluster;" ::: "memory");
      fence_async();
      mbar_expect(sb + MB_X + 8, XT); mbar_expect(sb + MB_X + 16, XT);
      mbar_expect(sb + MB_WO, 16384);
      mbar_expect(sb + MB_S, rank < 2 ? 640 + 2048 : 1280);
      mbar_expect(sb + MB_VX, 8192); mbar_expect(sb + MB_VX + 8, 8192);
    }
    __syncwarp();
    asm volatile("setmaxnreg.inc.sync.aligned.u32 192;");
    __syncwarp();
    QSTAMP(0);
    if (tid < 32) bar_arrive(0, 160);
    QSTAMP(1);
    proj_role(sb, tm, rank, wg, w, lane);
  } else {
    asm volatile("setmaxnreg.dec.sync.aligned.u32 120;");
    attn_role(sb, smem_raw, tm, rank, x, mem0, w, lane);
  }
}

constexpr int NAUX = 36;
constexpr int A_ST = 6, A_STAGE = 8192 + 12288, A_W8 = A_ST * A_STAGE, A_EXC = A_W8 + A_ST * 1536, A_ROWS = 57;
constexpr int A_XT = 3 * XT, A_XW = A_XT + 3 * 4096;
constexpr int A_IN = A_EXC + 8 * 2304, A_INB = 3 * SEGB, A_OST = A_IN + 2 * A_INB, A_P = A_OST + 8192, A_G = A_P + 3072;
constexpr int A_BAR = A_G + 1024;
constexpr int A_TOTAL = A_BAR + 512;
static_assert(A_IN % 1024 == 0 && A_IN >= 4 * XT && A_IN + 64 * DM * 2 <= A_BAR && A_TOTAL <= 232448, "side kernel shared memory");
struct AMaps { CUtensorMap x, wa, wa8, o, o3, wob, woa; const unsigned char* red; uint32_t poll; };

DI void wgmma_n192_ss_nt(float* d, uint64_t da, uint64_t db, int acc) {
  asm volatile("{\n.reg .pred p;\nsetp.ne.b32 p, %98, 0;\n"
               "wgmma.mma_async.sync.aligned.m64n192k16.f32.bf16.bf16 {"
               "%0,%1,%2,%3,%4,%5,%6,%7,%8,%9,%10,%11,%12,%13,%14,%15,%16,%17,%18,%19,%20,%21,%22,%23,%24,%25,%26,%27,%28,%29,%30,%31,"
               "%32,%33,%34,%35,%36,%37,%38,%39,%40,%41,%42,%43,%44,%45,%46,%47,%48,%49,%50,%51,%52,%53,%54,%55,%56,%57,%58,%59,%60,%61,%62,%63,"
               "%64,%65,%66,%67,%68,%69,%70,%71,%72,%73,%74,%75,%76,%77,%78,%79,%80,%81,%82,%83,%84,%85,%86,%87,%88,%89,%90,%91,%92,%93,%94,%95"
               "}, %96, %97, p, 1, 1, 0, 1;\n}\n"
               : ACC8(d, 0), ACC8(d, 8), ACC8(d, 16), ACC8(d, 24), ACC8(d, 32), ACC8(d, 40), ACC8(d, 48), ACC8(d, 56),
                 ACC8(d, 64), ACC8(d, 72), ACC8(d, 80), ACC8(d, 88) : "l"(da), "l"(db), "r"(acc));
}
DI void wgmma_n24_ss_nt(float* d, uint64_t da, uint64_t db, int acc) {
  asm volatile("{\n.reg .pred p;\nsetp.ne.b32 p, %14, 0;\n"
               "wgmma.mma_async.sync.aligned.m64n24k16.f32.bf16.bf16 {%0,%1,%2,%3,%4,%5,%6,%7,%8,%9,%10,%11}, %12, %13, p, 1, 1, 0, 1;\n}\n"
               : ACC8(d, 0), "+f"(d[8]), "+f"(d[9]), "+f"(d[10]), "+f"(d[11]) : "l"(da), "l"(db), "r"(acc));
}
DI void tma_load3d(uint32_t dst, const CUtensorMap* m, int c0, int c1, int c2, uint32_t mb) {
  asm volatile("cp.async.bulk.tensor.3d.shared::cluster.global.mbarrier::complete_tx::bytes [%0], [%1, {%3, %4, %5}], [%2];"
               :: "r"(dst), "l"(m), "r"(mb), "r"(c0), "r"(c1), "r"(c2) : "memory");
}
DI uint32_t trans8(uint32_t x) { uint32_t r; asm("movmatrix.sync.aligned.m8n8.trans.b16 %0, %1;" : "=r"(r) : "r"(x)); return r; }
DI void wgmma_n32_ss_tn(float* d, uint64_t da, uint64_t db) {
  asm volatile("wgmma.mma_async.sync.aligned.m64n32k16.f32.bf16.bf16 {%0,%1,%2,%3,%4,%5,%6,%7,%8,%9,%10,%11,%12,%13,%14,%15}, "
               "%16, %17, 1, 1, 1, 1, 0;"
               : ACC8(d, 0), ACC8(d, 8) : "l"(da), "l"(db));
}
DI void wgmma_n40_ss(float* d, uint64_t da, uint64_t db, int acc) {
  asm volatile("{\n.reg .pred p;\nsetp.ne.b32 p, %22, 0;\n"
               "wgmma.mma_async.sync.aligned.m64n40k16.f32.bf16.bf16 {%0,%1,%2,%3,%4,%5,%6,%7,%8,%9,%10,%11,%12,%13,%14,%15,%16,%17,%18,%19}, "
               "%20, %21, p, 1, 1, 1, 1;\n}\n"
               : ACC8(d, 0), ACC8(d, 8), "+f"(d[16]), "+f"(d[17]), "+f"(d[18]), "+f"(d[19]) : "l"(da), "l"(db), "r"(acc));
}
DI uint2 ldg_relaxed64(const void* p) {
  uint2 v; asm volatile("ld.relaxed.gpu.global.v2.b32 {%0,%1}, [%2];" : "=r"(v.x), "=r"(v.y) : "l"(p) : "memory"); return v;
}
template <int ST> DI void ldg8x64(uint32_t* m, const void* p) {
  asm volatile("ld.relaxed.gpu.global.v2.b32 {%0,%1}, [%16];\nld.relaxed.gpu.global.v2.b32 {%2,%3}, [%16 + %17];\n"
               "ld.relaxed.gpu.global.v2.b32 {%4,%5}, [%16 + %18];\nld.relaxed.gpu.global.v2.b32 {%6,%7}, [%16 + %19];\n"
               "ld.relaxed.gpu.global.v2.b32 {%8,%9}, [%16 + %20];\nld.relaxed.gpu.global.v2.b32 {%10,%11}, [%16 + %21];\n"
               "ld.relaxed.gpu.global.v2.b32 {%12,%13}, [%16 + %22];\nld.relaxed.gpu.global.v2.b32 {%14,%15}, [%16 + %23];"
               : "=r"(m[0]), "=r"(m[1]), "=r"(m[2]), "=r"(m[3]), "=r"(m[4]), "=r"(m[5]), "=r"(m[6]), "=r"(m[7]),
                 "=r"(m[8]), "=r"(m[9]), "=r"(m[10]), "=r"(m[11]), "=r"(m[12]), "=r"(m[13]), "=r"(m[14]), "=r"(m[15])
               : "l"(p), "n"(ST), "n"(2 * ST), "n"(3 * ST), "n"(4 * ST), "n"(5 * ST), "n"(6 * ST), "n"(7 * ST) : "memory");
}
template <int ST> DI void ldg4x128(uint32_t* m, const void* p) {
  asm volatile("ld.relaxed.gpu.global.v4.b32 {%0,%1,%2,%3}, [%16];\nld.relaxed.gpu.global.v4.b32 {%4,%5,%6,%7}, [%16 + %17];\n"
               "ld.relaxed.gpu.global.v4.b32 {%8,%9,%10,%11}, [%16 + %18];\nld.relaxed.gpu.global.v4.b32 {%12,%13,%14,%15}, [%16 + %19];"
               : "=r"(m[0]), "=r"(m[1]), "=r"(m[2]), "=r"(m[3]), "=r"(m[4]), "=r"(m[5]), "=r"(m[6]), "=r"(m[7]),
                 "=r"(m[8]), "=r"(m[9]), "=r"(m[10]), "=r"(m[11]), "=r"(m[12]), "=r"(m[13]), "=r"(m[14]), "=r"(m[15])
               : "l"(p), "n"(ST), "n"(2 * ST), "n"(3 * ST) : "memory");
}
template <int N, int ST> DI bool stale(const uint32_t* m, uint32_t tag) {
  uint32_t x = m[0] ^ tag;
#pragma unroll
  for (int i = 1; i < N; i++) asm("lop3.b32 %0, %0, %1, %2, 0xf6;" : "+r"(x) : "r"(m[i * ST]), "r"(tag));
  return __any_sync(0xffffffffu, x & 1);
}
DI bool mbar_test(uint32_t b, uint32_t par) {
  uint32_t r; asm volatile("{\n.reg .pred p;\nmbarrier.test_wait.parity.shared::cta.b64 p, [%1], %2;\nselp.u32 %0, 1, 0, p;\n}" : "=r"(r) : "r"(b), "r"(par) : "memory");
  return r;
}
DI int wait_flags(const unsigned* p, bool active, unsigned base, int seg) {
  int n = 0, m;
  while (true) {
    m = __reduce_min_sync(0xffffffffu, active ? (int)(ldg_acquire32(p) - base) : NSEG);
    if (m > seg || ++n > SPIN_LIMIT) break;
    __nanosleep((YP & 32) ? 400 : 40);
  }
  return max(m, seg + 1);
}
DI void wait_count(const unsigned* p, unsigned target) {
  int n = 0;
  unsigned v;
  while (true) {
    asm volatile("ld.acquire.gpu.global.b32 %0, [%1];" : "=r"(v) : "l"(p) : "memory");
    if ((int)(v - target) >= 0 || ++n > SPIN_LIMIT) break;
    __nanosleep(64);
  }
}
#define PACE_NEXT 800
#define AWARM 0
#define WPF 3
#define UNP 64
#define ADLY 0
#define ODLY 100
#define PING 60
#define FLAG 2
#define FPOS 1
#define QB 1
#define Q_LO 0
#define Q_HI 320
DI bool tick_wait(uint32_t pace, int step) {
  const int n = lds32v(pace);
  if (n <= step) mbar_wait(pace + 8, n & 1);
  return n <= step;
}
DI void quiet_wait(uint32_t pace) {
  uint32_t n, d;
  asm volatile("ld.volatile.shared.v2.b32 {%0,%1}, [%2];" : "=r"(n), "=r"(d) : "r"(pace) : "memory");
  if (n - 1 < NSEG - 2 && (int)(gtime() - d) > Q_HI) mbar_wait(pace + 8, n & 1);
}
DI void sleep_until(uint32_t t) {
  for (int n = 0; n < 64; n++) {
    const int r = t - gtime();
    if (r <= 0) break;
    __nanosleep(r >> 1);
  }
}
DI void aux_barrier(int i, unsigned epoch, bool wait = true) {
  asm volatile("fence.proxy.async;" ::: "memory");
  asm volatile("red.release.gpu.global.add.u32 [%0], 1;" :: "l"(&g_abar[i * 32]) : "memory");
  if (!wait) return;
  wait_count(&g_abar[i * 32], NAUX * (epoch + 1));
  asm volatile("fence.proxy.async;" ::: "memory");
}

__global__ void __launch_bounds__(512, 1)
aux_kernel(const __grid_constant__ AMaps tm, const bf16* __restrict__ x, const bf16* __restrict__ gate_w, bf16* __restrict__ out) {
  extern __shared__ __align__(1024) unsigned char smem_raw[];
  const uint32_t sb = smem_u32(smem_raw);
  const uint32_t full1 = sb + A_BAR, empty1 = full1 + 8 * A_ST, fullw = empty1 + 8 * A_ST, full3 = fullw + 16, empty3 = full3 + 32,
                 fulla = empty3 + 32, emptya = fulla + 32, fullg = emptya + 16, pace = fullg + 8;
  const int tid = threadIdx.x, lane = tid & 31, cta = blockIdx.x;
  const int wg = __shfl_sync(0xffffffffu, tid >> 7, 0), w = __shfl_sync(0xffffffffu, (tid >> 5) & 3, 0);
  ASTAMP(14);
  const unsigned epoch = *(volatile unsigned*)&g_epoch2;
  if (tid == 0) {
    for (int i = 0; i < A_ST; i++) { mbar_init(full1 + 8 * i, 1); mbar_init(empty1 + 8 * i, 8); }
    mbar_init(fullw, 1); mbar_init(fullw + 8, 1); mbar_init(fullg, 1);
    for (int i = 0; i < 2; i++) { mbar_init(fulla + 16 * i, 2); mbar_init(fulla + 16 * i + 8, 1); mbar_init(emptya + 8 * i, 4); }
    sts64(pace, 0, 0); mbar_init(pace + 8, 1); sts32(pace + 16, 0); sts64(pace + 24, 65536, 0xffff0000u);
    for (int i = 0; i < 4; i++) { mbar_init(full3 + 8 * i, 1); mbar_init(empty3 + 8 * i, cta < NH ? 8 : 4); }
    fence_async();
  }
  __syncthreads();
  ASTAMP(0);
  const bool wide = cta < NH;
  auto p3_ks = [&](int g) { return wide ? cta >> 2 : 2 * (cta - NH) + g; };
  auto p3_mt = [&](int g) { return wide ? 2 * (cta & 3) + g : 8; };
  const uint32_t xt = sb + (wide ? A_XT : A_IN), xw = sb + (wide ? A_XW : A_IN + 16384);
  const unsigned fbase = epoch * NSEG;
  if (wg == 3) {
    asm volatile("setmaxnreg.dec.sync.aligned.u32 48;");
    if (w == 1 && cta < NH) {
#pragma unroll 1
      for (int seg = 0; seg < ((XP & 2048) ? 0 : NSEG); seg++) {
        bar_arrive(5, 160);
        if (seg > 0 && lane == 0) {
          asm volatile("cp.async.bulk.wait_group 0;" ::: "memory");
          stg_relaxed32(&g_oflag[cta * 32], fbase + seg);
        }
        __syncwarp();
        bar_sync(4, 160);
        if (QM & 16) tick_wait(pace, seg + 1);
        if (lane == 0) {
          fence_async();
          if (!(YP & 2)) {
          tma_store(&tm.o, sb + A_OST, cta * DH, seg * 32);
          tma_store(&tm.o, sb + A_OST + 4096, cta * DH + 64, seg * 32);
          }
          asm volatile("cp.async.bulk.commit_group;" ::: "memory");
          asm volatile("cp.async.bulk.wait_group.read 0;" ::: "memory");
        }
        __syncwarp();
      }
      if (lane == 0) {
        asm volatile("cp.async.bulk.wait_group 0;" ::: "memory");
        { const int seg = NSEG - 1; TSTAMP(2); }
        stg_relaxed32(&g_oflag[cta * 32], fbase + NSEG);
      }
    }
    if (w == 2 && cta < NH) {
      const uint32_t ktag = (epoch + 1) & 1, ma = sb + A_IN + 8192 + lane * 16;
      int avail = 0;
      bar_sync(10, 64);
#pragma unroll 1
      for (int seg = 0; seg < ((XP & 2048) ? 0 : NSEG); seg++) {
        if (avail <= seg) avail = wait_flags(&g_sflag[(cta * 3 + min(lane, 2)) * 8], true, fbase, seg);
        if ((QM & 8) && seg < UNP) tick_wait(pace, seg);
        TSTAMP(0);
        const unsigned char* km = g_km + (size_t)(seg * NH + cta) * 4096 + lane * 8;
        uint32_t m[16];
        const float g = __ldcg(&g_gate[seg * 32 + lane]);
        ldg8x64<256>(m, km);
        const uint32_t b = seg & 1, full = fulla + 16 * b, mb = ma + b * A_INB;
        mbar_wait(emptya + 8 * b, (~seg >> 1) & 1);
        if (lane < 2) mbar_expect(full + 8 * lane, (YP & 8) ? 0 : 16384 >> lane);
        __syncwarp();
        if (lane < 3 && !(YP & 8)) ((EF & 2) ? bulk_load_ef : bulk_load)(sb + A_IN + b * A_INB + lane * SEGB, g_seg + ((size_t)(seg & RING) * 96 + cta * 3 + lane) * 8192, 8192, full + (lane & 2) * 4);
        int n = 0;
#pragma unroll 1
        while (stale<8, 2>(m, ktag) && ++n < SPIN_LIMIT) { if (seg < UNP - 1) __nanosleep(200); ldg8x64<256>(m, km); }
        TSTAMP(1);
#pragma unroll
        for (int i = 0; i < 4; i++) stsm4(mb + (i >> 1) * SEGB + (i & 1) * 512, m[4 * i], m[4 * i + 1], m[4 * i + 2], m[4 * i + 3]);
        sts32(sb + A_G + b * 128 + lane * 4, __float_as_uint(1.f - g));
        fence_async();
        __syncwarp();
        if (lane == 0) mbar_arrive(full);
      }
    }
    if (w == 3 && QM) {
      const unsigned char* const hp = tm.red + HINT_OFF + 65536 + (cta & 1) * 4096 + min(lane, 23) * 4;
      uint32_t d = 0;
      int s = 0, n = 0;
#pragma unroll 1
      while (s < NSEG - 1) {
        const uint32_t h = ldg_relaxed32(hp + RED_SLOT(s)), t = (gtime() - 1984) & ~31u, late = latest_hint(h, t, s);
        if (late < 64) {
          d = t + late * 32 + tm.poll + Q_LO;
          sleep_until(d);
          s++; n = 0;
          if (lane == 0) { mbar_arrive(pace + 8); sts64(pace, s < NSEG - 1 ? s : 2 * NSEG, d); }
          sleep_until(d + PACE_NEXT);
        } else {
          if (++n > (s ? 16 : 256) || lds32v(pace + 16)) break;
          if (!s) __nanosleep(100);
        }
      }
      if (s < NSEG - 1 && lane == 0) { mbar_arrive(pace + 8); sts64(pace, 2 * NSEG, d); }
    }
    if (w != 0) return;
    const bool lead = lane == 0;
    if (ADLY) sleep_until(gtime() + ADLY);
    if (lead) {
#pragma unroll 1
      for (int it = 0, st = 0, ph = 1, k = 0, col = (cta & 1) * (DM / 2); it < ((XP & 256) ? 0 : 72); it++) {
        mbar_wait(empty1 + 8 * st, ph);
        if (QM & 1) quiet_wait(pace);
        mbar_expect(full1 + 8 * st, A_STAGE + 1536);
        tma_load3d(sb + st * A_STAGE, &tm.x, k, (cta >> 1) * A_ROWS - 7, 0, full1 + 8 * st);
        tma_load3d(sb + st * A_STAGE + 8192, &tm.wa, col, k, 0, full1 + 8 * st);
        tma_load3d(sb + A_W8 + st * 1536, &tm.wa8, col + 64, k, 0, full1 + 8 * st);
        if (++st == A_ST) { st = 0; ph ^= 1; }
        k += 32;
        if (k == DM) { k = 0; col += 72; }
      }
    }
    __syncwarp();
    auto load_wo = [&](uint32_t dst, int g, int kb, uint32_t mb) {
      if (kb < 64) tma_load(dst, &tm.wob, p3_mt(g) * 64, kb * 64, mb);
      else tma_load(dst, &tm.woa, p3_mt(g) * 64, (kb - 64) * 64, mb);
    };
    if (lead) mbar_expect(fullw, 16 * 8192);
#pragma unroll 1
    for (int st = 0; st < A_ST; st++) {
      if (!(XP & 256)) mbar_wait(empty1 + 8 * st, 1);
      if (lane < 16 && min(((lane + 1) * 8192 - 1) / A_STAGE, A_ST - 1) == st) load_wo(sb + lane * 8192, lane >> 3, p3_ks(lane >> 3) * 9 + (lane & 7), fullw);
      __syncwarp();
    }
    __syncwarp(); bar_sync(6, 288);
    if (lead) mbar_expect(fullw + 8, 2 * 8192);
    __syncwarp();
    if (lane < 2) load_wo(sb + (16 + lane) * 8192, lane, p3_ks(lane) * 9 + 8, fullw + 8);
    __syncwarp();
    if (lead) aux_barrier(1, epoch, p3_ks(1) == 7);
    __syncwarp(); bar_sync(6, 288);
    {
      int avail = 0, sl = 0, ph = 1;
      const int h = (9 * p3_ks(0) >> 1) + lane;
#pragma unroll 1
      for (int seg = 0; seg < ((XP & 2048) ? 0 : NSEG); seg++) {
        if (avail <= seg) avail = wait_flags(&g_oflag[min(h, NH - 1) * 32], lane < (wide ? 5 : 9), fbase, seg);
        SSTAMP(seg, 4);
        for (int g = 0; g < (wide ? 1 : 2); g++) {
          const int ks = p3_ks(g);
          mbar_wait(empty3 + 8 * sl, ph);
          if ((QM & 4) && tick_wait(pace, seg + (QM >> 4 & 1) + 1) && ODLY) __nanosleep(ODLY);
          if (lead && (YP & 4)) mbar_arrive(full3 + 8 * sl);
          else if (lead) {
            mbar_expect(full3 + 8 * sl, XT + (ks == 7 ? (seg ? 4096 : wide ? 20480 : 12288) : 0));
            tma_load3d(sb + sl * XT, &tm.o3, 0, seg * 32, ks * 9, full3 + 8 * sl);
            if (ks == 7) {
              tma_load(xt + sl * 4096, &tm.o, 72 * 64, seg * 32, full3 + 8 * sl);
              if (seg == 0) { load_wo(xw + 8192, 1, 72, full3 + 8 * sl); if (wide) load_wo(xw, 0, 72, full3 + 8 * sl); }
            }
          }
          __syncwarp();
          if (++sl == (wide ? 3 : 4)) { sl = 0; ph ^= 1; }
        }
      }
    }
    sts32(pace + 16, 1);
    __syncwarp(); bar_sync(6, 288);
    asm volatile("griddepcontrol.wait;" ::: "memory");
  } else if (wg == 2) {
    asm volatile("setmaxnreg.dec.sync.aligned.u32 64;");
    if (cta < NH) {
      if (tid == 256) { mbar_expect(fullg, 64 * DM * 2); bulk_load(sb + A_IN, x + cta * 64 * DM, 64 * DM * 2, fullg); }
      uint32_t gw[9];
#pragma unroll
      for (int j = 0; j < 9; j++) gw[j] = ((const uint32_t*)gate_w)[j * 32 + lane];
      mbar_wait(fullg, 0);
      float mine = 0.f;
#pragma unroll 4
      for (int u = 0; u < 16; u++) {
        float d0 = 0.f, d1 = 0.f;
#pragma unroll
        for (int j = 0; j < 9; j++) {
          const uint32_t a = lds32(sb + A_IN + (w * 16 + u) * (DM * 2) + j * 128 + lane * 4);
          d0 = fmaf(bf_lo(a), bf_lo(gw[j]), d0); d1 = fmaf(bf_hi(a), bf_hi(gw[j]), d1);
        }
        d0 = warp_sum(d0 + d1);
        if (lane == u) mine = d0;
      }
      if (lane < 16) g_gate[cta * 64 + w * 16 + lane] = 1.f / (1.f + __expf(-mine));
      fence_async();
    }
    bar_sync(3, 128);
    if (tid == 256) { aux_barrier(0, epoch); if (cta == 0) *(volatile unsigned*)&g_epoch2 = epoch + 1; }
    __syncwarp();
    bar_sync(3, 128);
    if (w == 0) bar_arrive(8, 288);
    if (w == 1 && cta < NH) bar_arrive(10, 64);
    if (cta < NH) {
      CDECL;
#pragma unroll 1
      for (int seg = 0; seg < ((XP & 2048) ? 0 : NSEG); seg++) {
        CSTAMP(0);
        const uint32_t in = sb + A_IN + (seg & 1) * A_INB;
        const uint64_t qd = make_desc(in, 128, 1024, 0);
        mbar_wait(fulla + 16 * (seg & 1), (seg >> 1) & 1);
        CSTAMP(3);
        SSTAMP(seg, 0);
        float d[2][16];
        {
          float a[20];
          uint32_t vm[16];
          const unsigned char* vp = g_km + (size_t)(seg * NH + cta) * 4096 + 2048 + lane * 16;
          if (w == 3) ldg4x128<512>(vm, vp);
          WG_FENCE();
#pragma unroll
          for (int k = 0; k < ((YP & 16) ? 1 : 8); k++) wgmma_n40_ss(a, qd + ((k >> 2) * SEGB + (k & 3) * 256 >> 4), qd + ((k >> 2) * SEGB + (k & 3) * 256 + 4096 >> 4), k > 0);
          const uint32_t ga = sb + A_G + (seg & 1) * 128 + (w & 1) * 64 + (lane >> 2) * 4;
          const float f0 = __uint_as_float(lds32(ga)), f1 = __uint_as_float(lds32(ga + 32));
          WG_COMMIT();
          WG_WAIT(0);
          CSTAMP(5);
          SSTAMP(seg, 1);
          if (w < 2) {
            const int lim = w * 16 + (lane >> 2) - 2 * (lane & 3);
            float m0 = -3.0e38f, m1 = -3.0e38f;
#pragma unroll
            for (int i = 0; i < 20; i++) {
              a[i] *= SM_SCALE * LOG2E;
              if (i < 16 && (i >> 2) * 8 + (i & 1) - (i & 2) * 4 > lim) a[i] = -1.0e9f * LOG2E;
              if (i & 2) m1 = fmaxf(m1, a[i]); else m0 = fmaxf(m0, a[i]);
            }
#pragma unroll
            for (int o = 1; o < 4; o <<= 1) { m0 = fmaxf(m0, __shfl_xor_sync(0xffffffffu, m0, o)); m1 = fmaxf(m1, __shfl_xor_sync(0xffffffffu, m1, o)); }
            float s0 = 0.f, s1 = 0.f;
#pragma unroll
            for (int i = 0; i < 20; i++) { a[i] = ex2(a[i] - (i & 2 ? m1 : m0)); if (i & 2) s1 += a[i]; else s0 += a[i]; }
#pragma unroll
            for (int o = 1; o < 4; o <<= 1) { s0 += __shfl_xor_sync(0xffffffffu, s0, o); s1 += __shfl_xor_sync(0xffffffffu, s1, o); }
            s0 = f0 * rcp(s0); s1 = f1 * rcp(s1);
            uint32_t p[10];
#pragma unroll
            for (int i = 0; i < 10; i++) p[i] = pack_bf16(a[2 * i] * (i & 1 ? s1 : s0), a[2 * i + 1] * (i & 1 ? s1 : s0));
            const uint32_t pa = sb + A_P + (2 * w + ((lane >> 3) & 1)) * 768 + (lane >> 4) * 128 + (lane & 7) * 16;
            stsm4t(pa, p[0], p[1], p[2], p[3]); stsm4t(pa + 256, p[4], p[5], p[6], p[7]); stsm4t(pa + 512, p[8], p[9], 0, 0);
            CSTAMP(6);
            fence_async();
            CSTAMP(7);
          } else if (w == 3) {
            int n = 0;
#pragma unroll 1
            while (stale<4, 4>(vm, (epoch + 1) & 1) && ++n < SPIN_LIMIT) ldg4x128<512>(vm, vp);
#pragma unroll
            for (int i = 0; i < 4; i++) stsm4(in + 2 * SEGB + 8192 + (lane >> 4) * 1024 + (lane & 15) * 16 + i * 256, vm[4 * i], vm[4 * i + 1], vm[4 * i + 2], vm[4 * i + 3]);
            fence_async();
            mbar_wait(fulla + 16 * (seg & 1) + 8, (seg >> 1) & 1);
          }
        }
        CSTAMP(8);

        bar_sync(5, 160);
        CSTAMP(10);
        SSTAMP(seg, 2);
        const uint64_t pd = make_desc(sb + A_P, 128, 768, 0), vd = make_desc(in + 2 * SEGB, 128, 512, 0), md = make_desc(in + 2 * SEGB + 8192, 0, 128, 0);
        WG_FENCE();
#pragma unroll
        for (int i = 0; i < 2; i++) {
          wgmma_n32_ss<0>(d[i], vd + i * 256, pd, 0);
          wgmma_n32_ss<0>(d[i], vd + i * 256 + 16, pd + 16, 1);
          wgmma_n32_ss<0>(d[i], md + i * 64, pd + 32, 1);
        }
        WG_COMMIT();
        WG_WAIT(0);
        CSTAMP(11);
        if (lane == 0) mbar_arrive(emptya + 8 * (seg & 1));
#pragma unroll
        for (int i = 0; i < 2; i++) {
          const uint32_t oa = sb + A_OST + i * 4096 + ((lane & 7) + ((lane >> 4) << 3)) * 128 + (((2 * w + ((lane >> 3) & 1)) ^ (lane & 7)) << 4);
          stsm4t(oa, pack_bf16(d[i][0], d[i][1]), pack_bf16(d[i][2], d[i][3]), pack_bf16(d[i][4], d[i][5]), pack_bf16(d[i][6], d[i][7]));
          stsm4t(oa + 2048, pack_bf16(d[i][8], d[i][9]), pack_bf16(d[i][10], d[i][11]), pack_bf16(d[i][12], d[i][13]), pack_bf16(d[i][14], d[i][15]));
        }
        CSTAMP(12);
        bar_sync(4, 160);
        SSTAMP(seg, 3);
      }
      CDUMP;
    }
  } else {
    asm volatile("setmaxnreg.inc.sync.aligned.u32 200;");
    {
      const int g = lane >> 2, t = lane & 3, r0 = (cta >> 1) * A_ROWS - 7 + w * 16;
      const uint32_t prev = (2 * t > g ? 0xffffu : 0u) | (2 * t + 1 > g ? 0xffff0000u : 0u);
      const int k0 = r0 + 2 * t - (2 * t > g ? 8 : 0), k1 = r0 + 2 * t + 1 - (2 * t + 1 > g ? 8 : 0);
      const uint32_t slot = sb + A_EXC + (wg * 4 + w) * 2304;
      float gl = 0.f, gh = 0.f;
      int st = 0, ph = 0;
#pragma unroll 1
      for (int p = -AWARM; p < ((XP & 256) ? 0 : 4); p++) {
        float big[96], sml[12];
        if (p == WPF && tid < 18) {
          const int kb = p3_ks(tid >= 9) * 9 + tid % 9;
          tma_prefetch(kb < 64 ? &tm.wob : &tm.woa, p3_mt(tid >= 9) * 64, (kb & 63) * 64);
        }
        __syncwarp();
#pragma unroll
        for (int i = 0; i < 96; i++) big[i] = 0.f;
#pragma unroll
        for (int i = 0; i < 12; i++) sml[i] = 0.f;
#pragma unroll 1
        for (int k = p < 0 ? 18 : 0; k < 18; k++) {
          mbar_wait(full1 + 8 * st, ph);
          const uint64_t da = make_desc(sb + st * A_STAGE + wg * 4096, 16, 512, 2);
          const uint64_t db = make_desc(sb + st * A_STAGE + 8192, 4096, 1024, 1), dc = make_desc(sb + A_W8 + st * 1536, 128, 512, 0);
          WG_FENCE();
#pragma unroll
          for (int j = 0; j < 2; j++) { wgmma_n192_ss_nt(big, da + j * 2, db + j * 128, 1); wgmma_n24_ss_nt(sml, da + j * 2, dc + j * 16, 1); }
          WG_COMMIT();
          WG_WAIT(1);
          if (k > 0 && lane == 0) mbar_arrive(empty1 + 8 * (st ? st - 1 : A_ST - 1));
          if (++st == A_ST) { st = 0; ph ^= 1; }
        }
        WG_WAIT(0);
        ASTAMP(16 + max(p, 0) + wg * 16);
        if (lane == 0 && p >= 0) mbar_arrive(empty1 + 8 * (st ? st - 1 : A_ST - 1));
        uint32_t f[3][9][2];
#pragma unroll
        for (int c = 0; c < 3; c++)
#pragma unroll
          for (int j = 0; j < 9; j++)
#pragma unroll
            for (int i = 0; i < 2; i++) {
              const float* a = j < 8 ? &big[(c * 8 + j) * 4 + 2 * i] : &sml[c * 4 + 2 * i];
              f[c][j][i] = c < 2 ? pack_bf16(a[0], a[1]) : trans8(pack_bf16(a[0], a[1]));
            }
        if (p == 0) {
          bar_sync(8, 288);
          gl = __ldcg(&g_gate[min(max(r0 + g, 0), S_LEN / 2 - 1) * 2 + wg]); gh = __ldcg(&g_gate[min(max(r0 + g + 8, 0), S_LEN / 2 - 1) * 2 + wg]);
        }
        asm volatile("cp.async.bulk.wait_group.read 0;" ::: "memory");
        __syncwarp();
#pragma unroll
        for (int j = 0; j < 8; j += 2) sts128(slot + j * 256 + lane * 16, f[1][j][1], f[2][j][1], f[1][j + 1][1], f[2][j + 1][1]);
        sts64(slot + 2048 + lane * 8, f[1][8][1], f[2][8][1]);
        bar_sync(1 + wg, 128);
        ASTAMP(24 + max(p, 0) + wg * 16);
        uint32_t pv[9][2];
#pragma unroll
        for (int j = 0; j < 9; j++) pv[j][0] = pv[j][1] = 0;
        if (w) {
#pragma unroll
          for (int j = 0; j < 8; j += 2) lds128(slot - 2304 + j * 256 + lane * 16, pv[j]);
          lds64(slot - 256 + lane * 8, pv[8][0], pv[8][1]);
        }
        float a[4][4], m[4][2];
#pragma unroll
        for (int h = 0; h < 4; h++) {
          const int j = 2 * h;
          const uint32_t qa[4] = {t >= h ? f[0][j][0] : 0, t >= h ? f[0][j][1] : 0, f[0][j + 1][0], f[0][j + 1][1]};
          const uint32_t qb0 = t <= h ? f[0][j + 2][0] : 0, qb1 = t <= h ? f[0][j + 2][1] : 0;
          float s0[4], s1[4], s2[4];
          mma16816z(s1, qa, f[1][j][0], f[1][j + 1][0]); mma16816z(s2, qa, f[1][j][1], f[1][j + 1][1]); mma16816z(s0, qa, pv[j][0], pv[j + 1][0]);
          mma1688(s1, qb0, qb1, f[1][j + 2][0]); mma1688(s2, qb0, qb1, f[1][j + 2][1]); mma1688(s0, qb0, qb1, pv[j + 2][0]);
          a[h][0] = 2 * t > g ? s0[0] : s1[0]; a[h][1] = 2 * t + 1 > g ? s0[1] : s1[1]; a[h][2] = 2 * t > g ? s1[2] : s2[2]; a[h][3] = 2 * t + 1 > g ? s1[3] : s2[3];
        }
#pragma unroll
        for (int h = 0; h < 4; h++) {
#pragma unroll
          for (int i = 0; i < 4; i++) a[h][i] = (i & 1 ? k1 : k0) + (i & 2) * 4 >= 0 ? a[h][i] * (0.23570226039551584f * LOG2E) : -1.0e9f * LOG2E;
          m[h][0] = fmaxf(a[h][0], a[h][1]); m[h][1] = fmaxf(a[h][2], a[h][3]);
        }
#pragma unroll
        for (int x = 1; x < 4; x <<= 1)
#pragma unroll
          for (int i = 0; i < 8; i++) m[i >> 1][i & 1] = fmaxf(m[i >> 1][i & 1], __shfl_xor_sync(0xffffffffu, m[i >> 1][i & 1], x));
#pragma unroll
        for (int h = 0; h < 4; h++) {
#pragma unroll
          for (int i = 0; i < 4; i++) a[h][i] = ex2(a[h][i] - m[h][i >> 1]);
          m[h][0] = a[h][0] + a[h][1]; m[h][1] = a[h][2] + a[h][3];
        }
#pragma unroll
        for (int x = 1; x < 4; x <<= 1)
#pragma unroll
          for (int i = 0; i < 8; i++) m[i >> 1][i & 1] += __shfl_xor_sync(0xffffffffu, m[i >> 1][i & 1], x);
        uint32_t o[9][2];
#pragma unroll
        for (int h = 0; h < 4; h++) {
          const int j = 2 * h;
          const float z0 = gl * rcp(m[h][0]), z1 = gh * rcp(m[h][1]);
          const uint32_t pl = pack_bf16(a[h][0] * z0, a[h][1] * z0), pu = pack_bf16(a[h][2] * z1, a[h][3] * z1);
          const uint32_t pa[4] = {pl & prev, 0, pl & ~prev, pu & prev};
          float d[3][4];
#pragma unroll
          for (int i = 0; i < 3; i++) mma16816z(d[i], pa, pv[j + i][1], f[2][j + i][0]);
#pragma unroll
          for (int i = 0; i < 3; i++) mma1688(d[i], 0, pu & ~prev, f[2][j + i][1]);
#pragma unroll
          for (int i = 0; i < 3; i++) {
            const uint32_t d0 = pack_bf16(d[i][0], d[i][1]), d1 = pack_bf16(d[i][2], d[i][3]);
            o[j + i][0] = i == 0 && h > 0 && t < h ? o[j][0] : d0;
            o[j + i][1] = i == 0 && h > 0 && t < h ? o[j][1] : d1;
          }
        }
        ASTAMP(28 + max(p, 0) + wg * 16);
        bar_sync(1 + wg, 128);
        const uint32_t oa = slot + (lane & 15) * 144 + (lane >> 4) * 16;
#pragma unroll
        for (int j = 0; j < 8; j += 2) stsm4(oa + j * 16, o[j][0], o[j][1], o[j + 1][0], o[j + 1][1]);
        asm volatile("stmatrix.sync.aligned.m8n8.x2.shared.b16 [%0], {%1,%2};" :: "r"(oa + 128), "r"(o[8][0]), "r"(o[8][1]) : "memory");
        fence_async();
        __syncwarp();
        if (QM & 64) quiet_wait(pace);
        if (lane < 16 && w * 16 + lane >= 7 && r0 + lane < S_LEN / 2 && p >= 0)
          asm volatile("cp.async.bulk.global.shared::cta.bulk_group [%0], [%1], 144;"
                       :: "l"(g_Ocat + (size_t)((r0 + lane) * 2 + wg) * KCAT + 4096 + (cta & 1) * (DM / 2) + p * 72), "r"(slot + lane * 144) : "memory");
        asm volatile("cp.async.bulk.commit_group;" ::: "memory");
        ASTAMP(20 + max(p, 0) + wg * 16);
      }
      if (XP & 256) bar_sync(8, 288);
      asm volatile("cp.async.bulk.wait_group 0;" ::: "memory");
    }
    ASTAMP(3);
    bar_arrive(6, 288);
    uint32_t wa[36][4];
    mbar_wait(fullw, 0);
    const uint32_t la = sb + ((lane & 7) + ((lane >> 4) << 3)) * 128 + (((2 * w + ((lane >> 3) & 1)) ^ (lane & 7)) << 4);
#pragma unroll
    for (int k = 0; k < 32; k++) ldsm4t(wa[k], la + wg * 65536 + k * 2048);
    mbar_wait(fullw + 8, 0);
#pragma unroll
    for (int k = 32; k < 36; k++) ldsm4t(wa[k], la + wg * 8192 + 65536 + k * 2048);
    fence_async();
    if (XP & 2048) bar_sync(6, 288); else bar_arrive(6, 288);
    ASTAMP(4);
    const int ks = p3_ks(wg), mt = p3_mt(wg);
    uint32_t v[16];
    auto fetch = [&](int seg) { ldg8x64<1024>(v, g_part + (((seg & 7) * 9 + mt) * 4 + (ks & 3)) * 1024 + (tid & 127)); };
    auto finish = [&](int seg) {
      const uint32_t tagv = (~seg >> 3) & 1;
      int n = 0;
#pragma unroll 1
      while (stale<8, 2>(v, tagv) && ++n < SPIN_LIMIT) {
        if (seg < NSEG - 2) __nanosleep(100);
        fetch(seg);
      }
      float own[4] = {bf_lo(v[0]), bf_hi(v[0]), bf_lo(v[1]), bf_hi(v[1])};
#pragma unroll
      for (int j = 1; j < 8; j++) { own[0] += bf_lo(v[2 * j]); own[1] += bf_hi(v[2 * j]); own[2] += bf_lo(v[2 * j + 1]); own[3] += bf_hi(v[2 * j + 1]); }
      uint32_t p0 = pack_bf16(own[0], own[1]), p1 = pack_bf16(own[2], own[3]);
      asm volatile("movmatrix.sync.aligned.m8n8.trans.b16 %0, %0;" : "+r"(p0));
      asm volatile("movmatrix.sync.aligned.m8n8.trans.b16 %0, %0;" : "+r"(p1));
      uint32_t* o = (uint32_t*)(out + (size_t)(seg * 32 + (ks & 3) * 8 + (lane >> 2)) * DM + mt * 64 + w * 16) + (lane & 3);
      o[0] = p0; o[4] = p1;
      SSTAMP(seg, 7);
    };
    float acc[16];
#pragma unroll
    for (int i = 0; i < 16; i++) acc[i] = 0.f;
    int pend = -1, sl = wide ? 0 : wg, ph = 0;
    if (PING && wg) bar_arrive(1, 256);
    CDECL;
    auto run = [&](auto extra) {
#pragma unroll 1
    for (int seg = 0; seg < ((XP & 2048) ? 0 : NSEG); seg++) {
      CSTAMP(0);
      const bool fin = pend >= 0 && seg - pend >= FLAG;
      if (FPOS == 0 && fin) fetch(pend);
      mbar_wait(full3 + 8 * sl, ph);
      if (FPOS == 1 && fin) fetch(pend);
      CSTAMP(1);
      if (wg) SSTAMP(seg, 5);
      if (seg < PING) bar_sync(1 + wg, 256);
      CSTAMP(7);
      const uint64_t db = make_desc(sb + sl * XT, 16, 1024, 1);
      WG_FENCE();
#pragma unroll
      for (int k = 0; k < ((XP & 1024) ? 1 : 36); k++) wgmma_n32_rs(acc, wa[k][0], wa[k][1], wa[k][2], wa[k][3], db + (k >> 2) * 256 + (k & 3) * 2, k);
      if (decltype(extra)::value) {
        const uint64_t da = make_desc(xw + wg * 8192, 8192, 1024, 1), de = make_desc(xt + sl * 4096, 16, 1024, 1);
#pragma unroll
        for (int j = 0; j < 4; j++) wgmma_n32_ss_tn(acc, da + j * 128, de + j * 2);
      }
      WG_COMMIT();
      if (seg < PING) bar_arrive(2 - wg, 256);
      CSTAMP(2);
      if (FPOS == 2 && fin) fetch(pend);
      CSTAMP(3);
      WG_WAIT(0);
      CSTAMP(4);
      if (wg) SSTAMP(seg, 6);
      if (lane == 0) mbar_arrive(empty3 + 8 * sl);
      sl += wide ? 1 : 2;
      if (sl >= (wide ? 3 : 4)) { sl -= wide ? 3 : 4; ph ^= 1; }
      uint2* dst = g_part + (((seg & 7) * 9 + mt) * 32 + ks) * 128 + (tid & 127);
      uint32_t q[8];
#pragma unroll
      for (int j = 0; j < 8; j++) q[j] = j & 1 ? pack_bf16(acc[2 * j], acc[2 * j + 1]) : (pack_bf16(acc[2 * j], acc[2 * j + 1]) & ~1u) | ((~seg >> 3) & 1);
      if (QM & 32) tick_wait(pace, seg + (QM >> 4 & 1) + 2);
      if (!(YP & 1) || q[0] == 0x12345678)
      asm volatile("st.relaxed.gpu.global.v2.b32 [%0], {%1,%2};\nst.relaxed.gpu.global.v2.b32 [%0 + 8192], {%3,%4};\n"
                   "st.relaxed.gpu.global.v2.b32 [%0 + 16384], {%5,%6};\nst.relaxed.gpu.global.v2.b32 [%0 + 24576], {%7,%8};"
                   :: "l"(dst), "r"(q[0]), "r"(q[1]), "r"(q[2]), "r"(q[3]), "r"(q[4]), "r"(q[5]), "r"(q[6]), "r"(q[7]) : "memory");
      CSTAMP(5);
      if (fin) { finish(pend); pend = -1; }
      CSTAMP(6);
      if ((seg & 1) == ks >> 2 && !(YP & 1)) pend = seg;
      if (wg && (seg & 7) == 6) ASTAMP(5 + (seg >> 3));
    }
    };
    if (ks == 7) run(BoolC<true>()); else run(BoolC<false>());
    if (PING && !wg) bar_sync(1, 256);
    if (pend >= 0) { fetch(pend); finish(pend); }
    CDUMP;
    ASTAMP(13);
    bar_sync(6, 288);
  }
}

typedef CUresult (*EncodeFn)(CUtensorMap*, CUtensorMapDataType, cuuint32_t, void*, const cuuint64_t*, const cuuint64_t*,
                             const cuuint32_t*, const cuuint32_t*, CUtensorMapInterleave, CUtensorMapSwizzle,
                             CUtensorMapL2promotion, CUtensorMapFloatOOBfill);
#define PROMO 2
static void make_map(EncodeFn enc, CUtensorMap* m, const void* p, int rows, int cols, int box_rows) {
  cuuint64_t dims[2] = {(cuuint64_t)cols, (cuuint64_t)rows};
  cuuint64_t strides[1] = {(cuuint64_t)cols * 2};
  cuuint32_t box[2] = {64, (cuuint32_t)box_rows};
  cuuint32_t es[2] = {1, 1};
  enc(m, CU_TENSOR_MAP_DATA_TYPE_BFLOAT16, 2, (void*)p, dims, strides, box, es, CU_TENSOR_MAP_INTERLEAVE_NONE,
      CU_TENSOR_MAP_SWIZZLE_128B, (CUtensorMapL2promotion)PROMO, CU_TENSOR_MAP_FLOAT_OOB_FILL_NONE);
}

constexpr int g_poll = POLL_NS;
extern "C" void kernel_launch(void* const* d_in, const int* in_sizes, int n_in, void* d_out, int out_size) {
  const bf16* x = (const bf16*)d_in[0];
  const bf16* wqkvA = (const bf16*)d_in[1];
  const bf16* woA = (const bf16*)d_in[2];
  const bf16* mem0 = (const bf16*)d_in[4];
  const bf16* Wq = (const bf16*)d_in[5];
  const bf16* Wk = (const bf16*)d_in[6];
  const bf16* Wv = (const bf16*)d_in[7];
  const bf16* Wo = (const bf16*)d_in[8];
  const bf16* gate_w = (const bf16*)d_in[10];
  static EncodeFn enc = nullptr;
  static void *pO = nullptr, *pR = nullptr;
  if (!enc) {
    cudaDriverEntryPointQueryResult qr;
    cudaGetDriverEntryPoint("cuTensorMapEncodeTiled", (void**)&enc, cudaEnableDefault, &qr);
    cudaGetSymbolAddress(&pO, g_Ocat);
    cudaGetSymbolAddress(&pR, g_red_raw);
    cudaFuncSetAttribute(rec_kernel, cudaFuncAttributeMaxDynamicSharedMemorySize, SM_TOTAL);
    cudaFuncSetAttribute(aux_kernel, cudaFuncAttributeMaxDynamicSharedMemorySize, A_TOTAL);
  }
  RMaps rm;
  rm.poll = g_poll;
  rm.w[0] = (const unsigned char*)Wk; rm.w[1] = (const unsigned char*)Wq; rm.w[2] = (const unsigned char*)Wv; rm.w[3] = (const unsigned char*)Wo;
  rm.red = (unsigned char*)(((uintptr_t)pR + 262143) & ~(uintptr_t)262143);
  {
    cuuint64_t dims[3] = {64, S_LEN, 9}, strides[2] = {DM * 2, 128};
    cuuint32_t box[3] = {64, 32, 9}, es[3] = {1, 1, 1};
    enc(&rm.x, CU_TENSOR_MAP_DATA_TYPE_BFLOAT16, 3, (void*)x, dims, strides, box, es, CU_TENSOR_MAP_INTERLEAVE_NONE,
        CU_TENSOR_MAP_SWIZZLE_128B, CU_TENSOR_MAP_L2_PROMOTION_L2_128B, CU_TENSOR_MAP_FLOAT_OOB_FILL_NONE);
  }
  make_map(enc, &rm.wq, Wq, DM, 4096, 192);
  make_map(enc, &rm.wk, Wk, DM, 4096, 192);
  make_map(enc, &rm.wv, Wv, DM, 4096, 192);
  make_map(enc, &rm.wo, Wo, 4096, DM, 128);
  AMaps am;
  am.red = rm.red; am.poll = rm.poll;
  {
    cuuint64_t dims[3] = {DM, S_LEN / 2, 2}, strides[2] = {DM * 4, DM * 2};
    cuuint32_t box[3] = {32, 64, 2}, es[3] = {1, 1, 1};
    enc(&am.x, CU_TENSOR_MAP_DATA_TYPE_BFLOAT16, 3, (void*)x, dims, strides, box, es, CU_TENSOR_MAP_INTERLEAVE_NONE,
        CU_TENSOR_MAP_SWIZZLE_64B, CU_TENSOR_MAP_L2_PROMOTION_L2_128B, CU_TENSOR_MAP_FLOAT_OOB_FILL_NONE);
    cuuint64_t wdims[3] = {DM, DM, 3}, wstrides[2] = {DM * 6, DM * 2};
    cuuint32_t wbox[3] = {64, 32, 3}, wbox8[3] = {8, 32, 3};
    enc(&am.wa, CU_TENSOR_MAP_DATA_TYPE_BFLOAT16, 3, (void*)wqkvA, wdims, wstrides, wbox, es, CU_TENSOR_MAP_INTERLEAVE_NONE,
        CU_TENSOR_MAP_SWIZZLE_128B, CU_TENSOR_MAP_L2_PROMOTION_L2_128B, CU_TENSOR_MAP_FLOAT_OOB_FILL_NONE);
    enc(&am.wa8, CU_TENSOR_MAP_DATA_TYPE_BFLOAT16, 3, (void*)wqkvA, wdims, wstrides, wbox8, es, CU_TENSOR_MAP_INTERLEAVE_NONE,
        CU_TENSOR_MAP_SWIZZLE_NONE, CU_TENSOR_MAP_L2_PROMOTION_NONE, CU_TENSOR_MAP_FLOAT_OOB_FILL_NONE);
  }
  {
    cuuint64_t dims[3] = {64, S_LEN, KCAT / 64}, strides[2] = {KCAT * 2, 128};
    cuuint32_t box[3] = {64, 32, 9}, es[3] = {1, 1, 1};
    make_map(enc, &am.o, pO, S_LEN, KCAT, 32);
    enc(&am.o3, CU_TENSOR_MAP_DATA_TYPE_BFLOAT16, 3, pO, dims, strides, box, es, CU_TENSOR_MAP_INTERLEAVE_NONE,
        CU_TENSOR_MAP_SWIZZLE_128B, CU_TENSOR_MAP_L2_PROMOTION_L2_128B, CU_TENSOR_MAP_FLOAT_OOB_FILL_NONE);
  }
  make_map(enc, &am.wob, Wo, 4096, DM, 64);
  make_map(enc, &am.woa, woA, DM, DM, 64);

  rec_kernel<<<96, 384, SM_TOTAL, cudaStreamPerThread>>>(rm, x, mem0);
  cudaLaunchConfig_t cfg = {};
  cfg.gridDim = dim3(NAUX); cfg.blockDim = dim3(512); cfg.dynamicSmemBytes = A_TOTAL; cfg.stream = cudaStreamPerThread;
  cudaLaunchAttribute at[1];
  at[0].id = cudaLaunchAttributeProgrammaticStreamSerialization; at[0].val.programmaticStreamSerializationAllowed = 1;
  cfg.attrs = at; cfg.numAttrs = 1;
  if (XP & 16) cfg.numAttrs = 0;
  if (!(XP & 64)) cudaLaunchKernelEx(&cfg, aux_kernel, am, x, gate_w, (bf16*)d_out);
}
```

```cpp
#include <cuda_runtime.h>
#include <cuda_bf16.h>
#include <cuda_fp16.h>
#include <cuda.h>
#include <stdint.h>

typedef __nv_bfloat16 bf16;

constexpr int S_LEN = 2048, DM = 576, NH = 32, DH = 128, NSEG = 64, KCAT = 4096 + 576;
#define RED_LINE(i) (((i) >> 2) * 4096 + ((i) & 1) * 256 + ((i) & 2) * 512)
#define RED_SLOT(s) (((s) & 1) * 128 + ((s) & 2) * 256)

#define POLL_NS 832
#define NII 18
#define W3PRE 4
#define W3MID 4
#define GF 0
#define B5POS 0
#define NUP 4
#define UPF 1
#define B3Q 9
#define B3F 0
#define GATE 8
#define NTL 2
#define B7R 1
#define EXPOS 0
#define VW2 1
#define CLR 1
#define RFW 0
#define NIC 0
#define LEAD 0
#define FIN16 1
#define VXG 0
#define RING 63
#define EXB 0
#define EXD 0
#define EXB2 8192
#define HDLY 0
#define F10 1
#define NPROBE 2
#define WPOS 1
#define CW 0
#define WOPF 0
#define YP 0
#define EF 7
#define KME 0
#define MO 0
#define PS1 64
#define EXV 2
#define NOB 0
#define QM 60
#define N5 224
#define KP(i) (((i) >> 1) + 4 * ((i) & 1))
#define SPIN_LIMIT (1 << 14)
#define XP 0

__device__ __align__(1024) bf16 g_Ocat[S_LEN * KCAT];
__device__ __align__(1024) unsigned char g_red_raw[2 * 262144];
constexpr int HINT_OFF = 2048;
__device__ __align__(16) float g_gate[S_LEN];
__device__ __align__(128) uint4 g_stats[96 * 2];
__device__ unsigned g_epoch;
__device__ unsigned g_epoch2;
__device__ unsigned g_oflag[NH * 32];
__device__ unsigned g_abar[3 * 32];
__device__ unsigned g_sflag[96 * 8];
__device__ __align__(1024) unsigned char g_seg[NSEG * 96 * 8192];
__device__ __align__(1024) unsigned char g_km[NSEG * NH * 4096];
__device__ __align__(1024) uint2 g_part[8 * 9 * 4 * 8 * 128];
__device__ int g_err;
#define SSTAMP(seg, idx)
#define TSTAMP(idx)
#define QSTAMP(idx)
#define PROF(idx)
#define PROFP(idx)
#define STAMP(idx)
#define ASTAMP(idx)
#define WSTAMP(idx)

#define CSTAMP(idx)
#define CDECL
#define CDUMP
#define DI __device__ __forceinline__
DI uint32_t smem_u32(const void* p) { return (uint32_t)__cvta_generic_to_shared(p); }
DI uint32_t clock32() { uint32_t c; asm volatile("mov.u32 %0, %%clock;" : "=r"(c) :: "memory"); return c; }
DI uint32_t gtime() { uint32_t c; asm volatile("mov.u32 %0, %%globaltimer_lo;" : "=r"(c) :: "memory"); return c; }
DI uint32_t ldg_relaxed32(const void* p) { uint32_t v; asm volatile("ld.relaxed.gpu.global.b32 %0, [%1];" : "=r"(v) : "l"(p) : "memory"); return v; }
DI uint32_t ldg_acquire32(const void* p) { uint32_t v; asm volatile("ld.acquire.gpu.global.b32 %0, [%1];" : "=r"(v) : "l"(p) : "memory"); return v; }
DI void stg_relaxed32(void* p, uint32_t v) { asm volatile("st.relaxed.gpu.global.b32 [%0], %1;" :: "l"(p), "r"(v) : "memory"); }
DI int head_id() { int c; asm volatile("mov.u32 %0, %%clusterid.x;" : "=r"(c)); return c; }
DI uint32_t mapa(uint32_t a, uint32_t r) { uint32_t o; asm("mapa.shared::cluster.u32 %0, %1, %2;" : "=r"(o) : "r"(a), "r"(r)); return o; }
DI void cluster_arrive() { asm volatile("barrier.cluster.arrive.relaxed.aligned;" ::: "memory"); }
DI void cluster_wait() { asm volatile("barrier.cluster.wait.aligned;" ::: "memory"); }
DI void cluster_sync() { asm volatile("barrier.cluster.arrive.release.aligned;\nbarrier.cluster.wait.acquire.aligned;" ::: "memory"); }
DI void mbar_init(uint32_t b, uint32_t c) { asm volatile("mbarrier.init.shared::cta.b64 [%0], %1;" :: "r"(b), "r"(c) : "memory"); }
DI void mbar_expect(uint32_t b, uint32_t tx) { asm volatile("mbarrier.arrive.expect_tx.shared::cta.b64 _, [%0], %1;" :: "r"(b), "r"(tx) : "memory"); }
DI void mbar_arrive(uint32_t b) { asm volatile("mbarrier.arrive.shared::cta.b64 _, [%0];" :: "r"(b) : "memory"); }
DI void mbar_wait(uint32_t b, uint32_t par) {
  asm volatile("{\n.reg .pred p;\n.reg .u32 n, q;\nmov.u32 n, 0;\n"
               "WL: add.u32 n, n, 1;\nshr.u32 q, n, 12;\nxor.b32 q, q, %1;\n"
               "mbarrier.try_wait.parity.shared::cta.b64 p, [%0], q;\n@!p bra.uni WL;\n}"
               :: "r"(b), "r"(par) : "memory");
}
DI void wait_until(uint32_t t) {
  const uint32_t now = gtime();
  t = min(t, now + 8192);
  asm volatile("{\n.reg .pred p;\n.reg .u32 c;\nTL: mov.u32 c, %%globaltimer_lo;\nsetp.lt.u32 p, c, %0;\n@p bra.uni TL;\n}" :: "r"(t) : "memory");
}
#define PIN(v) v = __shfl_xor_sync(0xffffffffu, v, 0)
#define SCHED_FENCE(k) asm volatile("{\n.reg .pred p;\nsetp.eq.u32 p, %0, %1;\n@p exit;\n}" :: "r"(fence_reg), "r"(k) : "memory")
#define MEM_ORDER(k) asm volatile("{\n.reg .pred p;\nsetp.eq.u32 p, %0, %1;\n@p st.shared.u32 [%0], %0;\n}" :: "r"(fence_reg), "r"(k + 64) : "memory")
DI void bar_sync(int id, int n) { asm volatile("bar.sync %0, %1;" :: "r"(id), "r"(n) : "memory"); }
DI void bar_arrive(int id, int n) { asm volatile("bar.arrive %0, %1;" :: "r"(id), "r"(n) : "memory"); }
DI void fence_async() { asm volatile("fence.proxy.async.shared::cta;" ::: "memory"); }
DI void st_async4(uint32_t a, uint32_t x, uint32_t y, uint32_t z, uint32_t w, uint32_t mb) {
  asm volatile("st.async.weak.shared::cluster.mbarrier::complete_tx::bytes.v4.b32 [%0], {%1,%2,%3,%4}, [%5];"
               :: "r"(a), "r"(x), "r"(y), "r"(z), "r"(w), "r"(mb) : "memory");
}
DI void st_async2(uint32_t a, uint32_t x, uint32_t y, uint32_t mb) {
  asm volatile("st.async.weak.shared::cluster.mbarrier::complete_tx::bytes.v2.b32 [%0], {%1,%2}, [%3];"
               :: "r"(a), "r"(x), "r"(y), "r"(mb) : "memory");
}
DI void sts32(uint32_t a, uint32_t x) { asm volatile("st.shared.b32 [%0], %1;" :: "r"(a), "r"(x) : "memory"); }
DI void sts64(uint32_t a, uint32_t x, uint32_t y) { asm volatile("st.shared.v2.b32 [%0], {%1,%2};" :: "r"(a), "r"(x), "r"(y) : "memory"); }
DI void sts128(uint32_t a, uint32_t x, uint32_t y, uint32_t z, uint32_t w) {
  asm volatile("st.shared.v4.b32 [%0], {%1,%2,%3,%4};" :: "r"(a), "r"(x), "r"(y), "r"(z), "r"(w) : "memory");
}
DI uint32_t lds32(uint32_t a) { uint32_t x; asm volatile("ld.shared.b32 %0, [%1];" : "=r"(x) : "r"(a) : "memory"); return x; }
DI uint32_t lds32v(uint32_t a) { uint32_t x; asm volatile("ld.volatile.shared.b32 %0, [%1];" : "=r"(x) : "r"(a) : "memory"); return x; }
DI void lds64(uint32_t a, uint32_t& x, uint32_t& y) { asm volatile("ld.shared.v2.b32 {%0,%1}, [%2];" : "=r"(x), "=r"(y) : "r"(a) : "memory"); }
DI void lds128(uint32_t a, uint32_t* r) {
  asm volatile("ld.shared.v4.b32 {%0,%1,%2,%3}, [%4];" : "=r"(r[0]), "=r"(r[1]), "=r"(r[2]), "=r"(r[3]) : "r"(a) : "memory");
}
DI void lds128f(uint32_t a, float* r) {
  asm volatile("ld.shared.v4.f32 {%0,%1,%2,%3}, [%4];" : "=f"(r[0]), "=f"(r[1]), "=f"(r[2]), "=f"(r[3]) : "r"(a) : "memory");
}
DI void lds64f(uint32_t a, float* r) { asm volatile("ld.shared.v2.f32 {%0,%1}, [%2];" : "=f"(r[0]), "=f"(r[1]) : "r"(a) : "memory"); }
DI void ldsm4t(uint32_t* r, uint32_t a) {
  asm volatile("ldmatrix.sync.aligned.m8n8.x4.trans.shared.b16 {%0,%1,%2,%3}, [%4];"
               : "=r"(r[0]), "=r"(r[1]), "=r"(r[2]), "=r"(r[3]) : "r"(a) : "memory");
}
DI void ldsm4t_in(uint32_t* r, uint32_t a, uint32_t t) {
  asm volatile("{\n.reg .pred p;\nsetp.ne.u32 p, %5, 0;\n@p ldmatrix.sync.aligned.m8n8.x4.trans.shared.b16 {%0,%1,%2,%3}, [%4];\n}"
               : "+r"(r[0]), "+r"(r[1]), "+r"(r[2]), "+r"(r[3]) : "r"(a), "r"(t) : "memory");
}
DI void lds128_in(uint32_t* r, uint32_t a, uint32_t t) {
  asm volatile("{\n.reg .pred p;\nsetp.ne.u32 p, %5, 0;\n@p ld.shared.v4.b32 {%0,%1,%2,%3}, [%4];\n}"
               : "+r"(r[0]), "+r"(r[1]), "+r"(r[2]), "+r"(r[3]) : "r"(a), "r"(t) : "memory");
}
DI void ldsm2t_in(uint32_t* r, uint32_t a, uint32_t t) {
  asm volatile("{\n.reg .pred p;\nsetp.ne.u32 p, %3, 0;\n@p ldmatrix.sync.aligned.m8n8.x2.trans.shared.b16 {%0,%1}, [%2];\n}" : "+r"(r[0]), "+r"(r[1]) : "r"(a), "r"(t) : "memory");
}
DI void reserve2(uint32_t* r) { asm volatile("{\n.reg .u64 t;\nmov.u64 t, %%clock64;\nmov.b64 {%0, %1}, t;\n}" : "=r"(r[0]), "=r"(r[1])); }
DI void scale_sum(float& x, float& y, float s, uint32_t t) {
  asm volatile("{\n.reg .pred p;\nsetp.ne.u32 p, %2, 0;\n@p mul.f32 %0, %0, %1;\n}" : "+f"(y) : "f"(s), "r"(t));
  asm volatile("{\n.reg .pred p;\nsetp.ne.u32 p, %3, 1;\n@p fma.rn.f32 %0, %0, %1, %2;\n}" : "+f"(x) : "f"(s), "f"(y), "r"(t));
}
DI void ldsm4(uint32_t* r, uint32_t a) {
  asm volatile("ldmatrix.sync.aligned.m8n8.x4.shared.b16 {%0,%1,%2,%3}, [%4];"
               : "=r"(r[0]), "=r"(r[1]), "=r"(r[2]), "=r"(r[3]) : "r"(a) : "memory");
}
DI void st_async1(uint32_t a, uint32_t x, uint32_t mb) {
  asm volatile("st.async.weak.shared::cluster.mbarrier::complete_tx::bytes.b32 [%0], %1, [%2];" :: "r"(a), "r"(x), "r"(mb) : "memory");
}
DI void stsm4(uint32_t a, uint32_t x, uint32_t y, uint32_t z, uint32_t w) {
  asm volatile("stmatrix.sync.aligned.m8n8.x4.shared.b16 [%0], {%1,%2,%3,%4};" :: "r"(a), "r"(x), "r"(y), "r"(z), "r"(w) : "memory");
}
DI void stsm4t(uint32_t a, uint32_t x, uint32_t y, uint32_t z, uint32_t w) {
  asm volatile("stmatrix.sync.aligned.m8n8.x4.trans.shared.b16 [%0], {%1,%2,%3,%4};" :: "r"(a), "r"(x), "r"(y), "r"(z), "r"(w) : "memory");
}
DI uint32_t pack_bf16(float lo, float hi) { uint32_t r; asm("cvt.rn.bf16x2.f32 %0, %1, %2;" : "=r"(r) : "f"(hi), "f"(lo)); return r; }
DI uint32_t pack_f16(float lo, float hi) { uint32_t r; asm("cvt.rn.f16x2.f32 %0, %1, %2;" : "=r"(r) : "f"(hi), "f"(lo)); return r; }
DI float ex2(float x) { float y; asm("ex2.approx.ftz.f32 %0, %1;" : "=f"(y) : "f"(x)); return y; }
DI float rcp(float x) { float y; asm("rcp.approx.ftz.f32 %0, %1;" : "=f"(y) : "f"(x)); return y; }
DI float bf_lo(uint32_t x) { return __uint_as_float(x << 16); }
DI float bf_hi(uint32_t x) { return __uint_as_float(x & 0xffff0000u); }
DI void mma16816(float* d, const uint32_t* a, uint32_t b0, uint32_t b1) {
  asm volatile("mma.sync.aligned.m16n8k16.row.col.f32.bf16.bf16.f32 {%0,%1,%2,%3}, {%4,%5,%6,%7}, {%8,%9}, {%0,%1,%2,%3};"
               : "+f"(d[0]), "+f"(d[1]), "+f"(d[2]), "+f"(d[3]) : "r"(a[0]), "r"(a[1]), "r"(a[2]), "r"(a[3]), "r"(b0), "r"(b1));
}
DI void mma16816z(float* d, const uint32_t* a, uint32_t b0, uint32_t b1) {
  asm volatile("mma.sync.aligned.m16n8k16.row.col.f32.bf16.bf16.f32 {%0,%1,%2,%3}, {%4,%5,%6,%7}, {%8,%9}, {%10,%10,%10,%10};"
               : "=f"(d[0]), "=f"(d[1]), "=f"(d[2]), "=f"(d[3]) : "r"(a[0]), "r"(a[1]), "r"(a[2]), "r"(a[3]), "r"(b0), "r"(b1), "f"(0.f));
}
DI void mma1688z(float* d, uint32_t a0, uint32_t a1, uint32_t b0) {
  asm volatile("mma.sync.aligned.m16n8k8.row.col.f32.bf16.bf16.f32 {%0,%1,%2,%3}, {%4,%5}, {%6}, {%7,%7,%7,%7};"
               : "=f"(d[0]), "=f"(d[1]), "=f"(d[2]), "=f"(d[3]) : "r"(a0), "r"(a1), "r"(b0), "f"(0.f));
}
DI void mma1688(float* d, uint32_t a0, uint32_t a1, uint32_t b0) {
  asm volatile("mma.sync.aligned.m16n8k8.row.col.f32.bf16.bf16.f32 {%0,%1,%2,%3}, {%4,%5}, {%6}, {%0,%1,%2,%3};"
               : "+f"(d[0]), "+f"(d[1]), "+f"(d[2]), "+f"(d[3]) : "r"(a0), "r"(a1), "r"(b0));
}
DI void ldsm2t(uint32_t* r, uint32_t a) {
  asm volatile("ldmatrix.sync.aligned.m8n8.x2.trans.shared.b16 {%0,%1}, [%2];" : "=r"(r[0]), "=r"(r[1]) : "r"(a) : "memory");
}
DI uint32_t add_bf16(uint32_t a, uint32_t b) { uint32_t r; asm("add.rn.bf16x2 %0, %1, %2;" : "=r"(r) : "r"(a), "r"(b)); return r; }
DI uint32_t mul_bf16(uint32_t a, uint32_t b) { uint32_t r; asm("mul.rn.bf16x2 %0, %1, %2;" : "=r"(r) : "r"(a), "r"(b)); return r; }
DI uint64_t make_desc(uint32_t addr, uint32_t lbo, uint32_t sbo, uint32_t swz) {
  return (uint64_t)((addr & 0x3FFFF) >> 4) | ((uint64_t)(lbo >> 4) << 16) | ((uint64_t)(sbo >> 4) << 32) | ((uint64_t)swz << 62);
}
#define WG_FENCE() asm volatile("wgmma.fence.sync.aligned;" ::: "memory")
#define WG_COMMIT() asm volatile("wgmma.commit_group.sync.aligned;" ::: "memory")
#define WG_WAIT(n) asm volatile("wgmma.wait_group.sync.aligned %0;" :: "n"(n) : "memory")
#define ACC8(d, o) "+f"(d[o]), "+f"(d[o + 1]), "+f"(d[o + 2]), "+f"(d[o + 3]), "+f"(d[o + 4]), "+f"(d[o + 5]), "+f"(d[o + 6]), "+f"(d[o + 7])
DI void wgmma_n32_rs(float* d, uint32_t a0, uint32_t a1, uint32_t a2, uint32_t a3, uint64_t db, int acc) {
  asm volatile("{\n.reg .pred p;\nsetp.ne.b32 p, %21, 0;\n"
               "wgmma.mma_async.sync.aligned.m64n32k16.f32.bf16.bf16 {%0,%1,%2,%3,%4,%5,%6,%7,%8,%9,%10,%11,%12,%13,%14,%15}, "
               "{%16,%17,%18,%19}, %20, p, 1, 1, 0;\n}\n"
               : ACC8(d, 0), ACC8(d, 8) : "r"(a0), "r"(a1), "r"(a2), "r"(a3), "l"(db), "r"(acc));
}
template <int TA>
DI void wgmma_n32_ss(float* d, uint64_t da, uint64_t db, int acc) {
  asm volatile("{\n.reg .pred p;\nsetp.ne.b32 p, %18, 0;\n"
               "wgmma.mma_async.sync.aligned.m64n32k16.f32.bf16.bf16 {%0,%1,%2,%3,%4,%5,%6,%7,%8,%9,%10,%11,%12,%13,%14,%15}, "
               "%16, %17, p, 1, 1, %19, 1;\n}\n"
               : ACC8(d, 0), ACC8(d, 8) : "l"(da), "l"(db), "r"(acc), "n"(TA));
}
DI void tma_load(uint32_t dst, const CUtensorMap* m, int c0, int c1, uint32_t mb) {
  asm volatile("cp.async.bulk.tensor.2d.shared::cluster.global.mbarrier::complete_tx::bytes [%0], [%1, {%3, %4}], [%2];"
               :: "r"(dst), "l"(m), "r"(mb), "r"(c0), "r"(c1) : "memory");
}
DI void tma_load3(uint32_t dst, const CUtensorMap* m, int row, uint32_t mb) {
  asm volatile("cp.async.bulk.tensor.3d.shared::cluster.global.mbarrier::complete_tx::bytes [%0], [%1, {%3, %4, %3}], [%2];"
               :: "r"(dst), "l"(m), "r"(mb), "r"(0), "r"(row) : "memory");
}
DI bool elect_one() {
  uint32_t p;
  asm volatile("{\n.reg .pred p;\nelect.sync _|p, 0xffffffff;\nselp.u32 %0, 1, 0, p;\n}" : "=r"(p));
  return p;
}
DI void bulk_s2s(uint32_t dst, uint32_t src, uint32_t bytes, uint32_t mb) {
  asm volatile("cp.async.bulk.shared::cluster.shared::cta.mbarrier::complete_tx::bytes [%0], [%1], %2, [%3];"
               :: "r"(dst), "r"(src), "r"(bytes), "r"(mb) : "memory");
}
DI void bulk_load(uint32_t dst, const void* src, uint32_t bytes, uint32_t mb) {
  asm volatile("cp.async.bulk.shared::cluster.global.mbarrier::complete_tx::bytes [%0], [%1], %2, [%3];" :: "r"(dst), "l"(src), "r"(bytes), "r"(mb) : "memory");
}
#define EVICT_FIRST ".reg .b64 pol;\ncreatepolicy.fractional.L2::evict_first.b64 pol, 1.0;\n"
DI void bulk_load_ef(uint32_t dst, const void* src, uint32_t bytes, uint32_t mb) {
  asm volatile("{\n" EVICT_FIRST "cp.async.bulk.shared::cluster.global.mbarrier::complete_tx::bytes.L2::cache_hint [%0], [%1], %2, [%3], pol;\n}"
               :: "r"(dst), "l"(src), "r"(bytes), "r"(mb) : "memory");
}
DI void tma_load_ef(uint32_t dst, const CUtensorMap* m, int c0, int c1, uint32_t mb) {
  asm volatile("{\n" EVICT_FIRST "cp.async.bulk.tensor.2d.shared::cluster.global.mbarrier::complete_tx::bytes.L2::cache_hint [%0], [%1, {%3, %4}], [%2], pol;\n}"
               :: "r"(dst), "l"(m), "r"(mb), "r"(c0), "r"(c1) : "memory");
}
DI void tma_prefetch(const CUtensorMap* m, int c0, int c1) {
  asm volatile("cp.async.bulk.prefetch.tensor.2d.L2.global.tile [%0, {%1, %2}];" :: "l"(m), "r"(c0), "r"(c1) : "memory");
}
DI void tma_store(const CUtensorMap* m, uint32_t src, int c0, int c1) {
  asm volatile("cp.async.bulk.tensor.2d.global.shared::cta.bulk_group [%0, {%2, %3}], [%1];" :: "l"(m), "r"(src), "r"(c0), "r"(c1) : "memory");
}
DI uint4 ldg_relaxed(const void* p) {
  uint4 v;
  asm volatile("ld.relaxed.gpu.global.v4.b32 {%0,%1,%2,%3}, [%4];" : "=r"(v.x), "=r"(v.y), "=r"(v.z), "=r"(v.w) : "l"(p) : "memory");
  return v;
}
DI void stg_relaxed(void* p, uint32_t x, uint32_t y, uint32_t z, uint32_t w) {
  asm volatile("st.relaxed.gpu.global.v4.b32 [%0], {%1,%2,%3,%4};" :: "l"(p), "r"(x), "r"(y), "r"(z), "r"(w) : "memory");
}
DI void red_f16x8(void* p, uint32_t x, uint32_t y, uint32_t z, uint32_t w) {
  asm volatile("red.relaxed.gpu.global.add.noftz.v4.f16x2 [%0], {%1,%2,%3,%4};" :: "l"(p), "r"(x), "r"(y), "r"(z), "r"(w) : "memory");
}
DI void sq_acc(uint32_t& a, uint32_t x) { asm("fma.rn.bf16x2 %0, %1, %1, %0;" : "+r"(a) : "r"(x)); }
DI __half2 amax4(__half2 h, const uint32_t* v) {
  h = __hmax2_nan(__hmax2_nan(h, __habs2(*(const __half2*)&v[0])), __habs2(*(const __half2*)&v[1]));
  return __hmax2_nan(__hmax2_nan(h, __habs2(*(const __half2*)&v[2])), __habs2(*(const __half2*)&v[3]));
}
DI uint32_t wexp(__half2 h) { const uint32_t u = *(const uint32_t*)&h; return __reduce_max_sync(0xffffffffu, max((u >> 16) & 0x7fffu, u & 0x7fffu)) >> 7; }
DI float max10(const float* a) {
  return fmaxf(fmaxf(fmaxf(fmaxf(a[0], a[1]), fmaxf(a[2], a[3])), fmaxf(fmaxf(a[4], a[5]), fmaxf(a[6], a[7]))), fmaxf(a[8], a[9]));
}
DI float quad_max(float m) {
  return fmaxf(fmaxf(m, __shfl_xor_sync(0xffffffffu, m, 1)), fmaxf(__shfl_xor_sync(0xffffffffu, m, 2), __shfl_xor_sync(0xffffffffu, m, 3)));
}
DI float warp_sum(float v) {
#pragma unroll
  for (int o = 16; o; o >>= 1) v += __shfl_xor_sync(0xffffffffu, v, o);
  return v;
}

constexpr int SM_WO3 = 0;
constexpr int SM_X = 16384;
constexpr int XT = 36864;
constexpr int SM_EXP = 126976;
constexpr int SEGB = 10240;
constexpr int SM_BLK = SM_EXP + 8192;
constexpr int SM_VC = SM_BLK + 4 * SEGB;
constexpr int SM_PART = SM_VC + 16384;
constexpr int SM_QM = SM_PART + 4096;
constexpr int SM_E = SM_QM + 1024;
constexpr int SM_VM = SM_E + 1536;
constexpr int SM_OB = SM_VM + 2048;
constexpr int SM_FB = SM_OB + 2048;
constexpr int SM_STAGE = SM_X + XT;
constexpr int SM_M0 = SM_STAGE + 3 * 49152;
constexpr int SM_MISC = 210944;
constexpr int SM_WOST = 212992;
constexpr int SM_MEM = SM_WOST;
constexpr int SM_MAX = SM_MEM + 11264;
#define MEM_BLK(q) ((q) / 3 * 4096 + (q) % 3 * 1024)
constexpr int SM_TOTAL = 229376;
constexpr int MB_W = SM_MISC;
constexpr int MB_WO = SM_MISC + 24;
constexpr int MB_WO3 = SM_MISC + 32;
constexpr int MB_X = SM_MISC + 40;
constexpr int MB_S = SM_MISC + 64;
constexpr int MB_F = SM_MISC + 72;
constexpr int MB_VX = SM_MISC + 80;
constexpr int SC_FPAR = SM_MISC + 136;
constexpr int SC_DEAD = SM_MISC + 96;
constexpr int SC_UNSC = SM_MISC + 112;
constexpr int SC_EXPW = SM_MISC + 132;
constexpr int SC_ONES = SM_MISC + 144;
constexpr int SC_SS = SM_MISC + 160;
constexpr int SC_LAT = SM_MISC + 224;
constexpr int SC_EPO = SM_MISC + 240;
constexpr int MB_XS = SM_MISC + 248;
constexpr int SC_XMAX = SM_MISC + 256;
constexpr int SC_PROF = 229376;

constexpr float SM_SCALE = 0.08838834764831845f;
constexpr float LOG2E = 1.4426950408889634f;
constexpr float E_LIM = 20.f;

template <bool B> struct BoolC { static constexpr bool value = B; };
template <int I> struct IntC { static constexpr int value = I; };
struct RMaps { CUtensorMap x, wq, wk, wv, wo; unsigned char* red; uint32_t poll; const unsigned char* w[4]; };

DI uint32_t latest_hint(uint32_t h, uint32_t d, int s) {
  const uint32_t x = (((h | 0xc0c0c0c0u) - ((d >> 5) & 63) * 0x01010101u) & 0x3f3f3f3fu) | ((h ^ (((s >> 2) + 1) & 3) * 0x40404040u) & 0xc0c0c0c0u);
  const uint32_t y = __vmaxu2(x & 0x00ff00ffu, (x >> 8) & 0x00ff00ffu);
  return __reduce_max_sync(0xffffffffu, max(y & 0xffffu, y >> 16));
}
DI uint32_t near_half(uint32_t sb) {
  uint32_t a, b; lds64(sb + SC_LAT, a, b);
  return a > b;
}

template <int RT, int K0, int K1, bool D32 = false>
DI void xproj(float* acc, const uint32_t (&wa)[2][18][4], uint64_t xd) {
  if (XP & 1) return;
  WG_FENCE();
#pragma unroll
  for (int k = K0; k < ((XP & 128) ? K0 + 1 : K1); k++)
  {
    uint64_t d = xd + (uint64_t)(((k >> 1) * 4096 + (k & 1) * 32) >> 4);
    if (D32) asm("mov.b64 %0, {%1, %2};" : "=l"(d) : "r"((uint32_t)xd + (((k >> 1) * 4096 + (k & 1) * 32) >> 4)), "r"((uint32_t)(xd >> 32)));
    wgmma_n32_rs(acc, wa[RT][k][0], wa[RT][k][1], wa[RT][k][2], wa[RT][k][3], d, k != 0);
  }
  WG_COMMIT();
}

DI void load_w(uint32_t sb, const RMaps& tm, uint32_t rank, int c) {
  const int h = blockIdx.x / 3;
  mbar_expect(sb + MB_W + 8 * c, 49152);
  ((EF & 4) ? tma_load_ef : tma_load)(sb + SM_STAGE + c * 49152, rank < 2 ? &tm.wk : &tm.wv, h * DH + (rank == 1 ? 64 : 0), c * 192, sb + MB_W + 8 * c);
  ((EF & 4) ? tma_load_ef : tma_load)(sb + SM_STAGE + c * 49152 + 24576, rank < 2 ? &tm.wq : &tm.wv, h * DH + (rank == 0 ? 0 : 64), c * 192, sb + MB_W + 8 * c);
}
DI void seg_store(int seg, uint32_t sb) {
  fence_async();
  if (EF & 1)
    asm volatile("{\n" EVICT_FIRST "cp.async.bulk.global.shared::cta.bulk_group.L2::cache_hint [%0], [%1], 8192, pol;\n}"
                 :: "l"(g_seg + ((size_t)(seg & RING) * 96 + blockIdx.x) * 8192), "r"(sb + SM_BLK + (seg & 3) * SEGB) : "memory");
  else
  asm volatile("cp.async.bulk.global.shared::cta.bulk_group [%0], [%1], 8192;"
               :: "l"(g_seg + ((size_t)(seg & RING) * 96 + blockIdx.x) * 8192), "r"(sb + SM_BLK + (seg & 3) * SEGB) : "memory");
  asm volatile("cp.async.bulk.commit_group;" ::: "memory");
}
DI void seg_publish(int seg, uint32_t sb) {
  const uint32_t v = lds32(sb + SC_EPO) + seg;
  asm volatile("cp.async.bulk.wait_group 0;" ::: "memory");
  stg_relaxed32(&g_sflag[blockIdx.x * 8], v);
}

DI void proj_role(const uint32_t sb, const RMaps& tm, const uint32_t rank, const int wg, const int w, const int lane) {
  const bool qk = rank < 2;
  uint32_t wa[2][18][4];
  float acc[16];
  const uint64_t xd0 = make_desc(sb + SM_X + wg * 64, 16, 1024, 1);
  {
    const int rr = (lane & 7) + ((lane >> 4) << 3);
    const uint32_t col = ((2 * w + ((lane >> 3) & 1)) ^ (lane & 7)) << 4;
    float ss = 0.f;
    bar_sync(3, 256);
    mbar_wait(sb + MB_X, 0);
    auto chunk = [&](auto cc) {
      constexpr int c = decltype(cc)::value;
      QSTAMP(2 + 2 * c);
      mbar_wait(sb + MB_W + 8 * c, 0);
      QSTAMP(3 + 2 * c);
#pragma unroll
      for (int rt = 1; rt >= 0; rt--)
#pragma unroll
        for (int k = 0; k < 6; k++)
          ldsm4t(wa[rt][c * 6 + k], sb + SM_STAGE + c * 49152 + (rt ^ wg) * 24576 + (64 * (k >> 1) + 32 * wg + 16 * (k & 1) + rr) * 128 + col);
      fence_async();
      if (c < 2) {
        bar_sync(3, 256);
        QSTAMP(17 + c);
        if (threadIdx.x == 0) {
          if (c == 0) tma_load(sb + SM_X + XT, &tm.wo, rank * 192, (blockIdx.x / 3) * DH, sb + MB_WO);
          else tma_load3(sb + SM_X + 2 * XT, &tm.x, 64, sb + MB_X + 16);
        }
        __syncwarp();
      } else {
        cluster_arrive();
      }
      xproj<1, 6 * c, 6 * c + 6>(acc, wa, xd0);
      if (!qk) {
        uint32_t q[4] = {0, 0, 0, 0};
#pragma unroll
        for (int rt = 0; rt < 2; rt++)
#pragma unroll
          for (int k = 0; k < 6; k++)
#pragma unroll
            for (int i = 0; i < 4; i++) sq_acc(q[i], wa[rt][c * 6 + k][i]);
#pragma unroll
        for (int i = 0; i < 4; i++) ss += bf_lo(q[i]) + bf_hi(q[i]);
      }
      if (c < 2 && CW) WG_WAIT(0);
    };
    chunk(IntC<0>()); chunk(IntC<1>()); chunk(IntC<2>());
    ss = warp_sum(ss);
    if (lane == 0) sts32(sb + SC_SS + 4 * (wg * 4 + w), __float_as_uint(ss));
    bar_arrive(11, 384);
  }
  STAMP(1);
  QSTAMP(8);
  STAMP(2);

  uint32_t t16 = sb + (w * 32 + lane) * 16;
  uint32_t mem_a = sb + SM_MEM + wg * 512 + lane * 16;
  uint32_t fin_a = sb + (lane & 7) * 16 + SM_BLK + (qk ? (wg ^ 1) * 4096 + w * 256 + (lane & 8) * 16 + (lane & 16) * 64
                                              : wg * 4096 + w * 1024 + (lane & 8) * 64 + (lane & 16) * 8);
  PIN(t16); PIN(mem_a); PIN(fin_a);
  const uint32_t fence_reg = mem_a;
  const uint32_t fin2 = qk ? 2048 : 256;
  auto do_export = [&](auto retire, uint32_t always) {
    WG_WAIT(0);
    uint32_t p[2];
#pragma unroll
    for (int i = 0; i < 2; i++) {
      p[i] = pack_bf16(acc[8 * i], acc[8 * i + 1]);
      sts128(t16 + SM_EXP + wg * 4096 + i * 2048, p[i], pack_bf16(acc[8 * i + 2], acc[8 * i + 3]),
             pack_bf16(acc[8 * i + 4], acc[8 * i + 5]), pack_bf16(acc[8 * i + 6], acc[8 * i + 7]));
    }
    if (decltype(retire)::value)
      asm volatile("{\n.reg .pred p, q;\nsetp.ne.u32 p, %2, 0;\nsetp.ne.u32 q, %2, 1;\n@p ld.shared.b32 %0, [%3];\n@q ld.shared.b32 %1, [%3 + 4];\n"
                   "setp.ne.u32 p, %0, %1;\n@p exit;\n}" : "+r"(p[0]), "+r"(p[1]) : "r"(always), "r"(sb + SC_DEAD) : "memory");
  };
  uint32_t o[8];
  auto import = [&]() { lds128(t16 + SM_EXP + (wg ^ 1) * 4096, o); lds128(t16 + SM_EXP + (wg ^ 1) * 4096 + 2048, o + 4); };
  auto finish_from = [&](int seg, const float* d) {
    const uint32_t a = fin_a + (seg & 3) * SEGB;
#pragma unroll
    for (int i = 0; i < 8; i++) o[i] = add_bf16(pack_bf16(d[2 * i], d[2 * i + 1]), o[i]);
    stsm4(a, o[0], o[1], o[2], o[3]);
    stsm4(a + fin2, o[4], o[5], o[6], o[7]);
  };
  auto finish = [&](int seg) { WG_WAIT(0); finish_from(seg, acc); };
  auto send_v = [&](int seg, int dst) {
    fence_async();
    if (seg < NSEG - 1 && !(XP & 2) && elect_one())
      bulk_s2s(mapa(sb + SM_VC + (seg & 1) * 8192, dst), sb + SM_BLK + (seg & 3) * SEGB, 8192, mapa(sb + MB_VX + (seg & 1) * 8, dst));
    __syncwarp();
  };
  auto wait_v = [&](int seg) {
    if (seg < NSEG - 1 && !(XP & 2)) {
      mbar_wait(sb + MB_VX + (seg & 1) * 8, (seg >> 1) & 1);
      if (elect_one()) mbar_expect(sb + MB_VX + (seg & 1) * 8, 8192);
      __syncwarp();
    }
  };
  auto export_seg = [&](int seg) { if (!(XP & (4 | 8192)) && elect_one()) seg_store(seg, sb); __syncwarp(); };
  auto publish = [&](int seg) { if (!(XP & (4 | 16384)) && elect_one()) seg_publish(seg, sb); __syncwarp(); };
  do_export(BoolC<false>(), 0);
  QSTAMP(9);
  SCHED_FENCE(11);
  xproj<0, 0, 18>(acc, wa, xd0);
  bar_sync(3, 256);
  QSTAMP(10);
  cluster_wait();
  QSTAMP(11);
  mbar_wait(sb + MB_X + 8, 0);
  QSTAMP(12);
  import();
  finish(0);
  SCHED_FENCE(12);
  uint64_t dA = xd0 + (XT >> 4);
  xproj<1, 0, 18>(acc, wa, dA);
  bar_sync(3, 256);
  if (!qk && wg == 0 && w < 2) send_v(0, w);
  if (!(EXV & 1) && wg == 0 && w == 3) export_seg(0);
  QSTAMP(13);
  if (qk && wg == 0 && w == 0) wait_v(0);
  QSTAMP(14);
  bar_arrive(13, 384);
  if (!qk) {
    do_export(BoolC<false>(), 0);
    SCHED_FENCE(15);
    xproj<0, 0, 18>(acc, wa, dA);
    if (threadIdx.x == 0 && !(XP & 8)) { mbar_expect(sb + MB_X, XT); tma_load3(sb + SM_X, &tm.x, 96, sb + MB_X); }
    bar_sync(3, 256);
    mbar_wait(sb + MB_X + 16, 0);
    import();
    finish(1);
    SCHED_FENCE(16);
    dA += XT >> 4;
    xproj<1, 0, 18>(acc, wa, dA);
    if (!(EXV & 2)) bar_sync(3, 256);
    if (!(EXV & 2) && wg == 0 && w < VW2) send_v(1, w);
  }
  QSTAMP(15);
  WG_WAIT(0);
  bar_sync(0, 384);
  if (!(EXV & 1) && wg == 0 && w == 3) publish(0);
  QSTAMP(16);
  const int ro = __shfl_sync(0xffffffffu, near_half(sb) ^ wg, 0);
  STAMP(5);
  const uint32_t always = __shfl_sync(0xffffffffu, lds32(sb + SC_DEAD + 12), 0);
  const int ah = qk ? 1 : 2;
  int b2 = qk ? 2 : 0;
  int s = 0;
  uint32_t hint_lo = (uint32_t)(uint64_t)tm.red + HINT_OFF + blockIdx.x + (lane & 1) * 4096 + (lane >> 1) * 16384;
  PIN(hint_lo);
  auto post_hint = [&]() {
    asm volatile("{\n.reg .pred p;\n.reg .b64 a;\n.reg .u32 t;\nsetp.lt.u32 p, %0, %1;\nmov.b64 a, {%2, %3};\nmov.u32 t, %%globaltimer_lo;\n"
                 "bfe.u32 t, t, 5, 6;\nor.b32 t, t, %4;\n@p st.relaxed.gpu.global.u8 [a], t;\n}"
                 :: "r"(t16), "r"(sb + 160), "r"(hint_lo + RED_SLOT(s)), "r"((uint32_t)((uint64_t)tm.red >> 32)), "r"(((s >> 2) + 1) << 6) : "memory");
  };
  auto memproj = [&](auto second, int id, uint32_t dep, float u0, float u1, float* r) {
    constexpr bool R1 = decltype(second)::value;
    uint32_t b[NUP][4], b0[4];
    if (R1) asm volatile("{\n.reg .pred p;\nsetp.eq.u32 p, %0, %1;\n@p exit;\n}" :: "r"(dep), "r"(id) : "memory");
    bar_sync(R1 ? 2 : 1, 256);
    PROF(0);
    ldsm4t(b0, mem_a);
#pragma unroll
    for (int q = 0; q < NUP; q++) {
      if (R1 && q == 2) {
        bar_sync(11, 256);
        SCHED_FENCE(id + 1);
      }
      ldsm4t(b[q], mem_a + MEM_BLK(q + 1));
    }
    mma16816z(&acc[0], wa[0][0], b0[0], b0[1]);
    mma16816z(&acc[4], wa[1][0], b0[0], b0[1]);
    mma16816z(&acc[8], wa[0][1], b0[2], b0[3]);
    mma16816z(&acc[12], wa[1][1], b0[2], b0[3]);
#pragma unroll
    for (int q = 1; q < 9; q++) {
      uint32_t* const c = b[(q - 1) % NUP];
      mma16816(&acc[0], wa[0][2 * q], c[0], c[1]);
      mma16816(&acc[4], wa[1][2 * q], c[0], c[1]);
      mma16816(&acc[8], wa[0][2 * q + 1], c[2], c[3]);
      mma16816(&acc[12], wa[1][2 * q + 1], c[2], c[3]);
      if (R1 && q + NUP == B3Q) bar_sync(3, 256);
      if (q + NUP < 9) ldsm4t_in(c, mem_a + MEM_BLK(q + NUP), always);
      else if (R1 && q + NUP < 11) lds128_in(c, t16 + SM_PART + (10 - q - NUP) * 2048, always);
      else if (!R1 && GATE && q == GATE) { bar_arrive(11, 256); lds128_in(c, sb + SC_DEAD, always); u0 = u1 = __uint_as_float(c[3]); }
    }
#pragma unroll
    for (int i = 0; i < 8; i++) {
      const float u = i < 4 ? u0 : u1;
      r[i] = R1 ? fmaf(acc[8 + i], u, (acc[i] + __uint_as_float(b[(8 + i / 4) % NUP][i & 3])) * u) : (GATE ? fmaf(acc[i], u, acc[8 + i]) : acc[i] + acc[8 + i]);
    }
  };
  if (ro == 0) {
#pragma unroll 1
    while (true) {
      do_export(BoolC<true>(), always);
      PROFP(3);
      if (s == 8) STAMP(6);
      float r[8];
      memproj(BoolC<false>(), 30, 0, 0.f, 0.f, r);
      sts128(t16 + SM_PART, __float_as_uint(r[0]), __float_as_uint(r[1]), __float_as_uint(r[2]), __float_as_uint(r[3]));
      sts128(t16 + SM_PART + 2048, __float_as_uint(r[4]), __float_as_uint(r[5]), __float_as_uint(r[6]), __float_as_uint(r[7]));
      bar_arrive(3, 256);
      PROF(1);
      bar_sync(9, 256);
      if (s == NSEG - 1) break;
      post_hint();
      if (!(EXV & 1) && w == 3 && s) publish(s);
      if (w == 1) {
        uint32_t m[8];
        lds128(t16 + SM_MAX - 512, m); lds128(t16 + SM_MAX, m + 4);
        const int em = (wexp(amax4(amax4(*(const __half2*)&m[0], m), m + 4)) >> 3) + (int)(lds32(sb + SC_UNSC + (s & 1) * 8) >> 23) - 15;
        const int ex = max(s ? em : 0, (int)lds32(sb + SC_XMAX + 4 * s)) - 127 + (int)lds32(sb + SC_EXPW);
        sts32(sb + SC_UNSC + (~s & 1) * 8, (127 + min(max(ex, -120), 120)) << 23);
        __syncwarp();
        if (elect_one()) mbar_arrive(sb + MB_S);
      }
      SCHED_FENCE(9);
      bar_sync(5, qk ? N5 : 256);
      PROF(2);
      import();
      xproj<0, 0, NII>(acc, wa, dA);
      if (NII < 18) {
        if (qk) bar_sync(7, 384);
        xproj<0, NII, 18>(acc, wa, dA);
        if (!qk) bar_sync(7, 384);
      } else {
        if (F10) WG_WAIT(0);
        bar_sync(10, 256);
        if (F10) SCHED_FENCE(17);
      }
      dA += (int64_t)(b2 ? XT >> 4 : -(XT >> 3));
      finish(s + ah);
      if (((EXV & 1) || w != 3) && ((EXV & 2) || qk || w >= VW2)) bar_arrive(13, 384);
      PROF(6);
      SCHED_FENCE(14);
      if (NOB & 2) bar_arrive(14, 256);
      bar_sync(12, 256);
      PROF(7);
      xproj<1, 0, 18, true>(acc, wa, dA);
      if (!(NOB & 2)) bar_arrive(14, 256);
      b2 = b2 == 2 ? 0 : b2 + 1;
      s++;
      if ((!(EXV & 1) && w == 3) || (!(EXV & 2) && !qk && w < VW2)) {
        bar_sync(13, 384);
        if (!(EXV & 1) && w == 3) export_seg(s); else send_v(s + 1, w);
      }
      PROFP(8);
    }
    if (!qk) bar_arrive(5, 256);
    if (!(EXV & 1) && w == 3) publish(NSEG - 1);
  } else {
    uint32_t km[4];
    auto send_km = [&]() {
      if (XP & (4 | 4096)) return;
      const uint32_t t = (km[0] & ~1u) | lds32(sb + SC_EPO + 4), u = (s * NH + head_id()) * 4096;
      if (qk)
        asm volatile("{\n.reg .u32 o;\n.reg .u64 a;\nshr.u32 o, %0, 1;\nadd.u32 o, o, %1;\nmad.wide.u32 a, o, 1, %2;\nst.relaxed.gpu.global.v2.b32 [a], {%3,%4};\n}"
                     :: "r"(t16), "r"(u + rank * 1024 - (sb >> 1)), "l"(g_km), "r"(t), "r"(km[1]) : "memory");
      else
        asm volatile("{\n.reg .u32 o;\n.reg .u64 a;\nadd.u32 o, %0, %1;\nmad.wide.u32 a, o, 1, %2;\nst.relaxed.gpu.global.v4.b32 [a], {%3,%4,%5,%6};\n}"
                     :: "r"(t16), "r"(u + 2048 - sb), "l"(g_km), "r"(t), "r"(km[1]), "r"(km[2]), "r"(km[3]) : "memory");
    };
#pragma unroll 1
    while (true) {
      do_export(BoolC<true>(), always);
      if ((EXV & 1) && w == 1) export_seg(s);
      if ((EXV & 2) && !qk && w == 2) send_v(s + 1, 0);
      PROFP(3);
      if (s == 8) STAMP(6);
      const uint32_t tl = ((t16 >> 8) ^ wg) & 1, am = (t16 & ~256u) - w * 256;
      const float un = __uint_as_float(lds32(sb + SC_UNSC + (s & 1) * 8));
      float r[8];
      if (qk) {
        uint32_t a0 = am + (tl ? SM_QM : SM_BLK + 8192 + (s & 3) * SEGB);
        float u0 = wg ? un * (SM_SCALE * LOG2E) : un, u1 = wg ? un : un * (SM_SCALE * LOG2E);
        PIN(a0); PIN(u0); PIN(u1);
        memproj(BoolC<true>(), 32, a0, u0, u1, r);
        const uint32_t p0 = pack_bf16(r[0], r[1]), p1 = pack_bf16(r[2], r[3]), p2 = pack_bf16(r[4], r[5]), p3 = pack_bf16(r[6], r[7]);
        stsm4(a0, p0, p1, p2, p3);
        bar_arrive(4, 256);
        km[0] = wg ? p2 : p0; km[1] = wg ? p3 : p1;
      } else {
        const uint32_t d0 = s < NSEG - 1 ? 0 : 2, d1 = s < NSEG - 1 ? 1 : 2;
        uint32_t r0 = mapa(t16 + SM_VM, d0), r1 = mapa(t16 + SM_VM, d1);
        PIN(r0); PIN(r1);
        memproj(BoolC<true>(), 34, r0 | r1, un, un, r);
        const uint32_t p0 = pack_bf16(r[0], r[1]), p1 = pack_bf16(r[2], r[3]), p2 = pack_bf16(r[4], r[5]), p3 = pack_bf16(r[6], r[7]);
        const uint32_t v0 = wg ? p2 : p0, v1 = wg ? p3 : p1, v2 = wg ? p0 : p2, v3 = wg ? p1 : p3;
        st_async4(r0, v0, v1, v2, v3, mapa(sb + MB_S, d0));
        st_async4(r1, v0, v1, v2, v3, mapa(sb + MB_S, d1));
        bar_arrive(5, 256);
        sts128(t16 + SM_VM, v0, v1, v2, v3);
        __syncwarp();
        if (elect_one()) mbar_arrive(sb + MB_S);
        km[0] = v0; km[1] = v1; km[2] = v2; km[3] = v3;
      }
      if (s == NSEG - 1) break;
      PROF(1);
      if (KME && (qk || w != 2)) send_km();
      auto rearm = [&]() { mbar_wait(sb + MB_S, s & 1); if (elect_one()) mbar_expect(sb + MB_S, qk ? 640 + 2048 : 1280); __syncwarp(); };
      if (w == 1) {
        if ((t16 & 384) == 0) stg_relaxed(tm.red + (RED_SLOT(s + 2) + RED_LINE(blockIdx.x)) + (t16 & 112), 0, 0, 0, 0);
        if (EXV & 1) publish(s);
      } else if (w == 0) {
        const int tn = s + ah + 1;
        if (RFW) mbar_wait(sb + MB_S, s & 1);
        if (tn + 1 < NSEG && !(XP & 8) && elect_one()) {
          const int b0 = b2 == 2 ? 0 : b2 + 1;
          mbar_expect(sb + MB_X + 8 * b0, XT);
          tma_load3(sb + SM_X + b0 * XT, &tm.x, (tn + 1) * 32, sb + MB_X + 8 * b0);
        }
        if (tn < NSEG && (!(XP & 8) || tn < 3)) mbar_wait(sb + MB_X + 8 * b2, (tn / 3) & 1);
      } else if (w == 2) {
        if (!qk) { if (VW2 < 1) send_v(s + 1, 0); if (VW2 < 2) send_v(s + 1, 1); }
      } else if (qk || !NIC) {
        rearm();
      }
      __syncwarp();
      if (!KME || (!qk && w == 2)) send_km();
      import();
      PROF(4);
      SCHED_FENCE(10);
      if (NIC) {
        if (qk) bar_sync(7, NII < 18 ? 384 : 256);
        xproj<0, 0, NIC>(acc, wa, dA);
        if (!qk) { if (w == 3) rearm(); bar_sync(7, NII < 18 ? 384 : 256); }
      } else {
        bar_sync(7, NII < 18 ? 384 : 256);
      }
      if (NOB & 1) bar_arrive(12, 256);
      xproj<0, NIC, 18>(acc, wa, dA);
      if (!(NOB & 1)) bar_arrive(12, 256);
      dA += (int64_t)(b2 ? XT >> 4 : -(XT >> 3));
      finish(s + ah);
      if (qk && w == 0) wait_v(s + 1);
      bar_arrive(13, 384);
      PROF(6);
      SCHED_FENCE(13);
      bar_sync(14, 256);
      PROF(7);
      xproj<1, 0, 18>(acc, wa, dA);
      b2 = b2 == 2 ? 0 : b2 + 1;
      s++;
      PROFP(8);
    }
    send_km();
    if ((EXV & 1) && w == 1) publish(NSEG - 1);
    PIN(t16);
    if (t16 - sb < 128) stg_relaxed(tm.red + (RED_SLOT(NSEG + 1) + RED_LINE(head_id() * 3 + rank)) + (t16 & 112), 0, 0, 0, 0);
  }
  bar_arrive(0, 384);
  STAMP(3);
  cluster_sync();
  STAMP(4);
}

DI void attn_role(const uint32_t sb, unsigned char* smem_raw, const RMaps& tm, const uint32_t RANK, const bf16* __restrict__ x, const bf16* __restrict__ mem0,
                  const int w, const int lane) {
  const int t2 = w * 32 + lane;
  uint32_t wo[8][4], w1[8][4];
  const uint32_t wo_lane = sb + ((lane & 7) + ((lane >> 4) << 3)) * 128 + (((w + 4 * ((lane >> 3) & 1)) ^ (lane & 7)) << 4);
  unsigned char* const g_red = tm.red;
  {
    const uint32_t tag = *(volatile unsigned*)&g_epoch + 1;
    QSTAMP(0);
    bar_sync(0, 160);
    QSTAMP(1);
    cluster_arrive();
    __half2 hx = __float2half2_rn(0.f);
    if (blockIdx.x < NSEG) {
      mbar_wait(sb + MB_XS, 0);
#pragma unroll
      for (int i = 0; i < 18; i++) { uint32_t v[4]; lds128(sb + SM_STAGE + 2 * 49152 + t2 * 16 + i * 2048, v); hx = amax4(hx, v); }
      fence_async();
      bar_sync(6, 128);
      if (t2 == 0) load_w(sb, tm, RANK, 2);
      __syncwarp();
    }
    if (t2 == 0) { sts64(sb + SC_EPO, (tag - 1) * NSEG + 1, tag & 1); sts32(sb + SC_UNSC, __float_as_uint(1.f)); sts128(sb + SC_DEAD, 0, 0, 0, 0x3f800000u); sts64(sb + SC_FPAR, 0, 0); sts128(sb + SC_ONES, 0x3f803f80u, 0x3f803f80u, 0x3f803f80u, 0x3f803f80u); }
    WSTAMP(27);
    uint32_t q[8] = {0, 0, 0, 0, 0, 0, 0, 0};
    QSTAMP(2);
    mbar_wait(sb + MB_WO3, 0);
    QSTAMP(3);
    uint32_t mv[5][4];
#pragma unroll
    for (int i = 0; i < 5; i++) {
      ldsm4(mv[i], sb + SM_M0 + (lane & 7) * (DM * 2) + min(w + 4 * i, 17) * 64 + (lane >> 3) * 16);
      if (blockIdx.x == 0) hx = amax4(hx, mv[i]);
    }
    sts32(sb + SC_SS + 4 * (12 + w), wexp(hx));
#pragma unroll
    for (int k = 0; k < 8; k++) {
      ldsm4t(wo[k], wo_lane + SM_WO3 + k * 2048); ldsm4t(w1[k], wo_lane + SM_WOST + k * 2048);
#pragma unroll
      for (int i = 0; i < 4; i++) { sq_acc(q[i], wo[k][i]); sq_acc(q[i], w1[k][i]); }
    }
    bar_sync(6, 128);
#pragma unroll
    for (int k = 0; k < 8; k++) sts128(sb + SM_WO3 + t2 * 16 + k * 2048, wo[k][0], wo[k][1], wo[k][2], wo[k][3]);
#pragma unroll
    for (int i = 0; i < 5; i++) {
      const int c = (w + 4 * i) * 32;
      if (c < DM) stsm4t(sb + SM_MEM + (c + c / 192 * 64 + lane) * 16, mv[i][0], mv[i][1], mv[i][2], mv[i][3]);
    }
    bar_arrive(1, 256); bar_arrive(2, 256); bar_arrive(9, 256);
    QSTAMP(4);
    mbar_wait(sb + MB_WO, 0);
    QSTAMP(5);
#pragma unroll
    for (int k = 0; k < 8; k++) ldsm4t(wo[k], wo_lane + SM_X + XT + k * 2048);
    fence_async();
    bar_sync(6, 128);
    if (t2 == 32) tma_load3(sb + SM_X + XT, &tm.x, 32, sb + MB_X + 8);
    __syncwarp();
#pragma unroll
    for (int k = 0; k < 8; k++)
#pragma unroll
      for (int i = 0; i < 4; i++) sq_acc(q[4 + i], wo[k][i]);
    float ss = 0.f;
#pragma unroll
    for (int i = 0; i < 8; i++) ss += bf_lo(q[i]) + bf_hi(q[i]);
    ss = warp_sum(ss);
    if (lane == 0) sts32(sb + SC_SS + 4 * (8 + w), __float_as_uint(ss));
    QSTAMP(6);
    bar_sync(11, 384);
    QSTAMP(7);
    if (t2 == 0) {
      float a[16];
#pragma unroll
      for (int i = 0; i < 4; i++) lds128f(sb + SC_SS + 16 * i, &a[4 * i]);
      stg_relaxed(&g_stats[blockIdx.x * 2], __float_as_uint(((a[0] + a[1]) + (a[2] + a[3])) + ((a[4] + a[5]) + (a[6] + a[7]))),
                  __float_as_uint((a[8] + a[9]) + (a[10] + a[11])),
                  max(max(__float_as_uint(a[12]), __float_as_uint(a[13])), max(__float_as_uint(a[14]), __float_as_uint(a[15]))), tag);
    }
    __syncwarp();
    WSTAMP(24);
    QSTAMP(8);
    cluster_wait();
    QSTAMP(9);
    if (w == 0) {
      uint4 v[3];
      int n = 0;
      while (true) {
#pragma unroll
        for (int i = 0; i < 3; i++) v[i] = ldg_relaxed(&g_stats[(i * 32 + lane) * 2]);
        if (__all_sync(0xffffffffu, v[0].w == tag && v[1].w == tag && v[2].w == tag) || ++n > SPIN_LIMIT) break;
        __nanosleep(100);
      }
      WSTAMP(25);
      QSTAMP(10);
      const float sv = warp_sum(__uint_as_float(v[0].x) + __uint_as_float(v[1].x) + __uint_as_float(v[2].x));
      const float so = warp_sum(__uint_as_float(v[0].y) + __uint_as_float(v[1].y) + __uint_as_float(v[2].y));
      const int expW = ((int)(__float_as_uint(sv) >> 23) + (int)(__float_as_uint(so) >> 23) - 254 + 2 + 10 + 1) >> 1;
      sts32(sb + SC_XMAX + 4 * lane, v[0].z); sts32(sb + SC_XMAX + 128 + 4 * lane, v[1].z);
      sts32(sb + SC_EXPW, expW + 1 - 15);
      if (blockIdx.x == 0 && lane == 0) *(volatile unsigned*)&g_epoch = tag;
      sts32(sb + SC_FPAR + 4, 1);
    } else if (w < 3) {
      const uint32_t u = blockIdx.x >> 4;
      unsigned char* const z = g_red + 98304 + (blockIdx.x & 15) * 128 + (u & 1) * 2048 + (u & 6) * 4096 + (((u >> 1) ^ w) & 1) * 4096 + lane * 4;
      stg_relaxed32(z, 0);
      uint32_t best = 0xffffffffu;
#pragma unroll 1
      for (int i = 0; i < 64; i++) {
        uint32_t dt;
        asm volatile("{\n.reg .pred p;\n.reg .u32 c, v;\nmov.u32 c, %%clock;\n"
                     "atom.relaxed.gpu.global.exch.b32 v, [%1], 0;\nsetp.eq.u32 p, v, 0;\nmov.u32 %0, 0;\n@p mov.u32 %0, %%clock;\nsub.u32 %0, %0, c;\n}"
                     : "=r"(dt) : "l"(z) : "memory");
        best = min(best, dt);
        if (lds32v(sb + SC_FPAR + 4) && i >= NPROBE - 1) break;
      }
      sts32(sb + SC_LAT + (w - 1) * 4, best);
    }
    QSTAMP(11);
    bar_sync(13, 384);
    bar_arrive(0, 384);
    QSTAMP(12);
    WSTAMP(26);
  }

  const uint32_t nh = __shfl_sync(0xffffffffu, near_half(sb), 0);
  uint32_t l16 = sb + lane * 16;
  PIN(l16);
#define LV ((l16 >> 4) & 31)
#define fence_reg l16
  const uint32_t red_lo = (uint32_t)(uint64_t)g_red, red_hi = (uint32_t)((uint64_t)g_red >> 32);
  uint32_t lp;
  auto slot = [&](int s, uint32_t c, uint32_t ofs) {
    const uint32_t lo = lp | (red_lo + ((w >> 1) * 4 + (w & 1) * 2 + ((w ^ c) & 1)) * 4096 + RED_SLOT(s) + ofs);
    uint64_t a; asm("mov.b64 %0, {%1, %2};" : "=l"(a) : "r"(lo), "r"(red_hi));
    return (unsigned char*)a;
  };
  const uint32_t always = __shfl_sync(0xffffffffu, lds32(sb + SC_DEAD + 12), 0);
  const int mode0 = RANK < 2 ? w : w | 4;
  auto hint_addr = [&](int s) { return min(LV, 23u) * 4 + (red_lo + HINT_OFF + nh * 4096 + w * 16384 + RED_SLOT(s)); };
  auto load_hints = [&](uint32_t lo) {
    uint64_t a; asm("mov.b64 %0, {%1, %2};" : "=l"(a) : "r"(lo), "r"(red_hi));
    return ldg_relaxed32((const void*)a);
  };
  int s = 0;
  bool bad = false;
#pragma unroll 1
  while (true) {
    const uint32_t par = s & 1;
    uint32_t vx[4][4], hints;
    auto load_vx = [&]() {
      const uint32_t va = l16 + (RANK < 2 ? SM_VC + par * 8192 : SM_BLK + (s & 3) * SEGB) + w * 1024 + ((LV >> 3) & 1) * 384 - (LV >> 4) * 128;
#pragma unroll
      for (int i = 0; i < 4; i++) ldsm4(vx[i], va + (i & 1) * 4096 + (i >> 1) * 256);
    };
    auto retire = [&](uint32_t x) {
      asm volatile("{\n.reg .pred p;\nsetp.eq.u32 p, %0, 0;\n@p exit;\n}" :: "r"(vx[0][0] | vx[1][0] | vx[2][0] | vx[3][0] | x) : "memory");
    };
    auto scores = [&](auto memkeys, auto first, float* sc) {
      constexpr bool MK = decltype(memkeys)::value, FIRST = decltype(first)::value;
      uint32_t kb[4][4], qb[2][4];
      const uint32_t m = LV >> 3;
      uint32_t kaddr = l16 + SM_BLK + 4096 + (s & 3) * SEGB + w * 2048 + (m & 1) * (MK ? 128 : 896) - (m >> 1) * 128;
      if (MK) { PIN(kaddr); }
      else {
#pragma unroll
        for (int k = 0; k < 4; k++) ldsm4t(kb[k], kaddr + k * 256);
      }
      if (FIRST) { load_vx(); retire(MK ? kaddr : kb[0][0] | kb[1][0] | kb[2][0] | kb[3][0] | l16); bar_sync(4, 256); PROF(4); }
      ldsm4t(qb[0], l16 + SM_QM);
      if (MK) ldsm4t(kb[0], kaddr);
      ldsm4t(qb[1], l16 + SM_QM + 512);
      if (MK) ldsm4t(kb[2], kaddr + 512);
      float c[4][4];
      mma16816z(c[0], kb[0], qb[0][0], qb[0][1]); mma16816z(c[1], kb[MK ? 0 : 1], qb[0][2], qb[0][3]);
      mma16816z(c[2], kb[2], qb[1][0], qb[1][1]); mma16816z(c[3], kb[MK ? 2 : 3], qb[1][2], qb[1][3]);
      if (FIRST && B5POS == 0) bar_arrive(5, N5);
#pragma unroll
      for (int i = 0; i < (MK ? 2 : 4); i++) sc[i] = ((c[0][i] + c[1][MK ? i + 2 : i]) + c[2][i]) + c[3][MK ? i + 2 : i];
    };
    auto send = [&](auto memkeys) {
      constexpr bool MK = decltype(memkeys)::value;
      constexpr int N = MK ? 1 : 2;
      const uint32_t sa = sb + LV * 4 + SM_E + (MK ? 1024 + RANK * 128 : RANK * 512 + w * 256);
      uint32_t ra[N][2], mb[N][2];
#pragma unroll
      for (int i = 0; i < N; i++)
#pragma unroll
        for (int j = 0; j < 2; j++) {
          ra[i][j] = mapa(sa + i * 128, j ? 2 : RANK ^ 1); mb[i][j] = mapa(sb + MB_S, j ? 2 : RANK ^ 1);
          PIN(ra[i][j]);
        }
      float sc[4];
      scores(memkeys, BoolC<true>(), sc);
      uint32_t e[N];
#pragma unroll
      for (int i = 0; i < N; i++) {
        e[i] = pack_bf16(ex2(sc[2 * i]), ex2(sc[2 * i + 1]));
        if (!(fmaxf(fabsf(sc[2 * i]), fabsf(sc[2 * i + 1])) <= E_LIM)) e[i] = 0x7fff7fffu;
        st_async1(ra[i][0], e[i], mb[i][0]);
        st_async1(ra[i][1], e[i], mb[i][1]);
      }
#pragma unroll
      for (int i = 0; i < N; i++) sts32(sa + i * 128, e[i]);
      __syncwarp();
      if (l16 == sb) mbar_arrive(sb + MB_S);
      PROF(5);
    };
    const int mode = bad ? 8 : mode0;
    if (mode < 2) {
      send(BoolC<false>());
    } else if (mode == 2) {
      send(BoolC<true>());
    } else if (mode == 8) {
      load_vx();
      retire(l16);
      const uint32_t fp = lds32(sb + SC_FPAR);
      bar_sync(6, 128);
      if (w == 0 && l16 == sb) { sts32(sb + SC_FPAR, fp ^ 1); mbar_expect(sb + MB_F, 3072); }
      if (RANK < 2 && w < 3) {
        float sc[4] = {0.f, 0.f, 0.f, 0.f};
        if (w < 2) scores(BoolC<false>(), BoolC<false>(), sc); else scores(BoolC<true>(), BoolC<false>(), sc);
#pragma unroll 1
        for (int r = 0; r < 3; r++)
          st_async4(mapa(l16 + SM_FB + RANK * 1536 + w * 512, r), __float_as_uint(sc[0]), __float_as_uint(sc[1]), __float_as_uint(sc[2]), __float_as_uint(sc[3]), mapa(sb + MB_F, r));
      }
      mbar_wait(sb + MB_F, fp);
      float a[12];
#pragma unroll
      for (int j = 0; j < 3; j++) {
        float b[4];
        lds128f(l16 + SM_FB + j * 512, a + 4 * j); lds128f(l16 + SM_FB + 1536 + j * 512, b);
#pragma unroll
        for (int i = 0; i < 4; i++) a[4 * j + i] += b[i];
      }
      float m0 = fmaxf(fmaxf(fmaxf(a[0], a[2]), fmaxf(a[4], a[6])), a[8]), m1 = fmaxf(fmaxf(fmaxf(a[1], a[3]), fmaxf(a[5], a[7])), a[9]);
#pragma unroll
      for (int o = 4; o < 32; o <<= 1) { m0 = fmaxf(m0, __shfl_xor_sync(0xffffffffu, m0, o)); m1 = fmaxf(m1, __shfl_xor_sync(0xffffffffu, m1, o)); }
#pragma unroll
      for (int i = 0; i < 5; i++) {
        const uint32_t ea = sb + SM_E + LV * 4 + (i < 4 ? i * 128 : 1024);
        sts32(ea, pack_bf16(ex2(a[2 * i] - m0), ex2(a[2 * i + 1] - m1)));
        sts32(ea + (i < 4 ? 512 : 128), 0x3f803f80u);
      }
      __syncwarp();
    } else {
      load_vx();
      if (mode == 3) bar_arrive(4, 256);
      retire(l16 + 1);
    }
    {
      uint32_t wa[4], wb[4], oc[4];
      constexpr int WS = 2048;
      const uint32_t w3a = l16 + SM_WO3 + w * 512;
      lds128(w3a + KP(0) * WS, wa); lds128(w3a + KP(1) * WS, wb); lds128(sb + SC_ONES, oc);
      if (B5POS == 1 && mode < 3) bar_arrive(5, N5);
      uint32_t e[10], p[5], vm[4], ob[4];
      float o0[4], o1[4], f[3][2][4], rs[4];
      reserve2(vm); reserve2(vm + 2); reserve2(e + 8);
      hints = hint_addr(s);
      PIN(hints);
      if (CLR & 2) asm volatile("{\n.reg .pred p;\nsetp.eq.u32 p, %0, 0;\n@p exit;\n}" :: "r"(wa[0] | wb[0] | oc[0] | hints) : "memory");
      mbar_wait(sb + MB_S, par);
      PROF(6);
      ldsm4t(e, l16 + SM_E); ldsm2t_in(e + 8, l16 + SM_E + 1024, always); ldsm4t(e + 4, l16 + SM_E + 512);
      lds128_in(vm, l16 + w * 512 + SM_VM, always);
      const float scl = __uint_as_float(lds32(sb + SC_UNSC + 8 - par * 8));
      hints = load_hints(hints);
      if (GF & 1) SCHED_FENCE(4);
#pragma unroll
      for (int i = 0; i < 4; i++) p[i] = mul_bf16(e[i], e[4 + i]);
      p[4] = mul_bf16(e[8], e[9]);
      if (MO & 4) {
        float a0[4], a1[4];
        mma16816z(o0, vx[0], p[0], p[1]); mma16816z(o1, vx[1], p[0], p[1]);
        mma16816z(a0, vx[2], p[2], p[3]); lds128_in(vx[2], w3a + KP(2) * WS, always);
        mma16816z(a1, vx[3], p[2], p[3]); lds128_in(vx[3], w3a + KP(3) * WS, always);
        mma1688(o0, vm[0], vm[1], p[4]); mma1688(o1, vm[2], vm[3], p[4]);
        mma16816z(rs, oc, p[0], p[1]); mma16816(rs, oc, p[2], p[3]); mma1688(rs, oc[0], oc[1], p[4]);
#pragma unroll
        for (int i = 0; i < 4; i++) { o0[i] += a0[i]; o1[i] += a1[i]; }
      } else {
      mma16816z(o0, vx[0], p[0], p[1]); mma16816z(o1, vx[1], p[0], p[1]); mma16816z(rs, oc, p[0], p[1]);
      mma16816(o0, vx[2], p[2], p[3]); lds128_in(vx[2], w3a + KP(2) * WS, always);
      mma16816(o1, vx[3], p[2], p[3]); lds128_in(vx[3], w3a + KP(3) * WS, always);
      mma16816(rs, oc, p[2], p[3]);
      mma1688(o0, vm[0], vm[1], p[4]); mma1688(o1, vm[2], vm[3], p[4]); mma1688(rs, oc[0], oc[1], p[4]);
      }
      stsm4(l16 + w * 512 + SM_OB, pack_bf16(o0[0], o0[1]), pack_bf16(o0[2], o0[3]), pack_bf16(o1[0], o1[1]), pack_bf16(o1[2], o1[3]));
      bar_sync(6, 128);
      PROF(7);
      ldsm4t_in(oc, l16 + SM_OB, always);
      bad = __any_sync(0xffffffffu, !(rs[0] + rs[1] > 0.f) && !bad);
      rs[0] *= scl; rs[1] *= scl;
      asm volatile("{\n.reg .pred p;\nsetp.ne.u32 p, %1, 0;\n@p rcp.approx.ftz.f32 %0, %0;\n}" : "+f"(rs[0]) : "r"(always));
      asm volatile("{\n.reg .pred p;\nsetp.ne.u32 p, %1, 1;\n@p rcp.approx.ftz.f32 %0, %0;\n}" : "+f"(rs[1]) : "r"(always));
      asm volatile("lop3.b32 %0, %1, %2, %3, 0xfe;" : "=r"(lp) : "r"((l16 & 128) * 2), "r"((l16 & 256) * 4), "r"(l16 & 112));
      if (bad) continue;
      ldsm4t(ob, l16 + SM_OB + 512);
      mma16816z(f[2][0], wa, oc[0], oc[1]); mma16816z(f[2][1], wb, oc[2], oc[3]);
      mma16816z(f[0][0], wo[0], oc[0], oc[1]); mma16816z(f[0][1], wo[4], oc[2], oc[3]);
      mma16816z(f[1][0], w1[0], oc[0], oc[1]); mma16816z(f[1][1], w1[4], oc[2], oc[3]);
      ldsm4t_in(oc, l16 + SM_OB + 1024, always);
      mma16816(f[2][0], vx[2], ob[0], ob[1]); lds128_in(vx[2], w3a + KP(4) * WS, always);
      mma16816(f[2][1], vx[3], ob[2], ob[3]); lds128_in(vx[3], w3a + KP(5) * WS, always);
      mma16816(f[0][0], wo[1], ob[0], ob[1]); mma16816(f[0][1], wo[5], ob[2], ob[3]);
      mma16816(f[1][0], w1[1], ob[0], ob[1]); mma16816(f[1][1], w1[5], ob[2], ob[3]);
      ldsm4t_in(ob, l16 + SM_OB + 1536, always);
      mma16816(f[0][0], wo[2], oc[0], oc[1]); mma16816(f[0][1], wo[6], oc[2], oc[3]);
      mma16816(f[2][0], vx[2], oc[0], oc[1]); lds128_in(vx[2], w3a + KP(6) * WS, always);
      mma16816(f[2][1], vx[3], oc[2], oc[3]); lds128_in(vx[3], w3a + KP(7) * WS, always);
      mma16816(f[1][0], w1[2], oc[0], oc[1]); mma16816(f[1][1], w1[6], oc[2], oc[3]);
      mma16816(f[0][0], wo[3], ob[0], ob[1]); mma16816(f[0][1], wo[7], ob[2], ob[3]);
      mma16816(f[1][0], w1[3], ob[0], ob[1]); mma16816(f[1][1], w1[7], ob[2], ob[3]);
      mma16816(f[2][0], vx[2], ob[0], ob[1]); mma16816(f[2][1], vx[3], ob[2], ob[3]);
      bar_arrive(7, NII < 18 ? 384 : 256);
      lds128_in(ob, sb + SC_DEAD, always);
      uint32_t h[3][2];
#pragma unroll
      for (int j = 0; j < 3; j++)
#pragma unroll
        for (int i = 0; i < 2; i++)
        {
          scale_sum(f[j][1][2 * i], f[j][0][2 * i], rs[0], always); scale_sum(f[j][1][2 * i + 1], f[j][0][2 * i + 1], rs[1], always);
          h[j][i] = pack_f16(f[j][1][2 * i], f[j][1][2 * i + 1]);
        }
      const uint32_t rofs = RANK * 32768;
      red_f16x8(slot(s, RANK >> 1, rofs), h[0][0], h[1][0], h[2][0], 0x3c00u);
      red_f16x8(slot(s, (RANK >> 1) ^ 1, rofs), h[0][1], h[1][1], h[2][1], 0x3c00u);
      if (NII == 18) bar_arrive(10, 256);
      SCHED_FENCE(5);
      l16 += ob[B7R];
    }
    {
    PROF(8);
    const uint32_t ma0 = l16 + SM_MEM + w * 128 + (LV >> 3) * 896 + nh * 512;
    const unsigned char* const sl[2] = {slot(s, nh, 0), slot(s, nh ^ 1, 0)};
    uint32_t dl = gtime() - 1984;
    uint32_t late = latest_hint(hints, dl, s);
    if (late >= 64) {
      int n = 0;
#pragma unroll 1
      do {
        hints = load_hints(hint_addr(s));
        dl = gtime() - 1984;
        late = latest_hint(hints, dl, s);
      } while (late >= 64 && ++n < SPIN_LIMIT);
    }
    dl += late * 32 + tm.poll + (s >= PS1 ? 32 : 0);
    PROF(9);
    {
      auto wait_until = [&](uint32_t t) {
        asm volatile("{\n.reg .pred p;\n.reg .s32 c;\n.reg .u64 t;\nTL: mov.u64 t, %%globaltimer;\ncvt.u32.u64 c, t;\nsub.s32 c, c, %0;\nsetp.lt.s32 p, c, 0;\n@p bra.uni TL;\n}" :: "r"(t + (l16 & 15)) : "memory");
      };
      uint4 v[2][3];
      auto load = [&](int c) {
#pragma unroll
        for (int r = 0; r < 3; r++) v[c][r] = ldg_relaxed(sl[c ^ (r >> 1)] + r * 32768);
      };
      auto decode = [&](int c, int n) {
        uint32_t q[9];
        __half2 hm;
        const uint32_t ma = ma0 ^ (c * 512);
#pragma unroll
        for (int i = 0; i < 9; i++) {
          const uint32_t h = i % 3 == 0 ? v[c][i / 3].x : (i % 3 == 1 ? v[c][i / 3].y : v[c][i / 3].z);
          const float2 f = __half22float2(*(const __half2*)&h);
          q[i] = pack_bf16(f.x, f.y);
          hm = i ? __hmax2(hm, __habs2(*(const __half2*)&h)) : __habs2(*(const __half2*)&h);
        }
#pragma unroll
        for (int r = 0; r < 3; r++) stsm4(ma + r * 4096, q[3 * r], q[3 * r + 1], q[3 * r + 2], r < 2 ? v[c][r].w : *(const uint32_t*)&hm);
        const bool done = __all_sync(0xffffffffu, v[c][0].w == 0x5000u && v[c][1].w == 0x5000u && v[c][2].w == 0x5000u) || n > SPIN_LIMIT;
        asm volatile("{\n.reg .pred p;\nsetp.ne.u32 p, %0, 0;\n@p bar.arrive %1, 256;\n}" :: "r"((int)done), "r"(1 + c) : "memory");
        return done;
      };
      if (LEAD) { wait_until(dl - LEAD); load(1); }
      int n = MO & 1 ? l16 & 15 : 0;
      if (MO & 1) PIN(n);
      if (MO & 2) {
        const uint32_t t = __shfl_sync(0xffffffffu, dl, 0);
        asm volatile("{\n.reg .pred p;\n.reg .s32 c;\nTL: mov.u32 c, %%globaltimer_lo;\nsub.s32 c, c, %0;\nsetp.lt.s32 p, c, 0;\n@p bra.uni TL;\n}" :: "r"(t) : "memory");
      } else wait_until(dl);
      PROF(10);
#pragma unroll 1
      do {
        load(0);
        if (!LEAD) load(1);
        asm volatile("{\n.reg .pred p;\nsetp.eq.u32 p, %0, 0;\n@p bar.sync 13, 384;\n}" :: "r"(n) : "memory");
      } while (!decode(0, n++));
      PROF(11);
#pragma unroll 1
      while (!decode(1, n++)) load(1);
      bar_arrive(9, 256);
      PROF(12);
    }
    PROF(13);
    if (++s == NSEG - 1) break;
    }
  }
#undef fence_reg
  if (RANK < 2) bar_arrive(4, 256);
  bar_sync(0, 384);
  cluster_sync();
}

__global__ void __cluster_dims__(3, 1, 1) __launch_bounds__(384, 1)
rec_kernel(const __grid_constant__ RMaps tm, const bf16* __restrict__ x, const bf16* __restrict__ mem0) {
  extern __shared__ __align__(1024) unsigned char smem_raw[];
  const uint32_t sb = smem_u32(smem_raw);
  const int tid = threadIdx.x, lane = tid & 31;
  const int wg = __shfl_sync(0xffffffffu, tid >> 7, 0);
  const int w = __shfl_sync(0xffffffffu, (tid >> 5) & 3, 0);
  uint32_t rank; asm("mov.u32 %0, %%cluster_ctarank;" : "=r"(rank));
  STAMP(0);
  asm volatile("griddepcontrol.launch_dependents;" ::: "memory");

  if (wg < 2) {
    if (tid == 0) {
      const int h = blockIdx.x / 3;
      mbar_init(sb + MB_XS, 1);
      for (int i = 0; i < 3; i++) { mbar_init(sb + MB_W + 8 * i, 1); mbar_init(sb + MB_X + 8 * i, 1); }
      mbar_init(sb + MB_WO3, 1);
      fence_async();
      if (blockIdx.x < NSEG) { mbar_expect(sb + MB_XS, XT); bulk_load(sb + SM_STAGE + 2 * 49152, x + blockIdx.x * 32 * DM, XT, sb + MB_XS); }
      load_w(sb, tm, rank, 0);
      mbar_expect(sb + MB_X, XT);
      tma_load3(sb + SM_X, &tm.x, 0, sb + MB_X);
      if (WPOS == 2) load_w(sb, tm, rank, 1);
      mbar_expect(sb + MB_WO3, 32768 + 8 * DM * 2);
      tma_load(sb + SM_WOST, &tm.wo, rank * 192 + 64, h * DH, sb + MB_WO3);
      tma_load(sb + SM_WO3, &tm.wo, rank * 192 + 128, h * DH, sb + MB_WO3);
      bulk_load(sb + SM_M0, mem0, 8 * DM * 2, sb + MB_WO3);
      if (WOPF) tma_prefetch(&tm.wo, rank * 192, h * DH);
      if (WPOS == 1) load_w(sb, tm, rank, 1);
      if (blockIdx.x >= NSEG) load_w(sb, tm, rank, 2);
      mbar_init(sb + MB_WO, 1);
      mbar_init(sb + MB_S, rank < 2 ? 5 : 6);
      mbar_init(sb + MB_F, 1);
      mbar_init(sb + MB_VX, 1); mbar_init(sb + MB_VX + 8, 1);
      asm volatile("fence.mbarrier_init.release.cluster;" ::: "memory");
      fence_async();
      mbar_expect(sb + MB_X + 8, XT); mbar_expect(sb + MB_X + 16, XT);
      mbar_expect(sb + MB_WO, 16384);
      mbar_expect(sb + MB_S, rank < 2 ? 640 + 2048 : 1280);
      mbar_expect(sb + MB_VX, 8192); mbar_expect(sb + MB_VX + 8, 8192);
    }
    __syncwarp();
    asm volatile("setmaxnreg.inc.sync.aligned.u32 192;");
    __syncwarp();
    QSTAMP(0);
    if (tid < 32) bar_arrive(0, 160);
    QSTAMP(1);
    proj_role(sb, tm, rank, wg, w, lane);
  } else {
    asm volatile("setmaxnreg.dec.sync.aligned.u32 120;");
    attn_role(sb, smem_raw, tm, rank, x, mem0, w, lane);
  }
}

constexpr int NAUX = 36;
constexpr int A_ST = 6, A_STAGE = 8192 + 12288, A_W8 = A_ST * A_STAGE, A_EXC = A_W8 + A_ST * 1536, A_ROWS = 57;
constexpr int A_IN = A_EXC + 8 * 2304, A_INB = 3 * SEGB, A_OST = A_IN + 2 * A_INB, A_P = A_OST + 8192, A_G = A_P + 3072;
constexpr int A_BAR = A_G + 1024;
constexpr int A_XT = A_BAR + 1024, A_XW = A_XT;
constexpr int A_TOTAL = A_XT + 4096;
static_assert(A_IN % 1024 == 0 && A_XT % 1024 == 0 && A_IN >= 4 * XT && A_IN + 64 * DM * 2 <= A_BAR && A_TOTAL <= 232448, "side kernel shared memory");
struct AMaps { CUtensorMap x, wa, wa8, o, o3, o16, wob, woa, woa16; const unsigned char* red; uint32_t poll; };

DI void wgmma_n192_ss_nt(float* d, uint64_t da, uint64_t db, int acc) {
  asm volatile("{\n.reg .pred p;\nsetp.ne.b32 p, %98, 0;\n"
               "wgmma.mma_async.sync.aligned.m64n192k16.f32.bf16.bf16 {"
               "%0,%1,%2,%3,%4,%5,%6,%7,%8,%9,%10,%11,%12,%13,%14,%15,%16,%17,%18,%19,%20,%21,%22,%23,%24,%25,%26,%27,%28,%29,%30,%31,"
               "%32,%33,%34,%35,%36,%37,%38,%39,%40,%41,%42,%43,%44,%45,%46,%47,%48,%49,%50,%51,%52,%53,%54,%55,%56,%57,%58,%59,%60,%61,%62,%63,"
               "%64,%65,%66,%67,%68,%69,%70,%71,%72,%73,%74,%75,%76,%77,%78,%79,%80,%81,%82,%83,%84,%85,%86,%87,%88,%89,%90,%91,%92,%93,%94,%95"
               "}, %96, %97, p, 1, 1, 0, 1;\n}\n"
               : ACC8(d, 0), ACC8(d, 8), ACC8(d, 16), ACC8(d, 24), ACC8(d, 32), ACC8(d, 40), ACC8(d, 48), ACC8(d, 56),
                 ACC8(d, 64), ACC8(d, 72), ACC8(d, 80), ACC8(d, 88) : "l"(da), "l"(db), "r"(acc));
}
DI void wgmma_n24_ss_nt(float* d, uint64_t da, uint64_t db, int acc) {
  asm volatile("{\n.reg .pred p;\nsetp.ne.b32 p, %14, 0;\n"
               "wgmma.mma_async.sync.aligned.m64n24k16.f32.bf16.bf16 {%0,%1,%2,%3,%4,%5,%6,%7,%8,%9,%10,%11}, %12, %13, p, 1, 1, 0, 1;\n}\n"
               : ACC8(d, 0), "+f"(d[8]), "+f"(d[9]), "+f"(d[10]), "+f"(d[11]) : "l"(da), "l"(db), "r"(acc));
}
DI void tma_load3d(uint32_t dst, const CUtensorMap* m, int c0, int c1, int c2, uint32_t mb) {
  asm volatile("cp.async.bulk.tensor.3d.shared::cluster.global.mbarrier::complete_tx::bytes [%0], [%1, {%3, %4, %5}], [%2];"
               :: "r"(dst), "l"(m), "r"(mb), "r"(c0), "r"(c1), "r"(c2) : "memory");
}
DI uint32_t trans8(uint32_t x) { uint32_t r; asm("movmatrix.sync.aligned.m8n8.trans.b16 %0, %1;" : "=r"(r) : "r"(x)); return r; }
DI void wgmma_n40_ss(float* d, uint64_t da, uint64_t db, int acc) {
  asm volatile("{\n.reg .pred p;\nsetp.ne.b32 p, %22, 0;\n"
               "wgmma.mma_async.sync.aligned.m64n40k16.f32.bf16.bf16 {%0,%1,%2,%3,%4,%5,%6,%7,%8,%9,%10,%11,%12,%13,%14,%15,%16,%17,%18,%19}, "
               "%20, %21, p, 1, 1, 1, 1;\n}\n"
               : ACC8(d, 0), ACC8(d, 8), "+f"(d[16]), "+f"(d[17]), "+f"(d[18]), "+f"(d[19]) : "l"(da), "l"(db), "r"(acc));
}
DI uint2 ldg_relaxed64(const void* p) {
  uint2 v; asm volatile("ld.relaxed.gpu.global.v2.b32 {%0,%1}, [%2];" : "=r"(v.x), "=r"(v.y) : "l"(p) : "memory"); return v;
}
template <int ST> DI void ldg8x64(uint32_t* m, const void* p) {
  asm volatile("ld.relaxed.gpu.global.v2.b32 {%0,%1}, [%16];\nld.relaxed.gpu.global.v2.b32 {%2,%3}, [%16 + %17];\n"
               "ld.relaxed.gpu.global.v2.b32 {%4,%5}, [%16 + %18];\nld.relaxed.gpu.global.v2.b32 {%6,%7}, [%16 + %19];\n"
               "ld.relaxed.gpu.global.v2.b32 {%8,%9}, [%16 + %20];\nld.relaxed.gpu.global.v2.b32 {%10,%11}, [%16 + %21];\n"
               "ld.relaxed.gpu.global.v2.b32 {%12,%13}, [%16 + %22];\nld.relaxed.gpu.global.v2.b32 {%14,%15}, [%16 + %23];"
               : "=r"(m[0]), "=r"(m[1]), "=r"(m[2]), "=r"(m[3]), "=r"(m[4]), "=r"(m[5]), "=r"(m[6]), "=r"(m[7]),
                 "=r"(m[8]), "=r"(m[9]), "=r"(m[10]), "=r"(m[11]), "=r"(m[12]), "=r"(m[13]), "=r"(m[14]), "=r"(m[15])
               : "l"(p), "n"(ST), "n"(2 * ST), "n"(3 * ST), "n"(4 * ST), "n"(5 * ST), "n"(6 * ST), "n"(7 * ST) : "memory");
}
template <int ST> DI void ldg4x128(uint32_t* m, const void* p) {
  asm volatile("ld.relaxed.gpu.global.v4.b32 {%0,%1,%2,%3}, [%16];\nld.relaxed.gpu.global.v4.b32 {%4,%5,%6,%7}, [%16 + %17];\n"
               "ld.relaxed.gpu.global.v4.b32 {%8,%9,%10,%11}, [%16 + %18];\nld.relaxed.gpu.global.v4.b32 {%12,%13,%14,%15}, [%16 + %19];"
               : "=r"(m[0]), "=r"(m[1]), "=r"(m[2]), "=r"(m[3]), "=r"(m[4]), "=r"(m[5]), "=r"(m[6]), "=r"(m[7]),
                 "=r"(m[8]), "=r"(m[9]), "=r"(m[10]), "=r"(m[11]), "=r"(m[12]), "=r"(m[13]), "=r"(m[14]), "=r"(m[15])
               : "l"(p), "n"(ST), "n"(2 * ST), "n"(3 * ST) : "memory");
}
template <int N, int ST> DI bool stale(const uint32_t* m, uint32_t tag) {
  uint32_t x = m[0] ^ tag;
#pragma unroll
  for (int i = 1; i < N; i++) asm("lop3.b32 %0, %0, %1, %2, 0xf6;" : "+r"(x) : "r"(m[i * ST]), "r"(tag));
  return __any_sync(0xffffffffu, x & 1);
}
DI bool mbar_test(uint32_t b, uint32_t par) {
  uint32_t r; asm volatile("{\n.reg .pred p;\nmbarrier.test_wait.parity.shared::cta.b64 p, [%1], %2;\nselp.u32 %0, 1, 0, p;\n}" : "=r"(r) : "r"(b), "r"(par) : "memory");
  return r;
}
DI int wait_flags(const unsigned* p, bool active, unsigned base, int seg) {
  int n = 0, m;
  while (true) {
    m = __reduce_min_sync(0xffffffffu, active ? (int)(ldg_acquire32(p) - base) : NSEG);
    if (m > seg || ++n > SPIN_LIMIT) break;
    __nanosleep((YP & 32) ? 400 : 40);
  }
  return max(m, seg + 1);
}
DI void wait_count(const unsigned* p, unsigned target) {
  int n = 0;
  unsigned v;
  while (true) {
    asm volatile("ld.acquire.gpu.global.b32 %0, [%1];" : "=r"(v) : "l"(p) : "memory");
    if ((int)(v - target) >= 0 || ++n > SPIN_LIMIT) break;
    __nanosleep(64);
  }
}
#define PACE_NEXT 800
#define AWARM 0
#define WPF 3
#define UNP 64
#define ADLY 0
#define ODLY 100
#define SDLY 0
#define RSL 100
#define TWO 0
#define ALLW 1
#define PING 60
#define FLAG 2
#define FPOS 1
#define QB 1
#define Q_LO 0
#define Q_HI 320
DI bool tick_wait(uint32_t pace, int step) {
  const int n = lds32v(pace);
  if (n <= step) mbar_wait(pace + 8, n & 1);
  return n <= step;
}
DI void quiet_wait(uint32_t pace) {
  uint32_t n, d;
  asm volatile("ld.volatile.shared.v2.b32 {%0,%1}, [%2];" : "=r"(n), "=r"(d) : "r"(pace) : "memory");
  if (n - 1 < NSEG - 2 && (int)(gtime() - d) > Q_HI) mbar_wait(pace + 8, n & 1);
}
DI void sleep_until(uint32_t t) {
  for (int n = 0; n < 64; n++) {
    const int r = t - gtime();
    if (r <= 0) break;
    __nanosleep(r >> 1);
  }
}
DI void aux_barrier(int i, unsigned epoch, bool wait = true) {
  asm volatile("fence.proxy.async;" ::: "memory");
  asm volatile("red.release.gpu.global.add.u32 [%0], 1;" :: "l"(&g_abar[i * 32]) : "memory");
  if (!wait) return;
  wait_count(&g_abar[i * 32], NAUX * (epoch + 1));
  asm volatile("fence.proxy.async;" ::: "memory");
}

__global__ void __launch_bounds__(512, 1)
aux_kernel(const __grid_constant__ AMaps tm, const bf16* __restrict__ x, const bf16* __restrict__ gate_w, bf16* __restrict__ out) {
  extern __shared__ __align__(1024) unsigned char smem_raw[];
  const uint32_t sb = smem_u32(smem_raw);
  const uint32_t full1 = sb + A_BAR, empty1 = full1 + 8 * A_ST, fullw = empty1 + 8 * A_ST, full3 = fullw + 16, empty3 = full3 + 32,
                 fulla = empty3 + 32, emptya = fulla + 32, fullg = emptya + 16, pace = fullg + 8;
  const int tid = threadIdx.x, lane = tid & 31, cta = blockIdx.x;
  const int wg = __shfl_sync(0xffffffffu, tid >> 7, 0), w = __shfl_sync(0xffffffffu, (tid >> 5) & 3, 0);
  ASTAMP(14);
  const unsigned epoch = *(volatile unsigned*)&g_epoch2;
  if (tid == 0) {
    for (int i = 0; i < A_ST; i++) { mbar_init(full1 + 8 * i, 1); mbar_init(empty1 + 8 * i, 8); }
    mbar_init(fullw, 1); mbar_init(fullw + 8, 1); mbar_init(fullg, 1);
    for (int i = 0; i < 2; i++) { mbar_init(fulla + 16 * i, 2); mbar_init(fulla + 16 * i + 8, 1); mbar_init(emptya + 8 * i, 4); }
    sts64(pace, 0, 0); mbar_init(pace + 8, 1); sts32(pace + 16, 0); sts64(pace + 24, 65536, 0xffff0000u);
    for (int i = 0; i < 4; i++) { mbar_init(full3 + 8 * i, 1); mbar_init(empty3 + 8 * i, cta < NH ? 8 : 4); }
    fence_async();
  }
  __syncthreads();
  ASTAMP(0);
  const bool wide = cta < NH;
  auto p3_ks = [&](int g) { return wide ? cta >> 2 : 2 * (cta - NH) + g; };
  auto p3_mt = [&](int g) { return wide ? 2 * (cta & 3) + g : 8; };
  const unsigned fbase = epoch * NSEG;
  if (wg == 3) {
    asm volatile("setmaxnreg.dec.sync.aligned.u32 %0;" :: "n"(TWO ? 32 : 48));
    if (w == 1 && cta < NH) {
#pragma unroll 1
      for (int seg = 0; seg < ((XP & 2048) ? 0 : NSEG); seg++) {
        bar_arrive(5, 160);
        if (seg > 0 && lane == 0) {
          asm volatile("cp.async.bulk.wait_group 0;" ::: "memory");
          stg_relaxed32(&g_oflag[cta * 32], fbase + seg);
        }
        __syncwarp();
        bar_sync(4, 160);
        if (QM & 16) tick_wait(pace, seg + 1);
        if (lane == 0) {
          fence_async();
          if (!(YP & 2)) {
          tma_store(&tm.o, sb + A_OST, cta * DH, seg * 32);
          tma_store(&tm.o, sb + A_OST + 4096, cta * DH + 64, seg * 32);
          }
          asm volatile("cp.async.bulk.commit_group;" ::: "memory");
          asm volatile("cp.async.bulk.wait_group.read 0;" ::: "memory");
        }
        __syncwarp();
      }
      if (lane == 0) {
        asm volatile("cp.async.bulk.wait_group 0;" ::: "memory");
        { const int seg = NSEG - 1; TSTAMP(2); }
        stg_relaxed32(&g_oflag[cta * 32], fbase + NSEG);
      }
    }
    if (w == 2 && cta < NH) {
      const uint32_t ktag = (epoch + 1) & 1, ma = sb + A_IN + 8192 + lane * 16;
      int avail = 0;
      bar_sync(10, 64);
#pragma unroll 1
      for (int seg = 0; seg < ((XP & 2048) ? 0 : NSEG); seg++) {
        if (avail <= seg) avail = wait_flags(&g_sflag[(cta * 3 + min(lane, 2)) * 8], true, fbase, seg);
        if ((QM & 8) && seg < UNP) tick_wait(pace, seg);
        TSTAMP(0);
        const unsigned char* km = g_km + (size_t)(seg * NH + cta) * 4096 + lane * 8;
        uint32_t m[16];
        const float g = __ldcg(&g_gate[seg * 32 + lane]);
        ldg8x64<256>(m, km);
        const uint32_t b = seg & 1, full = fulla + 16 * b, mb = ma + b * A_INB;
        mbar_wait(emptya + 8 * b, (~seg >> 1) & 1);
        if (lane < 2) mbar_expect(full + 8 * lane, (YP & 8) ? 0 : 16384 >> lane);
        __syncwarp();
        if (lane < 3 && !(YP & 8)) ((EF & 2) ? bulk_load_ef : bulk_load)(sb + A_IN + b * A_INB + lane * SEGB, g_seg + ((size_t)(seg & RING) * 96 + cta * 3 + lane) * 8192, 8192, full + (lane & 2) * 4);
        int n = 0;
#pragma unroll 1
        while (stale<8, 2>(m, ktag) && ++n < SPIN_LIMIT) { if (seg < UNP - 1) __nanosleep(200); ldg8x64<256>(m, km); }
        TSTAMP(1);
#pragma unroll
        for (int i = 0; i < 4; i++) stsm4(mb + (i >> 1) * SEGB + (i & 1) * 512, m[4 * i], m[4 * i + 1], m[4 * i + 2], m[4 * i + 3]);
        sts32(sb + A_G + b * 128 + lane * 4, __float_as_uint(1.f - g));
        fence_async();
        __syncwarp();
        if (lane == 0) mbar_arrive(full);
      }
    }
    if (w == 3 && QM) {
      const unsigned char* const hp = tm.red + HINT_OFF + 65536 + (cta & 1) * 4096 + min(lane, 23) * 4;
      uint32_t d = 0;
      int s = 0, n = 0;
#pragma unroll 1
      while (s < NSEG - 1) {
        const uint32_t h = ldg_relaxed32(hp + RED_SLOT(s)), t = (gtime() - 1984) & ~31u, late = latest_hint(h, t, s);
        if (late < 64) {
          d = t + late * 32 + tm.poll + (s >= PS1 ? 32 : 0) + Q_LO;
          sleep_until(d);
          s++; n = 0;
          if (lane == 0) { mbar_arrive(pace + 8); sts64(pace, s < NSEG - 1 ? s : 2 * NSEG, d); }
          sleep_until(d + PACE_NEXT);
        } else {
          if (++n > (s ? 16 : 256) || lds32v(pace + 16)) break;
          if (!s) __nanosleep(100);
        }
      }
      if (s < NSEG - 1 && lane == 0) { mbar_arrive(pace + 8); sts64(pace, 2 * NSEG, d); }
    }
    if (w != 0) return;
    const bool lead = lane == 0;
#pragma unroll 1
    for (int it = 0, st = 0, ph = 1, k = 0, col = (cta & 1) * (DM / 2); it < ((XP & 256) ? 0 : 72); it++) {
      mbar_wait(empty1 + 8 * st, ph);
      if (QM & 1) quiet_wait(pace);
      if (elect_one()) {
        mbar_expect(full1 + 8 * st, A_STAGE + 1536);
        tma_load3d(sb + st * A_STAGE, &tm.x, k, (cta >> 1) * A_ROWS - 7, 0, full1 + 8 * st);
        tma_load3d(sb + st * A_STAGE + 8192, &tm.wa, col, k, 0, full1 + 8 * st);
        tma_load3d(sb + A_W8 + st * 1536, &tm.wa8, col + 64, k, 0, full1 + 8 * st);
      }
      __syncwarp();
      if (++st == A_ST) { st = 0; ph ^= 1; }
      k += 32;
      if (k == DM) { k = 0; col += 72; }
    }
    auto load_wo = [&](uint32_t dst, int g, int kb, uint32_t mb) {
      if (kb < 64) tma_load(dst, &tm.wob, p3_mt(g) * 64, kb * 64, mb);
      else tma_load(dst, &tm.woa, p3_mt(g) * 64, (kb - 64) * 64, mb);
    };
    if (lead) mbar_expect(fullw, 16 * 8192);
#pragma unroll 1
    for (int st = 0; st < A_ST; st++) {
      if (!(XP & 256)) mbar_wait(empty1 + 8 * st, 1);
      if (lane < 16 && min(((lane + 1) * 8192 - 1) / A_STAGE, A_ST - 1) == st) load_wo(sb + lane * 8192, lane >> 3, p3_ks(lane >> 3) * 9 + (lane & 7), fullw);
      __syncwarp();
    }
    __syncwarp(); bar_sync(6, 288);
    if (lead) mbar_expect(fullw + 8, 2 * 8192 + (p3_ks(0) >= 4 ? 4096 : 0));
    __syncwarp();
    if (lane < 2) {
      load_wo(sb + (16 + lane) * 8192, lane, p3_ks(lane) * 9 + 8, fullw + 8);
      if (p3_ks(0) >= 4) tma_load(sb + A_XW + lane * 2048, &tm.woa16, p3_mt(lane) * 64, 448 + p3_ks(lane) * 16, fullw + 8);
    }
    __syncwarp();
    if (lead) aux_barrier(1, epoch, ALLW || p3_ks(0) >= 4);
    __syncwarp(); bar_sync(6, 288);
    {
      int avail = 0, sl = 0, ph = 1;
      const int h = (9 * p3_ks(0) >> 1) + lane;
#pragma unroll 1
      for (int seg = 0; seg < ((XP & 2048) ? 0 : NSEG); seg++) {
        if (avail <= seg) avail = wait_flags(&g_oflag[min(h, NH - 1) * 32], lane < (wide ? 5 : 9), fbase, seg);
        SSTAMP(seg, 4);
        for (int g = 0; g < (wide ? 1 : 2); g++) {
          const int ks = p3_ks(g);
          mbar_wait(empty3 + 8 * sl, ph);
          if ((QM & 4) && tick_wait(pace, seg + (QM >> 4 & 1) + 1) && ODLY) __nanosleep(ODLY);
          if (YP & 4) { if (lead) mbar_arrive(full3 + 8 * sl); }
          else if (elect_one()) {
            mbar_expect(full3 + 8 * sl, XT + (ks >= 4 ? 1024 : 0));
            tma_load3d(sb + sl * XT, &tm.o3, 0, seg * 32, ks * 9, full3 + 8 * sl);
            if (ks >= 4) tma_load(sb + A_XT + sl * 1024, &tm.o16, 72 * 64 - 64 + ks * 16, seg * 32, full3 + 8 * sl);
          }
          __syncwarp();
          if (++sl == (wide ? 3 : 4)) { sl = 0; ph ^= 1; }
        }
      }
    }
    sts32(pace + 16, 1);
    __syncwarp(); bar_sync(6, 288);
    asm volatile("griddepcontrol.wait;" ::: "memory");
  } else if (wg == 2) {
    asm volatile("setmaxnreg.dec.sync.aligned.u32 64;");
    if (cta < NH) {
      if (tid == 256) { mbar_expect(fullg, 64 * DM * 2); bulk_load(sb + A_IN, x + cta * 64 * DM, 64 * DM * 2, fullg); }
      uint32_t gw[9];
#pragma unroll
      for (int j = 0; j < 9; j++) gw[j] = ((const uint32_t*)gate_w)[j * 32 + lane];
      mbar_wait(fullg, 0);
      float mine = 0.f;
#pragma unroll 4
      for (int u = 0; u < 16; u++) {
        float d0 = 0.f, d1 = 0.f;
#pragma unroll
        for (int j = 0; j < 9; j++) {
          const uint32_t a = lds32(sb + A_IN + (w * 16 + u) * (DM * 2) + j * 128 + lane * 4);
          d0 = fmaf(bf_lo(a), bf_lo(gw[j]), d0); d1 = fmaf(bf_hi(a), bf_hi(gw[j]), d1);
        }
        d0 = warp_sum(d0 + d1);
        if (lane == u) mine = d0;
      }
      if (lane < 16) g_gate[cta * 64 + w * 16 + lane] = 1.f / (1.f + __expf(-mine));
      fence_async();
    }
    bar_sync(3, 128);
    if (tid == 256) { aux_barrier(0, epoch); if (cta == 0) *(volatile unsigned*)&g_epoch2 = epoch + 1; }
    __syncwarp();
    bar_sync(3, 128);
    if (w == 0) bar_arrive(8, 288);
    if (w == 1 && cta < NH) bar_arrive(10, 64);
    if (cta < NH) {
      CDECL;
#pragma unroll 1
      for (int seg = 0; seg < ((XP & 2048) ? 0 : NSEG); seg++) {
        CSTAMP(0);
        const uint32_t in = sb + A_IN + (seg & 1) * A_INB;
        const uint64_t qd = make_desc(in, 128, 1024, 0);
        mbar_wait(fulla + 16 * (seg & 1), (seg >> 1) & 1);
        CSTAMP(3);
        SSTAMP(seg, 0);
        float d[2][16];
        {
          float a[20];
          uint32_t vm[16];
          const unsigned char* vp = g_km + (size_t)(seg * NH + cta) * 4096 + 2048 + lane * 16;
          if (w == 3) ldg4x128<512>(vm, vp);
          WG_FENCE();
#pragma unroll
          for (int k = 0; k < ((YP & 16) ? 1 : 8); k++) wgmma_n40_ss(a, qd + ((k >> 2) * SEGB + (k & 3) * 256 >> 4), qd + ((k >> 2) * SEGB + (k & 3) * 256 + 4096 >> 4), k > 0);
          const uint32_t ga = sb + A_G + (seg & 1) * 128 + (w & 1) * 64 + (lane >> 2) * 4;
          const float f0 = __uint_as_float(lds32(ga)), f1 = __uint_as_float(lds32(ga + 32));
          WG_COMMIT();
          WG_WAIT(0);
          CSTAMP(5);
          SSTAMP(seg, 1);
          if (w < 2) {
            const int lim = w * 16 + (lane >> 2) - 2 * (lane & 3);
            float m0 = -3.0e38f, m1 = -3.0e38f;
#pragma unroll
            for (int i = 0; i < 20; i++) {
              a[i] *= SM_SCALE * LOG2E;
              if (i < 16 && (i >> 2) * 8 + (i & 1) - (i & 2) * 4 > lim) a[i] = -1.0e9f * LOG2E;
              if (i & 2) m1 = fmaxf(m1, a[i]); else m0 = fmaxf(m0, a[i]);
            }
#pragma unroll
            for (int o = 1; o < 4; o <<= 1) { m0 = fmaxf(m0, __shfl_xor_sync(0xffffffffu, m0, o)); m1 = fmaxf(m1, __shfl_xor_sync(0xffffffffu, m1, o)); }
            float s0 = 0.f, s1 = 0.f;
#pragma unroll
            for (int i = 0; i < 20; i++) { a[i] = ex2(a[i] - (i & 2 ? m1 : m0)); if (i & 2) s1 += a[i]; else s0 += a[i]; }
#pragma unroll
            for (int o = 1; o < 4; o <<= 1) { s0 += __shfl_xor_sync(0xffffffffu, s0, o); s1 += __shfl_xor_sync(0xffffffffu, s1, o); }
            s0 = f0 * rcp(s0); s1 = f1 * rcp(s1);
            uint32_t p[10];
#pragma unroll
            for (int i = 0; i < 10; i++) p[i] = pack_bf16(a[2 * i] * (i & 1 ? s1 : s0), a[2 * i + 1] * (i & 1 ? s1 : s0));
            const uint32_t pa = sb + A_P + (2 * w + ((lane >> 3) & 1)) * 768 + (lane >> 4) * 128 + (lane & 7) * 16;
            stsm4t(pa, p[0], p[1], p[2], p[3]); stsm4t(pa + 256, p[4], p[5], p[6], p[7]); stsm4t(pa + 512, p[8], p[9], 0, 0);
            CSTAMP(6);
            fence_async();
            CSTAMP(7);
          } else if (w == 3) {
            int n = 0;
#pragma unroll 1
            while (stale<4, 4>(vm, (epoch + 1) & 1) && ++n < SPIN_LIMIT) ldg4x128<512>(vm, vp);
#pragma unroll
            for (int i = 0; i < 4; i++) stsm4(in + 2 * SEGB + 8192 + (lane >> 4) * 1024 + (lane & 15) * 16 + i * 256, vm[4 * i], vm[4 * i + 1], vm[4 * i + 2], vm[4 * i + 3]);
            fence_async();
            mbar_wait(fulla + 16 * (seg & 1) + 8, (seg >> 1) & 1);
          }
        }
        CSTAMP(8);

        bar_sync(5, 160);
        CSTAMP(10);
        SSTAMP(seg, 2);
        const uint64_t pd = make_desc(sb + A_P, 128, 768, 0), vd = make_desc(in + 2 * SEGB, 128, 512, 0), md = make_desc(in + 2 * SEGB + 8192, 0, 128, 0);
        WG_FENCE();
#pragma unroll
        for (int i = 0; i < 2; i++) {
          wgmma_n32_ss<0>(d[i], vd + i * 256, pd, 0);
          wgmma_n32_ss<0>(d[i], vd + i * 256 + 16, pd + 16, 1);
          wgmma_n32_ss<0>(d[i], md + i * 64, pd + 32, 1);
        }
        WG_COMMIT();
        WG_WAIT(0);
        CSTAMP(11);
        if (lane == 0) mbar_arrive(emptya + 8 * (seg & 1));
#pragma unroll
        for (int i = 0; i < 2; i++) {
          const uint32_t oa = sb + A_OST + i * 4096 + ((lane & 7) + ((lane >> 4) << 3)) * 128 + (((2 * w + ((lane >> 3) & 1)) ^ (lane & 7)) << 4);
          stsm4t(oa, pack_bf16(d[i][0], d[i][1]), pack_bf16(d[i][2], d[i][3]), pack_bf16(d[i][4], d[i][5]), pack_bf16(d[i][6], d[i][7]));
          stsm4t(oa + 2048, pack_bf16(d[i][8], d[i][9]), pack_bf16(d[i][10], d[i][11]), pack_bf16(d[i][12], d[i][13]), pack_bf16(d[i][14], d[i][15]));
        }
        CSTAMP(12);
        bar_sync(4, 160);
        SSTAMP(seg, 3);
      }
      CDUMP;
    }
  } else {
    asm volatile("setmaxnreg.inc.sync.aligned.u32 %0;" :: "n"(TWO ? 208 : 200));
    {
      const int g = lane >> 2, t = lane & 3, r0 = (cta >> 1) * A_ROWS - 7 + w * 16;
      const uint32_t prev = (2 * t > g ? 0xffffu : 0u) | (2 * t + 1 > g ? 0xffff0000u : 0u);
      const int k0 = r0 + 2 * t - (2 * t > g ? 8 : 0), k1 = r0 + 2 * t + 1 - (2 * t + 1 > g ? 8 : 0);
      const uint32_t slot = sb + A_EXC + (wg * 4 + w) * 2304;
      float gl = 0.f, gh = 0.f;
      int st = 0, ph = 0;
#pragma unroll 1
      for (int p = -AWARM; p < ((XP & 256) ? 0 : 4); p++) {
        float big[96], sml[12];
        if (p == WPF && tid < 18) {
          const int kb = p3_ks(tid >= 9) * 9 + tid % 9;
          tma_prefetch(kb < 64 ? &tm.wob : &tm.woa, p3_mt(tid >= 9) * 64, (kb & 63) * 64);
        }
        __syncwarp();
#pragma unroll
        for (int i = 0; i < 96; i++) big[i] = 0.f;
#pragma unroll
        for (int i = 0; i < 12; i++) sml[i] = 0.f;
#pragma unroll 1
        for (int k = p < 0 ? 18 : 0; k < 18; k++) {
          mbar_wait(full1 + 8 * st, ph);
          const uint64_t da = make_desc(sb + st * A_STAGE + wg * 4096, 16, 512, 2);
          const uint64_t db = make_desc(sb + st * A_STAGE + 8192, 4096, 1024, 1), dc = make_desc(sb + A_W8 + st * 1536, 128, 512, 0);
          WG_FENCE();
#pragma unroll
          for (int j = 0; j < 2; j++) { wgmma_n192_ss_nt(big, da + j * 2, db + j * 128, 1); wgmma_n24_ss_nt(sml, da + j * 2, dc + j * 16, 1); }
          WG_COMMIT();
          WG_WAIT(1);
          if (k > 0 && lane == 0) mbar_arrive(empty1 + 8 * (st ? st - 1 : A_ST - 1));
          if (++st == A_ST) { st = 0; ph ^= 1; }
        }
        WG_WAIT(0);
        ASTAMP(16 + max(p, 0) + wg * 16);
        if (lane == 0 && p >= 0) mbar_arrive(empty1 + 8 * (st ? st - 1 : A_ST - 1));
        uint32_t f[3][9][2];
#pragma unroll
        for (int c = 0; c < 3; c++)
#pragma unroll
          for (int j = 0; j < 9; j++)
#pragma unroll
            for (int i = 0; i < 2; i++) {
              const float* a = j < 8 ? &big[(c * 8 + j) * 4 + 2 * i] : &sml[c * 4 + 2 * i];
              f[c][j][i] = c < 2 ? pack_bf16(a[0], a[1]) : trans8(pack_bf16(a[0], a[1]));
            }
        if (p == 0) {
          bar_sync(8, 288);
          gl = __ldcg(&g_gate[min(max(r0 + g, 0), S_LEN / 2 - 1) * 2 + wg]); gh = __ldcg(&g_gate[min(max(r0 + g + 8, 0), S_LEN / 2 - 1) * 2 + wg]);
        }
        asm volatile("cp.async.bulk.wait_group.read 0;" ::: "memory");
        __syncwarp();
#pragma unroll
        for (int j = 0; j < 8; j += 2) sts128(slot + j * 256 + lane * 16, f[1][j][1], f[2][j][1], f[1][j + 1][1], f[2][j + 1][1]);
        sts64(slot + 2048 + lane * 8, f[1][8][1], f[2][8][1]);
        bar_sync(1 + wg, 128);
        ASTAMP(24 + max(p, 0) + wg * 16);
        uint32_t pv[9][2];
#pragma unroll
        for (int j = 0; j < 9; j++) pv[j][0] = pv[j][1] = 0;
        if (w) {
#pragma unroll
          for (int j = 0; j < 8; j += 2) lds128(slot - 2304 + j * 256 + lane * 16, pv[j]);
          lds64(slot - 256 + lane * 8, pv[8][0], pv[8][1]);
        }
        float a[4][4], m[4][2];
#pragma unroll
        for (int h = 0; h < 4; h++) {
          const int j = 2 * h;
          const uint32_t qa[4] = {t >= h ? f[0][j][0] : 0, t >= h ? f[0][j][1] : 0, f[0][j + 1][0], f[0][j + 1][1]};
          const uint32_t qb0 = t <= h ? f[0][j + 2][0] : 0, qb1 = t <= h ? f[0][j + 2][1] : 0;
          float s0[4], s1[4], s2[4];
          mma16816z(s1, qa, f[1][j][0], f[1][j + 1][0]); mma16816z(s2, qa, f[1][j][1], f[1][j + 1][1]); mma16816z(s0, qa, pv[j][0], pv[j + 1][0]);
          mma1688(s1, qb0, qb1, f[1][j + 2][0]); mma1688(s2, qb0, qb1, f[1][j + 2][1]); mma1688(s0, qb0, qb1, pv[j + 2][0]);
          a[h][0] = 2 * t > g ? s0[0] : s1[0]; a[h][1] = 2 * t + 1 > g ? s0[1] : s1[1]; a[h][2] = 2 * t > g ? s1[2] : s2[2]; a[h][3] = 2 * t + 1 > g ? s1[3] : s2[3];
        }
#pragma unroll
        for (int h = 0; h < 4; h++) {
#pragma unroll
          for (int i = 0; i < 4; i++) a[h][i] = (i & 1 ? k1 : k0) + (i & 2) * 4 >= 0 ? a[h][i] * (0.23570226039551584f * LOG2E) : -1.0e9f * LOG2E;
          m[h][0] = fmaxf(a[h][0], a[h][1]); m[h][1] = fmaxf(a[h][2], a[h][3]);
        }
#pragma unroll
        for (int x = 1; x < 4; x <<= 1)
#pragma unroll
          for (int i = 0; i < 8; i++) m[i >> 1][i & 1] = fmaxf(m[i >> 1][i & 1], __shfl_xor_sync(0xffffffffu, m[i >> 1][i & 1], x));
#pragma unroll
        for (int h = 0; h < 4; h++) {
#pragma unroll
          for (int i = 0; i < 4; i++) a[h][i] = ex2(a[h][i] - m[h][i >> 1]);
          m[h][0] = a[h][0] + a[h][1]; m[h][1] = a[h][2] + a[h][3];
        }
#pragma unroll
        for (int x = 1; x < 4; x <<= 1)
#pragma unroll
          for (int i = 0; i < 8; i++) m[i >> 1][i & 1] += __shfl_xor_sync(0xffffffffu, m[i >> 1][i & 1], x);
        uint32_t o[9][2];
#pragma unroll
        for (int h = 0; h < 4; h++) {
          const int j = 2 * h;
          const float z0 = gl * rcp(m[h][0]), z1 = gh * rcp(m[h][1]);
          const uint32_t pl = pack_bf16(a[h][0] * z0, a[h][1] * z0), pu = pack_bf16(a[h][2] * z1, a[h][3] * z1);
          const uint32_t pa[4] = {pl & prev, 0, pl & ~prev, pu & prev};
          float d[3][4];
#pragma unroll
          for (int i = 0; i < 3; i++) mma16816z(d[i], pa, pv[j + i][1], f[2][j + i][0]);
#pragma unroll
          for (int i = 0; i < 3; i++) mma1688(d[i], 0, pu & ~prev, f[2][j + i][1]);
#pragma unroll
          for (int i = 0; i < 3; i++) {
            const uint32_t d0 = pack_bf16(d[i][0], d[i][1]), d1 = pack_bf16(d[i][2], d[i][3]);
            o[j + i][0] = i == 0 && h > 0 && t < h ? o[j][0] : d0;
            o[j + i][1] = i == 0 && h > 0 && t < h ? o[j][1] : d1;
          }
        }
        ASTAMP(28 + max(p, 0) + wg * 16);
        bar_sync(1 + wg, 128);
        const uint32_t oa = slot + (lane & 15) * 144 + (lane >> 4) * 16;
#pragma unroll
        for (int j = 0; j < 8; j += 2) stsm4(oa + j * 16, o[j][0], o[j][1], o[j + 1][0], o[j + 1][1]);
        asm volatile("stmatrix.sync.aligned.m8n8.x2.shared.b16 [%0], {%1,%2};" :: "r"(oa + 128), "r"(o[8][0]), "r"(o[8][1]) : "memory");
        fence_async();
        __syncwarp();
        if (QM & 64) quiet_wait(pace);
        if (lane < 16 && w * 16 + lane >= 7 && r0 + lane < S_LEN / 2 && p >= 0)
          asm volatile("cp.async.bulk.global.shared::cta.bulk_group [%0], [%1], 144;"
                       :: "l"(g_Ocat + (size_t)((r0 + lane) * 2 + wg) * KCAT + 4096 + (cta & 1) * (DM / 2) + p * 72), "r"(slot + lane * 144) : "memory");
        asm volatile("cp.async.bulk.commit_group;" ::: "memory");
        ASTAMP(20 + max(p, 0) + wg * 16);
      }
      if (XP & 256) bar_sync(8, 288);
      asm volatile("cp.async.bulk.wait_group 0;" ::: "memory");
    }
    ASTAMP(3);
    bar_arrive(6, 288);
    uint32_t wa[37][4];
    mbar_wait(fullw, 0);
    const uint32_t la = sb + ((lane & 7) + ((lane >> 4) << 3)) * 128 + (((2 * w + ((lane >> 3) & 1)) ^ (lane & 7)) << 4);
#pragma unroll
    for (int k = 0; k < 32; k++) ldsm4t(wa[k], la + wg * 65536 + k * 2048);
    mbar_wait(fullw + 8, 0);
#pragma unroll
    for (int k = 32; k < 36; k++) ldsm4t(wa[k], la + wg * 8192 + 65536 + k * 2048);
    ldsm4t(wa[36], la + A_XW + wg * 2048);
    fence_async();
    if (XP & 2048) bar_sync(6, 288); else bar_arrive(6, 288);
    ASTAMP(4);
    const int ks = p3_ks(wg), mt = p3_mt(wg);
    uint32_t v[16];
    auto fetch = [&](int seg) { ldg8x64<1024>(v, g_part + (((seg & 7) * 9 + mt) * 4 + (ks & 3)) * 1024 + (tid & 127)); };
    auto finish = [&](int seg) {
      const uint32_t tagv = (~seg >> 3) & 1;
      int n = 0;
#pragma unroll 1
      while (!(YP & 512) && stale<8, 2>(v, tagv) && ++n < SPIN_LIMIT) {
        if (seg < NSEG - 2) __nanosleep(RSL);
        fetch(seg);
      }
      float own[4] = {bf_lo(v[0]), bf_hi(v[0]), bf_lo(v[1]), bf_hi(v[1])};
#pragma unroll
      for (int j = 1; j < 8; j++) { own[0] += bf_lo(v[2 * j]); own[1] += bf_hi(v[2 * j]); own[2] += bf_lo(v[2 * j + 1]); own[3] += bf_hi(v[2 * j + 1]); }
      uint32_t p0 = pack_bf16(own[0], own[1]), p1 = pack_bf16(own[2], own[3]);
      asm volatile("movmatrix.sync.aligned.m8n8.trans.b16 %0, %0;" : "+r"(p0));
      asm volatile("movmatrix.sync.aligned.m8n8.trans.b16 %0, %0;" : "+r"(p1));
      uint32_t* o = (uint32_t*)(out + (size_t)(seg * 32 + (ks & 3) * 8 + (lane >> 2)) * DM + mt * 64 + w * 16) + (lane & 3);
      if (!(YP & 256) || p0 == 0x12345678) { o[0] = p0; o[4] = p1; }
      SSTAMP(seg, 7);
    };
    float acc[16], acc2[16];
#pragma unroll
    for (int i = 0; i < 16; i++) acc[i] = acc2[i] = 0.f;
    int pend = -1, sl = wide ? 0 : wg, ph = 0;
    if (PING && wg) bar_arrive(1, 256);
    CDECL;
    auto run = [&](auto extra) {
#pragma unroll 1
    for (int seg = 0; seg < ((XP & 2048) ? 0 : NSEG); seg++) {
      CSTAMP(0);
      const bool fin = pend >= 0 && seg - pend >= FLAG;
      if (FPOS == 0 && fin) fetch(pend);
      mbar_wait(full3 + 8 * sl, ph);
      if (FPOS == 1 && fin) fetch(pend);
      if (SDLY) {
        uint32_t n, d;
        asm volatile("ld.volatile.shared.v2.b32 {%0,%1}, [%2];" : "=r"(n), "=r"(d) : "r"(pace) : "memory");
        if ((int)n <= seg + 3) sleep_until(d + SDLY);
      }
      CSTAMP(1);
      if (wg) SSTAMP(seg, 5);
      if (seg < PING) bar_sync(1 + wg, 256);
      CSTAMP(7);
      const uint64_t db = make_desc(sb + sl * XT, 16, 1024, 1);
      WG_FENCE();
#pragma unroll
      for (int k = 0; k < ((XP & 1024) ? 1 : 36); k++)
        wgmma_n32_rs(TWO && (k & 1) ? acc2 : acc, wa[k][0], wa[k][1], wa[k][2], wa[k][3], db + (k >> 2) * 256 + (k & 3) * 2, k >> TWO);
      if (decltype(extra)::value) wgmma_n32_rs(acc, wa[36][0], wa[36][1], wa[36][2], wa[36][3], make_desc(sb + A_XT + sl * 1024, 16, 256, 3), 1);
      WG_COMMIT();
      if (seg < PING) bar_arrive(2 - wg, 256);
      CSTAMP(2);
      if (FPOS == 2 && fin) fetch(pend);
      CSTAMP(3);
      WG_WAIT(0);
      CSTAMP(4);
      if (wg) SSTAMP(seg, 6);
      if (lane == 0) mbar_arrive(empty3 + 8 * sl);
      sl += wide ? 1 : 2;
      if (sl >= (wide ? 3 : 4)) { sl -= wide ? 3 : 4; ph ^= 1; }
      uint2* dst = g_part + (((seg & 7) * 9 + mt) * 32 + ks) * 128 + (tid & 127);
      uint32_t q[8];
      if (TWO)
#pragma unroll
        for (int j = 0; j < 16; j++) acc[j] += acc2[j];
#pragma unroll
      for (int j = 0; j < 8; j++) q[j] = j & 1 ? pack_bf16(acc[2 * j], acc[2 * j + 1]) : (pack_bf16(acc[2 * j], acc[2 * j + 1]) & ~1u) | ((~seg >> 3) & 1);
      if (QM & 32) tick_wait(pace, seg + (QM >> 4 & 1) + 2);
      if (!(YP & 1025) || q[0] == 0x12345678)
      asm volatile("st.relaxed.gpu.global.v2.b32 [%0], {%1,%2};\nst.relaxed.gpu.global.v2.b32 [%0 + 8192], {%3,%4};\n"
                   "st.relaxed.gpu.global.v2.b32 [%0 + 16384], {%5,%6};\nst.relaxed.gpu.global.v2.b32 [%0 + 24576], {%7,%8};"
                   :: "l"(dst), "r"(q[0]), "r"(q[1]), "r"(q[2]), "r"(q[3]), "r"(q[4]), "r"(q[5]), "r"(q[6]), "r"(q[7]) : "memory");
      CSTAMP(5);
      if (fin) { finish(pend); pend = -1; }
      CSTAMP(6);
      if ((seg & 1) == ks >> 2 && !(YP & 1)) pend = seg;
      if (wg && (seg & 7) == 6) ASTAMP(5 + (seg >> 3));
    }
    };
    if (ks >= 4) run(BoolC<true>()); else run(BoolC<false>());
    if (PING && !wg) bar_sync(1, 256);
    if (pend >= 0) { fetch(pend); finish(pend); }
    CDUMP;
    ASTAMP(13);
    bar_sync(6, 288);
  }
}

typedef CUresult (*EncodeFn)(CUtensorMap*, CUtensorMapDataType, cuuint32_t, void*, const cuuint64_t*, const cuuint64_t*,
                             const cuuint32_t*, const cuuint32_t*, CUtensorMapInterleave, CUtensorMapSwizzle,
                             CUtensorMapL2promotion, CUtensorMapFloatOOBfill);
#define PROMO 2
static void make_map(EncodeFn enc, CUtensorMap* m, const void* p, int rows, int cols, int box_rows) {
  cuuint64_t dims[2] = {(cuuint64_t)cols, (cuuint64_t)rows};
  cuuint64_t strides[1] = {(cuuint64_t)cols * 2};
  cuuint32_t box[2] = {64, (cuuint32_t)box_rows};
  cuuint32_t es[2] = {1, 1};
  enc(m, CU_TENSOR_MAP_DATA_TYPE_BFLOAT16, 2, (void*)p, dims, strides, box, es, CU_TENSOR_MAP_INTERLEAVE_NONE,
      CU_TENSOR_MAP_SWIZZLE_128B, (CUtensorMapL2promotion)PROMO, CU_TENSOR_MAP_FLOAT_OOB_FILL_NONE);
}

constexpr int g_poll = POLL_NS;
extern "C" void kernel_launch(void* const* d_in, const int* in_sizes, int n_in, void* d_out, int out_size) {
  const bf16* x = (const bf16*)d_in[0];
  const bf16* wqkvA = (const bf16*)d_in[1];
  const bf16* woA = (const bf16*)d_in[2];
  const bf16* mem0 = (const bf16*)d_in[4];
  const bf16* Wq = (const bf16*)d_in[5];
  const bf16* Wk = (const bf16*)d_in[6];
  const bf16* Wv = (const bf16*)d_in[7];
  const bf16* Wo = (const bf16*)d_in[8];
  const bf16* gate_w = (const bf16*)d_in[10];
  static EncodeFn enc = nullptr;
  static void *pO = nullptr, *pR = nullptr;
  if (!enc) {
    cudaDriverEntryPointQueryResult qr;
    cudaGetDriverEntryPoint("cuTensorMapEncodeTiled", (void**)&enc, cudaEnableDefault, &qr);
    cudaGetSymbolAddress(&pO, g_Ocat);
    cudaGetSymbolAddress(&pR, g_red_raw);
    cudaFuncSetAttribute(rec_kernel, cudaFuncAttributeMaxDynamicSharedMemorySize, SM_TOTAL);
    cudaFuncSetAttribute(aux_kernel, cudaFuncAttributeMaxDynamicSharedMemorySize, A_TOTAL);
  }
  RMaps rm;
  rm.poll = g_poll;
  rm.w[0] = (const unsigned char*)Wk; rm.w[1] = (const unsigned char*)Wq; rm.w[2] = (const unsigned char*)Wv; rm.w[3] = (const unsigned char*)Wo;
  rm.red = (unsigned char*)(((uintptr_t)pR + 262143) & ~(uintptr_t)262143);
  {
    cuuint64_t dims[3] = {64, S_LEN, 9}, strides[2] = {DM * 2, 128};
    cuuint32_t box[3] = {64, 32, 9}, es[3] = {1, 1, 1};
    enc(&rm.x, CU_TENSOR_MAP_DATA_TYPE_BFLOAT16, 3, (void*)x, dims, strides, box, es, CU_TENSOR_MAP_INTERLEAVE_NONE,
        CU_TENSOR_MAP_SWIZZLE_128B, CU_TENSOR_MAP_L2_PROMOTION_L2_128B, CU_TENSOR_MAP_FLOAT_OOB_FILL_NONE);
  }
  make_map(enc, &rm.wq, Wq, DM, 4096, 192);
  make_map(enc, &rm.wk, Wk, DM, 4096, 192);
  make_map(enc, &rm.wv, Wv, DM, 4096, 192);
  make_map(enc, &rm.wo, Wo, 4096, DM, 128);
  AMaps am;
  am.red = rm.red; am.poll = rm.poll;
  {
    cuuint64_t dims[3] = {DM, S_LEN / 2, 2}, strides[2] = {DM * 4, DM * 2};
    cuuint32_t box[3] = {32, 64, 2}, es[3] = {1, 1, 1};
    enc(&am.x, CU_TENSOR_MAP_DATA_TYPE_BFLOAT16, 3, (void*)x, dims, strides, box, es, CU_TENSOR_MAP_INTERLEAVE_NONE,
        CU_TENSOR_MAP_SWIZZLE_64B, CU_TENSOR_MAP_L2_PROMOTION_L2_128B, CU_TENSOR_MAP_FLOAT_OOB_FILL_NONE);
    cuuint64_t wdims[3] = {DM, DM, 3}, wstrides[2] = {DM * 6, DM * 2};
    cuuint32_t wbox[3] = {64, 32, 3}, wbox8[3] = {8, 32, 3};
    enc(&am.wa, CU_TENSOR_MAP_DATA_TYPE_BFLOAT16, 3, (void*)wqkvA, wdims, wstrides, wbox, es, CU_TENSOR_MAP_INTERLEAVE_NONE,
        CU_TENSOR_MAP_SWIZZLE_128B, CU_TENSOR_MAP_L2_PROMOTION_L2_128B, CU_TENSOR_MAP_FLOAT_OOB_FILL_NONE);
    enc(&am.wa8, CU_TENSOR_MAP_DATA_TYPE_BFLOAT16, 3, (void*)wqkvA, wdims, wstrides, wbox8, es, CU_TENSOR_MAP_INTERLEAVE_NONE,
        CU_TENSOR_MAP_SWIZZLE_NONE, CU_TENSOR_MAP_L2_PROMOTION_NONE, CU_TENSOR_MAP_FLOAT_OOB_FILL_NONE);
  }
  {
    cuuint64_t dims[3] = {64, S_LEN, KCAT / 64}, strides[2] = {KCAT * 2, 128};
    cuuint32_t box[3] = {64, 32, 9}, es[3] = {1, 1, 1};
    make_map(enc, &am.o, pO, S_LEN, KCAT, 32);
    enc(&am.o3, CU_TENSOR_MAP_DATA_TYPE_BFLOAT16, 3, pO, dims, strides, box, es, CU_TENSOR_MAP_INTERLEAVE_NONE,
        CU_TENSOR_MAP_SWIZZLE_128B, CU_TENSOR_MAP_L2_PROMOTION_L2_128B, CU_TENSOR_MAP_FLOAT_OOB_FILL_NONE);
  }
  make_map(enc, &am.wob, Wo, 4096, DM, 64);
  make_map(enc, &am.woa, woA, DM, DM, 64);
  make_map(enc, &am.woa16, woA, DM, DM, 16);
  {
    cuuint64_t dims[2] = {KCAT, S_LEN}, strides[1] = {KCAT * 2};
    cuuint32_t box[2] = {16, 32}, es[2] = {1, 1};
    enc(&am.o16, CU_TENSOR_MAP_DATA_TYPE_BFLOAT16, 2, pO, dims, strides, box, es, CU_TENSOR_MAP_INTERLEAVE_NONE,
        CU_TENSOR_MAP_SWIZZLE_32B, CU_TENSOR_MAP_L2_PROMOTION_NONE, CU_TENSOR_MAP_FLOAT_OOB_FILL_NONE);
  }

  rec_kernel<<<96, 384, SM_TOTAL, cudaStreamPerThread>>>(rm, x, mem0);
  cudaLaunchConfig_t cfg = {};
  cfg.gridDim = dim3(NAUX); cfg.blockDim = dim3(512); cfg.dynamicSmemBytes = A_TOTAL; cfg.stream = cudaStreamPerThread;
  cudaLaunchAttribute at[1];
  at[0].id = cudaLaunchAttributeProgrammaticStreamSerialization; at[0].val.programmaticStreamSerializationAllowed = 1;
  cfg.attrs = at; cfg.numAttrs = 1;
  if (XP & 16) cfg.numAttrs = 0;
  if (!(XP & 64)) cudaLaunchKernelEx(&cfg, aux_kernel, am, x, gate_w, (bf16*)d_out);
}
```

```cpp
#include <cuda_runtime.h>
#include <cuda_bf16.h>
#include <cuda_fp16.h>
#include <cuda.h>
#include <stdint.h>

typedef __nv_bfloat16 bf16;

constexpr int S_LEN = 2048, DM = 576, NH = 32, DH = 128, NSEG = 64, KCAT = 4096 + 576;
#define RED_LINE(i) (((i) >> 2) * 4096 + ((i) & 1) * 256 + ((i) & 2) * 512)
#define RED_SLOT(s) (((s) & 1) * 128 + ((s) & 2) * 256)

#define POLL_NS 896
#define NII 18
#define W3PRE 4
#define W3MID 4
#define GF 0
#define B5POS 0
#define NUP 4
#define UPF 1
#define B3Q 9
#define B3F 0
#define GATE 8
#define NTL 2
#define B7R 1
#define EXPOS 0
#define VW2 1
#define CLR 1
#define RFW 0
#define NIC 0
#define LEAD 0
#define FIN16 1
#define VXG 0
#define RING 63
#define EXB 0
#define EXD 0
#define EXB2 8192
#define HDLY 0
#define F10 1
#define NPROBE 2
#define WPOS 1
#define CW 0
#define WOPF 0
#define YP 0
#define EF 7
#define MO 0
#define WE 3
#define EXV 2
#define NOB 0
#define QM 60
#define N5 224
#define KP(i) (((i) >> 1) + 4 * ((i) & 1))
#define SPIN_LIMIT (1 << 14)
#define XP 0

__device__ __align__(1024) bf16 g_Ocat[S_LEN * KCAT];
__device__ __align__(1024) unsigned char g_red_raw[2 * 262144];
constexpr int HINT_OFF = 2048;
__device__ __align__(16) float g_gate[S_LEN];
__device__ __align__(128) uint4 g_stats[96 * 2];
__device__ unsigned g_epoch;
__device__ unsigned g_epoch2;
__device__ unsigned g_oflag[NH * 32];
__device__ unsigned g_abar[3 * 32];
__device__ unsigned g_sflag[96 * 8];
__device__ __align__(1024) unsigned char g_seg[NSEG * 96 * 8192];
__device__ __align__(1024) unsigned char g_km[NSEG * NH * 4096];
__device__ __align__(1024) uint2 g_part[8 * 9 * 4 * 8 * 128];
__device__ int g_err;
#define SSTAMP(seg, idx)
#define TSTAMP(idx)
#define QSTAMP(idx)
#define PROF(idx)
#define PROFP(idx)
#define STAMP(idx)
#define ASTAMP(idx)
#define WSTAMP(idx)

#define CSTAMP(idx)
#define CDECL
#define CDUMP
#define DI __device__ __forceinline__
DI uint32_t smem_u32(const void* p) { return (uint32_t)__cvta_generic_to_shared(p); }
DI uint32_t clock32() { uint32_t c; asm volatile("mov.u32 %0, %%clock;" : "=r"(c) :: "memory"); return c; }
DI uint32_t gtime() { uint32_t c; asm volatile("mov.u32 %0, %%globaltimer_lo;" : "=r"(c) :: "memory"); return c; }
DI uint32_t ldg_relaxed32(const void* p) { uint32_t v; asm volatile("ld.relaxed.gpu.global.b32 %0, [%1];" : "=r"(v) : "l"(p) : "memory"); return v; }
DI uint32_t ldg_acquire32(const void* p) { uint32_t v; asm volatile("ld.acquire.gpu.global.b32 %0, [%1];" : "=r"(v) : "l"(p) : "memory"); return v; }
DI void stg_relaxed32(void* p, uint32_t v) { asm volatile("st.relaxed.gpu.global.b32 [%0], %1;" :: "l"(p), "r"(v) : "memory"); }
DI int head_id() { int c; asm volatile("mov.u32 %0, %%clusterid.x;" : "=r"(c)); return c; }
DI uint32_t mapa(uint32_t a, uint32_t r) { uint32_t o; asm("mapa.shared::cluster.u32 %0, %1, %2;" : "=r"(o) : "r"(a), "r"(r)); return o; }
DI void cluster_arrive() { asm volatile("barrier.cluster.arrive.relaxed.aligned;" ::: "memory"); }
DI void cluster_wait() { asm volatile("barrier.cluster.wait.aligned;" ::: "memory"); }
DI void cluster_sync() { asm volatile("barrier.cluster.arrive.release.aligned;\nbarrier.cluster.wait.acquire.aligned;" ::: "memory"); }
DI void mbar_init(uint32_t b, uint32_t c) { asm volatile("mbarrier.init.shared::cta.b64 [%0], %1;" :: "r"(b), "r"(c) : "memory"); }
DI void mbar_expect(uint32_t b, uint32_t tx) { asm volatile("mbarrier.arrive.expect_tx.shared::cta.b64 _, [%0], %1;" :: "r"(b), "r"(tx) : "memory"); }
DI void mbar_arrive(uint32_t b) { asm volatile("mbarrier.arrive.shared::cta.b64 _, [%0];" :: "r"(b) : "memory"); }
DI void mbar_wait(uint32_t b, uint32_t par) {
  asm volatile("{\n.reg .pred p;\n.reg .u32 n, q;\nmov.u32 n, 0;\n"
               "WL: add.u32 n, n, 1;\nshr.u32 q, n, 12;\nxor.b32 q, q, %1;\n"
               "mbarrier.try_wait.parity.shared::cta.b64 p, [%0], q;\n@!p bra.uni WL;\n}"
               :: "r"(b), "r"(par) : "memory");
}
DI void wait_until(uint32_t t) {
  const uint32_t now = gtime();
  t = min(t, now + 8192);
  asm volatile("{\n.reg .pred p;\n.reg .u32 c;\nTL: mov.u32 c, %%globaltimer_lo;\nsetp.lt.u32 p, c, %0;\n@p bra.uni TL;\n}" :: "r"(t) : "memory");
}
#define PIN(v) v = __shfl_xor_sync(0xffffffffu, v, 0)
#define SCHED_FENCE(k) asm volatile("{\n.reg .pred p;\nsetp.eq.u32 p, %0, %1;\n@p exit;\n}" :: "r"(fence_reg), "r"(k) : "memory")
#define MEM_ORDER(k) asm volatile("{\n.reg .pred p;\nsetp.eq.u32 p, %0, %1;\n@p st.shared.u32 [%0], %0;\n}" :: "r"(fence_reg), "r"(k + 64) : "memory")
DI void bar_sync(int id, int n) { asm volatile("bar.sync %0, %1;" :: "r"(id), "r"(n) : "memory"); }
DI void bar_arrive(int id, int n) { asm volatile("bar.arrive %0, %1;" :: "r"(id), "r"(n) : "memory"); }
DI void fence_async() { asm volatile("fence.proxy.async.shared::cta;" ::: "memory"); }
DI void st_async4(uint32_t a, uint32_t x, uint32_t y, uint32_t z, uint32_t w, uint32_t mb) {
  asm volatile("st.async.weak.shared::cluster.mbarrier::complete_tx::bytes.v4.b32 [%0], {%1,%2,%3,%4}, [%5];"
               :: "r"(a), "r"(x), "r"(y), "r"(z), "r"(w), "r"(mb) : "memory");
}
DI void st_async2(uint32_t a, uint32_t x, uint32_t y, uint32_t mb) {
  asm volatile("st.async.weak.shared::cluster.mbarrier::complete_tx::bytes.v2.b32 [%0], {%1,%2}, [%3];"
               :: "r"(a), "r"(x), "r"(y), "r"(mb) : "memory");
}
DI void sts32(uint32_t a, uint32_t x) { asm volatile("st.shared.b32 [%0], %1;" :: "r"(a), "r"(x) : "memory"); }
DI void sts64(uint32_t a, uint32_t x, uint32_t y) { asm volatile("st.shared.v2.b32 [%0], {%1,%2};" :: "r"(a), "r"(x), "r"(y) : "memory"); }
DI void sts128(uint32_t a, uint32_t x, uint32_t y, uint32_t z, uint32_t w) {
  asm volatile("st.shared.v4.b32 [%0], {%1,%2,%3,%4};" :: "r"(a), "r"(x), "r"(y), "r"(z), "r"(w) : "memory");
}
DI uint32_t lds32(uint32_t a) { uint32_t x; asm volatile("ld.shared.b32 %0, [%1];" : "=r"(x) : "r"(a) : "memory"); return x; }
DI uint32_t lds32v(uint32_t a) { uint32_t x; asm volatile("ld.volatile.shared.b32 %0, [%1];" : "=r"(x) : "r"(a) : "memory"); return x; }
DI void lds64(uint32_t a, uint32_t& x, uint32_t& y) { asm volatile("ld.shared.v2.b32 {%0,%1}, [%2];" : "=r"(x), "=r"(y) : "r"(a) : "memory"); }
DI void lds128(uint32_t a, uint32_t* r) {
  asm volatile("ld.shared.v4.b32 {%0,%1,%2,%3}, [%4];" : "=r"(r[0]), "=r"(r[1]), "=r"(r[2]), "=r"(r[3]) : "r"(a) : "memory");
}
DI void lds128f(uint32_t a, float* r) {
  asm volatile("ld.shared.v4.f32 {%0,%1,%2,%3}, [%4];" : "=f"(r[0]), "=f"(r[1]), "=f"(r[2]), "=f"(r[3]) : "r"(a) : "memory");
}
DI void lds64f(uint32_t a, float* r) { asm volatile("ld.shared.v2.f32 {%0,%1}, [%2];" : "=f"(r[0]), "=f"(r[1]) : "r"(a) : "memory"); }
DI void ldsm4t(uint32_t* r, uint32_t a) {
  asm volatile("ldmatrix.sync.aligned.m8n8.x4.trans.shared.b16 {%0,%1,%2,%3}, [%4];"
               : "=r"(r[0]), "=r"(r[1]), "=r"(r[2]), "=r"(r[3]) : "r"(a) : "memory");
}
DI void ldsm4t_in(uint32_t* r, uint32_t a, uint32_t t) {
  asm volatile("{\n.reg .pred p;\nsetp.ne.u32 p, %5, 0;\n@p ldmatrix.sync.aligned.m8n8.x4.trans.shared.b16 {%0,%1,%2,%3}, [%4];\n}"
               : "+r"(r[0]), "+r"(r[1]), "+r"(r[2]), "+r"(r[3]) : "r"(a), "r"(t) : "memory");
}
DI void lds128_in(uint32_t* r, uint32_t a, uint32_t t) {
  asm volatile("{\n.reg .pred p;\nsetp.ne.u32 p, %5, 0;\n@p ld.shared.v4.b32 {%0,%1,%2,%3}, [%4];\n}"
               : "+r"(r[0]), "+r"(r[1]), "+r"(r[2]), "+r"(r[3]) : "r"(a), "r"(t) : "memory");
}
DI void ldsm2t_in(uint32_t* r, uint32_t a, uint32_t t) {
  asm volatile("{\n.reg .pred p;\nsetp.ne.u32 p, %3, 0;\n@p ldmatrix.sync.aligned.m8n8.x2.trans.shared.b16 {%0,%1}, [%2];\n}" : "+r"(r[0]), "+r"(r[1]) : "r"(a), "r"(t) : "memory");
}
DI void reserve2(uint32_t* r) { asm volatile("{\n.reg .u64 t;\nmov.u64 t, %%clock64;\nmov.b64 {%0, %1}, t;\n}" : "=r"(r[0]), "=r"(r[1])); }
DI void scale_sum(float& x, float& y, float s, uint32_t t) {
  asm volatile("{\n.reg .pred p;\nsetp.ne.u32 p, %2, 0;\n@p mul.f32 %0, %0, %1;\n}" : "+f"(y) : "f"(s), "r"(t));
  asm volatile("{\n.reg .pred p;\nsetp.ne.u32 p, %3, 1;\n@p fma.rn.f32 %0, %0, %1, %2;\n}" : "+f"(x) : "f"(s), "f"(y), "r"(t));
}
DI void ldsm4(uint32_t* r, uint32_t a) {
  asm volatile("ldmatrix.sync.aligned.m8n8.x4.shared.b16 {%0,%1,%2,%3}, [%4];"
               : "=r"(r[0]), "=r"(r[1]), "=r"(r[2]), "=r"(r[3]) : "r"(a) : "memory");
}
DI void st_async1(uint32_t a, uint32_t x, uint32_t mb) {
  asm volatile("st.async.weak.shared::cluster.mbarrier::complete_tx::bytes.b32 [%0], %1, [%2];" :: "r"(a), "r"(x), "r"(mb) : "memory");
}
DI void stsm4(uint32_t a, uint32_t x, uint32_t y, uint32_t z, uint32_t w) {
  asm volatile("stmatrix.sync.aligned.m8n8.x4.shared.b16 [%0], {%1,%2,%3,%4};" :: "r"(a), "r"(x), "r"(y), "r"(z), "r"(w) : "memory");
}
DI void stsm4t(uint32_t a, uint32_t x, uint32_t y, uint32_t z, uint32_t w) {
  asm volatile("stmatrix.sync.aligned.m8n8.x4.trans.shared.b16 [%0], {%1,%2,%3,%4};" :: "r"(a), "r"(x), "r"(y), "r"(z), "r"(w) : "memory");
}
DI uint32_t pack_bf16(float lo, float hi) { uint32_t r; asm("cvt.rn.bf16x2.f32 %0, %1, %2;" : "=r"(r) : "f"(hi), "f"(lo)); return r; }
DI uint32_t pack_f16(float lo, float hi) { uint32_t r; asm("cvt.rn.f16x2.f32 %0, %1, %2;" : "=r"(r) : "f"(hi), "f"(lo)); return r; }
DI float ex2(float x) { float y; asm("ex2.approx.ftz.f32 %0, %1;" : "=f"(y) : "f"(x)); return y; }
DI float rcp(float x) { float y; asm("rcp.approx.ftz.f32 %0, %1;" : "=f"(y) : "f"(x)); return y; }
DI float bf_lo(uint32_t x) { return __uint_as_float(x << 16); }
DI float bf_hi(uint32_t x) { return __uint_as_float(x & 0xffff0000u); }
DI void mma16816(float* d, const uint32_t* a, uint32_t b0, uint32_t b1) {
  asm volatile("mma.sync.aligned.m16n8k16.row.col.f32.bf16.bf16.f32 {%0,%1,%2,%3}, {%4,%5,%6,%7}, {%8,%9}, {%0,%1,%2,%3};"
               : "+f"(d[0]), "+f"(d[1]), "+f"(d[2]), "+f"(d[3]) : "r"(a[0]), "r"(a[1]), "r"(a[2]), "r"(a[3]), "r"(b0), "r"(b1));
}
DI void mma16816z(float* d, const uint32_t* a, uint32_t b0, uint32_t b1) {
  asm volatile("mma.sync.aligned.m16n8k16.row.col.f32.bf16.bf16.f32 {%0,%1,%2,%3}, {%4,%5,%6,%7}, {%8,%9}, {%10,%10,%10,%10};"
               : "=f"(d[0]), "=f"(d[1]), "=f"(d[2]), "=f"(d[3]) : "r"(a[0]), "r"(a[1]), "r"(a[2]), "r"(a[3]), "r"(b0), "r"(b1), "f"(0.f));
}
DI void mma1688z(float* d, uint32_t a0, uint32_t a1, uint32_t b0) {
  asm volatile("mma.sync.aligned.m16n8k8.row.col.f32.bf16.bf16.f32 {%0,%1,%2,%3}, {%4,%5}, {%6}, {%7,%7,%7,%7};"
               : "=f"(d[0]), "=f"(d[1]), "=f"(d[2]), "=f"(d[3]) : "r"(a0), "r"(a1), "r"(b0), "f"(0.f));
}
DI void mma1688(float* d, uint32_t a0, uint32_t a1, uint32_t b0) {
  asm volatile("mma.sync.aligned.m16n8k8.row.col.f32.bf16.bf16.f32 {%0,%1,%2,%3}, {%4,%5}, {%6}, {%0,%1,%2,%3};"
               : "+f"(d[0]), "+f"(d[1]), "+f"(d[2]), "+f"(d[3]) : "r"(a0), "r"(a1), "r"(b0));
}
DI void ldsm2t(uint32_t* r, uint32_t a) {
  asm volatile("ldmatrix.sync.aligned.m8n8.x2.trans.shared.b16 {%0,%1}, [%2];" : "=r"(r[0]), "=r"(r[1]) : "r"(a) : "memory");
}
DI uint32_t add_bf16(uint32_t a, uint32_t b) { uint32_t r; asm("add.rn.bf16x2 %0, %1, %2;" : "=r"(r) : "r"(a), "r"(b)); return r; }
DI uint32_t mul_bf16(uint32_t a, uint32_t b) { uint32_t r; asm("mul.rn.bf16x2 %0, %1, %2;" : "=r"(r) : "r"(a), "r"(b)); return r; }
DI uint64_t make_desc(uint32_t addr, uint32_t lbo, uint32_t sbo, uint32_t swz) {
  return (uint64_t)((addr & 0x3FFFF) >> 4) | ((uint64_t)(lbo >> 4) << 16) | ((uint64_t)(sbo >> 4) << 32) | ((uint64_t)swz << 62);
}
#define WG_FENCE() asm volatile("wgmma.fence.sync.aligned;" ::: "memory")
#define WG_COMMIT() asm volatile("wgmma.commit_group.sync.aligned;" ::: "memory")
#define WG_WAIT(n) asm volatile("wgmma.wait_group.sync.aligned %0;" :: "n"(n) : "memory")
#define ACC8(d, o) "+f"(d[o]), "+f"(d[o + 1]), "+f"(d[o + 2]), "+f"(d[o + 3]), "+f"(d[o + 4]), "+f"(d[o + 5]), "+f"(d[o + 6]), "+f"(d[o + 7])
DI void wgmma_n32_rs(float* d, uint32_t a0, uint32_t a1, uint32_t a2, uint32_t a3, uint64_t db, int acc) {
  asm volatile("{\n.reg .pred p;\nsetp.ne.b32 p, %21, 0;\n"
               "wgmma.mma_async.sync.aligned.m64n32k16.f32.bf16.bf16 {%0,%1,%2,%3,%4,%5,%6,%7,%8,%9,%10,%11,%12,%13,%14,%15}, "
               "{%16,%17,%18,%19}, %20, p, 1, 1, 0;\n}\n"
               : ACC8(d, 0), ACC8(d, 8) : "r"(a0), "r"(a1), "r"(a2), "r"(a3), "l"(db), "r"(acc));
}
template <int TA>
DI void wgmma_n32_ss(float* d, uint64_t da, uint64_t db, int acc) {
  asm volatile("{\n.reg .pred p;\nsetp.ne.b32 p, %18, 0;\n"
               "wgmma.mma_async.sync.aligned.m64n32k16.f32.bf16.bf16 {%0,%1,%2,%3,%4,%5,%6,%7,%8,%9,%10,%11,%12,%13,%14,%15}, "
               "%16, %17, p, 1, 1, %19, 1;\n}\n"
               : ACC8(d, 0), ACC8(d, 8) : "l"(da), "l"(db), "r"(acc), "n"(TA));
}
DI void tma_load(uint32_t dst, const CUtensorMap* m, int c0, int c1, uint32_t mb) {
  asm volatile("cp.async.bulk.tensor.2d.shared::cluster.global.mbarrier::complete_tx::bytes [%0], [%1, {%3, %4}], [%2];"
               :: "r"(dst), "l"(m), "r"(mb), "r"(c0), "r"(c1) : "memory");
}
DI void tma_load3(uint32_t dst, const CUtensorMap* m, int row, uint32_t mb) {
  asm volatile("cp.async.bulk.tensor.3d.shared::cluster.global.mbarrier::complete_tx::bytes [%0], [%1, {%3, %4, %3}], [%2];"
               :: "r"(dst), "l"(m), "r"(mb), "r"(0), "r"(row) : "memory");
}
DI bool elect_one() {
  uint32_t p;
  asm volatile("{\n.reg .pred p;\nelect.sync _|p, 0xffffffff;\nselp.u32 %0, 1, 0, p;\n}" : "=r"(p));
  return p;
}
DI void bulk_s2s(uint32_t dst, uint32_t src, uint32_t bytes, uint32_t mb) {
  asm volatile("cp.async.bulk.shared::cluster.shared::cta.mbarrier::complete_tx::bytes [%0], [%1], %2, [%3];"
               :: "r"(dst), "r"(src), "r"(bytes), "r"(mb) : "memory");
}
DI void bulk_load(uint32_t dst, const void* src, uint32_t bytes, uint32_t mb) {
  asm volatile("cp.async.bulk.shared::cluster.global.mbarrier::complete_tx::bytes [%0], [%1], %2, [%3];" :: "r"(dst), "l"(src), "r"(bytes), "r"(mb) : "memory");
}
#define EVICT_FIRST ".reg .b64 pol;\ncreatepolicy.fractional.L2::evict_first.b64 pol, 1.0;\n"
DI void bulk_load_ef(uint32_t dst, const void* src, uint32_t bytes, uint32_t mb) {
  asm volatile("{\n" EVICT_FIRST "cp.async.bulk.shared::cluster.global.mbarrier::complete_tx::bytes.L2::cache_hint [%0], [%1], %2, [%3], pol;\n}"
               :: "r"(dst), "l"(src), "r"(bytes), "r"(mb) : "memory");
}
DI void tma_load_ef(uint32_t dst, const CUtensorMap* m, int c0, int c1, uint32_t mb) {
  asm volatile("{\n" EVICT_FIRST "cp.async.bulk.tensor.2d.shared::cluster.global.mbarrier::complete_tx::bytes.L2::cache_hint [%0], [%1, {%3, %4}], [%2], pol;\n}"
               :: "r"(dst), "l"(m), "r"(mb), "r"(c0), "r"(c1) : "memory");
}
DI void tma_prefetch(const CUtensorMap* m, int c0, int c1) {
  asm volatile("cp.async.bulk.prefetch.tensor.2d.L2.global.tile [%0, {%1, %2}];" :: "l"(m), "r"(c0), "r"(c1) : "memory");
}
DI void tma_store(const CUtensorMap* m, uint32_t src, int c0, int c1) {
  asm volatile("cp.async.bulk.tensor.2d.global.shared::cta.bulk_group [%0, {%2, %3}], [%1];" :: "l"(m), "r"(src), "r"(c0), "r"(c1) : "memory");
}
DI uint4 ldg_relaxed(const void* p) {
  uint4 v;
  asm volatile("ld.relaxed.gpu.global.v4.b32 {%0,%1,%2,%3}, [%4];" : "=r"(v.x), "=r"(v.y), "=r"(v.z), "=r"(v.w) : "l"(p) : "memory");
  return v;
}
DI void stg_relaxed(void* p, uint32_t x, uint32_t y, uint32_t z, uint32_t w) {
  asm volatile("st.relaxed.gpu.global.v4.b32 [%0], {%1,%2,%3,%4};" :: "l"(p), "r"(x), "r"(y), "r"(z), "r"(w) : "memory");
}
DI void red_f16x8(void* p, uint32_t x, uint32_t y, uint32_t z, uint32_t w) {
  asm volatile("red.relaxed.gpu.global.add.noftz.v4.f16x2 [%0], {%1,%2,%3,%4};" :: "l"(p), "r"(x), "r"(y), "r"(z), "r"(w) : "memory");
}
DI void sq_acc(uint32_t& a, uint32_t x) { asm("fma.rn.bf16x2 %0, %1, %1, %0;" : "+r"(a) : "r"(x)); }
DI __half2 amax4(__half2 h, const uint32_t* v) {
  h = __hmax2_nan(__hmax2_nan(h, __habs2(*(const __half2*)&v[0])), __habs2(*(const __half2*)&v[1]));
  return __hmax2_nan(__hmax2_nan(h, __habs2(*(const __half2*)&v[2])), __habs2(*(const __half2*)&v[3]));
}
DI uint32_t wexp(__half2 h) { const uint32_t u = *(const uint32_t*)&h; return __reduce_max_sync(0xffffffffu, max((u >> 16) & 0x7fffu, u & 0x7fffu)) >> 7; }
DI float max10(const float* a) {
  return fmaxf(fmaxf(fmaxf(fmaxf(a[0], a[1]), fmaxf(a[2], a[3])), fmaxf(fmaxf(a[4], a[5]), fmaxf(a[6], a[7]))), fmaxf(a[8], a[9]));
}
DI float quad_max(float m) {
  return fmaxf(fmaxf(m, __shfl_xor_sync(0xffffffffu, m, 1)), fmaxf(__shfl_xor_sync(0xffffffffu, m, 2), __shfl_xor_sync(0xffffffffu, m, 3)));
}
DI float warp_sum(float v) {
#pragma unroll
  for (int o = 16; o; o >>= 1) v += __shfl_xor_sync(0xffffffffu, v, o);
  return v;
}

constexpr int SM_WO3 = 0;
constexpr int SM_X = 16384;
constexpr int XT = 36864;
constexpr int SM_EXP = 126976;
constexpr int SEGB = 10240;
constexpr int SM_BLK = SM_EXP + 8192;
constexpr int SM_VC = SM_BLK + 4 * SEGB;
constexpr int SM_PART = SM_VC + 16384;
constexpr int SM_QM = SM_PART + 4096;
constexpr int SM_E = SM_QM + 1024;
constexpr int SM_VM = SM_E + 1536;
constexpr int SM_OB = SM_VM + 2048;
constexpr int SM_FB = SM_OB + 2048;
constexpr int SM_STAGE = SM_X + XT;
constexpr int SM_M0 = SM_STAGE + 3 * 49152;
constexpr int SM_MISC = 210944;
constexpr int SM_WOST = 212992;
constexpr int SM_MEM = SM_WOST;
constexpr int SM_MAX = SM_MEM + 11264;
#define MEM_BLK(q) ((q) / 3 * 4096 + (q) % 3 * 1024)
constexpr int SM_TOTAL = 229376;
constexpr int MB_W = SM_MISC;
constexpr int MB_WO = SM_MISC + 24;
constexpr int MB_WO3 = SM_MISC + 32;
constexpr int MB_X = SM_MISC + 40;
constexpr int MB_S = SM_MISC + 64;
constexpr int MB_F = SM_MISC + 72;
constexpr int MB_VX = SM_MISC + 80;
constexpr int SC_FPAR = SM_MISC + 136;
constexpr int SC_DEAD = SM_MISC + 96;
constexpr int SC_UNSC = SM_MISC + 112;
constexpr int SC_EXPW = SM_MISC + 132;
constexpr int SC_ONES = SM_MISC + 144;
constexpr int SC_SS = SM_MISC + 160;
constexpr int SC_LAT = SM_MISC + 224;
constexpr int SC_EPO = SM_MISC + 240;
constexpr int MB_XS = SM_MISC + 248;
constexpr int SC_XMAX = SM_MISC + 256;
constexpr int SC_PROF = 229376;

constexpr float SM_SCALE = 0.08838834764831845f;
constexpr float LOG2E = 1.4426950408889634f;
constexpr float E_LIM = 20.f;

template <bool B> struct BoolC { static constexpr bool value = B; };
template <int I> struct IntC { static constexpr int value = I; };
struct RMaps { CUtensorMap x, wq, wk, wv, wo; unsigned char* red; uint32_t poll; const unsigned char* w[4]; };

DI uint32_t latest_hint(uint32_t h, uint32_t d, int s) {
  const uint32_t x = (((h | 0xc0c0c0c0u) - ((d >> 5) & 63) * 0x01010101u) & 0x3f3f3f3fu) | ((h ^ (((s >> 2) + 1) & 3) * 0x40404040u) & 0xc0c0c0c0u);
  const uint32_t y = __vmaxu2(x & 0x00ff00ffu, (x >> 8) & 0x00ff00ffu);
  return __reduce_max_sync(0xffffffffu, max(y & 0xffffu, y >> 16));
}
DI uint32_t near_half(uint32_t sb) {
  uint32_t a, b; lds64(sb + SC_LAT, a, b);
  return a > b;
}

template <int RT, int K0, int K1, bool D32 = false>
DI void xproj(float* acc, const uint32_t (&wa)[2][18][4], uint64_t xd) {
  if (XP & 1) return;
  WG_FENCE();
#pragma unroll
  for (int k = K0; k < ((XP & 128) ? K0 + 1 : K1); k++)
  {
    uint64_t d = xd + (uint64_t)(((k >> 1) * 4096 + (k & 1) * 32) >> 4);
    if (D32) asm("mov.b64 %0, {%1, %2};" : "=l"(d) : "r"((uint32_t)xd + (((k >> 1) * 4096 + (k & 1) * 32) >> 4)), "r"((uint32_t)(xd >> 32)));
    wgmma_n32_rs(acc, wa[RT][k][0], wa[RT][k][1], wa[RT][k][2], wa[RT][k][3], d, k != 0);
  }
  WG_COMMIT();
}

DI void load_w(uint32_t sb, const RMaps& tm, uint32_t rank, int c) {
  const int h = blockIdx.x / 3;
  mbar_expect(sb + MB_W + 8 * c, 49152);
  ((EF & 4) ? tma_load_ef : tma_load)(sb + SM_STAGE + c * 49152, rank < 2 ? &tm.wk : &tm.wv, h * DH + (rank == 1 ? 64 : 0), c * 192, sb + MB_W + 8 * c);
  ((EF & 4) ? tma_load_ef : tma_load)(sb + SM_STAGE + c * 49152 + 24576, rank < 2 ? &tm.wq : &tm.wv, h * DH + (rank == 0 ? 0 : 64), c * 192, sb + MB_W + 8 * c);
}
DI void seg_store(int seg, uint32_t sb) {
  fence_async();
  if (EF & 1)
    asm volatile("{\n" EVICT_FIRST "cp.async.bulk.global.shared::cta.bulk_group.L2::cache_hint [%0], [%1], 8192, pol;\n}"
                 :: "l"(g_seg + ((size_t)(seg & RING) * 96 + blockIdx.x) * 8192), "r"(sb + SM_BLK + (seg & 3) * SEGB) : "memory");
  else
  asm volatile("cp.async.bulk.global.shared::cta.bulk_group [%0], [%1], 8192;"
               :: "l"(g_seg + ((size_t)(seg & RING) * 96 + blockIdx.x) * 8192), "r"(sb + SM_BLK + (seg & 3) * SEGB) : "memory");
  asm volatile("cp.async.bulk.commit_group;" ::: "memory");
}
DI void seg_publish(int seg, uint32_t sb) {
  const uint32_t v = lds32(sb + SC_EPO) + seg;
  asm volatile("cp.async.bulk.wait_group 0;" ::: "memory");
  stg_relaxed32(&g_sflag[blockIdx.x * 8], v);
}

DI void proj_role(const uint32_t sb, const RMaps& tm, const uint32_t rank, const int wg, const int w, const int lane) {
  const bool qk = rank < 2;
  uint32_t wa[2][18][4];
  float acc[16];
  const uint64_t xd0 = make_desc(sb + SM_X + wg * 64, 16, 1024, 1);
  {
    const int rr = (lane & 7) + ((lane >> 4) << 3);
    const uint32_t col = ((2 * w + ((lane >> 3) & 1)) ^ (lane & 7)) << 4;
    float ss = 0.f;
    bar_sync(3, 256);
    mbar_wait(sb + MB_X, 0);
    auto chunk = [&](auto cc) {
      constexpr int c = decltype(cc)::value;
      QSTAMP(2 + 2 * c);
      mbar_wait(sb + MB_W + 8 * c, 0);
      QSTAMP(3 + 2 * c);
#pragma unroll
      for (int rt = 1; rt >= 0; rt--)
#pragma unroll
        for (int k = 0; k < 6; k++)
          ldsm4t(wa[rt][c * 6 + k], sb + SM_STAGE + c * 49152 + (rt ^ wg) * 24576 + (64 * (k >> 1) + 32 * wg + 16 * (k & 1) + rr) * 128 + col);
      fence_async();
      if (c < 2) {
        bar_sync(3, 256);
        QSTAMP(17 + c);
        if (threadIdx.x == 0) {
          if (c == 0) tma_load(sb + SM_X + XT, &tm.wo, rank * 192, (blockIdx.x / 3) * DH, sb + MB_WO);
          else tma_load3(sb + SM_X + 2 * XT, &tm.x, 64, sb + MB_X + 16);
        }
        __syncwarp();
      } else {
        cluster_arrive();
      }
      xproj<1, 6 * c, 6 * c + 6>(acc, wa, xd0);
      if (!qk) {
        uint32_t q[4] = {0, 0, 0, 0};
#pragma unroll
        for (int rt = 0; rt < 2; rt++)
#pragma unroll
          for (int k = 0; k < 6; k++)
#pragma unroll
            for (int i = 0; i < 4; i++) sq_acc(q[i], wa[rt][c * 6 + k][i]);
#pragma unroll
        for (int i = 0; i < 4; i++) ss += bf_lo(q[i]) + bf_hi(q[i]);
      }
      if (c < 2 && CW) WG_WAIT(0);
    };
    chunk(IntC<0>()); chunk(IntC<1>()); chunk(IntC<2>());
    ss = warp_sum(ss);
    if (lane == 0) sts32(sb + SC_SS + 4 * (wg * 4 + w), __float_as_uint(ss));
    bar_arrive(11, 384);
  }
  STAMP(1);
  QSTAMP(8);
  STAMP(2);

  uint32_t t16 = sb + (w * 32 + lane) * 16;
  uint32_t mem_a = sb + SM_MEM + wg * 512 + lane * 16;
  uint32_t fin_a = sb + (lane & 7) * 16 + SM_BLK + (qk ? (wg ^ 1) * 4096 + w * 256 + (lane & 8) * 16 + (lane & 16) * 64
                                              : wg * 4096 + w * 1024 + (lane & 8) * 64 + (lane & 16) * 8);
  PIN(t16); PIN(mem_a); PIN(fin_a);
  const uint32_t fence_reg = mem_a;
  const uint32_t fin2 = qk ? 2048 : 256;
  auto do_export = [&](auto retire, uint32_t always) {
    WG_WAIT(0);
    uint32_t p[2];
#pragma unroll
    for (int i = 0; i < 2; i++) {
      p[i] = pack_bf16(acc[8 * i], acc[8 * i + 1]);
      sts128(t16 + SM_EXP + wg * 4096 + i * 2048, p[i], pack_bf16(acc[8 * i + 2], acc[8 * i + 3]),
             pack_bf16(acc[8 * i + 4], acc[8 * i + 5]), pack_bf16(acc[8 * i + 6], acc[8 * i + 7]));
    }
    if (decltype(retire)::value)
      asm volatile("{\n.reg .pred p, q;\nsetp.ne.u32 p, %2, 0;\nsetp.ne.u32 q, %2, 1;\n@p ld.shared.b32 %0, [%3];\n@q ld.shared.b32 %1, [%3 + 4];\n"
                   "setp.ne.u32 p, %0, %1;\n@p exit;\n}" : "+r"(p[0]), "+r"(p[1]) : "r"(always), "r"(sb + SC_DEAD) : "memory");
  };
  uint32_t o[8];
  auto import = [&]() { lds128(t16 + SM_EXP + (wg ^ 1) * 4096, o); lds128(t16 + SM_EXP + (wg ^ 1) * 4096 + 2048, o + 4); };
  auto finish_from = [&](int seg, const float* d) {
    const uint32_t a = fin_a + (seg & 3) * SEGB;
#pragma unroll
    for (int i = 0; i < 8; i++) o[i] = add_bf16(pack_bf16(d[2 * i], d[2 * i + 1]), o[i]);
    stsm4(a, o[0], o[1], o[2], o[3]);
    stsm4(a + fin2, o[4], o[5], o[6], o[7]);
  };
  auto finish = [&](int seg) { WG_WAIT(0); finish_from(seg, acc); };
  auto send_v = [&](int seg, int dst) {
    fence_async();
    if (seg < NSEG - 1 && !(XP & 2) && elect_one())
      bulk_s2s(mapa(sb + SM_VC + (seg & 1) * 8192, dst), sb + SM_BLK + (seg & 3) * SEGB, 8192, mapa(sb + MB_VX + (seg & 1) * 8, dst));
    __syncwarp();
  };
  auto wait_v = [&](int seg) {
    if (seg < NSEG - 1 && !(XP & 2)) {
      mbar_wait(sb + MB_VX + (seg & 1) * 8, (seg >> 1) & 1);
      if (elect_one()) mbar_expect(sb + MB_VX + (seg & 1) * 8, 8192);
      __syncwarp();
    }
  };
  auto export_seg = [&](int seg) { if (!(XP & (4 | 8192)) && elect_one()) seg_store(seg, sb); __syncwarp(); };
  auto publish = [&](int seg) { if (!(XP & (4 | 16384)) && elect_one()) seg_publish(seg, sb); __syncwarp(); };
  do_export(BoolC<false>(), 0);
  QSTAMP(9);
  SCHED_FENCE(11);
  xproj<0, 0, 18>(acc, wa, xd0);
  bar_sync(3, 256);
  QSTAMP(10);
  cluster_wait();
  QSTAMP(11);
  mbar_wait(sb + MB_X + 8, 0);
  QSTAMP(12);
  import();
  finish(0);
  SCHED_FENCE(12);
  uint64_t dA = xd0 + (XT >> 4);
  xproj<1, 0, 18>(acc, wa, dA);
  bar_sync(3, 256);
  if (!qk && wg == 0 && w < 2) send_v(0, w);
  if (!(EXV & 1) && wg == 0 && w == 3) export_seg(0);
  QSTAMP(13);
  if (qk && wg == 0 && w == 0) wait_v(0);
  QSTAMP(14);
  bar_arrive(13, 384);
  if (!qk) {
    do_export(BoolC<false>(), 0);
    SCHED_FENCE(15);
    xproj<0, 0, 18>(acc, wa, dA);
    if (threadIdx.x == 0 && !(XP & 8)) { mbar_expect(sb + MB_X, XT); tma_load3(sb + SM_X, &tm.x, 96, sb + MB_X); }
    bar_sync(3, 256);
    mbar_wait(sb + MB_X + 16, 0);
    import();
    finish(1);
    SCHED_FENCE(16);
    dA += XT >> 4;
    xproj<1, 0, 18>(acc, wa, dA);
    if (!(EXV & 2)) bar_sync(3, 256);
    if (!(EXV & 2) && wg == 0 && w < VW2) send_v(1, w);
  }
  QSTAMP(15);
  WG_WAIT(0);
  bar_sync(0, 384);
  if (!(EXV & 1) && wg == 0 && w == 3) publish(0);
  QSTAMP(16);
  const int ro = __shfl_sync(0xffffffffu, near_half(sb) ^ wg, 0);
  STAMP(5);
  const uint32_t always = __shfl_sync(0xffffffffu, lds32(sb + SC_DEAD + 12), 0);
  const int ah = qk ? 1 : 2;
  int b2 = qk ? 2 : 0;
  int s = 0;
  uint32_t hint_lo = (uint32_t)(uint64_t)tm.red + HINT_OFF + blockIdx.x + (lane & 1) * 4096 + (lane >> 1) * 16384;
  PIN(hint_lo);
  auto post_hint = [&]() {
    asm volatile("{\n.reg .pred p;\n.reg .b64 a;\n.reg .u32 t;\nsetp.lt.u32 p, %0, %1;\nmov.b64 a, {%2, %3};\nmov.u32 t, %%globaltimer_lo;\n"
                 "bfe.u32 t, t, 5, 6;\nor.b32 t, t, %4;\n@p st.relaxed.gpu.global.u8 [a], t;\n}"
                 :: "r"(t16), "r"(sb + 160), "r"(hint_lo + RED_SLOT(s)), "r"((uint32_t)((uint64_t)tm.red >> 32)), "r"(((s >> 2) + 1) << 6) : "memory");
  };
  auto memproj = [&](auto second, int id, uint32_t dep, float u0, float u1, float* r) {
    constexpr bool R1 = decltype(second)::value;
    uint32_t b[NUP][4], b0[4];
    if (R1) asm volatile("{\n.reg .pred p;\nsetp.eq.u32 p, %0, %1;\n@p exit;\n}" :: "r"(dep), "r"(id) : "memory");
    bar_sync(R1 ? 2 : 1, 256);
    PROF(0);
    ldsm4t(b0, mem_a);
#pragma unroll
    for (int q = 0; q < NUP; q++) {
      if (R1 && q == 2) {
        bar_sync(11, 256);
        SCHED_FENCE(id + 1);
      }
      ldsm4t(b[q], mem_a + MEM_BLK(q + 1));
    }
    mma16816z(&acc[0], wa[0][0], b0[0], b0[1]);
    mma16816z(&acc[4], wa[1][0], b0[0], b0[1]);
    mma16816z(&acc[8], wa[0][1], b0[2], b0[3]);
    mma16816z(&acc[12], wa[1][1], b0[2], b0[3]);
#pragma unroll
    for (int q = 1; q < 9; q++) {
      uint32_t* const c = b[(q - 1) % NUP];
      mma16816(&acc[0], wa[0][2 * q], c[0], c[1]);
      mma16816(&acc[4], wa[1][2 * q], c[0], c[1]);
      mma16816(&acc[8], wa[0][2 * q + 1], c[2], c[3]);
      mma16816(&acc[12], wa[1][2 * q + 1], c[2], c[3]);
      if (R1 && q + NUP == B3Q) bar_sync(3, 256);
      if (q + NUP < 9) ldsm4t_in(c, mem_a + MEM_BLK(q + NUP), always);
      else if (R1 && q + NUP < 11) lds128_in(c, t16 + SM_PART + (10 - q - NUP) * 2048, always);
      else if (!R1 && GATE && q == GATE) { bar_arrive(11, 256); lds128_in(c, sb + SC_DEAD, always); u0 = u1 = __uint_as_float(c[3]); }
    }
#pragma unroll
    for (int i = 0; i < 8; i++) {
      const float u = i < 4 ? u0 : u1;
      r[i] = R1 ? fmaf(acc[8 + i], u, (acc[i] + __uint_as_float(b[(8 + i / 4) % NUP][i & 3])) * u) : (GATE ? fmaf(acc[i], u, acc[8 + i]) : acc[i] + acc[8 + i]);
    }
  };
  if (ro == 0) {
#pragma unroll 1
    while (true) {
      do_export(BoolC<true>(), always);
      PROFP(3);
      if (s == 8) STAMP(6);
      float r[8];
      memproj(BoolC<false>(), 30, 0, 0.f, 0.f, r);
      sts128(t16 + SM_PART, __float_as_uint(r[0]), __float_as_uint(r[1]), __float_as_uint(r[2]), __float_as_uint(r[3]));
      sts128(t16 + SM_PART + 2048, __float_as_uint(r[4]), __float_as_uint(r[5]), __float_as_uint(r[6]), __float_as_uint(r[7]));
      bar_arrive(3, 256);
      PROF(1);
      bar_sync(9, 256);
      if (!(WE & 1) && s == NSEG - 1) break;
      post_hint();
      if (!(EXV & 1) && w == 3 && s) publish(s);
      if ((WE & 1) && s == NSEG - 1) break;
      if (w == 1) {
        uint32_t m[8];
        lds128(t16 + SM_MAX - 512, m); lds128(t16 + SM_MAX, m + 4);
        const int em = (wexp(amax4(amax4(*(const __half2*)&m[0], m), m + 4)) >> 3) + (int)(lds32(sb + SC_UNSC + (s & 1) * 8) >> 23) - 15;
        const int ex = max(s ? em : 0, (int)lds32(sb + SC_XMAX + 4 * s)) - 127 + (int)lds32(sb + SC_EXPW);
        sts32(sb + SC_UNSC + (~s & 1) * 8, (127 + min(max(ex, -120), 120)) << 23);
        __syncwarp();
        if (elect_one()) mbar_arrive(sb + MB_S);
      }
      SCHED_FENCE(9);
      bar_sync(5, qk ? N5 : 256);
      PROF(2);
      import();
      xproj<0, 0, NII>(acc, wa, dA);
      if (NII < 18) {
        if (qk) bar_sync(7, 384);
        xproj<0, NII, 18>(acc, wa, dA);
        if (!qk) bar_sync(7, 384);
      } else {
        if (F10) WG_WAIT(0);
        bar_sync(10, 256);
        if (F10) SCHED_FENCE(17);
      }
      dA += (int64_t)(b2 ? XT >> 4 : -(XT >> 3));
      finish(s + ah);
      if (((EXV & 1) || w != 3) && ((EXV & 2) || qk || w >= VW2)) bar_arrive(13, 384);
      PROF(6);
      SCHED_FENCE(14);
      if (NOB & 2) bar_arrive(14, 256);
      bar_sync(12, 256);
      PROF(7);
      xproj<1, 0, 18, true>(acc, wa, dA);
      if (!(NOB & 2)) bar_arrive(14, 256);
      b2 = b2 == 2 ? 0 : b2 + 1;
      s++;
      if ((!(EXV & 1) && w == 3) || (!(EXV & 2) && !qk && w < VW2)) {
        bar_sync(13, 384);
        if (!(EXV & 1) && w == 3) export_seg(s); else send_v(s + 1, w);
      }
      PROFP(8);
    }
    if (!qk) bar_arrive(5, 256);
    if (!(WE & 1) && w == 3) publish(NSEG - 1);
  } else {
    uint32_t km[4];
    auto send_km = [&]() {
      if (XP & (4 | 4096)) return;
      const uint32_t t = (km[0] & ~1u) | lds32(sb + SC_EPO + 4), u = (s * NH + head_id()) * 4096;
      if (qk)
        asm volatile("{\n.reg .u32 o;\n.reg .u64 a;\nshr.u32 o, %0, 1;\nadd.u32 o, o, %1;\nmad.wide.u32 a, o, 1, %2;\nst.relaxed.gpu.global.v2.b32 [a], {%3,%4};\n}"
                     :: "r"(t16), "r"(u + rank * 1024 - (sb >> 1)), "l"(g_km), "r"(t), "r"(km[1]) : "memory");
      else
        asm volatile("{\n.reg .u32 o;\n.reg .u64 a;\nadd.u32 o, %0, %1;\nmad.wide.u32 a, o, 1, %2;\nst.relaxed.gpu.global.v4.b32 [a], {%3,%4,%5,%6};\n}"
                     :: "r"(t16), "r"(u + 2048 - sb), "l"(g_km), "r"(t), "r"(km[1]), "r"(km[2]), "r"(km[3]) : "memory");
    };
#pragma unroll 1
    while (true) {
      do_export(BoolC<true>(), always);
      if ((EXV & 1) && w == 1) export_seg(s);
      if ((EXV & 2) && !qk && w == 2) send_v(s + 1, 0);
      PROFP(3);
      if (s == 8) STAMP(6);
      const uint32_t tl = ((t16 >> 8) ^ wg) & 1, am = (t16 & ~256u) - w * 256;
      const float un = __uint_as_float(lds32(sb + SC_UNSC + (s & 1) * 8));
      float r[8];
      if (qk) {
        uint32_t a0 = am + (tl ? SM_QM : SM_BLK + 8192 + (s & 3) * SEGB);
        float u0 = wg ? un * (SM_SCALE * LOG2E) : un, u1 = wg ? un : un * (SM_SCALE * LOG2E);
        PIN(a0); PIN(u0); PIN(u1);
        memproj(BoolC<true>(), 32, a0, u0, u1, r);
        const uint32_t p0 = pack_bf16(r[0], r[1]), p1 = pack_bf16(r[2], r[3]), p2 = pack_bf16(r[4], r[5]), p3 = pack_bf16(r[6], r[7]);
        stsm4(a0, p0, p1, p2, p3);
        bar_arrive(4, 256);
        km[0] = wg ? p2 : p0; km[1] = wg ? p3 : p1;
      } else {
        const uint32_t d0 = s < NSEG - 1 ? 0 : 2, d1 = s < NSEG - 1 ? 1 : 2;
        uint32_t r0 = mapa(t16 + SM_VM, d0), r1 = mapa(t16 + SM_VM, d1);
        PIN(r0); PIN(r1);
        memproj(BoolC<true>(), 34, r0 | r1, un, un, r);
        const uint32_t p0 = pack_bf16(r[0], r[1]), p1 = pack_bf16(r[2], r[3]), p2 = pack_bf16(r[4], r[5]), p3 = pack_bf16(r[6], r[7]);
        const uint32_t v0 = wg ? p2 : p0, v1 = wg ? p3 : p1, v2 = wg ? p0 : p2, v3 = wg ? p1 : p3;
        st_async4(r0, v0, v1, v2, v3, mapa(sb + MB_S, d0));
        st_async4(r1, v0, v1, v2, v3, mapa(sb + MB_S, d1));
        bar_arrive(5, 256);
        sts128(t16 + SM_VM, v0, v1, v2, v3);
        __syncwarp();
        if (elect_one()) mbar_arrive(sb + MB_S);
        km[0] = v0; km[1] = v1; km[2] = v2; km[3] = v3;
      }
      if (!(WE & 2) && s == NSEG - 1) break;
      PROF(1);
      auto rearm = [&]() { mbar_wait(sb + MB_S, s & 1); if (elect_one()) mbar_expect(sb + MB_S, qk ? 640 + 2048 : 1280); __syncwarp(); };
      if ((WE & 2) && s == NSEG - 1 && w != 1) {
      } else if (w == 1) {
        if ((t16 & 384) == 0) stg_relaxed(tm.red + (RED_SLOT(s + 2) + RED_LINE(blockIdx.x)) + (t16 & 112), 0, 0, 0, 0);
        if (EXV & 1) publish(s);
      } else if (w == 0) {
        const int tn = s + ah + 1;
        if (RFW) mbar_wait(sb + MB_S, s & 1);
        if (tn + 1 < NSEG && !(XP & 8) && elect_one()) {
          const int b0 = b2 == 2 ? 0 : b2 + 1;
          mbar_expect(sb + MB_X + 8 * b0, XT);
          tma_load3(sb + SM_X + b0 * XT, &tm.x, (tn + 1) * 32, sb + MB_X + 8 * b0);
        }
        if (tn < NSEG && (!(XP & 8) || tn < 3)) mbar_wait(sb + MB_X + 8 * b2, (tn / 3) & 1);
      } else if (w == 2) {
        if (!qk) { if (VW2 < 1) send_v(s + 1, 0); if (VW2 < 2) send_v(s + 1, 1); }
      } else if (qk || !NIC) {
        rearm();
      }
      __syncwarp();
      send_km();
      if ((WE & 2) && s == NSEG - 1) break;
      import();
      PROF(4);
      SCHED_FENCE(10);
      if (NIC) {
        if (qk) bar_sync(7, NII < 18 ? 384 : 256);
        xproj<0, 0, NIC>(acc, wa, dA);
        if (!qk) { if (w == 3) rearm(); bar_sync(7, NII < 18 ? 384 : 256); }
      } else {
        bar_sync(7, NII < 18 ? 384 : 256);
      }
      if (NOB & 1) bar_arrive(12, 256);
      xproj<0, NIC, 18>(acc, wa, dA);
      if (!(NOB & 1)) bar_arrive(12, 256);
      dA += (int64_t)(b2 ? XT >> 4 : -(XT >> 3));
      finish(s + ah);
      if (qk && w == 0) wait_v(s + 1);
      bar_arrive(13, 384);
      PROF(6);
      SCHED_FENCE(13);
      bar_sync(14, 256);
      PROF(7);
      xproj<1, 0, 18>(acc, wa, dA);
      b2 = b2 == 2 ? 0 : b2 + 1;
      s++;
      PROFP(8);
    }
    if (!(WE & 2)) {
      send_km();
      PIN(t16);
      if (t16 - sb < 128) stg_relaxed(tm.red + (RED_SLOT(NSEG + 1) + RED_LINE(head_id() * 3 + rank)) + (t16 & 112), 0, 0, 0, 0);
    }
  }
  bar_arrive(0, 384);
  STAMP(3);
  cluster_sync();
  STAMP(4);
}

DI void attn_role(const uint32_t sb, unsigned char* smem_raw, const RMaps& tm, const uint32_t RANK, const bf16* __restrict__ x, const bf16* __restrict__ mem0,
                  const int w, const int lane) {
  const int t2 = w * 32 + lane;
  uint32_t wo[8][4], w1[8][4];
  const uint32_t wo_lane = sb + ((lane & 7) + ((lane >> 4) << 3)) * 128 + (((w + 4 * ((lane >> 3) & 1)) ^ (lane & 7)) << 4);
  unsigned char* const g_red = tm.red;
  {
    const uint32_t tag = *(volatile unsigned*)&g_epoch + 1;
    QSTAMP(0);
    bar_sync(0, 160);
    QSTAMP(1);
    cluster_arrive();
    __half2 hx = __float2half2_rn(0.f);
    if (blockIdx.x < NSEG) {
      mbar_wait(sb + MB_XS, 0);
#pragma unroll
      for (int i = 0; i < 18; i++) { uint32_t v[4]; lds128(sb + SM_STAGE + 2 * 49152 + t2 * 16 + i * 2048, v); hx = amax4(hx, v); }
      fence_async();
      bar_sync(6, 128);
      if (t2 == 0) load_w(sb, tm, RANK, 2);
      __syncwarp();
    }
    if (t2 == 0) { sts64(sb + SC_EPO, (tag - 1) * NSEG + 1, tag & 1); sts32(sb + SC_UNSC, __float_as_uint(1.f)); sts128(sb + SC_DEAD, 0, 0, 0, 0x3f800000u); sts64(sb + SC_FPAR, 0, 0); sts128(sb + SC_ONES, 0x3f803f80u, 0x3f803f80u, 0x3f803f80u, 0x3f803f80u); }
    WSTAMP(27);
    uint32_t q[8] = {0, 0, 0, 0, 0, 0, 0, 0};
    QSTAMP(2);
    mbar_wait(sb + MB_WO3, 0);
    QSTAMP(3);
    uint32_t mv[5][4];
#pragma unroll
    for (int i = 0; i < 5; i++) {
      ldsm4(mv[i], sb + SM_M0 + (lane & 7) * (DM * 2) + min(w + 4 * i, 17) * 64 + (lane >> 3) * 16);
      if (blockIdx.x == 0) hx = amax4(hx, mv[i]);
    }
    sts32(sb + SC_SS + 4 * (12 + w), wexp(hx));
#pragma unroll
    for (int k = 0; k < 8; k++) {
      ldsm4t(wo[k], wo_lane + SM_WO3 + k * 2048); ldsm4t(w1[k], wo_lane + SM_WOST + k * 2048);
#pragma unroll
      for (int i = 0; i < 4; i++) { sq_acc(q[i], wo[k][i]); sq_acc(q[i], w1[k][i]); }
    }
    bar_sync(6, 128);
#pragma unroll
    for (int k = 0; k < 8; k++) sts128(sb + SM_WO3 + t2 * 16 + k * 2048, wo[k][0], wo[k][1], wo[k][2], wo[k][3]);
#pragma unroll
    for (int i = 0; i < 5; i++) {
      const int c = (w + 4 * i) * 32;
      if (c < DM) stsm4t(sb + SM_MEM + (c + c / 192 * 64 + lane) * 16, mv[i][0], mv[i][1], mv[i][2], mv[i][3]);
    }
    bar_arrive(1, 256); bar_arrive(2, 256); bar_arrive(9, 256);
    QSTAMP(4);
    mbar_wait(sb + MB_WO, 0);
    QSTAMP(5);
#pragma unroll
    for (int k = 0; k < 8; k++) ldsm4t(wo[k], wo_lane + SM_X + XT + k * 2048);
    fence_async();
    bar_sync(6, 128);
    if (t2 == 32) tma_load3(sb + SM_X + XT, &tm.x, 32, sb + MB_X + 8);
    __syncwarp();
#pragma unroll
    for (int k = 0; k < 8; k++)
#pragma unroll
      for (int i = 0; i < 4; i++) sq_acc(q[4 + i], wo[k][i]);
    float ss = 0.f;
#pragma unroll
    for (int i = 0; i < 8; i++) ss += bf_lo(q[i]) + bf_hi(q[i]);
    ss = warp_sum(ss);
    if (lane == 0) sts32(sb + SC_SS + 4 * (8 + w), __float_as_uint(ss));
    QSTAMP(6);
    bar_sync(11, 384);
    QSTAMP(7);
    if (t2 == 0) {
      float a[16];
#pragma unroll
      for (int i = 0; i < 4; i++) lds128f(sb + SC_SS + 16 * i, &a[4 * i]);
      stg_relaxed(&g_stats[blockIdx.x * 2], __float_as_uint(((a[0] + a[1]) + (a[2] + a[3])) + ((a[4] + a[5]) + (a[6] + a[7]))),
                  __float_as_uint((a[8] + a[9]) + (a[10] + a[11])),
                  max(max(__float_as_uint(a[12]), __float_as_uint(a[13])), max(__float_as_uint(a[14]), __float_as_uint(a[15]))), tag);
    }
    __syncwarp();
    WSTAMP(24);
    QSTAMP(8);
    cluster_wait();
    QSTAMP(9);
    if (w == 0) {
      uint4 v[3];
      int n = 0;
      while (true) {
#pragma unroll
        for (int i = 0; i < 3; i++) v[i] = ldg_relaxed(&g_stats[(i * 32 + lane) * 2]);
        if (__all_sync(0xffffffffu, v[0].w == tag && v[1].w == tag && v[2].w == tag) || ++n > SPIN_LIMIT) break;
        __nanosleep(100);
      }
      WSTAMP(25);
      QSTAMP(10);
      const float sv = warp_sum(__uint_as_float(v[0].x) + __uint_as_float(v[1].x) + __uint_as_float(v[2].x));
      const float so = warp_sum(__uint_as_float(v[0].y) + __uint_as_float(v[1].y) + __uint_as_float(v[2].y));
      const int expW = ((int)(__float_as_uint(sv) >> 23) + (int)(__float_as_uint(so) >> 23) - 254 + 2 + 10 + 1) >> 1;
      sts32(sb + SC_XMAX + 4 * lane, v[0].z); sts32(sb + SC_XMAX + 128 + 4 * lane, v[1].z);
      sts32(sb + SC_EXPW, expW + 1 - 15);
      if (blockIdx.x == 0 && lane == 0) *(volatile unsigned*)&g_epoch = tag;
      sts32(sb + SC_FPAR + 4, 1);
    } else if (w < 3) {
      const uint32_t u = blockIdx.x >> 4;
      unsigned char* const z = g_red + 98304 + (blockIdx.x & 15) * 128 + (u & 1) * 2048 + (u & 6) * 4096 + (((u >> 1) ^ w) & 1) * 4096 + lane * 4;
      stg_relaxed32(z, 0);
      uint32_t best = 0xffffffffu;
#pragma unroll 1
      for (int i = 0; i < 64; i++) {
        uint32_t dt;
        asm volatile("{\n.reg .pred p;\n.reg .u32 c, v;\nmov.u32 c, %%clock;\n"
                     "atom.relaxed.gpu.global.exch.b32 v, [%1], 0;\nsetp.eq.u32 p, v, 0;\nmov.u32 %0, 0;\n@p mov.u32 %0, %%clock;\nsub.u32 %0, %0, c;\n}"
                     : "=r"(dt) : "l"(z) : "memory");
        best = min(best, dt);
        if (lds32v(sb + SC_FPAR + 4) && i >= NPROBE - 1) break;
      }
      sts32(sb + SC_LAT + (w - 1) * 4, best);
    }
    QSTAMP(11);
    bar_sync(13, 384);
    bar_arrive(0, 384);
    QSTAMP(12);
    WSTAMP(26);
  }

  const uint32_t nh = __shfl_sync(0xffffffffu, near_half(sb), 0);
  uint32_t l16 = sb + lane * 16;
  PIN(l16);
#define LV ((l16 >> 4) & 31)
#define fence_reg l16
  const uint32_t red_lo = (uint32_t)(uint64_t)g_red, red_hi = (uint32_t)((uint64_t)g_red >> 32);
  uint32_t lp;
  auto slot = [&](int s, uint32_t c, uint32_t ofs) {
    const uint32_t lo = lp | (red_lo + ((w >> 1) * 4 + (w & 1) * 2 + ((w ^ c) & 1)) * 4096 + RED_SLOT(s) + ofs);
    uint64_t a; asm("mov.b64 %0, {%1, %2};" : "=l"(a) : "r"(lo), "r"(red_hi));
    return (unsigned char*)a;
  };
  const uint32_t always = __shfl_sync(0xffffffffu, lds32(sb + SC_DEAD + 12), 0);
  const int mode0 = RANK < 2 ? w : w | 4;
  auto hint_addr = [&](int s) { return min(LV, 23u) * 4 + (red_lo + HINT_OFF + nh * 4096 + w * 16384 + RED_SLOT(s)); };
  auto load_hints = [&](uint32_t lo) {
    uint64_t a; asm("mov.b64 %0, {%1, %2};" : "=l"(a) : "r"(lo), "r"(red_hi));
    return ldg_relaxed32((const void*)a);
  };
  int s = 0;
  bool bad = false;
#pragma unroll 1
  while (true) {
    const uint32_t par = s & 1;
    uint32_t vx[4][4], hints;
    auto load_vx = [&]() {
      const uint32_t va = l16 + (RANK < 2 ? SM_VC + par * 8192 : SM_BLK + (s & 3) * SEGB) + w * 1024 + ((LV >> 3) & 1) * 384 - (LV >> 4) * 128;
#pragma unroll
      for (int i = 0; i < 4; i++) ldsm4(vx[i], va + (i & 1) * 4096 + (i >> 1) * 256);
    };
    auto retire = [&](uint32_t x) {
      asm volatile("{\n.reg .pred p;\nsetp.eq.u32 p, %0, 0;\n@p exit;\n}" :: "r"(vx[0][0] | vx[1][0] | vx[2][0] | vx[3][0] | x) : "memory");
    };
    auto scores = [&](auto memkeys, auto first, float* sc) {
      constexpr bool MK = decltype(memkeys)::value, FIRST = decltype(first)::value;
      uint32_t kb[4][4], qb[2][4];
      const uint32_t m = LV >> 3;
      uint32_t kaddr = l16 + SM_BLK + 4096 + (s & 3) * SEGB + w * 2048 + (m & 1) * (MK ? 128 : 896) - (m >> 1) * 128;
      if (MK) { PIN(kaddr); }
      else {
#pragma unroll
        for (int k = 0; k < 4; k++) ldsm4t(kb[k], kaddr + k * 256);
      }
      if (FIRST) { load_vx(); retire(MK ? kaddr : kb[0][0] | kb[1][0] | kb[2][0] | kb[3][0] | l16); bar_sync(4, 256); PROF(4); }
      ldsm4t(qb[0], l16 + SM_QM);
      if (MK) ldsm4t(kb[0], kaddr);
      ldsm4t(qb[1], l16 + SM_QM + 512);
      if (MK) ldsm4t(kb[2], kaddr + 512);
      float c[4][4];
      mma16816z(c[0], kb[0], qb[0][0], qb[0][1]); mma16816z(c[1], kb[MK ? 0 : 1], qb[0][2], qb[0][3]);
      mma16816z(c[2], kb[2], qb[1][0], qb[1][1]); mma16816z(c[3], kb[MK ? 2 : 3], qb[1][2], qb[1][3]);
      if (FIRST && B5POS == 0) bar_arrive(5, N5);
#pragma unroll
      for (int i = 0; i < (MK ? 2 : 4); i++) sc[i] = ((c[0][i] + c[1][MK ? i + 2 : i]) + c[2][i]) + c[3][MK ? i + 2 : i];
    };
    auto send = [&](auto memkeys) {
      constexpr bool MK = decltype(memkeys)::value;
      constexpr int N = MK ? 1 : 2;
      const uint32_t sa = sb + LV * 4 + SM_E + (MK ? 1024 + RANK * 128 : RANK * 512 + w * 256);
      uint32_t ra[N][2], mb[N][2];
#pragma unroll
      for (int i = 0; i < N; i++)
#pragma unroll
        for (int j = 0; j < 2; j++) {
          ra[i][j] = mapa(sa + i * 128, j ? 2 : RANK ^ 1); mb[i][j] = mapa(sb + MB_S, j ? 2 : RANK ^ 1);
          PIN(ra[i][j]);
        }
      float sc[4];
      scores(memkeys, BoolC<true>(), sc);
      uint32_t e[N];
#pragma unroll
      for (int i = 0; i < N; i++) {
        e[i] = pack_bf16(ex2(sc[2 * i]), ex2(sc[2 * i + 1]));
        if (!(fmaxf(fabsf(sc[2 * i]), fabsf(sc[2 * i + 1])) <= E_LIM)) e[i] = 0x7fff7fffu;
        st_async1(ra[i][0], e[i], mb[i][0]);
        st_async1(ra[i][1], e[i], mb[i][1]);
      }
#pragma unroll
      for (int i = 0; i < N; i++) sts32(sa + i * 128, e[i]);
      __syncwarp();
      if (l16 == sb) mbar_arrive(sb + MB_S);
      PROF(5);
    };
    const int mode = bad ? 8 : mode0;
    if (mode < 2) {
      send(BoolC<false>());
    } else if (mode == 2) {
      send(BoolC<true>());
    } else if (mode == 8) {
      load_vx();
      retire(l16);
      const uint32_t fp = lds32(sb + SC_FPAR);
      bar_sync(6, 128);
      if (w == 0 && l16 == sb) { sts32(sb + SC_FPAR, fp ^ 1); mbar_expect(sb + MB_F, 3072); }
      if (RANK < 2 && w < 3) {
        float sc[4] = {0.f, 0.f, 0.f, 0.f};
        if (w < 2) scores(BoolC<false>(), BoolC<false>(), sc); else scores(BoolC<true>(), BoolC<false>(), sc);
#pragma unroll 1
        for (int r = 0; r < 3; r++)
          st_async4(mapa(l16 + SM_FB + RANK * 1536 + w * 512, r), __float_as_uint(sc[0]), __float_as_uint(sc[1]), __float_as_uint(sc[2]), __float_as_uint(sc[3]), mapa(sb + MB_F, r));
      }
      mbar_wait(sb + MB_F, fp);
      float a[12];
#pragma unroll
      for (int j = 0; j < 3; j++) {
        float b[4];
        lds128f(l16 + SM_FB + j * 512, a + 4 * j); lds128f(l16 + SM_FB + 1536 + j * 512, b);
#pragma unroll
        for (int i = 0; i < 4; i++) a[4 * j + i] += b[i];
      }
      float m0 = fmaxf(fmaxf(fmaxf(a[0], a[2]), fmaxf(a[4], a[6])), a[8]), m1 = fmaxf(fmaxf(fmaxf(a[1], a[3]), fmaxf(a[5], a[7])), a[9]);
#pragma unroll
      for (int o = 4; o < 32; o <<= 1) { m0 = fmaxf(m0, __shfl_xor_sync(0xffffffffu, m0, o)); m1 = fmaxf(m1, __shfl_xor_sync(0xffffffffu, m1, o)); }
#pragma unroll
      for (int i = 0; i < 5; i++) {
        const uint32_t ea = sb + SM_E + LV * 4 + (i < 4 ? i * 128 : 1024);
        sts32(ea, pack_bf16(ex2(a[2 * i] - m0), ex2(a[2 * i + 1] - m1)));
        sts32(ea + (i < 4 ? 512 : 128), 0x3f803f80u);
      }
      __syncwarp();
    } else {
      load_vx();
      if (mode == 3) bar_arrive(4, 256);
      retire(l16 + 1);
    }
    {
      uint32_t wa[4], wb[4], oc[4];
      constexpr int WS = 2048;
      const uint32_t w3a = l16 + SM_WO3 + w * 512;
      lds128(w3a + KP(0) * WS, wa); lds128(w3a + KP(1) * WS, wb); lds128(sb + SC_ONES, oc);
      if (B5POS == 1 && mode < 3) bar_arrive(5, N5);
      uint32_t e[10], p[5], vm[4], ob[4];
      float o0[4], o1[4], f[3][2][4], rs[4];
      reserve2(vm); reserve2(vm + 2); reserve2(e + 8);
      hints = hint_addr(s);
      PIN(hints);
      if (CLR & 2) asm volatile("{\n.reg .pred p;\nsetp.eq.u32 p, %0, 0;\n@p exit;\n}" :: "r"(wa[0] | wb[0] | oc[0] | hints) : "memory");
      mbar_wait(sb + MB_S, par);
      PROF(6);
      ldsm4t(e, l16 + SM_E); ldsm2t_in(e + 8, l16 + SM_E + 1024, always); ldsm4t(e + 4, l16 + SM_E + 512);
      lds128_in(vm, l16 + w * 512 + SM_VM, always);
      const float scl = __uint_as_float(lds32(sb + SC_UNSC + 8 - par * 8));
      hints = load_hints(hints);
      if (GF & 1) SCHED_FENCE(4);
#pragma unroll
      for (int i = 0; i < 4; i++) p[i] = mul_bf16(e[i], e[4 + i]);
      p[4] = mul_bf16(e[8], e[9]);
      if (MO & 4) {
        float a0[4], a1[4];
        mma16816z(o0, vx[0], p[0], p[1]); mma16816z(o1, vx[1], p[0], p[1]);
        mma16816z(a0, vx[2], p[2], p[3]); lds128_in(vx[2], w3a + KP(2) * WS, always);
        mma16816z(a1, vx[3], p[2], p[3]); lds128_in(vx[3], w3a + KP(3) * WS, always);
        mma1688(o0, vm[0], vm[1], p[4]); mma1688(o1, vm[2], vm[3], p[4]);
        mma16816z(rs, oc, p[0], p[1]); mma16816(rs, oc, p[2], p[3]); mma1688(rs, oc[0], oc[1], p[4]);
#pragma unroll
        for (int i = 0; i < 4; i++) { o0[i] += a0[i]; o1[i] += a1[i]; }
      } else {
      mma16816z(o0, vx[0], p[0], p[1]); mma16816z(o1, vx[1], p[0], p[1]); mma16816z(rs, oc, p[0], p[1]);
      mma16816(o0, vx[2], p[2], p[3]); lds128_in(vx[2], w3a + KP(2) * WS, always);
      mma16816(o1, vx[3], p[2], p[3]); lds128_in(vx[3], w3a + KP(3) * WS, always);
      mma16816(rs, oc, p[2], p[3]);
      mma1688(o0, vm[0], vm[1], p[4]); mma1688(o1, vm[2], vm[3], p[4]); mma1688(rs, oc[0], oc[1], p[4]);
      }
      stsm4(l16 + w * 512 + SM_OB, pack_bf16(o0[0], o0[1]), pack_bf16(o0[2], o0[3]), pack_bf16(o1[0], o1[1]), pack_bf16(o1[2], o1[3]));
      bar_sync(6, 128);
      PROF(7);
      ldsm4t_in(oc, l16 + SM_OB, always);
      bad = __any_sync(0xffffffffu, !(rs[0] + rs[1] > 0.f) && !bad);
      rs[0] *= scl; rs[1] *= scl;
      asm volatile("{\n.reg .pred p;\nsetp.ne.u32 p, %1, 0;\n@p rcp.approx.ftz.f32 %0, %0;\n}" : "+f"(rs[0]) : "r"(always));
      asm volatile("{\n.reg .pred p;\nsetp.ne.u32 p, %1, 1;\n@p rcp.approx.ftz.f32 %0, %0;\n}" : "+f"(rs[1]) : "r"(always));
      asm volatile("lop3.b32 %0, %1, %2, %3, 0xfe;" : "=r"(lp) : "r"((l16 & 128) * 2), "r"((l16 & 256) * 4), "r"(l16 & 112));
      if (bad) continue;
      ldsm4t(ob, l16 + SM_OB + 512);
      mma16816z(f[2][0], wa, oc[0], oc[1]); mma16816z(f[2][1], wb, oc[2], oc[3]);
      mma16816z(f[0][0], wo[0], oc[0], oc[1]); mma16816z(f[0][1], wo[4], oc[2], oc[3]);
      mma16816z(f[1][0], w1[0], oc[0], oc[1]); mma16816z(f[1][1], w1[4], oc[2], oc[3]);
      ldsm4t_in(oc, l16 + SM_OB + 1024, always);
      mma16816(f[2][0], vx[2], ob[0], ob[1]); lds128_in(vx[2], w3a + KP(4) * WS, always);
      mma16816(f[2][1], vx[3], ob[2], ob[3]); lds128_in(vx[3], w3a + KP(5) * WS, always);
      mma16816(f[0][0], wo[1], ob[0], ob[1]); mma16816(f[0][1], wo[5], ob[2], ob[3]);
      mma16816(f[1][0], w1[1], ob[0], ob[1]); mma16816(f[1][1], w1[5], ob[2], ob[3]);
      ldsm4t_in(ob, l16 + SM_OB + 1536, always);
      mma16816(f[0][0], wo[2], oc[0], oc[1]); mma16816(f[0][1], wo[6], oc[2], oc[3]);
      mma16816(f[2][0], vx[2], oc[0], oc[1]); lds128_in(vx[2], w3a + KP(6) * WS, always);
      mma16816(f[2][1], vx[3], oc[2], oc[3]); lds128_in(vx[3], w3a + KP(7) * WS, always);
      mma16816(f[1][0], w1[2], oc[0], oc[1]); mma16816(f[1][1], w1[6], oc[2], oc[3]);
      mma16816(f[0][0], wo[3], ob[0], ob[1]); mma16816(f[0][1], wo[7], ob[2], ob[3]);
      mma16816(f[1][0], w1[3], ob[0], ob[1]); mma16816(f[1][1], w1[7], ob[2], ob[3]);
      mma16816(f[2][0], vx[2], ob[0], ob[1]); mma16816(f[2][1], vx[3], ob[2], ob[3]);
      bar_arrive(7, NII < 18 ? 384 : 256);
      lds128_in(ob, sb + SC_DEAD, always);
      uint32_t h[3][2];
#pragma unroll
      for (int j = 0; j < 3; j++)
#pragma unroll
        for (int i = 0; i < 2; i++)
        {
          scale_sum(f[j][1][2 * i], f[j][0][2 * i], rs[0], always); scale_sum(f[j][1][2 * i + 1], f[j][0][2 * i + 1], rs[1], always);
          h[j][i] = pack_f16(f[j][1][2 * i], f[j][1][2 * i + 1]);
        }
      const uint32_t rofs = RANK * 32768;
      red_f16x8(slot(s, RANK >> 1, rofs), h[0][0], h[1][0], h[2][0], 0x3c00u);
      red_f16x8(slot(s, (RANK >> 1) ^ 1, rofs), h[0][1], h[1][1], h[2][1], 0x3c00u);
      if (NII == 18) bar_arrive(10, 256);
      SCHED_FENCE(5);
      l16 += ob[B7R];
    }
    {
    PROF(8);
    const uint32_t ma0 = l16 + SM_MEM + w * 128 + (LV >> 3) * 896 + nh * 512;
    const unsigned char* const sl[2] = {slot(s, nh, 0), slot(s, nh ^ 1, 0)};
    uint32_t dl = gtime() - 1984;
    uint32_t late = latest_hint(hints, dl, s);
    if (late >= 64) {
      int n = 0;
#pragma unroll 1
      do {
        hints = load_hints(hint_addr(s));
        dl = gtime() - 1984;
        late = latest_hint(hints, dl, s);
      } while (late >= 64 && ++n < SPIN_LIMIT);
    }
    dl += late * 32 + tm.poll;
    PROF(9);
    {
      auto wait_until = [&](uint32_t t) {
        asm volatile("{\n.reg .pred p;\n.reg .s32 c;\n.reg .u64 t;\nTL: mov.u64 t, %%globaltimer;\ncvt.u32.u64 c, t;\nsub.s32 c, c, %0;\nsetp.lt.s32 p, c, 0;\n@p bra.uni TL;\n}" :: "r"(t + (l16 & 15)) : "memory");
      };
      uint4 v[2][3];
      auto load = [&](int c) {
#pragma unroll
        for (int r = 0; r < 3; r++) v[c][r] = ldg_relaxed(sl[c ^ (r >> 1)] + r * 32768);
      };
      auto decode = [&](int c, int n) {
        uint32_t q[9];
        __half2 hm;
        const uint32_t ma = ma0 ^ (c * 512);
#pragma unroll
        for (int i = 0; i < 9; i++) {
          const uint32_t h = i % 3 == 0 ? v[c][i / 3].x : (i % 3 == 1 ? v[c][i / 3].y : v[c][i / 3].z);
          const float2 f = __half22float2(*(const __half2*)&h);
          q[i] = pack_bf16(f.x, f.y);
          hm = i ? __hmax2(hm, __habs2(*(const __half2*)&h)) : __habs2(*(const __half2*)&h);
        }
#pragma unroll
        for (int r = 0; r < 3; r++) stsm4(ma + r * 4096, q[3 * r], q[3 * r + 1], q[3 * r + 2], r < 2 ? v[c][r].w : *(const uint32_t*)&hm);
        const bool done = __all_sync(0xffffffffu, v[c][0].w == 0x5000u && v[c][1].w == 0x5000u && v[c][2].w == 0x5000u) || n > SPIN_LIMIT;
        asm volatile("{\n.reg .pred p;\nsetp.ne.u32 p, %0, 0;\n@p bar.arrive %1, 256;\n}" :: "r"((int)done), "r"(1 + c) : "memory");
        return done;
      };
      if (LEAD) { wait_until(dl - LEAD); load(1); }
      int n = MO & 1 ? l16 & 15 : 0;
      if (MO & 1) PIN(n);
      if (MO & 2) {
        const uint32_t t = __shfl_sync(0xffffffffu, dl, 0);
        asm volatile("{\n.reg .pred p;\n.reg .s32 c;\nTL: mov.u32 c, %%globaltimer_lo;\nsub.s32 c, c, %0;\nsetp.lt.s32 p, c, 0;\n@p bra.uni TL;\n}" :: "r"(t) : "memory");
      } else wait_until(dl);
      PROF(10);
#pragma unroll 1
      do {
        load(0);
        if (!LEAD) load(1);
        asm volatile("{\n.reg .pred p;\nsetp.eq.u32 p, %0, 0;\n@p bar.sync 13, 384;\n}" :: "r"(n) : "memory");
      } while (!decode(0, n++));
      PROF(11);
#pragma unroll 1
      while (!decode(1, n++)) load(1);
      bar_arrive(9, 256);
      PROF(12);
    }
    PROF(13);
    if (++s == NSEG - 1) break;
    }
  }
#undef fence_reg
  if (RANK < 2) bar_arrive(4, 256);
  bar_sync(0, 384);
  cluster_sync();
}

__global__ void __cluster_dims__(3, 1, 1) __launch_bounds__(384, 1)
rec_kernel(const __grid_constant__ RMaps tm, const bf16* __restrict__ x, const bf16* __restrict__ mem0) {
  extern __shared__ __align__(1024) unsigned char smem_raw[];
  const uint32_t sb = smem_u32(smem_raw);
  const int tid = threadIdx.x, lane = tid & 31;
  const int wg = __shfl_sync(0xffffffffu, tid >> 7, 0);
  const int w = __shfl_sync(0xffffffffu, (tid >> 5) & 3, 0);
  uint32_t rank; asm("mov.u32 %0, %%cluster_ctarank;" : "=r"(rank));
  STAMP(0);
  asm volatile("griddepcontrol.launch_dependents;" ::: "memory");

  if (wg < 2) {
    if (tid == 0) {
      const int h = blockIdx.x / 3;
      mbar_init(sb + MB_XS, 1);
      for (int i = 0; i < 3; i++) { mbar_init(sb + MB_W + 8 * i, 1); mbar_init(sb + MB_X + 8 * i, 1); }
      mbar_init(sb + MB_WO3, 1);
      fence_async();
      if (blockIdx.x < NSEG) { mbar_expect(sb + MB_XS, XT); bulk_load(sb + SM_STAGE + 2 * 49152, x + blockIdx.x * 32 * DM, XT, sb + MB_XS); }
      load_w(sb, tm, rank, 0);
      mbar_expect(sb + MB_X, XT);
      tma_load3(sb + SM_X, &tm.x, 0, sb + MB_X);
      if (WPOS == 2) load_w(sb, tm, rank, 1);
      mbar_expect(sb + MB_WO3, 32768 + 8 * DM * 2);
      tma_load(sb + SM_WOST, &tm.wo, rank * 192 + 64, h * DH, sb + MB_WO3);
      tma_load(sb + SM_WO3, &tm.wo, rank * 192 + 128, h * DH, sb + MB_WO3);
      bulk_load(sb + SM_M0, mem0, 8 * DM * 2, sb + MB_WO3);
      if (WOPF) tma_prefetch(&tm.wo, rank * 192, h * DH);
      if (WPOS == 1) load_w(sb, tm, rank, 1);
      if (blockIdx.x >= NSEG) load_w(sb, tm, rank, 2);
      mbar_init(sb + MB_WO, 1);
      mbar_init(sb + MB_S, rank < 2 ? 5 : 6);
      mbar_init(sb + MB_F, 1);
      mbar_init(sb + MB_VX, 1); mbar_init(sb + MB_VX + 8, 1);
      asm volatile("fence.mbarrier_init.release.cluster;" ::: "memory");
      fence_async();
      mbar_expect(sb + MB_X + 8, XT); mbar_expect(sb + MB_X + 16, XT);
      mbar_expect(sb + MB_WO, 16384);
      mbar_expect(sb + MB_S, rank < 2 ? 640 + 2048 : 1280);
      mbar_expect(sb + MB_VX, 8192); mbar_expect(sb + MB_VX + 8, 8192);
    }
    __syncwarp();
    asm volatile("setmaxnreg.inc.sync.aligned.u32 192;");
    __syncwarp();
    QSTAMP(0);
    if (tid < 32) bar_arrive(0, 160);
    QSTAMP(1);
    proj_role(sb, tm, rank, wg, w, lane);
  } else {
    asm volatile("setmaxnreg.dec.sync.aligned.u32 120;");
    attn_role(sb, smem_raw, tm, rank, x, mem0, w, lane);
  }
}

constexpr int NAUX = 36;
constexpr int A_ST = 6, A_STAGE = 8192 + 12288, A_W8 = A_ST * A_STAGE, A_EXC = A_W8 + A_ST * 1536, A_ROWS = 57;
constexpr int A_IN = A_EXC + 8 * 2304, A_INB = 3 * SEGB, A_OST = A_IN + 2 * A_INB, A_P = A_OST + 8192, A_G = A_P + 3072;
constexpr int A_BAR = A_G + 1024;
constexpr int A_XT = A_BAR + 1024, A_XW = A_XT;
constexpr int A_TOTAL = A_XT + 4096;
static_assert(A_IN % 1024 == 0 && A_XT % 1024 == 0 && A_IN >= 4 * XT && A_IN + 64 * DM * 2 <= A_BAR && A_TOTAL <= 232448, "side kernel shared memory");
struct AMaps { CUtensorMap x, wa, wa8, o, o3, o16, wob, woa, woa16; const unsigned char* red; uint32_t poll; };

DI void wgmma_n192_ss_nt(float* d, uint64_t da, uint64_t db, int acc) {
  asm volatile("{\n.reg .pred p;\nsetp.ne.b32 p, %98, 0;\n"
               "wgmma.mma_async.sync.aligned.m64n192k16.f32.bf16.bf16 {"
               "%0,%1,%2,%3,%4,%5,%6,%7,%8,%9,%10,%11,%12,%13,%14,%15,%16,%17,%18,%19,%20,%21,%22,%23,%24,%25,%26,%27,%28,%29,%30,%31,"
               "%32,%33,%34,%35,%36,%37,%38,%39,%40,%41,%42,%43,%44,%45,%46,%47,%48,%49,%50,%51,%52,%53,%54,%55,%56,%57,%58,%59,%60,%61,%62,%63,"
               "%64,%65,%66,%67,%68,%69,%70,%71,%72,%73,%74,%75,%76,%77,%78,%79,%80,%81,%82,%83,%84,%85,%86,%87,%88,%89,%90,%91,%92,%93,%94,%95"
               "}, %96, %97, p, 1, 1, 0, 1;\n}\n"
               : ACC8(d, 0), ACC8(d, 8), ACC8(d, 16), ACC8(d, 24), ACC8(d, 32), ACC8(d, 40), ACC8(d, 48), ACC8(d, 56),
                 ACC8(d, 64), ACC8(d, 72), ACC8(d, 80), ACC8(d, 88) : "l"(da), "l"(db), "r"(acc));
}
DI void wgmma_n24_ss_nt(float* d, uint64_t da, uint64_t db, int acc) {
  asm volatile("{\n.reg .pred p;\nsetp.ne.b32 p, %14, 0;\n"
               "wgmma.mma_async.sync.aligned.m64n24k16.f32.bf16.bf16 {%0,%1,%2,%3,%4,%5,%6,%7,%8,%9,%10,%11}, %12, %13, p, 1, 1, 0, 1;\n}\n"
               : ACC8(d, 0), "+f"(d[8]), "+f"(d[9]), "+f"(d[10]), "+f"(d[11]) : "l"(da), "l"(db), "r"(acc));
}
DI void tma_load3d(uint32_t dst, const CUtensorMap* m, int c0, int c1, int c2, uint32_t mb) {
  asm volatile("cp.async.bulk.tensor.3d.shared::cluster.global.mbarrier::complete_tx::bytes [%0], [%1, {%3, %4, %5}], [%2];"
               :: "r"(dst), "l"(m), "r"(mb), "r"(c0), "r"(c1), "r"(c2) : "memory");
}
DI uint32_t trans8(uint32_t x) { uint32_t r; asm("movmatrix.sync.aligned.m8n8.trans.b16 %0, %1;" : "=r"(r) : "r"(x)); return r; }
DI void wgmma_n40_ss(float* d, uint64_t da, uint64_t db, int acc) {
  asm volatile("{\n.reg .pred p;\nsetp.ne.b32 p, %22, 0;\n"
               "wgmma.mma_async.sync.aligned.m64n40k16.f32.bf16.bf16 {%0,%1,%2,%3,%4,%5,%6,%7,%8,%9,%10,%11,%12,%13,%14,%15,%16,%17,%18,%19}, "
               "%20, %21, p, 1, 1, 1, 1;\n}\n"
               : ACC8(d, 0), ACC8(d, 8), "+f"(d[16]), "+f"(d[17]), "+f"(d[18]), "+f"(d[19]) : "l"(da), "l"(db), "r"(acc));
}
DI uint2 ldg_relaxed64(const void* p) {
  uint2 v; asm volatile("ld.relaxed.gpu.global.v2.b32 {%0,%1}, [%2];" : "=r"(v.x), "=r"(v.y) : "l"(p) : "memory"); return v;
}
template <int ST> DI void ldg8x64(uint32_t* m, const void* p) {
  asm volatile("ld.relaxed.gpu.global.v2.b32 {%0,%1}, [%16];\nld.relaxed.gpu.global.v2.b32 {%2,%3}, [%16 + %17];\n"
               "ld.relaxed.gpu.global.v2.b32 {%4,%5}, [%16 + %18];\nld.relaxed.gpu.global.v2.b32 {%6,%7}, [%16 + %19];\n"
               "ld.relaxed.gpu.global.v2.b32 {%8,%9}, [%16 + %20];\nld.relaxed.gpu.global.v2.b32 {%10,%11}, [%16 + %21];\n"
               "ld.relaxed.gpu.global.v2.b32 {%12,%13}, [%16 + %22];\nld.relaxed.gpu.global.v2.b32 {%14,%15}, [%16 + %23];"
               : "=r"(m[0]), "=r"(m[1]), "=r"(m[2]), "=r"(m[3]), "=r"(m[4]), "=r"(m[5]), "=r"(m[6]), "=r"(m[7]),
                 "=r"(m[8]), "=r"(m[9]), "=r"(m[10]), "=r"(m[11]), "=r"(m[12]), "=r"(m[13]), "=r"(m[14]), "=r"(m[15])
               : "l"(p), "n"(ST), "n"(2 * ST), "n"(3 * ST), "n"(4 * ST), "n"(5 * ST), "n"(6 * ST), "n"(7 * ST) : "memory");
}
template <int ST> DI void ldg4x128(uint32_t* m, const void* p) {
  asm volatile("ld.relaxed.gpu.global.v4.b32 {%0,%1,%2,%3}, [%16];\nld.relaxed.gpu.global.v4.b32 {%4,%5,%6,%7}, [%16 + %17];\n"
               "ld.relaxed.gpu.global.v4.b32 {%8,%9,%10,%11}, [%16 + %18];\nld.relaxed.gpu.global.v4.b32 {%12,%13,%14,%15}, [%16 + %19];"
               : "=r"(m[0]), "=r"(m[1]), "=r"(m[2]), "=r"(m[3]), "=r"(m[4]), "=r"(m[5]), "=r"(m[6]), "=r"(m[7]),
                 "=r"(m[8]), "=r"(m[9]), "=r"(m[10]), "=r"(m[11]), "=r"(m[12]), "=r"(m[13]), "=r"(m[14]), "=r"(m[15])
               : "l"(p), "n"(ST), "n"(2 * ST), "n"(3 * ST) : "memory");
}
template <int N, int ST> DI bool stale(const uint32_t* m, uint32_t tag) {
  uint32_t x = m[0] ^ tag;
#pragma unroll
  for (int i = 1; i < N; i++) asm("lop3.b32 %0, %0, %1, %2, 0xf6;" : "+r"(x) : "r"(m[i * ST]), "r"(tag));
  return __any_sync(0xffffffffu, x & 1);
}
DI bool mbar_test(uint32_t b, uint32_t par) {
  uint32_t r; asm volatile("{\n.reg .pred p;\nmbarrier.test_wait.parity.shared::cta.b64 p, [%1], %2;\nselp.u32 %0, 1, 0, p;\n}" : "=r"(r) : "r"(b), "r"(par) : "memory");
  return r;
}
DI int wait_flags(const unsigned* p, bool active, unsigned base, int seg) {
  int n = 0, m;
  while (true) {
    m = __reduce_min_sync(0xffffffffu, active ? (int)(ldg_acquire32(p) - base) : NSEG);
    if (m > seg || ++n > SPIN_LIMIT) break;
    __nanosleep((YP & 32) ? 400 : 40);
  }
  return max(m, seg + 1);
}
DI void wait_count(const unsigned* p, unsigned target) {
  int n = 0;
  unsigned v;
  while (true) {
    asm volatile("ld.acquire.gpu.global.b32 %0, [%1];" : "=r"(v) : "l"(p) : "memory");
    if ((int)(v - target) >= 0 || ++n > SPIN_LIMIT) break;
    __nanosleep(64);
  }
}
#define PACE_NEXT 800
#define AWARM 0
#define WPF 3
#define UNP 64
#define ADLY 0
#define ODLY 100
#define SDLY 0
#define RSL 100
#define TWO 0
#define ALLW 1
#define PING 60
#define FLAG 2
#define FPOS 1
#define QB 1
#define Q_LO 0
#define Q_HI 320
DI bool tick_wait(uint32_t pace, int step) {
  const int n = lds32v(pace);
  if (n <= step) mbar_wait(pace + 8, n & 1);
  return n <= step;
}
DI void quiet_wait(uint32_t pace) {
  uint32_t n, d;
  asm volatile("ld.volatile.shared.v2.b32 {%0,%1}, [%2];" : "=r"(n), "=r"(d) : "r"(pace) : "memory");
  if (n - 1 < NSEG - 2 && (int)(gtime() - d) > Q_HI) mbar_wait(pace + 8, n & 1);
}
DI void sleep_until(uint32_t t) {
  for (int n = 0; n < 64; n++) {
    const int r = t - gtime();
    if (r <= 0) break;
    __nanosleep(r >> 1);
  }
}
DI void aux_barrier(int i, unsigned epoch, bool wait = true) {
  asm volatile("fence.proxy.async;" ::: "memory");
  asm volatile("red.release.gpu.global.add.u32 [%0], 1;" :: "l"(&g_abar[i * 32]) : "memory");
  if (!wait) return;
  wait_count(&g_abar[i * 32], NAUX * (epoch + 1));
  asm volatile("fence.proxy.async;" ::: "memory");
}

__global__ void __launch_bounds__(512, 1)
aux_kernel(const __grid_constant__ AMaps tm, const bf16* __restrict__ x, const bf16* __restrict__ gate_w, bf16* __restrict__ out) {
  extern __shared__ __align__(1024) unsigned char smem_raw[];
  const uint32_t sb = smem_u32(smem_raw);
  const uint32_t full1 = sb + A_BAR, empty1 = full1 + 8 * A_ST, fullw = empty1 + 8 * A_ST, full3 = fullw + 16, empty3 = full3 + 32,
                 fulla = empty3 + 32, emptya = fulla + 32, fullg = emptya + 16, pace = fullg + 8;
  const int tid = threadIdx.x, lane = tid & 31, cta = blockIdx.x;
  const int wg = __shfl_sync(0xffffffffu, tid >> 7, 0), w = __shfl_sync(0xffffffffu, (tid >> 5) & 3, 0);
  ASTAMP(14);
  const unsigned epoch = *(volatile unsigned*)&g_epoch2;
  if (tid == 0) {
    for (int i = 0; i < A_ST; i++) { mbar_init(full1 + 8 * i, 1); mbar_init(empty1 + 8 * i, 8); }
    mbar_init(fullw, 1); mbar_init(fullw + 8, 1); mbar_init(fullg, 1);
    for (int i = 0; i < 2; i++) { mbar_init(fulla + 16 * i, 2); mbar_init(fulla + 16 * i + 8, 1); mbar_init(emptya + 8 * i, 4); }
    sts64(pace, 0, 0); mbar_init(pace + 8, 1); sts32(pace + 16, 0); sts64(pace + 24, 65536, 0xffff0000u);
    for (int i = 0; i < 4; i++) { mbar_init(full3 + 8 * i, 1); mbar_init(empty3 + 8 * i, cta < NH ? 8 : 4); }
    fence_async();
  }
  __syncthreads();
  ASTAMP(0);
  const bool wide = cta < NH;
  auto p3_ks = [&](int g) { return wide ? cta >> 2 : 2 * (cta - NH) + g; };
  auto p3_mt = [&](int g) { return wide ? 2 * (cta & 3) + g : 8; };
  const unsigned fbase = epoch * NSEG;
  if (wg == 3) {
    asm volatile("setmaxnreg.dec.sync.aligned.u32 %0;" :: "n"(TWO ? 32 : 48));
    if (w == 1 && cta < NH) {
#pragma unroll 1
      for (int seg = 0; seg < ((XP & 2048) ? 0 : NSEG); seg++) {
        bar_arrive(5, 160);
        if (seg > 0 && lane == 0) {
          asm volatile("cp.async.bulk.wait_group 0;" ::: "memory");
          stg_relaxed32(&g_oflag[cta * 32], fbase + seg);
        }
        __syncwarp();
        bar_sync(4, 160);
        if (QM & 16) tick_wait(pace, seg + 1);
        if (lane == 0) {
          fence_async();
          if (!(YP & 2)) {
          tma_store(&tm.o, sb + A_OST, cta * DH, seg * 32);
          tma_store(&tm.o, sb + A_OST + 4096, cta * DH + 64, seg * 32);
          }
          asm volatile("cp.async.bulk.commit_group;" ::: "memory");
          asm volatile("cp.async.bulk.wait_group.read 0;" ::: "memory");
        }
        __syncwarp();
      }
      if (lane == 0) {
        asm volatile("cp.async.bulk.wait_group 0;" ::: "memory");
        { const int seg = NSEG - 1; TSTAMP(2); }
        stg_relaxed32(&g_oflag[cta * 32], fbase + NSEG);
      }
    }
    if (w == 2 && cta < NH) {
      const uint32_t ktag = (epoch + 1) & 1, ma = sb + A_IN + 8192 + lane * 16;
      int avail = 0;
      bar_sync(10, 64);
#pragma unroll 1
      for (int seg = 0; seg < ((XP & 2048) ? 0 : NSEG); seg++) {
        if (avail <= seg) avail = wait_flags(&g_sflag[(cta * 3 + min(lane, 2)) * 8], true, fbase, seg);
        if ((QM & 8) && seg < UNP) tick_wait(pace, seg);
        TSTAMP(0);
        const unsigned char* km = g_km + (size_t)(seg * NH + cta) * 4096 + lane * 8;
        uint32_t m[16];
        const float g = __ldcg(&g_gate[seg * 32 + lane]);
        ldg8x64<256>(m, km);
        const uint32_t b = seg & 1, full = fulla + 16 * b, mb = ma + b * A_INB;
        mbar_wait(emptya + 8 * b, (~seg >> 1) & 1);
        if (lane < 2) mbar_expect(full + 8 * lane, (YP & 8) ? 0 : 16384 >> lane);
        __syncwarp();
        if (lane < 3 && !(YP & 8)) ((EF & 2) ? bulk_load_ef : bulk_load)(sb + A_IN + b * A_INB + lane * SEGB, g_seg + ((size_t)(seg & RING) * 96 + cta * 3 + lane) * 8192, 8192, full + (lane & 2) * 4);
        int n = 0;
#pragma unroll 1
        while (stale<8, 2>(m, ktag) && ++n < SPIN_LIMIT) { if (seg < UNP - 1) __nanosleep(200); ldg8x64<256>(m, km); }
        TSTAMP(1);
#pragma unroll
        for (int i = 0; i < 4; i++) stsm4(mb + (i >> 1) * SEGB + (i & 1) * 512, m[4 * i], m[4 * i + 1], m[4 * i + 2], m[4 * i + 3]);
        sts32(sb + A_G + b * 128 + lane * 4, __float_as_uint(1.f - g));
        fence_async();
        __syncwarp();
        if (lane == 0) mbar_arrive(full);
      }
    }
    if (w == 3 && QM) {
      const unsigned char* const hp = tm.red + HINT_OFF + 65536 + (cta & 1) * 4096 + min(lane, 23) * 4;
      uint32_t d = 0;
      int s = 0, n = 0;
#pragma unroll 1
      while (s < NSEG - 1) {
        const uint32_t h = ldg_relaxed32(hp + RED_SLOT(s)), t = (gtime() - 1984) & ~31u, late = latest_hint(h, t, s);
        if (late < 64) {
          d = t + late * 32 + tm.poll + Q_LO;
          sleep_until(d);
          s++; n = 0;
          if (lane == 0) { mbar_arrive(pace + 8); sts64(pace, s < NSEG - 1 ? s : 2 * NSEG, d); }
          sleep_until(d + PACE_NEXT);
        } else {
          if (++n > (s ? 16 : 256) || lds32v(pace + 16)) break;
          if (!s) __nanosleep(100);
        }
      }
      if (s < NSEG - 1 && lane == 0) { mbar_arrive(pace + 8); sts64(pace, 2 * NSEG, d); }
    }
    if (w != 0) return;
    const bool lead = lane == 0;
#pragma unroll 1
    for (int it = 0, st = 0, ph = 1, k = 0, col = (cta & 1) * (DM / 2); it < ((XP & 256) ? 0 : 72); it++) {
      mbar_wait(empty1 + 8 * st, ph);
      if (QM & 1) quiet_wait(pace);
      if (elect_one()) {
        mbar_expect(full1 + 8 * st, A_STAGE + 1536);
        tma_load3d(sb + st * A_STAGE, &tm.x, k, (cta >> 1) * A_ROWS - 7, 0, full1 + 8 * st);
        tma_load3d(sb + st * A_STAGE + 8192, &tm.wa, col, k, 0, full1 + 8 * st);
        tma_load3d(sb + A_W8 + st * 1536, &tm.wa8, col + 64, k, 0, full1 + 8 * st);
      }
      __syncwarp();
      if (++st == A_ST) { st = 0; ph ^= 1; }
      k += 32;
      if (k == DM) { k = 0; col += 72; }
    }
    auto load_wo = [&](uint32_t dst, int g, int kb, uint32_t mb) {
      if (kb < 64) tma_load(dst, &tm.wob, p3_mt(g) * 64, kb * 64, mb);
      else tma_load(dst, &tm.woa, p3_mt(g) * 64, (kb - 64) * 64, mb);
    };
    if (lead) mbar_expect(fullw, 16 * 8192);
#pragma unroll 1
    for (int st = 0; st < A_ST; st++) {
      if (!(XP & 256)) mbar_wait(empty1 + 8 * st, 1);
      if (lane < 16 && min(((lane + 1) * 8192 - 1) / A_STAGE, A_ST - 1) == st) load_wo(sb + lane * 8192, lane >> 3, p3_ks(lane >> 3) * 9 + (lane & 7), fullw);
      __syncwarp();
    }
    __syncwarp(); bar_sync(6, 288);
    if (lead) mbar_expect(fullw + 8, 2 * 8192 + (p3_ks(0) >= 4 ? 4096 : 0));
    __syncwarp();
    if (lane < 2) {
      load_wo(sb + (16 + lane) * 8192, lane, p3_ks(lane) * 9 + 8, fullw + 8);
      if (p3_ks(0) >= 4) tma_load(sb + A_XW + lane * 2048, &tm.woa16, p3_mt(lane) * 64, 448 + p3_ks(lane) * 16, fullw + 8);
    }
    __syncwarp();
    if (lead) aux_barrier(1, epoch, ALLW || p3_ks(0) >= 4);
    __syncwarp(); bar_sync(6, 288);
    {
      int avail = 0, sl = 0, ph = 1;
      const int h = (9 * p3_ks(0) >> 1) + lane;
#pragma unroll 1
      for (int seg = 0; seg < ((XP & 2048) ? 0 : NSEG); seg++) {
        if (avail <= seg) avail = wait_flags(&g_oflag[min(h, NH - 1) * 32], lane < (wide ? 5 : 9), fbase, seg);
        SSTAMP(seg, 4);
        for (int g = 0; g < (wide ? 1 : 2); g++) {
          const int ks = p3_ks(g);
          mbar_wait(empty3 + 8 * sl, ph);
          if ((QM & 4) && tick_wait(pace, seg + (QM >> 4 & 1) + 1) && ODLY) __nanosleep(ODLY);
          if (YP & 4) { if (lead) mbar_arrive(full3 + 8 * sl); }
          else if (elect_one()) {
            mbar_expect(full3 + 8 * sl, XT + (ks >= 4 ? 1024 : 0));
            tma_load3d(sb + sl * XT, &tm.o3, 0, seg * 32, ks * 9, full3 + 8 * sl);
            if (ks >= 4) tma_load(sb + A_XT + sl * 1024, &tm.o16, 72 * 64 - 64 + ks * 16, seg * 32, full3 + 8 * sl);
          }
          __syncwarp();
          if (++sl == (wide ? 3 : 4)) { sl = 0; ph ^= 1; }
        }
      }
    }
    sts32(pace + 16, 1);
    __syncwarp(); bar_sync(6, 288);
    asm volatile("griddepcontrol.wait;" ::: "memory");
  } else if (wg == 2) {
    asm volatile("setmaxnreg.dec.sync.aligned.u32 64;");
    if (cta < NH) {
      if (tid == 256) { mbar_expect(fullg, 64 * DM * 2); bulk_load(sb + A_IN, x + cta * 64 * DM, 64 * DM * 2, fullg); }
      uint32_t gw[9];
#pragma unroll
      for (int j = 0; j < 9; j++) gw[j] = ((const uint32_t*)gate_w)[j * 32 + lane];
      mbar_wait(fullg, 0);
      float mine = 0.f;
#pragma unroll 4
      for (int u = 0; u < 16; u++) {
        float d0 = 0.f, d1 = 0.f;
#pragma unroll
        for (int j = 0; j < 9; j++) {
          const uint32_t a = lds32(sb + A_IN + (w * 16 + u) * (DM * 2) + j * 128 + lane * 4);
          d0 = fmaf(bf_lo(a), bf_lo(gw[j]), d0); d1 = fmaf(bf_hi(a), bf_hi(gw[j]), d1);
        }
        d0 = warp_sum(d0 + d1);
        if (lane == u) mine = d0;
      }
      if (lane < 16) g_gate[cta * 64 + w * 16 + lane] = 1.f / (1.f + __expf(-mine));
      fence_async();
    }
    bar_sync(3, 128);
    if (tid == 256) { aux_barrier(0, epoch); if (cta == 0) *(volatile unsigned*)&g_epoch2 = epoch + 1; }
    __syncwarp();
    bar_sync(3, 128);
    if (w == 0) bar_arrive(8, 288);
    if (w == 1 && cta < NH) bar_arrive(10, 64);
    if (cta < NH) {
      CDECL;
#pragma unroll 1
      for (int seg = 0; seg < ((XP & 2048) ? 0 : NSEG); seg++) {
        CSTAMP(0);
        const uint32_t in = sb + A_IN + (seg & 1) * A_INB;
        const uint64_t qd = make_desc(in, 128, 1024, 0);
        mbar_wait(fulla + 16 * (seg & 1), (seg >> 1) & 1);
        CSTAMP(3);
        SSTAMP(seg, 0);
        float d[2][16];
        {
          float a[20];
          uint32_t vm[16];
          const unsigned char* vp = g_km + (size_t)(seg * NH + cta) * 4096 + 2048 + lane * 16;
          if (w == 3) ldg4x128<512>(vm, vp);
          WG_FENCE();
#pragma unroll
          for (int k = 0; k < ((YP & 16) ? 1 : 8); k++) wgmma_n40_ss(a, qd + ((k >> 2) * SEGB + (k & 3) * 256 >> 4), qd + ((k >> 2) * SEGB + (k & 3) * 256 + 4096 >> 4), k > 0);
          const uint32_t ga = sb + A_G + (seg & 1) * 128 + (w & 1) * 64 + (lane >> 2) * 4;
          const float f0 = __uint_as_float(lds32(ga)), f1 = __uint_as_float(lds32(ga + 32));
          WG_COMMIT();
          WG_WAIT(0);
          CSTAMP(5);
          SSTAMP(seg, 1);
          if (w < 2) {
            const int lim = w * 16 + (lane >> 2) - 2 * (lane & 3);
            float m0 = -3.0e38f, m1 = -3.0e38f;
#pragma unroll
            for (int i = 0; i < 20; i++) {
              a[i] *= SM_SCALE * LOG2E;
              if (i < 16 && (i >> 2) * 8 + (i & 1) - (i & 2) * 4 > lim) a[i] = -1.0e9f * LOG2E;
              if (i & 2) m1 = fmaxf(m1, a[i]); else m0 = fmaxf(m0, a[i]);
            }
#pragma unroll
            for (int o = 1; o < 4; o <<= 1) { m0 = fmaxf(m0, __shfl_xor_sync(0xffffffffu, m0, o)); m1 = fmaxf(m1, __shfl_xor_sync(0xffffffffu, m1, o)); }
            float s0 = 0.f, s1 = 0.f;
#pragma unroll
            for (int i = 0; i < 20; i++) { a[i] = ex2(a[i] - (i & 2 ? m1 : m0)); if (i & 2) s1 += a[i]; else s0 += a[i]; }
#pragma unroll
            for (int o = 1; o < 4; o <<= 1) { s0 += __shfl_xor_sync(0xffffffffu, s0, o); s1 += __shfl_xor_sync(0xffffffffu, s1, o); }
            s0 = f0 * rcp(s0); s1 = f1 * rcp(s1);
            uint32_t p[10];
#pragma unroll
            for (int i = 0; i < 10; i++) p[i] = pack_bf16(a[2 * i] * (i & 1 ? s1 : s0), a[2 * i + 1] * (i & 1 ? s1 : s0));
            const uint32_t pa = sb + A_P + (2 * w + ((lane >> 3) & 1)) * 768 + (lane >> 4) * 128 + (lane & 7) * 16;
            stsm4t(pa, p[0], p[1], p[2], p[3]); stsm4t(pa + 256, p[4], p[5], p[6], p[7]); stsm4t(pa + 512, p[8], p[9], 0, 0);
            CSTAMP(6);
            fence_async();
            CSTAMP(7);
          } else if (w == 3) {
            int n = 0;
#pragma unroll 1
            while (stale<4, 4>(vm, (epoch + 1) & 1) && ++n < SPIN_LIMIT) ldg4x128<512>(vm, vp);
#pragma unroll
            for (int i = 0; i < 4; i++) stsm4(in + 2 * SEGB + 8192 + (lane >> 4) * 1024 + (lane & 15) * 16 + i * 256, vm[4 * i], vm[4 * i + 1], vm[4 * i + 2], vm[4 * i + 3]);
            fence_async();
            mbar_wait(fulla + 16 * (seg & 1) + 8, (seg >> 1) & 1);
          }
        }
        CSTAMP(8);

        bar_sync(5, 160);
        CSTAMP(10);
        SSTAMP(seg, 2);
        const uint64_t pd = make_desc(sb + A_P, 128, 768, 0), vd = make_desc(in + 2 * SEGB, 128, 512, 0), md = make_desc(in + 2 * SEGB + 8192, 0, 128, 0);
        WG_FENCE();
#pragma unroll
        for (int i = 0; i < 2; i++) {
          wgmma_n32_ss<0>(d[i], vd + i * 256, pd, 0);
          wgmma_n32_ss<0>(d[i], vd + i * 256 + 16, pd + 16, 1);
          wgmma_n32_ss<0>(d[i], md + i * 64, pd + 32, 1);
        }
        WG_COMMIT();
        WG_WAIT(0);
        CSTAMP(11);
        if (lane == 0) mbar_arrive(emptya + 8 * (seg & 1));
#pragma unroll
        for (int i = 0; i < 2; i++) {
          const uint32_t oa = sb + A_OST + i * 4096 + ((lane & 7) + ((lane >> 4) << 3)) * 128 + (((2 * w + ((lane >> 3) & 1)) ^ (lane & 7)) << 4);
          stsm4t(oa, pack_bf16(d[i][0], d[i][1]), pack_bf16(d[i][2], d[i][3]), pack_bf16(d[i][4], d[i][5]), pack_bf16(d[i][6], d[i][7]));
          stsm4t(oa + 2048, pack_bf16(d[i][8], d[i][9]), pack_bf16(d[i][10], d[i][11]), pack_bf16(d[i][12], d[i][13]), pack_bf16(d[i][14], d[i][15]));
        }
        CSTAMP(12);
        bar_sync(4, 160);
        SSTAMP(seg, 3);
      }
      CDUMP;
    }
  } else {
    asm volatile("setmaxnreg.inc.sync.aligned.u32 %0;" :: "n"(TWO ? 208 : 200));
    {
      const int g = lane >> 2, t = lane & 3, r0 = (cta >> 1) * A_ROWS - 7 + w * 16;
      const uint32_t prev = (2 * t > g ? 0xffffu : 0u) | (2 * t + 1 > g ? 0xffff0000u : 0u);
      const int k0 = r0 + 2 * t - (2 * t > g ? 8 : 0), k1 = r0 + 2 * t + 1 - (2 * t + 1 > g ? 8 : 0);
      const uint32_t slot = sb + A_EXC + (wg * 4 + w) * 2304;
      float gl = 0.f, gh = 0.f;
      int st = 0, ph = 0;
#pragma unroll 1
      for (int p = -AWARM; p < ((XP & 256) ? 0 : 4); p++) {
        float big[96], sml[12];
        if (p == WPF && tid < 18) {
          const int kb = p3_ks(tid >= 9) * 9 + tid % 9;
          tma_prefetch(kb < 64 ? &tm.wob : &tm.woa, p3_mt(tid >= 9) * 64, (kb & 63) * 64);
        }
        __syncwarp();
#pragma unroll
        for (int i = 0; i < 96; i++) big[i] = 0.f;
#pragma unroll
        for (int i = 0; i < 12; i++) sml[i] = 0.f;
#pragma unroll 1
        for (int k = p < 0 ? 18 : 0; k < 18; k++) {
          mbar_wait(full1 + 8 * st, ph);
          const uint64_t da = make_desc(sb + st * A_STAGE + wg * 4096, 16, 512, 2);
          const uint64_t db = make_desc(sb + st * A_STAGE + 8192, 4096, 1024, 1), dc = make_desc(sb + A_W8 + st * 1536, 128, 512, 0);
          WG_FENCE();
#pragma unroll
          for (int j = 0; j < 2; j++) { wgmma_n192_ss_nt(big, da + j * 2, db + j * 128, 1); wgmma_n24_ss_nt(sml, da + j * 2, dc + j * 16, 1); }
          WG_COMMIT();
          WG_WAIT(1);
          if (k > 0 && lane == 0) mbar_arrive(empty1 + 8 * (st ? st - 1 : A_ST - 1));
          if (++st == A_ST) { st = 0; ph ^= 1; }
        }
        WG_WAIT(0);
        ASTAMP(16 + max(p, 0) + wg * 16);
        if (lane == 0 && p >= 0) mbar_arrive(empty1 + 8 * (st ? st - 1 : A_ST - 1));
        uint32_t f[3][9][2];
#pragma unroll
        for (int c = 0; c < 3; c++)
#pragma unroll
          for (int j = 0; j < 9; j++)
#pragma unroll
            for (int i = 0; i < 2; i++) {
              const float* a = j < 8 ? &big[(c * 8 + j) * 4 + 2 * i] : &sml[c * 4 + 2 * i];
              f[c][j][i] = c < 2 ? pack_bf16(a[0], a[1]) : trans8(pack_bf16(a[0], a[1]));
            }
        if (p == 0) {
          bar_sync(8, 288);
          gl = __ldcg(&g_gate[min(max(r0 + g, 0), S_LEN / 2 - 1) * 2 + wg]); gh = __ldcg(&g_gate[min(max(r0 + g + 8, 0), S_LEN / 2 - 1) * 2 + wg]);
        }
        asm volatile("cp.async.bulk.wait_group.read 0;" ::: "memory");
        __syncwarp();
#pragma unroll
        for (int j = 0; j < 8; j += 2) sts128(slot + j * 256 + lane * 16, f[1][j][1], f[2][j][1], f[1][j + 1][1], f[2][j + 1][1]);
        sts64(slot + 2048 + lane * 8, f[1][8][1], f[2][8][1]);
        bar_sync(1 + wg, 128);
        ASTAMP(24 + max(p, 0) + wg * 16);
        uint32_t pv[9][2];
#pragma unroll
        for (int j = 0; j < 9; j++) pv[j][0] = pv[j][1] = 0;
        if (w) {
#pragma unroll
          for (int j = 0; j < 8; j += 2) lds128(slot - 2304 + j * 256 + lane * 16, pv[j]);
          lds64(slot - 256 + lane * 8, pv[8][0], pv[8][1]);
        }
        float a[4][4], m[4][2];
#pragma unroll
        for (int h = 0; h < 4; h++) {
          const int j = 2 * h;
          const uint32_t qa[4] = {t >= h ? f[0][j][0] : 0, t >= h ? f[0][j][1] : 0, f[0][j + 1][0], f[0][j + 1][1]};
          const uint32_t qb0 = t <= h ? f[0][j + 2][0] : 0, qb1 = t <= h ? f[0][j + 2][1] : 0;
          float s0[4], s1[4], s2[4];
          mma16816z(s1, qa, f[1][j][0], f[1][j + 1][0]); mma16816z(s2, qa, f[1][j][1], f[1][j + 1][1]); mma16816z(s0, qa, pv[j][0], pv[j + 1][0]);
          mma1688(s1, qb0, qb1, f[1][j + 2][0]); mma1688(s2, qb0, qb1, f[1][j + 2][1]); mma1688(s0, qb0, qb1, pv[j + 2][0]);
          a[h][0] = 2 * t > g ? s0[0] : s1[0]; a[h][1] = 2 * t + 1 > g ? s0[1] : s1[1]; a[h][2] = 2 * t > g ? s1[2] : s2[2]; a[h][3] = 2 * t + 1 > g ? s1[3] : s2[3];
        }
#pragma unroll
        for (int h = 0; h < 4; h++) {
#pragma unroll
          for (int i = 0; i < 4; i++) a[h][i] = (i & 1 ? k1 : k0) + (i & 2) * 4 >= 0 ? a[h][i] * (0.23570226039551584f * LOG2E) : -1.0e9f * LOG2E;
          m[h][0] = fmaxf(a[h][0], a[h][1]); m[h][1] = fmaxf(a[h][2], a[h][3]);
        }
#pragma unroll
        for (int x = 1; x < 4; x <<= 1)
#pragma unroll
          for (int i = 0; i < 8; i++) m[i >> 1][i & 1] = fmaxf(m[i >> 1][i & 1], __shfl_xor_sync(0xffffffffu, m[i >> 1][i & 1], x));
#pragma unroll
        for (int h = 0; h < 4; h++) {
#pragma unroll
          for (int i = 0; i < 4; i++) a[h][i] = ex2(a[h][i] - m[h][i >> 1]);
          m[h][0] = a[h][0] + a[h][1]; m[h][1] = a[h][2] + a[h][3];
        }
#pragma unroll
        for (int x = 1; x < 4; x <<= 1)
#pragma unroll
          for (int i = 0; i < 8; i++) m[i >> 1][i & 1] += __shfl_xor_sync(0xffffffffu, m[i >> 1][i & 1], x);
        uint32_t o[9][2];
#pragma unroll
        for (int h = 0; h < 4; h++) {
          const int j = 2 * h;
          const float z0 = gl * rcp(m[h][0]), z1 = gh * rcp(m[h][1]);
          const uint32_t pl = pack_bf16(a[h][0] * z0, a[h][1] * z0), pu = pack_bf16(a[h][2] * z1, a[h][3] * z1);
          const uint32_t pa[4] = {pl & prev, 0, pl & ~prev, pu & prev};
          float d[3][4];
#pragma unroll
          for (int i = 0; i < 3; i++) mma16816z(d[i], pa, pv[j + i][1], f[2][j + i][0]);
#pragma unroll
          for (int i = 0; i < 3; i++) mma1688(d[i], 0, pu & ~prev, f[2][j + i][1]);
#pragma unroll
          for (int i = 0; i < 3; i++) {
            const uint32_t d0 = pack_bf16(d[i][0], d[i][1]), d1 = pack_bf16(d[i][2], d[i][3]);
            o[j + i][0] = i == 0 && h > 0 && t < h ? o[j][0] : d0;
            o[j + i][1] = i == 0 && h > 0 && t < h ? o[j][1] : d1;
          }
        }
        ASTAMP(28 + max(p, 0) + wg * 16);
        bar_sync(1 + wg, 128);
        const uint32_t oa = slot + (lane & 15) * 144 + (lane >> 4) * 16;
#pragma unroll
        for (int j = 0; j < 8; j += 2) stsm4(oa + j * 16, o[j][0], o[j][1], o[j + 1][0], o[j + 1][1]);
        asm volatile("stmatrix.sync.aligned.m8n8.x2.shared.b16 [%0], {%1,%2};" :: "r"(oa + 128), "r"(o[8][0]), "r"(o[8][1]) : "memory");
        fence_async();
        __syncwarp();
        if (QM & 64) quiet_wait(pace);
        if (lane < 16 && w * 16 + lane >= 7 && r0 + lane < S_LEN / 2 && p >= 0)
          asm volatile("cp.async.bulk.global.shared::cta.bulk_group [%0], [%1], 144;"
                       :: "l"(g_Ocat + (size_t)((r0 + lane) * 2 + wg) * KCAT + 4096 + (cta & 1) * (DM / 2) + p * 72), "r"(slot + lane * 144) : "memory");
        asm volatile("cp.async.bulk.commit_group;" ::: "memory");
        ASTAMP(20 + max(p, 0) + wg * 16);
      }
      if (XP & 256) bar_sync(8, 288);
      asm volatile("cp.async.bulk.wait_group 0;" ::: "memory");
    }
    ASTAMP(3);
    bar_arrive(6, 288);
    uint32_t wa[37][4];
    mbar_wait(fullw, 0);
    const uint32_t la = sb + ((lane & 7) + ((lane >> 4) << 3)) * 128 + (((2 * w + ((lane >> 3) & 1)) ^ (lane & 7)) << 4);
#pragma unroll
    for (int k = 0; k < 32; k++) ldsm4t(wa[k], la + wg * 65536 + k * 2048);
    mbar_wait(fullw + 8, 0);
#pragma unroll
    for (int k = 32; k < 36; k++) ldsm4t(wa[k], la + wg * 8192 + 65536 + k * 2048);
    ldsm4t(wa[36], la + A_XW + wg * 2048);
    fence_async();
    if (XP & 2048) bar_sync(6, 288); else bar_arrive(6, 288);
    ASTAMP(4);
    const int ks = p3_ks(wg), mt = p3_mt(wg);
    uint32_t v[16];
    auto fetch = [&](int seg) { ldg8x64<1024>(v, g_part + (((seg & 7) * 9 + mt) * 4 + (ks & 3)) * 1024 + (tid & 127)); };
    auto finish = [&](int seg) {
      const uint32_t tagv = (~seg >> 3) & 1;
      int n = 0;
#pragma unroll 1
      while (!(YP & 512) && stale<8, 2>(v, tagv) && ++n < SPIN_LIMIT) {
        if (seg < NSEG - 2) __nanosleep(RSL);
        fetch(seg);
      }
      float own[4] = {bf_lo(v[0]), bf_hi(v[0]), bf_lo(v[1]), bf_hi(v[1])};
#pragma unroll
      for (int j = 1; j < 8; j++) { own[0] += bf_lo(v[2 * j]); own[1] += bf_hi(v[2 * j]); own[2] += bf_lo(v[2 * j + 1]); own[3] += bf_hi(v[2 * j + 1]); }
      uint32_t p0 = pack_bf16(own[0], own[1]), p1 = pack_bf16(own[2], own[3]);
      asm volatile("movmatrix.sync.aligned.m8n8.trans.b16 %0, %0;" : "+r"(p0));
      asm volatile("movmatrix.sync.aligned.m8n8.trans.b16 %0, %0;" : "+r"(p1));
      uint32_t* o = (uint32_t*)(out + (size_t)(seg * 32 + (ks & 3) * 8 + (lane >> 2)) * DM + mt * 64 + w * 16) + (lane & 3);
      if (!(YP & 256) || p0 == 0x12345678) { o[0] = p0; o[4] = p1; }
      SSTAMP(seg, 7);
    };
    float acc[16], acc2[16];
#pragma unroll
    for (int i = 0; i < 16; i++) acc[i] = acc2[i] = 0.f;
    int pend = -1, sl = wide ? 0 : wg, ph = 0;
    if (PING && wg) bar_arrive(1, 256);
    CDECL;
    auto run = [&](auto extra) {
#pragma unroll 1
    for (int seg = 0; seg <= ((XP & 2048) ? -1 : NSEG); seg++) {
      CSTAMP(0);
      const bool fin = pend >= 0 && (seg - pend >= FLAG || seg == NSEG);
      if (seg < NSEG) mbar_wait(full3 + 8 * sl, ph);
      if (FPOS == 1 && fin) fetch(pend);
      if (SDLY) {
        uint32_t n, d;
        asm volatile("ld.volatile.shared.v2.b32 {%0,%1}, [%2];" : "=r"(n), "=r"(d) : "r"(pace) : "memory");
        if ((int)n <= seg + 3) sleep_until(d + SDLY);
      }
      CSTAMP(1);
      if (seg < NSEG) {
      if (wg) SSTAMP(seg, 5);
      if (seg < PING) bar_sync(1 + wg, 256);
      CSTAMP(7);
      const uint64_t db = make_desc(sb + sl * XT, 16, 1024, 1);
      WG_FENCE();
#pragma unroll
      for (int k = 0; k < ((XP & 1024) ? 1 : 36); k++)
        wgmma_n32_rs(TWO && (k & 1) ? acc2 : acc, wa[k][0], wa[k][1], wa[k][2], wa[k][3], db + (k >> 2) * 256 + (k & 3) * 2, k >> TWO);
      if (decltype(extra)::value) wgmma_n32_rs(acc, wa[36][0], wa[36][1], wa[36][2], wa[36][3], make_desc(sb + A_XT + sl * 1024, 16, 256, 3), 1);
      WG_COMMIT();
      if (seg < PING) bar_arrive(2 - wg, 256);
      CSTAMP(2);
      CSTAMP(3);
      WG_WAIT(0);
      CSTAMP(4);
      if (wg) SSTAMP(seg, 6);
      if (lane == 0) mbar_arrive(empty3 + 8 * sl);
      sl += wide ? 1 : 2;
      if (sl >= (wide ? 3 : 4)) { sl -= wide ? 3 : 4; ph ^= 1; }
      uint2* dst = g_part + (((seg & 7) * 9 + mt) * 32 + ks) * 128 + (tid & 127);
      uint32_t q[8];
      if (TWO)
#pragma unroll
        for (int j = 0; j < 16; j++) acc[j] += acc2[j];
#pragma unroll
      for (int j = 0; j < 8; j++) q[j] = j & 1 ? pack_bf16(acc[2 * j], acc[2 * j + 1]) : (pack_bf16(acc[2 * j], acc[2 * j + 1]) & ~1u) | ((~seg >> 3) & 1);
      if (QM & 32) tick_wait(pace, seg + (QM >> 4 & 1) + 2);
      if (!(YP & 1025) || q[0] == 0x12345678)
      asm volatile("st.relaxed.gpu.global.v2.b32 [%0], {%1,%2};\nst.relaxed.gpu.global.v2.b32 [%0 + 8192], {%3,%4};\n"
                   "st.relaxed.gpu.global.v2.b32 [%0 + 16384], {%5,%6};\nst.relaxed.gpu.global.v2.b32 [%0 + 24576], {%7,%8};"
                   :: "l"(dst), "r"(q[0]), "r"(q[1]), "r"(q[2]), "r"(q[3]), "r"(q[4]), "r"(q[5]), "r"(q[6]), "r"(q[7]) : "memory");
      }
      CSTAMP(5);
      if (fin) { finish(pend); pend = -1; }
      CSTAMP(6);
      if ((seg & 1) == ks >> 2 && !(YP & 1)) pend = seg;
      if (wg && (seg & 7) == 6) ASTAMP(5 + (seg >> 3));
    }
    };
    if (ks >= 4) run(BoolC<true>()); else run(BoolC<false>());
    if (PING && !wg) bar_sync(1, 256);
    CDUMP;
    ASTAMP(13);
    bar_sync(6, 288);
  }
}

typedef CUresult (*EncodeFn)(CUtensorMap*, CUtensorMapDataType, cuuint32_t, void*, const cuuint64_t*, const cuuint64_t*,
                             const cuuint32_t*, const cuuint32_t*, CUtensorMapInterleave, CUtensorMapSwizzle,
                             CUtensorMapL2promotion, CUtensorMapFloatOOBfill);
#define PROMO 2
static void make_map(EncodeFn enc, CUtensorMap* m, const void* p, int rows, int cols, int box_rows) {
  cuuint64_t dims[2] = {(cuuint64_t)cols, (cuuint64_t)rows};
  cuuint64_t strides[1] = {(cuuint64_t)cols * 2};
  cuuint32_t box[2] = {64, (cuuint32_t)box_rows};
  cuuint32_t es[2] = {1, 1};
  enc(m, CU_TENSOR_MAP_DATA_TYPE_BFLOAT16, 2, (void*)p, dims, strides, box, es, CU_TENSOR_MAP_INTERLEAVE_NONE,
      CU_TENSOR_MAP_SWIZZLE_128B, (CUtensorMapL2promotion)PROMO, CU_TENSOR_MAP_FLOAT_OOB_FILL_NONE);
}

constexpr int g_poll = POLL_NS;
extern "C" void kernel_launch(void* const* d_in, const int* in_sizes, int n_in, void* d_out, int out_size) {
  const bf16* x = (const bf16*)d_in[0];
  const bf16* wqkvA = (const bf16*)d_in[1];
  const bf16* woA = (const bf16*)d_in[2];
  const bf16* mem0 = (const bf16*)d_in[4];
  const bf16* Wq = (const bf16*)d_in[5];
  const bf16* Wk = (const bf16*)d_in[6];
  const bf16* Wv = (const bf16*)d_in[7];
  const bf16* Wo = (const bf16*)d_in[8];
  const bf16* gate_w = (const bf16*)d_in[10];
  static EncodeFn enc = nullptr;
  static void *pO = nullptr, *pR = nullptr;
  if (!enc) {
    cudaDriverEntryPointQueryResult qr;
    cudaGetDriverEntryPoint("cuTensorMapEncodeTiled", (void**)&enc, cudaEnableDefault, &qr);
    cudaGetSymbolAddress(&pO, g_Ocat);
    cudaGetSymbolAddress(&pR, g_red_raw);
    cudaFuncSetAttribute(rec_kernel, cudaFuncAttributeMaxDynamicSharedMemorySize, SM_TOTAL);
    cudaFuncSetAttribute(aux_kernel, cudaFuncAttributeMaxDynamicSharedMemorySize, A_TOTAL);
  }
  RMaps rm;
  rm.poll = g_poll;
  rm.w[0] = (const unsigned char*)Wk; rm.w[1] = (const unsigned char*)Wq; rm.w[2] = (const unsigned char*)Wv; rm.w[3] = (const unsigned char*)Wo;
  rm.red = (unsigned char*)(((uintptr_t)pR + 262143) & ~(uintptr_t)262143);
  {
    cuuint64_t dims[3] = {64, S_LEN, 9}, strides[2] = {DM * 2, 128};
    cuuint32_t box[3] = {64, 32, 9}, es[3] = {1, 1, 1};
    enc(&rm.x, CU_TENSOR_MAP_DATA_TYPE_BFLOAT16, 3, (void*)x, dims, strides, box, es, CU_TENSOR_MAP_INTERLEAVE_NONE,
        CU_TENSOR_MAP_SWIZZLE_128B, CU_TENSOR_MAP_L2_PROMOTION_L2_128B, CU_TENSOR_MAP_FLOAT_OOB_FILL_NONE);
  }
  make_map(enc, &rm.wq, Wq, DM, 4096, 192);
  make_map(enc, &rm.wk, Wk, DM, 4096, 192);
  make_map(enc, &rm.wv, Wv, DM, 4096, 192);
  make_map(enc, &rm.wo, Wo, 4096, DM, 128);
  AMaps am;
  am.red = rm.red; am.poll = rm.poll;
  {
    cuuint64_t dims[3] = {DM, S_LEN / 2, 2}, strides[2] = {DM * 4, DM * 2};
    cuuint32_t box[3] = {32, 64, 2}, es[3] = {1, 1, 1};
    enc(&am.x, CU_TENSOR_MAP_DATA_TYPE_BFLOAT16, 3, (void*)x, dims, strides, box, es, CU_TENSOR_MAP_INTERLEAVE_NONE,
        CU_TENSOR_MAP_SWIZZLE_64B, CU_TENSOR_MAP_L2_PROMOTION_L2_128B, CU_TENSOR_MAP_FLOAT_OOB_FILL_NONE);
    cuuint64_t wdims[3] = {DM, DM, 3}, wstrides[2] = {DM * 6, DM * 2};
    cuuint32_t wbox[3] = {64, 32, 3}, wbox8[3] = {8, 32, 3};
    enc(&am.wa, CU_TENSOR_MAP_DATA_TYPE_BFLOAT16, 3, (void*)wqkvA, wdims, wstrides, wbox, es, CU_TENSOR_MAP_INTERLEAVE_NONE,
        CU_TENSOR_MAP_SWIZZLE_128B, CU_TENSOR_MAP_L2_PROMOTION_L2_128B, CU_TENSOR_MAP_FLOAT_OOB_FILL_NONE);
    enc(&am.wa8, CU_TENSOR_MAP_DATA_TYPE_BFLOAT16, 3, (void*)wqkvA, wdims, wstrides, wbox8, es, CU_TENSOR_MAP_INTERLEAVE_NONE,
        CU_TENSOR_MAP_SWIZZLE_NONE, CU_TENSOR_MAP_L2_PROMOTION_NONE, CU_TENSOR_MAP_FLOAT_OOB_FILL_NONE);
  }
  {
    cuuint64_t dims[3] = {64, S_LEN, KCAT / 64}, strides[2] = {KCAT * 2, 128};
    cuuint32_t box[3] = {64, 32, 9}, es[3] = {1, 1, 1};
    make_map(enc, &am.o, pO, S_LEN, KCAT, 32);
    enc(&am.o3, CU_TENSOR_MAP_DATA_TYPE_BFLOAT16, 3, pO, dims, strides, box, es, CU_TENSOR_MAP_INTERLEAVE_NONE,
        CU_TENSOR_MAP_SWIZZLE_128B, CU_TENSOR_MAP_L2_PROMOTION_L2_128B, CU_TENSOR_MAP_FLOAT_OOB_FILL_NONE);
  }
  make_map(enc, &am.wob, Wo, 4096, DM, 64);
  make_map(enc, &am.woa, woA, DM, DM, 64);
  make_map(enc, &am.woa16, woA, DM, DM, 16);
  {
    cuuint64_t dims[2] = {KCAT, S_LEN}, strides[1] = {KCAT * 2};
    cuuint32_t box[2] = {16, 32}, es[2] = {1, 1};
    enc(&am.o16, CU_TENSOR_MAP_DATA_TYPE_BFLOAT16, 2, pO, dims, strides, box, es, CU_TENSOR_MAP_INTERLEAVE_NONE,
        CU_TENSOR_MAP_SWIZZLE_32B, CU_TENSOR_MAP_L2_PROMOTION_NONE, CU_TENSOR_MAP_FLOAT_OOB_FILL_NONE);
  }

  rec_kernel<<<96, 384, SM_TOTAL, cudaStreamPerThread>>>(rm, x, mem0);
  cudaLaunchConfig_t cfg = {};
  cfg.gridDim = dim3(NAUX); cfg.blockDim = dim3(512); cfg.dynamicSmemBytes = A_TOTAL; cfg.stream = cudaStreamPerThread;
  cudaLaunchAttribute at[1];
  at[0].id = cudaLaunchAttributeProgrammaticStreamSerialization; at[0].val.programmaticStreamSerializationAllowed = 1;
  cfg.attrs = at; cfg.numAttrs = 1;
  if (XP & 16) cfg.numAttrs = 0;
  if (!(XP & 64)) cudaLaunchKernelEx(&cfg, aux_kernel, am, x, gate_w, (bf16*)d_out);
}
```

```cpp
#include <cuda_runtime.h>
#include <cuda_bf16.h>
#include <cuda_fp16.h>
#include <cuda.h>
#include <stdint.h>

typedef __nv_bfloat16 bf16;

constexpr int S_LEN = 2048, DM = 576, NH = 32, DH = 128, NSEG = 64, KCAT = 4096 + 576;
#define RED_LINE(i) (((i) >> 2) * 4096 + ((i) & 1) * 256 + ((i) & 2) * 512)
#define RED_SLOT(s) (((s) & 1) * 128 + ((s) & 2) * 256)

#define POLL_NS 896
#define NII 18
#define W3PRE 4
#define W3MID 4
#define GF 0
#define B5POS 0
#define NUP 4
#define UPF 1
#define B3Q 9
#define B3F 0
#define GATE 8
#define NTL 2
#define B7R 1
#define EXPOS 0
#define VW2 1
#define CLR 1
#define RFW 0
#define NIC 0
#define LEAD 0
#define FIN16 1
#define VXG 0
#define RING 63
#define EXB 0
#define EXD 0
#define EXB2 8192
#define HDLY 0
#define F10 1
#define NPROBE 2
#define WPOS 1
#define CW 0
#define WOPF 0
#define YP 0
#define EF 7
#define MO 0
#define WE 3
#define EXV 2
#define NOB 0
#define QM 60
#define N5 224
#define KP(i) (((i) >> 1) + 4 * ((i) & 1))
#define SPIN_LIMIT (1 << 14)
#define XP 0

__device__ __align__(1024) bf16 g_Ocat[S_LEN * KCAT];
__device__ __align__(1024) unsigned char g_red_raw[2 * 262144];
constexpr int HINT_OFF = 2048;
__device__ __align__(16) float g_gate[S_LEN];
__device__ __align__(128) uint4 g_stats[96 * 2];
__device__ unsigned g_epoch;
__device__ unsigned g_epoch2;
__device__ unsigned g_oflag[NH * 32];
__device__ unsigned g_abar[3 * 32];
__device__ unsigned g_sflag[96 * 8];
__device__ __align__(1024) unsigned char g_seg[NSEG * 96 * 8192];
__device__ __align__(1024) unsigned char g_km[NSEG * NH * 4096];
__device__ __align__(1024) uint2 g_part[8 * 9 * 4 * 8 * 128];
__device__ int g_err;
#define SSTAMP(seg, idx)
#define TSTAMP(idx)
#define QSTAMP(idx)
#define PROF(idx)
#define PROFP(idx)
#define STAMP(idx)
#define ASTAMP(idx)
#define WSTAMP(idx)

#define CSTAMP(idx)
#define CDECL
#define CDUMP
#define DI __device__ __forceinline__
DI uint32_t smem_u32(const void* p) { return (uint32_t)__cvta_generic_to_shared(p); }
DI uint32_t clock32() { uint32_t c; asm volatile("mov.u32 %0, %%clock;" : "=r"(c) :: "memory"); return c; }
DI uint32_t gtime() { uint32_t c; asm volatile("mov.u32 %0, %%globaltimer_lo;" : "=r"(c) :: "memory"); return c; }
DI uint32_t ldg_relaxed32(const void* p) { uint32_t v; asm volatile("ld.relaxed.gpu.global.b32 %0, [%1];" : "=r"(v) : "l"(p) : "memory"); return v; }
DI uint32_t ldg_acquire32(const void* p) { uint32_t v; asm volatile("ld.acquire.gpu.global.b32 %0, [%1];" : "=r"(v) : "l"(p) : "memory"); return v; }
DI void stg_relaxed32(void* p, uint32_t v) { asm volatile("st.relaxed.gpu.global.b32 [%0], %1;" :: "l"(p), "r"(v) : "memory"); }
DI int head_id() { int c; asm volatile("mov.u32 %0, %%clusterid.x;" : "=r"(c)); return c; }
DI uint32_t mapa(uint32_t a, uint32_t r) { uint32_t o; asm("mapa.shared::cluster.u32 %0, %1, %2;" : "=r"(o) : "r"(a), "r"(r)); return o; }
DI void cluster_arrive() { asm volatile("barrier.cluster.arrive.relaxed.aligned;" ::: "memory"); }
DI void cluster_wait() { asm volatile("barrier.cluster.wait.aligned;" ::: "memory"); }
DI void cluster_sync() { asm volatile("barrier.cluster.arrive.release.aligned;\nbarrier.cluster.wait.acquire.aligned;" ::: "memory"); }
DI void mbar_init(uint32_t b, uint32_t c) { asm volatile("mbarrier.init.shared::cta.b64 [%0], %1;" :: "r"(b), "r"(c) : "memory"); }
DI void mbar_expect(uint32_t b, uint32_t tx) { asm volatile("mbarrier.arrive.expect_tx.shared::cta.b64 _, [%0], %1;" :: "r"(b), "r"(tx) : "memory"); }
DI void mbar_arrive(uint32_t b) { asm volatile("mbarrier.arrive.shared::cta.b64 _, [%0];" :: "r"(b) : "memory"); }
DI void mbar_wait(uint32_t b, uint32_t par) {
  asm volatile("{\n.reg .pred p;\n.reg .u32 n, q;\nmov.u32 n, 0;\n"
               "WL: add.u32 n, n, 1;\nshr.u32 q, n, 12;\nxor.b32 q, q, %1;\n"
               "mbarrier.try_wait.parity.shared::cta.b64 p, [%0], q;\n@!p bra.uni WL;\n}"
               :: "r"(b), "r"(par) : "memory");
}
DI void wait_until(uint32_t t) {
  const uint32_t now = gtime();
  t = min(t, now + 8192);
  asm volatile("{\n.reg .pred p;\n.reg .u32 c;\nTL: mov.u32 c, %%globaltimer_lo;\nsetp.lt.u32 p, c, %0;\n@p bra.uni TL;\n}" :: "r"(t) : "memory");
}
#define PIN(v) v = __shfl_xor_sync(0xffffffffu, v, 0)
#define SCHED_FENCE(k) asm volatile("{\n.reg .pred p;\nsetp.eq.u32 p, %0, %1;\n@p exit;\n}" :: "r"(fence_reg), "r"(k) : "memory")
#define MEM_ORDER(k) asm volatile("{\n.reg .pred p;\nsetp.eq.u32 p, %0, %1;\n@p st.shared.u32 [%0], %0;\n}" :: "r"(fence_reg), "r"(k + 64) : "memory")
DI void bar_sync(int id, int n) { asm volatile("bar.sync %0, %1;" :: "r"(id), "r"(n) : "memory"); }
DI void bar_arrive(int id, int n) { asm volatile("bar.arrive %0, %1;" :: "r"(id), "r"(n) : "memory"); }
DI void fence_async() { asm volatile("fence.proxy.async.shared::cta;" ::: "memory"); }
DI void st_async4(uint32_t a, uint32_t x, uint32_t y, uint32_t z, uint32_t w, uint32_t mb) {
  asm volatile("st.async.weak.shared::cluster.mbarrier::complete_tx::bytes.v4.b32 [%0], {%1,%2,%3,%4}, [%5];"
               :: "r"(a), "r"(x), "r"(y), "r"(z), "r"(w), "r"(mb) : "memory");
}
DI void st_async2(uint32_t a, uint32_t x, uint32_t y, uint32_t mb) {
  asm volatile("st.async.weak.shared::cluster.mbarrier::complete_tx::bytes.v2.b32 [%0], {%1,%2}, [%3];"
               :: "r"(a), "r"(x), "r"(y), "r"(mb) : "memory");
}
DI void sts32(uint32_t a, uint32_t x) { asm volatile("st.shared.b32 [%0], %1;" :: "r"(a), "r"(x) : "memory"); }
DI void sts64(uint32_t a, uint32_t x, uint32_t y) { asm volatile("st.shared.v2.b32 [%0], {%1,%2};" :: "r"(a), "r"(x), "r"(y) : "memory"); }
DI void sts128(uint32_t a, uint32_t x, uint32_t y, uint32_t z, uint32_t w) {
  asm volatile("st.shared.v4.b32 [%0], {%1,%2,%3,%4};" :: "r"(a), "r"(x), "r"(y), "r"(z), "r"(w) : "memory");
}
DI uint32_t lds32(uint32_t a) { uint32_t x; asm volatile("ld.shared.b32 %0, [%1];" : "=r"(x) : "r"(a) : "memory"); return x; }
DI uint32_t lds32v(uint32_t a) { uint32_t x; asm volatile("ld.volatile.shared.b32 %0, [%1];" : "=r"(x) : "r"(a) : "memory"); return x; }
DI void lds64(uint32_t a, uint32_t& x, uint32_t& y) { asm volatile("ld.shared.v2.b32 {%0,%1}, [%2];" : "=r"(x), "=r"(y) : "r"(a) : "memory"); }
DI void lds128(uint32_t a, uint32_t* r) {
  asm volatile("ld.shared.v4.b32 {%0,%1,%2,%3}, [%4];" : "=r"(r[0]), "=r"(r[1]), "=r"(r[2]), "=r"(r[3]) : "r"(a) : "memory");
}
DI void lds128f(uint32_t a, float* r) {
  asm volatile("ld.shared.v4.f32 {%0,%1,%2,%3}, [%4];" : "=f"(r[0]), "=f"(r[1]), "=f"(r[2]), "=f"(r[3]) : "r"(a) : "memory");
}
DI void lds64f(uint32_t a, float* r) { asm volatile("ld.shared.v2.f32 {%0,%1}, [%2];" : "=f"(r[0]), "=f"(r[1]) : "r"(a) : "memory"); }
DI void ldsm4t(uint32_t* r, uint32_t a) {
  asm volatile("ldmatrix.sync.aligned.m8n8.x4.trans.shared.b16 {%0,%1,%2,%3}, [%4];"
               : "=r"(r[0]), "=r"(r[1]), "=r"(r[2]), "=r"(r[3]) : "r"(a) : "memory");
}
DI void ldsm4t_in(uint32_t* r, uint32_t a, uint32_t t) {
  asm volatile("{\n.reg .pred p;\nsetp.ne.u32 p, %5, 0;\n@p ldmatrix.sync.aligned.m8n8.x4.trans.shared.b16 {%0,%1,%2,%3}, [%4];\n}"
               : "+r"(r[0]), "+r"(r[1]), "+r"(r[2]), "+r"(r[3]) : "r"(a), "r"(t) : "memory");
}
DI void lds128_in(uint32_t* r, uint32_t a, uint32_t t) {
  asm volatile("{\n.reg .pred p;\nsetp.ne.u32 p, %5, 0;\n@p ld.shared.v4.b32 {%0,%1,%2,%3}, [%4];\n}"
               : "+r"(r[0]), "+r"(r[1]), "+r"(r[2]), "+r"(r[3]) : "r"(a), "r"(t) : "memory");
}
DI void ldsm2t_in(uint32_t* r, uint32_t a, uint32_t t) {
  asm volatile("{\n.reg .pred p;\nsetp.ne.u32 p, %3, 0;\n@p ldmatrix.sync.aligned.m8n8.x2.trans.shared.b16 {%0,%1}, [%2];\n}" : "+r"(r[0]), "+r"(r[1]) : "r"(a), "r"(t) : "memory");
}
DI void reserve2(uint32_t* r) { asm volatile("{\n.reg .u64 t;\nmov.u64 t, %%clock64;\nmov.b64 {%0, %1}, t;\n}" : "=r"(r[0]), "=r"(r[1])); }
DI void scale_sum(float& x, float& y, float s, uint32_t t) {
  asm volatile("{\n.reg .pred p;\nsetp.ne.u32 p, %2, 0;\n@p mul.f32 %0, %0, %1;\n}" : "+f"(y) : "f"(s), "r"(t));
  asm volatile("{\n.reg .pred p;\nsetp.ne.u32 p, %3, 1;\n@p fma.rn.f32 %0, %0, %1, %2;\n}" : "+f"(x) : "f"(s), "f"(y), "r"(t));
}
DI void ldsm4(uint32_t* r, uint32_t a) {
  asm volatile("ldmatrix.sync.aligned.m8n8.x4.shared.b16 {%0,%1,%2,%3}, [%4];"
               : "=r"(r[0]), "=r"(r[1]), "=r"(r[2]), "=r"(r[3]) : "r"(a) : "memory");
}
DI void st_async1(uint32_t a, uint32_t x, uint32_t mb) {
  asm volatile("st.async.weak.shared::cluster.mbarrier::complete_tx::bytes.b32 [%0], %1, [%2];" :: "r"(a), "r"(x), "r"(mb) : "memory");
}
DI void stsm4(uint32_t a, uint32_t x, uint32_t y, uint32_t z, uint32_t w) {
  asm volatile("stmatrix.sync.aligned.m8n8.x4.shared.b16 [%0], {%1,%2,%3,%4};" :: "r"(a), "r"(x), "r"(y), "r"(z), "r"(w) : "memory");
}
DI void stsm4t(uint32_t a, uint32_t x, uint32_t y, uint32_t z, uint32_t w) {
  asm volatile("stmatrix.sync.aligned.m8n8.x4.trans.shared.b16 [%0], {%1,%2,%3,%4};" :: "r"(a), "r"(x), "r"(y), "r"(z), "r"(w) : "memory");
}
DI uint32_t pack_bf16(float lo, float hi) { uint32_t r; asm("cvt.rn.bf16x2.f32 %0, %1, %2;" : "=r"(r) : "f"(hi), "f"(lo)); return r; }
DI uint32_t pack_f16(float lo, float hi) { uint32_t r; asm("cvt.rn.f16x2.f32 %0, %1, %2;" : "=r"(r) : "f"(hi), "f"(lo)); return r; }
DI float ex2(float x) { float y; asm("ex2.approx.ftz.f32 %0, %1;" : "=f"(y) : "f"(x)); return y; }
DI float rcp(float x) { float y; asm("rcp.approx.ftz.f32 %0, %1;" : "=f"(y) : "f"(x)); return y; }
DI float bf_lo(uint32_t x) { return __uint_as_float(x << 16); }
DI float bf_hi(uint32_t x) { return __uint_as_float(x & 0xffff0000u); }
DI void mma16816(float* d, const uint32_t* a, uint32_t b0, uint32_t b1) {
  asm volatile("mma.sync.aligned.m16n8k16.row.col.f32.bf16.bf16.f32 {%0,%1,%2,%3}, {%4,%5,%6,%7}, {%8,%9}, {%0,%1,%2,%3};"
               : "+f"(d[0]), "+f"(d[1]), "+f"(d[2]), "+f"(d[3]) : "r"(a[0]), "r"(a[1]), "r"(a[2]), "r"(a[3]), "r"(b0), "r"(b1));
}
DI void mma16816z(float* d, const uint32_t* a, uint32_t b0, uint32_t b1) {
  asm volatile("mma.sync.aligned.m16n8k16.row.col.f32.bf16.bf16.f32 {%0,%1,%2,%3}, {%4,%5,%6,%7}, {%8,%9}, {%10,%10,%10,%10};"
               : "=f"(d[0]), "=f"(d[1]), "=f"(d[2]), "=f"(d[3]) : "r"(a[0]), "r"(a[1]), "r"(a[2]), "r"(a[3]), "r"(b0), "r"(b1), "f"(0.f));
}
DI void mma1688z(float* d, uint32_t a0, uint32_t a1, uint32_t b0) {
  asm volatile("mma.sync.aligned.m16n8k8.row.col.f32.bf16.bf16.f32 {%0,%1,%2,%3}, {%4,%5}, {%6}, {%7,%7,%7,%7};"
               : "=f"(d[0]), "=f"(d[1]), "=f"(d[2]), "=f"(d[3]) : "r"(a0), "r"(a1), "r"(b0), "f"(0.f));
}
DI void mma1688(float* d, uint32_t a0, uint32_t a1, uint32_t b0) {
  asm volatile("mma.sync.aligned.m16n8k8.row.col.f32.bf16.bf16.f32 {%0,%1,%2,%3}, {%4,%5}, {%6}, {%0,%1,%2,%3};"
               : "+f"(d[0]), "+f"(d[1]), "+f"(d[2]), "+f"(d[3]) : "r"(a0), "r"(a1), "r"(b0));
}
DI void ldsm2t(uint32_t* r, uint32_t a) {
  asm volatile("ldmatrix.sync.aligned.m8n8.x2.trans.shared.b16 {%0,%1}, [%2];" : "=r"(r[0]), "=r"(r[1]) : "r"(a) : "memory");
}
DI uint32_t add_bf16(uint32_t a, uint32_t b) { uint32_t r; asm("add.rn.bf16x2 %0, %1, %2;" : "=r"(r) : "r"(a), "r"(b)); return r; }
DI uint32_t mul_bf16(uint32_t a, uint32_t b) { uint32_t r; asm("mul.rn.bf16x2 %0, %1, %2;" : "=r"(r) : "r"(a), "r"(b)); return r; }
DI uint64_t make_desc(uint32_t addr, uint32_t lbo, uint32_t sbo, uint32_t swz) {
  return (uint64_t)((addr & 0x3FFFF) >> 4) | ((uint64_t)(lbo >> 4) << 16) | ((uint64_t)(sbo >> 4) << 32) | ((uint64_t)swz << 62);
}
#define WG_FENCE() asm volatile("wgmma.fence.sync.aligned;" ::: "memory")
#define WG_COMMIT() asm volatile("wgmma.commit_group.sync.aligned;" ::: "memory")
#define WG_WAIT(n) asm volatile("wgmma.wait_group.sync.aligned %0;" :: "n"(n) : "memory")
#define ACC8(d, o) "+f"(d[o]), "+f"(d[o + 1]), "+f"(d[o + 2]), "+f"(d[o + 3]), "+f"(d[o + 4]), "+f"(d[o + 5]), "+f"(d[o + 6]), "+f"(d[o + 7])
DI void wgmma_n32_rs(float* d, uint32_t a0, uint32_t a1, uint32_t a2, uint32_t a3, uint64_t db, int acc) {
  asm volatile("{\n.reg .pred p;\nsetp.ne.b32 p, %21, 0;\n"
               "wgmma.mma_async.sync.aligned.m64n32k16.f32.bf16.bf16 {%0,%1,%2,%3,%4,%5,%6,%7,%8,%9,%10,%11,%12,%13,%14,%15}, "
               "{%16,%17,%18,%19}, %20, p, 1, 1, 0;\n}\n"
               : ACC8(d, 0), ACC8(d, 8) : "r"(a0), "r"(a1), "r"(a2), "r"(a3), "l"(db), "r"(acc));
}
template <int TA>
DI void wgmma_n32_ss(float* d, uint64_t da, uint64_t db, int acc) {
  asm volatile("{\n.reg .pred p;\nsetp.ne.b32 p, %18, 0;\n"
               "wgmma.mma_async.sync.aligned.m64n32k16.f32.bf16.bf16 {%0,%1,%2,%3,%4,%5,%6,%7,%8,%9,%10,%11,%12,%13,%14,%15}, "
               "%16, %17, p, 1, 1, %19, 1;\n}\n"
               : ACC8(d, 0), ACC8(d, 8) : "l"(da), "l"(db), "r"(acc), "n"(TA));
}
DI void tma_load(uint32_t dst, const CUtensorMap* m, int c0, int c1, uint32_t mb) {
  asm volatile("cp.async.bulk.tensor.2d.shared::cluster.global.mbarrier::complete_tx::bytes [%0], [%1, {%3, %4}], [%2];"
               :: "r"(dst), "l"(m), "r"(mb), "r"(c0), "r"(c1) : "memory");
}
DI void tma_load3(uint32_t dst, const CUtensorMap* m, int row, uint32_t mb) {
  asm volatile("cp.async.bulk.tensor.3d.shared::cluster.global.mbarrier::complete_tx::bytes [%0], [%1, {%3, %4, %3}], [%2];"
               :: "r"(dst), "l"(m), "r"(mb), "r"(0), "r"(row) : "memory");
}
DI bool elect_one() {
  uint32_t p;
  asm volatile("{\n.reg .pred p;\nelect.sync _|p, 0xffffffff;\nselp.u32 %0, 1, 0, p;\n}" : "=r"(p));
  return p;
}
DI void bulk_s2s(uint32_t dst, uint32_t src, uint32_t bytes, uint32_t mb) {
  asm volatile("cp.async.bulk.shared::cluster.shared::cta.mbarrier::complete_tx::bytes [%0], [%1], %2, [%3];"
               :: "r"(dst), "r"(src), "r"(bytes), "r"(mb) : "memory");
}
DI void bulk_load(uint32_t dst, const void* src, uint32_t bytes, uint32_t mb) {
  asm volatile("cp.async.bulk.shared::cluster.global.mbarrier::complete_tx::bytes [%0], [%1], %2, [%3];" :: "r"(dst), "l"(src), "r"(bytes), "r"(mb) : "memory");
}
#define EVICT_FIRST ".reg .b64 pol;\ncreatepolicy.fractional.L2::evict_first.b64 pol, 1.0;\n"
DI void bulk_load_ef(uint32_t dst, const void* src, uint32_t bytes, uint32_t mb) {
  asm volatile("{\n" EVICT_FIRST "cp.async.bulk.shared::cluster.global.mbarrier::complete_tx::bytes.L2::cache_hint [%0], [%1], %2, [%3], pol;\n}"
               :: "r"(dst), "l"(src), "r"(bytes), "r"(mb) : "memory");
}
DI void tma_load_ef(uint32_t dst, const CUtensorMap* m, int c0, int c1, uint32_t mb) {
  asm volatile("{\n" EVICT_FIRST "cp.async.bulk.tensor.2d.shared::cluster.global.mbarrier::complete_tx::bytes.L2::cache_hint [%0], [%1, {%3, %4}], [%2], pol;\n}"
               :: "r"(dst), "l"(m), "r"(mb), "r"(c0), "r"(c1) : "memory");
}
DI void tma_prefetch(const CUtensorMap* m, int c0, int c1) {
  asm volatile("cp.async.bulk.prefetch.tensor.2d.L2.global.tile [%0, {%1, %2}];" :: "l"(m), "r"(c0), "r"(c1) : "memory");
}
DI void tma_store(const CUtensorMap* m, uint32_t src, int c0, int c1) {
  asm volatile("cp.async.bulk.tensor.2d.global.shared::cta.bulk_group [%0, {%2, %3}], [%1];" :: "l"(m), "r"(src), "r"(c0), "r"(c1) : "memory");
}
DI uint4 ldg_relaxed(const void* p) {
  uint4 v;
  asm volatile("ld.relaxed.gpu.global.v4.b32 {%0,%1,%2,%3}, [%4];" : "=r"(v.x), "=r"(v.y), "=r"(v.z), "=r"(v.w) : "l"(p) : "memory");
  return v;
}
DI void stg_relaxed(void* p, uint32_t x, uint32_t y, uint32_t z, uint32_t w) {
  asm volatile("st.relaxed.gpu.global.v4.b32 [%0], {%1,%2,%3,%4};" :: "l"(p), "r"(x), "r"(y), "r"(z), "r"(w) : "memory");
}
DI void red_f16x8(void* p, uint32_t x, uint32_t y, uint32_t z, uint32_t w) {
  asm volatile("red.relaxed.gpu.global.add.noftz.v4.f16x2 [%0], {%1,%2,%3,%4};" :: "l"(p), "r"(x), "r"(y), "r"(z), "r"(w) : "memory");
}
DI void sq_acc(uint32_t& a, uint32_t x) { asm("fma.rn.bf16x2 %0, %1, %1, %0;" : "+r"(a) : "r"(x)); }
DI __half2 amax4(__half2 h, const uint32_t* v) {
  h = __hmax2_nan(__hmax2_nan(h, __habs2(*(const __half2*)&v[0])), __habs2(*(const __half2*)&v[1]));
  return __hmax2_nan(__hmax2_nan(h, __habs2(*(const __half2*)&v[2])), __habs2(*(const __half2*)&v[3]));
}
DI uint32_t wexp(__half2 h) { const uint32_t u = *(const uint32_t*)&h; return __reduce_max_sync(0xffffffffu, max((u >> 16) & 0x7fffu, u & 0x7fffu)) >> 7; }
DI float max10(const float* a) {
  return fmaxf(fmaxf(fmaxf(fmaxf(a[0], a[1]), fmaxf(a[2], a[3])), fmaxf(fmaxf(a[4], a[5]), fmaxf(a[6], a[7]))), fmaxf(a[8], a[9]));
}
DI float quad_max(float m) {
  return fmaxf(fmaxf(m, __shfl_xor_sync(0xffffffffu, m, 1)), fmaxf(__shfl_xor_sync(0xffffffffu, m, 2), __shfl_xor_sync(0xffffffffu, m, 3)));
}
DI float warp_sum(float v) {
#pragma unroll
  for (int o = 16; o; o >>= 1) v += __shfl_xor_sync(0xffffffffu, v, o);
  return v;
}

constexpr int SM_WO3 = 0;
constexpr int SM_X = 16384;
constexpr int XT = 36864;
constexpr int SM_EXP = 126976;
constexpr int SEGB = 10240;
constexpr int SM_BLK = SM_EXP + 8192;
constexpr int SM_VC = SM_BLK + 4 * SEGB;
constexpr int SM_PART = SM_VC + 16384;
constexpr int SM_QM = SM_PART + 4096;
constexpr int SM_E = SM_QM + 1024;
constexpr int SM_VM = SM_E + 1536;
constexpr int SM_OB = SM_VM + 2048;
constexpr int SM_FB = SM_OB + 2048;
constexpr int SM_STAGE = SM_X + XT;
constexpr int SM_M0 = SM_STAGE + 3 * 49152;
constexpr int SM_MISC = 210944;
constexpr int SM_WOST = 212992;
constexpr int SM_MEM = SM_WOST;
constexpr int SM_MAX = SM_MEM + 11264;
#define MEM_BLK(q) ((q) / 3 * 4096 + (q) % 3 * 1024)
constexpr int SM_TOTAL = 229376;
constexpr int MB_W = SM_MISC;
constexpr int MB_WO = SM_MISC + 24;
constexpr int MB_WO3 = SM_MISC + 32;
constexpr int MB_X = SM_MISC + 40;
constexpr int MB_S = SM_MISC + 64;
constexpr int MB_F = SM_MISC + 72;
constexpr int MB_VX = SM_MISC + 80;
constexpr int SC_FPAR = SM_MISC + 136;
constexpr int SC_DEAD = SM_MISC + 96;
constexpr int SC_UNSC = SM_MISC + 112;
constexpr int SC_EXPW = SM_MISC + 132;
constexpr int SC_ONES = SM_MISC + 144;
constexpr int SC_SS = SM_MISC + 160;
constexpr int SC_LAT = SM_MISC + 224;
constexpr int SC_EPO = SM_MISC + 240;
constexpr int MB_XS = SM_MISC + 248;
constexpr int SC_XMAX = SM_MISC + 256;
constexpr int SC_PROF = 229376;

constexpr float SM_SCALE = 0.08838834764831845f;
constexpr float LOG2E = 1.4426950408889634f;
constexpr float E_LIM = 20.f;

template <bool B> struct BoolC { static constexpr bool value = B; };
template <int I> struct IntC { static constexpr int value = I; };
struct RMaps { CUtensorMap x, wq, wk, wv, wo; unsigned char* red; uint32_t poll; const unsigned char* w[4]; };

DI uint32_t latest_hint(uint32_t h, uint32_t d, int s) {
  const uint32_t x = (((h | 0xc0c0c0c0u) - ((d >> 5) & 63) * 0x01010101u) & 0x3f3f3f3fu) | ((h ^ (((s >> 2) + 1) & 3) * 0x40404040u) & 0xc0c0c0c0u);
  const uint32_t y = __vmaxu2(x & 0x00ff00ffu, (x >> 8) & 0x00ff00ffu);
  return __reduce_max_sync(0xffffffffu, max(y & 0xffffu, y >> 16));
}
DI uint32_t near_half(uint32_t sb) {
  uint32_t a, b; lds64(sb + SC_LAT, a, b);
  return a > b;
}

template <int RT, int K0, int K1, bool D32 = false>
DI void xproj(float* acc, const uint32_t (&wa)[2][18][4], uint64_t xd) {
  if (XP & 1) return;
  WG_FENCE();
#pragma unroll
  for (int k = K0; k < ((XP & 128) ? K0 + 1 : K1); k++)
  {
    uint64_t d = xd + (uint64_t)(((k >> 1) * 4096 + (k & 1) * 32) >> 4);
    if (D32) asm("mov.b64 %0, {%1, %2};" : "=l"(d) : "r"((uint32_t)xd + (((k >> 1) * 4096 + (k & 1) * 32) >> 4)), "r"((uint32_t)(xd >> 32)));
    wgmma_n32_rs(acc, wa[RT][k][0], wa[RT][k][1], wa[RT][k][2], wa[RT][k][3], d, k != 0);
  }
  WG_COMMIT();
}

DI void load_w(uint32_t sb, const RMaps& tm, uint32_t rank, int c) {
  const int h = blockIdx.x / 3;
  mbar_expect(sb + MB_W + 8 * c, 49152);
  ((EF & 4) ? tma_load_ef : tma_load)(sb + SM_STAGE + c * 49152, rank < 2 ? &tm.wk : &tm.wv, h * DH + (rank == 1 ? 64 : 0), c * 192, sb + MB_W + 8 * c);
  ((EF & 4) ? tma_load_ef : tma_load)(sb + SM_STAGE + c * 49152 + 24576, rank < 2 ? &tm.wq : &tm.wv, h * DH + (rank == 0 ? 0 : 64), c * 192, sb + MB_W + 8 * c);
}
DI void seg_store(int seg, uint32_t sb) {
  fence_async();
  if (EF & 1)
    asm volatile("{\n" EVICT_FIRST "cp.async.bulk.global.shared::cta.bulk_group.L2::cache_hint [%0], [%1], 8192, pol;\n}"
                 :: "l"(g_seg + ((size_t)(seg & RING) * 96 + blockIdx.x) * 8192), "r"(sb + SM_BLK + (seg & 3) * SEGB) : "memory");
  else
  asm volatile("cp.async.bulk.global.shared::cta.bulk_group [%0], [%1], 8192;"
               :: "l"(g_seg + ((size_t)(seg & RING) * 96 + blockIdx.x) * 8192), "r"(sb + SM_BLK + (seg & 3) * SEGB) : "memory");
  asm volatile("cp.async.bulk.commit_group;" ::: "memory");
}
DI void seg_publish(int seg, uint32_t sb) {
  const uint32_t v = lds32(sb + SC_EPO) + seg;
  asm volatile("cp.async.bulk.wait_group 0;" ::: "memory");
  stg_relaxed32(&g_sflag[blockIdx.x * 8], v);
}

DI void proj_role(const uint32_t sb, const RMaps& tm, const bf16* __restrict__ x, const uint32_t rank, const int wg, const int w, const int lane) {
  const bool qk = rank < 2;
  uint32_t wa[2][18][4];
  float acc[16];
  const uint64_t xd0 = make_desc(sb + SM_X + wg * 64, 16, 1024, 1);
  {
    const int rr = (lane & 7) + ((lane >> 4) << 3);
    const uint32_t col = ((2 * w + ((lane >> 3) & 1)) ^ (lane & 7)) << 4;
    float ss = 0.f;
    bar_sync(3, 256);
    mbar_wait(sb + MB_X, 0);
    auto chunk = [&](auto cc) {
      constexpr int c = decltype(cc)::value;
      QSTAMP(2 + 2 * c);
      mbar_wait(sb + MB_W + 8 * c, 0);
      QSTAMP(3 + 2 * c);
#pragma unroll
      for (int rt = 1; rt >= 0; rt--)
#pragma unroll
        for (int k = 0; k < 6; k++)
          ldsm4t(wa[rt][c * 6 + k], sb + SM_STAGE + c * 49152 + (rt ^ wg) * 24576 + (64 * (k >> 1) + 32 * wg + 16 * (k & 1) + rr) * 128 + col);
      fence_async();
      if (c < 2) {
        bar_sync(3, 256);
        QSTAMP(17 + c);
        if (threadIdx.x == 0) {
          if (c == 0) tma_load(sb + SM_X + XT, &tm.wo, rank * 192, (blockIdx.x / 3) * DH, sb + MB_WO);
          else if (blockIdx.x < NSEG) bulk_load(sb + SM_X + 2 * XT, x + blockIdx.x * 32 * DM, XT, sb + MB_XS);
          else tma_load3(sb + SM_X + 2 * XT, &tm.x, 64, sb + MB_X + 16);
        }
        __syncwarp();
      } else {
        cluster_arrive();
      }
      xproj<1, 6 * c, 6 * c + 6>(acc, wa, xd0);
      if (!qk) {
        uint32_t q[4] = {0, 0, 0, 0};
#pragma unroll
        for (int rt = 0; rt < 2; rt++)
#pragma unroll
          for (int k = 0; k < 6; k++)
#pragma unroll
            for (int i = 0; i < 4; i++) sq_acc(q[i], wa[rt][c * 6 + k][i]);
#pragma unroll
        for (int i = 0; i < 4; i++) ss += bf_lo(q[i]) + bf_hi(q[i]);
      }
      if (c < 2 && CW) WG_WAIT(0);
    };
    chunk(IntC<0>()); chunk(IntC<1>()); chunk(IntC<2>());
    ss = warp_sum(ss);
    if (lane == 0) sts32(sb + SC_SS + 4 * (wg * 4 + w), __float_as_uint(ss));
    bar_arrive(11, 384);
  }
  STAMP(1);
  QSTAMP(8);
  STAMP(2);

  uint32_t t16 = sb + (w * 32 + lane) * 16;
  uint32_t mem_a = sb + SM_MEM + wg * 512 + lane * 16;
  uint32_t fin_a = sb + (lane & 7) * 16 + SM_BLK + (qk ? (wg ^ 1) * 4096 + w * 256 + (lane & 8) * 16 + (lane & 16) * 64
                                              : wg * 4096 + w * 1024 + (lane & 8) * 64 + (lane & 16) * 8);
  PIN(t16); PIN(mem_a); PIN(fin_a);
  const uint32_t fence_reg = mem_a;
  const uint32_t fin2 = qk ? 2048 : 256;
  auto do_export = [&](auto retire, uint32_t always) {
    WG_WAIT(0);
    uint32_t p[2];
#pragma unroll
    for (int i = 0; i < 2; i++) {
      p[i] = pack_bf16(acc[8 * i], acc[8 * i + 1]);
      sts128(t16 + SM_EXP + wg * 4096 + i * 2048, p[i], pack_bf16(acc[8 * i + 2], acc[8 * i + 3]),
             pack_bf16(acc[8 * i + 4], acc[8 * i + 5]), pack_bf16(acc[8 * i + 6], acc[8 * i + 7]));
    }
    if (decltype(retire)::value)
      asm volatile("{\n.reg .pred p, q;\nsetp.ne.u32 p, %2, 0;\nsetp.ne.u32 q, %2, 1;\n@p ld.shared.b32 %0, [%3];\n@q ld.shared.b32 %1, [%3 + 4];\n"
                   "setp.ne.u32 p, %0, %1;\n@p exit;\n}" : "+r"(p[0]), "+r"(p[1]) : "r"(always), "r"(sb + SC_DEAD) : "memory");
  };
  uint32_t o[8];
  auto import = [&]() { lds128(t16 + SM_EXP + (wg ^ 1) * 4096, o); lds128(t16 + SM_EXP + (wg ^ 1) * 4096 + 2048, o + 4); };
  auto finish_from = [&](int seg, const float* d) {
    const uint32_t a = fin_a + (seg & 3) * SEGB;
#pragma unroll
    for (int i = 0; i < 8; i++) o[i] = add_bf16(pack_bf16(d[2 * i], d[2 * i + 1]), o[i]);
    stsm4(a, o[0], o[1], o[2], o[3]);
    stsm4(a + fin2, o[4], o[5], o[6], o[7]);
  };
  auto finish = [&](int seg) { WG_WAIT(0); finish_from(seg, acc); };
  auto send_v = [&](int seg, int dst) {
    fence_async();
    if (seg < NSEG - 1 && !(XP & 2) && elect_one())
      bulk_s2s(mapa(sb + SM_VC + (seg & 1) * 8192, dst), sb + SM_BLK + (seg & 3) * SEGB, 8192, mapa(sb + MB_VX + (seg & 1) * 8, dst));
    __syncwarp();
  };
  auto wait_v = [&](int seg) {
    if (seg < NSEG - 1 && !(XP & 2)) {
      mbar_wait(sb + MB_VX + (seg & 1) * 8, (seg >> 1) & 1);
      if (elect_one()) mbar_expect(sb + MB_VX + (seg & 1) * 8, 8192);
      __syncwarp();
    }
  };
  auto export_seg = [&](int seg) { if (!(XP & (4 | 8192)) && elect_one()) seg_store(seg, sb); __syncwarp(); };
  auto publish = [&](int seg) { if (!(XP & (4 | 16384)) && elect_one()) seg_publish(seg, sb); __syncwarp(); };
  do_export(BoolC<false>(), 0);
  QSTAMP(9);
  SCHED_FENCE(11);
  xproj<0, 0, 18>(acc, wa, xd0);
  bar_sync(3, 256);
  QSTAMP(10);
  cluster_wait();
  QSTAMP(11);
  mbar_wait(sb + MB_X + 8, 0);
  QSTAMP(12);
  import();
  finish(0);
  SCHED_FENCE(12);
  uint64_t dA = xd0 + (XT >> 4);
  xproj<1, 0, 18>(acc, wa, dA);
  bar_sync(3, 256);
  if (!qk && wg == 0 && w < 2) send_v(0, w);
  if (!(EXV & 1) && wg == 0 && w == 3) export_seg(0);
  QSTAMP(13);
  if (qk && wg == 0 && w == 0) wait_v(0);
  QSTAMP(14);
  bar_arrive(13, 384);
  if (!qk) {
    do_export(BoolC<false>(), 0);
    SCHED_FENCE(15);
    xproj<0, 0, 18>(acc, wa, dA);
    if (threadIdx.x == 0 && !(XP & 8)) { mbar_expect(sb + MB_X, XT); tma_load3(sb + SM_X, &tm.x, 96, sb + MB_X); }
    bar_sync(3, 256);
    mbar_wait(sb + MB_X + 16, 0);
    import();
    finish(1);
    SCHED_FENCE(16);
    dA += XT >> 4;
    xproj<1, 0, 18>(acc, wa, dA);
    if (!(EXV & 2)) bar_sync(3, 256);
    if (!(EXV & 2) && wg == 0 && w < VW2) send_v(1, w);
  }
  QSTAMP(15);
  WG_WAIT(0);
  bar_sync(0, 384);
  if (!(EXV & 1) && wg == 0 && w == 3) publish(0);
  QSTAMP(16);
  const int ro = __shfl_sync(0xffffffffu, near_half(sb) ^ wg, 0);
  STAMP(5);
  const uint32_t always = __shfl_sync(0xffffffffu, lds32(sb + SC_DEAD + 12), 0);
  const int ah = qk ? 1 : 2;
  int b2 = qk ? 2 : 0;
  int s = 0;
  uint32_t hint_lo = (uint32_t)(uint64_t)tm.red + HINT_OFF + blockIdx.x + (lane & 1) * 4096 + (lane >> 1) * 16384;
  PIN(hint_lo);
  auto post_hint = [&]() {
    asm volatile("{\n.reg .pred p;\n.reg .b64 a;\n.reg .u32 t;\nsetp.lt.u32 p, %0, %1;\nmov.b64 a, {%2, %3};\nmov.u32 t, %%globaltimer_lo;\n"
                 "bfe.u32 t, t, 5, 6;\nor.b32 t, t, %4;\n@p st.relaxed.gpu.global.u8 [a], t;\n}"
                 :: "r"(t16), "r"(sb + 160), "r"(hint_lo + RED_SLOT(s)), "r"((uint32_t)((uint64_t)tm.red >> 32)), "r"(((s >> 2) + 1) << 6) : "memory");
  };
  auto memproj = [&](auto second, int id, uint32_t dep, float u0, float u1, float* r) {
    constexpr bool R1 = decltype(second)::value;
    uint32_t b[NUP][4], b0[4];
    if (R1) asm volatile("{\n.reg .pred p;\nsetp.eq.u32 p, %0, %1;\n@p exit;\n}" :: "r"(dep), "r"(id) : "memory");
    bar_sync(R1 ? 2 : 1, 256);
    PROF(0);
    ldsm4t(b0, mem_a);
#pragma unroll
    for (int q = 0; q < NUP; q++) {
      if (R1 && q == 2) {
        bar_sync(11, 256);
        SCHED_FENCE(id + 1);
      }
      ldsm4t(b[q], mem_a + MEM_BLK(q + 1));
    }
    mma16816z(&acc[0], wa[0][0], b0[0], b0[1]);
    mma16816z(&acc[4], wa[1][0], b0[0], b0[1]);
    mma16816z(&acc[8], wa[0][1], b0[2], b0[3]);
    mma16816z(&acc[12], wa[1][1], b0[2], b0[3]);
#pragma unroll
    for (int q = 1; q < 9; q++) {
      uint32_t* const c = b[(q - 1) % NUP];
      mma16816(&acc[0], wa[0][2 * q], c[0], c[1]);
      mma16816(&acc[4], wa[1][2 * q], c[0], c[1]);
      mma16816(&acc[8], wa[0][2 * q + 1], c[2], c[3]);
      mma16816(&acc[12], wa[1][2 * q + 1], c[2], c[3]);
      if (R1 && q + NUP == B3Q) bar_sync(3, 256);
      if (q + NUP < 9) ldsm4t_in(c, mem_a + MEM_BLK(q + NUP), always);
      else if (R1 && q + NUP < 11) lds128_in(c, t16 + SM_PART + (10 - q - NUP) * 2048, always);
      else if (!R1 && GATE && q == GATE) { bar_arrive(11, 256); lds128_in(c, sb + SC_DEAD, always); u0 = u1 = __uint_as_float(c[3]); }
    }
#pragma unroll
    for (int i = 0; i < 8; i++) {
      const float u = i < 4 ? u0 : u1;
      r[i] = R1 ? fmaf(acc[8 + i], u, (acc[i] + __uint_as_float(b[(8 + i / 4) % NUP][i & 3])) * u) : (GATE ? fmaf(acc[i], u, acc[8 + i]) : acc[i] + acc[8 + i]);
    }
  };
  if (ro == 0) {
#pragma unroll 1
    while (true) {
      do_export(BoolC<true>(), always);
      PROFP(3);
      if (s == 8) STAMP(6);
      float r[8];
      memproj(BoolC<false>(), 30, 0, 0.f, 0.f, r);
      sts128(t16 + SM_PART, __float_as_uint(r[0]), __float_as_uint(r[1]), __float_as_uint(r[2]), __float_as_uint(r[3]));
      sts128(t16 + SM_PART + 2048, __float_as_uint(r[4]), __float_as_uint(r[5]), __float_as_uint(r[6]), __float_as_uint(r[7]));
      bar_arrive(3, 256);
      PROF(1);
      bar_sync(9, 256);
      if (!(WE & 1) && s == NSEG - 1) break;
      post_hint();
      if (!(EXV & 1) && w == 3 && s) publish(s);
      if ((WE & 1) && s == NSEG - 1) break;
      if (w == 1) {
        uint32_t m[8];
        lds128(t16 + SM_MAX - 512, m); lds128(t16 + SM_MAX, m + 4);
        const int em = (wexp(amax4(amax4(*(const __half2*)&m[0], m), m + 4)) >> 3) + (int)(lds32(sb + SC_UNSC + (s & 1) * 8) >> 23) - 15;
        const int ex = max(s ? em : 0, (int)lds32(sb + SC_XMAX + 4 * s)) - 127 + (int)lds32(sb + SC_EXPW);
        sts32(sb + SC_UNSC + (~s & 1) * 8, (127 + min(max(ex, -120), 120)) << 23);
        __syncwarp();
        if (elect_one()) mbar_arrive(sb + MB_S);
      }
      SCHED_FENCE(9);
      bar_sync(5, qk ? N5 : 256);
      PROF(2);
      import();
      xproj<0, 0, NII>(acc, wa, dA);
      if (NII < 18) {
        if (qk) bar_sync(7, 384);
        xproj<0, NII, 18>(acc, wa, dA);
        if (!qk) bar_sync(7, 384);
      } else {
        if (F10) WG_WAIT(0);
        bar_sync(10, 256);
        if (F10) SCHED_FENCE(17);
      }
      dA += (int64_t)(b2 ? XT >> 4 : -(XT >> 3));
      finish(s + ah);
      if (((EXV & 1) || w != 3) && ((EXV & 2) || qk || w >= VW2)) bar_arrive(13, 384);
      PROF(6);
      SCHED_FENCE(14);
      if (NOB & 2) bar_arrive(14, 256);
      bar_sync(12, 256);
      PROF(7);
      xproj<1, 0, 18, true>(acc, wa, dA);
      if (!(NOB & 2)) bar_arrive(14, 256);
      b2 = b2 == 2 ? 0 : b2 + 1;
      s++;
      if ((!(EXV & 1) && w == 3) || (!(EXV & 2) && !qk && w < VW2)) {
        bar_sync(13, 384);
        if (!(EXV & 1) && w == 3) export_seg(s); else send_v(s + 1, w);
      }
      PROFP(8);
    }
    if (!qk) bar_arrive(5, 256);
    if (!(WE & 1) && w == 3) publish(NSEG - 1);
  } else {
    uint32_t km[4];
    auto send_km = [&]() {
      if (XP & (4 | 4096)) return;
      const uint32_t t = (km[0] & ~1u) | lds32(sb + SC_EPO + 4), u = (s * NH + head_id()) * 4096;
      if (qk)
        asm volatile("{\n.reg .u32 o;\n.reg .u64 a;\nshr.u32 o, %0, 1;\nadd.u32 o, o, %1;\nmad.wide.u32 a, o, 1, %2;\nst.relaxed.gpu.global.v2.b32 [a], {%3,%4};\n}"
                     :: "r"(t16), "r"(u + rank * 1024 - (sb >> 1)), "l"(g_km), "r"(t), "r"(km[1]) : "memory");
      else
        asm volatile("{\n.reg .u32 o;\n.reg .u64 a;\nadd.u32 o, %0, %1;\nmad.wide.u32 a, o, 1, %2;\nst.relaxed.gpu.global.v4.b32 [a], {%3,%4,%5,%6};\n}"
                     :: "r"(t16), "r"(u + 2048 - sb), "l"(g_km), "r"(t), "r"(km[1]), "r"(km[2]), "r"(km[3]) : "memory");
    };
#pragma unroll 1
    while (true) {
      do_export(BoolC<true>(), always);
      if ((EXV & 1) && w == 1) export_seg(s);
      if ((EXV & 2) && !qk && w == 2) send_v(s + 1, 0);
      PROFP(3);
      if (s == 8) STAMP(6);
      const uint32_t tl = ((t16 >> 8) ^ wg) & 1, am = (t16 & ~256u) - w * 256;
      const float un = __uint_as_float(lds32(sb + SC_UNSC + (s & 1) * 8));
      float r[8];
      if (qk) {
        uint32_t a0 = am + (tl ? SM_QM : SM_BLK + 8192 + (s & 3) * SEGB);
        float u0 = wg ? un * (SM_SCALE * LOG2E) : un, u1 = wg ? un : un * (SM_SCALE * LOG2E);
        PIN(a0); PIN(u0); PIN(u1);
        memproj(BoolC<true>(), 32, a0, u0, u1, r);
        const uint32_t p0 = pack_bf16(r[0], r[1]), p1 = pack_bf16(r[2], r[3]), p2 = pack_bf16(r[4], r[5]), p3 = pack_bf16(r[6], r[7]);
        stsm4(a0, p0, p1, p2, p3);
        bar_arrive(4, 256);
        km[0] = wg ? p2 : p0; km[1] = wg ? p3 : p1;
      } else {
        const uint32_t d0 = s < NSEG - 1 ? 0 : 2, d1 = s < NSEG - 1 ? 1 : 2;
        uint32_t r0 = mapa(t16 + SM_VM, d0), r1 = mapa(t16 + SM_VM, d1);
        PIN(r0); PIN(r1);
        memproj(BoolC<true>(), 34, r0 | r1, un, un, r);
        const uint32_t p0 = pack_bf16(r[0], r[1]), p1 = pack_bf16(r[2], r[3]), p2 = pack_bf16(r[4], r[5]), p3 = pack_bf16(r[6], r[7]);
        const uint32_t v0 = wg ? p2 : p0, v1 = wg ? p3 : p1, v2 = wg ? p0 : p2, v3 = wg ? p1 : p3;
        st_async4(r0, v0, v1, v2, v3, mapa(sb + MB_S, d0));
        st_async4(r1, v0, v1, v2, v3, mapa(sb + MB_S, d1));
        bar_arrive(5, 256);
        sts128(t16 + SM_VM, v0, v1, v2, v3);
        __syncwarp();
        if (elect_one()) mbar_arrive(sb + MB_S);
        km[0] = v0; km[1] = v1; km[2] = v2; km[3] = v3;
      }
      if (!(WE & 2) && s == NSEG - 1) break;
      PROF(1);
      auto rearm = [&]() { mbar_wait(sb + MB_S, s & 1); if (elect_one()) mbar_expect(sb + MB_S, qk ? 640 + 2048 : 1280); __syncwarp(); };
      if ((WE & 2) && s == NSEG - 1 && w != 1) {
      } else if (w == 1) {
        if ((t16 & 384) == 0) stg_relaxed(tm.red + (RED_SLOT(s + 2) + RED_LINE(blockIdx.x)) + (t16 & 112), 0, 0, 0, 0);
        if (EXV & 1) publish(s);
      } else if (w == 0) {
        const int tn = s + ah + 1;
        if (RFW) mbar_wait(sb + MB_S, s & 1);
        if (tn + 1 < NSEG && !(XP & 8) && elect_one()) {
          const int b0 = b2 == 2 ? 0 : b2 + 1;
          mbar_expect(sb + MB_X + 8 * b0, XT);
          tma_load3(sb + SM_X + b0 * XT, &tm.x, (tn + 1) * 32, sb + MB_X + 8 * b0);
        }
        if (tn < NSEG && (!(XP & 8) || tn < 3)) mbar_wait(sb + MB_X + 8 * b2, (tn / 3) & 1);
      } else if (w == 2) {
        if (!qk) { if (VW2 < 1) send_v(s + 1, 0); if (VW2 < 2) send_v(s + 1, 1); }
      } else if (qk || !NIC) {
        rearm();
      }
      __syncwarp();
      send_km();
      if ((WE & 2) && s == NSEG - 1) break;
      import();
      PROF(4);
      SCHED_FENCE(10);
      if (NIC) {
        if (qk) bar_sync(7, NII < 18 ? 384 : 256);
        xproj<0, 0, NIC>(acc, wa, dA);
        if (!qk) { if (w == 3) rearm(); bar_sync(7, NII < 18 ? 384 : 256); }
      } else {
        bar_sync(7, NII < 18 ? 384 : 256);
      }
      if (NOB & 1) bar_arrive(12, 256);
      xproj<0, NIC, 18>(acc, wa, dA);
      if (!(NOB & 1)) bar_arrive(12, 256);
      dA += (int64_t)(b2 ? XT >> 4 : -(XT >> 3));
      finish(s + ah);
      if (qk && w == 0) wait_v(s + 1);
      bar_arrive(13, 384);
      PROF(6);
      SCHED_FENCE(13);
      bar_sync(14, 256);
      PROF(7);
      xproj<1, 0, 18>(acc, wa, dA);
      b2 = b2 == 2 ? 0 : b2 + 1;
      s++;
      PROFP(8);
    }
    if (!(WE & 2)) {
      send_km();
      PIN(t16);
      if (t16 - sb < 128) stg_relaxed(tm.red + (RED_SLOT(NSEG + 1) + RED_LINE(head_id() * 3 + rank)) + (t16 & 112), 0, 0, 0, 0);
    }
  }
  bar_arrive(0, 384);
  STAMP(3);
  cluster_sync();
  STAMP(4);
}

DI void attn_role(const uint32_t sb, unsigned char* smem_raw, const RMaps& tm, const uint32_t RANK, const bf16* __restrict__ x, const bf16* __restrict__ mem0,
                  const int w, const int lane) {
  const int t2 = w * 32 + lane;
  uint32_t wo[8][4], w1[8][4];
  const uint32_t wo_lane = sb + ((lane & 7) + ((lane >> 4) << 3)) * 128 + (((w + 4 * ((lane >> 3) & 1)) ^ (lane & 7)) << 4);
  unsigned char* const g_red = tm.red;
  {
    const uint32_t tag = *(volatile unsigned*)&g_epoch + 1;
    QSTAMP(0);
    bar_sync(0, 160);
    QSTAMP(1);
    cluster_arrive();
    __half2 hx = __float2half2_rn(0.f);
    if (t2 == 0) { sts64(sb + SC_EPO, (tag - 1) * NSEG + 1, tag & 1); sts32(sb + SC_UNSC, __float_as_uint(1.f)); sts128(sb + SC_DEAD, 0, 0, 0, 0x3f800000u); sts64(sb + SC_FPAR, 0, 0); sts128(sb + SC_ONES, 0x3f803f80u, 0x3f803f80u, 0x3f803f80u, 0x3f803f80u); }
    WSTAMP(27);
    uint32_t q[8] = {0, 0, 0, 0, 0, 0, 0, 0};
    QSTAMP(2);
    mbar_wait(sb + MB_WO3, 0);
    QSTAMP(3);
    uint32_t mv[5][4];
#pragma unroll
    for (int i = 0; i < 5; i++) {
      ldsm4(mv[i], sb + SM_M0 + (lane & 7) * (DM * 2) + min(w + 4 * i, 17) * 64 + (lane >> 3) * 16);
      if (blockIdx.x == 0) hx = amax4(hx, mv[i]);
    }
#pragma unroll
    for (int k = 0; k < 8; k++) {
      ldsm4t(wo[k], wo_lane + SM_WO3 + k * 2048); ldsm4t(w1[k], wo_lane + SM_WOST + k * 2048);
#pragma unroll
      for (int i = 0; i < 4; i++) { sq_acc(q[i], wo[k][i]); sq_acc(q[i], w1[k][i]); }
    }
    bar_sync(6, 128);
#pragma unroll
    for (int k = 0; k < 8; k++) sts128(sb + SM_WO3 + t2 * 16 + k * 2048, wo[k][0], wo[k][1], wo[k][2], wo[k][3]);
#pragma unroll
    for (int i = 0; i < 5; i++) {
      const int c = (w + 4 * i) * 32;
      if (c < DM) stsm4t(sb + SM_MEM + (c + c / 192 * 64 + lane) * 16, mv[i][0], mv[i][1], mv[i][2], mv[i][3]);
    }
    bar_arrive(1, 256); bar_arrive(2, 256); bar_arrive(9, 256);
    QSTAMP(4);
    mbar_wait(sb + MB_WO, 0);
    QSTAMP(5);
#pragma unroll
    for (int k = 0; k < 8; k++) ldsm4t(wo[k], wo_lane + SM_X + XT + k * 2048);
    fence_async();
    bar_sync(6, 128);
    if (t2 == 32) tma_load3(sb + SM_X + XT, &tm.x, 32, sb + MB_X + 8);
    __syncwarp();
#pragma unroll
    for (int k = 0; k < 8; k++)
#pragma unroll
      for (int i = 0; i < 4; i++) sq_acc(q[4 + i], wo[k][i]);
    float ss = 0.f;
#pragma unroll
    for (int i = 0; i < 8; i++) ss += bf_lo(q[i]) + bf_hi(q[i]);
    ss = warp_sum(ss);
    if (lane == 0) sts32(sb + SC_SS + 4 * (8 + w), __float_as_uint(ss));
    if (blockIdx.x < NSEG) {
      mbar_wait(sb + MB_XS, 0);
#pragma unroll
      for (int i = 0; i < 18; i++) { uint32_t v[4]; lds128(sb + SM_X + 2 * XT + t2 * 16 + i * 2048, v); hx = amax4(hx, v); }
      fence_async();
      bar_sync(6, 128);
      if (t2 == 32) tma_load3(sb + SM_X + 2 * XT, &tm.x, 64, sb + MB_X + 16);
      __syncwarp();
    }
    sts32(sb + SC_SS + 4 * (12 + w), wexp(hx));
    QSTAMP(6);
    bar_sync(11, 384);
    QSTAMP(7);
    if (t2 == 0) {
      float a[16];
#pragma unroll
      for (int i = 0; i < 4; i++) lds128f(sb + SC_SS + 16 * i, &a[4 * i]);
      stg_relaxed(&g_stats[blockIdx.x * 2], __float_as_uint(((a[0] + a[1]) + (a[2] + a[3])) + ((a[4] + a[5]) + (a[6] + a[7]))),
                  __float_as_uint((a[8] + a[9]) + (a[10] + a[11])),
                  max(max(__float_as_uint(a[12]), __float_as_uint(a[13])), max(__float_as_uint(a[14]), __float_as_uint(a[15]))), tag);
    }
    __syncwarp();
    WSTAMP(24);
    QSTAMP(8);
    cluster_wait();
    QSTAMP(9);
    if (w == 0) {
      uint4 v[3];
      int n = 0;
      while (true) {
#pragma unroll
        for (int i = 0; i < 3; i++) v[i] = ldg_relaxed(&g_stats[(i * 32 + lane) * 2]);
        if (__all_sync(0xffffffffu, v[0].w == tag && v[1].w == tag && v[2].w == tag) || ++n > SPIN_LIMIT) break;
        __nanosleep(100);
      }
      WSTAMP(25);
      QSTAMP(10);
      const float sv = warp_sum(__uint_as_float(v[0].x) + __uint_as_float(v[1].x) + __uint_as_float(v[2].x));
      const float so = warp_sum(__uint_as_float(v[0].y) + __uint_as_float(v[1].y) + __uint_as_float(v[2].y));
      const int expW = ((int)(__float_as_uint(sv) >> 23) + (int)(__float_as_uint(so) >> 23) - 254 + 2 + 10 + 1) >> 1;
      sts32(sb + SC_XMAX + 4 * lane, v[0].z); sts32(sb + SC_XMAX + 128 + 4 * lane, v[1].z);
      sts32(sb + SC_EXPW, expW + 1 - 15);
      if (blockIdx.x == 0 && lane == 0) *(volatile unsigned*)&g_epoch = tag;
      sts32(sb + SC_FPAR + 4, 1);
    } else if (w < 3) {
      const uint32_t u = blockIdx.x >> 4;
      unsigned char* const z = g_red + 98304 + (blockIdx.x & 15) * 128 + (u & 1) * 2048 + (u & 6) * 4096 + (((u >> 1) ^ w) & 1) * 4096 + lane * 4;
      stg_relaxed32(z, 0);
      uint32_t best = 0xffffffffu;
#pragma unroll 1
      for (int i = 0; i < 64; i++) {
        uint32_t dt;
        asm volatile("{\n.reg .pred p;\n.reg .u32 c, v;\nmov.u32 c, %%clock;\n"
                     "atom.relaxed.gpu.global.exch.b32 v, [%1], 0;\nsetp.eq.u32 p, v, 0;\nmov.u32 %0, 0;\n@p mov.u32 %0, %%clock;\nsub.u32 %0, %0, c;\n}"
                     : "=r"(dt) : "l"(z) : "memory");
        best = min(best, dt);
        if (lds32v(sb + SC_FPAR + 4) && i >= NPROBE - 1) break;
      }
      sts32(sb + SC_LAT + (w - 1) * 4, best);
    }
    QSTAMP(11);
    bar_sync(13, 384);
    bar_arrive(0, 384);
    QSTAMP(12);
    WSTAMP(26);
  }

  const uint32_t nh = __shfl_sync(0xffffffffu, near_half(sb), 0);
  uint32_t l16 = sb + lane * 16;
  PIN(l16);
#define LV ((l16 >> 4) & 31)
#define fence_reg l16
  const uint32_t red_lo = (uint32_t)(uint64_t)g_red, red_hi = (uint32_t)((uint64_t)g_red >> 32);
  uint32_t lp;
  auto slot = [&](int s, uint32_t c, uint32_t ofs) {
    const uint32_t lo = lp | (red_lo + ((w >> 1) * 4 + (w & 1) * 2 + ((w ^ c) & 1)) * 4096 + RED_SLOT(s) + ofs);
    uint64_t a; asm("mov.b64 %0, {%1, %2};" : "=l"(a) : "r"(lo), "r"(red_hi));
    return (unsigned char*)a;
  };
  const uint32_t always = __shfl_sync(0xffffffffu, lds32(sb + SC_DEAD + 12), 0);
  const int mode0 = RANK < 2 ? w : w | 4;
  auto hint_addr = [&](int s) { return min(LV, 23u) * 4 + (red_lo + HINT_OFF + nh * 4096 + w * 16384 + RED_SLOT(s)); };
  auto load_hints = [&](uint32_t lo) {
    uint64_t a; asm("mov.b64 %0, {%1, %2};" : "=l"(a) : "r"(lo), "r"(red_hi));
    return ldg_relaxed32((const void*)a);
  };
  int s = 0;
  bool bad = false;
#pragma unroll 1
  while (true) {
    const uint32_t par = s & 1;
    uint32_t vx[4][4], hints;
    auto load_vx = [&]() {
      const uint32_t va = l16 + (RANK < 2 ? SM_VC + par * 8192 : SM_BLK + (s & 3) * SEGB) + w * 1024 + ((LV >> 3) & 1) * 384 - (LV >> 4) * 128;
#pragma unroll
      for (int i = 0; i < 4; i++) ldsm4(vx[i], va + (i & 1) * 4096 + (i >> 1) * 256);
    };
    auto retire = [&](uint32_t x) {
      asm volatile("{\n.reg .pred p;\nsetp.eq.u32 p, %0, 0;\n@p exit;\n}" :: "r"(vx[0][0] | vx[1][0] | vx[2][0] | vx[3][0] | x) : "memory");
    };
    auto scores = [&](auto memkeys, auto first, float* sc) {
      constexpr bool MK = decltype(memkeys)::value, FIRST = decltype(first)::value;
      uint32_t kb[4][4], qb[2][4];
      const uint32_t m = LV >> 3;
      uint32_t kaddr = l16 + SM_BLK + 4096 + (s & 3) * SEGB + w * 2048 + (m & 1) * (MK ? 128 : 896) - (m >> 1) * 128;
      if (MK) { PIN(kaddr); }
      else {
#pragma unroll
        for (int k = 0; k < 4; k++) ldsm4t(kb[k], kaddr + k * 256);
      }
      if (FIRST) { load_vx(); retire(MK ? kaddr : kb[0][0] | kb[1][0] | kb[2][0] | kb[3][0] | l16); bar_sync(4, 256); PROF(4); }
      ldsm4t(qb[0], l16 + SM_QM);
      if (MK) ldsm4t(kb[0], kaddr);
      ldsm4t(qb[1], l16 + SM_QM + 512);
      if (MK) ldsm4t(kb[2], kaddr + 512);
      float c[4][4];
      mma16816z(c[0], kb[0], qb[0][0], qb[0][1]); mma16816z(c[1], kb[MK ? 0 : 1], qb[0][2], qb[0][3]);
      mma16816z(c[2], kb[2], qb[1][0], qb[1][1]); mma16816z(c[3], kb[MK ? 2 : 3], qb[1][2], qb[1][3]);
      if (FIRST && B5POS == 0) bar_arrive(5, N5);
#pragma unroll
      for (int i = 0; i < (MK ? 2 : 4); i++) sc[i] = ((c[0][i] + c[1][MK ? i + 2 : i]) + c[2][i]) + c[3][MK ? i + 2 : i];
    };
    auto send = [&](auto memkeys) {
      constexpr bool MK = decltype(memkeys)::value;
      constexpr int N = MK ? 1 : 2;
      const uint32_t sa = sb + LV * 4 + SM_E + (MK ? 1024 + RANK * 128 : RANK * 512 + w * 256);
      uint32_t ra[N][2], mb[N][2];
#pragma unroll
      for (int i = 0; i < N; i++)
#pragma unroll
        for (int j = 0; j < 2; j++) {
          ra[i][j] = mapa(sa + i * 128, j ? 2 : RANK ^ 1); mb[i][j] = mapa(sb + MB_S, j ? 2 : RANK ^ 1);
          PIN(ra[i][j]);
        }
      float sc[4];
      scores(memkeys, BoolC<true>(), sc);
      uint32_t e[N];
#pragma unroll
      for (int i = 0; i < N; i++) {
        e[i] = pack_bf16(ex2(sc[2 * i]), ex2(sc[2 * i + 1]));
        if (!(fmaxf(fabsf(sc[2 * i]), fabsf(sc[2 * i + 1])) <= E_LIM)) e[i] = 0x7fff7fffu;
        st_async1(ra[i][0], e[i], mb[i][0]);
        st_async1(ra[i][1], e[i], mb[i][1]);
      }
#pragma unroll
      for (int i = 0; i < N; i++) sts32(sa + i * 128, e[i]);
      __syncwarp();
      if (l16 == sb) mbar_arrive(sb + MB_S);
      PROF(5);
    };
    const int mode = bad ? 8 : mode0;
    if (mode < 2) {
      send(BoolC<false>());
    } else if (mode == 2) {
      send(BoolC<true>());
    } else if (mode == 8) {
      load_vx();
      retire(l16);
      const uint32_t fp = lds32(sb + SC_FPAR);
      bar_sync(6, 128);
      if (w == 0 && l16 == sb) { sts32(sb + SC_FPAR, fp ^ 1); mbar_expect(sb + MB_F, 3072); }
      if (RANK < 2 && w < 3) {
        float sc[4] = {0.f, 0.f, 0.f, 0.f};
        if (w < 2) scores(BoolC<false>(), BoolC<false>(), sc); else scores(BoolC<true>(), BoolC<false>(), sc);
#pragma unroll 1
        for (int r = 0; r < 3; r++)
          st_async4(mapa(l16 + SM_FB + RANK * 1536 + w * 512, r), __float_as_uint(sc[0]), __float_as_uint(sc[1]), __float_as_uint(sc[2]), __float_as_uint(sc[3]), mapa(sb + MB_F, r));
      }
      mbar_wait(sb + MB_F, fp);
      float a[12];
#pragma unroll
      for (int j = 0; j < 3; j++) {
        float b[4];
        lds128f(l16 + SM_FB + j * 512, a + 4 * j); lds128f(l16 + SM_FB + 1536 + j * 512, b);
#pragma unroll
        for (int i = 0; i < 4; i++) a[4 * j + i] += b[i];
      }
      float m0 = fmaxf(fmaxf(fmaxf(a[0], a[2]), fmaxf(a[4], a[6])), a[8]), m1 = fmaxf(fmaxf(fmaxf(a[1], a[3]), fmaxf(a[5], a[7])), a[9]);
#pragma unroll
      for (int o = 4; o < 32; o <<= 1) { m0 = fmaxf(m0, __shfl_xor_sync(0xffffffffu, m0, o)); m1 = fmaxf(m1, __shfl_xor_sync(0xffffffffu, m1, o)); }
#pragma unroll
      for (int i = 0; i < 5; i++) {
        const uint32_t ea = sb + SM_E + LV * 4 + (i < 4 ? i * 128 : 1024);
        sts32(ea, pack_bf16(ex2(a[2 * i] - m0), ex2(a[2 * i + 1] - m1)));
        sts32(ea + (i < 4 ? 512 : 128), 0x3f803f80u);
      }
      __syncwarp();
    } else {
      load_vx();
      if (mode == 3) bar_arrive(4, 256);
      retire(l16 + 1);
    }
    {
      uint32_t wa[4], wb[4], oc[4];
      constexpr int WS = 2048;
      const uint32_t w3a = l16 + SM_WO3 + w * 512;
      lds128(w3a + KP(0) * WS, wa); lds128(w3a + KP(1) * WS, wb); lds128(sb + SC_ONES, oc);
      if (B5POS == 1 && mode < 3) bar_arrive(5, N5);
      uint32_t e[10], p[5], vm[4], ob[4];
      float o0[4], o1[4], f[3][2][4], rs[4];
      reserve2(vm); reserve2(vm + 2); reserve2(e + 8);
      hints = hint_addr(s);
      PIN(hints);
      if (CLR & 2) asm volatile("{\n.reg .pred p;\nsetp.eq.u32 p, %0, 0;\n@p exit;\n}" :: "r"(wa[0] | wb[0] | oc[0] | hints) : "memory");
      mbar_wait(sb + MB_S, par);
      PROF(6);
      ldsm4t(e, l16 + SM_E); ldsm2t_in(e + 8, l16 + SM_E + 1024, always); ldsm4t(e + 4, l16 + SM_E + 512);
      lds128_in(vm, l16 + w * 512 + SM_VM, always);
      const float scl = __uint_as_float(lds32(sb + SC_UNSC + 8 - par * 8));
      hints = load_hints(hints);
      if (GF & 1) SCHED_FENCE(4);
#pragma unroll
      for (int i = 0; i < 4; i++) p[i] = mul_bf16(e[i], e[4 + i]);
      p[4] = mul_bf16(e[8], e[9]);
      if (MO & 4) {
        float a0[4], a1[4];
        mma16816z(o0, vx[0], p[0], p[1]); mma16816z(o1, vx[1], p[0], p[1]);
        mma16816z(a0, vx[2], p[2], p[3]); lds128_in(vx[2], w3a + KP(2) * WS, always);
        mma16816z(a1, vx[3], p[2], p[3]); lds128_in(vx[3], w3a + KP(3) * WS, always);
        mma1688(o0, vm[0], vm[1], p[4]); mma1688(o1, vm[2], vm[3], p[4]);
        mma16816z(rs, oc, p[0], p[1]); mma16816(rs, oc, p[2], p[3]); mma1688(rs, oc[0], oc[1], p[4]);
#pragma unroll
        for (int i = 0; i < 4; i++) { o0[i] += a0[i]; o1[i] += a1[i]; }
      } else {
      mma16816z(o0, vx[0], p[0], p[1]); mma16816z(o1, vx[1], p[0], p[1]); mma16816z(rs, oc, p[0], p[1]);
      mma16816(o0, vx[2], p[2], p[3]); lds128_in(vx[2], w3a + KP(2) * WS, always);
      mma16816(o1, vx[3], p[2], p[3]); lds128_in(vx[3], w3a + KP(3) * WS, always);
      mma16816(rs, oc, p[2], p[3]);
      mma1688(o0, vm[0], vm[1], p[4]); mma1688(o1, vm[2], vm[3], p[4]); mma1688(rs, oc[0], oc[1], p[4]);
      }
      stsm4(l16 + w * 512 + SM_OB, pack_bf16(o0[0], o0[1]), pack_bf16(o0[2], o0[3]), pack_bf16(o1[0], o1[1]), pack_bf16(o1[2], o1[3]));
      bar_sync(6, 128);
      PROF(7);
      ldsm4t_in(oc, l16 + SM_OB, always);
      bad = __any_sync(0xffffffffu, !(rs[0] + rs[1] > 0.f) && !bad);
      rs[0] *= scl; rs[1] *= scl;
      asm volatile("{\n.reg .pred p;\nsetp.ne.u32 p, %1, 0;\n@p rcp.approx.ftz.f32 %0, %0;\n}" : "+f"(rs[0]) : "r"(always));
      asm volatile("{\n.reg .pred p;\nsetp.ne.u32 p, %1, 1;\n@p rcp.approx.ftz.f32 %0, %0;\n}" : "+f"(rs[1]) : "r"(always));
      asm volatile("lop3.b32 %0, %1, %2, %3, 0xfe;" : "=r"(lp) : "r"((l16 & 128) * 2), "r"((l16 & 256) * 4), "r"(l16 & 112));
      if (bad) continue;
      ldsm4t(ob, l16 + SM_OB + 512);
      mma16816z(f[2][0], wa, oc[0], oc[1]); mma16816z(f[2][1], wb, oc[2], oc[3]);
      mma16816z(f[0][0], wo[0], oc[0], oc[1]); mma16816z(f[0][1], wo[4], oc[2], oc[3]);
      mma16816z(f[1][0], w1[0], oc[0], oc[1]); mma16816z(f[1][1], w1[4], oc[2], oc[3]);
      ldsm4t_in(oc, l16 + SM_OB + 1024, always);
      mma16816(f[2][0], vx[2], ob[0], ob[1]); lds128_in(vx[2], w3a + KP(4) * WS, always);
      mma16816(f[2][1], vx[3], ob[2], ob[3]); lds128_in(vx[3], w3a + KP(5) * WS, always);
      mma16816(f[0][0], wo[1], ob[0], ob[1]); mma16816(f[0][1], wo[5], ob[2], ob[3]);
      mma16816(f[1][0], w1[1], ob[0], ob[1]); mma16816(f[1][1], w1[5], ob[2], ob[3]);
      ldsm4t_in(ob, l16 + SM_OB + 1536, always);
      mma16816(f[0][0], wo[2], oc[0], oc[1]); mma16816(f[0][1], wo[6], oc[2], oc[3]);
      mma16816(f[2][0], vx[2], oc[0], oc[1]); lds128_in(vx[2], w3a + KP(6) * WS, always);
      mma16816(f[2][1], vx[3], oc[2], oc[3]); lds128_in(vx[3], w3a + KP(7) * WS, always);
      mma16816(f[1][0], w1[2], oc[0], oc[1]); mma16816(f[1][1], w1[6], oc[2], oc[3]);
      mma16816(f[0][0], wo[3], ob[0], ob[1]); mma16816(f[0][1], wo[7], ob[2], ob[3]);
      mma16816(f[1][0], w1[3], ob[0], ob[1]); mma16816(f[1][1], w1[7], ob[2], ob[3]);
      mma16816(f[2][0], vx[2], ob[0], ob[1]); mma16816(f[2][1], vx[3], ob[2], ob[3]);
      bar_arrive(7, NII < 18 ? 384 : 256);
      lds128_in(ob, sb + SC_DEAD, always);
      uint32_t h[3][2];
#pragma unroll
      for (int j = 0; j < 3; j++)
#pragma unroll
        for (int i = 0; i < 2; i++)
        {
          scale_sum(f[j][1][2 * i], f[j][0][2 * i], rs[0], always); scale_sum(f[j][1][2 * i + 1], f[j][0][2 * i + 1], rs[1], always);
          h[j][i] = pack_f16(f[j][1][2 * i], f[j][1][2 * i + 1]);
        }
      const uint32_t rofs = RANK * 32768;
      red_f16x8(slot(s, RANK >> 1, rofs), h[0][0], h[1][0], h[2][0], 0x3c00u);
      red_f16x8(slot(s, (RANK >> 1) ^ 1, rofs), h[0][1], h[1][1], h[2][1], 0x3c00u);
      if (NII == 18) bar_arrive(10, 256);
      SCHED_FENCE(5);
      l16 += ob[B7R];
    }
    {
    PROF(8);
    const uint32_t ma0 = l16 + SM_MEM + w * 128 + (LV >> 3) * 896 + nh * 512;
    const unsigned char* const sl[2] = {slot(s, nh, 0), slot(s, nh ^ 1, 0)};
    uint32_t dl = gtime() - 1984;
    uint32_t late = latest_hint(hints, dl, s);
    if (late >= 64) {
      int n = 0;
#pragma unroll 1
      do {
        hints = load_hints(hint_addr(s));
        dl = gtime() - 1984;
        late = latest_hint(hints, dl, s);
      } while (late >= 64 && ++n < SPIN_LIMIT);
    }
    dl += late * 32 + tm.poll;
    PROF(9);
    {
      auto wait_until = [&](uint32_t t) {
        asm volatile("{\n.reg .pred p;\n.reg .s32 c;\n.reg .u64 t;\nTL: mov.u64 t, %%globaltimer;\ncvt.u32.u64 c, t;\nsub.s32 c, c, %0;\nsetp.lt.s32 p, c, 0;\n@p bra.uni TL;\n}" :: "r"(t + (l16 & 15)) : "memory");
      };
      uint4 v[2][3];
      auto load = [&](int c) {
#pragma unroll
        for (int r = 0; r < 3; r++) v[c][r] = ldg_relaxed(sl[c ^ (r >> 1)] + r * 32768);
      };
      auto decode = [&](int c, int n) {
        uint32_t q[9];
        __half2 hm;
        const uint32_t ma = ma0 ^ (c * 512);
#pragma unroll
        for (int i = 0; i < 9; i++) {
          const uint32_t h = i % 3 == 0 ? v[c][i / 3].x : (i % 3 == 1 ? v[c][i / 3].y : v[c][i / 3].z);
          const float2 f = __half22float2(*(const __half2*)&h);
          q[i] = pack_bf16(f.x, f.y);
          hm = i ? __hmax2(hm, __habs2(*(const __half2*)&h)) : __habs2(*(const __half2*)&h);
        }
#pragma unroll
        for (int r = 0; r < 3; r++) stsm4(ma + r * 4096, q[3 * r], q[3 * r + 1], q[3 * r + 2], r < 2 ? v[c][r].w : *(const uint32_t*)&hm);
        const bool done = __all_sync(0xffffffffu, v[c][0].w == 0x5000u && v[c][1].w == 0x5000u && v[c][2].w == 0x5000u) || n > SPIN_LIMIT;
        asm volatile("{\n.reg .pred p;\nsetp.ne.u32 p, %0, 0;\n@p bar.arrive %1, 256;\n}" :: "r"((int)done), "r"(1 + c) : "memory");
        return done;
      };
      if (LEAD) { wait_until(dl - LEAD); load(1); }
      int n = MO & 1 ? l16 & 15 : 0;
      if (MO & 1) PIN(n);
      if (MO & 2) {
        const uint32_t t = __shfl_sync(0xffffffffu, dl, 0);
        asm volatile("{\n.reg .pred p;\n.reg .s32 c;\nTL: mov.u32 c, %%globaltimer_lo;\nsub.s32 c, c, %0;\nsetp.lt.s32 p, c, 0;\n@p bra.uni TL;\n}" :: "r"(t) : "memory");
      } else wait_until(dl);
      PROF(10);
#pragma unroll 1
      do {
        load(0);
        if (!LEAD) load(1);
        asm volatile("{\n.reg .pred p;\nsetp.eq.u32 p, %0, 0;\n@p bar.sync 13, 384;\n}" :: "r"(n) : "memory");
      } while (!decode(0, n++));
      PROF(11);
#pragma unroll 1
      while (!decode(1, n++)) load(1);
      bar_arrive(9, 256);
      PROF(12);
    }
    PROF(13);
    if (++s == NSEG - 1) break;
    }
  }
#undef fence_reg
  if (RANK < 2) bar_arrive(4, 256);
  bar_sync(0, 384);
  cluster_sync();
}

__global__ void __cluster_dims__(3, 1, 1) __launch_bounds__(384, 1)
rec_kernel(const __grid_constant__ RMaps tm, const bf16* __restrict__ x, const bf16* __restrict__ mem0) {
  extern __shared__ __align__(1024) unsigned char smem_raw[];
  const uint32_t sb = smem_u32(smem_raw);
  const int tid = threadIdx.x, lane = tid & 31;
  const int wg = __shfl_sync(0xffffffffu, tid >> 7, 0);
  const int w = __shfl_sync(0xffffffffu, (tid >> 5) & 3, 0);
  uint32_t rank; asm("mov.u32 %0, %%cluster_ctarank;" : "=r"(rank));
  STAMP(0);
  asm volatile("griddepcontrol.launch_dependents;" ::: "memory");

  if (wg < 2) {
    if (tid == 0) {
      const int h = blockIdx.x / 3;
      mbar_init(sb + MB_XS, 1);
      for (int i = 0; i < 3; i++) { mbar_init(sb + MB_W + 8 * i, 1); mbar_init(sb + MB_X + 8 * i, 1); }
      mbar_init(sb + MB_WO3, 1);
      fence_async();
      load_w(sb, tm, rank, 0);
      mbar_expect(sb + MB_X, XT);
      tma_load3(sb + SM_X, &tm.x, 0, sb + MB_X);
      if (WPOS == 2) load_w(sb, tm, rank, 1);
      mbar_expect(sb + MB_WO3, 32768 + 8 * DM * 2);
      tma_load(sb + SM_WOST, &tm.wo, rank * 192 + 64, h * DH, sb + MB_WO3);
      tma_load(sb + SM_WO3, &tm.wo, rank * 192 + 128, h * DH, sb + MB_WO3);
      bulk_load(sb + SM_M0, mem0, 8 * DM * 2, sb + MB_WO3);
      if (WOPF) tma_prefetch(&tm.wo, rank * 192, h * DH);
      if (WPOS == 1) load_w(sb, tm, rank, 1);
      load_w(sb, tm, rank, 2);
      mbar_init(sb + MB_WO, 1);
      mbar_init(sb + MB_S, rank < 2 ? 5 : 6);
      mbar_init(sb + MB_F, 1);
      mbar_init(sb + MB_VX, 1); mbar_init(sb + MB_VX + 8, 1);
      asm volatile("fence.mbarrier_init.release.cluster;" ::: "memory");
      fence_async();
      mbar_expect(sb + MB_X + 8, XT); mbar_expect(sb + MB_X + 16, XT);
      mbar_expect(sb + MB_WO, 16384); mbar_expect(sb + MB_XS, XT);
      mbar_expect(sb + MB_S, rank < 2 ? 640 + 2048 : 1280);
      mbar_expect(sb + MB_VX, 8192); mbar_expect(sb + MB_VX + 8, 8192);
    }
    __syncwarp();
    asm volatile("setmaxnreg.inc.sync.aligned.u32 192;");
    __syncwarp();
    QSTAMP(0);
    if (tid < 32) bar_arrive(0, 160);
    QSTAMP(1);
    proj_role(sb, tm, x, rank, wg, w, lane);
  } else {
    asm volatile("setmaxnreg.dec.sync.aligned.u32 120;");
    attn_role(sb, smem_raw, tm, rank, x, mem0, w, lane);
  }
}

constexpr int NAUX = 36;
constexpr int A_ST = 6, A_STAGE = 8192 + 12288, A_W8 = A_ST * A_STAGE, A_EXC = A_W8 + A_ST * 1536, A_ROWS = 57;
constexpr int A_IN = A_EXC + 8 * 2304, A_INB = 3 * SEGB, A_OST = A_IN + 2 * A_INB, A_P = A_OST + 8192, A_G = A_P + 3072;
constexpr int A_BAR = A_G + 1024;
constexpr int A_XT = A_BAR + 1024, A_XW = A_XT;
constexpr int A_TOTAL = A_XT + 4096;
static_assert(A_IN % 1024 == 0 && A_XT % 1024 == 0 && A_IN >= 4 * XT && A_IN + 64 * DM * 2 <= A_BAR && A_TOTAL <= 232448, "side kernel shared memory");
struct AMaps { CUtensorMap x, wa, wa8, o, o3, o16, wob, woa, woa16; const unsigned char* red; uint32_t poll; };

DI void wgmma_n192_ss_nt(float* d, uint64_t da, uint64_t db, int acc) {
  asm volatile("{\n.reg .pred p;\nsetp.ne.b32 p, %98, 0;\n"
               "wgmma.mma_async.sync.aligned.m64n192k16.f32.bf16.bf16 {"
               "%0,%1,%2,%3,%4,%5,%6,%7,%8,%9,%10,%11,%12,%13,%14,%15,%16,%17,%18,%19,%20,%21,%22,%23,%24,%25,%26,%27,%28,%29,%30,%31,"
               "%32,%33,%34,%35,%36,%37,%38,%39,%40,%41,%42,%43,%44,%45,%46,%47,%48,%49,%50,%51,%52,%53,%54,%55,%56,%57,%58,%59,%60,%61,%62,%63,"
               "%64,%65,%66,%67,%68,%69,%70,%71,%72,%73,%74,%75,%76,%77,%78,%79,%80,%81,%82,%83,%84,%85,%86,%87,%88,%89,%90,%91,%92,%93,%94,%95"
               "}, %96, %97, p, 1, 1, 0, 1;\n}\n"
               : ACC8(d, 0), ACC8(d, 8), ACC8(d, 16), ACC8(d, 24), ACC8(d, 32), ACC8(d, 40), ACC8(d, 48), ACC8(d, 56),
                 ACC8(d, 64), ACC8(d, 72), ACC8(d, 80), ACC8(d, 88) : "l"(da), "l"(db), "r"(acc));
}
DI void wgmma_n24_ss_nt(float* d, uint64_t da, uint64_t db, int acc) {
  asm volatile("{\n.reg .pred p;\nsetp.ne.b32 p, %14, 0;\n"
               "wgmma.mma_async.sync.aligned.m64n24k16.f32.bf16.bf16 {%0,%1,%2,%3,%4,%5,%6,%7,%8,%9,%10,%11}, %12, %13, p, 1, 1, 0, 1;\n}\n"
               : ACC8(d, 0), "+f"(d[8]), "+f"(d[9]), "+f"(d[10]), "+f"(d[11]) : "l"(da), "l"(db), "r"(acc));
}
DI void tma_load3d(uint32_t dst, const CUtensorMap* m, int c0, int c1, int c2, uint32_t mb) {
  asm volatile("cp.async.bulk.tensor.3d.shared::cluster.global.mbarrier::complete_tx::bytes [%0], [%1, {%3, %4, %5}], [%2];"
               :: "r"(dst), "l"(m), "r"(mb), "r"(c0), "r"(c1), "r"(c2) : "memory");
}
DI uint32_t trans8(uint32_t x) { uint32_t r; asm("movmatrix.sync.aligned.m8n8.trans.b16 %0, %1;" : "=r"(r) : "r"(x)); return r; }
DI void wgmma_n40_ss(float* d, uint64_t da, uint64_t db, int acc) {
  asm volatile("{\n.reg .pred p;\nsetp.ne.b32 p, %22, 0;\n"
               "wgmma.mma_async.sync.aligned.m64n40k16.f32.bf16.bf16 {%0,%1,%2,%3,%4,%5,%6,%7,%8,%9,%10,%11,%12,%13,%14,%15,%16,%17,%18,%19}, "
               "%20, %21, p, 1, 1, 1, 1;\n}\n"
               : ACC8(d, 0), ACC8(d, 8), "+f"(d[16]), "+f"(d[17]), "+f"(d[18]), "+f"(d[19]) : "l"(da), "l"(db), "r"(acc));
}
DI uint2 ldg_relaxed64(const void* p) {
  uint2 v; asm volatile("ld.relaxed.gpu.global.v2.b32 {%0,%1}, [%2];" : "=r"(v.x), "=r"(v.y) : "l"(p) : "memory"); return v;
}
template <int ST> DI void ldg8x64(uint32_t* m, const void* p) {
  asm volatile("ld.relaxed.gpu.global.v2.b32 {%0,%1}, [%16];\nld.relaxed.gpu.global.v2.b32 {%2,%3}, [%16 + %17];\n"
               "ld.relaxed.gpu.global.v2.b32 {%4,%5}, [%16 + %18];\nld.relaxed.gpu.global.v2.b32 {%6,%7}, [%16 + %19];\n"
               "ld.relaxed.gpu.global.v2.b32 {%8,%9}, [%16 + %20];\nld.relaxed.gpu.global.v2.b32 {%10,%11}, [%16 + %21];\n"
               "ld.relaxed.gpu.global.v2.b32 {%12,%13}, [%16 + %22];\nld.relaxed.gpu.global.v2.b32 {%14,%15}, [%16 + %23];"
               : "=r"(m[0]), "=r"(m[1]), "=r"(m[2]), "=r"(m[3]), "=r"(m[4]), "=r"(m[5]), "=r"(m[6]), "=r"(m[7]),
                 "=r"(m[8]), "=r"(m[9]), "=r"(m[10]), "=r"(m[11]), "=r"(m[12]), "=r"(m[13]), "=r"(m[14]), "=r"(m[15])
               : "l"(p), "n"(ST), "n"(2 * ST), "n"(3 * ST), "n"(4 * ST), "n"(5 * ST), "n"(6 * ST), "n"(7 * ST) : "memory");
}
template <int ST> DI void ldg4x128(uint32_t* m, const void* p) {
  asm volatile("ld.relaxed.gpu.global.v4.b32 {%0,%1,%2,%3}, [%16];\nld.relaxed.gpu.global.v4.b32 {%4,%5,%6,%7}, [%16 + %17];\n"
               "ld.relaxed.gpu.global.v4.b32 {%8,%9,%10,%11}, [%16 + %18];\nld.relaxed.gpu.global.v4.b32 {%12,%13,%14,%15}, [%16 + %19];"
               : "=r"(m[0]), "=r"(m[1]), "=r"(m[2]), "=r"(m[3]), "=r"(m[4]), "=r"(m[5]), "=r"(m[6]), "=r"(m[7]),
                 "=r"(m[8]), "=r"(m[9]), "=r"(m[10]), "=r"(m[11]), "=r"(m[12]), "=r"(m[13]), "=r"(m[14]), "=r"(m[15])
               : "l"(p), "n"(ST), "n"(2 * ST), "n"(3 * ST) : "memory");
}
template <int N, int ST> DI bool stale(const uint32_t* m, uint32_t tag) {
  uint32_t x = m[0] ^ tag;
#pragma unroll
  for (int i = 1; i < N; i++) asm("lop3.b32 %0, %0, %1, %2, 0xf6;" : "+r"(x) : "r"(m[i * ST]), "r"(tag));
  return __any_sync(0xffffffffu, x & 1);
}
DI bool mbar_test(uint32_t b, uint32_t par) {
  uint32_t r; asm volatile("{\n.reg .pred p;\nmbarrier.test_wait.parity.shared::cta.b64 p, [%1], %2;\nselp.u32 %0, 1, 0, p;\n}" : "=r"(r) : "r"(b), "r"(par) : "memory");
  return r;
}
DI int wait_flags(const unsigned* p, bool active, unsigned base, int seg) {
  int n = 0, m;
  while (true) {
    m = __reduce_min_sync(0xffffffffu, active ? (int)(ldg_acquire32(p) - base) : NSEG);
    if (m > seg || ++n > SPIN_LIMIT) break;
    __nanosleep((YP & 32) ? 400 : 40);
  }
  return max(m, seg + 1);
}
DI void wait_count(const unsigned* p, unsigned target) {
  int n = 0;
  unsigned v;
  while (true) {
    asm volatile("ld.acquire.gpu.global.b32 %0, [%1];" : "=r"(v) : "l"(p) : "memory");
    if ((int)(v - target) >= 0 || ++n > SPIN_LIMIT) break;
    __nanosleep(64);
  }
}
#define PACE_NEXT 800
#define AWARM 0
#define WPF 3
#define UNP 64
#define ADLY 0
#define ODLY 100
#define SDLY 0
#define RSL 100
#define TWO 0
#define ALLW 1
#define PING 60
#define FLAG 2
#define FPOS 1
#define QB 1
#define Q_LO 0
#define Q_HI 320
DI bool tick_wait(uint32_t pace, int step) {
  const int n = lds32v(pace);
  if (n <= step) mbar_wait(pace + 8, n & 1);
  return n <= step;
}
DI void quiet_wait(uint32_t pace) {
  uint32_t n, d;
  asm volatile("ld.volatile.shared.v2.b32 {%0,%1}, [%2];" : "=r"(n), "=r"(d) : "r"(pace) : "memory");
  if (n - 1 < NSEG - 2 && (int)(gtime() - d) > Q_HI) mbar_wait(pace + 8, n & 1);
}
DI void sleep_until(uint32_t t) {
  for (int n = 0; n < 64; n++) {
    const int r = t - gtime();
    if (r <= 0) break;
    __nanosleep(r >> 1);
  }
}
DI void aux_barrier(int i, unsigned epoch, bool wait = true) {
  asm volatile("fence.proxy.async;" ::: "memory");
  asm volatile("red.release.gpu.global.add.u32 [%0], 1;" :: "l"(&g_abar[i * 32]) : "memory");
  if (!wait) return;
  wait_count(&g_abar[i * 32], NAUX * (epoch + 1));
  asm volatile("fence.proxy.async;" ::: "memory");
}

__global__ void __launch_bounds__(512, 1)
aux_kernel(const __grid_constant__ AMaps tm, const bf16* __restrict__ x, const bf16* __restrict__ gate_w, bf16* __restrict__ out) {
  extern __shared__ __align__(1024) unsigned char smem_raw[];
  const uint32_t sb = smem_u32(smem_raw);
  const uint32_t full1 = sb + A_BAR, empty1 = full1 + 8 * A_ST, fullw = empty1 + 8 * A_ST, full3 = fullw + 16, empty3 = full3 + 32,
                 fulla = empty3 + 32, emptya = fulla + 32, fullg = emptya + 16, pace = fullg + 8;
  const int tid = threadIdx.x, lane = tid & 31, cta = blockIdx.x;
  const int wg = __shfl_sync(0xffffffffu, tid >> 7, 0), w = __shfl_sync(0xffffffffu, (tid >> 5) & 3, 0);
  ASTAMP(14);
  const unsigned epoch = *(volatile unsigned*)&g_epoch2;
  if (tid == 0) {
    for (int i = 0; i < A_ST; i++) { mbar_init(full1 + 8 * i, 1); mbar_init(empty1 + 8 * i, 8); }
    mbar_init(fullw, 1); mbar_init(fullw + 8, 1); mbar_init(fullg, 1);
    for (int i = 0; i < 2; i++) { mbar_init(fulla + 16 * i, 2); mbar_init(fulla + 16 * i + 8, 1); mbar_init(emptya + 8 * i, 4); }
    sts64(pace, 0, 0); mbar_init(pace + 8, 1); sts32(pace + 16, 0); sts64(pace + 24, 65536, 0xffff0000u);
    for (int i = 0; i < 4; i++) { mbar_init(full3 + 8 * i, 1); mbar_init(empty3 + 8 * i, cta < NH ? 8 : 4); }
    fence_async();
  }
  __syncthreads();
  ASTAMP(0);
  const bool wide = cta < NH;
  auto p3_ks = [&](int g) { return wide ? cta >> 2 : 2 * (cta - NH) + g; };
  auto p3_mt = [&](int g) { return wide ? 2 * (cta & 3) + g : 8; };
  const unsigned fbase = epoch * NSEG;
  if (wg == 3) {
    asm volatile("setmaxnreg.dec.sync.aligned.u32 %0;" :: "n"(TWO ? 32 : 48));
    if (w == 1 && cta < NH) {
#pragma unroll 1
      for (int seg = 0; seg < ((XP & 2048) ? 0 : NSEG); seg++) {
        bar_arrive(5, 160);
        if (seg > 0 && lane == 0) {
          asm volatile("cp.async.bulk.wait_group 0;" ::: "memory");
          stg_relaxed32(&g_oflag[cta * 32], fbase + seg);
        }
        __syncwarp();
        bar_sync(4, 160);
        if (QM & 16) tick_wait(pace, seg + 1);
        if (lane == 0) {
          fence_async();
          if (!(YP & 2)) {
          tma_store(&tm.o, sb + A_OST, cta * DH, seg * 32);
          tma_store(&tm.o, sb + A_OST + 4096, cta * DH + 64, seg * 32);
          }
          asm volatile("cp.async.bulk.commit_group;" ::: "memory");
          asm volatile("cp.async.bulk.wait_group.read 0;" ::: "memory");
        }
        __syncwarp();
      }
      if (lane == 0) {
        asm volatile("cp.async.bulk.wait_group 0;" ::: "memory");
        { const int seg = NSEG - 1; TSTAMP(2); }
        stg_relaxed32(&g_oflag[cta * 32], fbase + NSEG);
      }
    }
    if (w == 2 && cta < NH) {
      const uint32_t ktag = (epoch + 1) & 1, ma = sb + A_IN + 8192 + lane * 16;
      int avail = 0;
      bar_sync(10, 64);
#pragma unroll 1
      for (int seg = 0; seg < ((XP & 2048) ? 0 : NSEG); seg++) {
        if (avail <= seg) avail = wait_flags(&g_sflag[(cta * 3 + min(lane, 2)) * 8], true, fbase, seg);
        if ((QM & 8) && seg < UNP) tick_wait(pace, seg);
        TSTAMP(0);
        const unsigned char* km = g_km + (size_t)(seg * NH + cta) * 4096 + lane * 8;
        uint32_t m[16];
        const float g = __ldcg(&g_gate[seg * 32 + lane]);
        ldg8x64<256>(m, km);
        const uint32_t b = seg & 1, full = fulla + 16 * b, mb = ma + b * A_INB;
        mbar_wait(emptya + 8 * b, (~seg >> 1) & 1);
        if (lane < 2) mbar_expect(full + 8 * lane, (YP & 8) ? 0 : 16384 >> lane);
        __syncwarp();
        if (lane < 3 && !(YP & 8)) ((EF & 2) ? bulk_load_ef : bulk_load)(sb + A_IN + b * A_INB + lane * SEGB, g_seg + ((size_t)(seg & RING) * 96 + cta * 3 + lane) * 8192, 8192, full + (lane & 2) * 4);
        int n = 0;
#pragma unroll 1
        while (stale<8, 2>(m, ktag) && ++n < SPIN_LIMIT) { if (seg < UNP - 1) __nanosleep(200); ldg8x64<256>(m, km); }
        TSTAMP(1);
#pragma unroll
        for (int i = 0; i < 4; i++) stsm4(mb + (i >> 1) * SEGB + (i & 1) * 512, m[4 * i], m[4 * i + 1], m[4 * i + 2], m[4 * i + 3]);
        sts32(sb + A_G + b * 128 + lane * 4, __float_as_uint(1.f - g));
        fence_async();
        __syncwarp();
        if (lane == 0) mbar_arrive(full);
      }
    }
    if (w == 3 && QM) {
      const unsigned char* const hp = tm.red + HINT_OFF + 65536 + (cta & 1) * 4096 + min(lane, 23) * 4;
      uint32_t d = 0;
      int s = 0, n = 0;
#pragma unroll 1
      while (s < NSEG - 1) {
        const uint32_t h = ldg_relaxed32(hp + RED_SLOT(s)), t = (gtime() - 1984) & ~31u, late = latest_hint(h, t, s);
        if (late < 64) {
          d = t + late * 32 + tm.poll + Q_LO;
          sleep_until(d);
          s++; n = 0;
          if (lane == 0) { mbar_arrive(pace + 8); sts64(pace, s < NSEG - 1 ? s : 2 * NSEG, d); }
          sleep_until(d + PACE_NEXT);
        } else {
          if (++n > (s ? 16 : 256) || lds32v(pace + 16)) break;
          if (!s) __nanosleep(100);
        }
      }
      if (s < NSEG - 1 && lane == 0) { mbar_arrive(pace + 8); sts64(pace, 2 * NSEG, d); }
    }
    if (w != 0) return;
    const bool lead = lane == 0;
#pragma unroll 1
    for (int it = 0, st = 0, ph = 1, k = 0, col = (cta & 1) * (DM / 2); it < ((XP & 256) ? 0 : 72); it++) {
      mbar_wait(empty1 + 8 * st, ph);
      if (QM & 1) quiet_wait(pace);
      if (elect_one()) {
        mbar_expect(full1 + 8 * st, A_STAGE + 1536);
        tma_load3d(sb + st * A_STAGE, &tm.x, k, (cta >> 1) * A_ROWS - 7, 0, full1 + 8 * st);
        tma_load3d(sb + st * A_STAGE + 8192, &tm.wa, col, k, 0, full1 + 8 * st);
        tma_load3d(sb + A_W8 + st * 1536, &tm.wa8, col + 64, k, 0, full1 + 8 * st);
      }
      __syncwarp();
      if (++st == A_ST) { st = 0; ph ^= 1; }
      k += 32;
      if (k == DM) { k = 0; col += 72; }
    }
    auto load_wo = [&](uint32_t dst, int g, int kb, uint32_t mb) {
      if (kb < 64) tma_load(dst, &tm.wob, p3_mt(g) * 64, kb * 64, mb);
      else tma_load(dst, &tm.woa, p3_mt(g) * 64, (kb - 64) * 64, mb);
    };
    if (lead) mbar_expect(fullw, 16 * 8192);
#pragma unroll 1
    for (int st = 0; st < A_ST; st++) {
      if (!(XP & 256)) mbar_wait(empty1 + 8 * st, 1);
      if (lane < 16 && min(((lane + 1) * 8192 - 1) / A_STAGE, A_ST - 1) == st) load_wo(sb + lane * 8192, lane >> 3, p3_ks(lane >> 3) * 9 + (lane & 7), fullw);
      __syncwarp();
    }
    __syncwarp(); bar_sync(6, 288);
    if (lead) mbar_expect(fullw + 8, 2 * 8192 + (p3_ks(0) >= 4 ? 4096 : 0));
    __syncwarp();
    if (lane < 2) {
      load_wo(sb + (16 + lane) * 8192, lane, p3_ks(lane) * 9 + 8, fullw + 8);
      if (p3_ks(0) >= 4) tma_load(sb + A_XW + lane * 2048, &tm.woa16, p3_mt(lane) * 64, 448 + p3_ks(lane) * 16, fullw + 8);
    }
    __syncwarp();
    if (lead) aux_barrier(1, epoch, ALLW || p3_ks(0) >= 4);
    __syncwarp(); bar_sync(6, 288);
    {
      int avail = 0, sl = 0, ph = 1;
      const int h = (9 * p3_ks(0) >> 1) + lane;
#pragma unroll 1
      for (int seg = 0; seg < ((XP & 2048) ? 0 : NSEG); seg++) {
        if (avail <= seg) avail = wait_flags(&g_oflag[min(h, NH - 1) * 32], lane < (wide ? 5 : 9), fbase, seg);
        SSTAMP(seg, 4);
        for (int g = 0; g < (wide ? 1 : 2); g++) {
          const int ks = p3_ks(g);
          mbar_wait(empty3 + 8 * sl, ph);
          if ((QM & 4) && tick_wait(pace, seg + (QM >> 4 & 1) + 1) && ODLY) __nanosleep(ODLY);
          if (YP & 4) { if (lead) mbar_arrive(full3 + 8 * sl); }
          else if (elect_one()) {
            mbar_expect(full3 + 8 * sl, XT + (ks >= 4 ? 1024 : 0));
            tma_load3d(sb + sl * XT, &tm.o3, 0, seg * 32, ks * 9, full3 + 8 * sl);
            if (ks >= 4) tma_load(sb + A_XT + sl * 1024, &tm.o16, 72 * 64 - 64 + ks * 16, seg * 32, full3 + 8 * sl);
          }
          __syncwarp();
          if (++sl == (wide ? 3 : 4)) { sl = 0; ph ^= 1; }
        }
      }
    }
    sts32(pace + 16, 1);
    __syncwarp(); bar_sync(6, 288);
    asm volatile("griddepcontrol.wait;" ::: "memory");
  } else if (wg == 2) {
    asm volatile("setmaxnreg.dec.sync.aligned.u32 64;");
    if (cta < NH) {
      if (tid == 256) { mbar_expect(fullg, 64 * DM * 2); bulk_load(sb + A_IN, x + cta * 64 * DM, 64 * DM * 2, fullg); }
      uint32_t gw[9];
#pragma unroll
      for (int j = 0; j < 9; j++) gw[j] = ((const uint32_t*)gate_w)[j * 32 + lane];
      mbar_wait(fullg, 0);
      float mine = 0.f;
#pragma unroll 4
      for (int u = 0; u < 16; u++) {
        float d0 = 0.f, d1 = 0.f;
#pragma unroll
        for (int j = 0; j < 9; j++) {
          const uint32_t a = lds32(sb + A_IN + (w * 16 + u) * (DM * 2) + j * 128 + lane * 4);
          d0 = fmaf(bf_lo(a), bf_lo(gw[j]), d0); d1 = fmaf(bf_hi(a), bf_hi(gw[j]), d1);
        }
        d0 = warp_sum(d0 + d1);
        if (lane == u) mine = d0;
      }
      if (lane < 16) g_gate[cta * 64 + w * 16 + lane] = 1.f / (1.f + __expf(-mine));
      fence_async();
    }
    bar_sync(3, 128);
    if (tid == 256) { aux_barrier(0, epoch); if (cta == 0) *(volatile unsigned*)&g_epoch2 = epoch + 1; }
    __syncwarp();
    bar_sync(3, 128);
    if (w == 0) bar_arrive(8, 288);
    if (w == 1 && cta < NH) bar_arrive(10, 64);
    if (cta < NH) {
      CDECL;
#pragma unroll 1
      for (int seg = 0; seg < ((XP & 2048) ? 0 : NSEG); seg++) {
        CSTAMP(0);
        const uint32_t in = sb + A_IN + (seg & 1) * A_INB;
        const uint64_t qd = make_desc(in, 128, 1024, 0);
        mbar_wait(fulla + 16 * (seg & 1), (seg >> 1) & 1);
        CSTAMP(3);
        SSTAMP(seg, 0);
        float d[2][16];
        {
          float a[20];
          uint32_t vm[16];
          const unsigned char* vp = g_km + (size_t)(seg * NH + cta) * 4096 + 2048 + lane * 16;
          if (w == 3) ldg4x128<512>(vm, vp);
          WG_FENCE();
#pragma unroll
          for (int k = 0; k < ((YP & 16) ? 1 : 8); k++) wgmma_n40_ss(a, qd + ((k >> 2) * SEGB + (k & 3) * 256 >> 4), qd + ((k >> 2) * SEGB + (k & 3) * 256 + 4096 >> 4), k > 0);
          const uint32_t ga = sb + A_G + (seg & 1) * 128 + (w & 1) * 64 + (lane >> 2) * 4;
          const float f0 = __uint_as_float(lds32(ga)), f1 = __uint_as_float(lds32(ga + 32));
          WG_COMMIT();
          WG_WAIT(0);
          CSTAMP(5);
          SSTAMP(seg, 1);
          if (w < 2) {
            const int lim = w * 16 + (lane >> 2) - 2 * (lane & 3);
            float m0 = -3.0e38f, m1 = -3.0e38f;
#pragma unroll
            for (int i = 0; i < 20; i++) {
              a[i] *= SM_SCALE * LOG2E;
              if (i < 16 && (i >> 2) * 8 + (i & 1) - (i & 2) * 4 > lim) a[i] = -1.0e9f * LOG2E;
              if (i & 2) m1 = fmaxf(m1, a[i]); else m0 = fmaxf(m0, a[i]);
            }
#pragma unroll
            for (int o = 1; o < 4; o <<= 1) { m0 = fmaxf(m0, __shfl_xor_sync(0xffffffffu, m0, o)); m1 = fmaxf(m1, __shfl_xor_sync(0xffffffffu, m1, o)); }
            float s0 = 0.f, s1 = 0.f;
#pragma unroll
            for (int i = 0; i < 20; i++) { a[i] = ex2(a[i] - (i & 2 ? m1 : m0)); if (i & 2) s1 += a[i]; else s0 += a[i]; }
#pragma unroll
            for (int o = 1; o < 4; o <<= 1) { s0 += __shfl_xor_sync(0xffffffffu, s0, o); s1 += __shfl_xor_sync(0xffffffffu, s1, o); }
            s0 = f0 * rcp(s0); s1 = f1 * rcp(s1);
            uint32_t p[10];
#pragma unroll
            for (int i = 0; i < 10; i++) p[i] = pack_bf16(a[2 * i] * (i & 1 ? s1 : s0), a[2 * i + 1] * (i & 1 ? s1 : s0));
            const uint32_t pa = sb + A_P + (2 * w + ((lane >> 3) & 1)) * 768 + (lane >> 4) * 128 + (lane & 7) * 16;
            stsm4t(pa, p[0], p[1], p[2], p[3]); stsm4t(pa + 256, p[4], p[5], p[6], p[7]); stsm4t(pa + 512, p[8], p[9], 0, 0);
            CSTAMP(6);
            fence_async();
            CSTAMP(7);
          } else if (w == 3) {
            int n = 0;
#pragma unroll 1
            while (stale<4, 4>(vm, (epoch + 1) & 1) && ++n < SPIN_LIMIT) ldg4x128<512>(vm, vp);
#pragma unroll
            for (int i = 0; i < 4; i++) stsm4(in + 2 * SEGB + 8192 + (lane >> 4) * 1024 + (lane & 15) * 16 + i * 256, vm[4 * i], vm[4 * i + 1], vm[4 * i + 2], vm[4 * i + 3]);
            fence_async();
            mbar_wait(fulla + 16 * (seg & 1) + 8, (seg >> 1) & 1);
          }
        }
        CSTAMP(8);

        bar_sync(5, 160);
        CSTAMP(10);
        SSTAMP(seg, 2);
        const uint64_t pd = make_desc(sb + A_P, 128, 768, 0), vd = make_desc(in + 2 * SEGB, 128, 512, 0), md = make_desc(in + 2 * SEGB + 8192, 0, 128, 0);
        WG_FENCE();
#pragma unroll
        for (int i = 0; i < 2; i++) {
          wgmma_n32_ss<0>(d[i], vd + i * 256, pd, 0);
          wgmma_n32_ss<0>(d[i], vd + i * 256 + 16, pd + 16, 1);
          wgmma_n32_ss<0>(d[i], md + i * 64, pd + 32, 1);
        }
        WG_COMMIT();
        WG_WAIT(0);
        CSTAMP(11);
        if (lane == 0) mbar_arrive(emptya + 8 * (seg & 1));
#pragma unroll
        for (int i = 0; i < 2; i++) {
          const uint32_t oa = sb + A_OST + i * 4096 + ((lane & 7) + ((lane >> 4) << 3)) * 128 + (((2 * w + ((lane >> 3) & 1)) ^ (lane & 7)) << 4);
          stsm4t(oa, pack_bf16(d[i][0], d[i][1]), pack_bf16(d[i][2], d[i][3]), pack_bf16(d[i][4], d[i][5]), pack_bf16(d[i][6], d[i][7]));
          stsm4t(oa + 2048, pack_bf16(d[i][8], d[i][9]), pack_bf16(d[i][10], d[i][11]), pack_bf16(d[i][12], d[i][13]), pack_bf16(d[i][14], d[i][15]));
        }
        CSTAMP(12);
        bar_sync(4, 160);
        SSTAMP(seg, 3);
      }
      CDUMP;
    }
  } else {
    asm volatile("setmaxnreg.inc.sync.aligned.u32 %0;" :: "n"(TWO ? 208 : 200));
    {
      const int g = lane >> 2, t = lane & 3, r0 = (cta >> 1) * A_ROWS - 7 + w * 16;
      const uint32_t prev = (2 * t > g ? 0xffffu : 0u) | (2 * t + 1 > g ? 0xffff0000u : 0u);
      const int k0 = r0 + 2 * t - (2 * t > g ? 8 : 0), k1 = r0 + 2 * t + 1 - (2 * t + 1 > g ? 8 : 0);
      const uint32_t slot = sb + A_EXC + (wg * 4 + w) * 2304;
      float gl = 0.f, gh = 0.f;
      int st = 0, ph = 0;
#pragma unroll 1
      for (int p = -AWARM; p < ((XP & 256) ? 0 : 4); p++) {
        float big[96], sml[12];
        if (p == WPF && tid < 18) {
          const int kb = p3_ks(tid >= 9) * 9 + tid % 9;
          tma_prefetch(kb < 64 ? &tm.wob : &tm.woa, p3_mt(tid >= 9) * 64, (kb & 63) * 64);
        }
        __syncwarp();
#pragma unroll
        for (int i = 0; i < 96; i++) big[i] = 0.f;
#pragma unroll
        for (int i = 0; i < 12; i++) sml[i] = 0.f;
#pragma unroll 1
        for (int k = p < 0 ? 18 : 0; k < 18; k++) {
          mbar_wait(full1 + 8 * st, ph);
          const uint64_t da = make_desc(sb + st * A_STAGE + wg * 4096, 16, 512, 2);
          const uint64_t db = make_desc(sb + st * A_STAGE + 8192, 4096, 1024, 1), dc = make_desc(sb + A_W8 + st * 1536, 128, 512, 0);
          WG_FENCE();
#pragma unroll
          for (int j = 0; j < 2; j++) { wgmma_n192_ss_nt(big, da + j * 2, db + j * 128, 1); wgmma_n24_ss_nt(sml, da + j * 2, dc + j * 16, 1); }
          WG_COMMIT();
          WG_WAIT(1);
          if (k > 0 && lane == 0) mbar_arrive(empty1 + 8 * (st ? st - 1 : A_ST - 1));
          if (++st == A_ST) { st = 0; ph ^= 1; }
        }
        WG_WAIT(0);
        ASTAMP(16 + max(p, 0) + wg * 16);
        if (lane == 0 && p >= 0) mbar_arrive(empty1 + 8 * (st ? st - 1 : A_ST - 1));
        uint32_t f[3][9][2];
#pragma unroll
        for (int c = 0; c < 3; c++)
#pragma unroll
          for (int j = 0; j < 9; j++)
#pragma unroll
            for (int i = 0; i < 2; i++) {
              const float* a = j < 8 ? &big[(c * 8 + j) * 4 + 2 * i] : &sml[c * 4 + 2 * i];
              f[c][j][i] = c < 2 ? pack_bf16(a[0], a[1]) : trans8(pack_bf16(a[0], a[1]));
            }
        if (p == 0) {
          bar_sync(8, 288);
          gl = __ldcg(&g_gate[min(max(r0 + g, 0), S_LEN / 2 - 1) * 2 + wg]); gh = __ldcg(&g_gate[min(max(r0 + g + 8, 0), S_LEN / 2 - 1) * 2 + wg]);
        }
        asm volatile("cp.async.bulk.wait_group.read 0;" ::: "memory");
        __syncwarp();
#pragma unroll
        for (int j = 0; j < 8; j += 2) sts128(slot + j * 256 + lane * 16, f[1][j][1], f[2][j][1], f[1][j + 1][1], f[2][j + 1][1]);
        sts64(slot + 2048 + lane * 8, f[1][8][1], f[2][8][1]);
        bar_sync(1 + wg, 128);
        ASTAMP(24 + max(p, 0) + wg * 16);
        uint32_t pv[9][2];
#pragma unroll
        for (int j = 0; j < 9; j++) pv[j][0] = pv[j][1] = 0;
        if (w) {
#pragma unroll
          for (int j = 0; j < 8; j += 2) lds128(slot - 2304 + j * 256 + lane * 16, pv[j]);
          lds64(slot - 256 + lane * 8, pv[8][0], pv[8][1]);
        }
        float a[4][4], m[4][2];
#pragma unroll
        for (int h = 0; h < 4; h++) {
          const int j = 2 * h;
          const uint32_t qa[4] = {t >= h ? f[0][j][0] : 0, t >= h ? f[0][j][1] : 0, f[0][j + 1][0], f[0][j + 1][1]};
          const uint32_t qb0 = t <= h ? f[0][j + 2][0] : 0, qb1 = t <= h ? f[0][j + 2][1] : 0;
          float s0[4], s1[4], s2[4];
          mma16816z(s1, qa, f[1][j][0], f[1][j + 1][0]); mma16816z(s2, qa, f[1][j][1], f[1][j + 1][1]); mma16816z(s0, qa, pv[j][0], pv[j + 1][0]);
          mma1688(s1, qb0, qb1, f[1][j + 2][0]); mma1688(s2, qb0, qb1, f[1][j + 2][1]); mma1688(s0, qb0, qb1, pv[j + 2][0]);
          a[h][0] = 2 * t > g ? s0[0] : s1[0]; a[h][1] = 2 * t + 1 > g ? s0[1] : s1[1]; a[h][2] = 2 * t > g ? s1[2] : s2[2]; a[h][3] = 2 * t + 1 > g ? s1[3] : s2[3];
        }
#pragma unroll
        for (int h = 0; h < 4; h++) {
#pragma unroll
          for (int i = 0; i < 4; i++) a[h][i] = (i & 1 ? k1 : k0) + (i & 2) * 4 >= 0 ? a[h][i] * (0.23570226039551584f * LOG2E) : -1.0e9f * LOG2E;
          m[h][0] = fmaxf(a[h][0], a[h][1]); m[h][1] = fmaxf(a[h][2], a[h][3]);
        }
#pragma unroll
        for (int x = 1; x < 4; x <<= 1)
#pragma unroll
          for (int i = 0; i < 8; i++) m[i >> 1][i & 1] = fmaxf(m[i >> 1][i & 1], __shfl_xor_sync(0xffffffffu, m[i >> 1][i & 1], x));
#pragma unroll
        for (int h = 0; h < 4; h++) {
#pragma unroll
          for (int i = 0; i < 4; i++) a[h][i] = ex2(a[h][i] - m[h][i >> 1]);
          m[h][0] = a[h][0] + a[h][1]; m[h][1] = a[h][2] + a[h][3];
        }
#pragma unroll
        for (int x = 1; x < 4; x <<= 1)
#pragma unroll
          for (int i = 0; i < 8; i++) m[i >> 1][i & 1] += __shfl_xor_sync(0xffffffffu, m[i >> 1][i & 1], x);
        uint32_t o[9][2];
#pragma unroll
        for (int h = 0; h < 4; h++) {
          const int j = 2 * h;
          const float z0 = gl * rcp(m[h][0]), z1 = gh * rcp(m[h][1]);
          const uint32_t pl = pack_bf16(a[h][0] * z0, a[h][1] * z0), pu = pack_bf16(a[h][2] * z1, a[h][3] * z1);
          const uint32_t pa[4] = {pl & prev, 0, pl & ~prev, pu & prev};
          float d[3][4];
#pragma unroll
          for (int i = 0; i < 3; i++) mma16816z(d[i], pa, pv[j + i][1], f[2][j + i][0]);
#pragma unroll
          for (int i = 0; i < 3; i++) mma1688(d[i], 0, pu & ~prev, f[2][j + i][1]);
#pragma unroll
          for (int i = 0; i < 3; i++) {
            const uint32_t d0 = pack_bf16(d[i][0], d[i][1]), d1 = pack_bf16(d[i][2], d[i][3]);
            o[j + i][0] = i == 0 && h > 0 && t < h ? o[j][0] : d0;
            o[j + i][1] = i == 0 && h > 0 && t < h ? o[j][1] : d1;
          }
        }
        ASTAMP(28 + max(p, 0) + wg * 16);
        bar_sync(1 + wg, 128);
        const uint32_t oa = slot + (lane & 15) * 144 + (lane >> 4) * 16;
#pragma unroll
        for (int j = 0; j < 8; j += 2) stsm4(oa + j * 16, o[j][0], o[j][1], o[j + 1][0], o[j + 1][1]);
        asm volatile("stmatrix.sync.aligned.m8n8.x2.shared.b16 [%0], {%1,%2};" :: "r"(oa + 128), "r"(o[8][0]), "r"(o[8][1]) : "memory");
        fence_async();
        __syncwarp();
        if (QM & 64) quiet_wait(pace);
        if (lane < 16 && w * 16 + lane >= 7 && r0 + lane < S_LEN / 2 && p >= 0)
          asm volatile("cp.async.bulk.global.shared::cta.bulk_group [%0], [%1], 144;"
                       :: "l"(g_Ocat + (size_t)((r0 + lane) * 2 + wg) * KCAT + 4096 + (cta & 1) * (DM / 2) + p * 72), "r"(slot + lane * 144) : "memory");
        asm volatile("cp.async.bulk.commit_group;" ::: "memory");
        ASTAMP(20 + max(p, 0) + wg * 16);
      }
      if (XP & 256) bar_sync(8, 288);
      asm volatile("cp.async.bulk.wait_group 0;" ::: "memory");
    }
    ASTAMP(3);
    bar_arrive(6, 288);
    uint32_t wa[37][4];
    mbar_wait(fullw, 0);
    const uint32_t la = sb + ((lane & 7) + ((lane >> 4) << 3)) * 128 + (((2 * w + ((lane >> 3) & 1)) ^ (lane & 7)) << 4);
#pragma unroll
    for (int k = 0; k < 32; k++) ldsm4t(wa[k], la + wg * 65536 + k * 2048);
    mbar_wait(fullw + 8, 0);
#pragma unroll
    for (int k = 32; k < 36; k++) ldsm4t(wa[k], la + wg * 8192 + 65536 + k * 2048);
    ldsm4t(wa[36], la + A_XW + wg * 2048);
    fence_async();
    if (XP & 2048) bar_sync(6, 288); else bar_arrive(6, 288);
    ASTAMP(4);
    const int ks = p3_ks(wg), mt = p3_mt(wg);
    uint32_t v[16];
    auto fetch = [&](int seg) { ldg8x64<1024>(v, g_part + (((seg & 7) * 9 + mt) * 4 + (ks & 3)) * 1024 + (tid & 127)); };
    auto finish = [&](int seg) {
      const uint32_t tagv = (~seg >> 3) & 1;
      int n = 0;
#pragma unroll 1
      while (!(YP & 512) && stale<8, 2>(v, tagv) && ++n < SPIN_LIMIT) {
        if (seg < NSEG - 2) __nanosleep(RSL);
        fetch(seg);
      }
      float own[4] = {bf_lo(v[0]), bf_hi(v[0]), bf_lo(v[1]), bf_hi(v[1])};
#pragma unroll
      for (int j = 1; j < 8; j++) { own[0] += bf_lo(v[2 * j]); own[1] += bf_hi(v[2 * j]); own[2] += bf_lo(v[2 * j + 1]); own[3] += bf_hi(v[2 * j + 1]); }
      uint32_t p0 = pack_bf16(own[0], own[1]), p1 = pack_bf16(own[2], own[3]);
      asm volatile("movmatrix.sync.aligned.m8n8.trans.b16 %0, %0;" : "+r"(p0));
      asm volatile("movmatrix.sync.aligned.m8n8.trans.b16 %0, %0;" : "+r"(p1));
      uint32_t* o = (uint32_t*)(out + (size_t)(seg * 32 + (ks & 3) * 8 + (lane >> 2)) * DM + mt * 64 + w * 16) + (lane & 3);
      if (!(YP & 256) || p0 == 0x12345678) { o[0] = p0; o[4] = p1; }
      SSTAMP(seg, 7);
    };
    float acc[16], acc2[16];
#pragma unroll
    for (int i = 0; i < 16; i++) acc[i] = acc2[i] = 0.f;
    int pend = -1, sl = wide ? 0 : wg, ph = 0;
    if (PING && wg) bar_arrive(1, 256);
    CDECL;
    auto run = [&](auto extra) {
#pragma unroll 1
    for (int seg = 0; seg <= ((XP & 2048) ? -1 : NSEG); seg++) {
      CSTAMP(0);
      const bool fin = pend >= 0 && (seg - pend >= FLAG || seg == NSEG);
      if (seg < NSEG) mbar_wait(full3 + 8 * sl, ph);
      if (FPOS == 1 && fin) fetch(pend);
      if (SDLY) {
        uint32_t n, d;
        asm volatile("ld.volatile.shared.v2.b32 {%0,%1}, [%2];" : "=r"(n), "=r"(d) : "r"(pace) : "memory");
        if ((int)n <= seg + 3) sleep_until(d + SDLY);
      }
      CSTAMP(1);
      if (seg < NSEG) {
      if (wg) SSTAMP(seg, 5);
      if (seg < PING) bar_sync(1 + wg, 256);
      CSTAMP(7);
      const uint64_t db = make_desc(sb + sl * XT, 16, 1024, 1);
      WG_FENCE();
#pragma unroll
      for (int k = 0; k < ((XP & 1024) ? 1 : 36); k++)
        wgmma_n32_rs(TWO && (k & 1) ? acc2 : acc, wa[k][0], wa[k][1], wa[k][2], wa[k][3], db + (k >> 2) * 256 + (k & 3) * 2, k >> TWO);
      if (decltype(extra)::value) wgmma_n32_rs(acc, wa[36][0], wa[36][1], wa[36][2], wa[36][3], make_desc(sb + A_XT + sl * 1024, 16, 256, 3), 1);
      WG_COMMIT();
      if (seg < PING) bar_arrive(2 - wg, 256);
      CSTAMP(2);
      CSTAMP(3);
      WG_WAIT(0);
      CSTAMP(4);
      if (wg) SSTAMP(seg, 6);
      if (lane == 0) mbar_arrive(empty3 + 8 * sl);
      sl += wide ? 1 : 2;
      if (sl >= (wide ? 3 : 4)) { sl -= wide ? 3 : 4; ph ^= 1; }
      uint2* dst = g_part + (((seg & 7) * 9 + mt) * 32 + ks) * 128 + (tid & 127);
      uint32_t q[8];
      if (TWO)
#pragma unroll
        for (int j = 0; j < 16; j++) acc[j] += acc2[j];
#pragma unroll
      for (int j = 0; j < 8; j++) q[j] = j & 1 ? pack_bf16(acc[2 * j], acc[2 * j + 1]) : (pack_bf16(acc[2 * j], acc[2 * j + 1]) & ~1u) | ((~seg >> 3) & 1);
      if (QM & 32) tick_wait(pace, seg + (QM >> 4 & 1) + 2);
      if (!(YP & 1025) || q[0] == 0x12345678)
      asm volatile("st.relaxed.gpu.global.v2.b32 [%0], {%1,%2};\nst.relaxed.gpu.global.v2.b32 [%0 + 8192], {%3,%4};\n"
                   "st.relaxed.gpu.global.v2.b32 [%0 + 16384], {%5,%6};\nst.relaxed.gpu.global.v2.b32 [%0 + 24576], {%7,%8};"
                   :: "l"(dst), "r"(q[0]), "r"(q[1]), "r"(q[2]), "r"(q[3]), "r"(q[4]), "r"(q[5]), "r"(q[6]), "r"(q[7]) : "memory");
      }
      CSTAMP(5);
      if (fin) { finish(pend); pend = -1; }
      CSTAMP(6);
      if ((seg & 1) == ks >> 2 && !(YP & 1)) pend = seg;
      if (wg && (seg & 7) == 6) ASTAMP(5 + (seg >> 3));
    }
    };
    if (ks >= 4) run(BoolC<true>()); else run(BoolC<false>());
    if (PING && !wg) bar_sync(1, 256);
    CDUMP;
    ASTAMP(13);
    bar_sync(6, 288);
  }
}

typedef CUresult (*EncodeFn)(CUtensorMap*, CUtensorMapDataType, cuuint32_t, void*, const cuuint64_t*, const cuuint64_t*,
                             const cuuint32_t*, const cuuint32_t*, CUtensorMapInterleave, CUtensorMapSwizzle,
                             CUtensorMapL2promotion, CUtensorMapFloatOOBfill);
#define PROMO 2
static void make_map(EncodeFn enc, CUtensorMap* m, const void* p, int rows, int cols, int box_rows) {
  cuuint64_t dims[2] = {(cuuint64_t)cols, (cuuint64_t)rows};
  cuuint64_t strides[1] = {(cuuint64_t)cols * 2};
  cuuint32_t box[2] = {64, (cuuint32_t)box_rows};
  cuuint32_t es[2] = {1, 1};
  enc(m, CU_TENSOR_MAP_DATA_TYPE_BFLOAT16, 2, (void*)p, dims, strides, box, es, CU_TENSOR_MAP_INTERLEAVE_NONE,
      CU_TENSOR_MAP_SWIZZLE_128B, (CUtensorMapL2promotion)PROMO, CU_TENSOR_MAP_FLOAT_OOB_FILL_NONE);
}

constexpr int g_poll = POLL_NS;
extern "C" void kernel_launch(void* const* d_in, const int* in_sizes, int n_in, void* d_out, int out_size) {
  const bf16* x = (const bf16*)d_in[0];
  const bf16* wqkvA = (const bf16*)d_in[1];
  const bf16* woA = (const bf16*)d_in[2];
  const bf16* mem0 = (const bf16*)d_in[4];
  const bf16* Wq = (const bf16*)d_in[5];
  const bf16* Wk = (const bf16*)d_in[6];
  const bf16* Wv = (const bf16*)d_in[7];
  const bf16* Wo = (const bf16*)d_in[8];
  const bf16* gate_w = (const bf16*)d_in[10];
  static EncodeFn enc = nullptr;
  static void *pO = nullptr, *pR = nullptr;
  if (!enc) {
    cudaDriverEntryPointQueryResult qr;
    cudaGetDriverEntryPoint("cuTensorMapEncodeTiled", (void**)&enc, cudaEnableDefault, &qr);
    cudaGetSymbolAddress(&pO, g_Ocat);
    cudaGetSymbolAddress(&pR, g_red_raw);
    cudaFuncSetAttribute(rec_kernel, cudaFuncAttributeMaxDynamicSharedMemorySize, SM_TOTAL);
    cudaFuncSetAttribute(aux_kernel, cudaFuncAttributeMaxDynamicSharedMemorySize, A_TOTAL);
  }
  RMaps rm;
  rm.poll = g_poll;
  rm.w[0] = (const unsigned char*)Wk; rm.w[1] = (const unsigned char*)Wq; rm.w[2] = (const unsigned char*)Wv; rm.w[3] = (const unsigned char*)Wo;
  rm.red = (unsigned char*)(((uintptr_t)pR + 262143) & ~(uintptr_t)262143);
  {
    cuuint64_t dims[3] = {64, S_LEN, 9}, strides[2] = {DM * 2, 128};
    cuuint32_t box[3] = {64, 32, 9}, es[3] = {1, 1, 1};
    enc(&rm.x, CU_TENSOR_MAP_DATA_TYPE_BFLOAT16, 3, (void*)x, dims, strides, box, es, CU_TENSOR_MAP_INTERLEAVE_NONE,
        CU_TENSOR_MAP_SWIZZLE_128B, CU_TENSOR_MAP_L2_PROMOTION_L2_128B, CU_TENSOR_MAP_FLOAT_OOB_FILL_NONE);
  }
  make_map(enc, &rm.wq, Wq, DM, 4096, 192);
  make_map(enc, &rm.wk, Wk, DM, 4096, 192);
  make_map(enc, &rm.wv, Wv, DM, 4096, 192);
  make_map(enc, &rm.wo, Wo, 4096, DM, 128);
  AMaps am;
  am.red = rm.red; am.poll = rm.poll;
  {
    cuuint64_t dims[3] = {DM, S_LEN / 2, 2}, strides[2] = {DM * 4, DM * 2};
    cuuint32_t box[3] = {32, 64, 2}, es[3] = {1, 1, 1};
    enc(&am.x, CU_TENSOR_MAP_DATA_TYPE_BFLOAT16, 3, (void*)x, dims, strides, box, es, CU_TENSOR_MAP_INTERLEAVE_NONE,
        CU_TENSOR_MAP_SWIZZLE_64B, CU_TENSOR_MAP_L2_PROMOTION_L2_128B, CU_TENSOR_MAP_FLOAT_OOB_FILL_NONE);
    cuuint64_t wdims[3] = {DM, DM, 3}, wstrides[2] = {DM * 6, DM * 2};
    cuuint32_t wbox[3] = {64, 32, 3}, wbox8[3] = {8, 32, 3};
    enc(&am.wa, CU_TENSOR_MAP_DATA_TYPE_BFLOAT16, 3, (void*)wqkvA, wdims, wstrides, wbox, es, CU_TENSOR_MAP_INTERLEAVE_NONE,
        CU_TENSOR_MAP_SWIZZLE_128B, CU_TENSOR_MAP_L2_PROMOTION_L2_128B, CU_TENSOR_MAP_FLOAT_OOB_FILL_NONE);
    enc(&am.wa8, CU_TENSOR_MAP_DATA_TYPE_BFLOAT16, 3, (void*)wqkvA, wdims, wstrides, wbox8, es, CU_TENSOR_MAP_INTERLEAVE_NONE,
        CU_TENSOR_MAP_SWIZZLE_NONE, CU_TENSOR_MAP_L2_PROMOTION_NONE, CU_TENSOR_MAP_FLOAT_OOB_FILL_NONE);
  }
  {
    cuuint64_t dims[3] = {64, S_LEN, KCAT / 64}, strides[2] = {KCAT * 2, 128};
    cuuint32_t box[3] = {64, 32, 9}, es[3] = {1, 1, 1};
    make_map(enc, &am.o, pO, S_LEN, KCAT, 32);
    enc(&am.o3, CU_TENSOR_MAP_DATA_TYPE_BFLOAT16, 3, pO, dims, strides, box, es, CU_TENSOR_MAP_INTERLEAVE_NONE,
        CU_TENSOR_MAP_SWIZZLE_128B, CU_TENSOR_MAP_L2_PROMOTION_L2_128B, CU_TENSOR_MAP_FLOAT_OOB_FILL_NONE);
  }
  make_map(enc, &am.wob, Wo, 4096, DM, 64);
  make_map(enc, &am.woa, woA, DM, DM, 64);
  make_map(enc, &am.woa16, woA, DM, DM, 16);
  {
    cuuint64_t dims[2] = {KCAT, S_LEN}, strides[1] = {KCAT * 2};
    cuuint32_t box[2] = {16, 32}, es[2] = {1, 1};
    enc(&am.o16, CU_TENSOR_MAP_DATA_TYPE_BFLOAT16, 2, pO, dims, strides, box, es, CU_TENSOR_MAP_INTERLEAVE_NONE,
        CU_TENSOR_MAP_SWIZZLE_32B, CU_TENSOR_MAP_L2_PROMOTION_NONE, CU_TENSOR_MAP_FLOAT_OOB_FILL_NONE);
  }

  rec_kernel<<<96, 384, SM_TOTAL, cudaStreamPerThread>>>(rm, x, mem0);
  cudaLaunchConfig_t cfg = {};
  cfg.gridDim = dim3(NAUX); cfg.blockDim = dim3(512); cfg.dynamicSmemBytes = A_TOTAL; cfg.stream = cudaStreamPerThread;
  cudaLaunchAttribute at[1];
  at[0].id = cudaLaunchAttributeProgrammaticStreamSerialization; at[0].val.programmaticStreamSerializationAllowed = 1;
  cfg.attrs = at; cfg.numAttrs = 1;
  if (XP & 16) cfg.numAttrs = 0;
  if (!(XP & 64)) cudaLaunchKernelEx(&cfg, aux_kernel, am, x, gate_w, (bf16*)d_out);
}
```

```cpp
#include <cuda_runtime.h>
#include <cuda_bf16.h>
#include <cuda_fp16.h>
#include <cuda.h>
#include <stdint.h>

typedef __nv_bfloat16 bf16;

constexpr int S_LEN = 2048, DM = 576, NH = 32, DH = 128, NSEG = 64, KCAT = 4096 + 576;
#define RED_LINE(i) (((i) >> 2) * 4096 + ((i) & 1) * 256 + ((i) & 2) * 512)
#define RED_SLOT(s) (((s) & 1) * 128 + ((s) & 2) * 256)

#define POLL_NS 896
#define NII 18
#define W3PRE 4
#define W3MID 4
#define GF 0
#define B5POS 0
#define NUP 4
#define UPF 1
#define B3Q 9
#define B3F 0
#define GATE 8
#define NTL 2
#define B7R 1
#define EXPOS 0
#define VW2 1
#define CLR 1
#define RFW 0
#define NIC 0
#define LEAD 0
#define FIN16 1
#define VXG 0
#define RING 63
#define EXB 0
#define EXD 0
#define EXB2 8192
#define HDLY 0
#define F10 1
#define NPROBE 2
#define WPOS 1
#define CW 0
#define WOPF 0
#define YP 0
#define EF 7
#define MO 0
#define WE 3
#define EXV 2
#define NOB 0
#define QM 60
#define N5 224
#define KP(i) (((i) >> 1) + 4 * ((i) & 1))
#define SPIN_LIMIT (1 << 14)
#define XP 0

__device__ __align__(1024) bf16 g_Ocat[S_LEN * KCAT];
__device__ __align__(1024) unsigned char g_red_raw[2 * 262144];
constexpr int HINT_OFF = 2048;
__device__ __align__(16) float g_gate[S_LEN];
__device__ __align__(128) uint4 g_stats[96 * 2];
__device__ unsigned g_epoch;
__device__ unsigned g_epoch2;
__device__ unsigned g_oflag[NH * 32];
__device__ unsigned g_abar[3 * 32];
__device__ unsigned g_sflag[96 * 8];
__device__ __align__(1024) unsigned char g_seg[NSEG * 96 * 8192];
__device__ __align__(1024) unsigned char g_km[NSEG * NH * 4096];
__device__ __align__(1024) uint2 g_part[8 * 9 * 4 * 8 * 128];
__device__ int g_err;
#define SSTAMP(seg, idx)
#define TSTAMP(idx)
#define QSTAMP(idx)
#define PROF(idx)
#define PROFP(idx)
#define STAMP(idx)
#define ASTAMP(idx)
#define WSTAMP(idx)

#define CSTAMP(idx)
#define CDECL
#define CDUMP
#define DI __device__ __forceinline__
DI uint32_t smem_u32(const void* p) { return (uint32_t)__cvta_generic_to_shared(p); }
DI uint32_t clock32() { uint32_t c; asm volatile("mov.u32 %0, %%clock;" : "=r"(c) :: "memory"); return c; }
DI uint32_t gtime() { uint32_t c; asm volatile("mov.u32 %0, %%globaltimer_lo;" : "=r"(c) :: "memory"); return c; }
DI uint32_t ldg_relaxed32(const void* p) { uint32_t v; asm volatile("ld.relaxed.gpu.global.b32 %0, [%1];" : "=r"(v) : "l"(p) : "memory"); return v; }
DI uint32_t ldg_acquire32(const void* p) { uint32_t v; asm volatile("ld.acquire.gpu.global.b32 %0, [%1];" : "=r"(v) : "l"(p) : "memory"); return v; }
DI void stg_relaxed32(void* p, uint32_t v) { asm volatile("st.relaxed.gpu.global.b32 [%0], %1;" :: "l"(p), "r"(v) : "memory"); }
DI int head_id() { int c; asm volatile("mov.u32 %0, %%clusterid.x;" : "=r"(c)); return c; }
DI uint32_t mapa(uint32_t a, uint32_t r) { uint32_t o; asm("mapa.shared::cluster.u32 %0, %1, %2;" : "=r"(o) : "r"(a), "r"(r)); return o; }
DI void cluster_arrive() { asm volatile("barrier.cluster.arrive.relaxed.aligned;" ::: "memory"); }
DI void cluster_wait() { asm volatile("barrier.cluster.wait.aligned;" ::: "memory"); }
DI void cluster_sync() { asm volatile("barrier.cluster.arrive.release.aligned;\nbarrier.cluster.wait.acquire.aligned;" ::: "memory"); }
DI void mbar_init(uint32_t b, uint32_t c) { asm volatile("mbarrier.init.shared::cta.b64 [%0], %1;" :: "r"(b), "r"(c) : "memory"); }
DI void mbar_expect(uint32_t b, uint32_t tx) { asm volatile("mbarrier.arrive.expect_tx.shared::cta.b64 _, [%0], %1;" :: "r"(b), "r"(tx) : "memory"); }
DI void mbar_arrive(uint32_t b) { asm volatile("mbarrier.arrive.shared::cta.b64 _, [%0];" :: "r"(b) : "memory"); }
DI void mbar_wait(uint32_t b, uint32_t par) {
  asm volatile("{\n.reg .pred p;\n.reg .u32 n, q;\nmov.u32 n, 0;\n"
               "WL: add.u32 n, n, 1;\nshr.u32 q, n, 12;\nxor.b32 q, q, %1;\n"
               "mbarrier.try_wait.parity.shared::cta.b64 p, [%0], q;\n@!p bra.uni WL;\n}"
               :: "r"(b), "r"(par) : "memory");
}
DI void wait_until(uint32_t t) {
  const uint32_t now = gtime();
  t = min(t, now + 8192);
  asm volatile("{\n.reg .pred p;\n.reg .u32 c;\nTL: mov.u32 c, %%globaltimer_lo;\nsetp.lt.u32 p, c, %0;\n@p bra.uni TL;\n}" :: "r"(t) : "memory");
}
#define PIN(v) v = __shfl_xor_sync(0xffffffffu, v, 0)
#define SCHED_FENCE(k) asm volatile("{\n.reg .pred p;\nsetp.eq.u32 p, %0, %1;\n@p exit;\n}" :: "r"(fence_reg), "r"(k) : "memory")
#define MEM_ORDER(k) asm volatile("{\n.reg .pred p;\nsetp.eq.u32 p, %0, %1;\n@p st.shared.u32 [%0], %0;\n}" :: "r"(fence_reg), "r"(k + 64) : "memory")
DI void bar_sync(int id, int n) { asm volatile("bar.sync %0, %1;" :: "r"(id), "r"(n) : "memory"); }
DI void bar_arrive(int id, int n) { asm volatile("bar.arrive %0, %1;" :: "r"(id), "r"(n) : "memory"); }
DI void fence_async() { asm volatile("fence.proxy.async.shared::cta;" ::: "memory"); }
DI void st_async4(uint32_t a, uint32_t x, uint32_t y, uint32_t z, uint32_t w, uint32_t mb) {
  asm volatile("st.async.weak.shared::cluster.mbarrier::complete_tx::bytes.v4.b32 [%0], {%1,%2,%3,%4}, [%5];"
               :: "r"(a), "r"(x), "r"(y), "r"(z), "r"(w), "r"(mb) : "memory");
}
DI void st_async2(uint32_t a, uint32_t x, uint32_t y, uint32_t mb) {
  asm volatile("st.async.weak.shared::cluster.mbarrier::complete_tx::bytes.v2.b32 [%0], {%1,%2}, [%3];"
               :: "r"(a), "r"(x), "r"(y), "r"(mb) : "memory");
}
DI void sts32(uint32_t a, uint32_t x) { asm volatile("st.shared.b32 [%0], %1;" :: "r"(a), "r"(x) : "memory"); }
DI void sts64(uint32_t a, uint32_t x, uint32_t y) { asm volatile("st.shared.v2.b32 [%0], {%1,%2};" :: "r"(a), "r"(x), "r"(y) : "memory"); }
DI void sts128(uint32_t a, uint32_t x, uint32_t y, uint32_t z, uint32_t w) {
  asm volatile("st.shared.v4.b32 [%0], {%1,%2,%3,%4};" :: "r"(a), "r"(x), "r"(y), "r"(z), "r"(w) : "memory");
}
DI uint32_t lds32(uint32_t a) { uint32_t x; asm volatile("ld.shared.b32 %0, [%1];" : "=r"(x) : "r"(a) : "memory"); return x; }
DI uint32_t lds32v(uint32_t a) { uint32_t x; asm volatile("ld.volatile.shared.b32 %0, [%1];" : "=r"(x) : "r"(a) : "memory"); return x; }
DI void lds64(uint32_t a, uint32_t& x, uint32_t& y) { asm volatile("ld.shared.v2.b32 {%0,%1}, [%2];" : "=r"(x), "=r"(y) : "r"(a) : "memory"); }
DI void lds128(uint32_t a, uint32_t* r) {
  asm volatile("ld.shared.v4.b32 {%0,%1,%2,%3}, [%4];" : "=r"(r[0]), "=r"(r[1]), "=r"(r[2]), "=r"(r[3]) : "r"(a) : "memory");
}
DI void lds128f(uint32_t a, float* r) {
  asm volatile("ld.shared.v4.f32 {%0,%1,%2,%3}, [%4];" : "=f"(r[0]), "=f"(r[1]), "=f"(r[2]), "=f"(r[3]) : "r"(a) : "memory");
}
DI void lds64f(uint32_t a, float* r) { asm volatile("ld.shared.v2.f32 {%0,%1}, [%2];" : "=f"(r[0]), "=f"(r[1]) : "r"(a) : "memory"); }
DI void ldsm4t(uint32_t* r, uint32_t a) {
  asm volatile("ldmatrix.sync.aligned.m8n8.x4.trans.shared.b16 {%0,%1,%2,%3}, [%4];"
               : "=r"(r[0]), "=r"(r[1]), "=r"(r[2]), "=r"(r[3]) : "r"(a) : "memory");
}
DI void ldsm4t_in(uint32_t* r, uint32_t a, uint32_t t) {
  asm volatile("{\n.reg .pred p;\nsetp.ne.u32 p, %5, 0;\n@p ldmatrix.sync.aligned.m8n8.x4.trans.shared.b16 {%0,%1,%2,%3}, [%4];\n}"
               : "+r"(r[0]), "+r"(r[1]), "+r"(r[2]), "+r"(r[3]) : "r"(a), "r"(t) : "memory");
}
DI void lds128_in(uint32_t* r, uint32_t a, uint32_t t) {
  asm volatile("{\n.reg .pred p;\nsetp.ne.u32 p, %5, 0;\n@p ld.shared.v4.b32 {%0,%1,%2,%3}, [%4];\n}"
               : "+r"(r[0]), "+r"(r[1]), "+r"(r[2]), "+r"(r[3]) : "r"(a), "r"(t) : "memory");
}
DI void ldsm2t_in(uint32_t* r, uint32_t a, uint32_t t) {
  asm volatile("{\n.reg .pred p;\nsetp.ne.u32 p, %3, 0;\n@p ldmatrix.sync.aligned.m8n8.x2.trans.shared.b16 {%0,%1}, [%2];\n}" : "+r"(r[0]), "+r"(r[1]) : "r"(a), "r"(t) : "memory");
}
DI void reserve2(uint32_t* r) { asm volatile("{\n.reg .u64 t;\nmov.u64 t, %%clock64;\nmov.b64 {%0, %1}, t;\n}" : "=r"(r[0]), "=r"(r[1])); }
DI void scale_sum(float& x, float& y, float s, uint32_t t) {
  asm volatile("{\n.reg .pred p;\nsetp.ne.u32 p, %2, 0;\n@p mul.f32 %0, %0, %1;\n}" : "+f"(y) : "f"(s), "r"(t));
  asm volatile("{\n.reg .pred p;\nsetp.ne.u32 p, %3, 1;\n@p fma.rn.f32 %0, %0, %1, %2;\n}" : "+f"(x) : "f"(s), "f"(y), "r"(t));
}
DI void ldsm4(uint32_t* r, uint32_t a) {
  asm volatile("ldmatrix.sync.aligned.m8n8.x4.shared.b16 {%0,%1,%2,%3}, [%4];"
               : "=r"(r[0]), "=r"(r[1]), "=r"(r[2]), "=r"(r[3]) : "r"(a) : "memory");
}
DI void st_async1(uint32_t a, uint32_t x, uint32_t mb) {
  asm volatile("st.async.weak.shared::cluster.mbarrier::complete_tx::bytes.b32 [%0], %1, [%2];" :: "r"(a), "r"(x), "r"(mb) : "memory");
}
DI void stsm4(uint32_t a, uint32_t x, uint32_t y, uint32_t z, uint32_t w) {
  asm volatile("stmatrix.sync.aligned.m8n8.x4.shared.b16 [%0], {%1,%2,%3,%4};" :: "r"(a), "r"(x), "r"(y), "r"(z), "r"(w) : "memory");
}
DI void stsm4t(uint32_t a, uint32_t x, uint32_t y, uint32_t z, uint32_t w) {
  asm volatile("stmatrix.sync.aligned.m8n8.x4.trans.shared.b16 [%0], {%1,%2,%3,%4};" :: "r"(a), "r"(x), "r"(y), "r"(z), "r"(w) : "memory");
}
DI uint32_t pack_bf16(float lo, float hi) { uint32_t r; asm("cvt.rn.bf16x2.f32 %0, %1, %2;" : "=r"(r) : "f"(hi), "f"(lo)); return r; }
DI uint32_t pack_f16(float lo, float hi) { uint32_t r; asm("cvt.rn.f16x2.f32 %0, %1, %2;" : "=r"(r) : "f"(hi), "f"(lo)); return r; }
DI float ex2(float x) { float y; asm("ex2.approx.ftz.f32 %0, %1;" : "=f"(y) : "f"(x)); return y; }
DI float rcp(float x) { float y; asm("rcp.approx.ftz.f32 %0, %1;" : "=f"(y) : "f"(x)); return y; }
DI float bf_lo(uint32_t x) { return __uint_as_float(x << 16); }
DI float bf_hi(uint32_t x) { return __uint_as_float(x & 0xffff0000u); }
DI void mma16816(float* d, const uint32_t* a, uint32_t b0, uint32_t b1) {
  asm volatile("mma.sync.aligned.m16n8k16.row.col.f32.bf16.bf16.f32 {%0,%1,%2,%3}, {%4,%5,%6,%7}, {%8,%9}, {%0,%1,%2,%3};"
               : "+f"(d[0]), "+f"(d[1]), "+f"(d[2]), "+f"(d[3]) : "r"(a[0]), "r"(a[1]), "r"(a[2]), "r"(a[3]), "r"(b0), "r"(b1));
}
DI void mma16816z(float* d, const uint32_t* a, uint32_t b0, uint32_t b1) {
  asm volatile("mma.sync.aligned.m16n8k16.row.col.f32.bf16.bf16.f32 {%0,%1,%2,%3}, {%4,%5,%6,%7}, {%8,%9}, {%10,%10,%10,%10};"
               : "=f"(d[0]), "=f"(d[1]), "=f"(d[2]), "=f"(d[3]) : "r"(a[0]), "r"(a[1]), "r"(a[2]), "r"(a[3]), "r"(b0), "r"(b1), "f"(0.f));
}
DI void mma1688z(float* d, uint32_t a0, uint32_t a1, uint32_t b0) {
  asm volatile("mma.sync.aligned.m16n8k8.row.col.f32.bf16.bf16.f32 {%0,%1,%2,%3}, {%4,%5}, {%6}, {%7,%7,%7,%7};"
               : "=f"(d[0]), "=f"(d[1]), "=f"(d[2]), "=f"(d[3]) : "r"(a0), "r"(a1), "r"(b0), "f"(0.f));
}
DI void mma1688(float* d, uint32_t a0, uint32_t a1, uint32_t b0) {
  asm volatile("mma.sync.aligned.m16n8k8.row.col.f32.bf16.bf16.f32 {%0,%1,%2,%3}, {%4,%5}, {%6}, {%0,%1,%2,%3};"
               : "+f"(d[0]), "+f"(d[1]), "+f"(d[2]), "+f"(d[3]) : "r"(a0), "r"(a1), "r"(b0));
}
DI void ldsm2t(uint32_t* r, uint32_t a) {
  asm volatile("ldmatrix.sync.aligned.m8n8.x2.trans.shared.b16 {%0,%1}, [%2];" : "=r"(r[0]), "=r"(r[1]) : "r"(a) : "memory");
}
DI uint32_t add_bf16(uint32_t a, uint32_t b) { uint32_t r; asm("add.rn.bf16x2 %0, %1, %2;" : "=r"(r) : "r"(a), "r"(b)); return r; }
DI uint32_t mul_bf16(uint32_t a, uint32_t b) { uint32_t r; asm("mul.rn.bf16x2 %0, %1, %2;" : "=r"(r) : "r"(a), "r"(b)); return r; }
DI uint64_t make_desc(uint32_t addr, uint32_t lbo, uint32_t sbo, uint32_t swz) {
  return (uint64_t)((addr & 0x3FFFF) >> 4) | ((uint64_t)(lbo >> 4) << 16) | ((uint64_t)(sbo >> 4) << 32) | ((uint64_t)swz << 62);
}
#define WG_FENCE() asm volatile("wgmma.fence.sync.aligned;" ::: "memory")
#define WG_COMMIT() asm volatile("wgmma.commit_group.sync.aligned;" ::: "memory")
#define WG_WAIT(n) asm volatile("wgmma.wait_group.sync.aligned %0;" :: "n"(n) : "memory")
#define ACC8(d, o) "+f"(d[o]), "+f"(d[o + 1]), "+f"(d[o + 2]), "+f"(d[o + 3]), "+f"(d[o + 4]), "+f"(d[o + 5]), "+f"(d[o + 6]), "+f"(d[o + 7])
DI void wgmma_n32_rs(float* d, uint32_t a0, uint32_t a1, uint32_t a2, uint32_t a3, uint64_t db, int acc) {
  asm volatile("{\n.reg .pred p;\nsetp.ne.b32 p, %21, 0;\n"
               "wgmma.mma_async.sync.aligned.m64n32k16.f32.bf16.bf16 {%0,%1,%2,%3,%4,%5,%6,%7,%8,%9,%10,%11,%12,%13,%14,%15}, "
               "{%16,%17,%18,%19}, %20, p, 1, 1, 0;\n}\n"
               : ACC8(d, 0), ACC8(d, 8) : "r"(a0), "r"(a1), "r"(a2), "r"(a3), "l"(db), "r"(acc));
}
template <int TA>
DI void wgmma_n32_ss(float* d, uint64_t da, uint64_t db, int acc) {
  asm volatile("{\n.reg .pred p;\nsetp.ne.b32 p, %18, 0;\n"
               "wgmma.mma_async.sync.aligned.m64n32k16.f32.bf16.bf16 {%0,%1,%2,%3,%4,%5,%6,%7,%8,%9,%10,%11,%12,%13,%14,%15}, "
               "%16, %17, p, 1, 1, %19, 1;\n}\n"
               : ACC8(d, 0), ACC8(d, 8) : "l"(da), "l"(db), "r"(acc), "n"(TA));
}
DI void tma_load(uint32_t dst, const CUtensorMap* m, int c0, int c1, uint32_t mb) {
  asm volatile("cp.async.bulk.tensor.2d.shared::cluster.global.mbarrier::complete_tx::bytes [%0], [%1, {%3, %4}], [%2];"
               :: "r"(dst), "l"(m), "r"(mb), "r"(c0), "r"(c1) : "memory");
}
DI void tma_load3(uint32_t dst, const CUtensorMap* m, int row, uint32_t mb) {
  asm volatile("cp.async.bulk.tensor.3d.shared::cluster.global.mbarrier::complete_tx::bytes [%0], [%1, {%3, %4, %3}], [%2];"
               :: "r"(dst), "l"(m), "r"(mb), "r"(0), "r"(row) : "memory");
}
DI bool elect_one() {
  uint32_t p;
  asm volatile("{\n.reg .pred p;\nelect.sync _|p, 0xffffffff;\nselp.u32 %0, 1, 0, p;\n}" : "=r"(p));
  return p;
}
DI void bulk_s2s(uint32_t dst, uint32_t src, uint32_t bytes, uint32_t mb) {
  asm volatile("cp.async.bulk.shared::cluster.shared::cta.mbarrier::complete_tx::bytes [%0], [%1], %2, [%3];"
               :: "r"(dst), "r"(src), "r"(bytes), "r"(mb) : "memory");
}
DI void bulk_load(uint32_t dst, const void* src, uint32_t bytes, uint32_t mb) {
  asm volatile("cp.async.bulk.shared::cluster.global.mbarrier::complete_tx::bytes [%0], [%1], %2, [%3];" :: "r"(dst), "l"(src), "r"(bytes), "r"(mb) : "memory");
}
#define EVICT_FIRST ".reg .b64 pol;\ncreatepolicy.fractional.L2::evict_first.b64 pol, 1.0;\n"
DI void bulk_load_ef(uint32_t dst, const void* src, uint32_t bytes, uint32_t mb) {
  asm volatile("{\n" EVICT_FIRST "cp.async.bulk.shared::cluster.global.mbarrier::complete_tx::bytes.L2::cache_hint [%0], [%1], %2, [%3], pol;\n}"
               :: "r"(dst), "l"(src), "r"(bytes), "r"(mb) : "memory");
}
DI void tma_load_ef(uint32_t dst, const CUtensorMap* m, int c0, int c1, uint32_t mb) {
  asm volatile("{\n" EVICT_FIRST "cp.async.bulk.tensor.2d.shared::cluster.global.mbarrier::complete_tx::bytes.L2::cache_hint [%0], [%1, {%3, %4}], [%2], pol;\n}"
               :: "r"(dst), "l"(m), "r"(mb), "r"(c0), "r"(c1) : "memory");
}
DI void tma_prefetch(const CUtensorMap* m, int c0, int c1) {
  asm volatile("cp.async.bulk.prefetch.tensor.2d.L2.global.tile [%0, {%1, %2}];" :: "l"(m), "r"(c0), "r"(c1) : "memory");
}
DI void tma_store(const CUtensorMap* m, uint32_t src, int c0, int c1) {
  asm volatile("cp.async.bulk.tensor.2d.global.shared::cta.bulk_group [%0, {%2, %3}], [%1];" :: "l"(m), "r"(src), "r"(c0), "r"(c1) : "memory");
}
DI uint4 ldg_relaxed(const void* p) {
  uint4 v;
  asm volatile("ld.relaxed.gpu.global.v4.b32 {%0,%1,%2,%3}, [%4];" : "=r"(v.x), "=r"(v.y), "=r"(v.z), "=r"(v.w) : "l"(p) : "memory");
  return v;
}
DI void stg_relaxed(void* p, uint32_t x, uint32_t y, uint32_t z, uint32_t w) {
  asm volatile("st.relaxed.gpu.global.v4.b32 [%0], {%1,%2,%3,%4};" :: "l"(p), "r"(x), "r"(y), "r"(z), "r"(w) : "memory");
}
DI void red_f16x8(void* p, uint32_t x, uint32_t y, uint32_t z, uint32_t w) {
  asm volatile("red.relaxed.gpu.global.add.noftz.v4.f16x2 [%0], {%1,%2,%3,%4};" :: "l"(p), "r"(x), "r"(y), "r"(z), "r"(w) : "memory");
}
DI void sq_acc(uint32_t& a, uint32_t x) { asm("fma.rn.bf16x2 %0, %1, %1, %0;" : "+r"(a) : "r"(x)); }
DI __half2 amax4(__half2 h, const uint32_t* v) {
  h = __hmax2_nan(__hmax2_nan(h, __habs2(*(const __half2*)&v[0])), __habs2(*(const __half2*)&v[1]));
  return __hmax2_nan(__hmax2_nan(h, __habs2(*(const __half2*)&v[2])), __habs2(*(const __half2*)&v[3]));
}
DI uint32_t wexp(__half2 h) { const uint32_t u = *(const uint32_t*)&h; return __reduce_max_sync(0xffffffffu, max((u >> 16) & 0x7fffu, u & 0x7fffu)) >> 7; }
DI float max10(const float* a) {
  return fmaxf(fmaxf(fmaxf(fmaxf(a[0], a[1]), fmaxf(a[2], a[3])), fmaxf(fmaxf(a[4], a[5]), fmaxf(a[6], a[7]))), fmaxf(a[8], a[9]));
}
DI float quad_max(float m) {
  return fmaxf(fmaxf(m, __shfl_xor_sync(0xffffffffu, m, 1)), fmaxf(__shfl_xor_sync(0xffffffffu, m, 2), __shfl_xor_sync(0xffffffffu, m, 3)));
}
DI float warp_sum(float v) {
#pragma unroll
  for (int o = 16; o; o >>= 1) v += __shfl_xor_sync(0xffffffffu, v, o);
  return v;
}

constexpr int SM_WO3 = 0;
constexpr int SM_X = 16384;
constexpr int XT = 36864;
constexpr int SM_EXP = 126976;
constexpr int SEGB = 10240;
constexpr int SM_BLK = SM_EXP + 8192;
constexpr int SM_VC = SM_BLK + 4 * SEGB;
constexpr int SM_PART = SM_VC + 16384;
constexpr int SM_QM = SM_PART + 4096;
constexpr int SM_E = SM_QM + 1024;
constexpr int SM_VM = SM_E + 1536;
constexpr int SM_OB = SM_VM + 2048;
constexpr int SM_FB = SM_OB + 2048;
constexpr int SM_STAGE = SM_X + XT;
constexpr int SM_M0 = SM_STAGE + 3 * 49152;
constexpr int SM_MISC = 210944;
constexpr int SM_WOST = 212992;
constexpr int SM_MEM = SM_WOST;
constexpr int SM_MAX = SM_MEM + 11264;
#define MEM_BLK(q) ((q) / 3 * 4096 + (q) % 3 * 1024)
constexpr int SM_TOTAL = 229376;
constexpr int MB_W = SM_MISC;
constexpr int MB_WO = SM_MISC + 24;
constexpr int MB_WO3 = SM_MISC + 32;
constexpr int MB_X = SM_MISC + 40;
constexpr int MB_S = SM_MISC + 64;
constexpr int MB_F = SM_MISC + 72;
constexpr int MB_VX = SM_MISC + 80;
constexpr int SC_FPAR = SM_MISC + 136;
constexpr int SC_DEAD = SM_MISC + 96;
constexpr int SC_UNSC = SM_MISC + 112;
constexpr int SC_EXPW = SM_MISC + 132;
constexpr int SC_ONES = SM_MISC + 144;
constexpr int SC_SS = SM_MISC + 160;
constexpr int SC_LAT = SM_MISC + 224;
constexpr int SC_EPO = SM_MISC + 240;
constexpr int MB_XS = SM_MISC + 248;
constexpr int SC_XMAX = SM_MISC + 256;
constexpr int SC_PROF = 229376;

constexpr float SM_SCALE = 0.08838834764831845f;
constexpr float LOG2E = 1.4426950408889634f;
constexpr float E_LIM = 20.f;

template <bool B> struct BoolC { static constexpr bool value = B; };
template <int I> struct IntC { static constexpr int value = I; };
struct RMaps { CUtensorMap x, wq, wk, wv, wo; unsigned char* red; uint32_t poll; const unsigned char* w[4]; };

DI uint32_t latest_hint(uint32_t h, uint32_t d, int s) {
  const uint32_t x = (((h | 0xc0c0c0c0u) - ((d >> 5) & 63) * 0x01010101u) & 0x3f3f3f3fu) | ((h ^ (((s >> 2) + 1) & 3) * 0x40404040u) & 0xc0c0c0c0u);
  const uint32_t y = __vmaxu2(x & 0x00ff00ffu, (x >> 8) & 0x00ff00ffu);
  return __reduce_max_sync(0xffffffffu, max(y & 0xffffu, y >> 16));
}
DI uint32_t near_half(uint32_t sb) {
  uint32_t a, b; lds64(sb + SC_LAT, a, b);
  return a > b;
}

template <int RT, int K0, int K1, bool D32 = false>
DI void xproj(float* acc, const uint32_t (&wa)[2][18][4], uint64_t xd) {
  if (XP & 1) return;
  WG_FENCE();
#pragma unroll
  for (int k = K0; k < ((XP & 128) ? K0 + 1 : K1); k++)
  {
    uint64_t d = xd + (uint64_t)(((k >> 1) * 4096 + (k & 1) * 32) >> 4);
    if (D32) asm("mov.b64 %0, {%1, %2};" : "=l"(d) : "r"((uint32_t)xd + (((k >> 1) * 4096 + (k & 1) * 32) >> 4)), "r"((uint32_t)(xd >> 32)));
    wgmma_n32_rs(acc, wa[RT][k][0], wa[RT][k][1], wa[RT][k][2], wa[RT][k][3], d, k != 0);
  }
  WG_COMMIT();
}

DI void load_w(uint32_t sb, const RMaps& tm, uint32_t rank, int c) {
  const int h = blockIdx.x / 3;
  mbar_expect(sb + MB_W + 8 * c, 49152);
  ((EF & 4) ? tma_load_ef : tma_load)(sb + SM_STAGE + c * 49152, rank < 2 ? &tm.wk : &tm.wv, h * DH + (rank == 1 ? 64 : 0), c * 192, sb + MB_W + 8 * c);
  ((EF & 4) ? tma_load_ef : tma_load)(sb + SM_STAGE + c * 49152 + 24576, rank < 2 ? &tm.wq : &tm.wv, h * DH + (rank == 0 ? 0 : 64), c * 192, sb + MB_W + 8 * c);
}
DI void seg_store(int seg, uint32_t sb) {
  fence_async();
  if (EF & 1)
    asm volatile("{\n" EVICT_FIRST "cp.async.bulk.global.shared::cta.bulk_group.L2::cache_hint [%0], [%1], 8192, pol;\n}"
                 :: "l"(g_seg + ((size_t)(seg & RING) * 96 + blockIdx.x) * 8192), "r"(sb + SM_BLK + (seg & 3) * SEGB) : "memory");
  else
  asm volatile("cp.async.bulk.global.shared::cta.bulk_group [%0], [%1], 8192;"
               :: "l"(g_seg + ((size_t)(seg & RING) * 96 + blockIdx.x) * 8192), "r"(sb + SM_BLK + (seg & 3) * SEGB) : "memory");
  asm volatile("cp.async.bulk.commit_group;" ::: "memory");
}
DI void seg_publish(int seg, uint32_t sb) {
  const uint32_t v = lds32(sb + SC_EPO) + seg;
  asm volatile("cp.async.bulk.wait_group 0;" ::: "memory");
  stg_relaxed32(&g_sflag[blockIdx.x * 8], v);
}

DI void proj_role(const uint32_t sb, const RMaps& tm, const bf16* __restrict__ x, const uint32_t rank, const int wg, const int w, const int lane) {
  const bool qk = rank < 2;
  uint32_t wa[2][18][4];
  float acc[16];
  const uint64_t xd0 = make_desc(sb + SM_X + wg * 64, 16, 1024, 1);
  {
    const int rr = (lane & 7) + ((lane >> 4) << 3);
    const uint32_t col = ((2 * w + ((lane >> 3) & 1)) ^ (lane & 7)) << 4;
    float ss = 0.f;
    bar_sync(3, 256);
    mbar_wait(sb + MB_X, 0);
    auto chunk = [&](auto cc) {
      constexpr int c = decltype(cc)::value;
      QSTAMP(2 + 2 * c);
      mbar_wait(sb + MB_W + 8 * c, 0);
      QSTAMP(3 + 2 * c);
#pragma unroll
      for (int rt = 1; rt >= 0; rt--)
#pragma unroll
        for (int k = 0; k < 6; k++)
          ldsm4t(wa[rt][c * 6 + k], sb + SM_STAGE + c * 49152 + (rt ^ wg) * 24576 + (64 * (k >> 1) + 32 * wg + 16 * (k & 1) + rr) * 128 + col);
      fence_async();
      if (c < 2) {
        bar_sync(3, 256);
        QSTAMP(17 + c);
        if (threadIdx.x == 0) {
          if (c == 0) tma_load(sb + SM_X + XT, &tm.wo, rank * 192, (blockIdx.x / 3) * DH, sb + MB_WO);
          else if (blockIdx.x < NSEG) bulk_load(sb + SM_X + 2 * XT, x + blockIdx.x * 32 * DM, XT, sb + MB_XS);
          else tma_load3(sb + SM_X + 2 * XT, &tm.x, 64, sb + MB_X + 16);
        }
        __syncwarp();
      } else {
        cluster_arrive();
      }
      xproj<1, 6 * c, 6 * c + 6>(acc, wa, xd0);
      if (!qk) {
        uint32_t q[4] = {0, 0, 0, 0};
#pragma unroll
        for (int rt = 0; rt < 2; rt++)
#pragma unroll
          for (int k = 0; k < 6; k++)
#pragma unroll
            for (int i = 0; i < 4; i++) sq_acc(q[i], wa[rt][c * 6 + k][i]);
#pragma unroll
        for (int i = 0; i < 4; i++) ss += bf_lo(q[i]) + bf_hi(q[i]);
      }
      if (c < 2 && CW) WG_WAIT(0);
    };
    chunk(IntC<0>()); chunk(IntC<1>()); chunk(IntC<2>());
    ss = warp_sum(ss);
    if (lane == 0) sts32(sb + SC_SS + 4 * (wg * 4 + w), __float_as_uint(ss));
    bar_arrive(11, 384);
  }
  STAMP(1);
  QSTAMP(8);
  STAMP(2);

  uint32_t t16 = sb + (w * 32 + lane) * 16;
  uint32_t mem_a = sb + SM_MEM + wg * 512 + lane * 16;
  uint32_t fin_a = sb + (lane & 7) * 16 + SM_BLK + (qk ? (wg ^ 1) * 4096 + w * 256 + (lane & 8) * 16 + (lane & 16) * 64
                                              : wg * 4096 + w * 1024 + (lane & 8) * 64 + (lane & 16) * 8);
  PIN(t16); PIN(mem_a); PIN(fin_a);
  const uint32_t fence_reg = mem_a;
  const uint32_t fin2 = qk ? 2048 : 256;
  auto do_export = [&](auto retire, uint32_t always) {
    WG_WAIT(0);
    uint32_t p[2];
#pragma unroll
    for (int i = 0; i < 2; i++) {
      p[i] = pack_bf16(acc[8 * i], acc[8 * i + 1]);
      sts128(t16 + SM_EXP + wg * 4096 + i * 2048, p[i], pack_bf16(acc[8 * i + 2], acc[8 * i + 3]),
             pack_bf16(acc[8 * i + 4], acc[8 * i + 5]), pack_bf16(acc[8 * i + 6], acc[8 * i + 7]));
    }
    if (decltype(retire)::value)
      asm volatile("{\n.reg .pred p, q;\nsetp.ne.u32 p, %2, 0;\nsetp.ne.u32 q, %2, 1;\n@p ld.shared.b32 %0, [%3];\n@q ld.shared.b32 %1, [%3 + 4];\n"
                   "setp.ne.u32 p, %0, %1;\n@p exit;\n}" : "+r"(p[0]), "+r"(p[1]) : "r"(always), "r"(sb + SC_DEAD) : "memory");
  };
  uint32_t o[8];
  auto import = [&]() { lds128(t16 + SM_EXP + (wg ^ 1) * 4096, o); lds128(t16 + SM_EXP + (wg ^ 1) * 4096 + 2048, o + 4); };
  auto finish_from = [&](int seg, const float* d) {
    const uint32_t a = fin_a + (seg & 3) * SEGB;
#pragma unroll
    for (int i = 0; i < 8; i++) o[i] = add_bf16(pack_bf16(d[2 * i], d[2 * i + 1]), o[i]);
    stsm4(a, o[0], o[1], o[2], o[3]);
    stsm4(a + fin2, o[4], o[5], o[6], o[7]);
  };
  auto finish = [&](int seg) { WG_WAIT(0); finish_from(seg, acc); };
  auto send_v = [&](int seg, int dst) {
    fence_async();
    if (seg < NSEG - 1 && !(XP & 2) && elect_one())
      bulk_s2s(mapa(sb + SM_VC + (seg & 1) * 8192, dst), sb + SM_BLK + (seg & 3) * SEGB, 8192, mapa(sb + MB_VX + (seg & 1) * 8, dst));
    __syncwarp();
  };
  auto wait_v = [&](int seg) {
    if (seg < NSEG - 1 && !(XP & 2)) {
      mbar_wait(sb + MB_VX + (seg & 1) * 8, (seg >> 1) & 1);
      if (elect_one()) mbar_expect(sb + MB_VX + (seg & 1) * 8, 8192);
      __syncwarp();
    }
  };
  auto export_seg = [&](int seg) { if (!(XP & (4 | 8192)) && elect_one()) seg_store(seg, sb); __syncwarp(); };
  auto publish = [&](int seg) { if (!(XP & (4 | 16384)) && elect_one()) seg_publish(seg, sb); __syncwarp(); };
  do_export(BoolC<false>(), 0);
  QSTAMP(9);
  SCHED_FENCE(11);
  xproj<0, 0, 18>(acc, wa, xd0);
  bar_sync(3, 256);
  QSTAMP(10);
  cluster_wait();
  QSTAMP(11);
  mbar_wait(sb + MB_X + 8, 0);
  QSTAMP(12);
  import();
  finish(0);
  SCHED_FENCE(12);
  uint64_t dA = xd0 + (XT >> 4);
  xproj<1, 0, 18>(acc, wa, dA);
  bar_sync(3, 256);
  if (!qk && wg == 0 && w < 2) send_v(0, w);
  if (!(EXV & 1) && wg == 0 && w == 3) export_seg(0);
  QSTAMP(13);
  if (qk && wg == 0 && w == 0) wait_v(0);
  QSTAMP(14);
  bar_arrive(13, 384);
  if (!qk) {
    do_export(BoolC<false>(), 0);
    SCHED_FENCE(15);
    xproj<0, 0, 18>(acc, wa, dA);
    if (threadIdx.x == 0 && !(XP & 8)) { mbar_expect(sb + MB_X, XT); tma_load3(sb + SM_X, &tm.x, 96, sb + MB_X); }
    bar_sync(3, 256);
    mbar_wait(sb + MB_X + 16, 0);
    import();
    finish(1);
    SCHED_FENCE(16);
    dA += XT >> 4;
    xproj<1, 0, 18>(acc, wa, dA);
    if (!(EXV & 2)) bar_sync(3, 256);
    if (!(EXV & 2) && wg == 0 && w < VW2) send_v(1, w);
  }
  QSTAMP(15);
  WG_WAIT(0);
  bar_sync(0, 384);
  if (!(EXV & 1) && wg == 0 && w == 3) publish(0);
  QSTAMP(16);
  const int ro = __shfl_sync(0xffffffffu, near_half(sb) ^ wg, 0);
  STAMP(5);
  const uint32_t always = __shfl_sync(0xffffffffu, lds32(sb + SC_DEAD + 12), 0);
  const int ah = qk ? 1 : 2;
  int b2 = qk ? 2 : 0;
  int s = 0;
  uint32_t hint_lo = (uint32_t)(uint64_t)tm.red + HINT_OFF + blockIdx.x + (lane & 1) * 4096 + (lane >> 1) * 16384;
  PIN(hint_lo);
  auto post_hint = [&]() {
    asm volatile("{\n.reg .pred p;\n.reg .b64 a;\n.reg .u32 t;\nsetp.lt.u32 p, %0, %1;\nmov.b64 a, {%2, %3};\nmov.u32 t, %%globaltimer_lo;\n"
                 "bfe.u32 t, t, 5, 6;\nor.b32 t, t, %4;\n@p st.relaxed.gpu.global.u8 [a], t;\n}"
                 :: "r"(t16), "r"(sb + 160), "r"(hint_lo + RED_SLOT(s)), "r"((uint32_t)((uint64_t)tm.red >> 32)), "r"(((s >> 2) + 1) << 6) : "memory");
  };
  auto memproj = [&](auto second, int id, uint32_t dep, float u0, float u1, float* r) {
    constexpr bool R1 = decltype(second)::value;
    uint32_t b[NUP][4], b0[4];
    if (R1) asm volatile("{\n.reg .pred p;\nsetp.eq.u32 p, %0, %1;\n@p exit;\n}" :: "r"(dep), "r"(id) : "memory");
    bar_sync(R1 ? 2 : 1, 256);
    PROF(0);
    ldsm4t(b0, mem_a);
#pragma unroll
    for (int q = 0; q < NUP; q++) {
      if (R1 && q == 2) {
        bar_sync(11, 256);
        SCHED_FENCE(id + 1);
      }
      ldsm4t(b[q], mem_a + MEM_BLK(q + 1));
    }
    mma16816z(&acc[0], wa[0][0], b0[0], b0[1]);
    mma16816z(&acc[4], wa[1][0], b0[0], b0[1]);
    mma16816z(&acc[8], wa[0][1], b0[2], b0[3]);
    mma16816z(&acc[12], wa[1][1], b0[2], b0[3]);
#pragma unroll
    for (int q = 1; q < 9; q++) {
      uint32_t* const c = b[(q - 1) % NUP];
      mma16816(&acc[0], wa[0][2 * q], c[0], c[1]);
      mma16816(&acc[4], wa[1][2 * q], c[0], c[1]);
      mma16816(&acc[8], wa[0][2 * q + 1], c[2], c[3]);
      mma16816(&acc[12], wa[1][2 * q + 1], c[2], c[3]);
      if (R1 && q + NUP == B3Q) bar_sync(3, 256);
      if (q + NUP < 9) ldsm4t_in(c, mem_a + MEM_BLK(q + NUP), always);
      else if (R1 && q + NUP < 11) lds128_in(c, t16 + SM_PART + (10 - q - NUP) * 2048, always);
      else if (!R1 && GATE && q == GATE) { bar_arrive(11, 256); lds128_in(c, sb + SC_DEAD, always); u0 = u1 = __uint_as_float(c[3]); }
    }
#pragma unroll
    for (int i = 0; i < 8; i++) {
      const float u = i < 4 ? u0 : u1;
      r[i] = R1 ? fmaf(acc[8 + i], u, (acc[i] + __uint_as_float(b[(8 + i / 4) % NUP][i & 3])) * u) : (GATE ? fmaf(acc[i], u, acc[8 + i]) : acc[i] + acc[8 + i]);
    }
  };
  if (ro == 0) {
#pragma unroll 1
    while (true) {
      do_export(BoolC<true>(), always);
      PROFP(3);
      if (s == 8) STAMP(6);
      float r[8];
      memproj(BoolC<false>(), 30, 0, 0.f, 0.f, r);
      sts128(t16 + SM_PART, __float_as_uint(r[0]), __float_as_uint(r[1]), __float_as_uint(r[2]), __float_as_uint(r[3]));
      sts128(t16 + SM_PART + 2048, __float_as_uint(r[4]), __float_as_uint(r[5]), __float_as_uint(r[6]), __float_as_uint(r[7]));
      bar_arrive(3, 256);
      PROF(1);
      bar_sync(9, 256);
      if (!(WE & 1) && s == NSEG - 1) break;
      post_hint();
      if (!(EXV & 1) && w == 3 && s) publish(s);
      if ((WE & 1) && s == NSEG - 1) break;
      if (w == 1) {
        uint32_t m[8];
        lds128(t16 + SM_MAX - 512, m); lds128(t16 + SM_MAX, m + 4);
        const int em = (wexp(amax4(amax4(*(const __half2*)&m[0], m), m + 4)) >> 3) + (int)(lds32(sb + SC_UNSC + (s & 1) * 8) >> 23) - 15;
        const int ex = max(s ? em : 0, (int)lds32(sb + SC_XMAX + 4 * s)) - 127 + (int)lds32(sb + SC_EXPW);
        sts32(sb + SC_UNSC + (~s & 1) * 8, (127 + min(max(ex, -120), 120)) << 23);
        __syncwarp();
        if (elect_one()) mbar_arrive(sb + MB_S);
      }
      SCHED_FENCE(9);
      bar_sync(5, qk ? N5 : 256);
      PROF(2);
      import();
      xproj<0, 0, NII>(acc, wa, dA);
      if (NII < 18) {
        if (qk) bar_sync(7, 384);
        xproj<0, NII, 18>(acc, wa, dA);
        if (!qk) bar_sync(7, 384);
      } else {
        if (F10) WG_WAIT(0);
        bar_sync(10, 256);
        if (F10) SCHED_FENCE(17);
      }
      dA += (int64_t)(b2 ? XT >> 4 : -(XT >> 3));
      finish(s + ah);
      if (((EXV & 1) || w != 3) && ((EXV & 2) || qk || w >= VW2)) bar_arrive(13, 384);
      PROF(6);
      SCHED_FENCE(14);
      if (NOB & 2) bar_arrive(14, 256);
      bar_sync(12, 256);
      PROF(7);
      xproj<1, 0, 18, true>(acc, wa, dA);
      if (!(NOB & 2)) bar_arrive(14, 256);
      b2 = b2 == 2 ? 0 : b2 + 1;
      s++;
      if ((!(EXV & 1) && w == 3) || (!(EXV & 2) && !qk && w < VW2)) {
        bar_sync(13, 384);
        if (!(EXV & 1) && w == 3) export_seg(s); else send_v(s + 1, w);
      }
      PROFP(8);
    }
    if (!qk) bar_arrive(5, 256);
    if (!(WE & 1) && w == 3) publish(NSEG - 1);
  } else {
    uint32_t km[4];
    auto send_km = [&]() {
      if (XP & (4 | 4096)) return;
      const uint32_t t = (km[0] & ~1u) | lds32(sb + SC_EPO + 4), u = (s * NH + head_id()) * 4096;
      if (qk)
        asm volatile("{\n.reg .u32 o;\n.reg .u64 a;\nshr.u32 o, %0, 1;\nadd.u32 o, o, %1;\nmad.wide.u32 a, o, 1, %2;\nst.relaxed.gpu.global.v2.b32 [a], {%3,%4};\n}"
                     :: "r"(t16), "r"(u + rank * 1024 - (sb >> 1)), "l"(g_km), "r"(t), "r"(km[1]) : "memory");
      else
        asm volatile("{\n.reg .u32 o;\n.reg .u64 a;\nadd.u32 o, %0, %1;\nmad.wide.u32 a, o, 1, %2;\nst.relaxed.gpu.global.v4.b32 [a], {%3,%4,%5,%6};\n}"
                     :: "r"(t16), "r"(u + 2048 - sb), "l"(g_km), "r"(t), "r"(km[1]), "r"(km[2]), "r"(km[3]) : "memory");
    };
#pragma unroll 1
    while (true) {
      do_export(BoolC<true>(), always);
      if ((EXV & 1) && w == 1) export_seg(s);
      if ((EXV & 2) && !qk && w == 2) send_v(s + 1, 0);
      PROFP(3);
      if (s == 8) STAMP(6);
      const uint32_t tl = ((t16 >> 8) ^ wg) & 1, am = (t16 & ~256u) - w * 256;
      const float un = __uint_as_float(lds32(sb + SC_UNSC + (s & 1) * 8));
      float r[8];
      if (qk) {
        uint32_t a0 = am + (tl ? SM_QM : SM_BLK + 8192 + (s & 3) * SEGB);
        float u0 = wg ? un * (SM_SCALE * LOG2E) : un, u1 = wg ? un : un * (SM_SCALE * LOG2E);
        PIN(a0); PIN(u0); PIN(u1);
        memproj(BoolC<true>(), 32, a0, u0, u1, r);
        const uint32_t p0 = pack_bf16(r[0], r[1]), p1 = pack_bf16(r[2], r[3]), p2 = pack_bf16(r[4], r[5]), p3 = pack_bf16(r[6], r[7]);
        stsm4(a0, p0, p1, p2, p3);
        bar_arrive(4, 256);
        km[0] = wg ? p2 : p0; km[1] = wg ? p3 : p1;
      } else {
        const uint32_t d0 = s < NSEG - 1 ? 0 : 2, d1 = s < NSEG - 1 ? 1 : 2;
        uint32_t r0 = mapa(t16 + SM_VM, d0), r1 = mapa(t16 + SM_VM, d1);
        PIN(r0); PIN(r1);
        memproj(BoolC<true>(), 34, r0 | r1, un, un, r);
        const uint32_t p0 = pack_bf16(r[0], r[1]), p1 = pack_bf16(r[2], r[3]), p2 = pack_bf16(r[4], r[5]), p3 = pack_bf16(r[6], r[7]);
        const uint32_t v0 = wg ? p2 : p0, v1 = wg ? p3 : p1, v2 = wg ? p0 : p2, v3 = wg ? p1 : p3;
        st_async4(r0, v0, v1, v2, v3, mapa(sb + MB_S, d0));
        st_async4(r1, v0, v1, v2, v3, mapa(sb + MB_S, d1));
        bar_arrive(5, 256);
        sts128(t16 + SM_VM, v0, v1, v2, v3);
        __syncwarp();
        if (elect_one()) mbar_arrive(sb + MB_S);
        km[0] = v0; km[1] = v1; km[2] = v2; km[3] = v3;
      }
      if (!(WE & 2) && s == NSEG - 1) break;
      PROF(1);
      auto rearm = [&]() { mbar_wait(sb + MB_S, s & 1); if (elect_one()) mbar_expect(sb + MB_S, qk ? 640 + 2048 : 1280); __syncwarp(); };
      if ((WE & 2) && s == NSEG - 1 && w != 1) {
      } else if (w == 1) {
        if ((t16 & 384) == 0) stg_relaxed(tm.red + (RED_SLOT(s + 2) + RED_LINE(blockIdx.x)) + (t16 & 112), 0, 0, 0, 0);
        if (EXV & 1) publish(s);
      } else if (w == 0) {
        const int tn = s + ah + 1;
        if (RFW) mbar_wait(sb + MB_S, s & 1);
        if (tn + 1 < NSEG && !(XP & 8) && elect_one()) {
          const int b0 = b2 == 2 ? 0 : b2 + 1;
          mbar_expect(sb + MB_X + 8 * b0, XT);
          tma_load3(sb + SM_X + b0 * XT, &tm.x, (tn + 1) * 32, sb + MB_X + 8 * b0);
        }
        if (tn < NSEG && (!(XP & 8) || tn < 3)) mbar_wait(sb + MB_X + 8 * b2, (tn / 3) & 1);
      } else if (w == 2) {
        if (!qk) { if (VW2 < 1) send_v(s + 1, 0); if (VW2 < 2) send_v(s + 1, 1); }
      } else if (qk || !NIC) {
        rearm();
      }
      __syncwarp();
      send_km();
      if ((WE & 2) && s == NSEG - 1) break;
      import();
      PROF(4);
      SCHED_FENCE(10);
      if (NIC) {
        if (qk) bar_sync(7, NII < 18 ? 384 : 256);
        xproj<0, 0, NIC>(acc, wa, dA);
        if (!qk) { if (w == 3) rearm(); bar_sync(7, NII < 18 ? 384 : 256); }
      } else {
        bar_sync(7, NII < 18 ? 384 : 256);
      }
      if (NOB & 1) bar_arrive(12, 256);
      xproj<0, NIC, 18>(acc, wa, dA);
      if (!(NOB & 1)) bar_arrive(12, 256);
      dA += (int64_t)(b2 ? XT >> 4 : -(XT >> 3));
      finish(s + ah);
      if (qk && w == 0) wait_v(s + 1);
      bar_arrive(13, 384);
      PROF(6);
      SCHED_FENCE(13);
      bar_sync(14, 256);
      PROF(7);
      xproj<1, 0, 18>(acc, wa, dA);
      b2 = b2 == 2 ? 0 : b2 + 1;
      s++;
      PROFP(8);
    }
    if (!(WE & 2)) {
      send_km();
      PIN(t16);
      if (t16 - sb < 128) stg_relaxed(tm.red + (RED_SLOT(NSEG + 1) + RED_LINE(head_id() * 3 + rank)) + (t16 & 112), 0, 0, 0, 0);
    }
  }
  bar_arrive(0, 384);
  STAMP(3);
  cluster_sync();
  STAMP(4);
}

DI void attn_role(const uint32_t sb, unsigned char* smem_raw, const RMaps& tm, const uint32_t RANK, const bf16* __restrict__ x, const bf16* __restrict__ mem0,
                  const int w, const int lane) {
  const int t2 = w * 32 + lane;
  uint32_t wo[8][4], w1[8][4];
  const uint32_t wo_lane = sb + ((lane & 7) + ((lane >> 4) << 3)) * 128 + (((w + 4 * ((lane >> 3) & 1)) ^ (lane & 7)) << 4);
  unsigned char* const g_red = tm.red;
  {
    const uint32_t tag = *(volatile unsigned*)&g_epoch + 1;
    QSTAMP(0);
    bar_sync(0, 160);
    QSTAMP(1);
    cluster_arrive();
    __half2 hx = __float2half2_rn(0.f);
    if (t2 == 0) { sts64(sb + SC_EPO, (tag - 1) * NSEG + 1, tag & 1); sts32(sb + SC_UNSC, __float_as_uint(1.f)); sts128(sb + SC_DEAD, 0, 0, 0, 0x3f800000u); sts64(sb + SC_FPAR, 0, 0); sts128(sb + SC_ONES, 0x3f803f80u, 0x3f803f80u, 0x3f803f80u, 0x3f803f80u); }
    WSTAMP(27);
    uint32_t q[8] = {0, 0, 0, 0, 0, 0, 0, 0};
    QSTAMP(2);
    mbar_wait(sb + MB_WO3, 0);
    QSTAMP(3);
    uint32_t mv[5][4];
#pragma unroll
    for (int i = 0; i < 5; i++) {
      ldsm4(mv[i], sb + SM_M0 + (lane & 7) * (DM * 2) + min(w + 4 * i, 17) * 64 + (lane >> 3) * 16);
      if (blockIdx.x == 0) hx = amax4(hx, mv[i]);
    }
#pragma unroll
    for (int k = 0; k < 8; k++) {
      ldsm4t(wo[k], wo_lane + SM_WO3 + k * 2048); ldsm4t(w1[k], wo_lane + SM_WOST + k * 2048);
#pragma unroll
      for (int i = 0; i < 4; i++) { sq_acc(q[i], wo[k][i]); sq_acc(q[i], w1[k][i]); }
    }
    bar_sync(6, 128);
#pragma unroll
    for (int k = 0; k < 8; k++) sts128(sb + SM_WO3 + t2 * 16 + k * 2048, wo[k][0], wo[k][1], wo[k][2], wo[k][3]);
#pragma unroll
    for (int i = 0; i < 5; i++) {
      const int c = (w + 4 * i) * 32;
      if (c < DM) stsm4t(sb + SM_MEM + (c + c / 192 * 64 + lane) * 16, mv[i][0], mv[i][1], mv[i][2], mv[i][3]);
    }
    bar_arrive(1, 256); bar_arrive(2, 256); bar_arrive(9, 256);
    QSTAMP(4);
    mbar_wait(sb + MB_WO, 0);
    QSTAMP(5);
#pragma unroll
    for (int k = 0; k < 8; k++) ldsm4t(wo[k], wo_lane + SM_X + XT + k * 2048);
    fence_async();
    bar_sync(6, 128);
    if (t2 == 32) tma_load3(sb + SM_X + XT, &tm.x, 32, sb + MB_X + 8);
    __syncwarp();
#pragma unroll
    for (int k = 0; k < 8; k++)
#pragma unroll
      for (int i = 0; i < 4; i++) sq_acc(q[4 + i], wo[k][i]);
    float ss = 0.f;
#pragma unroll
    for (int i = 0; i < 8; i++) ss += bf_lo(q[i]) + bf_hi(q[i]);
    ss = warp_sum(ss);
    if (lane == 0) sts32(sb + SC_SS + 4 * (8 + w), __float_as_uint(ss));
    if (blockIdx.x < NSEG) {
      mbar_wait(sb + MB_XS, 0);
#pragma unroll
      for (int i = 0; i < 18; i++) { uint32_t v[4]; lds128(sb + SM_X + 2 * XT + t2 * 16 + i * 2048, v); hx = amax4(hx, v); }
      fence_async();
      bar_sync(6, 128);
      if (t2 == 32) tma_load3(sb + SM_X + 2 * XT, &tm.x, 64, sb + MB_X + 16);
      __syncwarp();
    }
    sts32(sb + SC_SS + 4 * (12 + w), wexp(hx));
    QSTAMP(6);
    bar_sync(11, 384);
    QSTAMP(7);
    if (t2 == 0) {
      float a[16];
#pragma unroll
      for (int i = 0; i < 4; i++) lds128f(sb + SC_SS + 16 * i, &a[4 * i]);
      stg_relaxed(&g_stats[blockIdx.x * 2], __float_as_uint(((a[0] + a[1]) + (a[2] + a[3])) + ((a[4] + a[5]) + (a[6] + a[7]))),
                  __float_as_uint((a[8] + a[9]) + (a[10] + a[11])),
                  max(max(__float_as_uint(a[12]), __float_as_uint(a[13])), max(__float_as_uint(a[14]), __float_as_uint(a[15]))), tag);
    }
    __syncwarp();
    WSTAMP(24);
    QSTAMP(8);
    cluster_wait();
    QSTAMP(9);
    if (w == 0) {
      uint4 v[3];
      int n = 0;
      while (true) {
#pragma unroll
        for (int i = 0; i < 3; i++) v[i] = ldg_relaxed(&g_stats[(i * 32 + lane) * 2]);
        if (__all_sync(0xffffffffu, v[0].w == tag && v[1].w == tag && v[2].w == tag) || ++n > SPIN_LIMIT) break;
        __nanosleep(100);
      }
      WSTAMP(25);
      QSTAMP(10);
      const float sv = warp_sum(__uint_as_float(v[0].x) + __uint_as_float(v[1].x) + __uint_as_float(v[2].x));
      const float so = warp_sum(__uint_as_float(v[0].y) + __uint_as_float(v[1].y) + __uint_as_float(v[2].y));
      const int expW = ((int)(__float_as_uint(sv) >> 23) + (int)(__float_as_uint(so) >> 23) - 254 + 2 + 10 + 1) >> 1;
      sts32(sb + SC_XMAX + 4 * lane, v[0].z); sts32(sb + SC_XMAX + 128 + 4 * lane, v[1].z);
      sts32(sb + SC_EXPW, expW + 1 - 15);
      if (blockIdx.x == 0 && lane == 0) *(volatile unsigned*)&g_epoch = tag;
      sts32(sb + SC_FPAR + 4, 1);
    } else if (w < 3) {
      const uint32_t u = blockIdx.x >> 4;
      unsigned char* const z = g_red + 98304 + (blockIdx.x & 15) * 128 + (u & 1) * 2048 + (u & 6) * 4096 + (((u >> 1) ^ w) & 1) * 4096 + lane * 4;
      stg_relaxed32(z, 0);
      uint32_t best = 0xffffffffu;
#pragma unroll 1
      for (int i = 0; i < 64; i++) {
        uint32_t dt;
        asm volatile("{\n.reg .pred p;\n.reg .u32 c, v;\nmov.u32 c, %%clock;\n"
                     "atom.relaxed.gpu.global.exch.b32 v, [%1], 0;\nsetp.eq.u32 p, v, 0;\nmov.u32 %0, 0;\n@p mov.u32 %0, %%clock;\nsub.u32 %0, %0, c;\n}"
                     : "=r"(dt) : "l"(z) : "memory");
        best = min(best, dt);
        if (lds32v(sb + SC_FPAR + 4) && i >= NPROBE - 1) break;
      }
      sts32(sb + SC_LAT + (w - 1) * 4, best);
    }
    QSTAMP(11);
    bar_sync(13, 384);
    bar_arrive(0, 384);
    QSTAMP(12);
    WSTAMP(26);
  }

  const uint32_t nh = __shfl_sync(0xffffffffu, near_half(sb), 0);
  uint32_t l16 = sb + lane * 16;
  PIN(l16);
#define LV ((l16 >> 4) & 31)
#define fence_reg l16
  const uint32_t red_lo = (uint32_t)(uint64_t)g_red, red_hi = (uint32_t)((uint64_t)g_red >> 32);
  uint32_t lp;
  auto slot = [&](int s, uint32_t c, uint32_t ofs) {
    const uint32_t lo = lp | (red_lo + ((w >> 1) * 4 + (w & 1) * 2 + ((w ^ c) & 1)) * 4096 + RED_SLOT(s) + ofs);
    uint64_t a; asm("mov.b64 %0, {%1, %2};" : "=l"(a) : "r"(lo), "r"(red_hi));
    return (unsigned char*)a;
  };
  const uint32_t always = __shfl_sync(0xffffffffu, lds32(sb + SC_DEAD + 12), 0);
  const int mode0 = RANK < 2 ? w : w | 4;
  auto hint_addr = [&](int s) { return min(LV, 23u) * 4 + (red_lo + HINT_OFF + nh * 4096 + w * 16384 + RED_SLOT(s)); };
  auto load_hints = [&](uint32_t lo) {
    uint64_t a; asm("mov.b64 %0, {%1, %2};" : "=l"(a) : "r"(lo), "r"(red_hi));
    return ldg_relaxed32((const void*)a);
  };
  int s = 0;
  bool bad = false;
#pragma unroll 1
  while (true) {
    const uint32_t par = s & 1;
    uint32_t vx[4][4], hints;
    auto load_vx = [&]() {
      const uint32_t va = l16 + (RANK < 2 ? SM_VC + par * 8192 : SM_BLK + (s & 3) * SEGB) + w * 1024 + ((LV >> 3) & 1) * 384 - (LV >> 4) * 128;
#pragma unroll
      for (int i = 0; i < 4; i++) ldsm4(vx[i], va + (i & 1) * 4096 + (i >> 1) * 256);
    };
    auto retire = [&](uint32_t x) {
      asm volatile("{\n.reg .pred p;\nsetp.eq.u32 p, %0, 0;\n@p exit;\n}" :: "r"(vx[0][0] | vx[1][0] | vx[2][0] | vx[3][0] | x) : "memory");
    };
    auto scores = [&](auto memkeys, auto first, float* sc) {
      constexpr bool MK = decltype(memkeys)::value, FIRST = decltype(first)::value;
      uint32_t kb[4][4], qb[2][4];
      const uint32_t m = LV >> 3;
      uint32_t kaddr = l16 + SM_BLK + 4096 + (s & 3) * SEGB + w * 2048 + (m & 1) * (MK ? 128 : 896) - (m >> 1) * 128;
      if (MK) { PIN(kaddr); }
      else {
#pragma unroll
        for (int k = 0; k < 4; k++) ldsm4t(kb[k], kaddr + k * 256);
      }
      if (FIRST) { load_vx(); retire(MK ? kaddr : kb[0][0] | kb[1][0] | kb[2][0] | kb[3][0] | l16); bar_sync(4, 256); PROF(4); }
      ldsm4t(qb[0], l16 + SM_QM);
      if (MK) ldsm4t(kb[0], kaddr);
      ldsm4t(qb[1], l16 + SM_QM + 512);
      if (MK) ldsm4t(kb[2], kaddr + 512);
      float c[4][4];
      mma16816z(c[0], kb[0], qb[0][0], qb[0][1]); mma16816z(c[1], kb[MK ? 0 : 1], qb[0][2], qb[0][3]);
      mma16816z(c[2], kb[2], qb[1][0], qb[1][1]); mma16816z(c[3], kb[MK ? 2 : 3], qb[1][2], qb[1][3]);
      if (FIRST && B5POS == 0) bar_arrive(5, N5);
#pragma unroll
      for (int i = 0; i < (MK ? 2 : 4); i++) sc[i] = ((c[0][i] + c[1][MK ? i + 2 : i]) + c[2][i]) + c[3][MK ? i + 2 : i];
    };
    auto send = [&](auto memkeys) {
      constexpr bool MK = decltype(memkeys)::value;
      constexpr int N = MK ? 1 : 2;
      const uint32_t sa = sb + LV * 4 + SM_E + (MK ? 1024 + RANK * 128 : RANK * 512 + w * 256);
      uint32_t ra[N][2], mb[N][2];
#pragma unroll
      for (int i = 0; i < N; i++)
#pragma unroll
        for (int j = 0; j < 2; j++) {
          ra[i][j] = mapa(sa + i * 128, j ? 2 : RANK ^ 1); mb[i][j] = mapa(sb + MB_S, j ? 2 : RANK ^ 1);
          PIN(ra[i][j]);
        }
      float sc[4];
      scores(memkeys, BoolC<true>(), sc);
      uint32_t e[N];
#pragma unroll
      for (int i = 0; i < N; i++) {
        e[i] = pack_bf16(ex2(sc[2 * i]), ex2(sc[2 * i + 1]));
        if (!(fmaxf(fabsf(sc[2 * i]), fabsf(sc[2 * i + 1])) <= E_LIM)) e[i] = 0x7fff7fffu;
        st_async1(ra[i][0], e[i], mb[i][0]);
        st_async1(ra[i][1], e[i], mb[i][1]);
      }
#pragma unroll
      for (int i = 0; i < N; i++) sts32(sa + i * 128, e[i]);
      __syncwarp();
      if (l16 == sb) mbar_arrive(sb + MB_S);
      PROF(5);
    };
    const int mode = bad ? 8 : mode0;
    if (mode < 2) {
      send(BoolC<false>());
    } else if (mode == 2) {
      send(BoolC<true>());
    } else if (mode == 8) {
      load_vx();
      retire(l16);
      const uint32_t fp = lds32(sb + SC_FPAR);
      bar_sync(6, 128);
      if (w == 0 && l16 == sb) { sts32(sb + SC_FPAR, fp ^ 1); mbar_expect(sb + MB_F, 3072); }
      if (RANK < 2 && w < 3) {
        float sc[4] = {0.f, 0.f, 0.f, 0.f};
        if (w < 2) scores(BoolC<false>(), BoolC<false>(), sc); else scores(BoolC<true>(), BoolC<false>(), sc);
#pragma unroll 1
        for (int r = 0; r < 3; r++)
          st_async4(mapa(l16 + SM_FB + RANK * 1536 + w * 512, r), __float_as_uint(sc[0]), __float_as_uint(sc[1]), __float_as_uint(sc[2]), __float_as_uint(sc[3]), mapa(sb + MB_F, r));
      }
      mbar_wait(sb + MB_F, fp);
      float a[12];
#pragma unroll
      for (int j = 0; j < 3; j++) {
        float b[4];
        lds128f(l16 + SM_FB + j * 512, a + 4 * j); lds128f(l16 + SM_FB + 1536 + j * 512, b);
#pragma unroll
        for (int i = 0; i < 4; i++) a[4 * j + i] += b[i];
      }
      float m0 = fmaxf(fmaxf(fmaxf(a[0], a[2]), fmaxf(a[4], a[6])), a[8]), m1 = fmaxf(fmaxf(fmaxf(a[1], a[3]), fmaxf(a[5], a[7])), a[9]);
#pragma unroll
      for (int o = 4; o < 32; o <<= 1) { m0 = fmaxf(m0, __shfl_xor_sync(0xffffffffu, m0, o)); m1 = fmaxf(m1, __shfl_xor_sync(0xffffffffu, m1, o)); }
#pragma unroll
      for (int i = 0; i < 5; i++) {
        const uint32_t ea = sb + SM_E + LV * 4 + (i < 4 ? i * 128 : 1024);
        sts32(ea, pack_bf16(ex2(a[2 * i] - m0), ex2(a[2 * i + 1] - m1)));
        sts32(ea + (i < 4 ? 512 : 128), 0x3f803f80u);
      }
      __syncwarp();
    } else {
      load_vx();
      if (mode == 3) bar_arrive(4, 256);
      retire(l16 + 1);
    }
    {
      uint32_t wa[4], wb[4], oc[4];
      constexpr int WS = 2048;
      const uint32_t w3a = l16 + SM_WO3 + w * 512;
      lds128(w3a + KP(0) * WS, wa); lds128(w3a + KP(1) * WS, wb); lds128(sb + SC_ONES, oc);
      if (B5POS == 1 && mode < 3) bar_arrive(5, N5);
      uint32_t e[10], p[5], vm[4], ob[4];
      float o0[4], o1[4], f[3][2][4], rs[4];
      reserve2(vm); reserve2(vm + 2); reserve2(e + 8);
      hints = hint_addr(s);
      PIN(hints);
      if (CLR & 2) asm volatile("{\n.reg .pred p;\nsetp.eq.u32 p, %0, 0;\n@p exit;\n}" :: "r"(wa[0] | wb[0] | oc[0] | hints) : "memory");
      mbar_wait(sb + MB_S, par);
      PROF(6);
      ldsm4t(e, l16 + SM_E); ldsm2t_in(e + 8, l16 + SM_E + 1024, always); ldsm4t(e + 4, l16 + SM_E + 512);
      lds128_in(vm, l16 + w * 512 + SM_VM, always);
      const float scl = __uint_as_float(lds32(sb + SC_UNSC + 8 - par * 8));
      hints = load_hints(hints);
      if (GF & 1) SCHED_FENCE(4);
#pragma unroll
      for (int i = 0; i < 4; i++) p[i] = mul_bf16(e[i], e[4 + i]);
      p[4] = mul_bf16(e[8], e[9]);
      if (MO & 4) {
        float a0[4], a1[4];
        mma16816z(o0, vx[0], p[0], p[1]); mma16816z(o1, vx[1], p[0], p[1]);
        mma16816z(a0, vx[2], p[2], p[3]); lds128_in(vx[2], w3a + KP(2) * WS, always);
        mma16816z(a1, vx[3], p[2], p[3]); lds128_in(vx[3], w3a + KP(3) * WS, always);
        mma1688(o0, vm[0], vm[1], p[4]); mma1688(o1, vm[2], vm[3], p[4]);
        mma16816z(rs, oc, p[0], p[1]); mma16816(rs, oc, p[2], p[3]); mma1688(rs, oc[0], oc[1], p[4]);
#pragma unroll
        for (int i = 0; i < 4; i++) { o0[i] += a0[i]; o1[i] += a1[i]; }
      } else {
      mma16816z(o0, vx[0], p[0], p[1]); mma16816z(o1, vx[1], p[0], p[1]); mma16816z(rs, oc, p[0], p[1]);
      mma16816(o0, vx[2], p[2], p[3]); lds128_in(vx[2], w3a + KP(2) * WS, always);
      mma16816(o1, vx[3], p[2], p[3]); lds128_in(vx[3], w3a + KP(3) * WS, always);
      mma16816(rs, oc, p[2], p[3]);
      mma1688(o0, vm[0], vm[1], p[4]); mma1688(o1, vm[2], vm[3], p[4]); mma1688(rs, oc[0], oc[1], p[4]);
      }
      stsm4(l16 + w * 512 + SM_OB, pack_bf16(o0[0], o0[1]), pack_bf16(o0[2], o0[3]), pack_bf16(o1[0], o1[1]), pack_bf16(o1[2], o1[3]));
      bar_sync(6, 128);
      PROF(7);
      ldsm4t_in(oc, l16 + SM_OB, always);
      bad = __any_sync(0xffffffffu, !(rs[0] + rs[1] > 0.f) && !bad);
      rs[0] *= scl; rs[1] *= scl;
      asm volatile("{\n.reg .pred p;\nsetp.ne.u32 p, %1, 0;\n@p rcp.approx.ftz.f32 %0, %0;\n}" : "+f"(rs[0]) : "r"(always));
      asm volatile("{\n.reg .pred p;\nsetp.ne.u32 p, %1, 1;\n@p rcp.approx.ftz.f32 %0, %0;\n}" : "+f"(rs[1]) : "r"(always));
      asm volatile("lop3.b32 %0, %1, %2, %3, 0xfe;" : "=r"(lp) : "r"((l16 & 128) * 2), "r"((l16 & 256) * 4), "r"(l16 & 112));
      if (bad) continue;
      ldsm4t(ob, l16 + SM_OB + 512);
      mma16816z(f[2][0], wa, oc[0], oc[1]); mma16816z(f[2][1], wb, oc[2], oc[3]);
      mma16816z(f[0][0], wo[0], oc[0], oc[1]); mma16816z(f[0][1], wo[4], oc[2], oc[3]);
      mma16816z(f[1][0], w1[0], oc[0], oc[1]); mma16816z(f[1][1], w1[4], oc[2], oc[3]);
      ldsm4t_in(oc, l16 + SM_OB + 1024, always);
      mma16816(f[2][0], vx[2], ob[0], ob[1]); lds128_in(vx[2], w3a + KP(4) * WS, always);
      mma16816(f[2][1], vx[3], ob[2], ob[3]); lds128_in(vx[3], w3a + KP(5) * WS, always);
      mma16816(f[0][0], wo[1], ob[0], ob[1]); mma16816(f[0][1], wo[5], ob[2], ob[3]);
      mma16816(f[1][0], w1[1], ob[0], ob[1]); mma16816(f[1][1], w1[5], ob[2], ob[3]);
      ldsm4t_in(ob, l16 + SM_OB + 1536, always);
      mma16816(f[0][0], wo[2], oc[0], oc[1]); mma16816(f[0][1], wo[6], oc[2], oc[3]);
      mma16816(f[2][0], vx[2], oc[0], oc[1]); lds128_in(vx[2], w3a + KP(6) * WS, always);
      mma16816(f[2][1], vx[3], oc[2], oc[3]); lds128_in(vx[3], w3a + KP(7) * WS, always);
      mma16816(f[1][0], w1[2], oc[0], oc[1]); mma16816(f[1][1], w1[6], oc[2], oc[3]);
      mma16816(f[0][0], wo[3], ob[0], ob[1]); mma16816(f[0][1], wo[7], ob[2], ob[3]);
      mma16816(f[1][0], w1[3], ob[0], ob[1]); mma16816(f[1][1], w1[7], ob[2], ob[3]);
      mma16816(f[2][0], vx[2], ob[0], ob[1]); mma16816(f[2][1], vx[3], ob[2], ob[3]);
      bar_arrive(7, NII < 18 ? 384 : 256);
      lds128_in(ob, sb + SC_DEAD, always);
      uint32_t h[3][2];
#pragma unroll
      for (int j = 0; j < 3; j++)
#pragma unroll
        for (int i = 0; i < 2; i++)
        {
          scale_sum(f[j][1][2 * i], f[j][0][2 * i], rs[0], always); scale_sum(f[j][1][2 * i + 1], f[j][0][2 * i + 1], rs[1], always);
          h[j][i] = pack_f16(f[j][1][2 * i], f[j][1][2 * i + 1]);
        }
      const uint32_t rofs = RANK * 32768;
      red_f16x8(slot(s, RANK >> 1, rofs), h[0][0], h[1][0], h[2][0], 0x3c00u);
      red_f16x8(slot(s, (RANK >> 1) ^ 1, rofs), h[0][1], h[1][1], h[2][1], 0x3c00u);
      if (NII == 18) bar_arrive(10, 256);
      SCHED_FENCE(5);
      l16 += ob[B7R];
    }
    {
    PROF(8);
    const uint32_t ma0 = l16 + SM_MEM + w * 128 + (LV >> 3) * 896 + nh * 512;
    const unsigned char* const sl[2] = {slot(s, nh, 0), slot(s, nh ^ 1, 0)};
    uint32_t dl = gtime() - 1984;
    uint32_t late = latest_hint(hints, dl, s);
    if (late >= 64) {
      int n = 0;
#pragma unroll 1
      do {
        hints = load_hints(hint_addr(s));
        dl = gtime() - 1984;
        late = latest_hint(hints, dl, s);
      } while (late >= 64 && ++n < SPIN_LIMIT);
    }
    dl += late * 32 + tm.poll;
    PROF(9);
    {
      auto wait_until = [&](uint32_t t) {
        asm volatile("{\n.reg .pred p;\n.reg .s32 c;\n.reg .u64 t;\nTL: mov.u64 t, %%globaltimer;\ncvt.u32.u64 c, t;\nsub.s32 c, c, %0;\nsetp.lt.s32 p, c, 0;\n@p bra.uni TL;\n}" :: "r"(t + (l16 & 15)) : "memory");
      };
      uint4 v[2][3];
      auto load = [&](int c) {
#pragma unroll
        for (int r = 0; r < 3; r++) v[c][r] = ldg_relaxed(sl[c ^ (r >> 1)] + r * 32768);
      };
      auto decode = [&](int c, int n) {
        uint32_t q[9];
        __half2 hm;
        const uint32_t ma = ma0 ^ (c * 512);
#pragma unroll
        for (int i = 0; i < 9; i++) {
          const uint32_t h = i % 3 == 0 ? v[c][i / 3].x : (i % 3 == 1 ? v[c][i / 3].y : v[c][i / 3].z);
          const float2 f = __half22float2(*(const __half2*)&h);
          q[i] = pack_bf16(f.x, f.y);
          hm = i ? __hmax2(hm, __habs2(*(const __half2*)&h)) : __habs2(*(const __half2*)&h);
        }
#pragma unroll
        for (int r = 0; r < 3; r++) stsm4(ma + r * 4096, q[3 * r], q[3 * r + 1], q[3 * r + 2], r < 2 ? v[c][r].w : *(const uint32_t*)&hm);
        const bool done = __all_sync(0xffffffffu, v[c][0].w == 0x5000u && v[c][1].w == 0x5000u && v[c][2].w == 0x5000u) || n > SPIN_LIMIT;
        asm volatile("{\n.reg .pred p;\nsetp.ne.u32 p, %0, 0;\n@p bar.arrive %1, 256;\n}" :: "r"((int)done), "r"(1 + c) : "memory");
        return done;
      };
      if (LEAD) { wait_until(dl - LEAD); load(1); }
      int n = MO & 1 ? l16 & 15 : 0;
      if (MO & 1) PIN(n);
      if (MO & 2) {
        const uint32_t t = __shfl_sync(0xffffffffu, dl, 0);
        asm volatile("{\n.reg .pred p;\n.reg .s32 c;\nTL: mov.u32 c, %%globaltimer_lo;\nsub.s32 c, c, %0;\nsetp.lt.s32 p, c, 0;\n@p bra.uni TL;\n}" :: "r"(t) : "memory");
      } else wait_until(dl);
      PROF(10);
#pragma unroll 1
      do {
        load(0);
        if (!LEAD) load(1);
        asm volatile("{\n.reg .pred p;\nsetp.eq.u32 p, %0, 0;\n@p bar.sync 13, 384;\n}" :: "r"(n) : "memory");
      } while (!decode(0, n++));
      PROF(11);
#pragma unroll 1
      while (!decode(1, n++)) load(1);
      bar_arrive(9, 256);
      PROF(12);
    }
    PROF(13);
    if (++s == NSEG - 1) break;
    }
  }
#undef fence_reg
  if (RANK < 2) bar_arrive(4, 256);
  bar_sync(0, 384);
  cluster_sync();
}

__global__ void __cluster_dims__(3, 1, 1) __launch_bounds__(384, 1)
rec_kernel(const __grid_constant__ RMaps tm, const bf16* __restrict__ x, const bf16* __restrict__ mem0) {
  extern __shared__ __align__(1024) unsigned char smem_raw[];
  const uint32_t sb = smem_u32(smem_raw);
  const int tid = threadIdx.x, lane = tid & 31;
  const int wg = __shfl_sync(0xffffffffu, tid >> 7, 0);
  const int w = __shfl_sync(0xffffffffu, (tid >> 5) & 3, 0);
  uint32_t rank; asm("mov.u32 %0, %%cluster_ctarank;" : "=r"(rank));
  STAMP(0);
  asm volatile("griddepcontrol.launch_dependents;" ::: "memory");

    if (tid == 0) {
      const int h = blockIdx.x / 3;
      mbar_init(sb + MB_XS, 1);
      for (int i = 0; i < 3; i++) { mbar_init(sb + MB_W + 8 * i, 1); mbar_init(sb + MB_X + 8 * i, 1); }
      mbar_init(sb + MB_WO3, 1);
      fence_async();
      load_w(sb, tm, rank, 0);
      mbar_expect(sb + MB_X, XT);
      tma_load3(sb + SM_X, &tm.x, 0, sb + MB_X);
      if (WPOS == 2) load_w(sb, tm, rank, 1);
      mbar_expect(sb + MB_WO3, 32768 + 8 * DM * 2);
      tma_load(sb + SM_WOST, &tm.wo, rank * 192 + 64, h * DH, sb + MB_WO3);
      tma_load(sb + SM_WO3, &tm.wo, rank * 192 + 128, h * DH, sb + MB_WO3);
      bulk_load(sb + SM_M0, mem0, 8 * DM * 2, sb + MB_WO3);
      if (WOPF) tma_prefetch(&tm.wo, rank * 192, h * DH);
      if (WPOS == 1) load_w(sb, tm, rank, 1);
      load_w(sb, tm, rank, 2);
      mbar_init(sb + MB_WO, 1);
      mbar_init(sb + MB_S, rank < 2 ? 5 : 6);
      mbar_init(sb + MB_F, 1);
      mbar_init(sb + MB_VX, 1); mbar_init(sb + MB_VX + 8, 1);
      asm volatile("fence.mbarrier_init.release.cluster;" ::: "memory");
      fence_async();
      mbar_expect(sb + MB_X + 8, XT); mbar_expect(sb + MB_X + 16, XT);
      mbar_expect(sb + MB_WO, 16384); mbar_expect(sb + MB_XS, XT);
      mbar_expect(sb + MB_S, rank < 2 ? 640 + 2048 : 1280);
      mbar_expect(sb + MB_VX, 8192); mbar_expect(sb + MB_VX + 8, 8192);
    }
  __syncwarp();
  if (wg < 2) {
    asm volatile("setmaxnreg.inc.sync.aligned.u32 192;");
    __syncwarp();
    QSTAMP(0);
    if (tid < 32) bar_arrive(0, 160);
    QSTAMP(1);
    proj_role(sb, tm, x, rank, wg, w, lane);
  } else {
    asm volatile("setmaxnreg.dec.sync.aligned.u32 120;");
    attn_role(sb, smem_raw, tm, rank, x, mem0, w, lane);
  }
}

constexpr int NAUX = 36;
constexpr int A_ST = 6, A_STAGE = 8192 + 12288, A_W8 = A_ST * A_STAGE, A_EXC = A_W8 + A_ST * 1536, A_ROWS = 57;
constexpr int A_IN = A_EXC + 8 * 2304, A_INB = 3 * SEGB, A_OST = A_IN + 2 * A_INB, A_P = A_OST + 8192, A_G = A_P + 3072;
constexpr int A_BAR = A_G + 1024;
constexpr int A_XT = A_BAR + 1024, A_XW = A_XT;
constexpr int A_TOTAL = A_XT + 4096;
static_assert(A_IN % 1024 == 0 && A_XT % 1024 == 0 && A_IN >= 4 * XT && A_IN + 64 * DM * 2 <= A_BAR && A_TOTAL <= 232448, "side kernel shared memory");
struct AMaps { CUtensorMap x, wa, wa8, o, o3, o16, wob, woa, woa16; const unsigned char* red; uint32_t poll; };

DI void wgmma_n192_ss_nt(float* d, uint64_t da, uint64_t db, int acc) {
  asm volatile("{\n.reg .pred p;\nsetp.ne.b32 p, %98, 0;\n"
               "wgmma.mma_async.sync.aligned.m64n192k16.f32.bf16.bf16 {"
               "%0,%1,%2,%3,%4,%5,%6,%7,%8,%9,%10,%11,%12,%13,%14,%15,%16,%17,%18,%19,%20,%21,%22,%23,%24,%25,%26,%27,%28,%29,%30,%31,"
               "%32,%33,%34,%35,%36,%37,%38,%39,%40,%41,%42,%43,%44,%45,%46,%47,%48,%49,%50,%51,%52,%53,%54,%55,%56,%57,%58,%59,%60,%61,%62,%63,"
               "%64,%65,%66,%67,%68,%69,%70,%71,%72,%73,%74,%75,%76,%77,%78,%79,%80,%81,%82,%83,%84,%85,%86,%87,%88,%89,%90,%91,%92,%93,%94,%95"
               "}, %96, %97, p, 1, 1, 0, 1;\n}\n"
               : ACC8(d, 0), ACC8(d, 8), ACC8(d, 16), ACC8(d, 24), ACC8(d, 32), ACC8(d, 40), ACC8(d, 48), ACC8(d, 56),
                 ACC8(d, 64), ACC8(d, 72), ACC8(d, 80), ACC8(d, 88) : "l"(da), "l"(db), "r"(acc));
}
DI void wgmma_n24_ss_nt(float* d, uint64_t da, uint64_t db, int acc) {
  asm volatile("{\n.reg .pred p;\nsetp.ne.b32 p, %14, 0;\n"
               "wgmma.mma_async.sync.aligned.m64n24k16.f32.bf16.bf16 {%0,%1,%2,%3,%4,%5,%6,%7,%8,%9,%10,%11}, %12, %13, p, 1, 1, 0, 1;\n}\n"
               : ACC8(d, 0), "+f"(d[8]), "+f"(d[9]), "+f"(d[10]), "+f"(d[11]) : "l"(da), "l"(db), "r"(acc));
}
DI void tma_load3d(uint32_t dst, const CUtensorMap* m, int c0, int c1, int c2, uint32_t mb) {
  asm volatile("cp.async.bulk.tensor.3d.shared::cluster.global.mbarrier::complete_tx::bytes [%0], [%1, {%3, %4, %5}], [%2];"
               :: "r"(dst), "l"(m), "r"(mb), "r"(c0), "r"(c1), "r"(c2) : "memory");
}
DI uint32_t trans8(uint32_t x) { uint32_t r; asm("movmatrix.sync.aligned.m8n8.trans.b16 %0, %1;" : "=r"(r) : "r"(x)); return r; }
DI void wgmma_n40_ss(float* d, uint64_t da, uint64_t db, int acc) {
  asm volatile("{\n.reg .pred p;\nsetp.ne.b32 p, %22, 0;\n"
               "wgmma.mma_async.sync.aligned.m64n40k16.f32.bf16.bf16 {%0,%1,%2,%3,%4,%5,%6,%7,%8,%9,%10,%11,%12,%13,%14,%15,%16,%17,%18,%19}, "
               "%20, %21, p, 1, 1, 1, 1;\n}\n"
               : ACC8(d, 0), ACC8(d, 8), "+f"(d[16]), "+f"(d[17]), "+f"(d[18]), "+f"(d[19]) : "l"(da), "l"(db), "r"(acc));
}
DI uint2 ldg_relaxed64(const void* p) {
  uint2 v; asm volatile("ld.relaxed.gpu.global.v2.b32 {%0,%1}, [%2];" : "=r"(v.x), "=r"(v.y) : "l"(p) : "memory"); return v;
}
template <int ST> DI void ldg8x64(uint32_t* m, const void* p) {
  asm volatile("ld.relaxed.gpu.global.v2.b32 {%0,%1}, [%16];\nld.relaxed.gpu.global.v2.b32 {%2,%3}, [%16 + %17];\n"
               "ld.relaxed.gpu.global.v2.b32 {%4,%5}, [%16 + %18];\nld.relaxed.gpu.global.v2.b32 {%6,%7}, [%16 + %19];\n"
               "ld.relaxed.gpu.global.v2.b32 {%8,%9}, [%16 + %20];\nld.relaxed.gpu.global.v2.b32 {%10,%11}, [%16 + %21];\n"
               "ld.relaxed.gpu.global.v2.b32 {%12,%13}, [%16 + %22];\nld.relaxed.gpu.global.v2.b32 {%14,%15}, [%16 + %23];"
               : "=r"(m[0]), "=r"(m[1]), "=r"(m[2]), "=r"(m[3]), "=r"(m[4]), "=r"(m[5]), "=r"(m[6]), "=r"(m[7]),
                 "=r"(m[8]), "=r"(m[9]), "=r"(m[10]), "=r"(m[11]), "=r"(m[12]), "=r"(m[13]), "=r"(m[14]), "=r"(m[15])
               : "l"(p), "n"(ST), "n"(2 * ST), "n"(3 * ST), "n"(4 * ST), "n"(5 * ST), "n"(6 * ST), "n"(7 * ST) : "memory");
}
template <int ST> DI void ldg4x128(uint32_t* m, const void* p) {
  asm volatile("ld.relaxed.gpu.global.v4.b32 {%0,%1,%2,%3}, [%16];\nld.relaxed.gpu.global.v4.b32 {%4,%5,%6,%7}, [%16 + %17];\n"
               "ld.relaxed.gpu.global.v4.b32 {%8,%9,%10,%11}, [%16 + %18];\nld.relaxed.gpu.global.v4.b32 {%12,%13,%14,%15}, [%16 + %19];"
               : "=r"(m[0]), "=r"(m[1]), "=r"(m[2]), "=r"(m[3]), "=r"(m[4]), "=r"(m[5]), "=r"(m[6]), "=r"(m[7]),
                 "=r"(m[8]), "=r"(m[9]), "=r"(m[10]), "=r"(m[11]), "=r"(m[12]), "=r"(m[13]), "=r"(m[14]), "=r"(m[15])
               : "l"(p), "n"(ST), "n"(2 * ST), "n"(3 * ST) : "memory");
}
template <int N, int ST> DI bool stale(const uint32_t* m, uint32_t tag) {
  uint32_t x = m[0] ^ tag;
#pragma unroll
  for (int i = 1; i < N; i++) asm("lop3.b32 %0, %0, %1, %2, 0xf6;" : "+r"(x) : "r"(m[i * ST]), "r"(tag));
  return __any_sync(0xffffffffu, x & 1);
}
DI bool mbar_test(uint32_t b, uint32_t par) {
  uint32_t r; asm volatile("{\n.reg .pred p;\nmbarrier.test_wait.parity.shared::cta.b64 p, [%1], %2;\nselp.u32 %0, 1, 0, p;\n}" : "=r"(r) : "r"(b), "r"(par) : "memory");
  return r;
}
DI int wait_flags(const unsigned* p, bool active, unsigned base, int seg) {
  int n = 0, m;
  while (true) {
    m = __reduce_min_sync(0xffffffffu, active ? (int)(ldg_acquire32(p) - base) : NSEG);
    if (m > seg || ++n > SPIN_LIMIT) break;
    __nanosleep((YP & 32) ? 400 : 40);
  }
  return max(m, seg + 1);
}
DI void wait_count(const unsigned* p, unsigned target) {
  int n = 0;
  unsigned v;
  while (true) {
    asm volatile("ld.acquire.gpu.global.b32 %0, [%1];" : "=r"(v) : "l"(p) : "memory");
    if ((int)(v - target) >= 0 || ++n > SPIN_LIMIT) break;
    __nanosleep(64);
  }
}
#define PACE_NEXT 800
#define AWARM 0
#define WPF 3
#define UNP 64
#define ADLY 0
#define ODLY 100
#define SDLY 0
#define RSL 100
#define TWO 0
#define ALLW 1
#define AE 0
#define PING 60
#define FLAG 2
#define FPOS 1
#define QB 1
#define Q_LO 0
#define Q_HI 320
DI bool tick_wait(uint32_t pace, int step) {
  const int n = lds32v(pace);
  if (n <= step) mbar_wait(pace + 8, n & 1);
  return n <= step;
}
DI void quiet_wait(uint32_t pace) {
  uint32_t n, d;
  asm volatile("ld.volatile.shared.v2.b32 {%0,%1}, [%2];" : "=r"(n), "=r"(d) : "r"(pace) : "memory");
  if (n - 1 < NSEG - 2 && (int)(gtime() - d) > Q_HI) mbar_wait(pace + 8, n & 1);
}
DI void sleep_until(uint32_t t) {
  for (int n = 0; n < 64; n++) {
    const int r = t - gtime();
    if (r <= 0) break;
    __nanosleep(r >> 1);
  }
}
DI void aux_barrier(int i, unsigned epoch, bool wait = true) {
  asm volatile("fence.proxy.async;" ::: "memory");
  asm volatile("red.release.gpu.global.add.u32 [%0], 1;" :: "l"(&g_abar[i * 32]) : "memory");
  if (!wait) return;
  wait_count(&g_abar[i * 32], NAUX * (epoch + 1));
  asm volatile("fence.proxy.async;" ::: "memory");
}

__global__ void __launch_bounds__(512, 1)
aux_kernel(const __grid_constant__ AMaps tm, const bf16* __restrict__ x, const bf16* __restrict__ gate_w, bf16* __restrict__ out) {
  extern __shared__ __align__(1024) unsigned char smem_raw[];
  const uint32_t sb = smem_u32(smem_raw);
  const uint32_t full1 = sb + A_BAR, empty1 = full1 + 8 * A_ST, fullw = empty1 + 8 * A_ST, full3 = fullw + 16, empty3 = full3 + 32,
                 fulla = empty3 + 32, emptya = fulla + 32, fullg = emptya + 16, pace = fullg + 8;
  const int tid = threadIdx.x, lane = tid & 31, cta = blockIdx.x;
  const int wg = __shfl_sync(0xffffffffu, tid >> 7, 0), w = __shfl_sync(0xffffffffu, (tid >> 5) & 3, 0);
  ASTAMP(14);
  const unsigned epoch = *(volatile unsigned*)&g_epoch2;
  if (tid == 0) {
    for (int i = 0; i < A_ST; i++) { mbar_init(full1 + 8 * i, 1); mbar_init(empty1 + 8 * i, 8); }
    mbar_init(fullw, 1); mbar_init(fullw + 8, 1); mbar_init(fullg, 1);
    for (int i = 0; i < 2; i++) { mbar_init(fulla + 16 * i, 2); mbar_init(fulla + 16 * i + 8, 1); mbar_init(emptya + 8 * i, 4); }
    sts64(pace, 0, 0); mbar_init(pace + 8, 1); sts32(pace + 16, 0); sts64(pace + 24, 65536, 0xffff0000u);
    for (int i = 0; i < 4; i++) { mbar_init(full3 + 8 * i, 1); mbar_init(empty3 + 8 * i, cta < NH ? 8 : 4); }
    fence_async();
  }
  auto load_a = [&](int st, int k, int col) {
    mbar_expect(full1 + 8 * st, A_STAGE + 1536);
    tma_load3d(sb + st * A_STAGE, &tm.x, k, (cta >> 1) * A_ROWS - 7, 0, full1 + 8 * st);
    tma_load3d(sb + st * A_STAGE + 8192, &tm.wa, col, k, 0, full1 + 8 * st);
    tma_load3d(sb + A_W8 + st * 1536, &tm.wa8, col + 64, k, 0, full1 + 8 * st);
  };
  if (AE && tid < 32 && !(XP & 256)) {
    __syncwarp();
#pragma unroll 1
    for (int st = 0; st < A_ST; st++) if (elect_one()) load_a(st, st * 32, (cta & 1) * (DM / 2));
  }
  __syncthreads();
  ASTAMP(0);
  const bool wide = cta < NH;
  auto p3_ks = [&](int g) { return wide ? cta >> 2 : 2 * (cta - NH) + g; };
  auto p3_mt = [&](int g) { return wide ? 2 * (cta & 3) + g : 8; };
  const unsigned fbase = epoch * NSEG;
  if (wg == 3) {
    asm volatile("setmaxnreg.dec.sync.aligned.u32 %0;" :: "n"(TWO ? 32 : 48));
    if (w == 1 && cta < NH) {
#pragma unroll 1
      for (int seg = 0; seg < ((XP & 2048) ? 0 : NSEG); seg++) {
        bar_arrive(5, 160);
        if (seg > 0 && lane == 0) {
          asm volatile("cp.async.bulk.wait_group 0;" ::: "memory");
          stg_relaxed32(&g_oflag[cta * 32], fbase + seg);
        }
        __syncwarp();
        bar_sync(4, 160);
        if (QM & 16) tick_wait(pace, seg + 1);
        if (lane == 0) {
          fence_async();
          if (!(YP & 2)) {
          tma_store(&tm.o, sb + A_OST, cta * DH, seg * 32);
          tma_store(&tm.o, sb + A_OST + 4096, cta * DH + 64, seg * 32);
          }
          asm volatile("cp.async.bulk.commit_group;" ::: "memory");
          asm volatile("cp.async.bulk.wait_group.read 0;" ::: "memory");
        }
        __syncwarp();
      }
      if (lane == 0) {
        asm volatile("cp.async.bulk.wait_group 0;" ::: "memory");
        { const int seg = NSEG - 1; TSTAMP(2); }
        stg_relaxed32(&g_oflag[cta * 32], fbase + NSEG);
      }
    }
    if (w == 2 && cta < NH) {
      const uint32_t ktag = (epoch + 1) & 1, ma = sb + A_IN + 8192 + lane * 16;
      int avail = 0;
      bar_sync(10, 64);
#pragma unroll 1
      for (int seg = 0; seg < ((XP & 2048) ? 0 : NSEG); seg++) {
        if (avail <= seg) avail = wait_flags(&g_sflag[(cta * 3 + min(lane, 2)) * 8], true, fbase, seg);
        if ((QM & 8) && seg < UNP) tick_wait(pace, seg);
        TSTAMP(0);
        const unsigned char* km = g_km + (size_t)(seg * NH + cta) * 4096 + lane * 8;
        uint32_t m[16];
        const float g = __ldcg(&g_gate[seg * 32 + lane]);
        ldg8x64<256>(m, km);
        const uint32_t b = seg & 1, full = fulla + 16 * b, mb = ma + b * A_INB;
        mbar_wait(emptya + 8 * b, (~seg >> 1) & 1);
        if (lane < 2) mbar_expect(full + 8 * lane, (YP & 8) ? 0 : 16384 >> lane);
        __syncwarp();
        if (lane < 3 && !(YP & 8)) ((EF & 2) ? bulk_load_ef : bulk_load)(sb + A_IN + b * A_INB + lane * SEGB, g_seg + ((size_t)(seg & RING) * 96 + cta * 3 + lane) * 8192, 8192, full + (lane & 2) * 4);
        int n = 0;
#pragma unroll 1
        while (stale<8, 2>(m, ktag) && ++n < SPIN_LIMIT) { if (seg < UNP - 1) __nanosleep(200); ldg8x64<256>(m, km); }
        TSTAMP(1);
#pragma unroll
        for (int i = 0; i < 4; i++) stsm4(mb + (i >> 1) * SEGB + (i & 1) * 512, m[4 * i], m[4 * i + 1], m[4 * i + 2], m[4 * i + 3]);
        sts32(sb + A_G + b * 128 + lane * 4, __float_as_uint(1.f - g));
        fence_async();
        __syncwarp();
        if (lane == 0) mbar_arrive(full);
      }
    }
    if (w == 3 && QM) {
      const unsigned char* const hp = tm.red + HINT_OFF + 65536 + (cta & 1) * 4096 + min(lane, 23) * 4;
      uint32_t d = 0;
      int s = 0, n = 0;
#pragma unroll 1
      while (s < NSEG - 1) {
        const uint32_t h = ldg_relaxed32(hp + RED_SLOT(s)), t = (gtime() - 1984) & ~31u, late = latest_hint(h, t, s);
        if (late < 64) {
          d = t + late * 32 + tm.poll + Q_LO;
          sleep_until(d);
          s++; n = 0;
          if (lane == 0) { mbar_arrive(pace + 8); sts64(pace, s < NSEG - 1 ? s : 2 * NSEG, d); }
          sleep_until(d + PACE_NEXT);
        } else {
          if (++n > (s ? 16 : 256) || lds32v(pace + 16)) break;
          if (!s) __nanosleep(100);
        }
      }
      if (s < NSEG - 1 && lane == 0) { mbar_arrive(pace + 8); sts64(pace, 2 * NSEG, d); }
    }
    if (w != 0) return;
    const bool lead = lane == 0;
#pragma unroll 1
    for (int it = AE * A_ST, st = 0, ph = !AE, k = AE * A_ST * 32, col = (cta & 1) * (DM / 2); it < ((XP & 256) ? 0 : 72); it++) {
      mbar_wait(empty1 + 8 * st, ph);
      if (QM & 1) quiet_wait(pace);
      if (elect_one()) load_a(st, k, col);
      __syncwarp();
      if (++st == A_ST) { st = 0; ph ^= 1; }
      k += 32;
      if (k == DM) { k = 0; col += 72; }
    }
    auto load_wo = [&](uint32_t dst, int g, int kb, uint32_t mb) {
      if (kb < 64) tma_load(dst, &tm.wob, p3_mt(g) * 64, kb * 64, mb);
      else tma_load(dst, &tm.woa, p3_mt(g) * 64, (kb - 64) * 64, mb);
    };
    if (lead) mbar_expect(fullw, 16 * 8192);
#pragma unroll 1
    for (int st = 0; st < A_ST; st++) {
      if (!(XP & 256)) mbar_wait(empty1 + 8 * st, 1);
      if (lane < 16 && min(((lane + 1) * 8192 - 1) / A_STAGE, A_ST - 1) == st) load_wo(sb + lane * 8192, lane >> 3, p3_ks(lane >> 3) * 9 + (lane & 7), fullw);
      __syncwarp();
    }
    __syncwarp(); bar_sync(6, 288);
    if (lead) mbar_expect(fullw + 8, 2 * 8192 + (p3_ks(0) >= 4 ? 4096 : 0));
    __syncwarp();
    if (lane < 2) {
      load_wo(sb + (16 + lane) * 8192, lane, p3_ks(lane) * 9 + 8, fullw + 8);
      if (p3_ks(0) >= 4) tma_load(sb + A_XW + lane * 2048, &tm.woa16, p3_mt(lane) * 64, 448 + p3_ks(lane) * 16, fullw + 8);
    }
    __syncwarp();
    if (lead) aux_barrier(1, epoch, ALLW || p3_ks(0) >= 4);
    __syncwarp(); bar_sync(6, 288);
    {
      int avail = 0, sl = 0, ph = 1;
      const int h = (9 * p3_ks(0) >> 1) + lane;
#pragma unroll 1
      for (int seg = 0; seg < ((XP & 2048) ? 0 : NSEG); seg++) {
        if (avail <= seg) avail = wait_flags(&g_oflag[min(h, NH - 1) * 32], lane < (wide ? 5 : 9), fbase, seg);
        SSTAMP(seg, 4);
        for (int g = 0; g < (wide ? 1 : 2); g++) {
          const int ks = p3_ks(g);
          mbar_wait(empty3 + 8 * sl, ph);
          if ((QM & 4) && tick_wait(pace, seg + (QM >> 4 & 1) + 1) && ODLY) __nanosleep(ODLY);
          if (YP & 4) { if (lead) mbar_arrive(full3 + 8 * sl); }
          else if (elect_one()) {
            mbar_expect(full3 + 8 * sl, XT + (ks >= 4 ? 1024 : 0));
            tma_load3d(sb + sl * XT, &tm.o3, 0, seg * 32, ks * 9, full3 + 8 * sl);
            if (ks >= 4) tma_load(sb + A_XT + sl * 1024, &tm.o16, 72 * 64 - 64 + ks * 16, seg * 32, full3 + 8 * sl);
          }
          __syncwarp();
          if (++sl == (wide ? 3 : 4)) { sl = 0; ph ^= 1; }
        }
      }
    }
    sts32(pace + 16, 1);
    __syncwarp(); bar_sync(6, 288);
    asm volatile("griddepcontrol.wait;" ::: "memory");
  } else if (wg == 2) {
    asm volatile("setmaxnreg.dec.sync.aligned.u32 64;");
    if (cta < NH) {
      if (tid == 256) { mbar_expect(fullg, 64 * DM * 2); bulk_load(sb + A_IN, x + cta * 64 * DM, 64 * DM * 2, fullg); }
      uint32_t gw[9];
#pragma unroll
      for (int j = 0; j < 9; j++) gw[j] = ((const uint32_t*)gate_w)[j * 32 + lane];
      mbar_wait(fullg, 0);
      float mine = 0.f;
#pragma unroll 4
      for (int u = 0; u < 16; u++) {
        float d0 = 0.f, d1 = 0.f;
#pragma unroll
        for (int j = 0; j < 9; j++) {
          const uint32_t a = lds32(sb + A_IN + (w * 16 + u) * (DM * 2) + j * 128 + lane * 4);
          d0 = fmaf(bf_lo(a), bf_lo(gw[j]), d0); d1 = fmaf(bf_hi(a), bf_hi(gw[j]), d1);
        }
        d0 = warp_sum(d0 + d1);
        if (lane == u) mine = d0;
      }
      if (lane < 16) g_gate[cta * 64 + w * 16 + lane] = 1.f / (1.f + __expf(-mine));
      fence_async();
    }
    bar_sync(3, 128);
    if (tid == 256) { aux_barrier(0, epoch); if (cta == 0) *(volatile unsigned*)&g_epoch2 = epoch + 1; }
    __syncwarp();
    bar_sync(3, 128);
    if (w == 0) bar_arrive(8, 288);
    if (w == 1 && cta < NH) bar_arrive(10, 64);
    if (cta < NH) {
      CDECL;
#pragma unroll 1
      for (int seg = 0; seg < ((XP & 2048) ? 0 : NSEG); seg++) {
        CSTAMP(0);
        const uint32_t in = sb + A_IN + (seg & 1) * A_INB;
        const uint64_t qd = make_desc(in, 128, 1024, 0);
        mbar_wait(fulla + 16 * (seg & 1), (seg >> 1) & 1);
        CSTAMP(3);
        SSTAMP(seg, 0);
        float d[2][16];
        {
          float a[20];
          uint32_t vm[16];
          const unsigned char* vp = g_km + (size_t)(seg * NH + cta) * 4096 + 2048 + lane * 16;
          if (w == 3) ldg4x128<512>(vm, vp);
          WG_FENCE();
#pragma unroll
          for (int k = 0; k < ((YP & 16) ? 1 : 8); k++) wgmma_n40_ss(a, qd + ((k >> 2) * SEGB + (k & 3) * 256 >> 4), qd + ((k >> 2) * SEGB + (k & 3) * 256 + 4096 >> 4), k > 0);
          const uint32_t ga = sb + A_G + (seg & 1) * 128 + (w & 1) * 64 + (lane >> 2) * 4;
          const float f0 = __uint_as_float(lds32(ga)), f1 = __uint_as_float(lds32(ga + 32));
          WG_COMMIT();
          WG_WAIT(0);
          CSTAMP(5);
          SSTAMP(seg, 1);
          if (w < 2) {
            const int lim = w * 16 + (lane >> 2) - 2 * (lane & 3);
            float m0 = -3.0e38f, m1 = -3.0e38f;
#pragma unroll
            for (int i = 0; i < 20; i++) {
              a[i] *= SM_SCALE * LOG2E;
              if (i < 16 && (i >> 2) * 8 + (i & 1) - (i & 2) * 4 > lim) a[i] = -1.0e9f * LOG2E;
              if (i & 2) m1 = fmaxf(m1, a[i]); else m0 = fmaxf(m0, a[i]);
            }
#pragma unroll
            for (int o = 1; o < 4; o <<= 1) { m0 = fmaxf(m0, __shfl_xor_sync(0xffffffffu, m0, o)); m1 = fmaxf(m1, __shfl_xor_sync(0xffffffffu, m1, o)); }
            float s0 = 0.f, s1 = 0.f;
#pragma unroll
            for (int i = 0; i < 20; i++) { a[i] = ex2(a[i] - (i & 2 ? m1 : m0)); if (i & 2) s1 += a[i]; else s0 += a[i]; }
#pragma unroll
            for (int o = 1; o < 4; o <<= 1) { s0 += __shfl_xor_sync(0xffffffffu, s0, o); s1 += __shfl_xor_sync(0xffffffffu, s1, o); }
            s0 = f0 * rcp(s0); s1 = f1 * rcp(s1);
            uint32_t p[10];
#pragma unroll
            for (int i = 0; i < 10; i++) p[i] = pack_bf16(a[2 * i] * (i & 1 ? s1 : s0), a[2 * i + 1] * (i & 1 ? s1 : s0));
            const uint32_t pa = sb + A_P + (2 * w + ((lane >> 3) & 1)) * 768 + (lane >> 4) * 128 + (lane & 7) * 16;
            stsm4t(pa, p[0], p[1], p[2], p[3]); stsm4t(pa + 256, p[4], p[5], p[6], p[7]); stsm4t(pa + 512, p[8], p[9], 0, 0);
            CSTAMP(6);
            fence_async();
            CSTAMP(7);
          } else if (w == 3) {
            int n = 0;
#pragma unroll 1
            while (stale<4, 4>(vm, (epoch + 1) & 1) && ++n < SPIN_LIMIT) ldg4x128<512>(vm, vp);
#pragma unroll
            for (int i = 0; i < 4; i++) stsm4(in + 2 * SEGB + 8192 + (lane >> 4) * 1024 + (lane & 15) * 16 + i * 256, vm[4 * i], vm[4 * i + 1], vm[4 * i + 2], vm[4 * i + 3]);
            fence_async();
            mbar_wait(fulla + 16 * (seg & 1) + 8, (seg >> 1) & 1);
          }
        }
        CSTAMP(8);

        bar_sync(5, 160);
        CSTAMP(10);
        SSTAMP(seg, 2);
        const uint64_t pd = make_desc(sb + A_P, 128, 768, 0), vd = make_desc(in + 2 * SEGB, 128, 512, 0), md = make_desc(in + 2 * SEGB + 8192, 0, 128, 0);
        WG_FENCE();
#pragma unroll
        for (int i = 0; i < 2; i++) {
          wgmma_n32_ss<0>(d[i], vd + i * 256, pd, 0);
          wgmma_n32_ss<0>(d[i], vd + i * 256 + 16, pd + 16, 1);
          wgmma_n32_ss<0>(d[i], md + i * 64, pd + 32, 1);
        }
        WG_COMMIT();
        WG_WAIT(0);
        CSTAMP(11);
        if (lane == 0) mbar_arrive(emptya + 8 * (seg & 1));
#pragma unroll
        for (int i = 0; i < 2; i++) {
          const uint32_t oa = sb + A_OST + i * 4096 + ((lane & 7) + ((lane >> 4) << 3)) * 128 + (((2 * w + ((lane >> 3) & 1)) ^ (lane & 7)) << 4);
          stsm4t(oa, pack_bf16(d[i][0], d[i][1]), pack_bf16(d[i][2], d[i][3]), pack_bf16(d[i][4], d[i][5]), pack_bf16(d[i][6], d[i][7]));
          stsm4t(oa + 2048, pack_bf16(d[i][8], d[i][9]), pack_bf16(d[i][10], d[i][11]), pack_bf16(d[i][12], d[i][13]), pack_bf16(d[i][14], d[i][15]));
        }
        CSTAMP(12);
        bar_sync(4, 160);
        SSTAMP(seg, 3);
      }
      CDUMP;
    }
  } else {
    asm volatile("setmaxnreg.inc.sync.aligned.u32 %0;" :: "n"(TWO ? 208 : 200));
    {
      const int g = lane >> 2, t = lane & 3, r0 = (cta >> 1) * A_ROWS - 7 + w * 16;
      const uint32_t prev = (2 * t > g ? 0xffffu : 0u) | (2 * t + 1 > g ? 0xffff0000u : 0u);
      const int k0 = r0 + 2 * t - (2 * t > g ? 8 : 0), k1 = r0 + 2 * t + 1 - (2 * t + 1 > g ? 8 : 0);
      const uint32_t slot = sb + A_EXC + (wg * 4 + w) * 2304;
      float gl = 0.f, gh = 0.f;
      int st = 0, ph = 0;
#pragma unroll 1
      for (int p = -AWARM; p < ((XP & 256) ? 0 : 4); p++) {
        float big[96], sml[12];
        if (p == WPF && tid < 18) {
          const int kb = p3_ks(tid >= 9) * 9 + tid % 9;
          tma_prefetch(kb < 64 ? &tm.wob : &tm.woa, p3_mt(tid >= 9) * 64, (kb & 63) * 64);
        }
        __syncwarp();
#pragma unroll
        for (int i = 0; i < 96; i++) big[i] = 0.f;
#pragma unroll
        for (int i = 0; i < 12; i++) sml[i] = 0.f;
#pragma unroll 1
        for (int k = p < 0 ? 18 : 0; k < 18; k++) {
          mbar_wait(full1 + 8 * st, ph);
          const uint64_t da = make_desc(sb + st * A_STAGE + wg * 4096, 16, 512, 2);
          const uint64_t db = make_desc(sb + st * A_STAGE + 8192, 4096, 1024, 1), dc = make_desc(sb + A_W8 + st * 1536, 128, 512, 0);
          WG_FENCE();
#pragma unroll
          for (int j = 0; j < 2; j++) { wgmma_n192_ss_nt(big, da + j * 2, db + j * 128, 1); wgmma_n24_ss_nt(sml, da + j * 2, dc + j * 16, 1); }
          WG_COMMIT();
          WG_WAIT(1);
          if (k > 0 && lane == 0) mbar_arrive(empty1 + 8 * (st ? st - 1 : A_ST - 1));
          if (++st == A_ST) { st = 0; ph ^= 1; }
        }
        WG_WAIT(0);
        ASTAMP(16 + max(p, 0) + wg * 16);
        if (lane == 0 && p >= 0) mbar_arrive(empty1 + 8 * (st ? st - 1 : A_ST - 1));
        uint32_t f[3][9][2];
#pragma unroll
        for (int c = 0; c < 3; c++)
#pragma unroll
          for (int j = 0; j < 9; j++)
#pragma unroll
            for (int i = 0; i < 2; i++) {
              const float* a = j < 8 ? &big[(c * 8 + j) * 4 + 2 * i] : &sml[c * 4 + 2 * i];
              f[c][j][i] = c < 2 ? pack_bf16(a[0], a[1]) : trans8(pack_bf16(a[0], a[1]));
            }
        if (p == 0) {
          bar_sync(8, 288);
          gl = __ldcg(&g_gate[min(max(r0 + g, 0), S_LEN / 2 - 1) * 2 + wg]); gh = __ldcg(&g_gate[min(max(r0 + g + 8, 0), S_LEN / 2 - 1) * 2 + wg]);
        }
        asm volatile("cp.async.bulk.wait_group.read 0;" ::: "memory");
        __syncwarp();
#pragma unroll
        for (int j = 0; j < 8; j += 2) sts128(slot + j * 256 + lane * 16, f[1][j][1], f[2][j][1], f[1][j + 1][1], f[2][j + 1][1]);
        sts64(slot + 2048 + lane * 8, f[1][8][1], f[2][8][1]);
        bar_sync(1 + wg, 128);
        ASTAMP(24 + max(p, 0) + wg * 16);
        uint32_t pv[9][2];
#pragma unroll
        for (int j = 0; j < 9; j++) pv[j][0] = pv[j][1] = 0;
        if (w) {
#pragma unroll
          for (int j = 0; j < 8; j += 2) lds128(slot - 2304 + j * 256 + lane * 16, pv[j]);
          lds64(slot - 256 + lane * 8, pv[8][0], pv[8][1]);
        }
        float a[4][4], m[4][2];
#pragma unroll
        for (int h = 0; h < 4; h++) {
          const int j = 2 * h;
          const uint32_t qa[4] = {t >= h ? f[0][j][0] : 0, t >= h ? f[0][j][1] : 0, f[0][j + 1][0], f[0][j + 1][1]};
          const uint32_t qb0 = t <= h ? f[0][j + 2][0] : 0, qb1 = t <= h ? f[0][j + 2][1] : 0;
          float s0[4], s1[4], s2[4];
          mma16816z(s1, qa, f[1][j][0], f[1][j + 1][0]); mma16816z(s2, qa, f[1][j][1], f[1][j + 1][1]); mma16816z(s0, qa, pv[j][0], pv[j + 1][0]);
          mma1688(s1, qb0, qb1, f[1][j + 2][0]); mma1688(s2, qb0, qb1, f[1][j + 2][1]); mma1688(s0, qb0, qb1, pv[j + 2][0]);
          a[h][0] = 2 * t > g ? s0[0] : s1[0]; a[h][1] = 2 * t + 1 > g ? s0[1] : s1[1]; a[h][2] = 2 * t > g ? s1[2] : s2[2]; a[h][3] = 2 * t + 1 > g ? s1[3] : s2[3];
        }
#pragma unroll
        for (int h = 0; h < 4; h++) {
#pragma unroll
          for (int i = 0; i < 4; i++) a[h][i] = (i & 1 ? k1 : k0) + (i & 2) * 4 >= 0 ? a[h][i] * (0.23570226039551584f * LOG2E) : -1.0e9f * LOG2E;
          m[h][0] = fmaxf(a[h][0], a[h][1]); m[h][1] = fmaxf(a[h][2], a[h][3]);
        }
#pragma unroll
        for (int x = 1; x < 4; x <<= 1)
#pragma unroll
          for (int i = 0; i < 8; i++) m[i >> 1][i & 1] = fmaxf(m[i >> 1][i & 1], __shfl_xor_sync(0xffffffffu, m[i >> 1][i & 1], x));
#pragma unroll
        for (int h = 0; h < 4; h++) {
#pragma unroll
          for (int i = 0; i < 4; i++) a[h][i] = ex2(a[h][i] - m[h][i >> 1]);
          m[h][0] = a[h][0] + a[h][1]; m[h][1] = a[h][2] + a[h][3];
        }
#pragma unroll
        for (int x = 1; x < 4; x <<= 1)
#pragma unroll
          for (int i = 0; i < 8; i++) m[i >> 1][i & 1] += __shfl_xor_sync(0xffffffffu, m[i >> 1][i & 1], x);
        uint32_t o[9][2];
#pragma unroll
        for (int h = 0; h < 4; h++) {
          const int j = 2 * h;
          const float z0 = gl * rcp(m[h][0]), z1 = gh * rcp(m[h][1]);
          const uint32_t pl = pack_bf16(a[h][0] * z0, a[h][1] * z0), pu = pack_bf16(a[h][2] * z1, a[h][3] * z1);
          const uint32_t pa[4] = {pl & prev, 0, pl & ~prev, pu & prev};
          float d[3][4];
#pragma unroll
          for (int i = 0; i < 3; i++) mma16816z(d[i], pa, pv[j + i][1], f[2][j + i][0]);
#pragma unroll
          for (int i = 0; i < 3; i++) mma1688(d[i], 0, pu & ~prev, f[2][j + i][1]);
#pragma unroll
          for (int i = 0; i < 3; i++) {
            const uint32_t d0 = pack_bf16(d[i][0], d[i][1]), d1 = pack_bf16(d[i][2], d[i][3]);
            o[j + i][0] = i == 0 && h > 0 && t < h ? o[j][0] : d0;
            o[j + i][1] = i == 0 && h > 0 && t < h ? o[j][1] : d1;
          }
        }
        ASTAMP(28 + max(p, 0) + wg * 16);
        bar_sync(1 + wg, 128);
        const uint32_t oa = slot + (lane & 15) * 144 + (lane >> 4) * 16;
#pragma unroll
        for (int j = 0; j < 8; j += 2) stsm4(oa + j * 16, o[j][0], o[j][1], o[j + 1][0], o[j + 1][1]);
        asm volatile("stmatrix.sync.aligned.m8n8.x2.shared.b16 [%0], {%1,%2};" :: "r"(oa + 128), "r"(o[8][0]), "r"(o[8][1]) : "memory");
        fence_async();
        __syncwarp();
        if (QM & 64) quiet_wait(pace);
        if (lane < 16 && w * 16 + lane >= 7 && r0 + lane < S_LEN / 2 && p >= 0)
          asm volatile("cp.async.bulk.global.shared::cta.bulk_group [%0], [%1], 144;"
                       :: "l"(g_Ocat + (size_t)((r0 + lane) * 2 + wg) * KCAT + 4096 + (cta & 1) * (DM / 2) + p * 72), "r"(slot + lane * 144) : "memory");
        asm volatile("cp.async.bulk.commit_group;" ::: "memory");
        ASTAMP(20 + max(p, 0) + wg * 16);
      }
      if (XP & 256) bar_sync(8, 288);
      asm volatile("cp.async.bulk.wait_group 0;" ::: "memory");
    }
    ASTAMP(3);
    bar_arrive(6, 288);
    uint32_t wa[37][4];
    mbar_wait(fullw, 0);
    const uint32_t la = sb + ((lane & 7) + ((lane >> 4) << 3)) * 128 + (((2 * w + ((lane >> 3) & 1)) ^ (lane & 7)) << 4);
#pragma unroll
    for (int k = 0; k < 32; k++) ldsm4t(wa[k], la + wg * 65536 + k * 2048);
    mbar_wait(fullw + 8, 0);
#pragma unroll
    for (int k = 32; k < 36; k++) ldsm4t(wa[k], la + wg * 8192 + 65536 + k * 2048);
    ldsm4t(wa[36], la + A_XW + wg * 2048);
    fence_async();
    if (XP & 2048) bar_sync(6, 288); else bar_arrive(6, 288);
    ASTAMP(4);
    const int ks = p3_ks(wg), mt = p3_mt(wg);
    uint32_t v[16];
    auto fetch = [&](int seg) { ldg8x64<1024>(v, g_part + (((seg & 7) * 9 + mt) * 4 + (ks & 3)) * 1024 + (tid & 127)); };
    auto finish = [&](int seg) {
      const uint32_t tagv = (~seg >> 3) & 1;
      int n = 0;
#pragma unroll 1
      while (!(YP & 512) && stale<8, 2>(v, tagv) && ++n < SPIN_LIMIT) {
        if (seg < NSEG - 2) __nanosleep(RSL);
        fetch(seg);
      }
      float own[4] = {bf_lo(v[0]), bf_hi(v[0]), bf_lo(v[1]), bf_hi(v[1])};
#pragma unroll
      for (int j = 1; j < 8; j++) { own[0] += bf_lo(v[2 * j]); own[1] += bf_hi(v[2 * j]); own[2] += bf_lo(v[2 * j + 1]); own[3] += bf_hi(v[2 * j + 1]); }
      uint32_t p0 = pack_bf16(own[0], own[1]), p1 = pack_bf16(own[2], own[3]);
      asm volatile("movmatrix.sync.aligned.m8n8.trans.b16 %0, %0;" : "+r"(p0));
      asm volatile("movmatrix.sync.aligned.m8n8.trans.b16 %0, %0;" : "+r"(p1));
      uint32_t* o = (uint32_t*)(out + (size_t)(seg * 32 + (ks & 3) * 8 + (lane >> 2)) * DM + mt * 64 + w * 16) + (lane & 3);
      if (!(YP & 256) || p0 == 0x12345678) { o[0] = p0; o[4] = p1; }
      SSTAMP(seg, 7);
    };
    float acc[16], acc2[16];
#pragma unroll
    for (int i = 0; i < 16; i++) acc[i] = acc2[i] = 0.f;
    int pend = -1, sl = wide ? 0 : wg, ph = 0;
    if (PING && wg) bar_arrive(1, 256);
    CDECL;
    auto run = [&](auto extra) {
#pragma unroll 1
    for (int seg = 0; seg <= ((XP & 2048) ? -1 : NSEG); seg++) {
      CSTAMP(0);
      const bool fin = pend >= 0 && (seg - pend >= FLAG || seg == NSEG);
      if (seg < NSEG) mbar_wait(full3 + 8 * sl, ph);
      if (FPOS == 1 && fin) fetch(pend);
      if (SDLY) {
        uint32_t n, d;
        asm volatile("ld.volatile.shared.v2.b32 {%0,%1}, [%2];" : "=r"(n), "=r"(d) : "r"(pace) : "memory");
        if ((int)n <= seg + 3) sleep_until(d + SDLY);
      }
      CSTAMP(1);
      if (seg < NSEG) {
      if (wg) SSTAMP(seg, 5);
      if (seg < PING) bar_sync(1 + wg, 256);
      CSTAMP(7);
      const uint64_t db = make_desc(sb + sl * XT, 16, 1024, 1);
      WG_FENCE();
#pragma unroll
      for (int k = 0; k < ((XP & 1024) ? 1 : 36); k++)
        wgmma_n32_rs(TWO && (k & 1) ? acc2 : acc, wa[k][0], wa[k][1], wa[k][2], wa[k][3], db + (k >> 2) * 256 + (k & 3) * 2, k >> TWO);
      if (decltype(extra)::value) wgmma_n32_rs(acc, wa[36][0], wa[36][1], wa[36][2], wa[36][3], make_desc(sb + A_XT + sl * 1024, 16, 256, 3), 1);
      WG_COMMIT();
      if (seg < PING) bar_arrive(2 - wg, 256);
      CSTAMP(2);
      CSTAMP(3);
      WG_WAIT(0);
      CSTAMP(4);
      if (wg) SSTAMP(seg, 6);
      if (lane == 0) mbar_arrive(empty3 + 8 * sl);
      sl += wide ? 1 : 2;
      if (sl >= (wide ? 3 : 4)) { sl -= wide ? 3 : 4; ph ^= 1; }
      uint2* dst = g_part + (((seg & 7) * 9 + mt) * 32 + ks) * 128 + (tid & 127);
      uint32_t q[8];
      if (TWO)
#pragma unroll
        for (int j = 0; j < 16; j++) acc[j] += acc2[j];
#pragma unroll
      for (int j = 0; j < 8; j++) q[j] = j & 1 ? pack_bf16(acc[2 * j], acc[2 * j + 1]) : (pack_bf16(acc[2 * j], acc[2 * j + 1]) & ~1u) | ((~seg >> 3) & 1);
      if (QM & 32) tick_wait(pace, seg + (QM >> 4 & 1) + 2);
      if (!(YP & 1025) || q[0] == 0x12345678)
      asm volatile("st.relaxed.gpu.global.v2.b32 [%0], {%1,%2};\nst.relaxed.gpu.global.v2.b32 [%0 + 8192], {%3,%4};\n"
                   "st.relaxed.gpu.global.v2.b32 [%0 + 16384], {%5,%6};\nst.relaxed.gpu.global.v2.b32 [%0 + 24576], {%7,%8};"
                   :: "l"(dst), "r"(q[0]), "r"(q[1]), "r"(q[2]), "r"(q[3]), "r"(q[4]), "r"(q[5]), "r"(q[6]), "r"(q[7]) : "memory");
      }
      CSTAMP(5);
      if (fin) { finish(pend); pend = -1; }
      CSTAMP(6);
      if ((seg & 1) == ks >> 2 && !(YP & 1)) pend = seg;
      if (wg && (seg & 7) == 6) ASTAMP(5 + (seg >> 3));
    }
    };
    if (ks >= 4) run(BoolC<true>()); else run(BoolC<false>());
    if (PING && !wg) bar_sync(1, 256);
    CDUMP;
    ASTAMP(13);
    bar_sync(6, 288);
  }
}

typedef CUresult (*EncodeFn)(CUtensorMap*, CUtensorMapDataType, cuuint32_t, void*, const cuuint64_t*, const cuuint64_t*,
                             const cuuint32_t*, const cuuint32_t*, CUtensorMapInterleave, CUtensorMapSwizzle,
                             CUtensorMapL2promotion, CUtensorMapFloatOOBfill);
#define PROMO 2
static void make_map(EncodeFn enc, CUtensorMap* m, const void* p, int rows, int cols, int box_rows) {
  cuuint64_t dims[2] = {(cuuint64_t)cols, (cuuint64_t)rows};
  cuuint64_t strides[1] = {(cuuint64_t)cols * 2};
  cuuint32_t box[2] = {64, (cuuint32_t)box_rows};
  cuuint32_t es[2] = {1, 1};
  enc(m, CU_TENSOR_MAP_DATA_TYPE_BFLOAT16, 2, (void*)p, dims, strides, box, es, CU_TENSOR_MAP_INTERLEAVE_NONE,
      CU_TENSOR_MAP_SWIZZLE_128B, (CUtensorMapL2promotion)PROMO, CU_TENSOR_MAP_FLOAT_OOB_FILL_NONE);
}

constexpr int g_poll = POLL_NS;
extern "C" void kernel_launch(void* const* d_in, const int* in_sizes, int n_in, void* d_out, int out_size) {
  const bf16* x = (const bf16*)d_in[0];
  const bf16* wqkvA = (const bf16*)d_in[1];
  const bf16* woA = (const bf16*)d_in[2];
  const bf16* mem0 = (const bf16*)d_in[4];
  const bf16* Wq = (const bf16*)d_in[5];
  const bf16* Wk = (const bf16*)d_in[6];
  const bf16* Wv = (const bf16*)d_in[7];
  const bf16* Wo = (const bf16*)d_in[8];
  const bf16* gate_w = (const bf16*)d_in[10];
  static EncodeFn enc = nullptr;
  static void *pO = nullptr, *pR = nullptr;
  if (!enc) {
    cudaDriverEntryPointQueryResult qr;
    cudaGetDriverEntryPoint("cuTensorMapEncodeTiled", (void**)&enc, cudaEnableDefault, &qr);
    cudaGetSymbolAddress(&pO, g_Ocat);
    cudaGetSymbolAddress(&pR, g_red_raw);
    cudaFuncSetAttribute(rec_kernel, cudaFuncAttributeMaxDynamicSharedMemorySize, SM_TOTAL);
    cudaFuncSetAttribute(aux_kernel, cudaFuncAttributeMaxDynamicSharedMemorySize, A_TOTAL);
  }
  RMaps rm;
  rm.poll = g_poll;
  rm.w[0] = (const unsigned char*)Wk; rm.w[1] = (const unsigned char*)Wq; rm.w[2] = (const unsigned char*)Wv; rm.w[3] = (const unsigned char*)Wo;
  rm.red = (unsigned char*)(((uintptr_t)pR + 262143) & ~(uintptr_t)262143);
  {
    cuuint64_t dims[3] = {64, S_LEN, 9}, strides[2] = {DM * 2, 128};
    cuuint32_t box[3] = {64, 32, 9}, es[3] = {1, 1, 1};
    enc(&rm.x, CU_TENSOR_MAP_DATA_TYPE_BFLOAT16, 3, (void*)x, dims, strides, box, es, CU_TENSOR_MAP_INTERLEAVE_NONE,
        CU_TENSOR_MAP_SWIZZLE_128B, CU_TENSOR_MAP_L2_PROMOTION_L2_128B, CU_TENSOR_MAP_FLOAT_OOB_FILL_NONE);
  }
  make_map(enc, &rm.wq, Wq, DM, 4096, 192);
  make_map(enc, &rm.wk, Wk, DM, 4096, 192);
  make_map(enc, &rm.wv, Wv, DM, 4096, 192);
  make_map(enc, &rm.wo, Wo, 4096, DM, 128);
  AMaps am;
  am.red = rm.red; am.poll = rm.poll;
  {
    cuuint64_t dims[3] = {DM, S_LEN / 2, 2}, strides[2] = {DM * 4, DM * 2};
    cuuint32_t box[3] = {32, 64, 2}, es[3] = {1, 1, 1};
    enc(&am.x, CU_TENSOR_MAP_DATA_TYPE_BFLOAT16, 3, (void*)x, dims, strides, box, es, CU_TENSOR_MAP_INTERLEAVE_NONE,
        CU_TENSOR_MAP_SWIZZLE_64B, CU_TENSOR_MAP_L2_PROMOTION_L2_128B, CU_TENSOR_MAP_FLOAT_OOB_FILL_NONE);
    cuuint64_t wdims[3] = {DM, DM, 3}, wstrides[2] = {DM * 6, DM * 2};
    cuuint32_t wbox[3] = {64, 32, 3}, wbox8[3] = {8, 32, 3};
    enc(&am.wa, CU_TENSOR_MAP_DATA_TYPE_BFLOAT16, 3, (void*)wqkvA, wdims, wstrides, wbox, es, CU_TENSOR_MAP_INTERLEAVE_NONE,
        CU_TENSOR_MAP_SWIZZLE_128B, CU_TENSOR_MAP_L2_PROMOTION_L2_128B, CU_TENSOR_MAP_FLOAT_OOB_FILL_NONE);
    enc(&am.wa8, CU_TENSOR_MAP_DATA_TYPE_BFLOAT16, 3, (void*)wqkvA, wdims, wstrides, wbox8, es, CU_TENSOR_MAP_INTERLEAVE_NONE,
        CU_TENSOR_MAP_SWIZZLE_NONE, CU_TENSOR_MAP_L2_PROMOTION_NONE, CU_TENSOR_MAP_FLOAT_OOB_FILL_NONE);
  }
  {
    cuuint64_t dims[3] = {64, S_LEN, KCAT / 64}, strides[2] = {KCAT * 2, 128};
    cuuint32_t box[3] = {64, 32, 9}, es[3] = {1, 1, 1};
    make_map(enc, &am.o, pO, S_LEN, KCAT, 32);
    enc(&am.o3, CU_TENSOR_MAP_DATA_TYPE_BFLOAT16, 3, pO, dims, strides, box, es, CU_TENSOR_MAP_INTERLEAVE_NONE,
        CU_TENSOR_MAP_SWIZZLE_128B, CU_TENSOR_MAP_L2_PROMOTION_L2_128B, CU_TENSOR_MAP_FLOAT_OOB_FILL_NONE);
  }
  make_map(enc, &am.wob, Wo, 4096, DM, 64);
  make_map(enc, &am.woa, woA, DM, DM, 64);
  make_map(enc, &am.woa16, woA, DM, DM, 16);
  {
    cuuint64_t dims[2] = {KCAT, S_LEN}, strides[1] = {KCAT * 2};
    cuuint32_t box[2] = {16, 32}, es[2] = {1, 1};
    enc(&am.o16, CU_TENSOR_MAP_DATA_TYPE_BFLOAT16, 2, pO, dims, strides, box, es, CU_TENSOR_MAP_INTERLEAVE_NONE,
        CU_TENSOR_MAP_SWIZZLE_32B, CU_TENSOR_MAP_L2_PROMOTION_NONE, CU_TENSOR_MAP_FLOAT_OOB_FILL_NONE);
  }

  rec_kernel<<<96, 384, SM_TOTAL, cudaStreamPerThread>>>(rm, x, mem0);
  cudaLaunchConfig_t cfg = {};
  cfg.gridDim = dim3(NAUX); cfg.blockDim = dim3(512); cfg.dynamicSmemBytes = A_TOTAL; cfg.stream = cudaStreamPerThread;
  cudaLaunchAttribute at[1];
  at[0].id = cudaLaunchAttributeProgrammaticStreamSerialization; at[0].val.programmaticStreamSerializationAllowed = 1;
  cfg.attrs = at; cfg.numAttrs = 1;
  if (XP & 16) cfg.numAttrs = 0;
  if (!(XP & 64)) cudaLaunchKernelEx(&cfg, aux_kernel, am, x, gate_w, (bf16*)d_out);
}
```

```cpp
#include <cuda_runtime.h>
#include <cuda_bf16.h>
#include <cuda_fp16.h>
#include <cuda.h>
#include <stdint.h>

typedef __nv_bfloat16 bf16;

constexpr int S_LEN = 2048, DM = 576, NH = 32, DH = 128, NSEG = 64, KCAT = 4096 + 576;
#define RED_LINE(i) (((i) >> 2) * 4096 + ((i) & 1) * 256 + ((i) & 2) * 512)
#define RED_SLOT(s) (((s) & 1) * 128 + ((s) & 2) * 256)

#define POLL_NS 896
#define NII 18
#define W3PRE 4
#define W3MID 4
#define GF 0
#define B5POS 0
#define NUP 4
#define UPF 1
#define B3Q 9
#define B3F 0
#define GATE 8
#define NTL 2
#define B7R 1
#define EXPOS 0
#define VW2 1
#define CLR 1
#define RFW 0
#define NIC 0
#define LEAD 0
#define FIN16 1
#define VXG 0
#define RING 63
#define EXB 0
#define EXD 0
#define EXB2 8192
#define HDLY 0
#define F10 1
#define NPROBE 2
#define WPOS 1
#define CW 0
#define WOPF 0
#define YP 0
#define EF 7
#define MO 0
#define WE 3
#define EXV 2
#define NOB 0
#define QM 60
#define N5 224
#define KP(i) (((i) >> 1) + 4 * ((i) & 1))
#define SPIN_LIMIT (1 << 14)
#define XP 0

__device__ __align__(1024) bf16 g_Ocat[S_LEN * KCAT];
__device__ __align__(1024) unsigned char g_red_raw[2 * 262144];
constexpr int HINT_OFF = 2048;
__device__ __align__(16) float g_gate[S_LEN];
__device__ __align__(128) uint4 g_stats[96 * 2];
__device__ unsigned g_epoch;
__device__ unsigned g_epoch2;
__device__ unsigned g_oflag[NH * 32];
__device__ unsigned g_abar[3 * 32];
__device__ unsigned g_sflag[96 * 8];
__device__ __align__(1024) unsigned char g_seg[NSEG * 96 * 8192];
__device__ __align__(1024) unsigned char g_km[NSEG * NH * 4096];
__device__ __align__(1024) uint2 g_part[8 * 9 * 4 * 8 * 128];
__device__ int g_err;
#define SSTAMP(seg, idx)
#define TSTAMP(idx)
#define QSTAMP(idx)
#define PROF(idx)
#define PROFP(idx)
#define STAMP(idx)
#define ASTAMP(idx)
#define WSTAMP(idx)

#define CSTAMP(idx)
#define CDECL
#define CDUMP
#define DI __device__ __forceinline__
DI uint32_t smem_u32(const void* p) { return (uint32_t)__cvta_generic_to_shared(p); }
DI uint32_t clock32() { uint32_t c; asm volatile("mov.u32 %0, %%clock;" : "=r"(c) :: "memory"); return c; }
DI uint32_t gtime() { uint32_t c; asm volatile("mov.u32 %0, %%globaltimer_lo;" : "=r"(c) :: "memory"); return c; }
DI uint32_t ldg_relaxed32(const void* p) { uint32_t v; asm volatile("ld.relaxed.gpu.global.b32 %0, [%1];" : "=r"(v) : "l"(p) : "memory"); return v; }
DI uint32_t ldg_acquire32(const void* p) { uint32_t v; asm volatile("ld.acquire.gpu.global.b32 %0, [%1];" : "=r"(v) : "l"(p) : "memory"); return v; }
DI void stg_relaxed32(void* p, uint32_t v) { asm volatile("st.relaxed.gpu.global.b32 [%0], %1;" :: "l"(p), "r"(v) : "memory"); }
DI int head_id() { int c; asm volatile("mov.u32 %0, %%clusterid.x;" : "=r"(c)); return c; }
DI uint32_t mapa(uint32_t a, uint32_t r) { uint32_t o; asm("mapa.shared::cluster.u32 %0, %1, %2;" : "=r"(o) : "r"(a), "r"(r)); return o; }
DI void cluster_arrive() { asm volatile("barrier.cluster.arrive.relaxed.aligned;" ::: "memory"); }
DI void cluster_wait() { asm volatile("barrier.cluster.wait.aligned;" ::: "memory"); }
DI void cluster_sync() { asm volatile("barrier.cluster.arrive.release.aligned;\nbarrier.cluster.wait.acquire.aligned;" ::: "memory"); }
DI void mbar_init(uint32_t b, uint32_t c) { asm volatile("mbarrier.init.shared::cta.b64 [%0], %1;" :: "r"(b), "r"(c) : "memory"); }
DI void mbar_expect(uint32_t b, uint32_t tx) { asm volatile("mbarrier.arrive.expect_tx.shared::cta.b64 _, [%0], %1;" :: "r"(b), "r"(tx) : "memory"); }
DI void mbar_arrive(uint32_t b) { asm volatile("mbarrier.arrive.shared::cta.b64 _, [%0];" :: "r"(b) : "memory"); }
DI void mbar_wait(uint32_t b, uint32_t par) {
  asm volatile("{\n.reg .pred p;\n.reg .u32 n, q;\nmov.u32 n, 0;\n"
               "WL: add.u32 n, n, 1;\nshr.u32 q, n, 12;\nxor.b32 q, q, %1;\n"
               "mbarrier.try_wait.parity.shared::cta.b64 p, [%0], q;\n@!p bra.uni WL;\n}"
               :: "r"(b), "r"(par) : "memory");
}
DI void wait_until(uint32_t t) {
  const uint32_t now = gtime();
  t = min(t, now + 8192);
  asm volatile("{\n.reg .pred p;\n.reg .u32 c;\nTL: mov.u32 c, %%globaltimer_lo;\nsetp.lt.u32 p, c, %0;\n@p bra.uni TL;\n}" :: "r"(t) : "memory");
}
#define PIN(v) v = __shfl_xor_sync(0xffffffffu, v, 0)
#define SCHED_FENCE(k) asm volatile("{\n.reg .pred p;\nsetp.eq.u32 p, %0, %1;\n@p exit;\n}" :: "r"(fence_reg), "r"(k) : "memory")
#define MEM_ORDER(k) asm volatile("{\n.reg .pred p;\nsetp.eq.u32 p, %0, %1;\n@p st.shared.u32 [%0], %0;\n}" :: "r"(fence_reg), "r"(k + 64) : "memory")
DI void bar_sync(int id, int n) { asm volatile("bar.sync %0, %1;" :: "r"(id), "r"(n) : "memory"); }
DI void bar_arrive(int id, int n) { asm volatile("bar.arrive %0, %1;" :: "r"(id), "r"(n) : "memory"); }
DI void fence_async() { asm volatile("fence.proxy.async.shared::cta;" ::: "memory"); }
DI void st_async4(uint32_t a, uint32_t x, uint32_t y, uint32_t z, uint32_t w, uint32_t mb) {
  asm volatile("st.async.weak.shared::cluster.mbarrier::complete_tx::bytes.v4.b32 [%0], {%1,%2,%3,%4}, [%5];"
               :: "r"(a), "r"(x), "r"(y), "r"(z), "r"(w), "r"(mb) : "memory");
}
DI void st_async2(uint32_t a, uint32_t x, uint32_t y, uint32_t mb) {
  asm volatile("st.async.weak.shared::cluster.mbarrier::complete_tx::bytes.v2.b32 [%0], {%1,%2}, [%3];"
               :: "r"(a), "r"(x), "r"(y), "r"(mb) : "memory");
}
DI void sts32(uint32_t a, uint32_t x) { asm volatile("st.shared.b32 [%0], %1;" :: "r"(a), "r"(x) : "memory"); }
DI void sts64(uint32_t a, uint32_t x, uint32_t y) { asm volatile("st.shared.v2.b32 [%0], {%1,%2};" :: "r"(a), "r"(x), "r"(y) : "memory"); }
DI void sts128(uint32_t a, uint32_t x, uint32_t y, uint32_t z, uint32_t w) {
  asm volatile("st.shared.v4.b32 [%0], {%1,%2,%3,%4};" :: "r"(a), "r"(x), "r"(y), "r"(z), "r"(w) : "memory");
}
DI uint32_t lds32(uint32_t a) { uint32_t x; asm volatile("ld.shared.b32 %0, [%1];" : "=r"(x) : "r"(a) : "memory"); return x; }
DI uint32_t lds32v(uint32_t a) { uint32_t x; asm volatile("ld.volatile.shared.b32 %0, [%1];" : "=r"(x) : "r"(a) : "memory"); return x; }
DI void lds64(uint32_t a, uint32_t& x, uint32_t& y) { asm volatile("ld.shared.v2.b32 {%0,%1}, [%2];" : "=r"(x), "=r"(y) : "r"(a) : "memory"); }
DI void lds128(uint32_t a, uint32_t* r) {
  asm volatile("ld.shared.v4.b32 {%0,%1,%2,%3}, [%4];" : "=r"(r[0]), "=r"(r[1]), "=r"(r[2]), "=r"(r[3]) : "r"(a) : "memory");
}
DI void lds128f(uint32_t a, float* r) {
  asm volatile("ld.shared.v4.f32 {%0,%1,%2,%3}, [%4];" : "=f"(r[0]), "=f"(r[1]), "=f"(r[2]), "=f"(r[3]) : "r"(a) : "memory");
}
DI void lds64f(uint32_t a, float* r) { asm volatile("ld.shared.v2.f32 {%0,%1}, [%2];" : "=f"(r[0]), "=f"(r[1]) : "r"(a) : "memory"); }
DI void ldsm4t(uint32_t* r, uint32_t a) {
  asm volatile("ldmatrix.sync.aligned.m8n8.x4.trans.shared.b16 {%0,%1,%2,%3}, [%4];"
               : "=r"(r[0]), "=r"(r[1]), "=r"(r[2]), "=r"(r[3]) : "r"(a) : "memory");
}
DI void ldsm4t_in(uint32_t* r, uint32_t a, uint32_t t) {
  asm volatile("{\n.reg .pred p;\nsetp.ne.u32 p, %5, 0;\n@p ldmatrix.sync.aligned.m8n8.x4.trans.shared.b16 {%0,%1,%2,%3}, [%4];\n}"
               : "+r"(r[0]), "+r"(r[1]), "+r"(r[2]), "+r"(r[3]) : "r"(a), "r"(t) : "memory");
}
DI void lds128_in(uint32_t* r, uint32_t a, uint32_t t) {
  asm volatile("{\n.reg .pred p;\nsetp.ne.u32 p, %5, 0;\n@p ld.shared.v4.b32 {%0,%1,%2,%3}, [%4];\n}"
               : "+r"(r[0]), "+r"(r[1]), "+r"(r[2]), "+r"(r[3]) : "r"(a), "r"(t) : "memory");
}
DI void ldsm2t_in(uint32_t* r, uint32_t a, uint32_t t) {
  asm volatile("{\n.reg .pred p;\nsetp.ne.u32 p, %3, 0;\n@p ldmatrix.sync.aligned.m8n8.x2.trans.shared.b16 {%0,%1}, [%2];\n}" : "+r"(r[0]), "+r"(r[1]) : "r"(a), "r"(t) : "memory");
}
DI void reserve2(uint32_t* r) { asm volatile("{\n.reg .u64 t;\nmov.u64 t, %%clock64;\nmov.b64 {%0, %1}, t;\n}" : "=r"(r[0]), "=r"(r[1])); }
DI void scale_sum(float& x, float& y, float s, uint32_t t) {
  asm volatile("{\n.reg .pred p;\nsetp.ne.u32 p, %2, 0;\n@p mul.f32 %0, %0, %1;\n}" : "+f"(y) : "f"(s), "r"(t));
  asm volatile("{\n.reg .pred p;\nsetp.ne.u32 p, %3, 1;\n@p fma.rn.f32 %0, %0, %1, %2;\n}" : "+f"(x) : "f"(s), "f"(y), "r"(t));
}
DI void ldsm4(uint32_t* r, uint32_t a) {
  asm volatile("ldmatrix.sync.aligned.m8n8.x4.shared.b16 {%0,%1,%2,%3}, [%4];"
               : "=r"(r[0]), "=r"(r[1]), "=r"(r[2]), "=r"(r[3]) : "r"(a) : "memory");
}
DI void st_async1(uint32_t a, uint32_t x, uint32_t mb) {
  asm volatile("st.async.weak.shared::cluster.mbarrier::complete_tx::bytes.b32 [%0], %1, [%2];" :: "r"(a), "r"(x), "r"(mb) : "memory");
}
DI void stsm4(uint32_t a, uint32_t x, uint32_t y, uint32_t z, uint32_t w) {
  asm volatile("stmatrix.sync.aligned.m8n8.x4.shared.b16 [%0], {%1,%2,%3,%4};" :: "r"(a), "r"(x), "r"(y), "r"(z), "r"(w) : "memory");
}
DI void stsm4t(uint32_t a, uint32_t x, uint32_t y, uint32_t z, uint32_t w) {
  asm volatile("stmatrix.sync.aligned.m8n8.x4.trans.shared.b16 [%0], {%1,%2,%3,%4};" :: "r"(a), "r"(x), "r"(y), "r"(z), "r"(w) : "memory");
}
DI uint32_t pack_bf16(float lo, float hi) { uint32_t r; asm("cvt.rn.bf16x2.f32 %0, %1, %2;" : "=r"(r) : "f"(hi), "f"(lo)); return r; }
DI uint32_t pack_f16(float lo, float hi) { uint32_t r; asm("cvt.rn.f16x2.f32 %0, %1, %2;" : "=r"(r) : "f"(hi), "f"(lo)); return r; }
DI float ex2(float x) { float y; asm("ex2.approx.ftz.f32 %0, %1;" : "=f"(y) : "f"(x)); return y; }
DI float rcp(float x) { float y; asm("rcp.approx.ftz.f32 %0, %1;" : "=f"(y) : "f"(x)); return y; }
DI float bf_lo(uint32_t x) { return __uint_as_float(x << 16); }
DI float bf_hi(uint32_t x) { return __uint_as_float(x & 0xffff0000u); }
DI void mma16816(float* d, const uint32_t* a, uint32_t b0, uint32_t b1) {
  asm volatile("mma.sync.aligned.m16n8k16.row.col.f32.bf16.bf16.f32 {%0,%1,%2,%3}, {%4,%5,%6,%7}, {%8,%9}, {%0,%1,%2,%3};"
               : "+f"(d[0]), "+f"(d[1]), "+f"(d[2]), "+f"(d[3]) : "r"(a[0]), "r"(a[1]), "r"(a[2]), "r"(a[3]), "r"(b0), "r"(b1));
}
DI void mma16816z(float* d, const uint32_t* a, uint32_t b0, uint32_t b1) {
  asm volatile("mma.sync.aligned.m16n8k16.row.col.f32.bf16.bf16.f32 {%0,%1,%2,%3}, {%4,%5,%6,%7}, {%8,%9}, {%10,%10,%10,%10};"
               : "=f"(d[0]), "=f"(d[1]), "=f"(d[2]), "=f"(d[3]) : "r"(a[0]), "r"(a[1]), "r"(a[2]), "r"(a[3]), "r"(b0), "r"(b1), "f"(0.f));
}
DI void mma1688z(float* d, uint32_t a0, uint32_t a1, uint32_t b0) {
  asm volatile("mma.sync.aligned.m16n8k8.row.col.f32.bf16.bf16.f32 {%0,%1,%2,%3}, {%4,%5}, {%6}, {%7,%7,%7,%7};"
               : "=f"(d[0]), "=f"(d[1]), "=f"(d[2]), "=f"(d[3]) : "r"(a0), "r"(a1), "r"(b0), "f"(0.f));
}
DI void mma1688(float* d, uint32_t a0, uint32_t a1, uint32_t b0) {
  asm volatile("mma.sync.aligned.m16n8k8.row.col.f32.bf16.bf16.f32 {%0,%1,%2,%3}, {%4,%5}, {%6}, {%0,%1,%2,%3};"
               : "+f"(d[0]), "+f"(d[1]), "+f"(d[2]), "+f"(d[3]) : "r"(a0), "r"(a1), "r"(b0));
}
DI void ldsm2t(uint32_t* r, uint32_t a) {
  asm volatile("ldmatrix.sync.aligned.m8n8.x2.trans.shared.b16 {%0,%1}, [%2];" : "=r"(r[0]), "=r"(r[1]) : "r"(a) : "memory");
}
DI uint32_t add_bf16(uint32_t a, uint32_t b) { uint32_t r; asm("add.rn.bf16x2 %0, %1, %2;" : "=r"(r) : "r"(a), "r"(b)); return r; }
DI uint32_t mul_bf16(uint32_t a, uint32_t b) { uint32_t r; asm("mul.rn.bf16x2 %0, %1, %2;" : "=r"(r) : "r"(a), "r"(b)); return r; }
DI uint64_t make_desc(uint32_t addr, uint32_t lbo, uint32_t sbo, uint32_t swz) {
  return (uint64_t)((addr & 0x3FFFF) >> 4) | ((uint64_t)(lbo >> 4) << 16) | ((uint64_t)(sbo >> 4) << 32) | ((uint64_t)swz << 62);
}
#define WG_FENCE() asm volatile("wgmma.fence.sync.aligned;" ::: "memory")
#define WG_COMMIT() asm volatile("wgmma.commit_group.sync.aligned;" ::: "memory")
#define WG_WAIT(n) asm volatile("wgmma.wait_group.sync.aligned %0;" :: "n"(n) : "memory")
#define ACC8(d, o) "+f"(d[o]), "+f"(d[o + 1]), "+f"(d[o + 2]), "+f"(d[o + 3]), "+f"(d[o + 4]), "+f"(d[o + 5]), "+f"(d[o + 6]), "+f"(d[o + 7])
DI void wgmma_n32_rs(float* d, uint32_t a0, uint32_t a1, uint32_t a2, uint32_t a3, uint64_t db, int acc) {
  asm volatile("{\n.reg .pred p;\nsetp.ne.b32 p, %21, 0;\n"
               "wgmma.mma_async.sync.aligned.m64n32k16.f32.bf16.bf16 {%0,%1,%2,%3,%4,%5,%6,%7,%8,%9,%10,%11,%12,%13,%14,%15}, "
               "{%16,%17,%18,%19}, %20, p, 1, 1, 0;\n}\n"
               : ACC8(d, 0), ACC8(d, 8) : "r"(a0), "r"(a1), "r"(a2), "r"(a3), "l"(db), "r"(acc));
}
template <int TA>
DI void wgmma_n32_ss(float* d, uint64_t da, uint64_t db, int acc) {
  asm volatile("{\n.reg .pred p;\nsetp.ne.b32 p, %18, 0;\n"
               "wgmma.mma_async.sync.aligned.m64n32k16.f32.bf16.bf16 {%0,%1,%2,%3,%4,%5,%6,%7,%8,%9,%10,%11,%12,%13,%14,%15}, "
               "%16, %17, p, 1, 1, %19, 1;\n}\n"
               : ACC8(d, 0), ACC8(d, 8) : "l"(da), "l"(db), "r"(acc), "n"(TA));
}
DI void tma_load(uint32_t dst, const CUtensorMap* m, int c0, int c1, uint32_t mb) {
  asm volatile("cp.async.bulk.tensor.2d.shared::cluster.global.mbarrier::complete_tx::bytes [%0], [%1, {%3, %4}], [%2];"
               :: "r"(dst), "l"(m), "r"(mb), "r"(c0), "r"(c1) : "memory");
}
DI void tma_load3(uint32_t dst, const CUtensorMap* m, int row, uint32_t mb) {
  asm volatile("cp.async.bulk.tensor.3d.shared::cluster.global.mbarrier::complete_tx::bytes [%0], [%1, {%3, %4, %3}], [%2];"
               :: "r"(dst), "l"(m), "r"(mb), "r"(0), "r"(row) : "memory");
}
DI bool elect_one() {
  uint32_t p;
  asm volatile("{\n.reg .pred p;\nelect.sync _|p, 0xffffffff;\nselp.u32 %0, 1, 0, p;\n}" : "=r"(p));
  return p;
}
DI void bulk_s2s(uint32_t dst, uint32_t src, uint32_t bytes, uint32_t mb) {
  asm volatile("cp.async.bulk.shared::cluster.shared::cta.mbarrier::complete_tx::bytes [%0], [%1], %2, [%3];"
               :: "r"(dst), "r"(src), "r"(bytes), "r"(mb) : "memory");
}
DI void bulk_load(uint32_t dst, const void* src, uint32_t bytes, uint32_t mb) {
  asm volatile("cp.async.bulk.shared::cluster.global.mbarrier::complete_tx::bytes [%0], [%1], %2, [%3];" :: "r"(dst), "l"(src), "r"(bytes), "r"(mb) : "memory");
}
#define EVICT_FIRST ".reg .b64 pol;\ncreatepolicy.fractional.L2::evict_first.b64 pol, 1.0;\n"
DI void bulk_load_ef(uint32_t dst, const void* src, uint32_t bytes, uint32_t mb) {
  asm volatile("{\n" EVICT_FIRST "cp.async.bulk.shared::cluster.global.mbarrier::complete_tx::bytes.L2::cache_hint [%0], [%1], %2, [%3], pol;\n}"
               :: "r"(dst), "l"(src), "r"(bytes), "r"(mb) : "memory");
}
DI void tma_load_ef(uint32_t dst, const CUtensorMap* m, int c0, int c1, uint32_t mb) {
  asm volatile("{\n" EVICT_FIRST "cp.async.bulk.tensor.2d.shared::cluster.global.mbarrier::complete_tx::bytes.L2::cache_hint [%0], [%1, {%3, %4}], [%2], pol;\n}"
               :: "r"(dst), "l"(m), "r"(mb), "r"(c0), "r"(c1) : "memory");
}
DI void tma_prefetch(const CUtensorMap* m, int c0, int c1) {
  asm volatile("cp.async.bulk.prefetch.tensor.2d.L2.global.tile [%0, {%1, %2}];" :: "l"(m), "r"(c0), "r"(c1) : "memory");
}
DI void tma_store(const CUtensorMap* m, uint32_t src, int c0, int c1) {
  asm volatile("cp.async.bulk.tensor.2d.global.shared::cta.bulk_group [%0, {%2, %3}], [%1];" :: "l"(m), "r"(src), "r"(c0), "r"(c1) : "memory");
}
DI uint4 ldg_relaxed(const void* p) {
  uint4 v;
  asm volatile("ld.relaxed.gpu.global.v4.b32 {%0,%1,%2,%3}, [%4];" : "=r"(v.x), "=r"(v.y), "=r"(v.z), "=r"(v.w) : "l"(p) : "memory");
  return v;
}
DI void stg_relaxed(void* p, uint32_t x, uint32_t y, uint32_t z, uint32_t w) {
  asm volatile("st.relaxed.gpu.global.v4.b32 [%0], {%1,%2,%3,%4};" :: "l"(p), "r"(x), "r"(y), "r"(z), "r"(w) : "memory");
}
DI void red_f16x8(void* p, uint32_t x, uint32_t y, uint32_t z, uint32_t w) {
  asm volatile("red.relaxed.gpu.global.add.noftz.v4.f16x2 [%0], {%1,%2,%3,%4};" :: "l"(p), "r"(x), "r"(y), "r"(z), "r"(w) : "memory");
}
DI void sq_acc(uint32_t& a, uint32_t x) { asm("fma.rn.bf16x2 %0, %1, %1, %0;" : "+r"(a) : "r"(x)); }
DI __half2 amax4(__half2 h, const uint32_t* v) {
  h = __hmax2_nan(__hmax2_nan(h, __habs2(*(const __half2*)&v[0])), __habs2(*(const __half2*)&v[1]));
  return __hmax2_nan(__hmax2_nan(h, __habs2(*(const __half2*)&v[2])), __habs2(*(const __half2*)&v[3]));
}
DI uint32_t wexp(__half2 h) { const uint32_t u = *(const uint32_t*)&h; return __reduce_max_sync(0xffffffffu, max((u >> 16) & 0x7fffu, u & 0x7fffu)) >> 7; }
DI float max10(const float* a) {
  return fmaxf(fmaxf(fmaxf(fmaxf(a[0], a[1]), fmaxf(a[2], a[3])), fmaxf(fmaxf(a[4], a[5]), fmaxf(a[6], a[7]))), fmaxf(a[8], a[9]));
}
DI float quad_max(float m) {
  return fmaxf(fmaxf(m, __shfl_xor_sync(0xffffffffu, m, 1)), fmaxf(__shfl_xor_sync(0xffffffffu, m, 2), __shfl_xor_sync(0xffffffffu, m, 3)));
}
DI float warp_sum(float v) {
#pragma unroll
  for (int o = 16; o; o >>= 1) v += __shfl_xor_sync(0xffffffffu, v, o);
  return v;
}

constexpr int SM_WO3 = 0;
constexpr int SM_X = 16384;
constexpr int XT = 36864;
constexpr int SM_EXP = 126976;
constexpr int SEGB = 10240;
constexpr int SM_BLK = SM_EXP + 8192;
constexpr int SM_VC = SM_BLK + 4 * SEGB;
constexpr int SM_PART = SM_VC + 16384;
constexpr int SM_QM = SM_PART + 4096;
constexpr int SM_E = SM_QM + 1024;
constexpr int SM_VM = SM_E + 1536;
constexpr int SM_OB = SM_VM + 2048;
constexpr int SM_FB = SM_OB + 2048;
constexpr int SM_STAGE = SM_X + XT;
constexpr int SM_M0 = SM_STAGE + 3 * 49152;
constexpr int SM_MISC = 210944;
constexpr int SM_WOST = 212992;
constexpr int SM_MEM = SM_WOST;
constexpr int SM_MAX = SM_MEM + 11264;
#define MEM_BLK(q) ((q) / 3 * 4096 + (q) % 3 * 1024)
constexpr int SM_TOTAL = 229376;
constexpr int MB_W = SM_MISC;
constexpr int MB_WO = SM_MISC + 24;
constexpr int MB_WO3 = SM_MISC + 32;
constexpr int MB_X = SM_MISC + 40;
constexpr int MB_S = SM_MISC + 64;
constexpr int MB_F = SM_MISC + 72;
constexpr int MB_VX = SM_MISC + 80;
constexpr int SC_FPAR = SM_MISC + 136;
constexpr int SC_DEAD = SM_MISC + 96;
constexpr int SC_UNSC = SM_MISC + 112;
constexpr int SC_EXPW = SM_MISC + 132;
constexpr int SC_ONES = SM_MISC + 144;
constexpr int SC_SS = SM_MISC + 160;
constexpr int SC_LAT = SM_MISC + 224;
constexpr int SC_EPO = SM_MISC + 240;
constexpr int MB_XS = SM_MISC + 248;
constexpr int SC_XMAX = SM_MISC + 256;
constexpr int SC_PROF = 229376;

constexpr float SM_SCALE = 0.08838834764831845f;
constexpr float LOG2E = 1.4426950408889634f;
constexpr float E_LIM = 20.f;

template <bool B> struct BoolC { static constexpr bool value = B; };
template <int I> struct IntC { static constexpr int value = I; };
struct RMaps { CUtensorMap x, wq, wk, wv, wo; unsigned char* red; uint32_t poll; const unsigned char* w[4]; };

DI uint32_t latest_hint(uint32_t h, uint32_t d, int s) {
  const uint32_t x = (((h | 0xc0c0c0c0u) - ((d >> 5) & 63) * 0x01010101u) & 0x3f3f3f3fu) | ((h ^ (((s >> 2) + 1) & 3) * 0x40404040u) & 0xc0c0c0c0u);
  const uint32_t y = __vmaxu2(x & 0x00ff00ffu, (x >> 8) & 0x00ff00ffu);
  return __reduce_max_sync(0xffffffffu, max(y & 0xffffu, y >> 16));
}
DI uint32_t near_half(uint32_t sb) {
  uint32_t a, b; lds64(sb + SC_LAT, a, b);
  return a > b;
}

template <int RT, int K0, int K1, bool D32 = false>
DI void xproj(float* acc, const uint32_t (&wa)[2][18][4], uint64_t xd) {
  if (XP & 1) return;
  WG_FENCE();
#pragma unroll
  for (int k = K0; k < ((XP & 128) ? K0 + 1 : K1); k++)
  {
    uint64_t d = xd + (uint64_t)(((k >> 1) * 4096 + (k & 1) * 32) >> 4);
    if (D32) asm("mov.b64 %0, {%1, %2};" : "=l"(d) : "r"((uint32_t)xd + (((k >> 1) * 4096 + (k & 1) * 32) >> 4)), "r"((uint32_t)(xd >> 32)));
    wgmma_n32_rs(acc, wa[RT][k][0], wa[RT][k][1], wa[RT][k][2], wa[RT][k][3], d, k != 0);
  }
  WG_COMMIT();
}

DI void load_w(uint32_t sb, const RMaps& tm, uint32_t rank, int c) {
  const int h = blockIdx.x / 3;
  mbar_expect(sb + MB_W + 8 * c, 49152);
  ((EF & 4) ? tma_load_ef : tma_load)(sb + SM_STAGE + c * 49152, rank < 2 ? &tm.wk : &tm.wv, h * DH + (rank == 1 ? 64 : 0), c * 192, sb + MB_W + 8 * c);
  ((EF & 4) ? tma_load_ef : tma_load)(sb + SM_STAGE + c * 49152 + 24576, rank < 2 ? &tm.wq : &tm.wv, h * DH + (rank == 0 ? 0 : 64), c * 192, sb + MB_W + 8 * c);
}
DI void seg_store(int seg, uint32_t sb) {
  fence_async();
  if (EF & 1)
    asm volatile("{\n" EVICT_FIRST "cp.async.bulk.global.shared::cta.bulk_group.L2::cache_hint [%0], [%1], 8192, pol;\n}"
                 :: "l"(g_seg + ((size_t)(seg & RING) * 96 + blockIdx.x) * 8192), "r"(sb + SM_BLK + (seg & 3) * SEGB) : "memory");
  else
  asm volatile("cp.async.bulk.global.shared::cta.bulk_group [%0], [%1], 8192;"
               :: "l"(g_seg + ((size_t)(seg & RING) * 96 + blockIdx.x) * 8192), "r"(sb + SM_BLK + (seg & 3) * SEGB) : "memory");
  asm volatile("cp.async.bulk.commit_group;" ::: "memory");
}
DI void seg_publish(int seg, uint32_t sb) {
  const uint32_t v = lds32(sb + SC_EPO) + seg;
  asm volatile("cp.async.bulk.wait_group 0;" ::: "memory");
  stg_relaxed32(&g_sflag[blockIdx.x * 8], v);
}

DI void proj_role(const uint32_t sb, const RMaps& tm, const bf16* __restrict__ x, const uint32_t rank, const int wg, const int w, const int lane) {
  const bool qk = rank < 2;
  uint32_t wa[2][18][4];
  float acc[16];
  const uint64_t xd0 = make_desc(sb + SM_X + wg * 64, 16, 1024, 1);
  {
    const int rr = (lane & 7) + ((lane >> 4) << 3);
    const uint32_t col = ((2 * w + ((lane >> 3) & 1)) ^ (lane & 7)) << 4;
    float ss = 0.f;
    bar_sync(3, 256);
    mbar_wait(sb + MB_X, 0);
    auto chunk = [&](auto cc) {
      constexpr int c = decltype(cc)::value;
      QSTAMP(2 + 2 * c);
      mbar_wait(sb + MB_W + 8 * c, 0);
      QSTAMP(3 + 2 * c);
#pragma unroll
      for (int rt = 1; rt >= 0; rt--)
#pragma unroll
        for (int k = 0; k < 6; k++)
          ldsm4t(wa[rt][c * 6 + k], sb + SM_STAGE + c * 49152 + (rt ^ wg) * 24576 + (64 * (k >> 1) + 32 * wg + 16 * (k & 1) + rr) * 128 + col);
      fence_async();
      if (c < 2) {
        bar_sync(3, 256);
        QSTAMP(17 + c);
        if (threadIdx.x == 0) {
          if (c == 0) tma_load(sb + SM_X + XT, &tm.wo, rank * 192, (blockIdx.x / 3) * DH, sb + MB_WO);
          else if (blockIdx.x < NSEG) bulk_load(sb + SM_X + 2 * XT, x + blockIdx.x * 32 * DM, XT, sb + MB_XS);
          else tma_load3(sb + SM_X + 2 * XT, &tm.x, 64, sb + MB_X + 16);
        }
        __syncwarp();
      } else {
        cluster_arrive();
      }
      xproj<1, 6 * c, 6 * c + 6>(acc, wa, xd0);
      if (!qk) {
        uint32_t q[4] = {0, 0, 0, 0};
#pragma unroll
        for (int rt = 0; rt < 2; rt++)
#pragma unroll
          for (int k = 0; k < 6; k++)
#pragma unroll
            for (int i = 0; i < 4; i++) sq_acc(q[i], wa[rt][c * 6 + k][i]);
#pragma unroll
        for (int i = 0; i < 4; i++) ss += bf_lo(q[i]) + bf_hi(q[i]);
      }
      if (c < 2 && CW) WG_WAIT(0);
    };
    chunk(IntC<0>()); chunk(IntC<1>()); chunk(IntC<2>());
    ss = warp_sum(ss);
    if (lane == 0) sts32(sb + SC_SS + 4 * (wg * 4 + w), __float_as_uint(ss));
    bar_arrive(11, 384);
  }
  STAMP(1);
  QSTAMP(8);
  STAMP(2);

  uint32_t t16 = sb + (w * 32 + lane) * 16;
  uint32_t mem_a = sb + SM_MEM + wg * 512 + lane * 16;
  uint32_t fin_a = sb + (lane & 7) * 16 + SM_BLK + (qk ? (wg ^ 1) * 4096 + w * 256 + (lane & 8) * 16 + (lane & 16) * 64
                                              : wg * 4096 + w * 1024 + (lane & 8) * 64 + (lane & 16) * 8);
  PIN(t16); PIN(mem_a); PIN(fin_a);
  const uint32_t fence_reg = mem_a;
  const uint32_t fin2 = qk ? 2048 : 256;
  auto do_export = [&](auto retire, uint32_t always) {
    WG_WAIT(0);
    uint32_t p[2];
#pragma unroll
    for (int i = 0; i < 2; i++) {
      p[i] = pack_bf16(acc[8 * i], acc[8 * i + 1]);
      sts128(t16 + SM_EXP + wg * 4096 + i * 2048, p[i], pack_bf16(acc[8 * i + 2], acc[8 * i + 3]),
             pack_bf16(acc[8 * i + 4], acc[8 * i + 5]), pack_bf16(acc[8 * i + 6], acc[8 * i + 7]));
    }
    if (decltype(retire)::value)
      asm volatile("{\n.reg .pred p, q;\nsetp.ne.u32 p, %2, 0;\nsetp.ne.u32 q, %2, 1;\n@p ld.shared.b32 %0, [%3];\n@q ld.shared.b32 %1, [%3 + 4];\n"
                   "setp.ne.u32 p, %0, %1;\n@p exit;\n}" : "+r"(p[0]), "+r"(p[1]) : "r"(always), "r"(sb + SC_DEAD) : "memory");
  };
  uint32_t o[8];
  auto import = [&]() { lds128(t16 + SM_EXP + (wg ^ 1) * 4096, o); lds128(t16 + SM_EXP + (wg ^ 1) * 4096 + 2048, o + 4); };
  auto finish_from = [&](int seg, const float* d) {
    const uint32_t a = fin_a + (seg & 3) * SEGB;
#pragma unroll
    for (int i = 0; i < 8; i++) o[i] = add_bf16(pack_bf16(d[2 * i], d[2 * i + 1]), o[i]);
    stsm4(a, o[0], o[1], o[2], o[3]);
    stsm4(a + fin2, o[4], o[5], o[6], o[7]);
  };
  auto finish = [&](int seg) { WG_WAIT(0); finish_from(seg, acc); };
  auto send_v = [&](int seg, int dst) {
    fence_async();
    if (seg < NSEG - 1 && !(XP & 2) && elect_one())
      bulk_s2s(mapa(sb + SM_VC + (seg & 1) * 8192, dst), sb + SM_BLK + (seg & 3) * SEGB, 8192, mapa(sb + MB_VX + (seg & 1) * 8, dst));
    __syncwarp();
  };
  auto wait_v = [&](int seg) {
    if (seg < NSEG - 1 && !(XP & 2)) {
      mbar_wait(sb + MB_VX + (seg & 1) * 8, (seg >> 1) & 1);
      if (elect_one()) mbar_expect(sb + MB_VX + (seg & 1) * 8, 8192);
      __syncwarp();
    }
  };
  auto export_seg = [&](int seg) { if (!(XP & (4 | 8192)) && elect_one()) seg_store(seg, sb); __syncwarp(); };
  auto publish = [&](int seg) { if (!(XP & (4 | 16384)) && elect_one()) seg_publish(seg, sb); __syncwarp(); };
  do_export(BoolC<false>(), 0);
  QSTAMP(9);
  SCHED_FENCE(11);
  xproj<0, 0, 18>(acc, wa, xd0);
  bar_sync(3, 256);
  QSTAMP(10);
  cluster_wait();
  QSTAMP(11);
  mbar_wait(sb + MB_X + 8, 0);
  QSTAMP(12);
  import();
  finish(0);
  SCHED_FENCE(12);
  uint64_t dA = xd0 + (XT >> 4);
  xproj<1, 0, 18>(acc, wa, dA);
  bar_sync(3, 256);
  if (!qk && wg == 0 && w < 2) send_v(0, w);
  if (!(EXV & 1) && wg == 0 && w == 3) export_seg(0);
  QSTAMP(13);
  if (qk && wg == 0 && w == 0) wait_v(0);
  QSTAMP(14);
  bar_arrive(13, 384);
  if (!qk) {
    do_export(BoolC<false>(), 0);
    SCHED_FENCE(15);
    xproj<0, 0, 18>(acc, wa, dA);
    if (threadIdx.x == 0 && !(XP & 8)) { mbar_expect(sb + MB_X, XT); tma_load3(sb + SM_X, &tm.x, 96, sb + MB_X); }
    bar_sync(3, 256);
    mbar_wait(sb + MB_X + 16, 0);
    import();
    finish(1);
    SCHED_FENCE(16);
    dA += XT >> 4;
    xproj<1, 0, 18>(acc, wa, dA);
    if (!(EXV & 2)) bar_sync(3, 256);
    if (!(EXV & 2) && wg == 0 && w < VW2) send_v(1, w);
  }
  QSTAMP(15);
  WG_WAIT(0);
  bar_sync(0, 384);
  if (!(EXV & 1) && wg == 0 && w == 3) publish(0);
  QSTAMP(16);
  const int ro = __shfl_sync(0xffffffffu, near_half(sb) ^ wg, 0);
  STAMP(5);
  const uint32_t always = __shfl_sync(0xffffffffu, lds32(sb + SC_DEAD + 12), 0);
  const int ah = qk ? 1 : 2;
  int b2 = qk ? 2 : 0;
  int s = 0;
  uint32_t hint_lo = (uint32_t)(uint64_t)tm.red + HINT_OFF + blockIdx.x + (lane & 1) * 4096 + (lane >> 1) * 16384;
  PIN(hint_lo);
  auto post_hint = [&]() {
    asm volatile("{\n.reg .pred p;\n.reg .b64 a;\n.reg .u32 t;\nsetp.lt.u32 p, %0, %1;\nmov.b64 a, {%2, %3};\nmov.u32 t, %%globaltimer_lo;\n"
                 "bfe.u32 t, t, 5, 6;\nor.b32 t, t, %4;\n@p st.relaxed.gpu.global.u8 [a], t;\n}"
                 :: "r"(t16), "r"(sb + 160), "r"(hint_lo + RED_SLOT(s)), "r"((uint32_t)((uint64_t)tm.red >> 32)), "r"(((s >> 2) + 1) << 6) : "memory");
  };
  auto memproj = [&](auto second, int id, uint32_t dep, float u0, float u1, float* r) {
    constexpr bool R1 = decltype(second)::value;
    uint32_t b[NUP][4], b0[4];
    if (R1) asm volatile("{\n.reg .pred p;\nsetp.eq.u32 p, %0, %1;\n@p exit;\n}" :: "r"(dep), "r"(id) : "memory");
    bar_sync(R1 ? 2 : 1, 256);
    PROF(0);
    ldsm4t(b0, mem_a);
#pragma unroll
    for (int q = 0; q < NUP; q++) {
      if (R1 && q == 2) {
        bar_sync(11, 256);
        SCHED_FENCE(id + 1);
      }
      ldsm4t(b[q], mem_a + MEM_BLK(q + 1));
    }
    mma16816z(&acc[0], wa[0][0], b0[0], b0[1]);
    mma16816z(&acc[4], wa[1][0], b0[0], b0[1]);
    mma16816z(&acc[8], wa[0][1], b0[2], b0[3]);
    mma16816z(&acc[12], wa[1][1], b0[2], b0[3]);
#pragma unroll
    for (int q = 1; q < 9; q++) {
      uint32_t* const c = b[(q - 1) % NUP];
      mma16816(&acc[0], wa[0][2 * q], c[0], c[1]);
      mma16816(&acc[4], wa[1][2 * q], c[0], c[1]);
      mma16816(&acc[8], wa[0][2 * q + 1], c[2], c[3]);
      mma16816(&acc[12], wa[1][2 * q + 1], c[2], c[3]);
      if (R1 && q + NUP == B3Q) bar_sync(3, 256);
      if (q + NUP < 9) ldsm4t_in(c, mem_a + MEM_BLK(q + NUP), always);
      else if (R1 && q + NUP < 11) lds128_in(c, t16 + SM_PART + (10 - q - NUP) * 2048, always);
      else if (!R1 && GATE && q == GATE) { bar_arrive(11, 256); lds128_in(c, sb + SC_DEAD, always); u0 = u1 = __uint_as_float(c[3]); }
    }
#pragma unroll
    for (int i = 0; i < 8; i++) {
      const float u = i < 4 ? u0 : u1;
      r[i] = R1 ? fmaf(acc[8 + i], u, (acc[i] + __uint_as_float(b[(8 + i / 4) % NUP][i & 3])) * u) : (GATE ? fmaf(acc[i], u, acc[8 + i]) : acc[i] + acc[8 + i]);
    }
  };
  if (ro == 0) {
#pragma unroll 1
    while (true) {
      do_export(BoolC<true>(), always);
      PROFP(3);
      if (s == 8) STAMP(6);
      float r[8];
      memproj(BoolC<false>(), 30, 0, 0.f, 0.f, r);
      sts128(t16 + SM_PART, __float_as_uint(r[0]), __float_as_uint(r[1]), __float_as_uint(r[2]), __float_as_uint(r[3]));
      sts128(t16 + SM_PART + 2048, __float_as_uint(r[4]), __float_as_uint(r[5]), __float_as_uint(r[6]), __float_as_uint(r[7]));
      bar_arrive(3, 256);
      PROF(1);
      bar_sync(9, 256);
      if (!(WE & 1) && s == NSEG - 1) break;
      post_hint();
      if (!(EXV & 1) && w == 3 && s) publish(s);
      if ((WE & 1) && s == NSEG - 1) break;
      if (w == 1) {
        uint32_t m[8];
        lds128(t16 + SM_MAX - 512, m); lds128(t16 + SM_MAX, m + 4);
        const int em = (wexp(amax4(amax4(*(const __half2*)&m[0], m), m + 4)) >> 3) + (int)(lds32(sb + SC_UNSC + (s & 1) * 8) >> 23) - 15;
        const int ex = max(s ? em : 0, (int)lds32(sb + SC_XMAX + 4 * s)) - 127 + (int)lds32(sb + SC_EXPW);
        sts32(sb + SC_UNSC + (~s & 1) * 8, (127 + min(max(ex, -120), 120)) << 23);
        __syncwarp();
        if (elect_one()) mbar_arrive(sb + MB_S);
      }
      SCHED_FENCE(9);
      bar_sync(5, qk ? N5 : 256);
      PROF(2);
      import();
      xproj<0, 0, NII>(acc, wa, dA);
      if (NII < 18) {
        if (qk) bar_sync(7, 384);
        xproj<0, NII, 18>(acc, wa, dA);
        if (!qk) bar_sync(7, 384);
      } else {
        if (F10) WG_WAIT(0);
        bar_sync(10, 256);
        if (F10) SCHED_FENCE(17);
      }
      dA += (int64_t)(b2 ? XT >> 4 : -(XT >> 3));
      finish(s + ah);
      if (((EXV & 1) || w != 3) && ((EXV & 2) || qk || w >= VW2)) bar_arrive(13, 384);
      PROF(6);
      SCHED_FENCE(14);
      if (NOB & 2) bar_arrive(14, 256);
      bar_sync(12, 256);
      PROF(7);
      xproj<1, 0, 18, true>(acc, wa, dA);
      if (!(NOB & 2)) bar_arrive(14, 256);
      b2 = b2 == 2 ? 0 : b2 + 1;
      s++;
      if ((!(EXV & 1) && w == 3) || (!(EXV & 2) && !qk && w < VW2)) {
        bar_sync(13, 384);
        if (!(EXV & 1) && w == 3) export_seg(s); else send_v(s + 1, w);
      }
      PROFP(8);
    }
    if (!qk) bar_arrive(5, 256);
    if (!(WE & 1) && w == 3) publish(NSEG - 1);
  } else {
    uint32_t km[4];
    auto send_km = [&]() {
      if (XP & (4 | 4096)) return;
      const uint32_t t = (km[0] & ~1u) | lds32(sb + SC_EPO + 4), u = (s * NH + head_id()) * 4096;
      if (qk)
        asm volatile("{\n.reg .u32 o;\n.reg .u64 a;\nshr.u32 o, %0, 1;\nadd.u32 o, o, %1;\nmad.wide.u32 a, o, 1, %2;\nst.relaxed.gpu.global.v2.b32 [a], {%3,%4};\n}"
                     :: "r"(t16), "r"(u + rank * 1024 - (sb >> 1)), "l"(g_km), "r"(t), "r"(km[1]) : "memory");
      else
        asm volatile("{\n.reg .u32 o;\n.reg .u64 a;\nadd.u32 o, %0, %1;\nmad.wide.u32 a, o, 1, %2;\nst.relaxed.gpu.global.v4.b32 [a], {%3,%4,%5,%6};\n}"
                     :: "r"(t16), "r"(u + 2048 - sb), "l"(g_km), "r"(t), "r"(km[1]), "r"(km[2]), "r"(km[3]) : "memory");
    };
#pragma unroll 1
    while (true) {
      do_export(BoolC<true>(), always);
      if ((EXV & 1) && w == 1) export_seg(s);
      if ((EXV & 2) && !qk && w == 2) send_v(s + 1, 0);
      PROFP(3);
      if (s == 8) STAMP(6);
      const uint32_t tl = ((t16 >> 8) ^ wg) & 1, am = (t16 & ~256u) - w * 256;
      const float un = __uint_as_float(lds32(sb + SC_UNSC + (s & 1) * 8));
      float r[8];
      if (qk) {
        uint32_t a0 = am + (tl ? SM_QM : SM_BLK + 8192 + (s & 3) * SEGB);
        float u0 = wg ? un * (SM_SCALE * LOG2E) : un, u1 = wg ? un : un * (SM_SCALE * LOG2E);
        PIN(a0); PIN(u0); PIN(u1);
        memproj(BoolC<true>(), 32, a0, u0, u1, r);
        const uint32_t p0 = pack_bf16(r[0], r[1]), p1 = pack_bf16(r[2], r[3]), p2 = pack_bf16(r[4], r[5]), p3 = pack_bf16(r[6], r[7]);
        stsm4(a0, p0, p1, p2, p3);
        bar_arrive(4, 256);
        km[0] = wg ? p2 : p0; km[1] = wg ? p3 : p1;
      } else {
        const uint32_t d0 = s < NSEG - 1 ? 0 : 2, d1 = s < NSEG - 1 ? 1 : 2;
        uint32_t r0 = mapa(t16 + SM_VM, d0), r1 = mapa(t16 + SM_VM, d1);
        PIN(r0); PIN(r1);
        memproj(BoolC<true>(), 34, r0 | r1, un, un, r);
        const uint32_t p0 = pack_bf16(r[0], r[1]), p1 = pack_bf16(r[2], r[3]), p2 = pack_bf16(r[4], r[5]), p3 = pack_bf16(r[6], r[7]);
        const uint32_t v0 = wg ? p2 : p0, v1 = wg ? p3 : p1, v2 = wg ? p0 : p2, v3 = wg ? p1 : p3;
        st_async4(r0, v0, v1, v2, v3, mapa(sb + MB_S, d0));
        st_async4(r1, v0, v1, v2, v3, mapa(sb + MB_S, d1));
        bar_arrive(5, 256);
        sts128(t16 + SM_VM, v0, v1, v2, v3);
        __syncwarp();
        if (elect_one()) mbar_arrive(sb + MB_S);
        km[0] = v0; km[1] = v1; km[2] = v2; km[3] = v3;
      }
      if (!(WE & 2) && s == NSEG - 1) break;
      PROF(1);
      auto rearm = [&]() { mbar_wait(sb + MB_S, s & 1); if (elect_one()) mbar_expect(sb + MB_S, qk ? 640 + 2048 : 1280); __syncwarp(); };
      if ((WE & 2) && s == NSEG - 1 && w != 1) {
      } else if (w == 1) {
        if ((t16 & 384) == 0) stg_relaxed(tm.red + (RED_SLOT(s + 2) + RED_LINE(blockIdx.x)) + (t16 & 112), 0, 0, 0, 0);
        if (EXV & 1) publish(s);
      } else if (w == 0) {
        const int tn = s + ah + 1;
        if (RFW) mbar_wait(sb + MB_S, s & 1);
        if (tn + 1 < NSEG && !(XP & 8) && elect_one()) {
          const int b0 = b2 == 2 ? 0 : b2 + 1;
          mbar_expect(sb + MB_X + 8 * b0, XT);
          tma_load3(sb + SM_X + b0 * XT, &tm.x, (tn + 1) * 32, sb + MB_X + 8 * b0);
        }
        if (tn < NSEG && (!(XP & 8) || tn < 3)) mbar_wait(sb + MB_X + 8 * b2, (tn / 3) & 1);
      } else if (w == 2) {
        if (!qk) { if (VW2 < 1) send_v(s + 1, 0); if (VW2 < 2) send_v(s + 1, 1); }
      } else if (qk || !NIC) {
        rearm();
      }
      __syncwarp();
      send_km();
      if ((WE & 2) && s == NSEG - 1) break;
      import();
      PROF(4);
      SCHED_FENCE(10);
      if (NIC) {
        if (qk) bar_sync(7, NII < 18 ? 384 : 256);
        xproj<0, 0, NIC>(acc, wa, dA);
        if (!qk) { if (w == 3) rearm(); bar_sync(7, NII < 18 ? 384 : 256); }
      } else {
        bar_sync(7, NII < 18 ? 384 : 256);
      }
      if (NOB & 1) bar_arrive(12, 256);
      xproj<0, NIC, 18>(acc, wa, dA);
      if (!(NOB & 1)) bar_arrive(12, 256);
      dA += (int64_t)(b2 ? XT >> 4 : -(XT >> 3));
      finish(s + ah);
      if (qk && w == 0) wait_v(s + 1);
      bar_arrive(13, 384);
      PROF(6);
      SCHED_FENCE(13);
      bar_sync(14, 256);
      PROF(7);
      xproj<1, 0, 18>(acc, wa, dA);
      b2 = b2 == 2 ? 0 : b2 + 1;
      s++;
      PROFP(8);
    }
    if (!(WE & 2)) {
      send_km();
      PIN(t16);
      if (t16 - sb < 128) stg_relaxed(tm.red + (RED_SLOT(NSEG + 1) + RED_LINE(head_id() * 3 + rank)) + (t16 & 112), 0, 0, 0, 0);
    }
  }
  bar_arrive(0, 384);
  STAMP(3);
  cluster_sync();
  STAMP(4);
}

DI void attn_role(const uint32_t sb, unsigned char* smem_raw, const RMaps& tm, const uint32_t RANK, const bf16* __restrict__ x, const bf16* __restrict__ mem0,
                  const int w, const int lane) {
  const int t2 = w * 32 + lane;
  uint32_t wo[8][4], w1[8][4];
  const uint32_t wo_lane = sb + ((lane & 7) + ((lane >> 4) << 3)) * 128 + (((w + 4 * ((lane >> 3) & 1)) ^ (lane & 7)) << 4);
  unsigned char* const g_red = tm.red;
  {
    const uint32_t tag = *(volatile unsigned*)&g_epoch + 1;
    QSTAMP(0);
    bar_sync(0, 160);
    QSTAMP(1);
    cluster_arrive();
    __half2 hx = __float2half2_rn(0.f);
    if (t2 == 0) { sts64(sb + SC_EPO, (tag - 1) * NSEG + 1, tag & 1); sts32(sb + SC_UNSC, __float_as_uint(1.f)); sts128(sb + SC_DEAD, 0, 0, 0, 0x3f800000u); sts64(sb + SC_FPAR, 0, 0); sts128(sb + SC_ONES, 0x3f803f80u, 0x3f803f80u, 0x3f803f80u, 0x3f803f80u); }
    WSTAMP(27);
    uint32_t q[8] = {0, 0, 0, 0, 0, 0, 0, 0};
    QSTAMP(2);
    mbar_wait(sb + MB_WO3, 0);
    QSTAMP(3);
    uint32_t mv[5][4];
#pragma unroll
    for (int i = 0; i < 5; i++) {
      ldsm4(mv[i], sb + SM_M0 + (lane & 7) * (DM * 2) + min(w + 4 * i, 17) * 64 + (lane >> 3) * 16);
      if (blockIdx.x == 0) hx = amax4(hx, mv[i]);
    }
#pragma unroll
    for (int k = 0; k < 8; k++) {
      ldsm4t(wo[k], wo_lane + SM_WO3 + k * 2048); ldsm4t(w1[k], wo_lane + SM_WOST + k * 2048);
#pragma unroll
      for (int i = 0; i < 4; i++) { sq_acc(q[i], wo[k][i]); sq_acc(q[i], w1[k][i]); }
    }
    bar_sync(6, 128);
#pragma unroll
    for (int k = 0; k < 8; k++) sts128(sb + SM_WO3 + t2 * 16 + k * 2048, wo[k][0], wo[k][1], wo[k][2], wo[k][3]);
#pragma unroll
    for (int i = 0; i < 5; i++) {
      const int c = (w + 4 * i) * 32;
      if (c < DM) stsm4t(sb + SM_MEM + (c + c / 192 * 64 + lane) * 16, mv[i][0], mv[i][1], mv[i][2], mv[i][3]);
    }
    bar_arrive(1, 256); bar_arrive(2, 256); bar_arrive(9, 256);
    QSTAMP(4);
    mbar_wait(sb + MB_WO, 0);
    QSTAMP(5);
#pragma unroll
    for (int k = 0; k < 8; k++) ldsm4t(wo[k], wo_lane + SM_X + XT + k * 2048);
    fence_async();
    bar_sync(6, 128);
    if (t2 == 32) tma_load3(sb + SM_X + XT, &tm.x, 32, sb + MB_X + 8);
    __syncwarp();
#pragma unroll
    for (int k = 0; k < 8; k++)
#pragma unroll
      for (int i = 0; i < 4; i++) sq_acc(q[4 + i], wo[k][i]);
    float ss = 0.f;
#pragma unroll
    for (int i = 0; i < 8; i++) ss += bf_lo(q[i]) + bf_hi(q[i]);
    ss = warp_sum(ss);
    if (lane == 0) sts32(sb + SC_SS + 4 * (8 + w), __float_as_uint(ss));
    if (blockIdx.x < NSEG) {
      mbar_wait(sb + MB_XS, 0);
#pragma unroll
      for (int i = 0; i < 18; i++) { uint32_t v[4]; lds128(sb + SM_X + 2 * XT + t2 * 16 + i * 2048, v); hx = amax4(hx, v); }
      fence_async();
      bar_sync(6, 128);
      if (t2 == 32) tma_load3(sb + SM_X + 2 * XT, &tm.x, 64, sb + MB_X + 16);
      __syncwarp();
    }
    sts32(sb + SC_SS + 4 * (12 + w), wexp(hx));
    QSTAMP(6);
    bar_sync(11, 384);
    QSTAMP(7);
    if (t2 == 0) {
      float a[16];
#pragma unroll
      for (int i = 0; i < 4; i++) lds128f(sb + SC_SS + 16 * i, &a[4 * i]);
      stg_relaxed(&g_stats[blockIdx.x * 2], __float_as_uint(((a[0] + a[1]) + (a[2] + a[3])) + ((a[4] + a[5]) + (a[6] + a[7]))),
                  __float_as_uint((a[8] + a[9]) + (a[10] + a[11])),
                  max(max(__float_as_uint(a[12]), __float_as_uint(a[13])), max(__float_as_uint(a[14]), __float_as_uint(a[15]))), tag);
    }
    __syncwarp();
    WSTAMP(24);
    QSTAMP(8);
    cluster_wait();
    QSTAMP(9);
    if (w == 0) {
      uint4 v[3];
      int n = 0;
      while (true) {
#pragma unroll
        for (int i = 0; i < 3; i++) v[i] = ldg_relaxed(&g_stats[(i * 32 + lane) * 2]);
        if (__all_sync(0xffffffffu, v[0].w == tag && v[1].w == tag && v[2].w == tag) || ++n > SPIN_LIMIT) break;
        __nanosleep(100);
      }
      WSTAMP(25);
      QSTAMP(10);
      const float sv = warp_sum(__uint_as_float(v[0].x) + __uint_as_float(v[1].x) + __uint_as_float(v[2].x));
      const float so = warp_sum(__uint_as_float(v[0].y) + __uint_as_float(v[1].y) + __uint_as_float(v[2].y));
      const int expW = ((int)(__float_as_uint(sv) >> 23) + (int)(__float_as_uint(so) >> 23) - 254 + 2 + 10 + 1) >> 1;
      sts32(sb + SC_XMAX + 4 * lane, v[0].z); sts32(sb + SC_XMAX + 128 + 4 * lane, v[1].z);
      sts32(sb + SC_EXPW, expW + 1 - 15);
      if (blockIdx.x == 0 && lane == 0) *(volatile unsigned*)&g_epoch = tag;
      sts32(sb + SC_FPAR + 4, 1);
    } else if (w < 3) {
      const uint32_t u = blockIdx.x >> 4;
      unsigned char* const z = g_red + 98304 + (blockIdx.x & 15) * 128 + (u & 1) * 2048 + (u & 6) * 4096 + (((u >> 1) ^ w) & 1) * 4096 + lane * 4;
      stg_relaxed32(z, 0);
      uint32_t best = 0xffffffffu;
#pragma unroll 1
      for (int i = 0; i < 64; i++) {
        uint32_t dt;
        asm volatile("{\n.reg .pred p;\n.reg .u32 c, v;\nmov.u32 c, %%clock;\n"
                     "atom.relaxed.gpu.global.exch.b32 v, [%1], 0;\nsetp.eq.u32 p, v, 0;\nmov.u32 %0, 0;\n@p mov.u32 %0, %%clock;\nsub.u32 %0, %0, c;\n}"
                     : "=r"(dt) : "l"(z) : "memory");
        best = min(best, dt);
        if (lds32v(sb + SC_FPAR + 4) && i >= NPROBE - 1) break;
      }
      sts32(sb + SC_LAT + (w - 1) * 4, best);
    }
    QSTAMP(11);
    bar_sync(13, 384);
    bar_arrive(0, 384);
    QSTAMP(12);
    WSTAMP(26);
  }

  const uint32_t nh = __shfl_sync(0xffffffffu, near_half(sb), 0);
  uint32_t l16 = sb + lane * 16;
  PIN(l16);
#define LV ((l16 >> 4) & 31)
#define fence_reg l16
  const uint32_t red_lo = (uint32_t)(uint64_t)g_red, red_hi = (uint32_t)((uint64_t)g_red >> 32);
  uint32_t lp;
  auto slot = [&](int s, uint32_t c, uint32_t ofs) {
    const uint32_t lo = lp | (red_lo + ((w >> 1) * 4 + (w & 1) * 2 + ((w ^ c) & 1)) * 4096 + RED_SLOT(s) + ofs);
    uint64_t a; asm("mov.b64 %0, {%1, %2};" : "=l"(a) : "r"(lo), "r"(red_hi));
    return (unsigned char*)a;
  };
  const uint32_t always = __shfl_sync(0xffffffffu, lds32(sb + SC_DEAD + 12), 0);
  const int mode0 = RANK < 2 ? w : w | 4;
  auto hint_addr = [&](int s) { return min(LV, 23u) * 4 + (red_lo + HINT_OFF + nh * 4096 + w * 16384 + RED_SLOT(s)); };
  auto load_hints = [&](uint32_t lo) {
    uint64_t a; asm("mov.b64 %0, {%1, %2};" : "=l"(a) : "r"(lo), "r"(red_hi));
    return ldg_relaxed32((const void*)a);
  };
  int s = 0;
  bool bad = false;
#pragma unroll 1
  while (true) {
    const uint32_t par = s & 1;
    uint32_t vx[4][4], hints;
    auto load_vx = [&]() {
      const uint32_t va = l16 + (RANK < 2 ? SM_VC + par * 8192 : SM_BLK + (s & 3) * SEGB) + w * 1024 + ((LV >> 3) & 1) * 384 - (LV >> 4) * 128;
#pragma unroll
      for (int i = 0; i < 4; i++) ldsm4(vx[i], va + (i & 1) * 4096 + (i >> 1) * 256);
    };
    auto retire = [&](uint32_t x) {
      asm volatile("{\n.reg .pred p;\nsetp.eq.u32 p, %0, 0;\n@p exit;\n}" :: "r"(vx[0][0] | vx[1][0] | vx[2][0] | vx[3][0] | x) : "memory");
    };
    auto scores = [&](auto memkeys, auto first, float* sc) {
      constexpr bool MK = decltype(memkeys)::value, FIRST = decltype(first)::value;
      uint32_t kb[4][4], qb[2][4];
      const uint32_t m = LV >> 3;
      uint32_t kaddr = l16 + SM_BLK + 4096 + (s & 3) * SEGB + w * 2048 + (m & 1) * (MK ? 128 : 896) - (m >> 1) * 128;
      if (MK) { PIN(kaddr); }
      else {
#pragma unroll
        for (int k = 0; k < 4; k++) ldsm4t(kb[k], kaddr + k * 256);
      }
      if (FIRST) { load_vx(); retire(MK ? kaddr : kb[0][0] | kb[1][0] | kb[2][0] | kb[3][0] | l16); bar_sync(4, 256); PROF(4); }
      ldsm4t(qb[0], l16 + SM_QM);
      if (MK) ldsm4t(kb[0], kaddr);
      ldsm4t(qb[1], l16 + SM_QM + 512);
      if (MK) ldsm4t(kb[2], kaddr + 512);
      float c[4][4];
      mma16816z(c[0], kb[0], qb[0][0], qb[0][1]); mma16816z(c[1], kb[MK ? 0 : 1], qb[0][2], qb[0][3]);
      mma16816z(c[2], kb[2], qb[1][0], qb[1][1]); mma16816z(c[3], kb[MK ? 2 : 3], qb[1][2], qb[1][3]);
      if (FIRST && B5POS == 0) bar_arrive(5, N5);
#pragma unroll
      for (int i = 0; i < (MK ? 2 : 4); i++) sc[i] = ((c[0][i] + c[1][MK ? i + 2 : i]) + c[2][i]) + c[3][MK ? i + 2 : i];
    };
    auto send = [&](auto memkeys) {
      constexpr bool MK = decltype(memkeys)::value;
      constexpr int N = MK ? 1 : 2;
      const uint32_t sa = sb + LV * 4 + SM_E + (MK ? 1024 + RANK * 128 : RANK * 512 + w * 256);
      uint32_t ra[N][2], mb[N][2];
#pragma unroll
      for (int i = 0; i < N; i++)
#pragma unroll
        for (int j = 0; j < 2; j++) {
          ra[i][j] = mapa(sa + i * 128, j ? 2 : RANK ^ 1); mb[i][j] = mapa(sb + MB_S, j ? 2 : RANK ^ 1);
          PIN(ra[i][j]);
        }
      float sc[4];
      scores(memkeys, BoolC<true>(), sc);
      uint32_t e[N];
#pragma unroll
      for (int i = 0; i < N; i++) {
        e[i] = pack_bf16(ex2(sc[2 * i]), ex2(sc[2 * i + 1]));
        if (!(fmaxf(fabsf(sc[2 * i]), fabsf(sc[2 * i + 1])) <= E_LIM)) e[i] = 0x7fff7fffu;
        st_async1(ra[i][0], e[i], mb[i][0]);
        st_async1(ra[i][1], e[i], mb[i][1]);
      }
#pragma unroll
      for (int i = 0; i < N; i++) sts32(sa + i * 128, e[i]);
      __syncwarp();
      if (l16 == sb) mbar_arrive(sb + MB_S);
      PROF(5);
    };
    const int mode = bad ? 8 : mode0;
    if (mode < 2) {
      send(BoolC<false>());
    } else if (mode == 2) {
      send(BoolC<true>());
    } else if (mode == 8) {
      load_vx();
      retire(l16);
      const uint32_t fp = lds32(sb + SC_FPAR);
      bar_sync(6, 128);
      if (w == 0 && l16 == sb) { sts32(sb + SC_FPAR, fp ^ 1); mbar_expect(sb + MB_F, 3072); }
      if (RANK < 2 && w < 3) {
        float sc[4] = {0.f, 0.f, 0.f, 0.f};
        if (w < 2) scores(BoolC<false>(), BoolC<false>(), sc); else scores(BoolC<true>(), BoolC<false>(), sc);
#pragma unroll 1
        for (int r = 0; r < 3; r++)
          st_async4(mapa(l16 + SM_FB + RANK * 1536 + w * 512, r), __float_as_uint(sc[0]), __float_as_uint(sc[1]), __float_as_uint(sc[2]), __float_as_uint(sc[3]), mapa(sb + MB_F, r));
      }
      mbar_wait(sb + MB_F, fp);
      float a[12];
#pragma unroll
      for (int j = 0; j < 3; j++) {
        float b[4];
        lds128f(l16 + SM_FB + j * 512, a + 4 * j); lds128f(l16 + SM_FB + 1536 + j * 512, b);
#pragma unroll
        for (int i = 0; i < 4; i++) a[4 * j + i] += b[i];
      }
      float m0 = fmaxf(fmaxf(fmaxf(a[0], a[2]), fmaxf(a[4], a[6])), a[8]), m1 = fmaxf(fmaxf(fmaxf(a[1], a[3]), fmaxf(a[5], a[7])), a[9]);
#pragma unroll
      for (int o = 4; o < 32; o <<= 1) { m0 = fmaxf(m0, __shfl_xor_sync(0xffffffffu, m0, o)); m1 = fmaxf(m1, __shfl_xor_sync(0xffffffffu, m1, o)); }
#pragma unroll
      for (int i = 0; i < 5; i++) {
        const uint32_t ea = sb + SM_E + LV * 4 + (i < 4 ? i * 128 : 1024);
        sts32(ea, pack_bf16(ex2(a[2 * i] - m0), ex2(a[2 * i + 1] - m1)));
        sts32(ea + (i < 4 ? 512 : 128), 0x3f803f80u);
      }
      __syncwarp();
    } else {
      load_vx();
      if (mode == 3) bar_arrive(4, 256);
      retire(l16 + 1);
    }
    {
      uint32_t wa[4], wb[4], oc[4];
      constexpr int WS = 2048;
      const uint32_t w3a = l16 + SM_WO3 + w * 512;
      lds128(w3a + KP(0) * WS, wa); lds128(w3a + KP(1) * WS, wb); lds128(sb + SC_ONES, oc);
      if (B5POS == 1 && mode < 3) bar_arrive(5, N5);
      uint32_t e[10], p[5], vm[4], ob[4];
      float o0[4], o1[4], f[3][2][4], rs[4];
      reserve2(vm); reserve2(vm + 2); reserve2(e + 8);
      hints = hint_addr(s);
      PIN(hints);
      if (CLR & 2) asm volatile("{\n.reg .pred p;\nsetp.eq.u32 p, %0, 0;\n@p exit;\n}" :: "r"(wa[0] | wb[0] | oc[0] | hints) : "memory");
      mbar_wait(sb + MB_S, par);
      PROF(6);
      ldsm4t(e, l16 + SM_E); ldsm2t_in(e + 8, l16 + SM_E + 1024, always); ldsm4t(e + 4, l16 + SM_E + 512);
      lds128_in(vm, l16 + w * 512 + SM_VM, always);
      const float scl = __uint_as_float(lds32(sb + SC_UNSC + 8 - par * 8));
      hints = load_hints(hints);
      if (GF & 1) SCHED_FENCE(4);
#pragma unroll
      for (int i = 0; i < 4; i++) p[i] = mul_bf16(e[i], e[4 + i]);
      p[4] = mul_bf16(e[8], e[9]);
      if (MO & 4) {
        float a0[4], a1[4];
        mma16816z(o0, vx[0], p[0], p[1]); mma16816z(o1, vx[1], p[0], p[1]);
        mma16816z(a0, vx[2], p[2], p[3]); lds128_in(vx[2], w3a + KP(2) * WS, always);
        mma16816z(a1, vx[3], p[2], p[3]); lds128_in(vx[3], w3a + KP(3) * WS, always);
        mma1688(o0, vm[0], vm[1], p[4]); mma1688(o1, vm[2], vm[3], p[4]);
        mma16816z(rs, oc, p[0], p[1]); mma16816(rs, oc, p[2], p[3]); mma1688(rs, oc[0], oc[1], p[4]);
#pragma unroll
        for (int i = 0; i < 4; i++) { o0[i] += a0[i]; o1[i] += a1[i]; }
      } else {
      mma16816z(o0, vx[0], p[0], p[1]); mma16816z(o1, vx[1], p[0], p[1]); mma16816z(rs, oc, p[0], p[1]);
      mma16816(o0, vx[2], p[2], p[3]); lds128_in(vx[2], w3a + KP(2) * WS, always);
      mma16816(o1, vx[3], p[2], p[3]); lds128_in(vx[3], w3a + KP(3) * WS, always);
      mma16816(rs, oc, p[2], p[3]);
      mma1688(o0, vm[0], vm[1], p[4]); mma1688(o1, vm[2], vm[3], p[4]); mma1688(rs, oc[0], oc[1], p[4]);
      }
      stsm4(l16 + w * 512 + SM_OB, pack_bf16(o0[0], o0[1]), pack_bf16(o0[2], o0[3]), pack_bf16(o1[0], o1[1]), pack_bf16(o1[2], o1[3]));
      bar_sync(6, 128);
      PROF(7);
      ldsm4t_in(oc, l16 + SM_OB, always);
      bad = __any_sync(0xffffffffu, !(rs[0] + rs[1] > 0.f) && !bad);
      rs[0] *= scl; rs[1] *= scl;
      asm volatile("{\n.reg .pred p;\nsetp.ne.u32 p, %1, 0;\n@p rcp.approx.ftz.f32 %0, %0;\n}" : "+f"(rs[0]) : "r"(always));
      asm volatile("{\n.reg .pred p;\nsetp.ne.u32 p, %1, 1;\n@p rcp.approx.ftz.f32 %0, %0;\n}" : "+f"(rs[1]) : "r"(always));
      asm volatile("lop3.b32 %0, %1, %2, %3, 0xfe;" : "=r"(lp) : "r"((l16 & 128) * 2), "r"((l16 & 256) * 4), "r"(l16 & 112));
      if (bad) continue;
      ldsm4t(ob, l16 + SM_OB + 512);
      mma16816z(f[2][0], wa, oc[0], oc[1]); mma16816z(f[2][1], wb, oc[2], oc[3]);
      mma16816z(f[0][0], wo[0], oc[0], oc[1]); mma16816z(f[0][1], wo[4], oc[2], oc[3]);
      mma16816z(f[1][0], w1[0], oc[0], oc[1]); mma16816z(f[1][1], w1[4], oc[2], oc[3]);
      ldsm4t_in(oc, l16 + SM_OB + 1024, always);
      mma16816(f[2][0], vx[2], ob[0], ob[1]); lds128_in(vx[2], w3a + KP(4) * WS, always);
      mma16816(f[2][1], vx[3], ob[2], ob[3]); lds128_in(vx[3], w3a + KP(5) * WS, always);
      mma16816(f[0][0], wo[1], ob[0], ob[1]); mma16816(f[0][1], wo[5], ob[2], ob[3]);
      mma16816(f[1][0], w1[1], ob[0], ob[1]); mma16816(f[1][1], w1[5], ob[2], ob[3]);
      ldsm4t_in(ob, l16 + SM_OB + 1536, always);
      mma16816(f[0][0], wo[2], oc[0], oc[1]); mma16816(f[0][1], wo[6], oc[2], oc[3]);
      mma16816(f[2][0], vx[2], oc[0], oc[1]); lds128_in(vx[2], w3a + KP(6) * WS, always);
      mma16816(f[2][1], vx[3], oc[2], oc[3]); lds128_in(vx[3], w3a + KP(7) * WS, always);
      mma16816(f[1][0], w1[2], oc[0], oc[1]); mma16816(f[1][1], w1[6], oc[2], oc[3]);
      mma16816(f[0][0], wo[3], ob[0], ob[1]); mma16816(f[0][1], wo[7], ob[2], ob[3]);
      mma16816(f[1][0], w1[3], ob[0], ob[1]); mma16816(f[1][1], w1[7], ob[2], ob[3]);
      mma16816(f[2][0], vx[2], ob[0], ob[1]); mma16816(f[2][1], vx[3], ob[2], ob[3]);
      bar_arrive(7, NII < 18 ? 384 : 256);
      lds128_in(ob, sb + SC_DEAD, always);
      uint32_t h[3][2];
#pragma unroll
      for (int j = 0; j < 3; j++)
#pragma unroll
        for (int i = 0; i < 2; i++)
        {
          scale_sum(f[j][1][2 * i], f[j][0][2 * i], rs[0], always); scale_sum(f[j][1][2 * i + 1], f[j][0][2 * i + 1], rs[1], always);
          h[j][i] = pack_f16(f[j][1][2 * i], f[j][1][2 * i + 1]);
        }
      const uint32_t rofs = RANK * 32768;
      red_f16x8(slot(s, RANK >> 1, rofs), h[0][0], h[1][0], h[2][0], 0x3c00u);
      red_f16x8(slot(s, (RANK >> 1) ^ 1, rofs), h[0][1], h[1][1], h[2][1], 0x3c00u);
      if (NII == 18) bar_arrive(10, 256);
      SCHED_FENCE(5);
      l16 += ob[B7R];
    }
    {
    PROF(8);
    const uint32_t ma0 = l16 + SM_MEM + w * 128 + (LV >> 3) * 896 + nh * 512;
    const unsigned char* const sl[2] = {slot(s, nh, 0), slot(s, nh ^ 1, 0)};
    uint32_t dl = gtime() - 1984;
    uint32_t late = latest_hint(hints, dl, s);
    if (late >= 64) {
      int n = 0;
#pragma unroll 1
      do {
        hints = load_hints(hint_addr(s));
        dl = gtime() - 1984;
        late = latest_hint(hints, dl, s);
      } while (late >= 64 && ++n < SPIN_LIMIT);
    }
    dl += late * 32 + tm.poll;
    PROF(9);
    {
      auto wait_until = [&](uint32_t t) {
        asm volatile("{\n.reg .pred p;\n.reg .s32 c;\n.reg .u64 t;\nTL: mov.u64 t, %%globaltimer;\ncvt.u32.u64 c, t;\nsub.s32 c, c, %0;\nsetp.lt.s32 p, c, 0;\n@p bra.uni TL;\n}" :: "r"(t + (l16 & 15)) : "memory");
      };
      uint4 v[2][3];
      auto load = [&](int c) {
#pragma unroll
        for (int r = 0; r < 3; r++) v[c][r] = ldg_relaxed(sl[c ^ (r >> 1)] + r * 32768);
      };
      auto decode = [&](int c, int n) {
        uint32_t q[9];
        __half2 hm;
        const uint32_t ma = ma0 ^ (c * 512);
#pragma unroll
        for (int i = 0; i < 9; i++) {
          const uint32_t h = i % 3 == 0 ? v[c][i / 3].x : (i % 3 == 1 ? v[c][i / 3].y : v[c][i / 3].z);
          const float2 f = __half22float2(*(const __half2*)&h);
          q[i] = pack_bf16(f.x, f.y);
          hm = i ? __hmax2(hm, __habs2(*(const __half2*)&h)) : __habs2(*(const __half2*)&h);
        }
#pragma unroll
        for (int r = 0; r < 3; r++) stsm4(ma + r * 4096, q[3 * r], q[3 * r + 1], q[3 * r + 2], r < 2 ? v[c][r].w : *(const uint32_t*)&hm);
        const bool done = __all_sync(0xffffffffu, v[c][0].w == 0x5000u && v[c][1].w == 0x5000u && v[c][2].w == 0x5000u) || n > SPIN_LIMIT;
        asm volatile("{\n.reg .pred p;\nsetp.ne.u32 p, %0, 0;\n@p bar.arrive %1, 256;\n}" :: "r"((int)done), "r"(1 + c) : "memory");
        return done;
      };
      if (LEAD) { wait_until(dl - LEAD); load(1); }
      int n = MO & 1 ? l16 & 15 : 0;
      if (MO & 1) PIN(n);
      if (MO & 2) {
        const uint32_t t = __shfl_sync(0xffffffffu, dl, 0);
        asm volatile("{\n.reg .pred p;\n.reg .s32 c;\nTL: mov.u32 c, %%globaltimer_lo;\nsub.s32 c, c, %0;\nsetp.lt.s32 p, c, 0;\n@p bra.uni TL;\n}" :: "r"(t) : "memory");
      } else wait_until(dl);
      PROF(10);
#pragma unroll 1
      do {
        load(0);
        if (!LEAD) load(1);
        asm volatile("{\n.reg .pred p;\nsetp.eq.u32 p, %0, 0;\n@p bar.sync 13, 384;\n}" :: "r"(n) : "memory");
      } while (!decode(0, n++));
      PROF(11);
#pragma unroll 1
      while (!decode(1, n++)) load(1);
      bar_arrive(9, 256);
      PROF(12);
    }
    PROF(13);
    if (++s == NSEG - 1) break;
    }
  }
#undef fence_reg
  if (RANK < 2) bar_arrive(4, 256);
  bar_sync(0, 384);
  cluster_sync();
}

__global__ void __cluster_dims__(3, 1, 1) __launch_bounds__(384, 1)
rec_kernel(const __grid_constant__ RMaps tm, const bf16* __restrict__ x, const bf16* __restrict__ mem0) {
  extern __shared__ __align__(1024) unsigned char smem_raw[];
  const uint32_t sb = smem_u32(smem_raw);
  const int tid = threadIdx.x, lane = tid & 31;
  const int wg = __shfl_sync(0xffffffffu, tid >> 7, 0);
  const int w = __shfl_sync(0xffffffffu, (tid >> 5) & 3, 0);
  uint32_t rank; asm("mov.u32 %0, %%cluster_ctarank;" : "=r"(rank));
  STAMP(0);
  asm volatile("griddepcontrol.launch_dependents;" ::: "memory");

    if (tid == 0) {
      const int h = blockIdx.x / 3;
      mbar_init(sb + MB_XS, 1);
      for (int i = 0; i < 3; i++) { mbar_init(sb + MB_W + 8 * i, 1); mbar_init(sb + MB_X + 8 * i, 1); }
      mbar_init(sb + MB_WO3, 1);
      fence_async();
      load_w(sb, tm, rank, 0);
      mbar_expect(sb + MB_X, XT);
      tma_load3(sb + SM_X, &tm.x, 0, sb + MB_X);
      if (WPOS == 2) load_w(sb, tm, rank, 1);
      mbar_expect(sb + MB_WO3, 32768 + 8 * DM * 2);
      tma_load(sb + SM_WOST, &tm.wo, rank * 192 + 64, h * DH, sb + MB_WO3);
      tma_load(sb + SM_WO3, &tm.wo, rank * 192 + 128, h * DH, sb + MB_WO3);
      bulk_load(sb + SM_M0, mem0, 8 * DM * 2, sb + MB_WO3);
      if (WOPF) tma_prefetch(&tm.wo, rank * 192, h * DH);
      if (WPOS == 1) load_w(sb, tm, rank, 1);
      load_w(sb, tm, rank, 2);
      mbar_init(sb + MB_WO, 1);
      mbar_init(sb + MB_S, rank < 2 ? 5 : 6);
      mbar_init(sb + MB_F, 1);
      mbar_init(sb + MB_VX, 1); mbar_init(sb + MB_VX + 8, 1);
      asm volatile("fence.mbarrier_init.release.cluster;" ::: "memory");
      fence_async();
      mbar_expect(sb + MB_X + 8, XT); mbar_expect(sb + MB_X + 16, XT);
      mbar_expect(sb + MB_WO, 16384); mbar_expect(sb + MB_XS, XT);
      mbar_expect(sb + MB_S, rank < 2 ? 640 + 2048 : 1280);
      mbar_expect(sb + MB_VX, 8192); mbar_expect(sb + MB_VX + 8, 8192);
    }
  __syncwarp();
  if (wg < 2) {
    asm volatile("setmaxnreg.inc.sync.aligned.u32 192;");
    __syncwarp();
    QSTAMP(0);
    if (tid < 32) bar_arrive(0, 160);
    QSTAMP(1);
    proj_role(sb, tm, x, rank, wg, w, lane);
  } else {
    asm volatile("setmaxnreg.dec.sync.aligned.u32 120;");
    attn_role(sb, smem_raw, tm, rank, x, mem0, w, lane);
  }
}

constexpr int NAUX = 36;
constexpr int A_ST = 6, A_STAGE = 8192 + 12288, A_W8 = A_ST * A_STAGE, A_EXC = A_W8 + A_ST * 1536, A_ROWS = 57;
constexpr int A_IN = A_EXC + 8 * 2304, A_INB = 3 * SEGB, A_OST = A_IN + 2 * A_INB, A_P = A_OST + 8192, A_G = A_P + 3072;
constexpr int A_BAR = A_G + 1024;
constexpr int A_XT = A_BAR + 1024, A_XW = A_XT;
constexpr int A_TOTAL = A_XT + 4096;
static_assert(A_IN % 1024 == 0 && A_XT % 1024 == 0 && A_IN >= 4 * XT && A_IN + 64 * DM * 2 <= A_BAR && A_TOTAL <= 232448, "side kernel shared memory");
struct AMaps { CUtensorMap x, wa, wa8, o, o3, o16, wob, woa, woa16; const unsigned char* red; uint32_t poll; };

DI void wgmma_n192_ss_nt(float* d, uint64_t da, uint64_t db, int acc) {
  asm volatile("{\n.reg .pred p;\nsetp.ne.b32 p, %98, 0;\n"
               "wgmma.mma_async.sync.aligned.m64n192k16.f32.bf16.bf16 {"
               "%0,%1,%2,%3,%4,%5,%6,%7,%8,%9,%10,%11,%12,%13,%14,%15,%16,%17,%18,%19,%20,%21,%22,%23,%24,%25,%26,%27,%28,%29,%30,%31,"
               "%32,%33,%34,%35,%36,%37,%38,%39,%40,%41,%42,%43,%44,%45,%46,%47,%48,%49,%50,%51,%52,%53,%54,%55,%56,%57,%58,%59,%60,%61,%62,%63,"
               "%64,%65,%66,%67,%68,%69,%70,%71,%72,%73,%74,%75,%76,%77,%78,%79,%80,%81,%82,%83,%84,%85,%86,%87,%88,%89,%90,%91,%92,%93,%94,%95"
               "}, %96, %97, p, 1, 1, 0, 1;\n}\n"
               : ACC8(d, 0), ACC8(d, 8), ACC8(d, 16), ACC8(d, 24), ACC8(d, 32), ACC8(d, 40), ACC8(d, 48), ACC8(d, 56),
                 ACC8(d, 64), ACC8(d, 72), ACC8(d, 80), ACC8(d, 88) : "l"(da), "l"(db), "r"(acc));
}
DI void wgmma_n24_ss_nt(float* d, uint64_t da, uint64_t db, int acc) {
  asm volatile("{\n.reg .pred p;\nsetp.ne.b32 p, %14, 0;\n"
               "wgmma.mma_async.sync.aligned.m64n24k16.f32.bf16.bf16 {%0,%1,%2,%3,%4,%5,%6,%7,%8,%9,%10,%11}, %12, %13, p, 1, 1, 0, 1;\n}\n"
               : ACC8(d, 0), "+f"(d[8]), "+f"(d[9]), "+f"(d[10]), "+f"(d[11]) : "l"(da), "l"(db), "r"(acc));
}
DI void tma_load3d(uint32_t dst, const CUtensorMap* m, int c0, int c1, int c2, uint32_t mb) {
  asm volatile("cp.async.bulk.tensor.3d.shared::cluster.global.mbarrier::complete_tx::bytes [%0], [%1, {%3, %4, %5}], [%2];"
               :: "r"(dst), "l"(m), "r"(mb), "r"(c0), "r"(c1), "r"(c2) : "memory");
}
DI uint32_t trans8(uint32_t x) { uint32_t r; asm("movmatrix.sync.aligned.m8n8.trans.b16 %0, %1;" : "=r"(r) : "r"(x)); return r; }
DI void wgmma_n40_ss(float* d, uint64_t da, uint64_t db, int acc) {
  asm volatile("{\n.reg .pred p;\nsetp.ne.b32 p, %22, 0;\n"
               "wgmma.mma_async.sync.aligned.m64n40k16.f32.bf16.bf16 {%0,%1,%2,%3,%4,%5,%6,%7,%8,%9,%10,%11,%12,%13,%14,%15,%16,%17,%18,%19}, "
               "%20, %21, p, 1, 1, 1, 1;\n}\n"
               : ACC8(d, 0), ACC8(d, 8), "+f"(d[16]), "+f"(d[17]), "+f"(d[18]), "+f"(d[19]) : "l"(da), "l"(db), "r"(acc));
}
DI uint2 ldg_relaxed64(const void* p) {
  uint2 v; asm volatile("ld.relaxed.gpu.global.v2.b32 {%0,%1}, [%2];" : "=r"(v.x), "=r"(v.y) : "l"(p) : "memory"); return v;
}
template <int ST> DI void ldg8x64(uint32_t* m, const void* p) {
  asm volatile("ld.relaxed.gpu.global.v2.b32 {%0,%1}, [%16];\nld.relaxed.gpu.global.v2.b32 {%2,%3}, [%16 + %17];\n"
               "ld.relaxed.gpu.global.v2.b32 {%4,%5}, [%16 + %18];\nld.relaxed.gpu.global.v2.b32 {%6,%7}, [%16 + %19];\n"
               "ld.relaxed.gpu.global.v2.b32 {%8,%9}, [%16 + %20];\nld.relaxed.gpu.global.v2.b32 {%10,%11}, [%16 + %21];\n"
               "ld.relaxed.gpu.global.v2.b32 {%12,%13}, [%16 + %22];\nld.relaxed.gpu.global.v2.b32 {%14,%15}, [%16 + %23];"
               : "=r"(m[0]), "=r"(m[1]), "=r"(m[2]), "=r"(m[3]), "=r"(m[4]), "=r"(m[5]), "=r"(m[6]), "=r"(m[7]),
                 "=r"(m[8]), "=r"(m[9]), "=r"(m[10]), "=r"(m[11]), "=r"(m[12]), "=r"(m[13]), "=r"(m[14]), "=r"(m[15])
               : "l"(p), "n"(ST), "n"(2 * ST), "n"(3 * ST), "n"(4 * ST), "n"(5 * ST), "n"(6 * ST), "n"(7 * ST) : "memory");
}
template <int ST> DI void ldg4x128(uint32_t* m, const void* p) {
  asm volatile("ld.relaxed.gpu.global.v4.b32 {%0,%1,%2,%3}, [%16];\nld.relaxed.gpu.global.v4.b32 {%4,%5,%6,%7}, [%16 + %17];\n"
               "ld.relaxed.gpu.global.v4.b32 {%8,%9,%10,%11}, [%16 + %18];\nld.relaxed.gpu.global.v4.b32 {%12,%13,%14,%15}, [%16 + %19];"
               : "=r"(m[0]), "=r"(m[1]), "=r"(m[2]), "=r"(m[3]), "=r"(m[4]), "=r"(m[5]), "=r"(m[6]), "=r"(m[7]),
                 "=r"(m[8]), "=r"(m[9]), "=r"(m[10]), "=r"(m[11]), "=r"(m[12]), "=r"(m[13]), "=r"(m[14]), "=r"(m[15])
               : "l"(p), "n"(ST), "n"(2 * ST), "n"(3 * ST) : "memory");
}
template <int N, int ST> DI bool stale(const uint32_t* m, uint32_t tag) {
  uint32_t x = m[0] ^ tag;
#pragma unroll
  for (int i = 1; i < N; i++) asm("lop3.b32 %0, %0, %1, %2, 0xf6;" : "+r"(x) : "r"(m[i * ST]), "r"(tag));
  return __any_sync(0xffffffffu, x & 1);
}
DI bool mbar_test(uint32_t b, uint32_t par) {
  uint32_t r; asm volatile("{\n.reg .pred p;\nmbarrier.test_wait.parity.shared::cta.b64 p, [%1], %2;\nselp.u32 %0, 1, 0, p;\n}" : "=r"(r) : "r"(b), "r"(par) : "memory");
  return r;
}
DI int wait_flags(const unsigned* p, bool active, unsigned base, int seg) {
  int n = 0, m;
  while (true) {
    m = __reduce_min_sync(0xffffffffu, active ? (int)(ldg_acquire32(p) - base) : NSEG);
    if (m > seg || ++n > SPIN_LIMIT) break;
    __nanosleep((YP & 32) ? 400 : 40);
  }
  return max(m, seg + 1);
}
DI void wait_count(const unsigned* p, unsigned target) {
  int n = 0;
  unsigned v;
  while (true) {
    asm volatile("ld.acquire.gpu.global.b32 %0, [%1];" : "=r"(v) : "l"(p) : "memory");
    if ((int)(v - target) >= 0 || ++n > SPIN_LIMIT) break;
    __nanosleep(64);
  }
}
#define PACE_NEXT 800
#define AWARM 0
#define WPF 3
#define UNP 64
#define ADLY 0
#define ODLY 100
#define SDLY 0
#define RSL 100
#define TWO 0
#define ALLW 1
#define AE 0
#define PING 60
#define FLAG 2
#define FPOS 1
#define QB 1
#define Q_LO 0
#define Q_HI 320
DI bool tick_wait(uint32_t pace, int step) {
  const int n = lds32v(pace);
  if (n <= step) mbar_wait(pace + 8, n & 1);
  return n <= step;
}
DI void quiet_wait(uint32_t pace) {
  uint32_t n, d;
  asm volatile("ld.volatile.shared.v2.b32 {%0,%1}, [%2];" : "=r"(n), "=r"(d) : "r"(pace) : "memory");
  if (n - 1 < NSEG - 2 && (int)(gtime() - d) > Q_HI) mbar_wait(pace + 8, n & 1);
}
DI void sleep_until(uint32_t t) {
  for (int n = 0; n < 64; n++) {
    const int r = t - gtime();
    if (r <= 0) break;
    __nanosleep(r >> 1);
  }
}
DI void aux_barrier(int i, unsigned epoch, bool wait = true) {
  asm volatile("fence.proxy.async;" ::: "memory");
  asm volatile("red.release.gpu.global.add.u32 [%0], 1;" :: "l"(&g_abar[i * 32]) : "memory");
  if (!wait) return;
  wait_count(&g_abar[i * 32], NAUX * (epoch + 1));
  asm volatile("fence.proxy.async;" ::: "memory");
}

__global__ void __launch_bounds__(512, 1)
aux_kernel(const __grid_constant__ AMaps tm, const bf16* __restrict__ x, const bf16* __restrict__ gate_w, bf16* __restrict__ out) {
  extern __shared__ __align__(1024) unsigned char smem_raw[];
  const uint32_t sb = smem_u32(smem_raw);
  const uint32_t full1 = sb + A_BAR, empty1 = full1 + 8 * A_ST, fullw = empty1 + 8 * A_ST, full3 = fullw + 16, empty3 = full3 + 32,
                 fulla = empty3 + 32, emptya = fulla + 32, fullg = emptya + 16, pace = fullg + 8;
  const int tid = threadIdx.x, lane = tid & 31, cta = blockIdx.x;
  const int wg = __shfl_sync(0xffffffffu, tid >> 7, 0), w = __shfl_sync(0xffffffffu, (tid >> 5) & 3, 0);
  ASTAMP(14);
  const unsigned epoch = *(volatile unsigned*)&g_epoch2;
  if (tid == 0) {
    for (int i = 0; i < A_ST; i++) { mbar_init(full1 + 8 * i, 1); mbar_init(empty1 + 8 * i, 8); }
    mbar_init(fullw, 1); mbar_init(fullw + 8, 1); mbar_init(fullg, 1);
    for (int i = 0; i < 2; i++) { mbar_init(fulla + 16 * i, 2); mbar_init(fulla + 16 * i + 8, 1); mbar_init(emptya + 8 * i, 4); }
    sts64(pace, 0, 0); mbar_init(pace + 8, 1); sts32(pace + 16, 0); sts64(pace + 24, 65536, 0xffff0000u);
    for (int i = 0; i < 4; i++) { mbar_init(full3 + 8 * i, 1); mbar_init(empty3 + 8 * i, cta < NH ? 8 : 4); }
    fence_async();
  }
  auto load_a = [&](int st, int k, int col) {
    mbar_expect(full1 + 8 * st, A_STAGE + 1536);
    tma_load3d(sb + st * A_STAGE, &tm.x, k, (cta >> 1) * A_ROWS - 7, 0, full1 + 8 * st);
    tma_load3d(sb + st * A_STAGE + 8192, &tm.wa, col, k, 0, full1 + 8 * st);
    tma_load3d(sb + A_W8 + st * 1536, &tm.wa8, col + 64, k, 0, full1 + 8 * st);
  };
  if (AE && tid < 32 && !(XP & 256)) {
    __syncwarp();
#pragma unroll 1
    for (int st = 0; st < A_ST; st++) if (elect_one()) load_a(st, st * 32, (cta & 1) * (DM / 2));
  }
  __syncthreads();
  ASTAMP(0);
  const bool wide = cta < NH;
  auto p3_ks = [&](int g) { return wide ? cta >> 2 : 2 * (cta - NH) + g; };
  auto p3_mt = [&](int g) { return wide ? 2 * (cta & 3) + g : 8; };
  const unsigned fbase = epoch * NSEG;
  if (wg == 3) {
    asm volatile("setmaxnreg.dec.sync.aligned.u32 %0;" :: "n"(TWO ? 32 : 48));
    if (w == 1 && cta < NH) {
#pragma unroll 1
      for (int seg = 0; seg < ((XP & 2048) ? 0 : NSEG); seg++) {
        bar_arrive(5, 160);
        if (seg > 0 && lane == 0) {
          asm volatile("cp.async.bulk.wait_group 0;" ::: "memory");
          stg_relaxed32(&g_oflag[cta * 32], fbase + seg);
        }
        __syncwarp();
        bar_sync(4, 160);
        if (QM & 16) tick_wait(pace, seg + 1);
        if (lane == 0) {
          fence_async();
          if (!(YP & 2)) {
          tma_store(&tm.o, sb + A_OST, cta * DH, seg * 32);
          tma_store(&tm.o, sb + A_OST + 4096, cta * DH + 64, seg * 32);
          }
          asm volatile("cp.async.bulk.commit_group;" ::: "memory");
          asm volatile("cp.async.bulk.wait_group.read 0;" ::: "memory");
        }
        __syncwarp();
      }
      if (lane == 0) {
        asm volatile("cp.async.bulk.wait_group 0;" ::: "memory");
        { const int seg = NSEG - 1; TSTAMP(2); }
        stg_relaxed32(&g_oflag[cta * 32], fbase + NSEG);
      }
    }
    if (w == 2 && cta < NH) {
      const uint32_t ktag = (epoch + 1) & 1, ma = sb + A_IN + 8192 + lane * 16;
      int avail = 0;
      bar_sync(10, 64);
#pragma unroll 1
      for (int seg = 0; seg < ((XP & 2048) ? 0 : NSEG); seg++) {
        if (avail <= seg) avail = wait_flags(&g_sflag[(cta * 3 + min(lane, 2)) * 8], true, fbase, seg);
        if ((QM & 8) && seg < UNP) tick_wait(pace, seg);
        TSTAMP(0);
        const unsigned char* km = g_km + (size_t)(seg * NH + cta) * 4096 + lane * 8;
        uint32_t m[16];
        const float g = __ldcg(&g_gate[seg * 32 + lane]);
        ldg8x64<256>(m, km);
        const uint32_t b = seg & 1, full = fulla + 16 * b, mb = ma + b * A_INB;
        mbar_wait(emptya + 8 * b, (~seg >> 1) & 1);
        if (lane < 2) mbar_expect(full + 8 * lane, (YP & 8) ? 0 : 16384 >> lane);
        __syncwarp();
        if (lane < 3 && !(YP & 8)) ((EF & 2) ? bulk_load_ef : bulk_load)(sb + A_IN + b * A_INB + lane * SEGB, g_seg + ((size_t)(seg & RING) * 96 + cta * 3 + lane) * 8192, 8192, full + (lane & 2) * 4);
        int n = 0;
#pragma unroll 1
        while (stale<8, 2>(m, ktag) && ++n < SPIN_LIMIT) { if (seg < UNP - 1) __nanosleep(200); ldg8x64<256>(m, km); }
        TSTAMP(1);
#pragma unroll
        for (int i = 0; i < 4; i++) stsm4(mb + (i >> 1) * SEGB + (i & 1) * 512, m[4 * i], m[4 * i + 1], m[4 * i + 2], m[4 * i + 3]);
        sts32(sb + A_G + b * 128 + lane * 4, __float_as_uint(1.f - g));
        fence_async();
        __syncwarp();
        if (lane == 0) mbar_arrive(full);
      }
    }
    if (w == 3 && QM) {
      const unsigned char* const hp = tm.red + HINT_OFF + 65536 + (cta & 1) * 4096 + min(lane, 23) * 4;
      uint32_t d = 0;
      int s = 0, n = 0;
#pragma unroll 1
      while (s < NSEG - 1) {
        const uint32_t h = ldg_relaxed32(hp + RED_SLOT(s)), t = (gtime() - 1984) & ~31u, late = latest_hint(h, t, s);
        if (late < 64) {
          d = t + late * 32 + tm.poll + Q_LO;
          sleep_until(d);
          s++; n = 0;
          if (lane == 0) { mbar_arrive(pace + 8); sts64(pace, s < NSEG - 1 ? s : 2 * NSEG, d); }
          sleep_until(d + PACE_NEXT);
        } else {
          if (++n > (s ? 16 : 256) || lds32v(pace + 16)) break;
          if (!s) __nanosleep(100);
        }
      }
      if (s < NSEG - 1 && lane == 0) { mbar_arrive(pace + 8); sts64(pace, 2 * NSEG, d); }
    }
    if (w != 0) return;
    const bool lead = lane == 0;
#pragma unroll 1
    for (int it = AE * A_ST, st = 0, ph = !AE, k = AE * A_ST * 32, col = (cta & 1) * (DM / 2); it < ((XP & 256) ? 0 : 72); it++) {
      mbar_wait(empty1 + 8 * st, ph);
      if (QM & 1) quiet_wait(pace);
      if (elect_one()) load_a(st, k, col);
      __syncwarp();
      if (++st == A_ST) { st = 0; ph ^= 1; }
      k += 32;
      if (k == DM) { k = 0; col += 72; }
    }
    auto load_wo = [&](uint32_t dst, int g, int kb, uint32_t mb) {
      if (kb < 64) tma_load(dst, &tm.wob, p3_mt(g) * 64, kb * 64, mb);
      else tma_load(dst, &tm.woa, p3_mt(g) * 64, (kb - 64) * 64, mb);
    };
    if (lead) mbar_expect(fullw, 16 * 8192);
#pragma unroll 1
    for (int st = 0; st < A_ST; st++) {
      if (!(XP & 256)) mbar_wait(empty1 + 8 * st, 1);
      if (lane < 16 && min(((lane + 1) * 8192 - 1) / A_STAGE, A_ST - 1) == st) load_wo(sb + lane * 8192, lane >> 3, p3_ks(lane >> 3) * 9 + (lane & 7), fullw);
      __syncwarp();
    }
    __syncwarp(); bar_sync(6, 288);
    if (lead) mbar_expect(fullw + 8, 2 * 8192 + (p3_ks(0) >= 4 ? 4096 : 0));
    __syncwarp();
    if (lane < 2) {
      load_wo(sb + (16 + lane) * 8192, lane, p3_ks(lane) * 9 + 8, fullw + 8);
      if (p3_ks(0) >= 4) tma_load(sb + A_XW + lane * 2048, &tm.woa16, p3_mt(lane) * 64, 448 + p3_ks(lane) * 16, fullw + 8);
    }
    __syncwarp();
    if (lead) aux_barrier(1, epoch, ALLW || p3_ks(0) >= 4);
    __syncwarp(); bar_sync(6, 288);
    {
      int avail = 0, sl = 0, ph = 1;
      const int h = (9 * p3_ks(0) >> 1) + lane;
#pragma unroll 1
      for (int seg = 0; seg < ((XP & 2048) ? 0 : NSEG); seg++) {
        if (avail <= seg) avail = wait_flags(&g_oflag[min(h, NH - 1) * 32], lane < (wide ? 5 : 9), fbase, seg);
        SSTAMP(seg, 4);
        for (int g = 0; g < (wide ? 1 : 2); g++) {
          const int ks = p3_ks(g);
          mbar_wait(empty3 + 8 * sl, ph);
          if ((QM & 4) && tick_wait(pace, seg + (QM >> 4 & 1) + 1) && ODLY) __nanosleep(ODLY);
          if (YP & 4) { if (lead) mbar_arrive(full3 + 8 * sl); }
          else if (elect_one()) {
            mbar_expect(full3 + 8 * sl, XT + (ks >= 4 ? 1024 : 0));
            tma_load3d(sb + sl * XT, &tm.o3, 0, seg * 32, ks * 9, full3 + 8 * sl);
            if (ks >= 4) tma_load(sb + A_XT + sl * 1024, &tm.o16, 72 * 64 - 64 + ks * 16, seg * 32, full3 + 8 * sl);
          }
          __syncwarp();
          if (++sl == (wide ? 3 : 4)) { sl = 0; ph ^= 1; }
        }
      }
    }
    sts32(pace + 16, 1);
    __syncwarp(); bar_sync(6, 288);
    asm volatile("griddepcontrol.wait;" ::: "memory");
  } else if (wg == 2) {
    asm volatile("setmaxnreg.dec.sync.aligned.u32 64;");
    if (cta < NH) {
      if (tid == 256) { mbar_expect(fullg, 64 * DM * 2); bulk_load(sb + A_IN, x + cta * 64 * DM, 64 * DM * 2, fullg); }
      uint32_t gw[9];
#pragma unroll
      for (int j = 0; j < 9; j++) gw[j] = ((const uint32_t*)gate_w)[j * 32 + lane];
      mbar_wait(fullg, 0);
      float mine = 0.f;
#pragma unroll 4
      for (int u = 0; u < 16; u++) {
        float d0 = 0.f, d1 = 0.f;
#pragma unroll
        for (int j = 0; j < 9; j++) {
          const uint32_t a = lds32(sb + A_IN + (w * 16 + u) * (DM * 2) + j * 128 + lane * 4);
          d0 = fmaf(bf_lo(a), bf_lo(gw[j]), d0); d1 = fmaf(bf_hi(a), bf_hi(gw[j]), d1);
        }
        d0 = warp_sum(d0 + d1);
        if (lane == u) mine = d0;
      }
      if (lane < 16) g_gate[cta * 64 + w * 16 + lane] = 1.f / (1.f + __expf(-mine));
      fence_async();
    }
    bar_sync(3, 128);
    if (tid == 256) { aux_barrier(0, epoch); if (cta == 0) *(volatile unsigned*)&g_epoch2 = epoch + 1; }
    __syncwarp();
    bar_sync(3, 128);
    if (w == 0) bar_arrive(8, 288);
    if (w == 1 && cta < NH) bar_arrive(10, 64);
    if (cta < NH) {
      CDECL;
#pragma unroll 1
      for (int seg = 0; seg < ((XP & 2048) ? 0 : NSEG); seg++) {
        CSTAMP(0);
        const uint32_t in = sb + A_IN + (seg & 1) * A_INB;
        const uint64_t qd = make_desc(in, 128, 1024, 0);
        mbar_wait(fulla + 16 * (seg & 1), (seg >> 1) & 1);
        CSTAMP(3);
        SSTAMP(seg, 0);
        float d[2][16];
        {
          float a[20];
          uint32_t vm[16];
          const unsigned char* vp = g_km + (size_t)(seg * NH + cta) * 4096 + 2048 + lane * 16;
          if (w == 3) ldg4x128<512>(vm, vp);
          WG_FENCE();
#pragma unroll
          for (int k = 0; k < ((YP & 16) ? 1 : 8); k++) wgmma_n40_ss(a, qd + ((k >> 2) * SEGB + (k & 3) * 256 >> 4), qd + ((k >> 2) * SEGB + (k & 3) * 256 + 4096 >> 4), k > 0);
          const uint32_t ga = sb + A_G + (seg & 1) * 128 + (w & 1) * 64 + (lane >> 2) * 4;
          const float f0 = __uint_as_float(lds32(ga)), f1 = __uint_as_float(lds32(ga + 32));
          WG_COMMIT();
          WG_WAIT(0);
          CSTAMP(5);
          SSTAMP(seg, 1);
          if (w < 2) {
            const int lim = w * 16 + (lane >> 2) - 2 * (lane & 3);
            float m0 = -3.0e38f, m1 = -3.0e38f;
#pragma unroll
            for (int i = 0; i < 20; i++) {
              a[i] *= SM_SCALE * LOG2E;
              if (i < 16 && (i >> 2) * 8 + (i & 1) - (i & 2) * 4 > lim) a[i] = -1.0e9f * LOG2E;
              if (i & 2) m1 = fmaxf(m1, a[i]); else m0 = fmaxf(m0, a[i]);
            }
#pragma unroll
            for (int o = 1; o < 4; o <<= 1) { m0 = fmaxf(m0, __shfl_xor_sync(0xffffffffu, m0, o)); m1 = fmaxf(m1, __shfl_xor_sync(0xffffffffu, m1, o)); }
            float s0 = 0.f, s1 = 0.f;
#pragma unroll
            for (int i = 0; i < 20; i++) { a[i] = ex2(a[i] - (i & 2 ? m1 : m0)); if (i & 2) s1 += a[i]; else s0 += a[i]; }
#pragma unroll
            for (int o = 1; o < 4; o <<= 1) { s0 += __shfl_xor_sync(0xffffffffu, s0, o); s1 += __shfl_xor_sync(0xffffffffu, s1, o); }
            s0 = f0 * rcp(s0); s1 = f1 * rcp(s1);
            uint32_t p[10];
#pragma unroll
            for (int i = 0; i < 10; i++) p[i] = pack_bf16(a[2 * i] * (i & 1 ? s1 : s0), a[2 * i + 1] * (i & 1 ? s1 : s0));
            const uint32_t pa = sb + A_P + (2 * w + ((lane >> 3) & 1)) * 768 + (lane >> 4) * 128 + (lane & 7) * 16;
            stsm4t(pa, p[0], p[1], p[2], p[3]); stsm4t(pa + 256, p[4], p[5], p[6], p[7]); stsm4t(pa + 512, p[8], p[9], 0, 0);
            CSTAMP(6);
            fence_async();
            CSTAMP(7);
          } else if (w == 3) {
            int n = 0;
#pragma unroll 1
            while (stale<4, 4>(vm, (epoch + 1) & 1) && ++n < SPIN_LIMIT) ldg4x128<512>(vm, vp);
#pragma unroll
            for (int i = 0; i < 4; i++) stsm4(in + 2 * SEGB + 8192 + (lane >> 4) * 1024 + (lane & 15) * 16 + i * 256, vm[4 * i], vm[4 * i + 1], vm[4 * i + 2], vm[4 * i + 3]);
            fence_async();
            mbar_wait(fulla + 16 * (seg & 1) + 8, (seg >> 1) & 1);
          }
        }
        CSTAMP(8);

        bar_sync(5, 160);
        CSTAMP(10);
        SSTAMP(seg, 2);
        const uint64_t pd = make_desc(sb + A_P, 128, 768, 0), vd = make_desc(in + 2 * SEGB, 128, 512, 0), md = make_desc(in + 2 * SEGB + 8192, 0, 128, 0);
        WG_FENCE();
#pragma unroll
        for (int i = 0; i < 2; i++) {
          wgmma_n32_ss<0>(d[i], vd + i * 256, pd, 0);
          wgmma_n32_ss<0>(d[i], vd + i * 256 + 16, pd + 16, 1);
          wgmma_n32_ss<0>(d[i], md + i * 64, pd + 32, 1);
        }
        WG_COMMIT();
        WG_WAIT(0);
        CSTAMP(11);
        if (lane == 0) mbar_arrive(emptya + 8 * (seg & 1));
#pragma unroll
        for (int i = 0; i < 2; i++) {
          const uint32_t oa = sb + A_OST + i * 4096 + ((lane & 7) + ((lane >> 4) << 3)) * 128 + (((2 * w + ((lane >> 3) & 1)) ^ (lane & 7)) << 4);
          stsm4t(oa, pack_bf16(d[i][0], d[i][1]), pack_bf16(d[i][2], d[i][3]), pack_bf16(d[i][4], d[i][5]), pack_bf16(d[i][6], d[i][7]));
          stsm4t(oa + 2048, pack_bf16(d[i][8], d[i][9]), pack_bf16(d[i][10], d[i][11]), pack_bf16(d[i][12], d[i][13]), pack_bf16(d[i][14], d[i][15]));
        }
        CSTAMP(12);
        bar_sync(4, 160);
        SSTAMP(seg, 3);
      }
      CDUMP;
    }
  } else {
    asm volatile("setmaxnreg.inc.sync.aligned.u32 %0;" :: "n"(TWO ? 208 : 200));
    {
      const int g = lane >> 2, t = lane & 3, r0 = (cta >> 1) * A_ROWS - 7 + w * 16;
      const uint32_t prev = (2 * t > g ? 0xffffu : 0u) | (2 * t + 1 > g ? 0xffff0000u : 0u);
      const int k0 = r0 + 2 * t - (2 * t > g ? 8 : 0), k1 = r0 + 2 * t + 1 - (2 * t + 1 > g ? 8 : 0);
      const uint32_t slot = sb + A_EXC + (wg * 4 + w) * 2304;
      float gl = 0.f, gh = 0.f;
      int st = 0, ph = 0;
#pragma unroll 1
      for (int p = -AWARM; p < ((XP & 256) ? 0 : 4); p++) {
        float big[96], sml[12];
        if (p == WPF && tid < 18) {
          const int kb = p3_ks(tid >= 9) * 9 + tid % 9;
          tma_prefetch(kb < 64 ? &tm.wob : &tm.woa, p3_mt(tid >= 9) * 64, (kb & 63) * 64);
        }
        __syncwarp();
#pragma unroll
        for (int i = 0; i < 96; i++) big[i] = 0.f;
#pragma unroll
        for (int i = 0; i < 12; i++) sml[i] = 0.f;
#pragma unroll 1
        for (int k = p < 0 ? 18 : 0; k < 18; k++) {
          mbar_wait(full1 + 8 * st, ph);
          const uint64_t da = make_desc(sb + st * A_STAGE + wg * 4096, 16, 512, 2);
          const uint64_t db = make_desc(sb + st * A_STAGE + 8192, 4096, 1024, 1), dc = make_desc(sb + A_W8 + st * 1536, 128, 512, 0);
          WG_FENCE();
#pragma unroll
          for (int j = 0; j < 2; j++) { wgmma_n192_ss_nt(big, da + j * 2, db + j * 128, 1); wgmma_n24_ss_nt(sml, da + j * 2, dc + j * 16, 1); }
          WG_COMMIT();
          WG_WAIT(1);
          if (k > 0 && lane == 0) mbar_arrive(empty1 + 8 * (st ? st - 1 : A_ST - 1));
          if (++st == A_ST) { st = 0; ph ^= 1; }
        }
        WG_WAIT(0);
        ASTAMP(16 + max(p, 0) + wg * 16);
        if (lane == 0 && p >= 0) mbar_arrive(empty1 + 8 * (st ? st - 1 : A_ST - 1));
        uint32_t f[3][9][2];
#pragma unroll
        for (int c = 0; c < 3; c++)
#pragma unroll
          for (int j = 0; j < 9; j++)
#pragma unroll
            for (int i = 0; i < 2; i++) {
              const float* a = j < 8 ? &big[(c * 8 + j) * 4 + 2 * i] : &sml[c * 4 + 2 * i];
              f[c][j][i] = c < 2 ? pack_bf16(a[0], a[1]) : trans8(pack_bf16(a[0], a[1]));
            }
        if (p == 0) {
          bar_sync(8, 288);
          gl = __ldcg(&g_gate[min(max(r0 + g, 0), S_LEN / 2 - 1) * 2 + wg]); gh = __ldcg(&g_gate[min(max(r0 + g + 8, 0), S_LEN / 2 - 1) * 2 + wg]);
        }
        asm volatile("cp.async.bulk.wait_group.read 0;" ::: "memory");
        __syncwarp();
#pragma unroll
        for (int j = 0; j < 8; j += 2) sts128(slot + j * 256 + lane * 16, f[1][j][1], f[2][j][1], f[1][j + 1][1], f[2][j + 1][1]);
        sts64(slot + 2048 + lane * 8, f[1][8][1], f[2][8][1]);
        bar_sync(1 + wg, 128);
        ASTAMP(24 + max(p, 0) + wg * 16);
        uint32_t pv[9][2];
#pragma unroll
        for (int j = 0; j < 9; j++) pv[j][0] = pv[j][1] = 0;
        if (w) {
#pragma unroll
          for (int j = 0; j < 8; j += 2) lds128(slot - 2304 + j * 256 + lane * 16, pv[j]);
          lds64(slot - 256 + lane * 8, pv[8][0], pv[8][1]);
        }
        float a[4][4], m[4][2];
#pragma unroll
        for (int h = 0; h < 4; h++) {
          const int j = 2 * h;
          const uint32_t qa[4] = {t >= h ? f[0][j][0] : 0, t >= h ? f[0][j][1] : 0, f[0][j + 1][0], f[0][j + 1][1]};
          const uint32_t qb0 = t <= h ? f[0][j + 2][0] : 0, qb1 = t <= h ? f[0][j + 2][1] : 0;
          float s0[4], s1[4], s2[4];
          mma16816z(s1, qa, f[1][j][0], f[1][j + 1][0]); mma16816z(s2, qa, f[1][j][1], f[1][j + 1][1]); mma16816z(s0, qa, pv[j][0], pv[j + 1][0]);
          mma1688(s1, qb0, qb1, f[1][j + 2][0]); mma1688(s2, qb0, qb1, f[1][j + 2][1]); mma1688(s0, qb0, qb1, pv[j + 2][0]);
          a[h][0] = 2 * t > g ? s0[0] : s1[0]; a[h][1] = 2 * t + 1 > g ? s0[1] : s1[1]; a[h][2] = 2 * t > g ? s1[2] : s2[2]; a[h][3] = 2 * t + 1 > g ? s1[3] : s2[3];
        }
#pragma unroll
        for (int h = 0; h < 4; h++) {
#pragma unroll
          for (int i = 0; i < 4; i++) a[h][i] = (i & 1 ? k1 : k0) + (i & 2) * 4 >= 0 ? a[h][i] * (0.23570226039551584f * LOG2E) : -1.0e9f * LOG2E;
          m[h][0] = fmaxf(a[h][0], a[h][1]); m[h][1] = fmaxf(a[h][2], a[h][3]);
        }
#pragma unroll
        for (int x = 1; x < 4; x <<= 1)
#pragma unroll
          for (int i = 0; i < 8; i++) m[i >> 1][i & 1] = fmaxf(m[i >> 1][i & 1], __shfl_xor_sync(0xffffffffu, m[i >> 1][i & 1], x));
#pragma unroll
        for (int h = 0; h < 4; h++) {
#pragma unroll
          for (int i = 0; i < 4; i++) a[h][i] = ex2(a[h][i] - m[h][i >> 1]);
          m[h][0] = a[h][0] + a[h][1]; m[h][1] = a[h][2] + a[h][3];
        }
#pragma unroll
        for (int x = 1; x < 4; x <<= 1)
#pragma unroll
          for (int i = 0; i < 8; i++) m[i >> 1][i & 1] += __shfl_xor_sync(0xffffffffu, m[i >> 1][i & 1], x);
        uint32_t o[9][2];
#pragma unroll
        for (int h = 0; h < 4; h++) {
          const int j = 2 * h;
          const float z0 = gl * rcp(m[h][0]), z1 = gh * rcp(m[h][1]);
          const uint32_t pl = pack_bf16(a[h][0] * z0, a[h][1] * z0), pu = pack_bf16(a[h][2] * z1, a[h][3] * z1);
          const uint32_t pa[4] = {pl & prev, 0, pl & ~prev, pu & prev};
          float d[3][4];
#pragma unroll
          for (int i = 0; i < 3; i++) mma16816z(d[i], pa, pv[j + i][1], f[2][j + i][0]);
#pragma unroll
          for (int i = 0; i < 3; i++) mma1688(d[i], 0, pu & ~prev, f[2][j + i][1]);
#pragma unroll
          for (int i = 0; i < 3; i++) {
            const uint32_t d0 = pack_bf16(d[i][0], d[i][1]), d1 = pack_bf16(d[i][2], d[i][3]);
            o[j + i][0] = i == 0 && h > 0 && t < h ? o[j][0] : d0;
            o[j + i][1] = i == 0 && h > 0 && t < h ? o[j][1] : d1;
          }
        }
        ASTAMP(28 + max(p, 0) + wg * 16);
        bar_sync(1 + wg, 128);
        const uint32_t oa = slot + (lane & 15) * 144 + (lane >> 4) * 16;
#pragma unroll
        for (int j = 0; j < 8; j += 2) stsm4(oa + j * 16, o[j][0], o[j][1], o[j + 1][0], o[j + 1][1]);
        asm volatile("stmatrix.sync.aligned.m8n8.x2.shared.b16 [%0], {%1,%2};" :: "r"(oa + 128), "r"(o[8][0]), "r"(o[8][1]) : "memory");
        fence_async();
        __syncwarp();
        if (QM & 64) quiet_wait(pace);
        if (lane < 16 && w * 16 + lane >= 7 && r0 + lane < S_LEN / 2 && p >= 0)
          asm volatile("cp.async.bulk.global.shared::cta.bulk_group [%0], [%1], 144;"
                       :: "l"(g_Ocat + (size_t)((r0 + lane) * 2 + wg) * KCAT + 4096 + (cta & 1) * (DM / 2) + p * 72), "r"(slot + lane * 144) : "memory");
        asm volatile("cp.async.bulk.commit_group;" ::: "memory");
        ASTAMP(20 + max(p, 0) + wg * 16);
      }
      if (XP & 256) bar_sync(8, 288);
      asm volatile("cp.async.bulk.wait_group 0;" ::: "memory");
    }
    ASTAMP(3);
    bar_arrive(6, 288);
    uint32_t wa[37][4];
    mbar_wait(fullw, 0);
    const uint32_t la = sb + ((lane & 7) + ((lane >> 4) << 3)) * 128 + (((2 * w + ((lane >> 3) & 1)) ^ (lane & 7)) << 4);
#pragma unroll
    for (int k = 0; k < 32; k++) ldsm4t(wa[k], la + wg * 65536 + k * 2048);
    mbar_wait(fullw + 8, 0);
#pragma unroll
    for (int k = 32; k < 36; k++) ldsm4t(wa[k], la + wg * 8192 + 65536 + k * 2048);
    ldsm4t(wa[36], la + A_XW + wg * 2048);
    fence_async();
    if (XP & 2048) bar_sync(6, 288); else bar_arrive(6, 288);
    ASTAMP(4);
    const int ks = p3_ks(wg), mt = p3_mt(wg);
    uint32_t v[16];
    auto fetch = [&](int seg) { ldg8x64<1024>(v, g_part + (((seg & 7) * 9 + mt) * 4 + (ks & 3)) * 1024 + (tid & 127)); };
    auto finish = [&](int seg) {
      const uint32_t tagv = (~seg >> 3) & 1;
      int n = 0;
#pragma unroll 1
      while (!(YP & 512) && stale<8, 2>(v, tagv) && ++n < SPIN_LIMIT) {
        if (seg < NSEG - 2) __nanosleep(RSL);
        fetch(seg);
      }
      float own[4] = {bf_lo(v[0]), bf_hi(v[0]), bf_lo(v[1]), bf_hi(v[1])};
#pragma unroll
      for (int j = 1; j < 8; j++) { own[0] += bf_lo(v[2 * j]); own[1] += bf_hi(v[2 * j]); own[2] += bf_lo(v[2 * j + 1]); own[3] += bf_hi(v[2 * j + 1]); }
      uint32_t p0 = pack_bf16(own[0], own[1]), p1 = pack_bf16(own[2], own[3]);
      asm volatile("movmatrix.sync.aligned.m8n8.trans.b16 %0, %0;" : "+r"(p0));
      asm volatile("movmatrix.sync.aligned.m8n8.trans.b16 %0, %0;" : "+r"(p1));
      const uint32_t r2 = __shfl_xor_sync(0xffffffffu, lane & 2 ? p0 : p1, 2);
      if (lane & 2) p0 = r2; else p1 = r2;
      const uint32_t r1 = __shfl_xor_sync(0xffffffffu, lane & 1 ? p0 : p1, 1);
      if (lane & 1) p0 = r1; else p1 = r1;
      if (!(YP & 256) || p0 == 0x12345678)
        *((uint2*)(out + (size_t)(seg * 32 + (ks & 3) * 8 + (lane >> 2)) * DM + mt * 64 + w * 16) + (lane & 3)) = make_uint2(p0, p1);
      SSTAMP(seg, 7);
    };
    float acc[16], acc2[16];
#pragma unroll
    for (int i = 0; i < 16; i++) acc[i] = acc2[i] = 0.f;
    int pend = -1, sl = wide ? 0 : wg, ph = 0;
    if (PING && wg) bar_arrive(1, 256);
    CDECL;
    auto run = [&](auto extra) {
#pragma unroll 1
    for (int seg = 0; seg <= ((XP & 2048) ? -1 : NSEG); seg++) {
      CSTAMP(0);
      const bool fin = pend >= 0 && (seg - pend >= FLAG || seg == NSEG);
      if (seg < NSEG) mbar_wait(full3 + 8 * sl, ph);
      if (FPOS == 1 && fin) fetch(pend);
      if (SDLY) {
        uint32_t n, d;
        asm volatile("ld.volatile.shared.v2.b32 {%0,%1}, [%2];" : "=r"(n), "=r"(d) : "r"(pace) : "memory");
        if ((int)n <= seg + 3) sleep_until(d + SDLY);
      }
      CSTAMP(1);
      if (seg < NSEG) {
      if (wg) SSTAMP(seg, 5);
      if (seg < PING) bar_sync(1 + wg, 256);
      CSTAMP(7);
      const uint64_t db = make_desc(sb + sl * XT, 16, 1024, 1);
      WG_FENCE();
#pragma unroll
      for (int k = 0; k < ((XP & 1024) ? 1 : 36); k++)
        wgmma_n32_rs(TWO && (k & 1) ? acc2 : acc, wa[k][0], wa[k][1], wa[k][2], wa[k][3], db + (k >> 2) * 256 + (k & 3) * 2, k >> TWO);
      if (decltype(extra)::value) wgmma_n32_rs(acc, wa[36][0], wa[36][1], wa[36][2], wa[36][3], make_desc(sb + A_XT + sl * 1024, 16, 256, 3), 1);
      WG_COMMIT();
      if (seg < PING) bar_arrive(2 - wg, 256);
      CSTAMP(2);
      CSTAMP(3);
      WG_WAIT(0);
      CSTAMP(4);
      if (wg) SSTAMP(seg, 6);
      if (lane == 0) mbar_arrive(empty3 + 8 * sl);
      sl += wide ? 1 : 2;
      if (sl >= (wide ? 3 : 4)) { sl -= wide ? 3 : 4; ph ^= 1; }
      uint2* dst = g_part + (((seg & 7) * 9 + mt) * 32 + ks) * 128 + (tid & 127);
      uint32_t q[8];
      if (TWO)
#pragma unroll
        for (int j = 0; j < 16; j++) acc[j] += acc2[j];
#pragma unroll
      for (int j = 0; j < 8; j++) q[j] = j & 1 ? pack_bf16(acc[2 * j], acc[2 * j + 1]) : (pack_bf16(acc[2 * j], acc[2 * j + 1]) & ~1u) | ((~seg >> 3) & 1);
      if (QM & 32) tick_wait(pace, seg + (QM >> 4 & 1) + 2);
      if (!(YP & 1025) || q[0] == 0x12345678)
      asm volatile("st.relaxed.gpu.global.v2.b32 [%0], {%1,%2};\nst.relaxed.gpu.global.v2.b32 [%0 + 8192], {%3,%4};\n"
                   "st.relaxed.gpu.global.v2.b32 [%0 + 16384], {%5,%6};\nst.relaxed.gpu.global.v2.b32 [%0 + 24576], {%7,%8};"
                   :: "l"(dst), "r"(q[0]), "r"(q[1]), "r"(q[2]), "r"(q[3]), "r"(q[4]), "r"(q[5]), "r"(q[6]), "r"(q[7]) : "memory");
      }
      CSTAMP(5);
      if (fin) { finish(pend); pend = -1; }
      CSTAMP(6);
      if ((seg & 1) == ks >> 2 && !(YP & 1)) pend = seg;
      if (wg && (seg & 7) == 6) ASTAMP(5 + (seg >> 3));
    }
    };
    if (ks >= 4) run(BoolC<true>()); else run(BoolC<false>());
    if (PING && !wg) bar_sync(1, 256);
    CDUMP;
    ASTAMP(13);
    bar_sync(6, 288);
  }
}

typedef CUresult (*EncodeFn)(CUtensorMap*, CUtensorMapDataType, cuuint32_t, void*, const cuuint64_t*, const cuuint64_t*,
                             const cuuint32_t*, const cuuint32_t*, CUtensorMapInterleave, CUtensorMapSwizzle,
                             CUtensorMapL2promotion, CUtensorMapFloatOOBfill);
#define PROMO 2
static void make_map(EncodeFn enc, CUtensorMap* m, const void* p, int rows, int cols, int box_rows) {
  cuuint64_t dims[2] = {(cuuint64_t)cols, (cuuint64_t)rows};
  cuuint64_t strides[1] = {(cuuint64_t)cols * 2};
  cuuint32_t box[2] = {64, (cuuint32_t)box_rows};
  cuuint32_t es[2] = {1, 1};
  enc(m, CU_TENSOR_MAP_DATA_TYPE_BFLOAT16, 2, (void*)p, dims, strides, box, es, CU_TENSOR_MAP_INTERLEAVE_NONE,
      CU_TENSOR_MAP_SWIZZLE_128B, (CUtensorMapL2promotion)PROMO, CU_TENSOR_MAP_FLOAT_OOB_FILL_NONE);
}

constexpr int g_poll = POLL_NS;
extern "C" void kernel_launch(void* const* d_in, const int* in_sizes, int n_in, void* d_out, int out_size) {
  const bf16* x = (const bf16*)d_in[0];
  const bf16* wqkvA = (const bf16*)d_in[1];
  const bf16* woA = (const bf16*)d_in[2];
  const bf16* mem0 = (const bf16*)d_in[4];
  const bf16* Wq = (const bf16*)d_in[5];
  const bf16* Wk = (const bf16*)d_in[6];
  const bf16* Wv = (const bf16*)d_in[7];
  const bf16* Wo = (const bf16*)d_in[8];
  const bf16* gate_w = (const bf16*)d_in[10];
  static EncodeFn enc = nullptr;
  static void *pO = nullptr, *pR = nullptr;
  if (!enc) {
    cudaDriverEntryPointQueryResult qr;
    cudaGetDriverEntryPoint("cuTensorMapEncodeTiled", (void**)&enc, cudaEnableDefault, &qr);
    cudaGetSymbolAddress(&pO, g_Ocat);
    cudaGetSymbolAddress(&pR, g_red_raw);
    cudaFuncSetAttribute(rec_kernel, cudaFuncAttributeMaxDynamicSharedMemorySize, SM_TOTAL);
    cudaFuncSetAttribute(aux_kernel, cudaFuncAttributeMaxDynamicSharedMemorySize, A_TOTAL);
  }
  RMaps rm;
  rm.poll = g_poll;
  rm.w[0] = (const unsigned char*)Wk; rm.w[1] = (const unsigned char*)Wq; rm.w[2] = (const unsigned char*)Wv; rm.w[3] = (const unsigned char*)Wo;
  rm.red = (unsigned char*)(((uintptr_t)pR + 262143) & ~(uintptr_t)262143);
  {
    cuuint64_t dims[3] = {64, S_LEN, 9}, strides[2] = {DM * 2, 128};
    cuuint32_t box[3] = {64, 32, 9}, es[3] = {1, 1, 1};
    enc(&rm.x, CU_TENSOR_MAP_DATA_TYPE_BFLOAT16, 3, (void*)x, dims, strides, box, es, CU_TENSOR_MAP_INTERLEAVE_NONE,
        CU_TENSOR_MAP_SWIZZLE_128B, CU_TENSOR_MAP_L2_PROMOTION_L2_128B, CU_TENSOR_MAP_FLOAT_OOB_FILL_NONE);
  }
  make_map(enc, &rm.wq, Wq, DM, 4096, 192);
  make_map(enc, &rm.wk, Wk, DM, 4096, 192);
  make_map(enc, &rm.wv, Wv, DM, 4096, 192);
  make_map(enc, &rm.wo, Wo, 4096, DM, 128);
  AMaps am;
  am.red = rm.red; am.poll = rm.poll;
  {
    cuuint64_t dims[3] = {DM, S_LEN / 2, 2}, strides[2] = {DM * 4, DM * 2};
    cuuint32_t box[3] = {32, 64, 2}, es[3] = {1, 1, 1};
    enc(&am.x, CU_TENSOR_MAP_DATA_TYPE_BFLOAT16, 3, (void*)x, dims, strides, box, es, CU_TENSOR_MAP_INTERLEAVE_NONE,
        CU_TENSOR_MAP_SWIZZLE_64B, CU_TENSOR_MAP_L2_PROMOTION_L2_128B, CU_TENSOR_MAP_FLOAT_OOB_FILL_NONE);
    cuuint64_t wdims[3] = {DM, DM, 3}, wstrides[2] = {DM * 6, DM * 2};
    cuuint32_t wbox[3] = {64, 32, 3}, wbox8[3] = {8, 32, 3};
    enc(&am.wa, CU_TENSOR_MAP_DATA_TYPE_BFLOAT16, 3, (void*)wqkvA, wdims, wstrides, wbox, es, CU_TENSOR_MAP_INTERLEAVE_NONE,
        CU_TENSOR_MAP_SWIZZLE_128B, CU_TENSOR_MAP_L2_PROMOTION_L2_128B, CU_TENSOR_MAP_FLOAT_OOB_FILL_NONE);
    enc(&am.wa8, CU_TENSOR_MAP_DATA_TYPE_BFLOAT16, 3, (void*)wqkvA, wdims, wstrides, wbox8, es, CU_TENSOR_MAP_INTERLEAVE_NONE,
        CU_TENSOR_MAP_SWIZZLE_NONE, CU_TENSOR_MAP_L2_PROMOTION_NONE, CU_TENSOR_MAP_FLOAT_OOB_FILL_NONE);
  }
  {
    cuuint64_t dims[3] = {64, S_LEN, KCAT / 64}, strides[2] = {KCAT * 2, 128};
    cuuint32_t box[3] = {64, 32, 9}, es[3] = {1, 1, 1};
    make_map(enc, &am.o, pO, S_LEN, KCAT, 32);
    enc(&am.o3, CU_TENSOR_MAP_DATA_TYPE_BFLOAT16, 3, pO, dims, strides, box, es, CU_TENSOR_MAP_INTERLEAVE_NONE,
        CU_TENSOR_MAP_SWIZZLE_128B, CU_TENSOR_MAP_L2_PROMOTION_L2_128B, CU_TENSOR_MAP_FLOAT_OOB_FILL_NONE);
  }
  make_map(enc, &am.wob, Wo, 4096, DM, 64);
  make_map(enc, &am.woa, woA, DM, DM, 64);
  make_map(enc, &am.woa16, woA, DM, DM, 16);
  {
    cuuint64_t dims[2] = {KCAT, S_LEN}, strides[1] = {KCAT * 2};
    cuuint32_t box[2] = {16, 32}, es[2] = {1, 1};
    enc(&am.o16, CU_TENSOR_MAP_DATA_TYPE_BFLOAT16, 2, pO, dims, strides, box, es, CU_TENSOR_MAP_INTERLEAVE_NONE,
        CU_TENSOR_MAP_SWIZZLE_32B, CU_TENSOR_MAP_L2_PROMOTION_NONE, CU_TENSOR_MAP_FLOAT_OOB_FILL_NONE);
  }

  rec_kernel<<<96, 384, SM_TOTAL, cudaStreamPerThread>>>(rm, x, mem0);
  cudaLaunchConfig_t cfg = {};
  cfg.gridDim = dim3(NAUX); cfg.blockDim = dim3(512); cfg.dynamicSmemBytes = A_TOTAL; cfg.stream = cudaStreamPerThread;
  cudaLaunchAttribute at[1];
  at[0].id = cudaLaunchAttributeProgrammaticStreamSerialization; at[0].val.programmaticStreamSerializationAllowed = 1;
  cfg.attrs = at; cfg.numAttrs = 1;
  if (XP & 16) cfg.numAttrs = 0;
  if (!(XP & 64)) cudaLaunchKernelEx(&cfg, aux_kernel, am, x, gate_w, (bf16*)d_out);
}
```

```cpp
#include <cuda_runtime.h>
#include <cuda_bf16.h>
#include <cuda_fp16.h>
#include <cuda.h>
#include <stdint.h>

typedef __nv_bfloat16 bf16;

constexpr int S_LEN = 2048, DM = 576, NH = 32, DH = 128, NSEG = 64, KCAT = 4096 + 576;
#define RED_LINE(i) (((i) >> 2) * 4096 + ((i) & 1) * 256 + ((i) & 2) * 512)
#define RED_SLOT(s) (((s) & 1) * 128 + ((s) & 2) * 256)

#define POLL_NS 896
#define NII 18
#define W3PRE 4
#define W3MID 4
#define GF 0
#define B5POS 0
#define NUP 4
#define UPF 1
#define B3Q 9
#define B3F 0
#define GATE 8
#define NTL 2
#define B7R 1
#define EXPOS 0
#define VW2 1
#define CLR 1
#define RFW 0
#define NIC 0
#define LEAD 0
#define FIN16 1
#define VXG 0
#define EXB 0
#define EXD 0
#define EXB2 8192
#define HDLY 0
#define F10 1
#define NPROBE 2
#define WPOS 1
#define CW 0
#define WOPF 0
#define YP 0
#define EF 4
#define MO 0
#define WE 3
#define ZR 0
#define EXV 2
#define NOB 0
#define QM 60
#define N5 224
#define KP(i) (((i) >> 1) + 4 * ((i) & 1))
#define SPIN_LIMIT (1 << 14)
#define XP 0

__device__ __align__(1024) bf16 g_Ocat[S_LEN * KCAT];
__device__ __align__(1024) unsigned char g_red_raw[2 * 262144];
constexpr int HINT_OFF = 2048;
__device__ __align__(16) float g_gate[S_LEN];
__device__ __align__(128) uint4 g_stats[96 * 2];
__device__ unsigned g_epoch;
__device__ unsigned g_epoch2;
__device__ __align__(128) unsigned g_oflag[NH * 32];
__device__ unsigned g_abar[3 * 32];
__device__ __align__(128) unsigned g_cflag[96 * 32];
__device__ uint2 g_sflag[96 * 4];
__device__ __align__(1024) unsigned char g_seg[NSEG * 96 * 8192];
__device__ __align__(1024) unsigned char g_km[NSEG * NH * 4096];
__device__ __align__(1024) uint2 g_part[8 * 9 * 4 * 8 * 128];
__device__ int g_err;
#define SSTAMP(seg, idx)
#define TSTAMP(idx)
#define QSTAMP(idx)
#define PROF(idx)
#define PROFP(idx)
#define STAMP(idx)
#define ASTAMP(idx)
#define WSTAMP(idx)

#define CSTAMP(idx)
#define CDECL
#define CDUMP
#define DI __device__ __forceinline__
DI uint32_t smem_u32(const void* p) { return (uint32_t)__cvta_generic_to_shared(p); }
DI uint32_t clock32() { uint32_t c; asm volatile("mov.u32 %0, %%clock;" : "=r"(c) :: "memory"); return c; }
DI uint32_t gtime() { uint32_t c; asm volatile("mov.u32 %0, %%globaltimer_lo;" : "=r"(c) :: "memory"); return c; }
DI uint32_t ldg_relaxed32(const void* p) { uint32_t v; asm volatile("ld.relaxed.gpu.global.b32 %0, [%1];" : "=r"(v) : "l"(p) : "memory"); return v; }
DI uint32_t ldg_acquire32(const void* p) { uint32_t v; asm volatile("ld.acquire.gpu.global.b32 %0, [%1];" : "=r"(v) : "l"(p) : "memory"); return v; }
DI void stg_relaxed32(void* p, uint32_t v) { asm volatile("st.relaxed.gpu.global.b32 [%0], %1;" :: "l"(p), "r"(v) : "memory"); }
DI int head_id() { int c; asm volatile("mov.u32 %0, %%clusterid.x;" : "=r"(c)); return c; }
DI uint32_t mapa(uint32_t a, uint32_t r) { uint32_t o; asm("mapa.shared::cluster.u32 %0, %1, %2;" : "=r"(o) : "r"(a), "r"(r)); return o; }
DI void cluster_arrive() { asm volatile("barrier.cluster.arrive.relaxed.aligned;" ::: "memory"); }
DI void cluster_wait() { asm volatile("barrier.cluster.wait.aligned;" ::: "memory"); }
DI void cluster_sync() { asm volatile("barrier.cluster.arrive.release.aligned;\nbarrier.cluster.wait.acquire.aligned;" ::: "memory"); }
DI void mbar_init(uint32_t b, uint32_t c) { asm volatile("mbarrier.init.shared::cta.b64 [%0], %1;" :: "r"(b), "r"(c) : "memory"); }
DI void mbar_expect(uint32_t b, uint32_t tx) { asm volatile("mbarrier.arrive.expect_tx.shared::cta.b64 _, [%0], %1;" :: "r"(b), "r"(tx) : "memory"); }
DI void mbar_arrive(uint32_t b) { asm volatile("mbarrier.arrive.shared::cta.b64 _, [%0];" :: "r"(b) : "memory"); }
DI void mbar_wait(uint32_t b, uint32_t par) {
  asm volatile("{\n.reg .pred p;\n.reg .u32 n, q;\nmov.u32 n, 0;\n"
               "WL: add.u32 n, n, 1;\nshr.u32 q, n, 12;\nxor.b32 q, q, %1;\n"
               "mbarrier.try_wait.parity.shared::cta.b64 p, [%0], q;\n@!p bra.uni WL;\n}"
               :: "r"(b), "r"(par) : "memory");
}
DI void wait_until(uint32_t t) {
  const uint32_t now = gtime();
  t = min(t, now + 8192);
  asm volatile("{\n.reg .pred p;\n.reg .u32 c;\nTL: mov.u32 c, %%globaltimer_lo;\nsetp.lt.u32 p, c, %0;\n@p bra.uni TL;\n}" :: "r"(t) : "memory");
}
#define PIN(v) v = __shfl_xor_sync(0xffffffffu, v, 0)
#define SCHED_FENCE(k) asm volatile("{\n.reg .pred p;\nsetp.eq.u32 p, %0, %1;\n@p exit;\n}" :: "r"(fence_reg), "r"(k) : "memory")
#define MEM_ORDER(k) asm volatile("{\n.reg .pred p;\nsetp.eq.u32 p, %0, %1;\n@p st.shared.u32 [%0], %0;\n}" :: "r"(fence_reg), "r"(k + 64) : "memory")
DI void bar_sync(int id, int n) { asm volatile("bar.sync %0, %1;" :: "r"(id), "r"(n) : "memory"); }
DI void bar_arrive(int id, int n) { asm volatile("bar.arrive %0, %1;" :: "r"(id), "r"(n) : "memory"); }
DI void fence_async() { asm volatile("fence.proxy.async.shared::cta;" ::: "memory"); }
DI void st_async4(uint32_t a, uint32_t x, uint32_t y, uint32_t z, uint32_t w, uint32_t mb) {
  asm volatile("st.async.weak.shared::cluster.mbarrier::complete_tx::bytes.v4.b32 [%0], {%1,%2,%3,%4}, [%5];"
               :: "r"(a), "r"(x), "r"(y), "r"(z), "r"(w), "r"(mb) : "memory");
}
DI void st_async2(uint32_t a, uint32_t x, uint32_t y, uint32_t mb) {
  asm volatile("st.async.weak.shared::cluster.mbarrier::complete_tx::bytes.v2.b32 [%0], {%1,%2}, [%3];"
               :: "r"(a), "r"(x), "r"(y), "r"(mb) : "memory");
}
DI void sts32(uint32_t a, uint32_t x) { asm volatile("st.shared.b32 [%0], %1;" :: "r"(a), "r"(x) : "memory"); }
DI void sts64(uint32_t a, uint32_t x, uint32_t y) { asm volatile("st.shared.v2.b32 [%0], {%1,%2};" :: "r"(a), "r"(x), "r"(y) : "memory"); }
DI void sts128(uint32_t a, uint32_t x, uint32_t y, uint32_t z, uint32_t w) {
  asm volatile("st.shared.v4.b32 [%0], {%1,%2,%3,%4};" :: "r"(a), "r"(x), "r"(y), "r"(z), "r"(w) : "memory");
}
DI uint32_t lds32(uint32_t a) { uint32_t x; asm volatile("ld.shared.b32 %0, [%1];" : "=r"(x) : "r"(a) : "memory"); return x; }
DI uint32_t lds32v(uint32_t a) { uint32_t x; asm volatile("ld.volatile.shared.b32 %0, [%1];" : "=r"(x) : "r"(a) : "memory"); return x; }
DI void lds64(uint32_t a, uint32_t& x, uint32_t& y) { asm volatile("ld.shared.v2.b32 {%0,%1}, [%2];" : "=r"(x), "=r"(y) : "r"(a) : "memory"); }
DI void lds128(uint32_t a, uint32_t* r) {
  asm volatile("ld.shared.v4.b32 {%0,%1,%2,%3}, [%4];" : "=r"(r[0]), "=r"(r[1]), "=r"(r[2]), "=r"(r[3]) : "r"(a) : "memory");
}
DI void lds128f(uint32_t a, float* r) {
  asm volatile("ld.shared.v4.f32 {%0,%1,%2,%3}, [%4];" : "=f"(r[0]), "=f"(r[1]), "=f"(r[2]), "=f"(r[3]) : "r"(a) : "memory");
}
DI void lds64f(uint32_t a, float* r) { asm volatile("ld.shared.v2.f32 {%0,%1}, [%2];" : "=f"(r[0]), "=f"(r[1]) : "r"(a) : "memory"); }
DI void ldsm4t(uint32_t* r, uint32_t a) {
  asm volatile("ldmatrix.sync.aligned.m8n8.x4.trans.shared.b16 {%0,%1,%2,%3}, [%4];"
               : "=r"(r[0]), "=r"(r[1]), "=r"(r[2]), "=r"(r[3]) : "r"(a) : "memory");
}
DI void ldsm4t_in(uint32_t* r, uint32_t a, uint32_t t) {
  asm volatile("{\n.reg .pred p;\nsetp.ne.u32 p, %5, 0;\n@p ldmatrix.sync.aligned.m8n8.x4.trans.shared.b16 {%0,%1,%2,%3}, [%4];\n}"
               : "+r"(r[0]), "+r"(r[1]), "+r"(r[2]), "+r"(r[3]) : "r"(a), "r"(t) : "memory");
}
DI void lds128_in(uint32_t* r, uint32_t a, uint32_t t) {
  asm volatile("{\n.reg .pred p;\nsetp.ne.u32 p, %5, 0;\n@p ld.shared.v4.b32 {%0,%1,%2,%3}, [%4];\n}"
               : "+r"(r[0]), "+r"(r[1]), "+r"(r[2]), "+r"(r[3]) : "r"(a), "r"(t) : "memory");
}
DI void ldsm2t_in(uint32_t* r, uint32_t a, uint32_t t) {
  asm volatile("{\n.reg .pred p;\nsetp.ne.u32 p, %3, 0;\n@p ldmatrix.sync.aligned.m8n8.x2.trans.shared.b16 {%0,%1}, [%2];\n}" : "+r"(r[0]), "+r"(r[1]) : "r"(a), "r"(t) : "memory");
}
DI void reserve2(uint32_t* r) { asm volatile("{\n.reg .u64 t;\nmov.u64 t, %%clock64;\nmov.b64 {%0, %1}, t;\n}" : "=r"(r[0]), "=r"(r[1])); }
DI void scale_sum(float& x, float& y, float s, uint32_t t) {
  asm volatile("{\n.reg .pred p;\nsetp.ne.u32 p, %2, 0;\n@p mul.f32 %0, %0, %1;\n}" : "+f"(y) : "f"(s), "r"(t));
  asm volatile("{\n.reg .pred p;\nsetp.ne.u32 p, %3, 1;\n@p fma.rn.f32 %0, %0, %1, %2;\n}" : "+f"(x) : "f"(s), "f"(y), "r"(t));
}
DI void ldsm4(uint32_t* r, uint32_t a) {
  asm volatile("ldmatrix.sync.aligned.m8n8.x4.shared.b16 {%0,%1,%2,%3}, [%4];"
               : "=r"(r[0]), "=r"(r[1]), "=r"(r[2]), "=r"(r[3]) : "r"(a) : "memory");
}
DI void st_async1(uint32_t a, uint32_t x, uint32_t mb) {
  asm volatile("st.async.weak.shared::cluster.mbarrier::complete_tx::bytes.b32 [%0], %1, [%2];" :: "r"(a), "r"(x), "r"(mb) : "memory");
}
DI void stsm4(uint32_t a, uint32_t x, uint32_t y, uint32_t z, uint32_t w) {
  asm volatile("stmatrix.sync.aligned.m8n8.x4.shared.b16 [%0], {%1,%2,%3,%4};" :: "r"(a), "r"(x), "r"(y), "r"(z), "r"(w) : "memory");
}
DI void stsm4t(uint32_t a, uint32_t x, uint32_t y, uint32_t z, uint32_t w) {
  asm volatile("stmatrix.sync.aligned.m8n8.x4.trans.shared.b16 [%0], {%1,%2,%3,%4};" :: "r"(a), "r"(x), "r"(y), "r"(z), "r"(w) : "memory");
}
DI uint32_t pack_bf16(float lo, float hi) { uint32_t r; asm("cvt.rn.bf16x2.f32 %0, %1, %2;" : "=r"(r) : "f"(hi), "f"(lo)); return r; }
DI uint32_t pack_f16(float lo, float hi) { uint32_t r; asm("cvt.rn.f16x2.f32 %0, %1, %2;" : "=r"(r) : "f"(hi), "f"(lo)); return r; }
DI float ex2(float x) { float y; asm("ex2.approx.ftz.f32 %0, %1;" : "=f"(y) : "f"(x)); return y; }
DI float rcp(float x) { float y; asm("rcp.approx.ftz.f32 %0, %1;" : "=f"(y) : "f"(x)); return y; }
DI float bf_lo(uint32_t x) { return __uint_as_float(x << 16); }
DI float bf_hi(uint32_t x) { return __uint_as_float(x & 0xffff0000u); }
DI void mma16816(float* d, const uint32_t* a, uint32_t b0, uint32_t b1) {
  asm volatile("mma.sync.aligned.m16n8k16.row.col.f32.bf16.bf16.f32 {%0,%1,%2,%3}, {%4,%5,%6,%7}, {%8,%9}, {%0,%1,%2,%3};"
               : "+f"(d[0]), "+f"(d[1]), "+f"(d[2]), "+f"(d[3]) : "r"(a[0]), "r"(a[1]), "r"(a[2]), "r"(a[3]), "r"(b0), "r"(b1));
}
DI void mma16816z(float* d, const uint32_t* a, uint32_t b0, uint32_t b1) {
  asm volatile("mma.sync.aligned.m16n8k16.row.col.f32.bf16.bf16.f32 {%0,%1,%2,%3}, {%4,%5,%6,%7}, {%8,%9}, {%10,%10,%10,%10};"
               : "=f"(d[0]), "=f"(d[1]), "=f"(d[2]), "=f"(d[3]) : "r"(a[0]), "r"(a[1]), "r"(a[2]), "r"(a[3]), "r"(b0), "r"(b1), "f"(0.f));
}
DI void mma1688z(float* d, uint32_t a0, uint32_t a1, uint32_t b0) {
  asm volatile("mma.sync.aligned.m16n8k8.row.col.f32.bf16.bf16.f32 {%0,%1,%2,%3}, {%4,%5}, {%6}, {%7,%7,%7,%7};"
               : "=f"(d[0]), "=f"(d[1]), "=f"(d[2]), "=f"(d[3]) : "r"(a0), "r"(a1), "r"(b0), "f"(0.f));
}
DI void mma1688(float* d, uint32_t a0, uint32_t a1, uint32_t b0) {
  asm volatile("mma.sync.aligned.m16n8k8.row.col.f32.bf16.bf16.f32 {%0,%1,%2,%3}, {%4,%5}, {%6}, {%0,%1,%2,%3};"
               : "+f"(d[0]), "+f"(d[1]), "+f"(d[2]), "+f"(d[3]) : "r"(a0), "r"(a1), "r"(b0));
}
DI void ldsm2t(uint32_t* r, uint32_t a) {
  asm volatile("ldmatrix.sync.aligned.m8n8.x2.trans.shared.b16 {%0,%1}, [%2];" : "=r"(r[0]), "=r"(r[1]) : "r"(a) : "memory");
}
DI uint32_t add_bf16(uint32_t a, uint32_t b) { uint32_t r; asm("add.rn.bf16x2 %0, %1, %2;" : "=r"(r) : "r"(a), "r"(b)); return r; }
DI uint32_t mul_bf16(uint32_t a, uint32_t b) { uint32_t r; asm("mul.rn.bf16x2 %0, %1, %2;" : "=r"(r) : "r"(a), "r"(b)); return r; }
DI uint64_t make_desc(uint32_t addr, uint32_t lbo, uint32_t sbo, uint32_t swz) {
  return (uint64_t)((addr & 0x3FFFF) >> 4) | ((uint64_t)(lbo >> 4) << 16) | ((uint64_t)(sbo >> 4) << 32) | ((uint64_t)swz << 62);
}
#define WG_FENCE() asm volatile("wgmma.fence.sync.aligned;" ::: "memory")
#define WG_COMMIT() asm volatile("wgmma.commit_group.sync.aligned;" ::: "memory")
#define WG_WAIT(n) asm volatile("wgmma.wait_group.sync.aligned %0;" :: "n"(n) : "memory")
#define ACC8(d, o) "+f"(d[o]), "+f"(d[o + 1]), "+f"(d[o + 2]), "+f"(d[o + 3]), "+f"(d[o + 4]), "+f"(d[o + 5]), "+f"(d[o + 6]), "+f"(d[o + 7])
DI void wgmma_n32_rs(float* d, uint32_t a0, uint32_t a1, uint32_t a2, uint32_t a3, uint64_t db, int acc) {
  asm volatile("{\n.reg .pred p;\nsetp.ne.b32 p, %21, 0;\n"
               "wgmma.mma_async.sync.aligned.m64n32k16.f32.bf16.bf16 {%0,%1,%2,%3,%4,%5,%6,%7,%8,%9,%10,%11,%12,%13,%14,%15}, "
               "{%16,%17,%18,%19}, %20, p, 1, 1, 0;\n}\n"
               : ACC8(d, 0), ACC8(d, 8) : "r"(a0), "r"(a1), "r"(a2), "r"(a3), "l"(db), "r"(acc));
}
template <int TA>
DI void wgmma_n32_ss(float* d, uint64_t da, uint64_t db, int acc) {
  asm volatile("{\n.reg .pred p;\nsetp.ne.b32 p, %18, 0;\n"
               "wgmma.mma_async.sync.aligned.m64n32k16.f32.bf16.bf16 {%0,%1,%2,%3,%4,%5,%6,%7,%8,%9,%10,%11,%12,%13,%14,%15}, "
               "%16, %17, p, 1, 1, %19, 1;\n}\n"
               : ACC8(d, 0), ACC8(d, 8) : "l"(da), "l"(db), "r"(acc), "n"(TA));
}
DI void tma_load(uint32_t dst, const CUtensorMap* m, int c0, int c1, uint32_t mb) {
  asm volatile("cp.async.bulk.tensor.2d.shared::cluster.global.mbarrier::complete_tx::bytes [%0], [%1, {%3, %4}], [%2];"
               :: "r"(dst), "l"(m), "r"(mb), "r"(c0), "r"(c1) : "memory");
}
DI void tma_load3(uint32_t dst, const CUtensorMap* m, int row, uint32_t mb) {
  asm volatile("cp.async.bulk.tensor.3d.shared::cluster.global.mbarrier::complete_tx::bytes [%0], [%1, {%3, %4, %3}], [%2];"
               :: "r"(dst), "l"(m), "r"(mb), "r"(0), "r"(row) : "memory");
}
DI bool elect_one() {
  uint32_t p;
  asm volatile("{\n.reg .pred p;\nelect.sync _|p, 0xffffffff;\nselp.u32 %0, 1, 0, p;\n}" : "=r"(p));
  return p;
}
DI void bulk_s2s(uint32_t dst, uint32_t src, uint32_t bytes, uint32_t mb) {
  asm volatile("cp.async.bulk.shared::cluster.shared::cta.mbarrier::complete_tx::bytes [%0], [%1], %2, [%3];"
               :: "r"(dst), "r"(src), "r"(bytes), "r"(mb) : "memory");
}
DI void bulk_load(uint32_t dst, const void* src, uint32_t bytes, uint32_t mb) {
  asm volatile("cp.async.bulk.shared::cluster.global.mbarrier::complete_tx::bytes [%0], [%1], %2, [%3];" :: "r"(dst), "l"(src), "r"(bytes), "r"(mb) : "memory");
}
#define EVICT_FIRST ".reg .b64 pol;\ncreatepolicy.fractional.L2::evict_first.b64 pol, 1.0;\n"
DI void bulk_load_ef(uint32_t dst, const void* src, uint32_t bytes, uint32_t mb) {
  asm volatile("{\n" EVICT_FIRST "cp.async.bulk.shared::cluster.global.mbarrier::complete_tx::bytes.L2::cache_hint [%0], [%1], %2, [%3], pol;\n}"
               :: "r"(dst), "l"(src), "r"(bytes), "r"(mb) : "memory");
}
DI void tma_load_ef(uint32_t dst, const CUtensorMap* m, int c0, int c1, uint32_t mb) {
  asm volatile("{\n" EVICT_FIRST "cp.async.bulk.tensor.2d.shared::cluster.global.mbarrier::complete_tx::bytes.L2::cache_hint [%0], [%1, {%3, %4}], [%2], pol;\n}"
               :: "r"(dst), "l"(m), "r"(mb), "r"(c0), "r"(c1) : "memory");
}
DI void tma_prefetch(const CUtensorMap* m, int c0, int c1) {
  asm volatile("cp.async.bulk.prefetch.tensor.2d.L2.global.tile [%0, {%1, %2}];" :: "l"(m), "r"(c0), "r"(c1) : "memory");
}
DI void tma_store(const CUtensorMap* m, uint32_t src, int c0, int c1) {
  asm volatile("cp.async.bulk.tensor.2d.global.shared::cta.bulk_group [%0, {%2, %3}], [%1];" :: "l"(m), "r"(src), "r"(c0), "r"(c1) : "memory");
}
DI uint4 ldg_relaxed(const void* p) {
  uint4 v;
  asm volatile("ld.relaxed.gpu.global.v4.b32 {%0,%1,%2,%3}, [%4];" : "=r"(v.x), "=r"(v.y), "=r"(v.z), "=r"(v.w) : "l"(p) : "memory");
  return v;
}
DI void stg_relaxed(void* p, uint32_t x, uint32_t y, uint32_t z, uint32_t w) {
  asm volatile("st.relaxed.gpu.global.v4.b32 [%0], {%1,%2,%3,%4};" :: "l"(p), "r"(x), "r"(y), "r"(z), "r"(w) : "memory");
}
DI void red_f16x8(void* p, uint32_t x, uint32_t y, uint32_t z, uint32_t w) {
  asm volatile("red.relaxed.gpu.global.add.noftz.v4.f16x2 [%0], {%1,%2,%3,%4};" :: "l"(p), "r"(x), "r"(y), "r"(z), "r"(w) : "memory");
}
DI void sq_acc(uint32_t& a, uint32_t x) { asm("fma.rn.bf16x2 %0, %1, %1, %0;" : "+r"(a) : "r"(x)); }
DI __half2 amax4(__half2 h, const uint32_t* v) {
  h = __hmax2_nan(__hmax2_nan(h, __habs2(*(const __half2*)&v[0])), __habs2(*(const __half2*)&v[1]));
  return __hmax2_nan(__hmax2_nan(h, __habs2(*(const __half2*)&v[2])), __habs2(*(const __half2*)&v[3]));
}
DI uint32_t wexp(__half2 h) { const uint32_t u = *(const uint32_t*)&h; return __reduce_max_sync(0xffffffffu, max((u >> 16) & 0x7fffu, u & 0x7fffu)) >> 7; }
DI float max10(const float* a) {
  return fmaxf(fmaxf(fmaxf(fmaxf(a[0], a[1]), fmaxf(a[2], a[3])), fmaxf(fmaxf(a[4], a[5]), fmaxf(a[6], a[7]))), fmaxf(a[8], a[9]));
}
DI float quad_max(float m) {
  return fmaxf(fmaxf(m, __shfl_xor_sync(0xffffffffu, m, 1)), fmaxf(__shfl_xor_sync(0xffffffffu, m, 2), __shfl_xor_sync(0xffffffffu, m, 3)));
}
DI float warp_sum(float v) {
#pragma unroll
  for (int o = 16; o; o >>= 1) v += __shfl_xor_sync(0xffffffffu, v, o);
  return v;
}

constexpr int SM_WO3 = 0;
constexpr int SM_X = 16384;
constexpr int XT = 36864;
constexpr int SM_EXP = 126976;
constexpr int SEGB = 10240;
constexpr int SM_BLK = SM_EXP + 8192;
constexpr int SM_VC = SM_BLK + 4 * SEGB;
constexpr int SM_PART = SM_VC + 16384;
constexpr int SM_QM = SM_PART + 4096;
constexpr int SM_E = SM_QM + 1024;
constexpr int SM_VM = SM_E + 1536;
constexpr int SM_OB = SM_VM + 2048;
constexpr int SM_FB = SM_OB + 2048;
constexpr int SM_STAGE = SM_X + XT;
constexpr int SM_M0 = SM_STAGE + 3 * 49152;
constexpr int SM_MISC = 210944;
constexpr int SM_WOST = 212992;
constexpr int SM_MEM = SM_WOST;
constexpr int SM_MAX = SM_MEM + 11264;
#define MEM_BLK(q) ((q) / 3 * 4096 + (q) % 3 * 1024)
constexpr int SM_TOTAL = 229376;
constexpr int MB_W = SM_MISC;
constexpr int MB_WO = SM_MISC + 24;
constexpr int MB_WO3 = SM_MISC + 32;
constexpr int MB_X = SM_MISC + 40;
constexpr int MB_S = SM_MISC + 64;
constexpr int MB_F = SM_MISC + 72;
constexpr int MB_VX = SM_MISC + 80;
constexpr int SC_FPAR = SM_MISC + 136;
constexpr int SC_DEAD = SM_MISC + 96;
constexpr int SC_UNSC = SM_MISC + 112;
constexpr int SC_OFL = SM_MISC + 1024;
constexpr int SC_EXPW = SM_MISC + 132;
constexpr int SC_ONES = SM_MISC + 144;
constexpr int SC_SS = SM_MISC + 160;
constexpr int SC_LAT = SM_MISC + 224;
constexpr int SC_TAG = SM_MISC + 232;
constexpr int SC_EPO = SM_MISC + 240;
constexpr int MB_XS = SM_MISC + 248;
constexpr int SC_XMAX = SM_MISC + 256;
constexpr int SC_PROF = 229376;

constexpr float SM_SCALE = 0.08838834764831845f;
constexpr float LOG2E = 1.4426950408889634f;
constexpr float E_LIM = 20.f;

template <bool B> struct BoolC { static constexpr bool value = B; };
template <int I> struct IntC { static constexpr int value = I; };
struct RMaps { CUtensorMap x, wq, wk, wv, wo; unsigned char* red; uint32_t poll; const unsigned char* oflag; };

DI uint32_t latest_hint(uint32_t h, uint32_t d, int s) {
  const uint32_t x = (((h | 0xc0c0c0c0u) - ((d >> 5) & 63) * 0x01010101u) & 0x3f3f3f3fu) | ((h ^ (((s >> 2) + 1) & 3) * 0x40404040u) & 0xc0c0c0c0u);
  const uint32_t y = __vmaxu2(x & 0x00ff00ffu, (x >> 8) & 0x00ff00ffu);
  return __reduce_max_sync(0xffffffffu, max(y & 0xffffu, y >> 16));
}
DI uint32_t near_half(uint32_t sb) {
  uint32_t a, b; lds64(sb + SC_LAT, a, b);
  return a > b;
}

template <int RT, int K0, int K1, bool D32 = false>
DI void xproj(float* acc, const uint32_t (&wa)[2][18][4], uint64_t xd) {
  if (XP & 1) return;
  WG_FENCE();
#pragma unroll
  for (int k = K0; k < ((XP & 128) ? K0 + 1 : K1); k++)
  {
    uint64_t d = xd + (uint64_t)(((k >> 1) * 4096 + (k & 1) * 32) >> 4);
    if (D32) asm("mov.b64 %0, {%1, %2};" : "=l"(d) : "r"((uint32_t)xd + (((k >> 1) * 4096 + (k & 1) * 32) >> 4)), "r"((uint32_t)(xd >> 32)));
    wgmma_n32_rs(acc, wa[RT][k][0], wa[RT][k][1], wa[RT][k][2], wa[RT][k][3], d, k != 0);
  }
  WG_COMMIT();
}

DI void load_w(uint32_t sb, const RMaps& tm, uint32_t rank, int c) {
  const int h = blockIdx.x / 3;
  mbar_expect(sb + MB_W + 8 * c, 49152);
  ((EF & 4) ? tma_load_ef : tma_load)(sb + SM_STAGE + c * 49152, rank < 2 ? &tm.wk : &tm.wv, h * DH + (rank == 1 ? 64 : 0), c * 192, sb + MB_W + 8 * c);
  ((EF & 4) ? tma_load_ef : tma_load)(sb + SM_STAGE + c * 49152 + 24576, rank < 2 ? &tm.wq : &tm.wv, h * DH + (rank == 0 ? 0 : 64), c * 192, sb + MB_W + 8 * c);
}
DI void seg_store(int seg, uint32_t slot, uint32_t sb) {
  fence_async();
  asm volatile("cp.async.bulk.global.shared::cta.bulk_group [%0], [%1], 8192;"
               :: "l"(g_seg + ((size_t)slot * 96 + blockIdx.x) * 8192), "r"(sb + SM_BLK + (seg & 3) * SEGB) : "memory");
  asm volatile("cp.async.bulk.commit_group;" ::: "memory");
}
DI void seg_publish(int seg, uint32_t sb) {
  uint32_t v, own;
  lds64(sb + SC_EPO, v, own);
  asm volatile("cp.async.bulk.wait_group 0;" ::: "memory");
  asm volatile("st.relaxed.gpu.global.v2.b32 [%0], {%1,%2};" :: "l"(&g_sflag[blockIdx.x * 4]), "r"(v + seg), "r"(own) : "memory");
}

DI void proj_role(const uint32_t sb, const RMaps& tm, const bf16* __restrict__ x, const uint32_t rank, const int wg, const int w, const int lane) {
  const bool qk = rank < 2;
  uint32_t wa[2][18][4];
  float acc[16];
  const uint64_t xd0 = make_desc(sb + SM_X + wg * 64, 16, 1024, 1);
  {
    const int rr = (lane & 7) + ((lane >> 4) << 3);
    const uint32_t col = ((2 * w + ((lane >> 3) & 1)) ^ (lane & 7)) << 4;
    float ss = 0.f;
    bar_sync(3, 256);
    mbar_wait(sb + MB_X, 0);
    auto chunk = [&](auto cc) {
      constexpr int c = decltype(cc)::value;
      QSTAMP(2 + 2 * c);
      mbar_wait(sb + MB_W + 8 * c, 0);
      QSTAMP(3 + 2 * c);
#pragma unroll
      for (int rt = 1; rt >= 0; rt--)
#pragma unroll
        for (int k = 0; k < 6; k++)
          ldsm4t(wa[rt][c * 6 + k], sb + SM_STAGE + c * 49152 + (rt ^ wg) * 24576 + (64 * (k >> 1) + 32 * wg + 16 * (k & 1) + rr) * 128 + col);
      fence_async();
      if (c < 2) {
        bar_sync(3, 256);
        QSTAMP(17 + c);
        if (threadIdx.x == 0) {
          if (c == 0) tma_load(sb + SM_X + XT, &tm.wo, rank * 192, (blockIdx.x / 3) * DH, sb + MB_WO);
          else if (blockIdx.x < NSEG) bulk_load(sb + SM_X + 2 * XT, x + blockIdx.x * 32 * DM, XT, sb + MB_XS);
          else tma_load3(sb + SM_X + 2 * XT, &tm.x, 64, sb + MB_X + 16);
        }
        __syncwarp();
      } else {
        cluster_arrive();
      }
      xproj<1, 6 * c, 6 * c + 6>(acc, wa, xd0);
      if (!qk) {
        uint32_t q[4] = {0, 0, 0, 0};
#pragma unroll
        for (int rt = 0; rt < 2; rt++)
#pragma unroll
          for (int k = 0; k < 6; k++)
#pragma unroll
            for (int i = 0; i < 4; i++) sq_acc(q[i], wa[rt][c * 6 + k][i]);
#pragma unroll
        for (int i = 0; i < 4; i++) ss += bf_lo(q[i]) + bf_hi(q[i]);
      }
      if (c < 2 && CW) WG_WAIT(0);
    };
    chunk(IntC<0>()); chunk(IntC<1>()); chunk(IntC<2>());
    ss = warp_sum(ss);
    if (lane == 0) sts32(sb + SC_SS + 4 * (wg * 4 + w), __float_as_uint(ss));
    bar_arrive(11, 384);
  }
  STAMP(1);
  QSTAMP(8);
  STAMP(2);

  uint32_t t16 = sb + (w * 32 + lane) * 16;
  uint32_t mem_a = sb + SM_MEM + wg * 512 + lane * 16;
  uint32_t fin_a = sb + (lane & 7) * 16 + SM_BLK + (qk ? (wg ^ 1) * 4096 + w * 256 + (lane & 8) * 16 + (lane & 16) * 64
                                              : wg * 4096 + w * 1024 + (lane & 8) * 64 + (lane & 16) * 8);
  PIN(t16); PIN(mem_a); PIN(fin_a);
  const uint32_t fence_reg = mem_a;
  const uint32_t fin2 = qk ? 2048 : 256;
  auto do_export = [&](auto retire, uint32_t always) {
    WG_WAIT(0);
    uint32_t p[2];
#pragma unroll
    for (int i = 0; i < 2; i++) {
      p[i] = pack_bf16(acc[8 * i], acc[8 * i + 1]);
      sts128(t16 + SM_EXP + wg * 4096 + i * 2048, p[i], pack_bf16(acc[8 * i + 2], acc[8 * i + 3]),
             pack_bf16(acc[8 * i + 4], acc[8 * i + 5]), pack_bf16(acc[8 * i + 6], acc[8 * i + 7]));
    }
    if (decltype(retire)::value)
      asm volatile("{\n.reg .pred p, q;\nsetp.ne.u32 p, %2, 0;\nsetp.ne.u32 q, %2, 1;\n@p ld.shared.b32 %0, [%3];\n@q ld.shared.b32 %1, [%3 + 4];\n"
                   "setp.ne.u32 p, %0, %1;\n@p exit;\n}" : "+r"(p[0]), "+r"(p[1]) : "r"(always), "r"(sb + SC_DEAD) : "memory");
  };
  uint32_t o[8];
  auto import = [&]() { lds128(t16 + SM_EXP + (wg ^ 1) * 4096, o); lds128(t16 + SM_EXP + (wg ^ 1) * 4096 + 2048, o + 4); };
  auto finish_from = [&](int seg, const float* d) {
    const uint32_t a = fin_a + (seg & 3) * SEGB;
#pragma unroll
    for (int i = 0; i < 8; i++) o[i] = add_bf16(pack_bf16(d[2 * i], d[2 * i + 1]), o[i]);
    stsm4(a, o[0], o[1], o[2], o[3]);
    stsm4(a + fin2, o[4], o[5], o[6], o[7]);
  };
  auto finish = [&](int seg) { WG_WAIT(0); finish_from(seg, acc); };
  auto send_v = [&](int seg, int dst) {
    fence_async();
    if (seg < NSEG - 1 && !(XP & 2) && elect_one())
      bulk_s2s(mapa(sb + SM_VC + (seg & 1) * 8192, dst), sb + SM_BLK + (seg & 3) * SEGB, 8192, mapa(sb + MB_VX + (seg & 1) * 8, dst));
    __syncwarp();
  };
  auto wait_v = [&](int seg) {
    if (seg < NSEG - 1 && !(XP & 2)) {
      mbar_wait(sb + MB_VX + (seg & 1) * 8, (seg >> 1) & 1);
      if (elect_one()) mbar_expect(sb + MB_VX + (seg & 1) * 8, 8192);
      __syncwarp();
    }
  };
  auto export_seg = [&](int seg, uint32_t slot) { if (!(XP & (4 | 8192)) && elect_one()) seg_store(seg, slot, sb); __syncwarp(); };
  auto publish = [&](int seg) { if (!(XP & (4 | 16384)) && elect_one()) seg_publish(seg, sb); __syncwarp(); };
  do_export(BoolC<false>(), 0);
  QSTAMP(9);
  SCHED_FENCE(11);
  xproj<0, 0, 18>(acc, wa, xd0);
  bar_sync(3, 256);
  QSTAMP(10);
  cluster_wait();
  QSTAMP(11);
  mbar_wait(sb + MB_X + 8, 0);
  QSTAMP(12);
  import();
  finish(0);
  SCHED_FENCE(12);
  uint64_t dA = xd0 + (XT >> 4);
  xproj<1, 0, 18>(acc, wa, dA);
  bar_sync(3, 256);
  if (!qk && wg == 0 && w < 2) send_v(0, w);
  if (wg == 0 && w == 3) export_seg(0, 0);
  QSTAMP(13);
  if (qk && wg == 0 && w == 0) wait_v(0);
  QSTAMP(14);
  bar_arrive(13, 384);
  if (!qk) {
    do_export(BoolC<false>(), 0);
    SCHED_FENCE(15);
    xproj<0, 0, 18>(acc, wa, dA);
    if (threadIdx.x == 0 && !(XP & 8)) { mbar_expect(sb + MB_X, XT); tma_load3(sb + SM_X, &tm.x, 96, sb + MB_X); }
    bar_sync(3, 256);
    mbar_wait(sb + MB_X + 16, 0);
    import();
    finish(1);
    SCHED_FENCE(16);
    dA += XT >> 4;
    xproj<1, 0, 18>(acc, wa, dA);
  }
  QSTAMP(15);
  WG_WAIT(0);
  bar_sync(0, 384);
  if (wg == 0 && w == 3) publish(0);
  QSTAMP(16);
  const int ro = __shfl_sync(0xffffffffu, near_half(sb) ^ wg, 0);
  STAMP(5);
  const uint32_t always = __shfl_sync(0xffffffffu, lds32(sb + SC_DEAD + 12), 0);
  const int ah = qk ? 1 : 2;
  int b2 = qk ? 2 : 0;
  int s = 0;
  uint32_t hint_lo = (uint32_t)(uint64_t)tm.red + HINT_OFF + blockIdx.x + (lane & 1) * 4096 + (lane >> 1) * 16384;
  PIN(hint_lo);
  auto post_hint = [&]() {
    asm volatile("{\n.reg .pred p;\n.reg .b64 a;\n.reg .u32 t;\nsetp.lt.u32 p, %0, %1;\nmov.b64 a, {%2, %3};\nmov.u32 t, %%globaltimer_lo;\n"
                 "bfe.u32 t, t, 5, 6;\nor.b32 t, t, %4;\n@p st.relaxed.gpu.global.u8 [a], t;\n}"
                 :: "r"(t16), "r"(sb + 160), "r"(hint_lo + RED_SLOT(s)), "r"((uint32_t)((uint64_t)tm.red >> 32)), "r"(((s >> 2) + 1) << 6) : "memory");
  };
  auto memproj = [&](auto second, int id, uint32_t dep, float u0, float u1, float* r) {
    constexpr bool R1 = decltype(second)::value;
    uint32_t b[NUP][4], b0[4];
    if (R1) asm volatile("{\n.reg .pred p;\nsetp.eq.u32 p, %0, %1;\n@p exit;\n}" :: "r"(dep), "r"(id) : "memory");
    bar_sync(R1 ? 2 : 1, 256);
    PROF(0);
    ldsm4t(b0, mem_a);
#pragma unroll
    for (int q = 0; q < NUP; q++) {
      if (R1 && q == 2) {
        bar_sync(11, 256);
        SCHED_FENCE(id + 1);
      }
      ldsm4t(b[q], mem_a + MEM_BLK(q + 1));
    }
    mma16816z(&acc[0], wa[0][0], b0[0], b0[1]);
    mma16816z(&acc[4], wa[1][0], b0[0], b0[1]);
    mma16816z(&acc[8], wa[0][1], b0[2], b0[3]);
    mma16816z(&acc[12], wa[1][1], b0[2], b0[3]);
#pragma unroll
    for (int q = 1; q < 9; q++) {
      uint32_t* const c = b[(q - 1) % NUP];
      mma16816(&acc[0], wa[0][2 * q], c[0], c[1]);
      mma16816(&acc[4], wa[1][2 * q], c[0], c[1]);
      mma16816(&acc[8], wa[0][2 * q + 1], c[2], c[3]);
      mma16816(&acc[12], wa[1][2 * q + 1], c[2], c[3]);
      if (R1 && q + NUP == B3Q) bar_sync(3, 256);
      if (q + NUP < 9) ldsm4t_in(c, mem_a + MEM_BLK(q + NUP), always);
      else if (R1 && q + NUP < 11) lds128_in(c, t16 + SM_PART + (10 - q - NUP) * 2048, always);
      else if (!R1 && GATE && q == GATE) { bar_arrive(11, 256); lds128_in(c, sb + SC_DEAD, always); u0 = u1 = __uint_as_float(c[3]); }
    }
#pragma unroll
    for (int i = 0; i < 8; i++) {
      const float u = i < 4 ? u0 : u1;
      r[i] = R1 ? fmaf(acc[8 + i], u, (acc[i] + __uint_as_float(b[(8 + i / 4) % NUP][i & 3])) * u) : (GATE ? fmaf(acc[i], u, acc[8 + i]) : acc[i] + acc[8 + i]);
    }
  };
  if (ro == 0) {
#pragma unroll 1
    while (true) {
      do_export(BoolC<true>(), always);
      PROFP(3);
      if (s == 8) STAMP(6);
      float r[8];
      memproj(BoolC<false>(), 30, 0, 0.f, 0.f, r);
      sts128(t16 + SM_PART, __float_as_uint(r[0]), __float_as_uint(r[1]), __float_as_uint(r[2]), __float_as_uint(r[3]));
      sts128(t16 + SM_PART + 2048, __float_as_uint(r[4]), __float_as_uint(r[5]), __float_as_uint(r[6]), __float_as_uint(r[7]));
      bar_arrive(3, 256);
      PROF(1);
      bar_sync(9, 256);
      if (!(WE & 1) && s == NSEG - 1) break;
      post_hint();
      if (w == 3 && s) publish(s);
      if ((WE & 1) && s == NSEG - 1) break;
      if (w == 1) {
        uint32_t m[8];
        lds128(t16 + SM_MAX - 512, m); lds128(t16 + SM_MAX, m + 4);
        const int em = (wexp(amax4(amax4(*(const __half2*)&m[0], m), m + 4)) >> 3) + (int)(lds32(sb + SC_UNSC + (s & 1) * 8) >> 23) - 15;
        const int ex = max(s ? em : 0, (int)lds32(sb + SC_XMAX + 4 * s)) - 127 + (int)lds32(sb + SC_EXPW);
        sts32(sb + SC_UNSC + (~s & 1) * 8, (127 + min(max(ex, -120), 120)) << 23);
        __syncwarp();
        if (elect_one()) mbar_arrive(sb + MB_S);
      }
      SCHED_FENCE(9);
      bar_sync(5, qk ? N5 : 256);
      PROF(2);
      import();
      xproj<0, 0, NII>(acc, wa, dA);
      if (NII < 18) {
        if (qk) bar_sync(7, 384);
        xproj<0, NII, 18>(acc, wa, dA);
        if (!qk) bar_sync(7, 384);
      } else {
        if (F10) WG_WAIT(0);
        bar_sync(10, 256);
        if (F10) SCHED_FENCE(17);
      }
      dA += (int64_t)(b2 ? XT >> 4 : -(XT >> 3));
      finish(s + ah);
      if (w != 3) bar_arrive(13, 384);
      PROF(6);
      SCHED_FENCE(14);
      if (NOB & 2) bar_arrive(14, 256);
      bar_sync(12, 256);
      PROF(7);
      xproj<1, 0, 18, true>(acc, wa, dA);
      if (!(NOB & 2)) bar_arrive(14, 256);
      b2 = b2 == 2 ? 0 : b2 + 1;
      s++;
      if (w == 3) {
        const uint32_t slot = (ZR & 2) || s < lds32(sb + SC_EPO + 4) ? s & 7 : s;
        bar_sync(13, 384);
        export_seg(s, slot);
      }
      PROFP(8);
    }
    if (!qk) bar_arrive(5, 256);
    if (!(WE & 1) && w == 3) publish(NSEG - 1);
  } else {
    uint32_t km[4];
    auto send_km = [&]() {
      if (XP & (4 | 4096)) return;
      uint32_t t, u;
      lds64(sb + SC_TAG, t, u);
      t |= km[0] & ~1u; u += s * (NH * 4096);
      if (qk)
        asm volatile("{\n.reg .u32 o;\n.reg .u64 a;\nshr.u32 o, %0, 1;\nadd.u32 o, o, %1;\nmad.wide.u32 a, o, 1, %2;\nst.relaxed.gpu.global.v2.b32 [a], {%3,%4};\n}"
                     :: "r"(t16), "r"(u), "l"(g_km), "r"(t), "r"(km[1]) : "memory");
      else
        asm volatile("{\n.reg .u32 o;\n.reg .u64 a;\nadd.u32 o, %0, %1;\nmad.wide.u32 a, o, 1, %2;\nst.relaxed.gpu.global.v4.b32 [a], {%3,%4,%5,%6};\n}"
                     :: "r"(t16), "r"(u), "l"(g_km), "r"(t), "r"(km[1]), "r"(km[2]), "r"(km[3]) : "memory");
    };
#pragma unroll 1
    while (true) {
      do_export(BoolC<true>(), always);
      if (!qk && w == 2) send_v(s + 1, 0);
      PROFP(3);
      if (s == 8) STAMP(6);
      const uint32_t tl = ((t16 >> 8) ^ wg) & 1, am = (t16 & ~256u) - w * 256;
      const float un = __uint_as_float(lds32(sb + SC_UNSC + (s & 1) * 8));
      float r[8];
      if (qk) {
        uint32_t a0 = am + (tl ? SM_QM : SM_BLK + 8192 + (s & 3) * SEGB);
        float u0 = wg ? un * (SM_SCALE * LOG2E) : un, u1 = wg ? un : un * (SM_SCALE * LOG2E);
        PIN(a0); PIN(u0); PIN(u1);
        memproj(BoolC<true>(), 32, a0, u0, u1, r);
        const uint32_t p0 = pack_bf16(r[0], r[1]), p1 = pack_bf16(r[2], r[3]), p2 = pack_bf16(r[4], r[5]), p3 = pack_bf16(r[6], r[7]);
        stsm4(a0, p0, p1, p2, p3);
        bar_arrive(4, 256);
        km[0] = wg ? p2 : p0; km[1] = wg ? p3 : p1;
      } else {
        const uint32_t d0 = s < NSEG - 1 ? 0 : 2, d1 = s < NSEG - 1 ? 1 : 2;
        uint32_t r0 = mapa(t16 + SM_VM, d0), r1 = mapa(t16 + SM_VM, d1);
        PIN(r0); PIN(r1);
        memproj(BoolC<true>(), 34, r0 | r1, un, un, r);
        const uint32_t p0 = pack_bf16(r[0], r[1]), p1 = pack_bf16(r[2], r[3]), p2 = pack_bf16(r[4], r[5]), p3 = pack_bf16(r[6], r[7]);
        const uint32_t v0 = wg ? p2 : p0, v1 = wg ? p3 : p1, v2 = wg ? p0 : p2, v3 = wg ? p1 : p3;
        st_async4(r0, v0, v1, v2, v3, mapa(sb + MB_S, d0));
        st_async4(r1, v0, v1, v2, v3, mapa(sb + MB_S, d1));
        bar_arrive(5, 256);
        sts128(t16 + SM_VM, v0, v1, v2, v3);
        __syncwarp();
        if (elect_one()) mbar_arrive(sb + MB_S);
        km[0] = v0; km[1] = v1; km[2] = v2; km[3] = v3;
      }
      if (!(WE & 2) && s == NSEG - 1) break;
      PROF(1);
      auto rearm = [&]() { mbar_wait(sb + MB_S, s & 1); if (elect_one()) mbar_expect(sb + MB_S, qk ? 640 + 2048 : 1280); __syncwarp(); };
      if ((WE & 2) && s == NSEG - 1 && w != 1) {
      } else if (w == 1) {
        if ((t16 & 384) == 0) stg_relaxed(tm.red + (RED_SLOT(s + 2) + RED_LINE(blockIdx.x)) + (t16 & 112), 0, 0, 0, 0);
        uint32_t base, own;
        lds64(sb + SC_EPO, base, own);
        if (!(ZR & 1))
        asm volatile("{\n.reg .pred p, q;\nsetp.lt.s32 p, %0, %1;\n@p st.shared.b32 [%2], %3;\nelect.sync _|q, 0xffffffff;\n@q cp.async.cg.shared.global [%4], [%5], 16;\n}"
                     :: "r"(lds32v(sb + SC_OFL) - base), "r"(s - 7), "r"(sb + SC_EPO + 4), "r"(min(own, s + 1)), "r"(sb + SC_OFL), "l"(tm.oflag + blockIdx.x * 128) : "memory");
      } else if (w == 0) {
        const int tn = s + ah + 1;
        if (RFW) mbar_wait(sb + MB_S, s & 1);
        if (tn + 1 < NSEG && !(XP & 8) && elect_one()) {
          const int b0 = b2 == 2 ? 0 : b2 + 1;
          mbar_expect(sb + MB_X + 8 * b0, XT);
          tma_load3(sb + SM_X + b0 * XT, &tm.x, (tn + 1) * 32, sb + MB_X + 8 * b0);
        }
        if (tn < NSEG && (!(XP & 8) || tn < 3)) mbar_wait(sb + MB_X + 8 * b2, (tn / 3) & 1);
      } else if (w == 2) {
        if (!qk) { if (VW2 < 1) send_v(s + 1, 0); if (VW2 < 2) send_v(s + 1, 1); }
      } else if (qk || !NIC) {
        rearm();
      }
      __syncwarp();
      send_km();
      if ((WE & 2) && s == NSEG - 1) break;
      import();
      PROF(4);
      SCHED_FENCE(10);
      if (NIC) {
        if (qk) bar_sync(7, NII < 18 ? 384 : 256);
        xproj<0, 0, NIC>(acc, wa, dA);
        if (!qk) { if (w == 3) rearm(); bar_sync(7, NII < 18 ? 384 : 256); }
      } else {
        bar_sync(7, NII < 18 ? 384 : 256);
      }
      if (NOB & 1) bar_arrive(12, 256);
      xproj<0, NIC, 18>(acc, wa, dA);
      if (!(NOB & 1)) bar_arrive(12, 256);
      dA += (int64_t)(b2 ? XT >> 4 : -(XT >> 3));
      finish(s + ah);
      if (qk && w == 0) wait_v(s + 1);
      bar_arrive(13, 384);
      PROF(6);
      SCHED_FENCE(13);
      bar_sync(14, 256);
      PROF(7);
      xproj<1, 0, 18>(acc, wa, dA);
      b2 = b2 == 2 ? 0 : b2 + 1;
      s++;
      PROFP(8);
    }
    if (!(WE & 2)) {
      send_km();
      PIN(t16);
      if (t16 - sb < 128) stg_relaxed(tm.red + (RED_SLOT(NSEG + 1) + RED_LINE(head_id() * 3 + rank)) + (t16 & 112), 0, 0, 0, 0);
    }
  }
  bar_arrive(0, 384);
  STAMP(3);
  cluster_sync();
  STAMP(4);
}

DI void attn_role(const uint32_t sb, unsigned char* smem_raw, const RMaps& tm, const uint32_t RANK, const bf16* __restrict__ x, const bf16* __restrict__ mem0,
                  const int w, const int lane) {
  const int t2 = w * 32 + lane;
  uint32_t wo[8][4], w1[8][4];
  const uint32_t wo_lane = sb + ((lane & 7) + ((lane >> 4) << 3)) * 128 + (((w + 4 * ((lane >> 3) & 1)) ^ (lane & 7)) << 4);
  unsigned char* const g_red = tm.red;
  {
    const uint32_t tag = *(volatile unsigned*)&g_epoch + 1;
    QSTAMP(0);
    bar_sync(0, 160);
    QSTAMP(1);
    cluster_arrive();
    __half2 hx = __float2half2_rn(0.f);
    if (t2 == 0) { sts32(sb + SC_OFL, (tag - 1) * NSEG); sts64(sb + SC_EPO, (tag - 1) * NSEG + 1, NSEG); sts64(sb + SC_TAG, tag & 1, blockIdx.x / 3 * 4096 + (RANK < 2 ? RANK * 1024 - (sb >> 1) : 2048 - sb)); sts32(sb + SC_UNSC, __float_as_uint(1.f)); sts128(sb + SC_DEAD, 0, 0, 0, 0x3f800000u); sts64(sb + SC_FPAR, 0, 0); sts128(sb + SC_ONES, 0x3f803f80u, 0x3f803f80u, 0x3f803f80u, 0x3f803f80u); }
    WSTAMP(27);
    uint32_t q[8] = {0, 0, 0, 0, 0, 0, 0, 0};
    QSTAMP(2);
    mbar_wait(sb + MB_WO3, 0);
    QSTAMP(3);
    uint32_t mv[5][4];
#pragma unroll
    for (int i = 0; i < 5; i++) {
      ldsm4(mv[i], sb + SM_M0 + (lane & 7) * (DM * 2) + min(w + 4 * i, 17) * 64 + (lane >> 3) * 16);
      if (blockIdx.x == 0) hx = amax4(hx, mv[i]);
    }
#pragma unroll
    for (int k = 0; k < 8; k++) {
      ldsm4t(wo[k], wo_lane + SM_WO3 + k * 2048); ldsm4t(w1[k], wo_lane + SM_WOST + k * 2048);
#pragma unroll
      for (int i = 0; i < 4; i++) { sq_acc(q[i], wo[k][i]); sq_acc(q[i], w1[k][i]); }
    }
    bar_sync(6, 128);
#pragma unroll
    for (int k = 0; k < 8; k++) sts128(sb + SM_WO3 + t2 * 16 + k * 2048, wo[k][0], wo[k][1], wo[k][2], wo[k][3]);
#pragma unroll
    for (int i = 0; i < 5; i++) {
      const int c = (w + 4 * i) * 32;
      if (c < DM) stsm4t(sb + SM_MEM + (c + c / 192 * 64 + lane) * 16, mv[i][0], mv[i][1], mv[i][2], mv[i][3]);
    }
    bar_arrive(1, 256); bar_arrive(2, 256); bar_arrive(9, 256);
    QSTAMP(4);
    mbar_wait(sb + MB_WO, 0);
    QSTAMP(5);
#pragma unroll
    for (int k = 0; k < 8; k++) ldsm4t(wo[k], wo_lane + SM_X + XT + k * 2048);
    fence_async();
    bar_sync(6, 128);
    if (t2 == 32) tma_load3(sb + SM_X + XT, &tm.x, 32, sb + MB_X + 8);
    __syncwarp();
#pragma unroll
    for (int k = 0; k < 8; k++)
#pragma unroll
      for (int i = 0; i < 4; i++) sq_acc(q[4 + i], wo[k][i]);
    float ss = 0.f;
#pragma unroll
    for (int i = 0; i < 8; i++) ss += bf_lo(q[i]) + bf_hi(q[i]);
    ss = warp_sum(ss);
    if (lane == 0) sts32(sb + SC_SS + 4 * (8 + w), __float_as_uint(ss));
    if (blockIdx.x < NSEG) {
      mbar_wait(sb + MB_XS, 0);
#pragma unroll
      for (int i = 0; i < 18; i++) { uint32_t v[4]; lds128(sb + SM_X + 2 * XT + t2 * 16 + i * 2048, v); hx = amax4(hx, v); }
      fence_async();
      bar_sync(6, 128);
      if (t2 == 32) tma_load3(sb + SM_X + 2 * XT, &tm.x, 64, sb + MB_X + 16);
      __syncwarp();
    }
    sts32(sb + SC_SS + 4 * (12 + w), wexp(hx));
    QSTAMP(6);
    bar_sync(11, 384);
    QSTAMP(7);
    if (t2 == 0) {
      float a[16];
#pragma unroll
      for (int i = 0; i < 4; i++) lds128f(sb + SC_SS + 16 * i, &a[4 * i]);
      stg_relaxed(&g_stats[blockIdx.x * 2], __float_as_uint(((a[0] + a[1]) + (a[2] + a[3])) + ((a[4] + a[5]) + (a[6] + a[7]))),
                  __float_as_uint((a[8] + a[9]) + (a[10] + a[11])),
                  max(max(__float_as_uint(a[12]), __float_as_uint(a[13])), max(__float_as_uint(a[14]), __float_as_uint(a[15]))), tag);
    }
    __syncwarp();
    WSTAMP(24);
    QSTAMP(8);
    cluster_wait();
    QSTAMP(9);
    if (w == 0) {
      uint4 v[3];
      int n = 0;
      while (true) {
#pragma unroll
        for (int i = 0; i < 3; i++) v[i] = ldg_relaxed(&g_stats[(i * 32 + lane) * 2]);
        if (__all_sync(0xffffffffu, v[0].w == tag && v[1].w == tag && v[2].w == tag) || ++n > SPIN_LIMIT) break;
        __nanosleep(100);
      }
      WSTAMP(25);
      QSTAMP(10);
      const float sv = warp_sum(__uint_as_float(v[0].x) + __uint_as_float(v[1].x) + __uint_as_float(v[2].x));
      const float so = warp_sum(__uint_as_float(v[0].y) + __uint_as_float(v[1].y) + __uint_as_float(v[2].y));
      const int expW = ((int)(__float_as_uint(sv) >> 23) + (int)(__float_as_uint(so) >> 23) - 254 + 2 + 10 + 1) >> 1;
      sts32(sb + SC_XMAX + 4 * lane, v[0].z); sts32(sb + SC_XMAX + 128 + 4 * lane, v[1].z);
      sts32(sb + SC_EXPW, expW + 1 - 15);
      if (blockIdx.x == 0 && lane == 0) *(volatile unsigned*)&g_epoch = tag;
      sts32(sb + SC_FPAR + 4, 1);
    } else if (w < 3) {
      const uint32_t u = blockIdx.x >> 4;
      unsigned char* const z = g_red + 98304 + (blockIdx.x & 15) * 128 + (u & 1) * 2048 + (u & 6) * 4096 + (((u >> 1) ^ w) & 1) * 4096 + lane * 4;
      stg_relaxed32(z, 0);
      uint32_t best = 0xffffffffu;
#pragma unroll 1
      for (int i = 0; i < 64; i++) {
        uint32_t dt;
        asm volatile("{\n.reg .pred p;\n.reg .u32 c, v;\nmov.u32 c, %%clock;\n"
                     "atom.relaxed.gpu.global.exch.b32 v, [%1], 0;\nsetp.eq.u32 p, v, 0;\nmov.u32 %0, 0;\n@p mov.u32 %0, %%clock;\nsub.u32 %0, %0, c;\n}"
                     : "=r"(dt) : "l"(z) : "memory");
        best = min(best, dt);
        if (lds32v(sb + SC_FPAR + 4) && i >= NPROBE - 1) break;
      }
      sts32(sb + SC_LAT + (w - 1) * 4, best);
    }
    QSTAMP(11);
    bar_sync(13, 384);
    bar_arrive(0, 384);
    QSTAMP(12);
    WSTAMP(26);
  }

  const uint32_t nh = __shfl_sync(0xffffffffu, near_half(sb), 0);
  uint32_t l16 = sb + lane * 16;
  PIN(l16);
#define LV ((l16 >> 4) & 31)
#define fence_reg l16
  const uint32_t red_lo = (uint32_t)(uint64_t)g_red, red_hi = (uint32_t)((uint64_t)g_red >> 32);
  uint32_t lp;
  auto slot = [&](int s, uint32_t c, uint32_t ofs) {
    const uint32_t lo = lp | (red_lo + ((w >> 1) * 4 + (w & 1) * 2 + ((w ^ c) & 1)) * 4096 + RED_SLOT(s) + ofs);
    uint64_t a; asm("mov.b64 %0, {%1, %2};" : "=l"(a) : "r"(lo), "r"(red_hi));
    return (unsigned char*)a;
  };
  const uint32_t always = __shfl_sync(0xffffffffu, lds32(sb + SC_DEAD + 12), 0);
  const int mode0 = RANK < 2 ? w : w | 4;
  auto hint_addr = [&](int s) { return min(LV, 23u) * 4 + (red_lo + HINT_OFF + nh * 4096 + w * 16384 + RED_SLOT(s)); };
  auto load_hints = [&](uint32_t lo) {
    uint64_t a; asm("mov.b64 %0, {%1, %2};" : "=l"(a) : "r"(lo), "r"(red_hi));
    return ldg_relaxed32((const void*)a);
  };
  int s = 0;
  bool bad = false;
#pragma unroll 1
  while (true) {
    const uint32_t par = s & 1;
    uint32_t vx[4][4], hints;
    auto load_vx = [&]() {
      const uint32_t va = l16 + (RANK < 2 ? SM_VC + par * 8192 : SM_BLK + (s & 3) * SEGB) + w * 1024 + ((LV >> 3) & 1) * 384 - (LV >> 4) * 128;
#pragma unroll
      for (int i = 0; i < 4; i++) ldsm4(vx[i], va + (i & 1) * 4096 + (i >> 1) * 256);
    };
    auto retire = [&](uint32_t x) {
      asm volatile("{\n.reg .pred p;\nsetp.eq.u32 p, %0, 0;\n@p exit;\n}" :: "r"(vx[0][0] | vx[1][0] | vx[2][0] | vx[3][0] | x) : "memory");
    };
    auto scores = [&](auto memkeys, auto first, float* sc) {
      constexpr bool MK = decltype(memkeys)::value, FIRST = decltype(first)::value;
      uint32_t kb[4][4], qb[2][4];
      const uint32_t m = LV >> 3;
      uint32_t kaddr = l16 + SM_BLK + 4096 + (s & 3) * SEGB + w * 2048 + (m & 1) * (MK ? 128 : 896) - (m >> 1) * 128;
      if (MK) { PIN(kaddr); }
      else {
#pragma unroll
        for (int k = 0; k < 4; k++) ldsm4t(kb[k], kaddr + k * 256);
      }
      if (FIRST) { load_vx(); retire(MK ? kaddr : kb[0][0] | kb[1][0] | kb[2][0] | kb[3][0] | l16); bar_sync(4, 256); PROF(4); }
      ldsm4t(qb[0], l16 + SM_QM);
      if (MK) ldsm4t(kb[0], kaddr);
      ldsm4t(qb[1], l16 + SM_QM + 512);
      if (MK) ldsm4t(kb[2], kaddr + 512);
      float c[4][4];
      mma16816z(c[0], kb[0], qb[0][0], qb[0][1]); mma16816z(c[1], kb[MK ? 0 : 1], qb[0][2], qb[0][3]);
      mma16816z(c[2], kb[2], qb[1][0], qb[1][1]); mma16816z(c[3], kb[MK ? 2 : 3], qb[1][2], qb[1][3]);
      if (FIRST && B5POS == 0) bar_arrive(5, N5);
#pragma unroll
      for (int i = 0; i < (MK ? 2 : 4); i++) sc[i] = ((c[0][i] + c[1][MK ? i + 2 : i]) + c[2][i]) + c[3][MK ? i + 2 : i];
    };
    auto send = [&](auto memkeys) {
      constexpr bool MK = decltype(memkeys)::value;
      constexpr int N = MK ? 1 : 2;
      const uint32_t sa = sb + LV * 4 + SM_E + (MK ? 1024 + RANK * 128 : RANK * 512 + w * 256);
      uint32_t ra[N][2], mb[N][2];
#pragma unroll
      for (int i = 0; i < N; i++)
#pragma unroll
        for (int j = 0; j < 2; j++) {
          ra[i][j] = mapa(sa + i * 128, j ? 2 : RANK ^ 1); mb[i][j] = mapa(sb + MB_S, j ? 2 : RANK ^ 1);
          PIN(ra[i][j]);
        }
      float sc[4];
      scores(memkeys, BoolC<true>(), sc);
      uint32_t e[N];
#pragma unroll
      for (int i = 0; i < N; i++) {
        e[i] = pack_bf16(ex2(sc[2 * i]), ex2(sc[2 * i + 1]));
        if (!(fmaxf(fabsf(sc[2 * i]), fabsf(sc[2 * i + 1])) <= E_LIM)) e[i] = 0x7fff7fffu;
        st_async1(ra[i][0], e[i], mb[i][0]);
        st_async1(ra[i][1], e[i], mb[i][1]);
      }
#pragma unroll
      for (int i = 0; i < N; i++) sts32(sa + i * 128, e[i]);
      __syncwarp();
      if (l16 == sb) mbar_arrive(sb + MB_S);
      PROF(5);
    };
    const int mode = bad ? 8 : mode0;
    if (mode < 2) {
      send(BoolC<false>());
    } else if (mode == 2) {
      send(BoolC<true>());
    } else if (mode == 8) {
      load_vx();
      retire(l16);
      const uint32_t fp = lds32(sb + SC_FPAR);
      bar_sync(6, 128);
      if (w == 0 && l16 == sb) { sts32(sb + SC_FPAR, fp ^ 1); mbar_expect(sb + MB_F, 3072); }
      if (RANK < 2 && w < 3) {
        float sc[4] = {0.f, 0.f, 0.f, 0.f};
        if (w < 2) scores(BoolC<false>(), BoolC<false>(), sc); else scores(BoolC<true>(), BoolC<false>(), sc);
#pragma unroll 1
        for (int r = 0; r < 3; r++)
          st_async4(mapa(l16 + SM_FB + RANK * 1536 + w * 512, r), __float_as_uint(sc[0]), __float_as_uint(sc[1]), __float_as_uint(sc[2]), __float_as_uint(sc[3]), mapa(sb + MB_F, r));
      }
      mbar_wait(sb + MB_F, fp);
      float a[12];
#pragma unroll
      for (int j = 0; j < 3; j++) {
        float b[4];
        lds128f(l16 + SM_FB + j * 512, a + 4 * j); lds128f(l16 + SM_FB + 1536 + j * 512, b);
#pragma unroll
        for (int i = 0; i < 4; i++) a[4 * j + i] += b[i];
      }
      float m0 = fmaxf(fmaxf(fmaxf(a[0], a[2]), fmaxf(a[4], a[6])), a[8]), m1 = fmaxf(fmaxf(fmaxf(a[1], a[3]), fmaxf(a[5], a[7])), a[9]);
#pragma unroll
      for (int o = 4; o < 32; o <<= 1) { m0 = fmaxf(m0, __shfl_xor_sync(0xffffffffu, m0, o)); m1 = fmaxf(m1, __shfl_xor_sync(0xffffffffu, m1, o)); }
#pragma unroll
      for (int i = 0; i < 5; i++) {
        const uint32_t ea = sb + SM_E + LV * 4 + (i < 4 ? i * 128 : 1024);
        sts32(ea, pack_bf16(ex2(a[2 * i] - m0), ex2(a[2 * i + 1] - m1)));
        sts32(ea + (i < 4 ? 512 : 128), 0x3f803f80u);
      }
      __syncwarp();
    } else {
      load_vx();
      if (mode == 3) bar_arrive(4, 256);
      retire(l16 + 1);
    }
    {
      uint32_t wa[4], wb[4], oc[4];
      constexpr int WS = 2048;
      const uint32_t w3a = l16 + SM_WO3 + w * 512;
      lds128(w3a + KP(0) * WS, wa); lds128(w3a + KP(1) * WS, wb); lds128(sb + SC_ONES, oc);
      if (B5POS == 1 && mode < 3) bar_arrive(5, N5);
      uint32_t e[10], p[5], vm[4], ob[4];
      float o0[4], o1[4], f[3][2][4], rs[4];
      reserve2(vm); reserve2(vm + 2); reserve2(e + 8);
      hints = hint_addr(s);
      PIN(hints);
      if (CLR & 2) asm volatile("{\n.reg .pred p;\nsetp.eq.u32 p, %0, 0;\n@p exit;\n}" :: "r"(wa[0] | wb[0] | oc[0] | hints) : "memory");
      mbar_wait(sb + MB_S, par);
      PROF(6);
      ldsm4t(e, l16 + SM_E); ldsm2t_in(e + 8, l16 + SM_E + 1024, always); ldsm4t(e + 4, l16 + SM_E + 512);
      lds128_in(vm, l16 + w * 512 + SM_VM, always);
      const float scl = __uint_as_float(lds32(sb + SC_UNSC + 8 - par * 8));
      hints = load_hints(hints);
      if (GF & 1) SCHED_FENCE(4);
#pragma unroll
      for (int i = 0; i < 4; i++) p[i] = mul_bf16(e[i], e[4 + i]);
      p[4] = mul_bf16(e[8], e[9]);
      if (MO & 4) {
        float a0[4], a1[4];
        mma16816z(o0, vx[0], p[0], p[1]); mma16816z(o1, vx[1], p[0], p[1]);
        mma16816z(a0, vx[2], p[2], p[3]); lds128_in(vx[2], w3a + KP(2) * WS, always);
        mma16816z(a1, vx[3], p[2], p[3]); lds128_in(vx[3], w3a + KP(3) * WS, always);
        mma1688(o0, vm[0], vm[1], p[4]); mma1688(o1, vm[2], vm[3], p[4]);
        mma16816z(rs, oc, p[0], p[1]); mma16816(rs, oc, p[2], p[3]); mma1688(rs, oc[0], oc[1], p[4]);
#pragma unroll
        for (int i = 0; i < 4; i++) { o0[i] += a0[i]; o1[i] += a1[i]; }
      } else {
      mma16816z(o0, vx[0], p[0], p[1]); mma16816z(o1, vx[1], p[0], p[1]); mma16816z(rs, oc, p[0], p[1]);
      mma16816(o0, vx[2], p[2], p[3]); lds128_in(vx[2], w3a + KP(2) * WS, always);
      mma16816(o1, vx[3], p[2], p[3]); lds128_in(vx[3], w3a + KP(3) * WS, always);
      mma16816(rs, oc, p[2], p[3]);
      mma1688(o0, vm[0], vm[1], p[4]); mma1688(o1, vm[2], vm[3], p[4]); mma1688(rs, oc[0], oc[1], p[4]);
      }
      stsm4(l16 + w * 512 + SM_OB, pack_bf16(o0[0], o0[1]), pack_bf16(o0[2], o0[3]), pack_bf16(o1[0], o1[1]), pack_bf16(o1[2], o1[3]));
      bar_sync(6, 128);
      PROF(7);
      ldsm4t_in(oc, l16 + SM_OB, always);
      bad = __any_sync(0xffffffffu, !(rs[0] + rs[1] > 0.f) && !bad);
      rs[0] *= scl; rs[1] *= scl;
      asm volatile("{\n.reg .pred p;\nsetp.ne.u32 p, %1, 0;\n@p rcp.approx.ftz.f32 %0, %0;\n}" : "+f"(rs[0]) : "r"(always));
      asm volatile("{\n.reg .pred p;\nsetp.ne.u32 p, %1, 1;\n@p rcp.approx.ftz.f32 %0, %0;\n}" : "+f"(rs[1]) : "r"(always));
      asm volatile("lop3.b32 %0, %1, %2, %3, 0xfe;" : "=r"(lp) : "r"((l16 & 128) * 2), "r"((l16 & 256) * 4), "r"(l16 & 112));
      if (bad) continue;
      ldsm4t(ob, l16 + SM_OB + 512);
      mma16816z(f[2][0], wa, oc[0], oc[1]); mma16816z(f[2][1], wb, oc[2], oc[3]);
      mma16816z(f[0][0], wo[0], oc[0], oc[1]); mma16816z(f[0][1], wo[4], oc[2], oc[3]);
      mma16816z(f[1][0], w1[0], oc[0], oc[1]); mma16816z(f[1][1], w1[4], oc[2], oc[3]);
      ldsm4t_in(oc, l16 + SM_OB + 1024, always);
      mma16816(f[2][0], vx[2], ob[0], ob[1]); lds128_in(vx[2], w3a + KP(4) * WS, always);
      mma16816(f[2][1], vx[3], ob[2], ob[3]); lds128_in(vx[3], w3a + KP(5) * WS, always);
      mma16816(f[0][0], wo[1], ob[0], ob[1]); mma16816(f[0][1], wo[5], ob[2], ob[3]);
      mma16816(f[1][0], w1[1], ob[0], ob[1]); mma16816(f[1][1], w1[5], ob[2], ob[3]);
      ldsm4t_in(ob, l16 + SM_OB + 1536, always);
      mma16816(f[0][0], wo[2], oc[0], oc[1]); mma16816(f[0][1], wo[6], oc[2], oc[3]);
      mma16816(f[2][0], vx[2], oc[0], oc[1]); lds128_in(vx[2], w3a + KP(6) * WS, always);
      mma16816(f[2][1], vx[3], oc[2], oc[3]); lds128_in(vx[3], w3a + KP(7) * WS, always);
      mma16816(f[1][0], w1[2], oc[0], oc[1]); mma16816(f[1][1], w1[6], oc[2], oc[3]);
      mma16816(f[0][0], wo[3], ob[0], ob[1]); mma16816(f[0][1], wo[7], ob[2], ob[3]);
      mma16816(f[1][0], w1[3], ob[0], ob[1]); mma16816(f[1][1], w1[7], ob[2], ob[3]);
      mma16816(f[2][0], vx[2], ob[0], ob[1]); mma16816(f[2][1], vx[3], ob[2], ob[3]);
      bar_arrive(7, NII < 18 ? 384 : 256);
      lds128_in(ob, sb + SC_DEAD, always);
      uint32_t h[3][2];
#pragma unroll
      for (int j = 0; j < 3; j++)
#pragma unroll
        for (int i = 0; i < 2; i++)
        {
          scale_sum(f[j][1][2 * i], f[j][0][2 * i], rs[0], always); scale_sum(f[j][1][2 * i + 1], f[j][0][2 * i + 1], rs[1], always);
          h[j][i] = pack_f16(f[j][1][2 * i], f[j][1][2 * i + 1]);
        }
      const uint32_t rofs = RANK * 32768;
      red_f16x8(slot(s, RANK >> 1, rofs), h[0][0], h[1][0], h[2][0], 0x3c00u);
      red_f16x8(slot(s, (RANK >> 1) ^ 1, rofs), h[0][1], h[1][1], h[2][1], 0x3c00u);
      if (NII == 18) bar_arrive(10, 256);
      SCHED_FENCE(5);
      l16 += ob[B7R];
    }
    {
    PROF(8);
    const uint32_t ma0 = l16 + SM_MEM + w * 128 + (LV >> 3) * 896 + nh * 512;
    const unsigned char* const sl[2] = {slot(s, nh, 0), slot(s, nh ^ 1, 0)};
    uint32_t dl = gtime() - 1984;
    uint32_t late = latest_hint(hints, dl, s);
    if (late >= 64) {
      int n = 0;
#pragma unroll 1
      do {
        hints = load_hints(hint_addr(s));
        dl = gtime() - 1984;
        late = latest_hint(hints, dl, s);
      } while (late >= 64 && ++n < SPIN_LIMIT);
    }
    dl += late * 32 + tm.poll;
    PROF(9);
    {
      auto wait_until = [&](uint32_t t) {
        asm volatile("{\n.reg .pred p;\n.reg .s32 c;\n.reg .u64 t;\nTL: mov.u64 t, %%globaltimer;\ncvt.u32.u64 c, t;\nsub.s32 c, c, %0;\nsetp.lt.s32 p, c, 0;\n@p bra.uni TL;\n}" :: "r"(t + (l16 & 15)) : "memory");
      };
      uint4 v[2][3];
      auto load = [&](int c) {
#pragma unroll
        for (int r = 0; r < 3; r++) v[c][r] = ldg_relaxed(sl[c ^ (r >> 1)] + r * 32768);
      };
      auto decode = [&](int c, int n) {
        uint32_t q[9];
        __half2 hm;
        const uint32_t ma = ma0 ^ (c * 512);
#pragma unroll
        for (int i = 0; i < 9; i++) {
          const uint32_t h = i % 3 == 0 ? v[c][i / 3].x : (i % 3 == 1 ? v[c][i / 3].y : v[c][i / 3].z);
          const float2 f = __half22float2(*(const __half2*)&h);
          q[i] = pack_bf16(f.x, f.y);
          hm = i ? __hmax2(hm, __habs2(*(const __half2*)&h)) : __habs2(*(const __half2*)&h);
        }
#pragma unroll
        for (int r = 0; r < 3; r++) stsm4(ma + r * 4096, q[3 * r], q[3 * r + 1], q[3 * r + 2], r < 2 ? v[c][r].w : *(const uint32_t*)&hm);
        const bool done = __all_sync(0xffffffffu, v[c][0].w == 0x5000u && v[c][1].w == 0x5000u && v[c][2].w == 0x5000u) || n > SPIN_LIMIT;
        asm volatile("{\n.reg .pred p;\nsetp.ne.u32 p, %0, 0;\n@p bar.arrive %1, 256;\n}" :: "r"((int)done), "r"(1 + c) : "memory");
        return done;
      };
      if (LEAD) { wait_until(dl - LEAD); load(1); }
      int n = MO & 1 ? l16 & 15 : 0;
      if (MO & 1) PIN(n);
      if (MO & 2) {
        const uint32_t t = __shfl_sync(0xffffffffu, dl, 0);
        asm volatile("{\n.reg .pred p;\n.reg .s32 c;\nTL: mov.u32 c, %%globaltimer_lo;\nsub.s32 c, c, %0;\nsetp.lt.s32 p, c, 0;\n@p bra.uni TL;\n}" :: "r"(t) : "memory");
      } else wait_until(dl);
      PROF(10);
#pragma unroll 1
      do {
        load(0);
        if (!LEAD) load(1);
        asm volatile("{\n.reg .pred p;\nsetp.eq.u32 p, %0, 0;\n@p bar.sync 13, 384;\n}" :: "r"(n) : "memory");
      } while (!decode(0, n++));
      PROF(11);
#pragma unroll 1
      while (!decode(1, n++)) load(1);
      bar_arrive(9, 256);
      PROF(12);
    }
    PROF(13);
    if (++s == NSEG - 1) break;
    }
  }
#undef fence_reg
  if (RANK < 2) bar_arrive(4, 256);
  bar_sync(0, 384);
  cluster_sync();
}

__global__ void __cluster_dims__(3, 1, 1) __launch_bounds__(384, 1)
rec_kernel(const __grid_constant__ RMaps tm, const bf16* __restrict__ x, const bf16* __restrict__ mem0) {
  extern __shared__ __align__(1024) unsigned char smem_raw[];
  const uint32_t sb = smem_u32(smem_raw);
  const int tid = threadIdx.x, lane = tid & 31;
  const int wg = __shfl_sync(0xffffffffu, tid >> 7, 0);
  const int w = __shfl_sync(0xffffffffu, (tid >> 5) & 3, 0);
  uint32_t rank; asm("mov.u32 %0, %%cluster_ctarank;" : "=r"(rank));
  STAMP(0);
  asm volatile("griddepcontrol.launch_dependents;" ::: "memory");
    if (tid == 0) {
      const int h = blockIdx.x / 3;
      mbar_init(sb + MB_XS, 1);
      for (int i = 0; i < 3; i++) { mbar_init(sb + MB_W + 8 * i, 1); mbar_init(sb + MB_X + 8 * i, 1); }
      mbar_init(sb + MB_WO3, 1);
      fence_async();
      load_w(sb, tm, rank, 0);
      mbar_expect(sb + MB_X, XT);
      tma_load3(sb + SM_X, &tm.x, 0, sb + MB_X);
      if (WPOS == 2) load_w(sb, tm, rank, 1);
      mbar_expect(sb + MB_WO3, 32768 + 8 * DM * 2);
      tma_load(sb + SM_WOST, &tm.wo, rank * 192 + 64, h * DH, sb + MB_WO3);
      tma_load(sb + SM_WO3, &tm.wo, rank * 192 + 128, h * DH, sb + MB_WO3);
      bulk_load(sb + SM_M0, mem0, 8 * DM * 2, sb + MB_WO3);
      if (WOPF) tma_prefetch(&tm.wo, rank * 192, h * DH);
      if (WPOS == 1) load_w(sb, tm, rank, 1);
      load_w(sb, tm, rank, 2);
      mbar_init(sb + MB_WO, 1);
      mbar_init(sb + MB_S, rank < 2 ? 5 : 6);
      mbar_init(sb + MB_F, 1);
      mbar_init(sb + MB_VX, 1); mbar_init(sb + MB_VX + 8, 1);
      asm volatile("fence.mbarrier_init.release.cluster;" ::: "memory");
      fence_async();
      mbar_expect(sb + MB_X + 8, XT); mbar_expect(sb + MB_X + 16, XT);
      mbar_expect(sb + MB_WO, 16384); mbar_expect(sb + MB_XS, XT);
      mbar_expect(sb + MB_S, rank < 2 ? 640 + 2048 : 1280);
      mbar_expect(sb + MB_VX, 8192); mbar_expect(sb + MB_VX + 8, 8192);
    }
  __syncwarp();
  if (wg < 2) {
    asm volatile("setmaxnreg.inc.sync.aligned.u32 192;");
    __syncwarp();
    QSTAMP(0);
    if (tid < 32) bar_arrive(0, 160);
    QSTAMP(1);
    proj_role(sb, tm, x, rank, wg, w, lane);
  } else {
    asm volatile("setmaxnreg.dec.sync.aligned.u32 120;");
    attn_role(sb, smem_raw, tm, rank, x, mem0, w, lane);
  }
}

constexpr int NAUX = 36;
constexpr int A_ST = 6, A_STAGE = 8192 + 12288, A_W8 = A_ST * A_STAGE, A_EXC = A_W8 + A_ST * 1536, A_ROWS = 57;
constexpr int A_IN = A_EXC + 8 * 2304, A_INB = 3 * SEGB, A_OST = A_IN + 2 * A_INB, A_P = A_OST + 8192, A_G = A_P + 3072;
constexpr int A_BAR = A_G + 1024;
constexpr int A_XT = A_BAR + 1024, A_XW = A_XT;
constexpr int A_TOTAL = A_XT + 4096;
static_assert(A_IN % 1024 == 0 && A_XT % 1024 == 0 && A_IN >= 4 * XT && A_IN + 64 * DM * 2 <= A_BAR && A_TOTAL <= 232448, "side kernel shared memory");
struct AMaps { CUtensorMap x, wa, wa8, o, o3, o16, wob, woa, woa16; const unsigned char* red; uint32_t poll; };

DI void wgmma_n192_ss_nt(float* d, uint64_t da, uint64_t db, int acc) {
  asm volatile("{\n.reg .pred p;\nsetp.ne.b32 p, %98, 0;\n"
               "wgmma.mma_async.sync.aligned.m64n192k16.f32.bf16.bf16 {"
               "%0,%1,%2,%3,%4,%5,%6,%7,%8,%9,%10,%11,%12,%13,%14,%15,%16,%17,%18,%19,%20,%21,%22,%23,%24,%25,%26,%27,%28,%29,%30,%31,"
               "%32,%33,%34,%35,%36,%37,%38,%39,%40,%41,%42,%43,%44,%45,%46,%47,%48,%49,%50,%51,%52,%53,%54,%55,%56,%57,%58,%59,%60,%61,%62,%63,"
               "%64,%65,%66,%67,%68,%69,%70,%71,%72,%73,%74,%75,%76,%77,%78,%79,%80,%81,%82,%83,%84,%85,%86,%87,%88,%89,%90,%91,%92,%93,%94,%95"
               "}, %96, %97, p, 1, 1, 0, 1;\n}\n"
               : ACC8(d, 0), ACC8(d, 8), ACC8(d, 16), ACC8(d, 24), ACC8(d, 32), ACC8(d, 40), ACC8(d, 48), ACC8(d, 56),
                 ACC8(d, 64), ACC8(d, 72), ACC8(d, 80), ACC8(d, 88) : "l"(da), "l"(db), "r"(acc));
}
DI void wgmma_n24_ss_nt(float* d, uint64_t da, uint64_t db, int acc) {
  asm volatile("{\n.reg .pred p;\nsetp.ne.b32 p, %14, 0;\n"
               "wgmma.mma_async.sync.aligned.m64n24k16.f32.bf16.bf16 {%0,%1,%2,%3,%4,%5,%6,%7,%8,%9,%10,%11}, %12, %13, p, 1, 1, 0, 1;\n}\n"
               : ACC8(d, 0), "+f"(d[8]), "+f"(d[9]), "+f"(d[10]), "+f"(d[11]) : "l"(da), "l"(db), "r"(acc));
}
DI void tma_load3d(uint32_t dst, const CUtensorMap* m, int c0, int c1, int c2, uint32_t mb) {
  asm volatile("cp.async.bulk.tensor.3d.shared::cluster.global.mbarrier::complete_tx::bytes [%0], [%1, {%3, %4, %5}], [%2];"
               :: "r"(dst), "l"(m), "r"(mb), "r"(c0), "r"(c1), "r"(c2) : "memory");
}
DI uint32_t trans8(uint32_t x) { uint32_t r; asm("movmatrix.sync.aligned.m8n8.trans.b16 %0, %1;" : "=r"(r) : "r"(x)); return r; }
DI void wgmma_n40_ss(float* d, uint64_t da, uint64_t db, int acc) {
  asm volatile("{\n.reg .pred p;\nsetp.ne.b32 p, %22, 0;\n"
               "wgmma.mma_async.sync.aligned.m64n40k16.f32.bf16.bf16 {%0,%1,%2,%3,%4,%5,%6,%7,%8,%9,%10,%11,%12,%13,%14,%15,%16,%17,%18,%19}, "
               "%20, %21, p, 1, 1, 1, 1;\n}\n"
               : ACC8(d, 0), ACC8(d, 8), "+f"(d[16]), "+f"(d[17]), "+f"(d[18]), "+f"(d[19]) : "l"(da), "l"(db), "r"(acc));
}
DI uint2 ldg_relaxed64(const void* p) {
  uint2 v; asm volatile("ld.relaxed.gpu.global.v2.b32 {%0,%1}, [%2];" : "=r"(v.x), "=r"(v.y) : "l"(p) : "memory"); return v;
}
template <int ST> DI void ldg8x64(uint32_t* m, const void* p) {
  asm volatile("ld.relaxed.gpu.global.v2.b32 {%0,%1}, [%16];\nld.relaxed.gpu.global.v2.b32 {%2,%3}, [%16 + %17];\n"
               "ld.relaxed.gpu.global.v2.b32 {%4,%5}, [%16 + %18];\nld.relaxed.gpu.global.v2.b32 {%6,%7}, [%16 + %19];\n"
               "ld.relaxed.gpu.global.v2.b32 {%8,%9}, [%16 + %20];\nld.relaxed.gpu.global.v2.b32 {%10,%11}, [%16 + %21];\n"
               "ld.relaxed.gpu.global.v2.b32 {%12,%13}, [%16 + %22];\nld.relaxed.gpu.global.v2.b32 {%14,%15}, [%16 + %23];"
               : "=r"(m[0]), "=r"(m[1]), "=r"(m[2]), "=r"(m[3]), "=r"(m[4]), "=r"(m[5]), "=r"(m[6]), "=r"(m[7]),
                 "=r"(m[8]), "=r"(m[9]), "=r"(m[10]), "=r"(m[11]), "=r"(m[12]), "=r"(m[13]), "=r"(m[14]), "=r"(m[15])
               : "l"(p), "n"(ST), "n"(2 * ST), "n"(3 * ST), "n"(4 * ST), "n"(5 * ST), "n"(6 * ST), "n"(7 * ST) : "memory");
}
template <int ST> DI void ldg4x128(uint32_t* m, const void* p) {
  asm volatile("ld.relaxed.gpu.global.v4.b32 {%0,%1,%2,%3}, [%16];\nld.relaxed.gpu.global.v4.b32 {%4,%5,%6,%7}, [%16 + %17];\n"
               "ld.relaxed.gpu.global.v4.b32 {%8,%9,%10,%11}, [%16 + %18];\nld.relaxed.gpu.global.v4.b32 {%12,%13,%14,%15}, [%16 + %19];"
               : "=r"(m[0]), "=r"(m[1]), "=r"(m[2]), "=r"(m[3]), "=r"(m[4]), "=r"(m[5]), "=r"(m[6]), "=r"(m[7]),
                 "=r"(m[8]), "=r"(m[9]), "=r"(m[10]), "=r"(m[11]), "=r"(m[12]), "=r"(m[13]), "=r"(m[14]), "=r"(m[15])
               : "l"(p), "n"(ST), "n"(2 * ST), "n"(3 * ST) : "memory");
}
template <int N, int ST> DI bool stale(const uint32_t* m, uint32_t tag) {
  uint32_t x = m[0] ^ tag;
#pragma unroll
  for (int i = 1; i < N; i++) asm("lop3.b32 %0, %0, %1, %2, 0xf6;" : "+r"(x) : "r"(m[i * ST]), "r"(tag));
  return __any_sync(0xffffffffu, x & 1);
}
DI bool mbar_test(uint32_t b, uint32_t par) {
  uint32_t r; asm volatile("{\n.reg .pred p;\nmbarrier.test_wait.parity.shared::cta.b64 p, [%1], %2;\nselp.u32 %0, 1, 0, p;\n}" : "=r"(r) : "r"(b), "r"(par) : "memory");
  return r;
}
DI int wait_flags(const unsigned* p, bool active, unsigned base, int seg) {
  int n = 0, m;
  while (true) {
    m = __reduce_min_sync(0xffffffffu, active ? (int)(ldg_acquire32(p) - base) : NSEG);
    if (m > seg || ++n > SPIN_LIMIT) break;
    __nanosleep((YP & 32) ? 400 : 40);
  }
  return max(m, seg + 1);
}
DI void wait_count(const unsigned* p, unsigned target) {
  int n = 0;
  unsigned v;
  while (true) {
    asm volatile("ld.acquire.gpu.global.b32 %0, [%1];" : "=r"(v) : "l"(p) : "memory");
    if ((int)(v - target) >= 0 || ++n > SPIN_LIMIT) break;
    __nanosleep(64);
  }
}
#define PACE_NEXT 800
#define AWARM 0
#define WPF 3
#define UNP 64
#define ADLY 0
#define ODLY 100
#define SDLY 0
#define RSL 100
#define TWO 0
#define ALLW 1
#define AE 0
#define PING 60
#define FLAG 2
#define FPOS 1
#define QB 1
#define Q_LO 0
#define Q_HI 320
DI bool tick_wait(uint32_t pace, int step) {
  const int n = lds32v(pace);
  if (n <= step) mbar_wait(pace + 8, n & 1);
  return n <= step;
}
DI void quiet_wait(uint32_t pace) {
  uint32_t n, d;
  asm volatile("ld.volatile.shared.v2.b32 {%0,%1}, [%2];" : "=r"(n), "=r"(d) : "r"(pace) : "memory");
  if (n - 1 < NSEG - 2 && (int)(gtime() - d) > Q_HI) mbar_wait(pace + 8, n & 1);
}
DI void sleep_until(uint32_t t) {
  for (int n = 0; n < 64; n++) {
    const int r = t - gtime();
    if (r <= 0) break;
    __nanosleep(r >> 1);
  }
}
DI void aux_barrier(int i, unsigned epoch, bool wait = true) {
  asm volatile("fence.proxy.async;" ::: "memory");
  asm volatile("red.release.gpu.global.add.u32 [%0], 1;" :: "l"(&g_abar[i * 32]) : "memory");
  if (!wait) return;
  wait_count(&g_abar[i * 32], NAUX * (epoch + 1));
  asm volatile("fence.proxy.async;" ::: "memory");
}

__global__ void __launch_bounds__(512, 1)
aux_kernel(const __grid_constant__ AMaps tm, const bf16* __restrict__ x, const bf16* __restrict__ gate_w, bf16* __restrict__ out) {
  extern __shared__ __align__(1024) unsigned char smem_raw[];
  const uint32_t sb = smem_u32(smem_raw);
  const uint32_t full1 = sb + A_BAR, empty1 = full1 + 8 * A_ST, fullw = empty1 + 8 * A_ST, full3 = fullw + 16, empty3 = full3 + 32,
                 fulla = empty3 + 32, emptya = fulla + 32, fullg = emptya + 16, pace = fullg + 8;
  const int tid = threadIdx.x, lane = tid & 31, cta = blockIdx.x;
  const int wg = __shfl_sync(0xffffffffu, tid >> 7, 0), w = __shfl_sync(0xffffffffu, (tid >> 5) & 3, 0);
  ASTAMP(14);
  const unsigned epoch = *(volatile unsigned*)&g_epoch2;
  if (tid == 0) {
    for (int i = 0; i < A_ST; i++) { mbar_init(full1 + 8 * i, 1); mbar_init(empty1 + 8 * i, 8); }
    mbar_init(fullw, 1); mbar_init(fullw + 8, 1); mbar_init(fullg, 1);
    for (int i = 0; i < 2; i++) { mbar_init(fulla + 16 * i, 2); mbar_init(fulla + 16 * i + 8, 1); mbar_init(emptya + 8 * i, 4); }
    sts64(pace, 0, 0); mbar_init(pace + 8, 1); sts32(pace + 16, 0); sts64(pace + 24, 65536, 0xffff0000u);
    for (int i = 0; i < 4; i++) { mbar_init(full3 + 8 * i, 1); mbar_init(empty3 + 8 * i, cta < NH ? 8 : 4); }
    fence_async();
  }
  auto load_a = [&](int st, int k, int col) {
    mbar_expect(full1 + 8 * st, A_STAGE + 1536);
    tma_load3d(sb + st * A_STAGE, &tm.x, k, (cta >> 1) * A_ROWS - 7, 0, full1 + 8 * st);
    tma_load3d(sb + st * A_STAGE + 8192, &tm.wa, col, k, 0, full1 + 8 * st);
    tma_load3d(sb + A_W8 + st * 1536, &tm.wa8, col + 64, k, 0, full1 + 8 * st);
  };
  if (AE && tid < 32 && !(XP & 256)) {
    __syncwarp();
#pragma unroll 1
    for (int st = 0; st < A_ST; st++) if (elect_one()) load_a(st, st * 32, (cta & 1) * (DM / 2));
  }
  __syncthreads();
  ASTAMP(0);
  const bool wide = cta < NH;
  auto p3_ks = [&](int g) { return wide ? cta >> 2 : 2 * (cta - NH) + g; };
  auto p3_mt = [&](int g) { return wide ? 2 * (cta & 3) + g : 8; };
  const unsigned fbase = epoch * NSEG;
  if (wg == 3) {
    asm volatile("setmaxnreg.dec.sync.aligned.u32 %0;" :: "n"(TWO ? 32 : 48));
    if (w == 1 && cta < NH) {
#pragma unroll 1
      for (int seg = 0; seg < ((XP & 2048) ? 0 : NSEG); seg++) {
        bar_arrive(5, 160);
        if (seg > 0 && lane == 0) {
          asm volatile("cp.async.bulk.wait_group 0;" ::: "memory");
          stg_relaxed32(&g_oflag[cta * 32], fbase + seg);
        }
        if (!(ZR & 4) && lane < 3) stg_relaxed32(&g_cflag[(cta * 3 + lane) * 32], fbase + seg);
        __syncwarp();
        bar_sync(4, 160);
        if (QM & 16) tick_wait(pace, seg + 1);
        if (lane == 0) {
          fence_async();
          if (!(YP & 2)) {
          tma_store(&tm.o, sb + A_OST, cta * DH, seg * 32);
          tma_store(&tm.o, sb + A_OST + 4096, cta * DH + 64, seg * 32);
          }
          asm volatile("cp.async.bulk.commit_group;" ::: "memory");
          asm volatile("cp.async.bulk.wait_group.read 0;" ::: "memory");
        }
        __syncwarp();
      }
      if (lane == 0) {
        asm volatile("cp.async.bulk.wait_group 0;" ::: "memory");
        { const int seg = NSEG - 1; TSTAMP(2); }
        stg_relaxed32(&g_oflag[cta * 32], fbase + NSEG);
      }
    }
    if (w == 2 && cta < NH) {
      const uint32_t ktag = (epoch + 1) & 1, ma = sb + A_IN + 8192 + lane * 16;
      int avail = 0;
      int own = 0;
      bar_sync(10, 64);
#pragma unroll 1
      for (int seg = 0; seg < ((XP & 2048) ? 0 : NSEG); seg++) {
        if (avail <= seg) {
          int n = 0;
          while (true) {
            asm volatile("ld.acquire.gpu.global.v2.b32 {%0,%1}, [%2];" : "=r"(avail), "=r"(own) : "l"(&g_sflag[(cta * 3 + min(lane, 2)) * 4]) : "memory");
            avail = __reduce_min_sync(0xffffffffu, (int)(avail - fbase));
            if (avail > seg || ++n > SPIN_LIMIT) break;
            __nanosleep(40);
          }
        }
        if ((QM & 8) && seg < UNP) tick_wait(pace, seg);
        TSTAMP(0);
        const unsigned char* km = g_km + (size_t)(seg * NH + cta) * 4096 + lane * 8;
        uint32_t m[16];
        const float g = __ldcg(&g_gate[seg * 32 + lane]);
        ldg8x64<256>(m, km);
        const uint32_t b = seg & 1, full = fulla + 16 * b, mb = ma + b * A_INB;
        mbar_wait(emptya + 8 * b, (~seg >> 1) & 1);
        if (lane < 2) mbar_expect(full + 8 * lane, (YP & 8) ? 0 : 16384 >> lane);
        __syncwarp();
        const int slot = seg < own ? seg & 7 : seg;
        if (lane < 3 && !(YP & 8)) bulk_load(sb + A_IN + b * A_INB + lane * SEGB, g_seg + ((size_t)slot * 96 + cta * 3 + lane) * 8192, 8192, full + (lane & 2) * 4);
        int n = 0;
#pragma unroll 1
        while (stale<8, 2>(m, ktag) && ++n < SPIN_LIMIT) { if (seg < UNP - 1) __nanosleep(200); ldg8x64<256>(m, km); }
        TSTAMP(1);
#pragma unroll
        for (int i = 0; i < 4; i++) stsm4(mb + (i >> 1) * SEGB + (i & 1) * 512, m[4 * i], m[4 * i + 1], m[4 * i + 2], m[4 * i + 3]);
        sts32(sb + A_G + b * 128 + lane * 4, __float_as_uint(1.f - g));
        fence_async();
        __syncwarp();
        if (lane == 0) mbar_arrive(full);
      }
    }
    if (w == 3 && QM) {
      const unsigned char* const hp = tm.red + HINT_OFF + 65536 + (cta & 1) * 4096 + min(lane, 23) * 4;
      uint32_t d = 0;
      int s = 0, n = 0;
#pragma unroll 1
      while (s < NSEG - 1) {
        const uint32_t h = ldg_relaxed32(hp + RED_SLOT(s)), t = (gtime() - 1984) & ~31u, late = latest_hint(h, t, s);
        if (late < 64) {
          d = t + late * 32 + tm.poll + Q_LO;
          sleep_until(d);
          s++; n = 0;
          if (lane == 0) { mbar_arrive(pace + 8); sts64(pace, s < NSEG - 1 ? s : 2 * NSEG, d); }
          sleep_until(d + PACE_NEXT);
        } else {
          if (++n > (s ? 16 : 256) || lds32v(pace + 16)) break;
          if (!s) __nanosleep(100);
        }
      }
      if (s < NSEG - 1 && lane == 0) { mbar_arrive(pace + 8); sts64(pace, 2 * NSEG, d); }
    }
    if (w != 0) return;
    const bool lead = lane == 0;
#pragma unroll 1
    for (int it = AE * A_ST, st = 0, ph = !AE, k = AE * A_ST * 32, col = (cta & 1) * (DM / 2); it < ((XP & 256) ? 0 : 72); it++) {
      mbar_wait(empty1 + 8 * st, ph);
      if (QM & 1) quiet_wait(pace);
      if (elect_one()) load_a(st, k, col);
      __syncwarp();
      if (++st == A_ST) { st = 0; ph ^= 1; }
      k += 32;
      if (k == DM) { k = 0; col += 72; }
    }
    auto load_wo = [&](uint32_t dst, int g, int kb, uint32_t mb) {
      if (kb < 64) tma_load(dst, &tm.wob, p3_mt(g) * 64, kb * 64, mb);
      else tma_load(dst, &tm.woa, p3_mt(g) * 64, (kb - 64) * 64, mb);
    };
    if (lead) mbar_expect(fullw, 16 * 8192);
#pragma unroll 1
    for (int st = 0; st < A_ST; st++) {
      if (!(XP & 256)) mbar_wait(empty1 + 8 * st, 1);
      if (lane < 16 && min(((lane + 1) * 8192 - 1) / A_STAGE, A_ST - 1) == st) load_wo(sb + lane * 8192, lane >> 3, p3_ks(lane >> 3) * 9 + (lane & 7), fullw);
      __syncwarp();
    }
    __syncwarp(); bar_sync(6, 288);
    if (lead) mbar_expect(fullw + 8, 2 * 8192 + (p3_ks(0) >= 4 ? 4096 : 0));
    __syncwarp();
    if (lane < 2) {
      load_wo(sb + (16 + lane) * 8192, lane, p3_ks(lane) * 9 + 8, fullw + 8);
      if (p3_ks(0) >= 4) tma_load(sb + A_XW + lane * 2048, &tm.woa16, p3_mt(lane) * 64, 448 + p3_ks(lane) * 16, fullw + 8);
    }
    __syncwarp();
    if (lead) aux_barrier(1, epoch, ALLW || p3_ks(0) >= 4);
    __syncwarp(); bar_sync(6, 288);
    {
      int avail = 0, sl = 0, ph = 1;
      const int h = (9 * p3_ks(0) >> 1) + lane;
#pragma unroll 1
      for (int seg = 0; seg < ((XP & 2048) ? 0 : NSEG); seg++) {
        if (avail <= seg) avail = wait_flags(&g_oflag[min(h, NH - 1) * 32], lane < (wide ? 5 : 9), fbase, seg);
        SSTAMP(seg, 4);
        for (int g = 0; g < (wide ? 1 : 2); g++) {
          const int ks = p3_ks(g);
          mbar_wait(empty3 + 8 * sl, ph);
          if ((QM & 4) && tick_wait(pace, seg + (QM >> 4 & 1) + 1) && ODLY) __nanosleep(ODLY);
          if (YP & 4) { if (lead) mbar_arrive(full3 + 8 * sl); }
          else if (elect_one()) {
            mbar_expect(full3 + 8 * sl, XT + (ks >= 4 ? 1024 : 0));
            tma_load3d(sb + sl * XT, &tm.o3, 0, seg * 32, ks * 9, full3 + 8 * sl);
            if (ks >= 4) tma_load(sb + A_XT + sl * 1024, &tm.o16, 72 * 64 - 64 + ks * 16, seg * 32, full3 + 8 * sl);
          }
          __syncwarp();
          if (++sl == (wide ? 3 : 4)) { sl = 0; ph ^= 1; }
        }
      }
    }
    sts32(pace + 16, 1);
    __syncwarp(); bar_sync(6, 288);
    asm volatile("griddepcontrol.wait;" ::: "memory");
  } else if (wg == 2) {
    asm volatile("setmaxnreg.dec.sync.aligned.u32 64;");
    if (cta < NH) {
      if (tid == 256) { mbar_expect(fullg, 64 * DM * 2); bulk_load(sb + A_IN, x + cta * 64 * DM, 64 * DM * 2, fullg); }
      uint32_t gw[9];
#pragma unroll
      for (int j = 0; j < 9; j++) gw[j] = ((const uint32_t*)gate_w)[j * 32 + lane];
      mbar_wait(fullg, 0);
      float mine = 0.f;
#pragma unroll 4
      for (int u = 0; u < 16; u++) {
        float d0 = 0.f, d1 = 0.f;
#pragma unroll
        for (int j = 0; j < 9; j++) {
          const uint32_t a = lds32(sb + A_IN + (w * 16 + u) * (DM * 2) + j * 128 + lane * 4);
          d0 = fmaf(bf_lo(a), bf_lo(gw[j]), d0); d1 = fmaf(bf_hi(a), bf_hi(gw[j]), d1);
        }
        d0 = warp_sum(d0 + d1);
        if (lane == u) mine = d0;
      }
      if (lane < 16) g_gate[cta * 64 + w * 16 + lane] = 1.f / (1.f + __expf(-mine));
      fence_async();
    }
    bar_sync(3, 128);
    if (tid == 256) { aux_barrier(0, epoch); if (cta == 0) *(volatile unsigned*)&g_epoch2 = epoch + 1; }
    __syncwarp();
    bar_sync(3, 128);
    if (w == 0) bar_arrive(8, 288);
    if (w == 1 && cta < NH) bar_arrive(10, 64);
    if (cta < NH) {
      CDECL;
#pragma unroll 1
      for (int seg = 0; seg < ((XP & 2048) ? 0 : NSEG); seg++) {
        CSTAMP(0);
        const uint32_t in = sb + A_IN + (seg & 1) * A_INB;
        const uint64_t qd = make_desc(in, 128, 1024, 0);
        mbar_wait(fulla + 16 * (seg & 1), (seg >> 1) & 1);
        CSTAMP(3);
        SSTAMP(seg, 0);
        float d[2][16];
        {
          float a[20];
          uint32_t vm[16];
          const unsigned char* vp = g_km + (size_t)(seg * NH + cta) * 4096 + 2048 + lane * 16;
          if (w == 3) ldg4x128<512>(vm, vp);
          WG_FENCE();
#pragma unroll
          for (int k = 0; k < ((YP & 16) ? 1 : 8); k++) wgmma_n40_ss(a, qd + ((k >> 2) * SEGB + (k & 3) * 256 >> 4), qd + ((k >> 2) * SEGB + (k & 3) * 256 + 4096 >> 4), k > 0);
          const uint32_t ga = sb + A_G + (seg & 1) * 128 + (w & 1) * 64 + (lane >> 2) * 4;
          const float f0 = __uint_as_float(lds32(ga)), f1 = __uint_as_float(lds32(ga + 32));
          WG_COMMIT();
          WG_WAIT(0);
          CSTAMP(5);
          SSTAMP(seg, 1);
          if (w < 2) {
            const int lim = w * 16 + (lane >> 2) - 2 * (lane & 3);
            float m0 = -3.0e38f, m1 = -3.0e38f;
#pragma unroll
            for (int i = 0; i < 20; i++) {
              a[i] *= SM_SCALE * LOG2E;
              if (i < 16 && (i >> 2) * 8 + (i & 1) - (i & 2) * 4 > lim) a[i] = -1.0e9f * LOG2E;
              if (i & 2) m1 = fmaxf(m1, a[i]); else m0 = fmaxf(m0, a[i]);
            }
#pragma unroll
            for (int o = 1; o < 4; o <<= 1) { m0 = fmaxf(m0, __shfl_xor_sync(0xffffffffu, m0, o)); m1 = fmaxf(m1, __shfl_xor_sync(0xffffffffu, m1, o)); }
            float s0 = 0.f, s1 = 0.f;
#pragma unroll
            for (int i = 0; i < 20; i++) { a[i] = ex2(a[i] - (i & 2 ? m1 : m0)); if (i & 2) s1 += a[i]; else s0 += a[i]; }
#pragma unroll
            for (int o = 1; o < 4; o <<= 1) { s0 += __shfl_xor_sync(0xffffffffu, s0, o); s1 += __shfl_xor_sync(0xffffffffu, s1, o); }
            s0 = f0 * rcp(s0); s1 = f1 * rcp(s1);
            uint32_t p[10];
#pragma unroll
            for (int i = 0; i < 10; i++) p[i] = pack_bf16(a[2 * i] * (i & 1 ? s1 : s0), a[2 * i + 1] * (i & 1 ? s1 : s0));
            const uint32_t pa = sb + A_P + (2 * w + ((lane >> 3) & 1)) * 768 + (lane >> 4) * 128 + (lane & 7) * 16;
            stsm4t(pa, p[0], p[1], p[2], p[3]); stsm4t(pa + 256, p[4], p[5], p[6], p[7]); stsm4t(pa + 512, p[8], p[9], 0, 0);
            CSTAMP(6);
            fence_async();
            CSTAMP(7);
          } else if (w == 3) {
            int n = 0;
#pragma unroll 1
            while (stale<4, 4>(vm, (epoch + 1) & 1) && ++n < SPIN_LIMIT) ldg4x128<512>(vm, vp);
#pragma unroll
            for (int i = 0; i < 4; i++) stsm4(in + 2 * SEGB + 8192 + (lane >> 4) * 1024 + (lane & 15) * 16 + i * 256, vm[4 * i], vm[4 * i + 1], vm[4 * i + 2], vm[4 * i + 3]);
            fence_async();
            mbar_wait(fulla + 16 * (seg & 1) + 8, (seg >> 1) & 1);
          }
        }
        CSTAMP(8);

        bar_sync(5, 160);
        CSTAMP(10);
        SSTAMP(seg, 2);
        const uint64_t pd = make_desc(sb + A_P, 128, 768, 0), vd = make_desc(in + 2 * SEGB, 128, 512, 0), md = make_desc(in + 2 * SEGB + 8192, 0, 128, 0);
        WG_FENCE();
#pragma unroll
        for (int i = 0; i < 2; i++) {
          wgmma_n32_ss<0>(d[i], vd + i * 256, pd, 0);
          wgmma_n32_ss<0>(d[i], vd + i * 256 + 16, pd + 16, 1);
          wgmma_n32_ss<0>(d[i], md + i * 64, pd + 32, 1);
        }
        WG_COMMIT();
        WG_WAIT(0);
        CSTAMP(11);
        if (lane == 0) mbar_arrive(emptya + 8 * (seg & 1));
#pragma unroll
        for (int i = 0; i < 2; i++) {
          const uint32_t oa = sb + A_OST + i * 4096 + ((lane & 7) + ((lane >> 4) << 3)) * 128 + (((2 * w + ((lane >> 3) & 1)) ^ (lane & 7)) << 4);
          stsm4t(oa, pack_bf16(d[i][0], d[i][1]), pack_bf16(d[i][2], d[i][3]), pack_bf16(d[i][4], d[i][5]), pack_bf16(d[i][6], d[i][7]));
          stsm4t(oa + 2048, pack_bf16(d[i][8], d[i][9]), pack_bf16(d[i][10], d[i][11]), pack_bf16(d[i][12], d[i][13]), pack_bf16(d[i][14], d[i][15]));
        }
        CSTAMP(12);
        bar_sync(4, 160);
        SSTAMP(seg, 3);
      }
      CDUMP;
    }
  } else {
    asm volatile("setmaxnreg.inc.sync.aligned.u32 %0;" :: "n"(TWO ? 208 : 200));
    {
      const int g = lane >> 2, t = lane & 3, r0 = (cta >> 1) * A_ROWS - 7 + w * 16;
      const uint32_t prev = (2 * t > g ? 0xffffu : 0u) | (2 * t + 1 > g ? 0xffff0000u : 0u);
      const int k0 = r0 + 2 * t - (2 * t > g ? 8 : 0), k1 = r0 + 2 * t + 1 - (2 * t + 1 > g ? 8 : 0);
      const uint32_t slot = sb + A_EXC + (wg * 4 + w) * 2304;
      float gl = 0.f, gh = 0.f;
      int st = 0, ph = 0;
#pragma unroll 1
      for (int p = -AWARM; p < ((XP & 256) ? 0 : 4); p++) {
        float big[96], sml[12];
        if (p == WPF && tid < 18) {
          const int kb = p3_ks(tid >= 9) * 9 + tid % 9;
          tma_prefetch(kb < 64 ? &tm.wob : &tm.woa, p3_mt(tid >= 9) * 64, (kb & 63) * 64);
        }
        __syncwarp();
#pragma unroll
        for (int i = 0; i < 96; i++) big[i] = 0.f;
#pragma unroll
        for (int i = 0; i < 12; i++) sml[i] = 0.f;
#pragma unroll 1
        for (int k = p < 0 ? 18 : 0; k < 18; k++) {
          mbar_wait(full1 + 8 * st, ph);
          const uint64_t da = make_desc(sb + st * A_STAGE + wg * 4096, 16, 512, 2);
          const uint64_t db = make_desc(sb + st * A_STAGE + 8192, 4096, 1024, 1), dc = make_desc(sb + A_W8 + st * 1536, 128, 512, 0);
          WG_FENCE();
#pragma unroll
          for (int j = 0; j < 2; j++) { wgmma_n192_ss_nt(big, da + j * 2, db + j * 128, 1); wgmma_n24_ss_nt(sml, da + j * 2, dc + j * 16, 1); }
          WG_COMMIT();
          WG_WAIT(1);
          if (k > 0 && lane == 0) mbar_arrive(empty1 + 8 * (st ? st - 1 : A_ST - 1));
          if (++st == A_ST) { st = 0; ph ^= 1; }
        }
        WG_WAIT(0);
        ASTAMP(16 + max(p, 0) + wg * 16);
        if (lane == 0 && p >= 0) mbar_arrive(empty1 + 8 * (st ? st - 1 : A_ST - 1));
        uint32_t f[3][9][2];
#pragma unroll
        for (int c = 0; c < 3; c++)
#pragma unroll
          for (int j = 0; j < 9; j++)
#pragma unroll
            for (int i = 0; i < 2; i++) {
              const float* a = j < 8 ? &big[(c * 8 + j) * 4 + 2 * i] : &sml[c * 4 + 2 * i];
              f[c][j][i] = c < 2 ? pack_bf16(a[0], a[1]) : trans8(pack_bf16(a[0], a[1]));
            }
        if (p == 0) {
          bar_sync(8, 288);
          gl = __ldcg(&g_gate[min(max(r0 + g, 0), S_LEN / 2 - 1) * 2 + wg]); gh = __ldcg(&g_gate[min(max(r0 + g + 8, 0), S_LEN / 2 - 1) * 2 + wg]);
        }
        asm volatile("cp.async.bulk.wait_group.read 0;" ::: "memory");
        __syncwarp();
#pragma unroll
        for (int j = 0; j < 8; j += 2) sts128(slot + j * 256 + lane * 16, f[1][j][1], f[2][j][1], f[1][j + 1][1], f[2][j + 1][1]);
        sts64(slot + 2048 + lane * 8, f[1][8][1], f[2][8][1]);
        bar_sync(1 + wg, 128);
        ASTAMP(24 + max(p, 0) + wg * 16);
        uint32_t pv[9][2];
#pragma unroll
        for (int j = 0; j < 9; j++) pv[j][0] = pv[j][1] = 0;
        if (w) {
#pragma unroll
          for (int j = 0; j < 8; j += 2) lds128(slot - 2304 + j * 256 + lane * 16, pv[j]);
          lds64(slot - 256 + lane * 8, pv[8][0], pv[8][1]);
        }
        float a[4][4], m[4][2];
#pragma unroll
        for (int h = 0; h < 4; h++) {
          const int j = 2 * h;
          const uint32_t qa[4] = {t >= h ? f[0][j][0] : 0, t >= h ? f[0][j][1] : 0, f[0][j + 1][0], f[0][j + 1][1]};
          const uint32_t qb0 = t <= h ? f[0][j + 2][0] : 0, qb1 = t <= h ? f[0][j + 2][1] : 0;
          float s0[4], s1[4], s2[4];
          mma16816z(s1, qa, f[1][j][0], f[1][j + 1][0]); mma16816z(s2, qa, f[1][j][1], f[1][j + 1][1]); mma16816z(s0, qa, pv[j][0], pv[j + 1][0]);
          mma1688(s1, qb0, qb1, f[1][j + 2][0]); mma1688(s2, qb0, qb1, f[1][j + 2][1]); mma1688(s0, qb0, qb1, pv[j + 2][0]);
          a[h][0] = 2 * t > g ? s0[0] : s1[0]; a[h][1] = 2 * t + 1 > g ? s0[1] : s1[1]; a[h][2] = 2 * t > g ? s1[2] : s2[2]; a[h][3] = 2 * t + 1 > g ? s1[3] : s2[3];
        }
#pragma unroll
        for (int h = 0; h < 4; h++) {
#pragma unroll
          for (int i = 0; i < 4; i++) a[h][i] = (i & 1 ? k1 : k0) + (i & 2) * 4 >= 0 ? a[h][i] * (0.23570226039551584f * LOG2E) : -1.0e9f * LOG2E;
          m[h][0] = fmaxf(a[h][0], a[h][1]); m[h][1] = fmaxf(a[h][2], a[h][3]);
        }
#pragma unroll
        for (int x = 1; x < 4; x <<= 1)
#pragma unroll
          for (int i = 0; i < 8; i++) m[i >> 1][i & 1] = fmaxf(m[i >> 1][i & 1], __shfl_xor_sync(0xffffffffu, m[i >> 1][i & 1], x));
#pragma unroll
        for (int h = 0; h < 4; h++) {
#pragma unroll
          for (int i = 0; i < 4; i++) a[h][i] = ex2(a[h][i] - m[h][i >> 1]);
          m[h][0] = a[h][0] + a[h][1]; m[h][1] = a[h][2] + a[h][3];
        }
#pragma unroll
        for (int x = 1; x < 4; x <<= 1)
#pragma unroll
          for (int i = 0; i < 8; i++) m[i >> 1][i & 1] += __shfl_xor_sync(0xffffffffu, m[i >> 1][i & 1], x);
        uint32_t o[9][2];
#pragma unroll
        for (int h = 0; h < 4; h++) {
          const int j = 2 * h;
          const float z0 = gl * rcp(m[h][0]), z1 = gh * rcp(m[h][1]);
          const uint32_t pl = pack_bf16(a[h][0] * z0, a[h][1] * z0), pu = pack_bf16(a[h][2] * z1, a[h][3] * z1);
          const uint32_t pa[4] = {pl & prev, 0, pl & ~prev, pu & prev};
          float d[3][4];
#pragma unroll
          for (int i = 0; i < 3; i++) mma16816z(d[i], pa, pv[j + i][1], f[2][j + i][0]);
#pragma unroll
          for (int i = 0; i < 3; i++) mma1688(d[i], 0, pu & ~prev, f[2][j + i][1]);
#pragma unroll
          for (int i = 0; i < 3; i++) {
            const uint32_t d0 = pack_bf16(d[i][0], d[i][1]), d1 = pack_bf16(d[i][2], d[i][3]);
            o[j + i][0] = i == 0 && h > 0 && t < h ? o[j][0] : d0;
            o[j + i][1] = i == 0 && h > 0 && t < h ? o[j][1] : d1;
          }
        }
        ASTAMP(28 + max(p, 0) + wg * 16);
        bar_sync(1 + wg, 128);
        const uint32_t oa = slot + (lane & 15) * 144 + (lane >> 4) * 16;
#pragma unroll
        for (int j = 0; j < 8; j += 2) stsm4(oa + j * 16, o[j][0], o[j][1], o[j + 1][0], o[j + 1][1]);
        asm volatile("stmatrix.sync.aligned.m8n8.x2.shared.b16 [%0], {%1,%2};" :: "r"(oa + 128), "r"(o[8][0]), "r"(o[8][1]) : "memory");
        fence_async();
        __syncwarp();
        if (QM & 64) quiet_wait(pace);
        if (lane < 16 && w * 16 + lane >= 7 && r0 + lane < S_LEN / 2 && p >= 0)
          asm volatile("cp.async.bulk.global.shared::cta.bulk_group [%0], [%1], 144;"
                       :: "l"(g_Ocat + (size_t)((r0 + lane) * 2 + wg) * KCAT + 4096 + (cta & 1) * (DM / 2) + p * 72), "r"(slot + lane * 144) : "memory");
        asm volatile("cp.async.bulk.commit_group;" ::: "memory");
        ASTAMP(20 + max(p, 0) + wg * 16);
      }
      if (XP & 256) bar_sync(8, 288);
      asm volatile("cp.async.bulk.wait_group 0;" ::: "memory");
    }
    ASTAMP(3);
    bar_arrive(6, 288);
    uint32_t wa[37][4];
    mbar_wait(fullw, 0);
    const uint32_t la = sb + ((lane & 7) + ((lane >> 4) << 3)) * 128 + (((2 * w + ((lane >> 3) & 1)) ^ (lane & 7)) << 4);
#pragma unroll
    for (int k = 0; k < 32; k++) ldsm4t(wa[k], la + wg * 65536 + k * 2048);
    mbar_wait(fullw + 8, 0);
#pragma unroll
    for (int k = 32; k < 36; k++) ldsm4t(wa[k], la + wg * 8192 + 65536 + k * 2048);
    ldsm4t(wa[36], la + A_XW + wg * 2048);
    fence_async();
    if (XP & 2048) bar_sync(6, 288); else bar_arrive(6, 288);
    ASTAMP(4);
    const int ks = p3_ks(wg), mt = p3_mt(wg);
    uint32_t v[16];
    auto fetch = [&](int seg) { ldg8x64<1024>(v, g_part + (((seg & 7) * 9 + mt) * 4 + (ks & 3)) * 1024 + (tid & 127)); };
    auto finish = [&](int seg) {
      const uint32_t tagv = (~seg >> 3) & 1;
      int n = 0;
#pragma unroll 1
      while (!(YP & 512) && stale<8, 2>(v, tagv) && ++n < SPIN_LIMIT) {
        if (seg < NSEG - 2) __nanosleep(RSL);
        fetch(seg);
      }
      float own[4] = {bf_lo(v[0]), bf_hi(v[0]), bf_lo(v[1]), bf_hi(v[1])};
#pragma unroll
      for (int j = 1; j < 8; j++) { own[0] += bf_lo(v[2 * j]); own[1] += bf_hi(v[2 * j]); own[2] += bf_lo(v[2 * j + 1]); own[3] += bf_hi(v[2 * j + 1]); }
      uint32_t p0 = pack_bf16(own[0], own[1]), p1 = pack_bf16(own[2], own[3]);
      asm volatile("movmatrix.sync.aligned.m8n8.trans.b16 %0, %0;" : "+r"(p0));
      asm volatile("movmatrix.sync.aligned.m8n8.trans.b16 %0, %0;" : "+r"(p1));
      const uint32_t r2 = __shfl_xor_sync(0xffffffffu, lane & 2 ? p0 : p1, 2);
      if (lane & 2) p0 = r2; else p1 = r2;
      const uint32_t r1 = __shfl_xor_sync(0xffffffffu, lane & 1 ? p0 : p1, 1);
      if (lane & 1) p0 = r1; else p1 = r1;
      if (!(YP & 256) || p0 == 0x12345678)
        *((uint2*)(out + (size_t)(seg * 32 + (ks & 3) * 8 + (lane >> 2)) * DM + mt * 64 + w * 16) + (lane & 3)) = make_uint2(p0, p1);
      SSTAMP(seg, 7);
    };
    float acc[16], acc2[16];
#pragma unroll
    for (int i = 0; i < 16; i++) acc[i] = acc2[i] = 0.f;
    int pend = -1, sl = wide ? 0 : wg, ph = 0;
    if (PING && wg) bar_arrive(1, 256);
    CDECL;
    auto run = [&](auto extra) {
#pragma unroll 1
    for (int seg = 0; seg <= ((XP & 2048) ? -1 : NSEG); seg++) {
      CSTAMP(0);
      const bool fin = pend >= 0 && (seg - pend >= FLAG || seg == NSEG);
      if (seg < NSEG) mbar_wait(full3 + 8 * sl, ph);
      if (FPOS == 1 && fin) fetch(pend);
      if (SDLY) {
        uint32_t n, d;
        asm volatile("ld.volatile.shared.v2.b32 {%0,%1}, [%2];" : "=r"(n), "=r"(d) : "r"(pace) : "memory");
        if ((int)n <= seg + 3) sleep_until(d + SDLY);
      }
      CSTAMP(1);
      if (seg < NSEG) {
      if (wg) SSTAMP(seg, 5);
      if (seg < PING) bar_sync(1 + wg, 256);
      CSTAMP(7);
      const uint64_t db = make_desc(sb + sl * XT, 16, 1024, 1);
      WG_FENCE();
#pragma unroll
      for (int k = 0; k < ((XP & 1024) ? 1 : 36); k++)
        wgmma_n32_rs(TWO && (k & 1) ? acc2 : acc, wa[k][0], wa[k][1], wa[k][2], wa[k][3], db + (k >> 2) * 256 + (k & 3) * 2, k >> TWO);
      if (decltype(extra)::value) wgmma_n32_rs(acc, wa[36][0], wa[36][1], wa[36][2], wa[36][3], make_desc(sb + A_XT + sl * 1024, 16, 256, 3), 1);
      WG_COMMIT();
      if (seg < PING) bar_arrive(2 - wg, 256);
      CSTAMP(2);
      CSTAMP(3);
      WG_WAIT(0);
      CSTAMP(4);
      if (wg) SSTAMP(seg, 6);
      if (lane == 0) mbar_arrive(empty3 + 8 * sl);
      sl += wide ? 1 : 2;
      if (sl >= (wide ? 3 : 4)) { sl -= wide ? 3 : 4; ph ^= 1; }
      uint2* dst = g_part + (((seg & 7) * 9 + mt) * 32 + ks) * 128 + (tid & 127);
      uint32_t q[8];
      if (TWO)
#pragma unroll
        for (int j = 0; j < 16; j++) acc[j] += acc2[j];
#pragma unroll
      for (int j = 0; j < 8; j++) q[j] = j & 1 ? pack_bf16(acc[2 * j], acc[2 * j + 1]) : (pack_bf16(acc[2 * j], acc[2 * j + 1]) & ~1u) | ((~seg >> 3) & 1);
      if (QM & 32) tick_wait(pace, seg + (QM >> 4 & 1) + 2);
      if (!(YP & 1025) || q[0] == 0x12345678)
      asm volatile("st.relaxed.gpu.global.v2.b32 [%0], {%1,%2};\nst.relaxed.gpu.global.v2.b32 [%0 + 8192], {%3,%4};\n"
                   "st.relaxed.gpu.global.v2.b32 [%0 + 16384], {%5,%6};\nst.relaxed.gpu.global.v2.b32 [%0 + 24576], {%7,%8};"
                   :: "l"(dst), "r"(q[0]), "r"(q[1]), "r"(q[2]), "r"(q[3]), "r"(q[4]), "r"(q[5]), "r"(q[6]), "r"(q[7]) : "memory");
      }
      CSTAMP(5);
      if (fin) { finish(pend); pend = -1; }
      CSTAMP(6);
      if ((seg & 1) == ks >> 2 && !(YP & 1)) pend = seg;
      if (wg && (seg & 7) == 6) ASTAMP(5 + (seg >> 3));
    }
    };
    if (ks >= 4) run(BoolC<true>()); else run(BoolC<false>());
    if (PING && !wg) bar_sync(1, 256);
    CDUMP;
    ASTAMP(13);
    bar_sync(6, 288);
  }
}

typedef CUresult (*EncodeFn)(CUtensorMap*, CUtensorMapDataType, cuuint32_t, void*, const cuuint64_t*, const cuuint64_t*,
                             const cuuint32_t*, const cuuint32_t*, CUtensorMapInterleave, CUtensorMapSwizzle,
                             CUtensorMapL2promotion, CUtensorMapFloatOOBfill);
#define PROMO 2
static void make_map(EncodeFn enc, CUtensorMap* m, const void* p, int rows, int cols, int box_rows) {
  cuuint64_t dims[2] = {(cuuint64_t)cols, (cuuint64_t)rows};
  cuuint64_t strides[1] = {(cuuint64_t)cols * 2};
  cuuint32_t box[2] = {64, (cuuint32_t)box_rows};
  cuuint32_t es[2] = {1, 1};
  enc(m, CU_TENSOR_MAP_DATA_TYPE_BFLOAT16, 2, (void*)p, dims, strides, box, es, CU_TENSOR_MAP_INTERLEAVE_NONE,
      CU_TENSOR_MAP_SWIZZLE_128B, (CUtensorMapL2promotion)PROMO, CU_TENSOR_MAP_FLOAT_OOB_FILL_NONE);
}

constexpr int g_poll = POLL_NS;
extern "C" void kernel_launch(void* const* d_in, const int* in_sizes, int n_in, void* d_out, int out_size) {
  const bf16* x = (const bf16*)d_in[0];
  const bf16* wqkvA = (const bf16*)d_in[1];
  const bf16* woA = (const bf16*)d_in[2];
  const bf16* mem0 = (const bf16*)d_in[4];
  const bf16* Wq = (const bf16*)d_in[5];
  const bf16* Wk = (const bf16*)d_in[6];
  const bf16* Wv = (const bf16*)d_in[7];
  const bf16* Wo = (const bf16*)d_in[8];
  const bf16* gate_w = (const bf16*)d_in[10];
  static EncodeFn enc = nullptr;
  static void *pO = nullptr, *pR = nullptr, *pF = nullptr;
  if (!enc) {
    cudaDriverEntryPointQueryResult qr;
    cudaGetDriverEntryPoint("cuTensorMapEncodeTiled", (void**)&enc, cudaEnableDefault, &qr);
    cudaGetSymbolAddress(&pO, g_Ocat);
    cudaGetSymbolAddress(&pR, g_red_raw);
    cudaGetSymbolAddress(&pF, g_cflag);
    cudaFuncSetAttribute(rec_kernel, cudaFuncAttributeMaxDynamicSharedMemorySize, SM_TOTAL);
    cudaFuncSetAttribute(aux_kernel, cudaFuncAttributeMaxDynamicSharedMemorySize, A_TOTAL);
  }
  RMaps rm;
  rm.poll = g_poll;
  rm.oflag = (const unsigned char*)pF;
  rm.red = (unsigned char*)(((uintptr_t)pR + 262143) & ~(uintptr_t)262143);
  {
    cuuint64_t dims[3] = {64, S_LEN, 9}, strides[2] = {DM * 2, 128};
    cuuint32_t box[3] = {64, 32, 9}, es[3] = {1, 1, 1};
    enc(&rm.x, CU_TENSOR_MAP_DATA_TYPE_BFLOAT16, 3, (void*)x, dims, strides, box, es, CU_TENSOR_MAP_INTERLEAVE_NONE,
        CU_TENSOR_MAP_SWIZZLE_128B, CU_TENSOR_MAP_L2_PROMOTION_L2_128B, CU_TENSOR_MAP_FLOAT_OOB_FILL_NONE);
  }
  make_map(enc, &rm.wq, Wq, DM, 4096, 192);
  make_map(enc, &rm.wk, Wk, DM, 4096, 192);
  make_map(enc, &rm.wv, Wv, DM, 4096, 192);
  make_map(enc, &rm.wo, Wo, 4096, DM, 128);
  AMaps am;
  am.red = rm.red; am.poll = rm.poll;
  {
    cuuint64_t dims[3] = {DM, S_LEN / 2, 2}, strides[2] = {DM * 4, DM * 2};
    cuuint32_t box[3] = {32, 64, 2}, es[3] = {1, 1, 1};
    enc(&am.x, CU_TENSOR_MAP_DATA_TYPE_BFLOAT16, 3, (void*)x, dims, strides, box, es, CU_TENSOR_MAP_INTERLEAVE_NONE,
        CU_TENSOR_MAP_SWIZZLE_64B, CU_TENSOR_MAP_L2_PROMOTION_L2_128B, CU_TENSOR_MAP_FLOAT_OOB_FILL_NONE);
    cuuint64_t wdims[3] = {DM, DM, 3}, wstrides[2] = {DM * 6, DM * 2};
    cuuint32_t wbox[3] = {64, 32, 3}, wbox8[3] = {8, 32, 3};
    enc(&am.wa, CU_TENSOR_MAP_DATA_TYPE_BFLOAT16, 3, (void*)wqkvA, wdims, wstrides, wbox, es, CU_TENSOR_MAP_INTERLEAVE_NONE,
        CU_TENSOR_MAP_SWIZZLE_128B, CU_TENSOR_MAP_L2_PROMOTION_L2_128B, CU_TENSOR_MAP_FLOAT_OOB_FILL_NONE);
    enc(&am.wa8, CU_TENSOR_MAP_DATA_TYPE_BFLOAT16, 3, (void*)wqkvA, wdims, wstrides, wbox8, es, CU_TENSOR_MAP_INTERLEAVE_NONE,
        CU_TENSOR_MAP_SWIZZLE_NONE, CU_TENSOR_MAP_L2_PROMOTION_NONE, CU_TENSOR_MAP_FLOAT_OOB_FILL_NONE);
  }
  {
    cuuint64_t dims[3] = {64, S_LEN, KCAT / 64}, strides[2] = {KCAT * 2, 128};
    cuuint32_t box[3] = {64, 32, 9}, es[3] = {1, 1, 1};
    make_map(enc, &am.o, pO, S_LEN, KCAT, 32);
    enc(&am.o3, CU_TENSOR_MAP_DATA_TYPE_BFLOAT16, 3, pO, dims, strides, box, es, CU_TENSOR_MAP_INTERLEAVE_NONE,
        CU_TENSOR_MAP_SWIZZLE_128B, CU_TENSOR_MAP_L2_PROMOTION_L2_128B, CU_TENSOR_MAP_FLOAT_OOB_FILL_NONE);
  }
  make_map(enc, &am.wob, Wo, 4096, DM, 64);
  make_map(enc, &am.woa, woA, DM, DM, 64);
  make_map(enc, &am.woa16, woA, DM, DM, 16);
  {
    cuuint64_t dims[2] = {KCAT, S_LEN}, strides[1] = {KCAT * 2};
    cuuint32_t box[2] = {16, 32}, es[2] = {1, 1};
    enc(&am.o16, CU_TENSOR_MAP_DATA_TYPE_BFLOAT16, 2, pO, dims, strides, box, es, CU_TENSOR_MAP_INTERLEAVE_NONE,
        CU_TENSOR_MAP_SWIZZLE_32B, CU_TENSOR_MAP_L2_PROMOTION_NONE, CU_TENSOR_MAP_FLOAT_OOB_FILL_NONE);
  }

  rec_kernel<<<96, 384, SM_TOTAL, cudaStreamPerThread>>>(rm, x, mem0);
  cudaLaunchConfig_t cfg = {};
  cfg.gridDim = dim3(NAUX); cfg.blockDim = dim3(512); cfg.dynamicSmemBytes = A_TOTAL; cfg.stream = cudaStreamPerThread;
  cudaLaunchAttribute at[1];
  at[0].id = cudaLaunchAttributeProgrammaticStreamSerialization; at[0].val.programmaticStreamSerializationAllowed = 1;
  cfg.attrs = at; cfg.numAttrs = 1;
  if (XP & 16) cfg.numAttrs = 0;
  if (!(XP & 64)) cudaLaunchKernelEx(&cfg, aux_kernel, am, x, gate_w, (bf16*)d_out);
}
```

```cpp
#include <cuda_runtime.h>
#include <cuda_bf16.h>
#include <cuda_fp16.h>
#include <cuda.h>
#include <stdint.h>

typedef __nv_bfloat16 bf16;

constexpr int S_LEN = 2048, DM = 576, NH = 32, DH = 128, NSEG = 64, KCAT = 4096 + 576;
#define RED_LINE(i) (((i) >> 2) * 4096 + ((i) & 1) * 256 + ((i) & 2) * 512)
#define RED_SLOT(s) (((s) & 1) * 128 + ((s) & 2) * 256)

#define POLL_NS 896
#define NII 18
#define W3PRE 4
#define W3MID 4
#define GF 0
#define B5POS 0
#define NUP 4
#define UPF 1
#define B3Q 9
#define B3F 0
#define GATE 8
#define NTL 2
#define B7R 1
#define EXPOS 0
#define VW2 1
#define CLR 1
#define RFW 0
#define NIC 0
#define LEAD 0
#define FIN16 1
#define VXG 0
#define EXB 0
#define EXD 0
#define EXB2 8192
#define HDLY 0
#define F10 1
#define NPROBE 2
#define WPOS 1
#define CW 0
#define WOPF 0
#define YP 0
#define EF 4
#define MO 0
#define WE 3
#define ZR 0
#define PAD1 0
#define PAD2 0
#define KPOS 0
#define FW 1
#define EXV 2
#define NOB 0
#define QM 60
#define N5 224
#define KP(i) (((i) >> 1) + 4 * ((i) & 1))
#define SPIN_LIMIT (1 << 14)
#define XP 0

__device__ __align__(1024) bf16 g_Ocat[S_LEN * KCAT];
__device__ __align__(1024) unsigned char g_red_raw[2 * 262144];
constexpr int HINT_OFF = 2048;
__device__ __align__(16) float g_gate[S_LEN];
__device__ __align__(128) uint4 g_stats[96 * 2];
__device__ unsigned g_epoch;
__device__ unsigned g_epoch2;
__device__ __align__(128) unsigned g_oflag[NH * 32];
__device__ unsigned g_abar[3 * 32];
__device__ __align__(128) unsigned g_cflag[96 * 32];
__device__ uint2 g_sflag[96 * 4];
__device__ __align__(1024) unsigned char g_seg[NSEG * 96 * 8192];
__device__ __align__(1024) unsigned char g_km[NSEG * NH * 4096];
__device__ __align__(1024) uint2 g_part[8 * 9 * 4 * 8 * 128];
__device__ int g_err;
#define SSTAMP(seg, idx)
#define TSTAMP(idx)
#define QSTAMP(idx)
#define PROF(idx)
#define PROFP(idx)
#define STAMP(idx)
#define ASTAMP(idx)
#define WSTAMP(idx)

#define CSTAMP(idx)
#define CDECL
#define CDUMP
#define DI __device__ __forceinline__
DI uint32_t smem_u32(const void* p) { return (uint32_t)__cvta_generic_to_shared(p); }
DI uint32_t clock32() { uint32_t c; asm volatile("mov.u32 %0, %%clock;" : "=r"(c) :: "memory"); return c; }
DI uint32_t gtime() { uint32_t c; asm volatile("mov.u32 %0, %%globaltimer_lo;" : "=r"(c) :: "memory"); return c; }
DI uint32_t ldg_relaxed32(const void* p) { uint32_t v; asm volatile("ld.relaxed.gpu.global.b32 %0, [%1];" : "=r"(v) : "l"(p) : "memory"); return v; }
DI uint32_t ldg_acquire32(const void* p) { uint32_t v; asm volatile("ld.acquire.gpu.global.b32 %0, [%1];" : "=r"(v) : "l"(p) : "memory"); return v; }
DI void stg_relaxed32(void* p, uint32_t v) { asm volatile("st.relaxed.gpu.global.b32 [%0], %1;" :: "l"(p), "r"(v) : "memory"); }
DI int head_id() { int c; asm volatile("mov.u32 %0, %%clusterid.x;" : "=r"(c)); return c; }
DI uint32_t mapa(uint32_t a, uint32_t r) { uint32_t o; asm("mapa.shared::cluster.u32 %0, %1, %2;" : "=r"(o) : "r"(a), "r"(r)); return o; }
DI void cluster_arrive() { asm volatile("barrier.cluster.arrive.relaxed.aligned;" ::: "memory"); }
DI void cluster_wait() { asm volatile("barrier.cluster.wait.aligned;" ::: "memory"); }
DI void cluster_sync() { asm volatile("barrier.cluster.arrive.release.aligned;\nbarrier.cluster.wait.acquire.aligned;" ::: "memory"); }
DI void mbar_init(uint32_t b, uint32_t c) { asm volatile("mbarrier.init.shared::cta.b64 [%0], %1;" :: "r"(b), "r"(c) : "memory"); }
DI void mbar_expect(uint32_t b, uint32_t tx) { asm volatile("mbarrier.arrive.expect_tx.shared::cta.b64 _, [%0], %1;" :: "r"(b), "r"(tx) : "memory"); }
DI void mbar_arrive(uint32_t b) { asm volatile("mbarrier.arrive.shared::cta.b64 _, [%0];" :: "r"(b) : "memory"); }
DI void mbar_wait(uint32_t b, uint32_t par) {
  asm volatile("{\n.reg .pred p;\n.reg .u32 n, q;\nmov.u32 n, 0;\n"
               "WL: add.u32 n, n, 1;\nshr.u32 q, n, 12;\nxor.b32 q, q, %1;\n"
               "mbarrier.try_wait.parity.shared::cta.b64 p, [%0], q;\n@!p bra.uni WL;\n}"
               :: "r"(b), "r"(par) : "memory");
}
DI void wait_until(uint32_t t) {
  const uint32_t now = gtime();
  t = min(t, now + 8192);
  asm volatile("{\n.reg .pred p;\n.reg .u32 c;\nTL: mov.u32 c, %%globaltimer_lo;\nsetp.lt.u32 p, c, %0;\n@p bra.uni TL;\n}" :: "r"(t) : "memory");
}
template <int N> DI void pad(uint32_t never) {
  if (N && never == 0x12345) {
#pragma unroll
    for (int i = 0; i < N; i++) asm volatile("nanosleep.u32 1;" ::: "memory");
  }
}
#define PIN(v) v = __shfl_xor_sync(0xffffffffu, v, 0)
#define SCHED_FENCE(k) asm volatile("{\n.reg .pred p;\nsetp.eq.u32 p, %0, %1;\n@p exit;\n}" :: "r"(fence_reg), "r"(k) : "memory")
#define MEM_ORDER(k) asm volatile("{\n.reg .pred p;\nsetp.eq.u32 p, %0, %1;\n@p st.shared.u32 [%0], %0;\n}" :: "r"(fence_reg), "r"(k + 64) : "memory")
DI void bar_sync(int id, int n) { asm volatile("bar.sync %0, %1;" :: "r"(id), "r"(n) : "memory"); }
DI void bar_arrive(int id, int n) { asm volatile("bar.arrive %0, %1;" :: "r"(id), "r"(n) : "memory"); }
DI void fence_async() { asm volatile("fence.proxy.async.shared::cta;" ::: "memory"); }
DI void st_async4(uint32_t a, uint32_t x, uint32_t y, uint32_t z, uint32_t w, uint32_t mb) {
  asm volatile("st.async.weak.shared::cluster.mbarrier::complete_tx::bytes.v4.b32 [%0], {%1,%2,%3,%4}, [%5];"
               :: "r"(a), "r"(x), "r"(y), "r"(z), "r"(w), "r"(mb) : "memory");
}
DI void st_async2(uint32_t a, uint32_t x, uint32_t y, uint32_t mb) {
  asm volatile("st.async.weak.shared::cluster.mbarrier::complete_tx::bytes.v2.b32 [%0], {%1,%2}, [%3];"
               :: "r"(a), "r"(x), "r"(y), "r"(mb) : "memory");
}
DI void sts32(uint32_t a, uint32_t x) { asm volatile("st.shared.b32 [%0], %1;" :: "r"(a), "r"(x) : "memory"); }
DI void sts64(uint32_t a, uint32_t x, uint32_t y) { asm volatile("st.shared.v2.b32 [%0], {%1,%2};" :: "r"(a), "r"(x), "r"(y) : "memory"); }
DI void sts128(uint32_t a, uint32_t x, uint32_t y, uint32_t z, uint32_t w) {
  asm volatile("st.shared.v4.b32 [%0], {%1,%2,%3,%4};" :: "r"(a), "r"(x), "r"(y), "r"(z), "r"(w) : "memory");
}
DI uint32_t lds32(uint32_t a) { uint32_t x; asm volatile("ld.shared.b32 %0, [%1];" : "=r"(x) : "r"(a) : "memory"); return x; }
DI uint32_t lds32v(uint32_t a) { uint32_t x; asm volatile("ld.volatile.shared.b32 %0, [%1];" : "=r"(x) : "r"(a) : "memory"); return x; }
DI void lds64(uint32_t a, uint32_t& x, uint32_t& y) { asm volatile("ld.shared.v2.b32 {%0,%1}, [%2];" : "=r"(x), "=r"(y) : "r"(a) : "memory"); }
DI void lds128(uint32_t a, uint32_t* r) {
  asm volatile("ld.shared.v4.b32 {%0,%1,%2,%3}, [%4];" : "=r"(r[0]), "=r"(r[1]), "=r"(r[2]), "=r"(r[3]) : "r"(a) : "memory");
}
DI void lds128f(uint32_t a, float* r) {
  asm volatile("ld.shared.v4.f32 {%0,%1,%2,%3}, [%4];" : "=f"(r[0]), "=f"(r[1]), "=f"(r[2]), "=f"(r[3]) : "r"(a) : "memory");
}
DI void lds64f(uint32_t a, float* r) { asm volatile("ld.shared.v2.f32 {%0,%1}, [%2];" : "=f"(r[0]), "=f"(r[1]) : "r"(a) : "memory"); }
DI void ldsm4t(uint32_t* r, uint32_t a) {
  asm volatile("ldmatrix.sync.aligned.m8n8.x4.trans.shared.b16 {%0,%1,%2,%3}, [%4];"
               : "=r"(r[0]), "=r"(r[1]), "=r"(r[2]), "=r"(r[3]) : "r"(a) : "memory");
}
DI void ldsm4t_in(uint32_t* r, uint32_t a, uint32_t t) {
  asm volatile("{\n.reg .pred p;\nsetp.ne.u32 p, %5, 0;\n@p ldmatrix.sync.aligned.m8n8.x4.trans.shared.b16 {%0,%1,%2,%3}, [%4];\n}"
               : "+r"(r[0]), "+r"(r[1]), "+r"(r[2]), "+r"(r[3]) : "r"(a), "r"(t) : "memory");
}
DI void lds128_in(uint32_t* r, uint32_t a, uint32_t t) {
  asm volatile("{\n.reg .pred p;\nsetp.ne.u32 p, %5, 0;\n@p ld.shared.v4.b32 {%0,%1,%2,%3}, [%4];\n}"
               : "+r"(r[0]), "+r"(r[1]), "+r"(r[2]), "+r"(r[3]) : "r"(a), "r"(t) : "memory");
}
DI void ldsm2t_in(uint32_t* r, uint32_t a, uint32_t t) {
  asm volatile("{\n.reg .pred p;\nsetp.ne.u32 p, %3, 0;\n@p ldmatrix.sync.aligned.m8n8.x2.trans.shared.b16 {%0,%1}, [%2];\n}" : "+r"(r[0]), "+r"(r[1]) : "r"(a), "r"(t) : "memory");
}
DI void reserve2(uint32_t* r) { asm volatile("{\n.reg .u64 t;\nmov.u64 t, %%clock64;\nmov.b64 {%0, %1}, t;\n}" : "=r"(r[0]), "=r"(r[1])); }
DI void scale_sum(float& x, float& y, float s, uint32_t t) {
  asm volatile("{\n.reg .pred p;\nsetp.ne.u32 p, %2, 0;\n@p mul.f32 %0, %0, %1;\n}" : "+f"(y) : "f"(s), "r"(t));
  asm volatile("{\n.reg .pred p;\nsetp.ne.u32 p, %3, 1;\n@p fma.rn.f32 %0, %0, %1, %2;\n}" : "+f"(x) : "f"(s), "f"(y), "r"(t));
}
DI void ldsm4(uint32_t* r, uint32_t a) {
  asm volatile("ldmatrix.sync.aligned.m8n8.x4.shared.b16 {%0,%1,%2,%3}, [%4];"
               : "=r"(r[0]), "=r"(r[1]), "=r"(r[2]), "=r"(r[3]) : "r"(a) : "memory");
}
DI void st_async1(uint32_t a, uint32_t x, uint32_t mb) {
  asm volatile("st.async.weak.shared::cluster.mbarrier::complete_tx::bytes.b32 [%0], %1, [%2];" :: "r"(a), "r"(x), "r"(mb) : "memory");
}
DI void stsm4(uint32_t a, uint32_t x, uint32_t y, uint32_t z, uint32_t w) {
  asm volatile("stmatrix.sync.aligned.m8n8.x4.shared.b16 [%0], {%1,%2,%3,%4};" :: "r"(a), "r"(x), "r"(y), "r"(z), "r"(w) : "memory");
}
DI void stsm4t(uint32_t a, uint32_t x, uint32_t y, uint32_t z, uint32_t w) {
  asm volatile("stmatrix.sync.aligned.m8n8.x4.trans.shared.b16 [%0], {%1,%2,%3,%4};" :: "r"(a), "r"(x), "r"(y), "r"(z), "r"(w) : "memory");
}
DI uint32_t pack_bf16(float lo, float hi) { uint32_t r; asm("cvt.rn.bf16x2.f32 %0, %1, %2;" : "=r"(r) : "f"(hi), "f"(lo)); return r; }
DI uint32_t pack_f16(float lo, float hi) { uint32_t r; asm("cvt.rn.f16x2.f32 %0, %1, %2;" : "=r"(r) : "f"(hi), "f"(lo)); return r; }
DI float ex2(float x) { float y; asm("ex2.approx.ftz.f32 %0, %1;" : "=f"(y) : "f"(x)); return y; }
DI float rcp(float x) { float y; asm("rcp.approx.ftz.f32 %0, %1;" : "=f"(y) : "f"(x)); return y; }
DI float bf_lo(uint32_t x) { return __uint_as_float(x << 16); }
DI float bf_hi(uint32_t x) { return __uint_as_float(x & 0xffff0000u); }
DI void mma16816(float* d, const uint32_t* a, uint32_t b0, uint32_t b1) {
  asm volatile("mma.sync.aligned.m16n8k16.row.col.f32.bf16.bf16.f32 {%0,%1,%2,%3}, {%4,%5,%6,%7}, {%8,%9}, {%0,%1,%2,%3};"
               : "+f"(d[0]), "+f"(d[1]), "+f"(d[2]), "+f"(d[3]) : "r"(a[0]), "r"(a[1]), "r"(a[2]), "r"(a[3]), "r"(b0), "r"(b1));
}
DI void mma16816z(float* d, const uint32_t* a, uint32_t b0, uint32_t b1) {
  asm volatile("mma.sync.aligned.m16n8k16.row.col.f32.bf16.bf16.f32 {%0,%1,%2,%3}, {%4,%5,%6,%7}, {%8,%9}, {%10,%10,%10,%10};"
               : "=f"(d[0]), "=f"(d[1]), "=f"(d[2]), "=f"(d[3]) : "r"(a[0]), "r"(a[1]), "r"(a[2]), "r"(a[3]), "r"(b0), "r"(b1), "f"(0.f));
}
DI void mma1688z(float* d, uint32_t a0, uint32_t a1, uint32_t b0) {
  asm volatile("mma.sync.aligned.m16n8k8.row.col.f32.bf16.bf16.f32 {%0,%1,%2,%3}, {%4,%5}, {%6}, {%7,%7,%7,%7};"
               : "=f"(d[0]), "=f"(d[1]), "=f"(d[2]), "=f"(d[3]) : "r"(a0), "r"(a1), "r"(b0), "f"(0.f));
}
DI void mma1688(float* d, uint32_t a0, uint32_t a1, uint32_t b0) {
  asm volatile("mma.sync.aligned.m16n8k8.row.col.f32.bf16.bf16.f32 {%0,%1,%2,%3}, {%4,%5}, {%6}, {%0,%1,%2,%3};"
               : "+f"(d[0]), "+f"(d[1]), "+f"(d[2]), "+f"(d[3]) : "r"(a0), "r"(a1), "r"(b0));
}
DI void ldsm2t(uint32_t* r, uint32_t a) {
  asm volatile("ldmatrix.sync.aligned.m8n8.x2.trans.shared.b16 {%0,%1}, [%2];" : "=r"(r[0]), "=r"(r[1]) : "r"(a) : "memory");
}
DI uint32_t add_bf16(uint32_t a, uint32_t b) { uint32_t r; asm("add.rn.bf16x2 %0, %1, %2;" : "=r"(r) : "r"(a), "r"(b)); return r; }
DI uint32_t mul_bf16(uint32_t a, uint32_t b) { uint32_t r; asm("mul.rn.bf16x2 %0, %1, %2;" : "=r"(r) : "r"(a), "r"(b)); return r; }
DI uint64_t make_desc(uint32_t addr, uint32_t lbo, uint32_t sbo, uint32_t swz) {
  return (uint64_t)((addr & 0x3FFFF) >> 4) | ((uint64_t)(lbo >> 4) << 16) | ((uint64_t)(sbo >> 4) << 32) | ((uint64_t)swz << 62);
}
#define WG_FENCE() asm volatile("wgmma.fence.sync.aligned;" ::: "memory")
#define WG_COMMIT() asm volatile("wgmma.commit_group.sync.aligned;" ::: "memory")
#define WG_WAIT(n) asm volatile("wgmma.wait_group.sync.aligned %0;" :: "n"(n) : "memory")
#define ACC8(d, o) "+f"(d[o]), "+f"(d[o + 1]), "+f"(d[o + 2]), "+f"(d[o + 3]), "+f"(d[o + 4]), "+f"(d[o + 5]), "+f"(d[o + 6]), "+f"(d[o + 7])
DI void wgmma_n32_rs(float* d, uint32_t a0, uint32_t a1, uint32_t a2, uint32_t a3, uint64_t db, int acc) {
  asm volatile("{\n.reg .pred p;\nsetp.ne.b32 p, %21, 0;\n"
               "wgmma.mma_async.sync.aligned.m64n32k16.f32.bf16.bf16 {%0,%1,%2,%3,%4,%5,%6,%7,%8,%9,%10,%11,%12,%13,%14,%15}, "
               "{%16,%17,%18,%19}, %20, p, 1, 1, 0;\n}\n"
               : ACC8(d, 0), ACC8(d, 8) : "r"(a0), "r"(a1), "r"(a2), "r"(a3), "l"(db), "r"(acc));
}
template <int TA>
DI void wgmma_n32_ss(float* d, uint64_t da, uint64_t db, int acc) {
  asm volatile("{\n.reg .pred p;\nsetp.ne.b32 p, %18, 0;\n"
               "wgmma.mma_async.sync.aligned.m64n32k16.f32.bf16.bf16 {%0,%1,%2,%3,%4,%5,%6,%7,%8,%9,%10,%11,%12,%13,%14,%15}, "
               "%16, %17, p, 1, 1, %19, 1;\n}\n"
               : ACC8(d, 0), ACC8(d, 8) : "l"(da), "l"(db), "r"(acc), "n"(TA));
}
DI void tma_load(uint32_t dst, const CUtensorMap* m, int c0, int c1, uint32_t mb) {
  asm volatile("cp.async.bulk.tensor.2d.shared::cluster.global.mbarrier::complete_tx::bytes [%0], [%1, {%3, %4}], [%2];"
               :: "r"(dst), "l"(m), "r"(mb), "r"(c0), "r"(c1) : "memory");
}
DI void tma_load3(uint32_t dst, const CUtensorMap* m, int row, uint32_t mb) {
  asm volatile("cp.async.bulk.tensor.3d.shared::cluster.global.mbarrier::complete_tx::bytes [%0], [%1, {%3, %4, %3}], [%2];"
               :: "r"(dst), "l"(m), "r"(mb), "r"(0), "r"(row) : "memory");
}
DI bool elect_one() {
  uint32_t p;
  asm volatile("{\n.reg .pred p;\nelect.sync _|p, 0xffffffff;\nselp.u32 %0, 1, 0, p;\n}" : "=r"(p));
  return p;
}
DI void bulk_s2s(uint32_t dst, uint32_t src, uint32_t bytes, uint32_t mb) {
  asm volatile("cp.async.bulk.shared::cluster.shared::cta.mbarrier::complete_tx::bytes [%0], [%1], %2, [%3];"
               :: "r"(dst), "r"(src), "r"(bytes), "r"(mb) : "memory");
}
DI void bulk_load(uint32_t dst, const void* src, uint32_t bytes, uint32_t mb) {
  asm volatile("cp.async.bulk.shared::cluster.global.mbarrier::complete_tx::bytes [%0], [%1], %2, [%3];" :: "r"(dst), "l"(src), "r"(bytes), "r"(mb) : "memory");
}
#define EVICT_FIRST ".reg .b64 pol;\ncreatepolicy.fractional.L2::evict_first.b64 pol, 1.0;\n"
DI void bulk_load_ef(uint32_t dst, const void* src, uint32_t bytes, uint32_t mb) {
  asm volatile("{\n" EVICT_FIRST "cp.async.bulk.shared::cluster.global.mbarrier::complete_tx::bytes.L2::cache_hint [%0], [%1], %2, [%3], pol;\n}"
               :: "r"(dst), "l"(src), "r"(bytes), "r"(mb) : "memory");
}
DI void tma_load_ef(uint32_t dst, const CUtensorMap* m, int c0, int c1, uint32_t mb) {
  asm volatile("{\n" EVICT_FIRST "cp.async.bulk.tensor.2d.shared::cluster.global.mbarrier::complete_tx::bytes.L2::cache_hint [%0], [%1, {%3, %4}], [%2], pol;\n}"
               :: "r"(dst), "l"(m), "r"(mb), "r"(c0), "r"(c1) : "memory");
}
DI void tma_prefetch(const CUtensorMap* m, int c0, int c1) {
  asm volatile("cp.async.bulk.prefetch.tensor.2d.L2.global.tile [%0, {%1, %2}];" :: "l"(m), "r"(c0), "r"(c1) : "memory");
}
DI void tma_store(const CUtensorMap* m, uint32_t src, int c0, int c1) {
  asm volatile("cp.async.bulk.tensor.2d.global.shared::cta.bulk_group [%0, {%2, %3}], [%1];" :: "l"(m), "r"(src), "r"(c0), "r"(c1) : "memory");
}
DI uint4 ldg_relaxed(const void* p) {
  uint4 v;
  asm volatile("ld.relaxed.gpu.global.v4.b32 {%0,%1,%2,%3}, [%4];" : "=r"(v.x), "=r"(v.y), "=r"(v.z), "=r"(v.w) : "l"(p) : "memory");
  return v;
}
DI void stg_relaxed(void* p, uint32_t x, uint32_t y, uint32_t z, uint32_t w) {
  asm volatile("st.relaxed.gpu.global.v4.b32 [%0], {%1,%2,%3,%4};" :: "l"(p), "r"(x), "r"(y), "r"(z), "r"(w) : "memory");
}
DI void red_f16x8(void* p, uint32_t x, uint32_t y, uint32_t z, uint32_t w) {
  asm volatile("red.relaxed.gpu.global.add.noftz.v4.f16x2 [%0], {%1,%2,%3,%4};" :: "l"(p), "r"(x), "r"(y), "r"(z), "r"(w) : "memory");
}
DI void sq_acc(uint32_t& a, uint32_t x) { asm("fma.rn.bf16x2 %0, %1, %1, %0;" : "+r"(a) : "r"(x)); }
DI __half2 amax4(__half2 h, const uint32_t* v) {
  h = __hmax2_nan(__hmax2_nan(h, __habs2(*(const __half2*)&v[0])), __habs2(*(const __half2*)&v[1]));
  return __hmax2_nan(__hmax2_nan(h, __habs2(*(const __half2*)&v[2])), __habs2(*(const __half2*)&v[3]));
}
DI uint32_t wexp(__half2 h) { const uint32_t u = *(const uint32_t*)&h; return __reduce_max_sync(0xffffffffu, max((u >> 16) & 0x7fffu, u & 0x7fffu)) >> 7; }
DI float max10(const float* a) {
  return fmaxf(fmaxf(fmaxf(fmaxf(a[0], a[1]), fmaxf(a[2], a[3])), fmaxf(fmaxf(a[4], a[5]), fmaxf(a[6], a[7]))), fmaxf(a[8], a[9]));
}
DI float quad_max(float m) {
  return fmaxf(fmaxf(m, __shfl_xor_sync(0xffffffffu, m, 1)), fmaxf(__shfl_xor_sync(0xffffffffu, m, 2), __shfl_xor_sync(0xffffffffu, m, 3)));
}
DI float warp_sum(float v) {
#pragma unroll
  for (int o = 16; o; o >>= 1) v += __shfl_xor_sync(0xffffffffu, v, o);
  return v;
}

constexpr int SM_WO3 = 0;
constexpr int SM_X = 16384;
constexpr int XT = 36864;
constexpr int SM_EXP = 126976;
constexpr int SEGB = 10240;
constexpr int SM_BLK = SM_EXP + 8192;
constexpr int SM_VC = SM_BLK + 4 * SEGB;
constexpr int SM_PART = SM_VC + 16384;
constexpr int SM_QM = SM_PART + 4096;
constexpr int SM_E = SM_QM + 1024;
constexpr int SM_VM = SM_E + 1536;
constexpr int SM_OB = SM_VM + 2048;
constexpr int SM_FB = SM_OB + 2048;
constexpr int SM_STAGE = SM_X + XT;
constexpr int SM_M0 = SM_STAGE + 3 * 49152;
constexpr int SM_MISC = 210944;
constexpr int SM_WOST = 212992;
constexpr int SM_MEM = SM_WOST;
constexpr int SM_MAX = SM_MEM + 11264;
#define MEM_BLK(q) ((q) / 3 * 4096 + (q) % 3 * 1024)
constexpr int SM_TOTAL = 229376;
constexpr int MB_W = SM_MISC;
constexpr int MB_WO = SM_MISC + 24;
constexpr int MB_WO3 = SM_MISC + 32;
constexpr int MB_X = SM_MISC + 40;
constexpr int MB_S = SM_MISC + 64;
constexpr int MB_F = SM_MISC + 72;
constexpr int MB_VX = SM_MISC + 80;
constexpr int SC_FPAR = SM_MISC + 136;
constexpr int SC_DEAD = SM_MISC + 96;
constexpr int SC_UNSC = SM_MISC + 112;
constexpr int SC_OFL = SM_MISC + 1024;
constexpr int SC_EXPW = SM_MISC + 132;
constexpr int SC_ONES = SM_MISC + 144;
constexpr int SC_SS = SM_MISC + 160;
constexpr int SC_LAT = SM_MISC + 224;
constexpr int SC_TAG = SM_MISC + 232;
constexpr int SC_EPO = SM_MISC + 240;
constexpr int MB_XS = SM_MISC + 248;
constexpr int SC_XMAX = SM_MISC + 256;
constexpr int SC_PROF = 229376;

constexpr float SM_SCALE = 0.08838834764831845f;
constexpr float LOG2E = 1.4426950408889634f;
constexpr float E_LIM = 20.f;

template <bool B> struct BoolC { static constexpr bool value = B; };
template <int I> struct IntC { static constexpr int value = I; };
struct RMaps { CUtensorMap x, wq, wk, wv, wo; unsigned char* red; uint32_t poll; const unsigned char* oflag; };

DI uint32_t latest_hint(uint32_t h, uint32_t d, int s) {
  const uint32_t x = (((h | 0xc0c0c0c0u) - ((d >> 5) & 63) * 0x01010101u) & 0x3f3f3f3fu) | ((h ^ (((s >> 2) + 1) & 3) * 0x40404040u) & 0xc0c0c0c0u);
  const uint32_t y = __vmaxu2(x & 0x00ff00ffu, (x >> 8) & 0x00ff00ffu);
  return __reduce_max_sync(0xffffffffu, max(y & 0xffffu, y >> 16));
}
DI uint32_t near_half(uint32_t sb) {
  uint32_t a, b; lds64(sb + SC_LAT, a, b);
  return a > b;
}

template <int RT, int K0, int K1, bool D32 = false>
DI void xproj(float* acc, const uint32_t (&wa)[2][18][4], uint64_t xd) {
  if (XP & 1) return;
  WG_FENCE();
#pragma unroll
  for (int k = K0; k < ((XP & 128) ? K0 + 1 : K1); k++)
  {
    uint64_t d = xd + (uint64_t)(((k >> 1) * 4096 + (k & 1) * 32) >> 4);
    if (D32) asm("mov.b64 %0, {%1, %2};" : "=l"(d) : "r"((uint32_t)xd + (((k >> 1) * 4096 + (k & 1) * 32) >> 4)), "r"((uint32_t)(xd >> 32)));
    wgmma_n32_rs(acc, wa[RT][k][0], wa[RT][k][1], wa[RT][k][2], wa[RT][k][3], d, k != 0);
  }
  WG_COMMIT();
}

DI void load_w(uint32_t sb, const RMaps& tm, uint32_t rank, int c) {
  const int h = blockIdx.x / 3;
  mbar_expect(sb + MB_W + 8 * c, 49152);
  ((EF & 4) ? tma_load_ef : tma_load)(sb + SM_STAGE + c * 49152, rank < 2 ? &tm.wk : &tm.wv, h * DH + (rank == 1 ? 64 : 0), c * 192, sb + MB_W + 8 * c);
  ((EF & 4) ? tma_load_ef : tma_load)(sb + SM_STAGE + c * 49152 + 24576, rank < 2 ? &tm.wq : &tm.wv, h * DH + (rank == 0 ? 0 : 64), c * 192, sb + MB_W + 8 * c);
}
DI void seg_store(int seg, uint32_t slot, uint32_t sb) {
  if (!FW) fence_async();
  asm volatile("cp.async.bulk.global.shared::cta.bulk_group [%0], [%1], 8192;"
               :: "l"(g_seg + ((size_t)slot * 96 + blockIdx.x) * 8192), "r"(sb + SM_BLK + (seg & 3) * SEGB) : "memory");
  asm volatile("cp.async.bulk.commit_group;" ::: "memory");
}
DI void seg_publish(int seg, uint32_t sb) {
  uint32_t v, own;
  lds64(sb + SC_EPO, v, own);
  asm volatile("cp.async.bulk.wait_group 0;" ::: "memory");
  asm volatile("st.relaxed.gpu.global.v2.b32 [%0], {%1,%2};" :: "l"(&g_sflag[blockIdx.x * 4]), "r"(v + seg), "r"(own) : "memory");
}

DI void proj_role(const uint32_t sb, const RMaps& tm, const bf16* __restrict__ x, const uint32_t rank, const int wg, const int w, const int lane) {
  const bool qk = rank < 2;
  uint32_t wa[2][18][4];
  float acc[16];
  const uint64_t xd0 = make_desc(sb + SM_X + wg * 64, 16, 1024, 1);
  {
    const int rr = (lane & 7) + ((lane >> 4) << 3);
    const uint32_t col = ((2 * w + ((lane >> 3) & 1)) ^ (lane & 7)) << 4;
    float ss = 0.f;
    bar_sync(3, 256);
    mbar_wait(sb + MB_X, 0);
    auto chunk = [&](auto cc) {
      constexpr int c = decltype(cc)::value;
      QSTAMP(2 + 2 * c);
      mbar_wait(sb + MB_W + 8 * c, 0);
      QSTAMP(3 + 2 * c);
#pragma unroll
      for (int rt = 1; rt >= 0; rt--)
#pragma unroll
        for (int k = 0; k < 6; k++)
          ldsm4t(wa[rt][c * 6 + k], sb + SM_STAGE + c * 49152 + (rt ^ wg) * 24576 + (64 * (k >> 1) + 32 * wg + 16 * (k & 1) + rr) * 128 + col);
      fence_async();
      if (c < 2) {
        bar_sync(3, 256);
        QSTAMP(17 + c);
        if (threadIdx.x == 0) {
          if (c == 0) tma_load(sb + SM_X + XT, &tm.wo, rank * 192, (blockIdx.x / 3) * DH, sb + MB_WO);
          else if (blockIdx.x < NSEG) bulk_load(sb + SM_X + 2 * XT, x + blockIdx.x * 32 * DM, XT, sb + MB_XS);
          else tma_load3(sb + SM_X + 2 * XT, &tm.x, 64, sb + MB_X + 16);
        }
        __syncwarp();
      } else {
        cluster_arrive();
      }
      xproj<1, 6 * c, 6 * c + 6>(acc, wa, xd0);
      if (!qk) {
        uint32_t q[4] = {0, 0, 0, 0};
#pragma unroll
        for (int rt = 0; rt < 2; rt++)
#pragma unroll
          for (int k = 0; k < 6; k++)
#pragma unroll
            for (int i = 0; i < 4; i++) sq_acc(q[i], wa[rt][c * 6 + k][i]);
#pragma unroll
        for (int i = 0; i < 4; i++) ss += bf_lo(q[i]) + bf_hi(q[i]);
      }
      if (c < 2 && CW) WG_WAIT(0);
    };
    chunk(IntC<0>()); chunk(IntC<1>()); chunk(IntC<2>());
    ss = warp_sum(ss);
    if (lane == 0) sts32(sb + SC_SS + 4 * (wg * 4 + w), __float_as_uint(ss));
    bar_arrive(11, 384);
  }
  STAMP(1);
  QSTAMP(8);
  STAMP(2);

  uint32_t t16 = sb + (w * 32 + lane) * 16;
  uint32_t mem_a = sb + SM_MEM + wg * 512 + lane * 16;
  uint32_t fin_a = sb + (lane & 7) * 16 + SM_BLK + (qk ? (wg ^ 1) * 4096 + w * 256 + (lane & 8) * 16 + (lane & 16) * 64
                                              : wg * 4096 + w * 1024 + (lane & 8) * 64 + (lane & 16) * 8);
  PIN(t16); PIN(mem_a); PIN(fin_a);
  const uint32_t fence_reg = mem_a;
  const uint32_t fin2 = qk ? 2048 : 256;
  auto do_export = [&](auto retire, uint32_t always) {
    WG_WAIT(0);
    uint32_t p[2];
#pragma unroll
    for (int i = 0; i < 2; i++) {
      p[i] = pack_bf16(acc[8 * i], acc[8 * i + 1]);
      sts128(t16 + SM_EXP + wg * 4096 + i * 2048, p[i], pack_bf16(acc[8 * i + 2], acc[8 * i + 3]),
             pack_bf16(acc[8 * i + 4], acc[8 * i + 5]), pack_bf16(acc[8 * i + 6], acc[8 * i + 7]));
    }
    if (decltype(retire)::value)
      asm volatile("{\n.reg .pred p, q;\nsetp.ne.u32 p, %2, 0;\nsetp.ne.u32 q, %2, 1;\n@p ld.shared.b32 %0, [%3];\n@q ld.shared.b32 %1, [%3 + 4];\n"
                   "setp.ne.u32 p, %0, %1;\n@p exit;\n}" : "+r"(p[0]), "+r"(p[1]) : "r"(always), "r"(sb + SC_DEAD) : "memory");
  };
  uint32_t o[8];
  auto import = [&]() { lds128(t16 + SM_EXP + (wg ^ 1) * 4096, o); lds128(t16 + SM_EXP + (wg ^ 1) * 4096 + 2048, o + 4); };
  auto finish_from = [&](int seg, const float* d) {
    const uint32_t a = fin_a + (seg & 3) * SEGB;
#pragma unroll
    for (int i = 0; i < 8; i++) o[i] = add_bf16(pack_bf16(d[2 * i], d[2 * i + 1]), o[i]);
    stsm4(a, o[0], o[1], o[2], o[3]);
    stsm4(a + fin2, o[4], o[5], o[6], o[7]);
    if (FW) fence_async();
  };
  auto finish = [&](int seg) { WG_WAIT(0); finish_from(seg, acc); };
  auto send_v = [&](int seg, int dst) {
    if (!FW) fence_async();
    if (seg < NSEG - 1 && !(XP & 2) && elect_one())
      bulk_s2s(mapa(sb + SM_VC + (seg & 1) * 8192, dst), sb + SM_BLK + (seg & 3) * SEGB, 8192, mapa(sb + MB_VX + (seg & 1) * 8, dst));
    __syncwarp();
  };
  auto wait_v = [&](int seg) {
    if (seg < NSEG - 1 && !(XP & 2)) {
      mbar_wait(sb + MB_VX + (seg & 1) * 8, (seg >> 1) & 1);
      if (elect_one()) mbar_expect(sb + MB_VX + (seg & 1) * 8, 8192);
      __syncwarp();
    }
  };
  auto export_seg = [&](int seg, uint32_t slot) { if (!(XP & (4 | 8192)) && elect_one()) seg_store(seg, slot, sb); __syncwarp(); };
  auto publish = [&](int seg) { if (!(XP & (4 | 16384)) && elect_one()) seg_publish(seg, sb); __syncwarp(); };
  do_export(BoolC<false>(), 0);
  QSTAMP(9);
  SCHED_FENCE(11);
  xproj<0, 0, 18>(acc, wa, xd0);
  bar_sync(3, 256);
  QSTAMP(10);
  cluster_wait();
  QSTAMP(11);
  mbar_wait(sb + MB_X + 8, 0);
  QSTAMP(12);
  import();
  finish(0);
  SCHED_FENCE(12);
  uint64_t dA = xd0 + (XT >> 4);
  xproj<1, 0, 18>(acc, wa, dA);
  bar_sync(3, 256);
  if (!qk && wg == 0 && w < 2) send_v(0, w);
  if (wg == 0 && w == 3) export_seg(0, 0);
  QSTAMP(13);
  if (qk && wg == 0 && w == 0) wait_v(0);
  QSTAMP(14);
  bar_arrive(13, 384);
  if (!qk) {
    do_export(BoolC<false>(), 0);
    SCHED_FENCE(15);
    xproj<0, 0, 18>(acc, wa, dA);
    if (threadIdx.x == 0 && !(XP & 8)) { mbar_expect(sb + MB_X, XT); tma_load3(sb + SM_X, &tm.x, 96, sb + MB_X); }
    bar_sync(3, 256);
    mbar_wait(sb + MB_X + 16, 0);
    import();
    finish(1);
    SCHED_FENCE(16);
    dA += XT >> 4;
    xproj<1, 0, 18>(acc, wa, dA);
  }
  QSTAMP(15);
  WG_WAIT(0);
  bar_sync(0, 384);
  if (wg == 0 && w == 3) publish(0);
  QSTAMP(16);
  pad<PAD2>(sb);
  const int ro = __shfl_sync(0xffffffffu, near_half(sb) ^ wg, 0);
  STAMP(5);
  const uint32_t always = __shfl_sync(0xffffffffu, lds32(sb + SC_DEAD + 12), 0);
  const int ah = qk ? 1 : 2;
  int b2 = qk ? 2 : 0;
  int s = 0;
  uint32_t hint_lo = (uint32_t)(uint64_t)tm.red + HINT_OFF + blockIdx.x + (lane & 1) * 4096 + (lane >> 1) * 16384;
  PIN(hint_lo);
  auto post_hint = [&]() {
    uint32_t t;
    asm volatile("{\n.reg .u64 g;\nmov.u64 g, %%globaltimer;\ncvt.u32.u64 %0, g;\n}" : "=r"(t) :: "memory");
    asm volatile("{\n.reg .pred p;\n.reg .b64 a;\n.reg .u32 t;\nsetp.lt.u32 p, %0, %1;\nmov.b64 a, {%2, %3};\n"
                 "bfe.u32 t, %5, 5, 6;\nor.b32 t, t, %4;\n@p st.relaxed.gpu.global.u8 [a], t;\n}"
                 :: "r"(t16), "r"(sb + 160), "r"(hint_lo + RED_SLOT(s)), "r"((uint32_t)((uint64_t)tm.red >> 32)), "r"(((s >> 2) + 1) << 6), "r"(t) : "memory");
  };
  auto memproj = [&](auto second, int id, uint32_t dep, float u0, float u1, float* r) {
    constexpr bool R1 = decltype(second)::value;
    uint32_t b[NUP][4], b0[4];
    if (R1) asm volatile("{\n.reg .pred p;\nsetp.eq.u32 p, %0, %1;\n@p exit;\n}" :: "r"(dep), "r"(id) : "memory");
    bar_sync(R1 ? 2 : 1, 256);
    PROF(0);
    ldsm4t(b0, mem_a);
#pragma unroll
    for (int q = 0; q < NUP; q++) {
      if (R1 && q == 2) {
        bar_sync(11, 256);
        SCHED_FENCE(id + 1);
      }
      ldsm4t(b[q], mem_a + MEM_BLK(q + 1));
    }
    mma16816z(&acc[0], wa[0][0], b0[0], b0[1]);
    mma16816z(&acc[4], wa[1][0], b0[0], b0[1]);
    mma16816z(&acc[8], wa[0][1], b0[2], b0[3]);
    mma16816z(&acc[12], wa[1][1], b0[2], b0[3]);
#pragma unroll
    for (int q = 1; q < 9; q++) {
      uint32_t* const c = b[(q - 1) % NUP];
      mma16816(&acc[0], wa[0][2 * q], c[0], c[1]);
      mma16816(&acc[4], wa[1][2 * q], c[0], c[1]);
      mma16816(&acc[8], wa[0][2 * q + 1], c[2], c[3]);
      mma16816(&acc[12], wa[1][2 * q + 1], c[2], c[3]);
      if (R1 && q + NUP == B3Q) bar_sync(3, 256);
      if (q + NUP < 9) ldsm4t_in(c, mem_a + MEM_BLK(q + NUP), always);
      else if (R1 && q + NUP < 11) lds128_in(c, t16 + SM_PART + (10 - q - NUP) * 2048, always);
      else if (!R1 && GATE && q == GATE) { bar_arrive(11, 256); lds128_in(c, sb + SC_DEAD, always); u0 = u1 = __uint_as_float(c[3]); }
    }
#pragma unroll
    for (int i = 0; i < 8; i++) {
      const float u = i < 4 ? u0 : u1;
      r[i] = R1 ? fmaf(acc[8 + i], u, (acc[i] + __uint_as_float(b[(8 + i / 4) % NUP][i & 3])) * u) : (GATE ? fmaf(acc[i], u, acc[8 + i]) : acc[i] + acc[8 + i]);
    }
  };
  if (ro == 0) {
#pragma unroll 1
    while (true) {
      do_export(BoolC<true>(), always);
      PROFP(3);
      if (s == 8) STAMP(6);
      float r[8];
      memproj(BoolC<false>(), 30, 0, 0.f, 0.f, r);
      sts128(t16 + SM_PART, __float_as_uint(r[0]), __float_as_uint(r[1]), __float_as_uint(r[2]), __float_as_uint(r[3]));
      sts128(t16 + SM_PART + 2048, __float_as_uint(r[4]), __float_as_uint(r[5]), __float_as_uint(r[6]), __float_as_uint(r[7]));
      bar_arrive(3, 256);
      PROF(1);
      bar_sync(9, 256);
      if (!(WE & 1) && s == NSEG - 1) break;
      post_hint();
      if (w == 3 && s) publish(s);
      if ((WE & 1) && s == NSEG - 1) break;
      if (w == 1) {
        uint32_t m[8];
        lds128(t16 + SM_MAX - 512, m); lds128(t16 + SM_MAX, m + 4);
        const int em = (wexp(amax4(amax4(*(const __half2*)&m[0], m), m + 4)) >> 3) + (int)(lds32(sb + SC_UNSC + (s & 1) * 8) >> 23) - 15;
        const int ex = max(s ? em : 0, (int)lds32(sb + SC_XMAX + 4 * s)) - 127 + (int)lds32(sb + SC_EXPW);
        sts32(sb + SC_UNSC + (~s & 1) * 8, (127 + min(max(ex, -120), 120)) << 23);
        __syncwarp();
        if (elect_one()) mbar_arrive(sb + MB_S);
      }
      SCHED_FENCE(9);
      bar_sync(5, qk ? N5 : 256);
      PROF(2);
      import();
      xproj<0, 0, NII>(acc, wa, dA);
      if (NII < 18) {
        if (qk) bar_sync(7, 384);
        xproj<0, NII, 18>(acc, wa, dA);
        if (!qk) bar_sync(7, 384);
      } else {
        if (F10) WG_WAIT(0);
        bar_sync(10, 256);
        if (F10) SCHED_FENCE(17);
      }
      dA += (int64_t)(b2 ? XT >> 4 : -(XT >> 3));
      finish(s + ah);
      if (w != 3) bar_arrive(13, 384);
      PROF(6);
      SCHED_FENCE(14);
      if (NOB & 2) bar_arrive(14, 256);
      bar_sync(12, 256);
      PROF(7);
      xproj<1, 0, 18, true>(acc, wa, dA);
      if (!(NOB & 2)) bar_arrive(14, 256);
      b2 = b2 == 2 ? 0 : b2 + 1;
      s++;
      if (w == 3) {
        const uint32_t slot = (ZR & 2) || s < lds32(sb + SC_EPO + 4) ? s & 7 : s;
        bar_sync(13, 384);
        export_seg(s, slot);
      }
      PROFP(8);
    }
    if (!qk) bar_arrive(5, 256);
    if (!(WE & 1) && w == 3) publish(NSEG - 1);
  } else {
    uint32_t km[4];
    auto send_km = [&]() {
      if (XP & (4 | 4096)) return;
      uint32_t t, u;
      lds64(sb + SC_TAG, t, u);
      t |= km[0] & ~1u; u += s * (NH * 4096);
      if (qk)
        asm volatile("{\n.reg .u32 o;\n.reg .u64 a;\nshr.u32 o, %0, 1;\nadd.u32 o, o, %1;\nmad.wide.u32 a, o, 1, %2;\nst.relaxed.gpu.global.v2.b32 [a], {%3,%4};\n}"
                     :: "r"(t16), "r"(u), "l"(g_km), "r"(t), "r"(km[1]) : "memory");
      else
        asm volatile("{\n.reg .u32 o;\n.reg .u64 a;\nadd.u32 o, %0, %1;\nmad.wide.u32 a, o, 1, %2;\nst.relaxed.gpu.global.v4.b32 [a], {%3,%4,%5,%6};\n}"
                     :: "r"(t16), "r"(u), "l"(g_km), "r"(t), "r"(km[1]), "r"(km[2]), "r"(km[3]) : "memory");
    };
#pragma unroll 1
    while (true) {
      do_export(BoolC<true>(), always);
      if (!qk && w == 2) send_v(s + 1, 0);
      PROFP(3);
      if (s == 8) STAMP(6);
      const uint32_t tl = ((t16 >> 8) ^ wg) & 1, am = (t16 & ~256u) - w * 256;
      const float un = __uint_as_float(lds32(sb + SC_UNSC + (s & 1) * 8));
      float r[8];
      if (qk) {
        uint32_t a0 = am + (tl ? SM_QM : SM_BLK + 8192 + (s & 3) * SEGB);
        float u0 = wg ? un * (SM_SCALE * LOG2E) : un, u1 = wg ? un : un * (SM_SCALE * LOG2E);
        PIN(a0); PIN(u0); PIN(u1);
        memproj(BoolC<true>(), 32, a0, u0, u1, r);
        const uint32_t p0 = pack_bf16(r[0], r[1]), p1 = pack_bf16(r[2], r[3]), p2 = pack_bf16(r[4], r[5]), p3 = pack_bf16(r[6], r[7]);
        stsm4(a0, p0, p1, p2, p3);
        bar_arrive(4, 256);
        km[0] = wg ? p2 : p0; km[1] = wg ? p3 : p1;
      } else {
        const uint32_t d0 = s < NSEG - 1 ? 0 : 2, d1 = s < NSEG - 1 ? 1 : 2;
        uint32_t r0 = mapa(t16 + SM_VM, d0), r1 = mapa(t16 + SM_VM, d1);
        PIN(r0); PIN(r1);
        memproj(BoolC<true>(), 34, r0 | r1, un, un, r);
        const uint32_t p0 = pack_bf16(r[0], r[1]), p1 = pack_bf16(r[2], r[3]), p2 = pack_bf16(r[4], r[5]), p3 = pack_bf16(r[6], r[7]);
        const uint32_t v0 = wg ? p2 : p0, v1 = wg ? p3 : p1, v2 = wg ? p0 : p2, v3 = wg ? p1 : p3;
        st_async4(r0, v0, v1, v2, v3, mapa(sb + MB_S, d0));
        st_async4(r1, v0, v1, v2, v3, mapa(sb + MB_S, d1));
        bar_arrive(5, 256);
        sts128(t16 + SM_VM, v0, v1, v2, v3);
        __syncwarp();
        if (elect_one()) mbar_arrive(sb + MB_S);
        km[0] = v0; km[1] = v1; km[2] = v2; km[3] = v3;
      }
      if (!(WE & 2) && s == NSEG - 1) break;
      PROF(1);
      auto rearm = [&]() { mbar_wait(sb + MB_S, s & 1); if (elect_one()) mbar_expect(sb + MB_S, qk ? 640 + 2048 : 1280); __syncwarp(); };
      if ((WE & 2) && s == NSEG - 1 && w != 1) {
      } else if (w == 1) {
        if ((t16 & 384) == 0) stg_relaxed(tm.red + (RED_SLOT(s + 2) + RED_LINE(blockIdx.x)) + (t16 & 112), 0, 0, 0, 0);
        uint32_t base, own;
        lds64(sb + SC_EPO, base, own);
        if (!(ZR & 1))
        asm volatile("{\n.reg .pred p, q;\nsetp.lt.s32 p, %0, %1;\n@p st.shared.b32 [%2], %3;\nelect.sync _|q, 0xffffffff;\n@q cp.async.cg.shared.global [%4], [%5], 16;\n}"
                     :: "r"(lds32v(sb + SC_OFL) - base), "r"(s - 7), "r"(sb + SC_EPO + 4), "r"(min(own, s + 1)), "r"(sb + SC_OFL), "l"(tm.oflag + blockIdx.x * 128) : "memory");
      } else if (w == 0) {
        const int tn = s + ah + 1;
        if (RFW) mbar_wait(sb + MB_S, s & 1);
        if (tn + 1 < NSEG && !(XP & 8) && elect_one()) {
          const int b0 = b2 == 2 ? 0 : b2 + 1;
          mbar_expect(sb + MB_X + 8 * b0, XT);
          tma_load3(sb + SM_X + b0 * XT, &tm.x, (tn + 1) * 32, sb + MB_X + 8 * b0);
        }
        if (tn < NSEG && (!(XP & 8) || tn < 3)) mbar_wait(sb + MB_X + 8 * b2, (tn / 3) & 1);
      } else if (w == 2) {
        if (!qk) { if (VW2 < 1) send_v(s + 1, 0); if (VW2 < 2) send_v(s + 1, 1); }
      } else if (qk || !NIC) {
        rearm();
      }
      __syncwarp();
      if (KPOS == 2 && s < NSEG - 1 && w != 3) mbar_wait(sb + MB_S, s & 1);
      if (KPOS >= 16) {
#pragma unroll
        for (int i = 0; i < KPOS / 16; i++) PIN(km[1]);
      }
      send_km();
      if ((WE & 2) && s == NSEG - 1) break;
      import();
      PROF(4);
      SCHED_FENCE(10);
      if (NIC) {
        if (qk) bar_sync(7, NII < 18 ? 384 : 256);
        xproj<0, 0, NIC>(acc, wa, dA);
        if (!qk) { if (w == 3) rearm(); bar_sync(7, NII < 18 ? 384 : 256); }
      } else {
        bar_sync(7, NII < 18 ? 384 : 256);
      }
      if (NOB & 1) bar_arrive(12, 256);
      xproj<0, NIC, 18>(acc, wa, dA);
      if (!(NOB & 1)) bar_arrive(12, 256);
      dA += (int64_t)(b2 ? XT >> 4 : -(XT >> 3));
      finish(s + ah);
      if (qk && w == 0) wait_v(s + 1);
      bar_arrive(13, 384);
      PROF(6);
      SCHED_FENCE(13);
      bar_sync(14, 256);
      PROF(7);
      xproj<1, 0, 18>(acc, wa, dA);
      b2 = b2 == 2 ? 0 : b2 + 1;
      s++;
      PROFP(8);
    }
    if (!(WE & 2)) {
      send_km();
      PIN(t16);
      if (t16 - sb < 128) stg_relaxed(tm.red + (RED_SLOT(NSEG + 1) + RED_LINE(head_id() * 3 + rank)) + (t16 & 112), 0, 0, 0, 0);
    }
  }
  bar_arrive(0, 384);
  STAMP(3);
  cluster_sync();
  STAMP(4);
}

DI void attn_role(const uint32_t sb, unsigned char* smem_raw, const RMaps& tm, const uint32_t RANK, const bf16* __restrict__ x, const bf16* __restrict__ mem0,
                  const int w, const int lane) {
  const int t2 = w * 32 + lane;
  uint32_t wo[8][4], w1[8][4];
  const uint32_t wo_lane = sb + ((lane & 7) + ((lane >> 4) << 3)) * 128 + (((w + 4 * ((lane >> 3) & 1)) ^ (lane & 7)) << 4);
  unsigned char* const g_red = tm.red;
  {
    const uint32_t tag = *(volatile unsigned*)&g_epoch + 1;
    QSTAMP(0);
    bar_sync(0, 160);
    QSTAMP(1);
    cluster_arrive();
    __half2 hx = __float2half2_rn(0.f);
    if (t2 == 0) { sts32(sb + SC_OFL, (tag - 1) * NSEG); sts64(sb + SC_EPO, (tag - 1) * NSEG + 1, NSEG); sts64(sb + SC_TAG, tag & 1, blockIdx.x / 3 * 4096 + (RANK < 2 ? RANK * 1024 - (sb >> 1) : 2048 - sb)); sts32(sb + SC_UNSC, __float_as_uint(1.f)); sts128(sb + SC_DEAD, 0, 0, 0, 0x3f800000u); sts64(sb + SC_FPAR, 0, 0); sts128(sb + SC_ONES, 0x3f803f80u, 0x3f803f80u, 0x3f803f80u, 0x3f803f80u); }
    WSTAMP(27);
    uint32_t q[8] = {0, 0, 0, 0, 0, 0, 0, 0};
    QSTAMP(2);
    mbar_wait(sb + MB_WO3, 0);
    QSTAMP(3);
    uint32_t mv[5][4];
#pragma unroll
    for (int i = 0; i < 5; i++) {
      ldsm4(mv[i], sb + SM_M0 + (lane & 7) * (DM * 2) + min(w + 4 * i, 17) * 64 + (lane >> 3) * 16);
      if (blockIdx.x == 0) hx = amax4(hx, mv[i]);
    }
#pragma unroll
    for (int k = 0; k < 8; k++) {
      ldsm4t(wo[k], wo_lane + SM_WO3 + k * 2048); ldsm4t(w1[k], wo_lane + SM_WOST + k * 2048);
#pragma unroll
      for (int i = 0; i < 4; i++) { sq_acc(q[i], wo[k][i]); sq_acc(q[i], w1[k][i]); }
    }
    bar_sync(6, 128);
#pragma unroll
    for (int k = 0; k < 8; k++) sts128(sb + SM_WO3 + t2 * 16 + k * 2048, wo[k][0], wo[k][1], wo[k][2], wo[k][3]);
#pragma unroll
    for (int i = 0; i < 5; i++) {
      const int c = (w + 4 * i) * 32;
      if (c < DM) stsm4t(sb + SM_MEM + (c + c / 192 * 64 + lane) * 16, mv[i][0], mv[i][1], mv[i][2], mv[i][3]);
    }
    bar_arrive(1, 256); bar_arrive(2, 256); bar_arrive(9, 256);
    QSTAMP(4);
    mbar_wait(sb + MB_WO, 0);
    QSTAMP(5);
#pragma unroll
    for (int k = 0; k < 8; k++) ldsm4t(wo[k], wo_lane + SM_X + XT + k * 2048);
    fence_async();
    bar_sync(6, 128);
    if (t2 == 32) tma_load3(sb + SM_X + XT, &tm.x, 32, sb + MB_X + 8);
    __syncwarp();
#pragma unroll
    for (int k = 0; k < 8; k++)
#pragma unroll
      for (int i = 0; i < 4; i++) sq_acc(q[4 + i], wo[k][i]);
    float ss = 0.f;
#pragma unroll
    for (int i = 0; i < 8; i++) ss += bf_lo(q[i]) + bf_hi(q[i]);
    ss = warp_sum(ss);
    if (lane == 0) sts32(sb + SC_SS + 4 * (8 + w), __float_as_uint(ss));
    if (blockIdx.x < NSEG) {
      mbar_wait(sb + MB_XS, 0);
#pragma unroll
      for (int i = 0; i < 18; i++) { uint32_t v[4]; lds128(sb + SM_X + 2 * XT + t2 * 16 + i * 2048, v); hx = amax4(hx, v); }
      fence_async();
      bar_sync(6, 128);
      if (t2 == 32) tma_load3(sb + SM_X + 2 * XT, &tm.x, 64, sb + MB_X + 16);
      __syncwarp();
    }
    sts32(sb + SC_SS + 4 * (12 + w), wexp(hx));
    QSTAMP(6);
    bar_sync(11, 384);
    QSTAMP(7);
    if (t2 == 0) {
      float a[16];
#pragma unroll
      for (int i = 0; i < 4; i++) lds128f(sb + SC_SS + 16 * i, &a[4 * i]);
      stg_relaxed(&g_stats[blockIdx.x * 2], __float_as_uint(((a[0] + a[1]) + (a[2] + a[3])) + ((a[4] + a[5]) + (a[6] + a[7]))),
                  __float_as_uint((a[8] + a[9]) + (a[10] + a[11])),
                  max(max(__float_as_uint(a[12]), __float_as_uint(a[13])), max(__float_as_uint(a[14]), __float_as_uint(a[15]))), tag);
    }
    __syncwarp();
    WSTAMP(24);
    QSTAMP(8);
    cluster_wait();
    QSTAMP(9);
    if (w == 0) {
      uint4 v[3];
      int n = 0;
      while (true) {
#pragma unroll
        for (int i = 0; i < 3; i++) v[i] = ldg_relaxed(&g_stats[(i * 32 + lane) * 2]);
        if (__all_sync(0xffffffffu, v[0].w == tag && v[1].w == tag && v[2].w == tag) || ++n > SPIN_LIMIT) break;
        __nanosleep(100);
      }
      WSTAMP(25);
      QSTAMP(10);
      const float sv = warp_sum(__uint_as_float(v[0].x) + __uint_as_float(v[1].x) + __uint_as_float(v[2].x));
      const float so = warp_sum(__uint_as_float(v[0].y) + __uint_as_float(v[1].y) + __uint_as_float(v[2].y));
      const int expW = ((int)(__float_as_uint(sv) >> 23) + (int)(__float_as_uint(so) >> 23) - 254 + 2 + 10 + 1) >> 1;
      sts32(sb + SC_XMAX + 4 * lane, v[0].z); sts32(sb + SC_XMAX + 128 + 4 * lane, v[1].z);
      sts32(sb + SC_EXPW, expW + 1 - 15);
      if (blockIdx.x == 0 && lane == 0) *(volatile unsigned*)&g_epoch = tag;
      sts32(sb + SC_FPAR + 4, 1);
    } else if (w < 3) {
      const uint32_t u = blockIdx.x >> 4;
      unsigned char* const z = g_red + 98304 + (blockIdx.x & 15) * 128 + (u & 1) * 2048 + (u & 6) * 4096 + (((u >> 1) ^ w) & 1) * 4096 + lane * 4;
      stg_relaxed32(z, 0);
      uint32_t best = 0xffffffffu;
#pragma unroll 1
      for (int i = 0; i < 64; i++) {
        uint32_t dt;
        asm volatile("{\n.reg .pred p;\n.reg .u32 c, v;\nmov.u32 c, %%clock;\n"
                     "atom.relaxed.gpu.global.exch.b32 v, [%1], 0;\nsetp.eq.u32 p, v, 0;\nmov.u32 %0, 0;\n@p mov.u32 %0, %%clock;\nsub.u32 %0, %0, c;\n}"
                     : "=r"(dt) : "l"(z) : "memory");
        best = min(best, dt);
        if (lds32v(sb + SC_FPAR + 4) && i >= NPROBE - 1) break;
      }
      sts32(sb + SC_LAT + (w - 1) * 4, best);
    }
    QSTAMP(11);
    bar_sync(13, 384);
    bar_arrive(0, 384);
    QSTAMP(12);
    WSTAMP(26);
  }

  pad<PAD1>(sb);
  const uint32_t nh = __shfl_sync(0xffffffffu, near_half(sb), 0);
  uint32_t l16 = sb + lane * 16;
  PIN(l16);
#define LV ((l16 >> 4) & 31)
#define fence_reg l16
  const uint32_t red_lo = (uint32_t)(uint64_t)g_red, red_hi = (uint32_t)((uint64_t)g_red >> 32);
  uint32_t lp;
  auto slot = [&](int s, uint32_t c, uint32_t ofs) {
    const uint32_t lo = lp | (red_lo + ((w >> 1) * 4 + (w & 1) * 2 + ((w ^ c) & 1)) * 4096 + RED_SLOT(s) + ofs);
    uint64_t a; asm("mov.b64 %0, {%1, %2};" : "=l"(a) : "r"(lo), "r"(red_hi));
    return (unsigned char*)a;
  };
  const uint32_t always = __shfl_sync(0xffffffffu, lds32(sb + SC_DEAD + 12), 0);
  const int mode0 = RANK < 2 ? w : w | 4;
  auto hint_addr = [&](int s) { return min(LV, 23u) * 4 + (red_lo + HINT_OFF + nh * 4096 + w * 16384 + RED_SLOT(s)); };
  auto load_hints = [&](uint32_t lo) {
    uint64_t a; asm("mov.b64 %0, {%1, %2};" : "=l"(a) : "r"(lo), "r"(red_hi));
    return ldg_relaxed32((const void*)a);
  };
  int s = 0;
  bool bad = false;
#pragma unroll 1
  while (true) {
    const uint32_t par = s & 1;
    uint32_t vx[4][4], hints;
    auto load_vx = [&]() {
      const uint32_t va = l16 + (RANK < 2 ? SM_VC + par * 8192 : SM_BLK + (s & 3) * SEGB) + w * 1024 + ((LV >> 3) & 1) * 384 - (LV >> 4) * 128;
#pragma unroll
      for (int i = 0; i < 4; i++) ldsm4(vx[i], va + (i & 1) * 4096 + (i >> 1) * 256);
    };
    auto retire = [&](uint32_t x) {
      asm volatile("{\n.reg .pred p;\nsetp.eq.u32 p, %0, 0;\n@p exit;\n}" :: "r"(vx[0][0] | vx[1][0] | vx[2][0] | vx[3][0] | x) : "memory");
    };
    auto scores = [&](auto memkeys, auto first, float* sc) {
      constexpr bool MK = decltype(memkeys)::value, FIRST = decltype(first)::value;
      uint32_t kb[4][4], qb[2][4];
      const uint32_t m = LV >> 3;
      uint32_t kaddr = l16 + SM_BLK + 4096 + (s & 3) * SEGB + w * 2048 + (m & 1) * (MK ? 128 : 896) - (m >> 1) * 128;
      if (MK) { PIN(kaddr); }
      else {
#pragma unroll
        for (int k = 0; k < 4; k++) ldsm4t(kb[k], kaddr + k * 256);
      }
      if (FIRST) { load_vx(); retire(MK ? kaddr : kb[0][0] | kb[1][0] | kb[2][0] | kb[3][0] | l16); bar_sync(4, 256); PROF(4); }
      ldsm4t(qb[0], l16 + SM_QM);
      if (MK) ldsm4t(kb[0], kaddr);
      ldsm4t(qb[1], l16 + SM_QM + 512);
      if (MK) ldsm4t(kb[2], kaddr + 512);
      float c[4][4];
      mma16816z(c[0], kb[0], qb[0][0], qb[0][1]); mma16816z(c[1], kb[MK ? 0 : 1], qb[0][2], qb[0][3]);
      mma16816z(c[2], kb[2], qb[1][0], qb[1][1]); mma16816z(c[3], kb[MK ? 2 : 3], qb[1][2], qb[1][3]);
      if (FIRST && B5POS == 0) bar_arrive(5, N5);
#pragma unroll
      for (int i = 0; i < (MK ? 2 : 4); i++) sc[i] = ((c[0][i] + c[1][MK ? i + 2 : i]) + c[2][i]) + c[3][MK ? i + 2 : i];
    };
    auto send = [&](auto memkeys) {
      constexpr bool MK = decltype(memkeys)::value;
      constexpr int N = MK ? 1 : 2;
      const uint32_t sa = sb + LV * 4 + SM_E + (MK ? 1024 + RANK * 128 : RANK * 512 + w * 256);
      uint32_t ra[N][2], mb[N][2];
#pragma unroll
      for (int i = 0; i < N; i++)
#pragma unroll
        for (int j = 0; j < 2; j++) {
          ra[i][j] = mapa(sa + i * 128, j ? 2 : RANK ^ 1); mb[i][j] = mapa(sb + MB_S, j ? 2 : RANK ^ 1);
          PIN(ra[i][j]);
        }
      float sc[4];
      scores(memkeys, BoolC<true>(), sc);
      uint32_t e[N];
#pragma unroll
      for (int i = 0; i < N; i++) {
        e[i] = pack_bf16(ex2(sc[2 * i]), ex2(sc[2 * i + 1]));
        if (!(fmaxf(fabsf(sc[2 * i]), fabsf(sc[2 * i + 1])) <= E_LIM)) e[i] = 0x7fff7fffu;
        st_async1(ra[i][0], e[i], mb[i][0]);
        st_async1(ra[i][1], e[i], mb[i][1]);
      }
#pragma unroll
      for (int i = 0; i < N; i++) sts32(sa + i * 128, e[i]);
      __syncwarp();
      if (l16 == sb) mbar_arrive(sb + MB_S);
      PROF(5);
    };
    const int mode = bad ? 8 : mode0;
    if (mode < 2) {
      send(BoolC<false>());
    } else if (mode == 2) {
      send(BoolC<true>());
    } else if (mode == 8) {
      load_vx();
      retire(l16);
      const uint32_t fp = lds32(sb + SC_FPAR);
      bar_sync(6, 128);
      if (w == 0 && l16 == sb) { sts32(sb + SC_FPAR, fp ^ 1); mbar_expect(sb + MB_F, 3072); }
      if (RANK < 2 && w < 3) {
        float sc[4] = {0.f, 0.f, 0.f, 0.f};
        if (w < 2) scores(BoolC<false>(), BoolC<false>(), sc); else scores(BoolC<true>(), BoolC<false>(), sc);
#pragma unroll 1
        for (int r = 0; r < 3; r++)
          st_async4(mapa(l16 + SM_FB + RANK * 1536 + w * 512, r), __float_as_uint(sc[0]), __float_as_uint(sc[1]), __float_as_uint(sc[2]), __float_as_uint(sc[3]), mapa(sb + MB_F, r));
      }
      mbar_wait(sb + MB_F, fp);
      float a[12];
#pragma unroll
      for (int j = 0; j < 3; j++) {
        float b[4];
        lds128f(l16 + SM_FB + j * 512, a + 4 * j); lds128f(l16 + SM_FB + 1536 + j * 512, b);
#pragma unroll
        for (int i = 0; i < 4; i++) a[4 * j + i] += b[i];
      }
      float m0 = fmaxf(fmaxf(fmaxf(a[0], a[2]), fmaxf(a[4], a[6])), a[8]), m1 = fmaxf(fmaxf(fmaxf(a[1], a[3]), fmaxf(a[5], a[7])), a[9]);
#pragma unroll
      for (int o = 4; o < 32; o <<= 1) { m0 = fmaxf(m0, __shfl_xor_sync(0xffffffffu, m0, o)); m1 = fmaxf(m1, __shfl_xor_sync(0xffffffffu, m1, o)); }
#pragma unroll
      for (int i = 0; i < 5; i++) {
        const uint32_t ea = sb + SM_E + LV * 4 + (i < 4 ? i * 128 : 1024);
        sts32(ea, pack_bf16(ex2(a[2 * i] - m0), ex2(a[2 * i + 1] - m1)));
        sts32(ea + (i < 4 ? 512 : 128), 0x3f803f80u);
      }
      __syncwarp();
    } else {
      load_vx();
      if (mode == 3) bar_arrive(4, 256);
      retire(l16 + 1);
    }
    {
      uint32_t wa[4], wb[4], oc[4];
      constexpr int WS = 2048;
      const uint32_t w3a = l16 + SM_WO3 + w * 512;
      lds128(w3a + KP(0) * WS, wa); lds128(w3a + KP(1) * WS, wb); lds128(sb + SC_ONES, oc);
      if (B5POS == 1 && mode < 3) bar_arrive(5, N5);
      uint32_t e[10], p[5], vm[4], ob[4];
      float o0[4], o1[4], f[3][2][4], rs[4];
      reserve2(vm); reserve2(vm + 2); reserve2(e + 8);
      hints = hint_addr(s);
      PIN(hints);
      if (CLR & 2) asm volatile("{\n.reg .pred p;\nsetp.eq.u32 p, %0, 0;\n@p exit;\n}" :: "r"(wa[0] | wb[0] | oc[0] | hints) : "memory");
      mbar_wait(sb + MB_S, par);
      PROF(6);
      ldsm4t(e, l16 + SM_E); ldsm2t_in(e + 8, l16 + SM_E + 1024, always); ldsm4t(e + 4, l16 + SM_E + 512);
      lds128_in(vm, l16 + w * 512 + SM_VM, always);
      const float scl = __uint_as_float(lds32(sb + SC_UNSC + 8 - par * 8));
      hints = load_hints(hints);
      if (GF & 1) SCHED_FENCE(4);
#pragma unroll
      for (int i = 0; i < 4; i++) p[i] = mul_bf16(e[i], e[4 + i]);
      p[4] = mul_bf16(e[8], e[9]);
      if (MO & 4) {
        float a0[4], a1[4];
        mma16816z(o0, vx[0], p[0], p[1]); mma16816z(o1, vx[1], p[0], p[1]);
        mma16816z(a0, vx[2], p[2], p[3]); lds128_in(vx[2], w3a + KP(2) * WS, always);
        mma16816z(a1, vx[3], p[2], p[3]); lds128_in(vx[3], w3a + KP(3) * WS, always);
        mma1688(o0, vm[0], vm[1], p[4]); mma1688(o1, vm[2], vm[3], p[4]);
        mma16816z(rs, oc, p[0], p[1]); mma16816(rs, oc, p[2], p[3]); mma1688(rs, oc[0], oc[1], p[4]);
#pragma unroll
        for (int i = 0; i < 4; i++) { o0[i] += a0[i]; o1[i] += a1[i]; }
      } else {
      mma16816z(o0, vx[0], p[0], p[1]); mma16816z(o1, vx[1], p[0], p[1]); mma16816z(rs, oc, p[0], p[1]);
      mma16816(o0, vx[2], p[2], p[3]); lds128_in(vx[2], w3a + KP(2) * WS, always);
      mma16816(o1, vx[3], p[2], p[3]); lds128_in(vx[3], w3a + KP(3) * WS, always);
      mma16816(rs, oc, p[2], p[3]);
      mma1688(o0, vm[0], vm[1], p[4]); mma1688(o1, vm[2], vm[3], p[4]); mma1688(rs, oc[0], oc[1], p[4]);
      }
      stsm4(l16 + w * 512 + SM_OB, pack_bf16(o0[0], o0[1]), pack_bf16(o0[2], o0[3]), pack_bf16(o1[0], o1[1]), pack_bf16(o1[2], o1[3]));
      bar_sync(6, 128);
      PROF(7);
      ldsm4t_in(oc, l16 + SM_OB, always);
      bad = __any_sync(0xffffffffu, !(rs[0] + rs[1] > 0.f) && !bad);
      rs[0] *= scl; rs[1] *= scl;
      asm volatile("{\n.reg .pred p;\nsetp.ne.u32 p, %1, 0;\n@p rcp.approx.ftz.f32 %0, %0;\n}" : "+f"(rs[0]) : "r"(always));
      asm volatile("{\n.reg .pred p;\nsetp.ne.u32 p, %1, 1;\n@p rcp.approx.ftz.f32 %0, %0;\n}" : "+f"(rs[1]) : "r"(always));
      asm volatile("lop3.b32 %0, %1, %2, %3, 0xfe;" : "=r"(lp) : "r"((l16 & 128) * 2), "r"((l16 & 256) * 4), "r"(l16 & 112));
      if (bad) continue;
      ldsm4t(ob, l16 + SM_OB + 512);
      mma16816z(f[2][0], wa, oc[0], oc[1]); mma16816z(f[2][1], wb, oc[2], oc[3]);
      mma16816z(f[0][0], wo[0], oc[0], oc[1]); mma16816z(f[0][1], wo[4], oc[2], oc[3]);
      mma16816z(f[1][0], w1[0], oc[0], oc[1]); mma16816z(f[1][1], w1[4], oc[2], oc[3]);
      ldsm4t_in(oc, l16 + SM_OB + 1024, always);
      mma16816(f[2][0], vx[2], ob[0], ob[1]); lds128_in(vx[2], w3a + KP(4) * WS, always);
      mma16816(f[2][1], vx[3], ob[2], ob[3]); lds128_in(vx[3], w3a + KP(5) * WS, always);
      mma16816(f[0][0], wo[1], ob[0], ob[1]); mma16816(f[0][1], wo[5], ob[2], ob[3]);
      mma16816(f[1][0], w1[1], ob[0], ob[1]); mma16816(f[1][1], w1[5], ob[2], ob[3]);
      ldsm4t_in(ob, l16 + SM_OB + 1536, always);
      mma16816(f[0][0], wo[2], oc[0], oc[1]); mma16816(f[0][1], wo[6], oc[2], oc[3]);
      mma16816(f[2][0], vx[2], oc[0], oc[1]); lds128_in(vx[2], w3a + KP(6) * WS, always);
      mma16816(f[2][1], vx[3], oc[2], oc[3]); lds128_in(vx[3], w3a + KP(7) * WS, always);
      mma16816(f[1][0], w1[2], oc[0], oc[1]); mma16816(f[1][1], w1[6], oc[2], oc[3]);
      mma16816(f[0][0], wo[3], ob[0], ob[1]); mma16816(f[0][1], wo[7], ob[2], ob[3]);
      mma16816(f[1][0], w1[3], ob[0], ob[1]); mma16816(f[1][1], w1[7], ob[2], ob[3]);
      mma16816(f[2][0], vx[2], ob[0], ob[1]); mma16816(f[2][1], vx[3], ob[2], ob[3]);
      bar_arrive(7, NII < 18 ? 384 : 256);
      lds128_in(ob, sb + SC_DEAD, always);
      uint32_t h[3][2];
#pragma unroll
      for (int j = 0; j < 3; j++)
#pragma unroll
        for (int i = 0; i < 2; i++)
        {
          scale_sum(f[j][1][2 * i], f[j][0][2 * i], rs[0], always); scale_sum(f[j][1][2 * i + 1], f[j][0][2 * i + 1], rs[1], always);
          h[j][i] = pack_f16(f[j][1][2 * i], f[j][1][2 * i + 1]);
        }
      const uint32_t rofs = RANK * 32768;
      red_f16x8(slot(s, RANK >> 1, rofs), h[0][0], h[1][0], h[2][0], 0x3c00u);
      red_f16x8(slot(s, (RANK >> 1) ^ 1, rofs), h[0][1], h[1][1], h[2][1], 0x3c00u);
      if (NII == 18) bar_arrive(10, 256);
      SCHED_FENCE(5);
      l16 += ob[B7R];
    }
    {
    PROF(8);
    const uint32_t ma0 = l16 + SM_MEM + w * 128 + (LV >> 3) * 896 + nh * 512;
    const unsigned char* const sl[2] = {slot(s, nh, 0), slot(s, nh ^ 1, 0)};
    uint32_t dl = gtime() - 1984;
    uint32_t late = latest_hint(hints, dl, s);
    if (late >= 64) {
      int n = 0;
#pragma unroll 1
      do {
        hints = load_hints(hint_addr(s));
        dl = gtime() - 1984;
        late = latest_hint(hints, dl, s);
      } while (late >= 64 && ++n < SPIN_LIMIT);
    }
    dl += late * 32 + tm.poll;
    PROF(9);
    {
      auto wait_until = [&](uint32_t t) {
        asm volatile("{\n.reg .pred p;\n.reg .s32 c;\n.reg .u64 t;\nTL: mov.u64 t, %%globaltimer;\ncvt.u32.u64 c, t;\nsub.s32 c, c, %0;\nsetp.lt.s32 p, c, 0;\n@p bra.uni TL;\n}" :: "r"(t + (l16 & 15)) : "memory");
      };
      uint4 v[2][3];
      auto load = [&](int c) {
#pragma unroll
        for (int r = 0; r < 3; r++) v[c][r] = ldg_relaxed(sl[c ^ (r >> 1)] + r * 32768);
      };
      auto decode = [&](int c, int n) {
        uint32_t q[9];
        __half2 hm;
        const uint32_t ma = ma0 ^ (c * 512);
#pragma unroll
        for (int i = 0; i < 9; i++) {
          const uint32_t h = i % 3 == 0 ? v[c][i / 3].x : (i % 3 == 1 ? v[c][i / 3].y : v[c][i / 3].z);
          const float2 f = __half22float2(*(const __half2*)&h);
          q[i] = pack_bf16(f.x, f.y);
          hm = i ? __hmax2(hm, __habs2(*(const __half2*)&h)) : __habs2(*(const __half2*)&h);
        }
#pragma unroll
        for (int r = 0; r < 3; r++) stsm4(ma + r * 4096, q[3 * r], q[3 * r + 1], q[3 * r + 2], r < 2 ? v[c][r].w : *(const uint32_t*)&hm);
        const bool done = __all_sync(0xffffffffu, v[c][0].w == 0x5000u && v[c][1].w == 0x5000u && v[c][2].w == 0x5000u) || n > SPIN_LIMIT;
        asm volatile("{\n.reg .pred p;\nsetp.ne.u32 p, %0, 0;\n@p bar.arrive %1, 256;\n}" :: "r"((int)done), "r"(1 + c) : "memory");
        return done;
      };
      if (LEAD) { wait_until(dl - LEAD); load(1); }
      int n = MO & 1 ? l16 & 15 : 0;
      if (MO & 1) PIN(n);
      if (MO & 2) {
        const uint32_t t = __shfl_sync(0xffffffffu, dl, 0);
        asm volatile("{\n.reg .pred p;\n.reg .s32 c;\nTL: mov.u32 c, %%globaltimer_lo;\nsub.s32 c, c, %0;\nsetp.lt.s32 p, c, 0;\n@p bra.uni TL;\n}" :: "r"(t) : "memory");
      } else wait_until(dl);
      if (HDLY) {
        uint32_t c;
        asm volatile("{\n.reg .u64 g;\nmov.u64 g, %%clock64;\ncvt.u32.u64 %0, g;\n}" : "=r"(c) :: "memory");
#pragma unroll
        for (int i = 1; i < HDLY; i++) asm volatile("mul.lo.u32 %0, %0, %1;" : "+r"(c) : "r"(l16));
        asm volatile("{\n.reg .pred p;\nsetp.ne.u32 p, %0, 0;\n@p exit;\n}" :: "r"(c & always & 1) : "memory");
      }
      PROF(10);
#pragma unroll 1
      do {
        load(0);
        if (!LEAD) load(1);
        asm volatile("{\n.reg .pred p;\nsetp.eq.u32 p, %0, 0;\n@p bar.sync 13, 384;\n}" :: "r"(n) : "memory");
      } while (!decode(0, n++));
      PROF(11);
#pragma unroll 1
      while (!decode(1, n++)) load(1);
      bar_arrive(9, 256);
      PROF(12);
    }
    PROF(13);
    if (++s == NSEG - 1) break;
    }
  }
#undef fence_reg
  if (RANK < 2) bar_arrive(4, 256);
  bar_sync(0, 384);
  cluster_sync();
}

__global__ void __cluster_dims__(3, 1, 1) __launch_bounds__(384, 1)
rec_kernel(const __grid_constant__ RMaps tm, const bf16* __restrict__ x, const bf16* __restrict__ mem0) {
  extern __shared__ __align__(1024) unsigned char smem_raw[];
  const uint32_t sb = smem_u32(smem_raw);
  const int tid = threadIdx.x, lane = tid & 31;
  const int wg = __shfl_sync(0xffffffffu, tid >> 7, 0);
  const int w = __shfl_sync(0xffffffffu, (tid >> 5) & 3, 0);
  uint32_t rank; asm("mov.u32 %0, %%cluster_ctarank;" : "=r"(rank));
  STAMP(0);
  asm volatile("griddepcontrol.launch_dependents;" ::: "memory");
    if (tid == 0) {
      const int h = blockIdx.x / 3;
      mbar_init(sb + MB_XS, 1);
      for (int i = 0; i < 3; i++) { mbar_init(sb + MB_W + 8 * i, 1); mbar_init(sb + MB_X + 8 * i, 1); }
      mbar_init(sb + MB_WO3, 1);
      fence_async();
      load_w(sb, tm, rank, 0);
      mbar_expect(sb + MB_X, XT);
      tma_load3(sb + SM_X, &tm.x, 0, sb + MB_X);
      if (WPOS == 2) load_w(sb, tm, rank, 1);
      mbar_expect(sb + MB_WO3, 32768 + 8 * DM * 2);
      tma_load(sb + SM_WOST, &tm.wo, rank * 192 + 64, h * DH, sb + MB_WO3);
      tma_load(sb + SM_WO3, &tm.wo, rank * 192 + 128, h * DH, sb + MB_WO3);
      bulk_load(sb + SM_M0, mem0, 8 * DM * 2, sb + MB_WO3);
      if (WOPF) tma_prefetch(&tm.wo, rank * 192, h * DH);
      if (WPOS == 1) load_w(sb, tm, rank, 1);
      load_w(sb, tm, rank, 2);
      mbar_init(sb + MB_WO, 1);
      mbar_init(sb + MB_S, rank < 2 ? 5 : 6);
      mbar_init(sb + MB_F, 1);
      mbar_init(sb + MB_VX, 1); mbar_init(sb + MB_VX + 8, 1);
      asm volatile("fence.mbarrier_init.release.cluster;" ::: "memory");
      fence_async();
      mbar_expect(sb + MB_X + 8, XT); mbar_expect(sb + MB_X + 16, XT);
      mbar_expect(sb + MB_WO, 16384); mbar_expect(sb + MB_XS, XT);
      mbar_expect(sb + MB_S, rank < 2 ? 640 + 2048 : 1280);
      mbar_expect(sb + MB_VX, 8192); mbar_expect(sb + MB_VX + 8, 8192);
    }
  __syncwarp();
  if (wg < 2) {
    asm volatile("setmaxnreg.inc.sync.aligned.u32 192;");
    __syncwarp();
    QSTAMP(0);
    if (tid < 32) bar_arrive(0, 160);
    QSTAMP(1);
    proj_role(sb, tm, x, rank, wg, w, lane);
  } else {
    asm volatile("setmaxnreg.dec.sync.aligned.u32 120;");
    attn_role(sb, smem_raw, tm, rank, x, mem0, w, lane);
  }
}

constexpr int NAUX = 36;
constexpr int A_ST = 6, A_STAGE = 8192 + 12288, A_W8 = A_ST * A_STAGE, A_EXC = A_W8 + A_ST * 1536, A_ROWS = 57;
constexpr int A_IN = A_EXC + 8 * 2304, A_INB = 3 * SEGB, A_OST = A_IN + 2 * A_INB, A_P = A_OST + 8192, A_G = A_P + 3072;
constexpr int A_BAR = A_G + 1024;
constexpr int A_XT = A_BAR + 1024, A_XW = A_XT;
constexpr int A_TOTAL = A_XT + 4096;
static_assert(A_IN % 1024 == 0 && A_XT % 1024 == 0 && A_IN >= 4 * XT && A_IN + 64 * DM * 2 <= A_BAR && A_TOTAL <= 232448, "side kernel shared memory");
struct AMaps { CUtensorMap x, wa, wa8, o, o3, o16, wob, woa, woa16; const unsigned char* red; uint32_t poll; };

DI void wgmma_n192_ss_nt(float* d, uint64_t da, uint64_t db, int acc) {
  asm volatile("{\n.reg .pred p;\nsetp.ne.b32 p, %98, 0;\n"
               "wgmma.mma_async.sync.aligned.m64n192k16.f32.bf16.bf16 {"
               "%0,%1,%2,%3,%4,%5,%6,%7,%8,%9,%10,%11,%12,%13,%14,%15,%16,%17,%18,%19,%20,%21,%22,%23,%24,%25,%26,%27,%28,%29,%30,%31,"
               "%32,%33,%34,%35,%36,%37,%38,%39,%40,%41,%42,%43,%44,%45,%46,%47,%48,%49,%50,%51,%52,%53,%54,%55,%56,%57,%58,%59,%60,%61,%62,%63,"
               "%64,%65,%66,%67,%68,%69,%70,%71,%72,%73,%74,%75,%76,%77,%78,%79,%80,%81,%82,%83,%84,%85,%86,%87,%88,%89,%90,%91,%92,%93,%94,%95"
               "}, %96, %97, p, 1, 1, 0, 1;\n}\n"
               : ACC8(d, 0), ACC8(d, 8), ACC8(d, 16), ACC8(d, 24), ACC8(d, 32), ACC8(d, 40), ACC8(d, 48), ACC8(d, 56),
                 ACC8(d, 64), ACC8(d, 72), ACC8(d, 80), ACC8(d, 88) : "l"(da), "l"(db), "r"(acc));
}
DI void wgmma_n24_ss_nt(float* d, uint64_t da, uint64_t db, int acc) {
  asm volatile("{\n.reg .pred p;\nsetp.ne.b32 p, %14, 0;\n"
               "wgmma.mma_async.sync.aligned.m64n24k16.f32.bf16.bf16 {%0,%1,%2,%3,%4,%5,%6,%7,%8,%9,%10,%11}, %12, %13, p, 1, 1, 0, 1;\n}\n"
               : ACC8(d, 0), "+f"(d[8]), "+f"(d[9]), "+f"(d[10]), "+f"(d[11]) : "l"(da), "l"(db), "r"(acc));
}
DI void tma_load3d(uint32_t dst, const CUtensorMap* m, int c0, int c1, int c2, uint32_t mb) {
  asm volatile("cp.async.bulk.tensor.3d.shared::cluster.global.mbarrier::complete_tx::bytes [%0], [%1, {%3, %4, %5}], [%2];"
               :: "r"(dst), "l"(m), "r"(mb), "r"(c0), "r"(c1), "r"(c2) : "memory");
}
DI uint32_t trans8(uint32_t x) { uint32_t r; asm("movmatrix.sync.aligned.m8n8.trans.b16 %0, %1;" : "=r"(r) : "r"(x)); return r; }
DI void wgmma_n40_ss(float* d, uint64_t da, uint64_t db, int acc) {
  asm volatile("{\n.reg .pred p;\nsetp.ne.b32 p, %22, 0;\n"
               "wgmma.mma_async.sync.aligned.m64n40k16.f32.bf16.bf16 {%0,%1,%2,%3,%4,%5,%6,%7,%8,%9,%10,%11,%12,%13,%14,%15,%16,%17,%18,%19}, "
               "%20, %21, p, 1, 1, 1, 1;\n}\n"
               : ACC8(d, 0), ACC8(d, 8), "+f"(d[16]), "+f"(d[17]), "+f"(d[18]), "+f"(d[19]) : "l"(da), "l"(db), "r"(acc));
}
DI uint2 ldg_relaxed64(const void* p) {
  uint2 v; asm volatile("ld.relaxed.gpu.global.v2.b32 {%0,%1}, [%2];" : "=r"(v.x), "=r"(v.y) : "l"(p) : "memory"); return v;
}
template <int ST> DI void ldg8x64(uint32_t* m, const void* p) {
  asm volatile("ld.relaxed.gpu.global.v2.b32 {%0,%1}, [%16];\nld.relaxed.gpu.global.v2.b32 {%2,%3}, [%16 + %17];\n"
               "ld.relaxed.gpu.global.v2.b32 {%4,%5}, [%16 + %18];\nld.relaxed.gpu.global.v2.b32 {%6,%7}, [%16 + %19];\n"
               "ld.relaxed.gpu.global.v2.b32 {%8,%9}, [%16 + %20];\nld.relaxed.gpu.global.v2.b32 {%10,%11}, [%16 + %21];\n"
               "ld.relaxed.gpu.global.v2.b32 {%12,%13}, [%16 + %22];\nld.relaxed.gpu.global.v2.b32 {%14,%15}, [%16 + %23];"
               : "=r"(m[0]), "=r"(m[1]), "=r"(m[2]), "=r"(m[3]), "=r"(m[4]), "=r"(m[5]), "=r"(m[6]), "=r"(m[7]),
                 "=r"(m[8]), "=r"(m[9]), "=r"(m[10]), "=r"(m[11]), "=r"(m[12]), "=r"(m[13]), "=r"(m[14]), "=r"(m[15])
               : "l"(p), "n"(ST), "n"(2 * ST), "n"(3 * ST), "n"(4 * ST), "n"(5 * ST), "n"(6 * ST), "n"(7 * ST) : "memory");
}
template <int ST> DI void ldg4x128(uint32_t* m, const void* p) {
  asm volatile("ld.relaxed.gpu.global.v4.b32 {%0,%1,%2,%3}, [%16];\nld.relaxed.gpu.global.v4.b32 {%4,%5,%6,%7}, [%16 + %17];\n"
               "ld.relaxed.gpu.global.v4.b32 {%8,%9,%10,%11}, [%16 + %18];\nld.relaxed.gpu.global.v4.b32 {%12,%13,%14,%15}, [%16 + %19];"
               : "=r"(m[0]), "=r"(m[1]), "=r"(m[2]), "=r"(m[3]), "=r"(m[4]), "=r"(m[5]), "=r"(m[6]), "=r"(m[7]),
                 "=r"(m[8]), "=r"(m[9]), "=r"(m[10]), "=r"(m[11]), "=r"(m[12]), "=r"(m[13]), "=r"(m[14]), "=r"(m[15])
               : "l"(p), "n"(ST), "n"(2 * ST), "n"(3 * ST) : "memory");
}
template <int N, int ST> DI bool stale(const uint32_t* m, uint32_t tag) {
  uint32_t x = m[0] ^ tag;
#pragma unroll
  for (int i = 1; i < N; i++) asm("lop3.b32 %0, %0, %1, %2, 0xf6;" : "+r"(x) : "r"(m[i * ST]), "r"(tag));
  return __any_sync(0xffffffffu, x & 1);
}
DI bool mbar_test(uint32_t b, uint32_t par) {
  uint32_t r; asm volatile("{\n.reg .pred p;\nmbarrier.test_wait.parity.shared::cta.b64 p, [%1], %2;\nselp.u32 %0, 1, 0, p;\n}" : "=r"(r) : "r"(b), "r"(par) : "memory");
  return r;
}
DI int wait_flags(const unsigned* p, bool active, unsigned base, int seg) {
  int n = 0, m;
  while (true) {
    m = __reduce_min_sync(0xffffffffu, active ? (int)(ldg_acquire32(p) - base) : NSEG);
    if (m > seg || ++n > SPIN_LIMIT) break;
    __nanosleep((YP & 32) ? 400 : 40);
  }
  return max(m, seg + 1);
}
DI void wait_count(const unsigned* p, unsigned target) {
  int n = 0;
  unsigned v;
  while (true) {
    asm volatile("ld.acquire.gpu.global.b32 %0, [%1];" : "=r"(v) : "l"(p) : "memory");
    if ((int)(v - target) >= 0 || ++n > SPIN_LIMIT) break;
    __nanosleep(64);
  }
}
#define PACE_NEXT 800
#define AWARM 0
#define WPF 3
#define UNP 64
#define ADLY 0
#define ODLY 100
#define SDLY 0
#define RSL 100
#define TWO 0
#define ALLW 1
#define AE 0
#define PING 60
#define FLAG 2
#define FPOS 1
#define QB 1
#define Q_LO 0
#define Q_HI 320
DI bool tick_wait(uint32_t pace, int step) {
  const int n = lds32v(pace);
  if (n <= step) mbar_wait(pace + 8, n & 1);
  return n <= step;
}
DI void quiet_wait(uint32_t pace) {
  uint32_t n, d;
  asm volatile("ld.volatile.shared.v2.b32 {%0,%1}, [%2];" : "=r"(n), "=r"(d) : "r"(pace) : "memory");
  if (n - 1 < NSEG - 2 && (int)(gtime() - d) > Q_HI) mbar_wait(pace + 8, n & 1);
}
DI void sleep_until(uint32_t t) {
  for (int n = 0; n < 64; n++) {
    const int r = t - gtime();
    if (r <= 0) break;
    __nanosleep(r >> 1);
  }
}
DI void aux_barrier(int i, unsigned epoch, bool wait = true) {
  asm volatile("fence.proxy.async;" ::: "memory");
  asm volatile("red.release.gpu.global.add.u32 [%0], 1;" :: "l"(&g_abar[i * 32]) : "memory");
  if (!wait) return;
  wait_count(&g_abar[i * 32], NAUX * (epoch + 1));
  asm volatile("fence.proxy.async;" ::: "memory");
}

__global__ void __launch_bounds__(512, 1)
aux_kernel(const __grid_constant__ AMaps tm, const bf16* __restrict__ x, const bf16* __restrict__ gate_w, bf16* __restrict__ out) {
  extern __shared__ __align__(1024) unsigned char smem_raw[];
  const uint32_t sb = smem_u32(smem_raw);
  const uint32_t full1 = sb + A_BAR, empty1 = full1 + 8 * A_ST, fullw = empty1 + 8 * A_ST, full3 = fullw + 16, empty3 = full3 + 32,
                 fulla = empty3 + 32, emptya = fulla + 32, fullg = emptya + 16, pace = fullg + 8;
  const int tid = threadIdx.x, lane = tid & 31, cta = blockIdx.x;
  const int wg = __shfl_sync(0xffffffffu, tid >> 7, 0), w = __shfl_sync(0xffffffffu, (tid >> 5) & 3, 0);
  ASTAMP(14);
  const unsigned epoch = *(volatile unsigned*)&g_epoch2;
  if (tid == 0) {
    for (int i = 0; i < A_ST; i++) { mbar_init(full1 + 8 * i, 1); mbar_init(empty1 + 8 * i, 8); }
    mbar_init(fullw, 1); mbar_init(fullw + 8, 1); mbar_init(fullg, 1);
    for (int i = 0; i < 2; i++) { mbar_init(fulla + 16 * i, 2); mbar_init(fulla + 16 * i + 8, 1); mbar_init(emptya + 8 * i, 4); }
    sts64(pace, 0, 0); mbar_init(pace + 8, 1); sts32(pace + 16, 0); sts64(pace + 24, 65536, 0xffff0000u);
    for (int i = 0; i < 4; i++) { mbar_init(full3 + 8 * i, 1); mbar_init(empty3 + 8 * i, cta < NH ? 8 : 4); }
    fence_async();
  }
  auto load_a = [&](int st, int k, int col) {
    mbar_expect(full1 + 8 * st, A_STAGE + 1536);
    tma_load3d(sb + st * A_STAGE, &tm.x, k, (cta >> 1) * A_ROWS - 7, 0, full1 + 8 * st);
    tma_load3d(sb + st * A_STAGE + 8192, &tm.wa, col, k, 0, full1 + 8 * st);
    tma_load3d(sb + A_W8 + st * 1536, &tm.wa8, col + 64, k, 0, full1 + 8 * st);
  };
  if (AE && tid < 32 && !(XP & 256)) {
    __syncwarp();
#pragma unroll 1
    for (int st = 0; st < A_ST; st++) if (elect_one()) load_a(st, st * 32, (cta & 1) * (DM / 2));
  }
  __syncthreads();
  ASTAMP(0);
  const bool wide = cta < NH;
  auto p3_ks = [&](int g) { return wide ? cta >> 2 : 2 * (cta - NH) + g; };
  auto p3_mt = [&](int g) { return wide ? 2 * (cta & 3) + g : 8; };
  const unsigned fbase = epoch * NSEG;
  if (wg == 3) {
    asm volatile("setmaxnreg.dec.sync.aligned.u32 %0;" :: "n"(TWO ? 32 : 48));
    if (w == 1 && cta < NH) {
#pragma unroll 1
      for (int seg = 0; seg < ((XP & 2048) ? 0 : NSEG); seg++) {
        bar_arrive(5, 160);
        if (seg > 0 && lane == 0) {
          asm volatile("cp.async.bulk.wait_group 0;" ::: "memory");
          stg_relaxed32(&g_oflag[cta * 32], fbase + seg);
        }
        if (!(ZR & 4) && lane < 3) stg_relaxed32(&g_cflag[(cta * 3 + lane) * 32], fbase + seg);
        __syncwarp();
        bar_sync(4, 160);
        if (QM & 16) tick_wait(pace, seg + 1);
        if (lane == 0) {
          fence_async();
          if (!(YP & 2)) {
          tma_store(&tm.o, sb + A_OST, cta * DH, seg * 32);
          tma_store(&tm.o, sb + A_OST + 4096, cta * DH + 64, seg * 32);
          }
          asm volatile("cp.async.bulk.commit_group;" ::: "memory");
          asm volatile("cp.async.bulk.wait_group.read 0;" ::: "memory");
        }
        __syncwarp();
      }
      if (lane == 0) {
        asm volatile("cp.async.bulk.wait_group 0;" ::: "memory");
        { const int seg = NSEG - 1; TSTAMP(2); }
        stg_relaxed32(&g_oflag[cta * 32], fbase + NSEG);
      }
    }
    if (w == 2 && cta < NH) {
      const uint32_t ktag = (epoch + 1) & 1, ma = sb + A_IN + 8192 + lane * 16;
      int avail = 0;
      int own = 0;
      bar_sync(10, 64);
#pragma unroll 1
      for (int seg = 0; seg < ((XP & 2048) ? 0 : NSEG); seg++) {
        if (avail <= seg) {
          int n = 0;
          while (true) {
            asm volatile("ld.acquire.gpu.global.v2.b32 {%0,%1}, [%2];" : "=r"(avail), "=r"(own) : "l"(&g_sflag[(cta * 3 + min(lane, 2)) * 4]) : "memory");
            avail = __reduce_min_sync(0xffffffffu, (int)(avail - fbase));
            if (avail > seg || ++n > SPIN_LIMIT) break;
            __nanosleep(40);
          }
        }
        if ((QM & 8) && seg < UNP) tick_wait(pace, seg);
        TSTAMP(0);
        const unsigned char* km = g_km + (size_t)(seg * NH + cta) * 4096 + lane * 8;
        uint32_t m[16];
        const float g = __ldcg(&g_gate[seg * 32 + lane]);
        ldg8x64<256>(m, km);
        const uint32_t b = seg & 1, full = fulla + 16 * b, mb = ma + b * A_INB;
        mbar_wait(emptya + 8 * b, (~seg >> 1) & 1);
        if (lane < 2) mbar_expect(full + 8 * lane, (YP & 8) ? 0 : 16384 >> lane);
        __syncwarp();
        const int slot = seg < own ? seg & 7 : seg;
        if (lane < 3 && !(YP & 8)) bulk_load(sb + A_IN + b * A_INB + lane * SEGB, g_seg + ((size_t)slot * 96 + cta * 3 + lane) * 8192, 8192, full + (lane & 2) * 4);
        int n = 0;
#pragma unroll 1
        while (stale<8, 2>(m, ktag) && ++n < SPIN_LIMIT) { if (seg < UNP - 1) __nanosleep(200); ldg8x64<256>(m, km); }
        TSTAMP(1);
#pragma unroll
        for (int i = 0; i < 4; i++) stsm4(mb + (i >> 1) * SEGB + (i & 1) * 512, m[4 * i], m[4 * i + 1], m[4 * i + 2], m[4 * i + 3]);
        sts32(sb + A_G + b * 128 + lane * 4, __float_as_uint(1.f - g));
        fence_async();
        __syncwarp();
        if (lane == 0) mbar_arrive(full);
      }
    }
    if (w == 3 && QM) {
      const unsigned char* const hp = tm.red + HINT_OFF + 65536 + (cta & 1) * 4096 + min(lane, 23) * 4;
      uint32_t d = 0;
      int s = 0, n = 0;
#pragma unroll 1
      while (s < NSEG - 1) {
        const uint32_t h = ldg_relaxed32(hp + RED_SLOT(s)), t = (gtime() - 1984) & ~31u, late = latest_hint(h, t, s);
        if (late < 64) {
          d = t + late * 32 + tm.poll + Q_LO;
          sleep_until(d);
          s++; n = 0;
          if (lane == 0) { mbar_arrive(pace + 8); sts64(pace, s < NSEG - 1 ? s : 2 * NSEG, d); }
          sleep_until(d + PACE_NEXT);
        } else {
          if (++n > (s ? 16 : 256) || lds32v(pace + 16)) break;
          if (!s) __nanosleep(100);
        }
      }
      if (s < NSEG - 1 && lane == 0) { mbar_arrive(pace + 8); sts64(pace, 2 * NSEG, d); }
    }
    if (w != 0) return;
    const bool lead = lane == 0;
#pragma unroll 1
    for (int it = AE * A_ST, st = 0, ph = !AE, k = AE * A_ST * 32, col = (cta & 1) * (DM / 2); it < ((XP & 256) ? 0 : 72); it++) {
      mbar_wait(empty1 + 8 * st, ph);
      if (QM & 1) quiet_wait(pace);
      if (elect_one()) load_a(st, k, col);
      __syncwarp();
      if (++st == A_ST) { st = 0; ph ^= 1; }
      k += 32;
      if (k == DM) { k = 0; col += 72; }
    }
    auto load_wo = [&](uint32_t dst, int g, int kb, uint32_t mb) {
      if (kb < 64) tma_load(dst, &tm.wob, p3_mt(g) * 64, kb * 64, mb);
      else tma_load(dst, &tm.woa, p3_mt(g) * 64, (kb - 64) * 64, mb);
    };
    if (lead) mbar_expect(fullw, 16 * 8192);
#pragma unroll 1
    for (int st = 0; st < A_ST; st++) {
      if (!(XP & 256)) mbar_wait(empty1 + 8 * st, 1);
      if (lane < 16 && min(((lane + 1) * 8192 - 1) / A_STAGE, A_ST - 1) == st) load_wo(sb + lane * 8192, lane >> 3, p3_ks(lane >> 3) * 9 + (lane & 7), fullw);
      __syncwarp();
    }
    __syncwarp(); bar_sync(6, 288);
    if (lead) mbar_expect(fullw + 8, 2 * 8192 + (p3_ks(0) >= 4 ? 4096 : 0));
    __syncwarp();
    if (lane < 2) {
      load_wo(sb + (16 + lane) * 8192, lane, p3_ks(lane) * 9 + 8, fullw + 8);
      if (p3_ks(0) >= 4) tma_load(sb + A_XW + lane * 2048, &tm.woa16, p3_mt(lane) * 64, 448 + p3_ks(lane) * 16, fullw + 8);
    }
    __syncwarp();
    if (lead) aux_barrier(1, epoch, ALLW || p3_ks(0) >= 4);
    __syncwarp(); bar_sync(6, 288);
    {
      int avail = 0, sl = 0, ph = 1;
      const int h = (9 * p3_ks(0) >> 1) + lane;
#pragma unroll 1
      for (int seg = 0; seg < ((XP & 2048) ? 0 : NSEG); seg++) {
        if (avail <= seg) avail = wait_flags(&g_oflag[min(h, NH - 1) * 32], lane < (wide ? 5 : 9), fbase, seg);
        SSTAMP(seg, 4);
        for (int g = 0; g < (wide ? 1 : 2); g++) {
          const int ks = p3_ks(g);
          mbar_wait(empty3 + 8 * sl, ph);
          if ((QM & 4) && tick_wait(pace, seg + (QM >> 4 & 1) + 1) && ODLY) __nanosleep(ODLY);
          if (YP & 4) { if (lead) mbar_arrive(full3 + 8 * sl); }
          else if (elect_one()) {
            mbar_expect(full3 + 8 * sl, XT + (ks >= 4 ? 1024 : 0));
            tma_load3d(sb + sl * XT, &tm.o3, 0, seg * 32, ks * 9, full3 + 8 * sl);
            if (ks >= 4) tma_load(sb + A_XT + sl * 1024, &tm.o16, 72 * 64 - 64 + ks * 16, seg * 32, full3 + 8 * sl);
          }
          __syncwarp();
          if (++sl == (wide ? 3 : 4)) { sl = 0; ph ^= 1; }
        }
      }
    }
    sts32(pace + 16, 1);
    __syncwarp(); bar_sync(6, 288);
    asm volatile("griddepcontrol.wait;" ::: "memory");
  } else if (wg == 2) {
    asm volatile("setmaxnreg.dec.sync.aligned.u32 64;");
    if (cta < NH) {
      if (tid == 256) { mbar_expect(fullg, 64 * DM * 2); bulk_load(sb + A_IN, x + cta * 64 * DM, 64 * DM * 2, fullg); }
      uint32_t gw[9];
#pragma unroll
      for (int j = 0; j < 9; j++) gw[j] = ((const uint32_t*)gate_w)[j * 32 + lane];
      mbar_wait(fullg, 0);
      float mine = 0.f;
#pragma unroll 4
      for (int u = 0; u < 16; u++) {
        float d0 = 0.f, d1 = 0.f;
#pragma unroll
        for (int j = 0; j < 9; j++) {
          const uint32_t a = lds32(sb + A_IN + (w * 16 + u) * (DM * 2) + j * 128 + lane * 4);
          d0 = fmaf(bf_lo(a), bf_lo(gw[j]), d0); d1 = fmaf(bf_hi(a), bf_hi(gw[j]), d1);
        }
        d0 = warp_sum(d0 + d1);
        if (lane == u) mine = d0;
      }
      if (lane < 16) g_gate[cta * 64 + w * 16 + lane] = 1.f / (1.f + __expf(-mine));
      fence_async();
    }
    bar_sync(3, 128);
    if (tid == 256) { aux_barrier(0, epoch); if (cta == 0) *(volatile unsigned*)&g_epoch2 = epoch + 1; }
    __syncwarp();
    bar_sync(3, 128);
    if (w == 0) bar_arrive(8, 288);
    if (w == 1 && cta < NH) bar_arrive(10, 64);
    if (cta < NH) {
      CDECL;
#pragma unroll 1
      for (int seg = 0; seg < ((XP & 2048) ? 0 : NSEG); seg++) {
        CSTAMP(0);
        const uint32_t in = sb + A_IN + (seg & 1) * A_INB;
        const uint64_t qd = make_desc(in, 128, 1024, 0);
        mbar_wait(fulla + 16 * (seg & 1), (seg >> 1) & 1);
        CSTAMP(3);
        SSTAMP(seg, 0);
        float d[2][16];
        {
          float a[20];
          uint32_t vm[16];
          const unsigned char* vp = g_km + (size_t)(seg * NH + cta) * 4096 + 2048 + lane * 16;
          if (w == 3) ldg4x128<512>(vm, vp);
          WG_FENCE();
#pragma unroll
          for (int k = 0; k < ((YP & 16) ? 1 : 8); k++) wgmma_n40_ss(a, qd + ((k >> 2) * SEGB + (k & 3) * 256 >> 4), qd + ((k >> 2) * SEGB + (k & 3) * 256 + 4096 >> 4), k > 0);
          const uint32_t ga = sb + A_G + (seg & 1) * 128 + (w & 1) * 64 + (lane >> 2) * 4;
          const float f0 = __uint_as_float(lds32(ga)), f1 = __uint_as_float(lds32(ga + 32));
          WG_COMMIT();
          WG_WAIT(0);
          CSTAMP(5);
          SSTAMP(seg, 1);
          if (w < 2) {
            const int lim = w * 16 + (lane >> 2) - 2 * (lane & 3);
            float m0 = -3.0e38f, m1 = -3.0e38f;
#pragma unroll
            for (int i = 0; i < 20; i++) {
              a[i] *= SM_SCALE * LOG2E;
              if (i < 16 && (i >> 2) * 8 + (i & 1) - (i & 2) * 4 > lim) a[i] = -1.0e9f * LOG2E;
              if (i & 2) m1 = fmaxf(m1, a[i]); else m0 = fmaxf(m0, a[i]);
            }
#pragma unroll
            for (int o = 1; o < 4; o <<= 1) { m0 = fmaxf(m0, __shfl_xor_sync(0xffffffffu, m0, o)); m1 = fmaxf(m1, __shfl_xor_sync(0xffffffffu, m1, o)); }
            float s0 = 0.f, s1 = 0.f;
#pragma unroll
            for (int i = 0; i < 20; i++) { a[i] = ex2(a[i] - (i & 2 ? m1 : m0)); if (i & 2) s1 += a[i]; else s0 += a[i]; }
#pragma unroll
            for (int o = 1; o < 4; o <<= 1) { s0 += __shfl_xor_sync(0xffffffffu, s0, o); s1 += __shfl_xor_sync(0xffffffffu, s1, o); }
            s0 = f0 * rcp(s0); s1 = f1 * rcp(s1);
            uint32_t p[10];
#pragma unroll
            for (int i = 0; i < 10; i++) p[i] = pack_bf16(a[2 * i] * (i & 1 ? s1 : s0), a[2 * i + 1] * (i & 1 ? s1 : s0));
            const uint32_t pa = sb + A_P + (2 * w + ((lane >> 3) & 1)) * 768 + (lane >> 4) * 128 + (lane & 7) * 16;
            stsm4t(pa, p[0], p[1], p[2], p[3]); stsm4t(pa + 256, p[4], p[5], p[6], p[7]); stsm4t(pa + 512, p[8], p[9], 0, 0);
            CSTAMP(6);
            fence_async();
            CSTAMP(7);
          } else if (w == 3) {
            int n = 0;
#pragma unroll 1
            while (stale<4, 4>(vm, (epoch + 1) & 1) && ++n < SPIN_LIMIT) ldg4x128<512>(vm, vp);
#pragma unroll
            for (int i = 0; i < 4; i++) stsm4(in + 2 * SEGB + 8192 + (lane >> 4) * 1024 + (lane & 15) * 16 + i * 256, vm[4 * i], vm[4 * i + 1], vm[4 * i + 2], vm[4 * i + 3]);
            fence_async();
            mbar_wait(fulla + 16 * (seg & 1) + 8, (seg >> 1) & 1);
          }
        }
        CSTAMP(8);

        bar_sync(5, 160);
        CSTAMP(10);
        SSTAMP(seg, 2);
        const uint64_t pd = make_desc(sb + A_P, 128, 768, 0), vd = make_desc(in + 2 * SEGB, 128, 512, 0), md = make_desc(in + 2 * SEGB + 8192, 0, 128, 0);
        WG_FENCE();
#pragma unroll
        for (int i = 0; i < 2; i++) {
          wgmma_n32_ss<0>(d[i], vd + i * 256, pd, 0);
          wgmma_n32_ss<0>(d[i], vd + i * 256 + 16, pd + 16, 1);
          wgmma_n32_ss<0>(d[i], md + i * 64, pd + 32, 1);
        }
        WG_COMMIT();
        WG_WAIT(0);
        CSTAMP(11);
        if (lane == 0) mbar_arrive(emptya + 8 * (seg & 1));
#pragma unroll
        for (int i = 0; i < 2; i++) {
          const uint32_t oa = sb + A_OST + i * 4096 + ((lane & 7) + ((lane >> 4) << 3)) * 128 + (((2 * w + ((lane >> 3) & 1)) ^ (lane & 7)) << 4);
          stsm4t(oa, pack_bf16(d[i][0], d[i][1]), pack_bf16(d[i][2], d[i][3]), pack_bf16(d[i][4], d[i][5]), pack_bf16(d[i][6], d[i][7]));
          stsm4t(oa + 2048, pack_bf16(d[i][8], d[i][9]), pack_bf16(d[i][10], d[i][11]), pack_bf16(d[i][12], d[i][13]), pack_bf16(d[i][14], d[i][15]));
        }
        CSTAMP(12);
        bar_sync(4, 160);
        SSTAMP(seg, 3);
      }
      CDUMP;
    }
  } else {
    asm volatile("setmaxnreg.inc.sync.aligned.u32 %0;" :: "n"(TWO ? 208 : 200));
    {
      const int g = lane >> 2, t = lane & 3, r0 = (cta >> 1) * A_ROWS - 7 + w * 16;
      const uint32_t prev = (2 * t > g ? 0xffffu : 0u) | (2 * t + 1 > g ? 0xffff0000u : 0u);
      const int k0 = r0 + 2 * t - (2 * t > g ? 8 : 0), k1 = r0 + 2 * t + 1 - (2 * t + 1 > g ? 8 : 0);
      const uint32_t slot = sb + A_EXC + (wg * 4 + w) * 2304;
      float gl = 0.f, gh = 0.f;
      int st = 0, ph = 0;
#pragma unroll 1
      for (int p = -AWARM; p < ((XP & 256) ? 0 : 4); p++) {
        float big[96], sml[12];
        if (p == WPF && tid < 18) {
          const int kb = p3_ks(tid >= 9) * 9 + tid % 9;
          tma_prefetch(kb < 64 ? &tm.wob : &tm.woa, p3_mt(tid >= 9) * 64, (kb & 63) * 64);
        }
        __syncwarp();
#pragma unroll
        for (int i = 0; i < 96; i++) big[i] = 0.f;
#pragma unroll
        for (int i = 0; i < 12; i++) sml[i] = 0.f;
#pragma unroll 1
        for (int k = p < 0 ? 18 : 0; k < 18; k++) {
          mbar_wait(full1 + 8 * st, ph);
          const uint64_t da = make_desc(sb + st * A_STAGE + wg * 4096, 16, 512, 2);
          const uint64_t db = make_desc(sb + st * A_STAGE + 8192, 4096, 1024, 1), dc = make_desc(sb + A_W8 + st * 1536, 128, 512, 0);
          WG_FENCE();
#pragma unroll
          for (int j = 0; j < 2; j++) { wgmma_n192_ss_nt(big, da + j * 2, db + j * 128, 1); wgmma_n24_ss_nt(sml, da + j * 2, dc + j * 16, 1); }
          WG_COMMIT();
          WG_WAIT(1);
          if (k > 0 && lane == 0) mbar_arrive(empty1 + 8 * (st ? st - 1 : A_ST - 1));
          if (++st == A_ST) { st = 0; ph ^= 1; }
        }
        WG_WAIT(0);
        ASTAMP(16 + max(p, 0) + wg * 16);
        if (lane == 0 && p >= 0) mbar_arrive(empty1 + 8 * (st ? st - 1 : A_ST - 1));
        uint32_t f[3][9][2];
#pragma unroll
        for (int c = 0; c < 3; c++)
#pragma unroll
          for (int j = 0; j < 9; j++)
#pragma unroll
            for (int i = 0; i < 2; i++) {
              const float* a = j < 8 ? &big[(c * 8 + j) * 4 + 2 * i] : &sml[c * 4 + 2 * i];
              f[c][j][i] = c < 2 ? pack_bf16(a[0], a[1]) : trans8(pack_bf16(a[0], a[1]));
            }
        if (p == 0) {
          bar_sync(8, 288);
          gl = __ldcg(&g_gate[min(max(r0 + g, 0), S_LEN / 2 - 1) * 2 + wg]); gh = __ldcg(&g_gate[min(max(r0 + g + 8, 0), S_LEN / 2 - 1) * 2 + wg]);
        }
        asm volatile("cp.async.bulk.wait_group.read 0;" ::: "memory");
        __syncwarp();
#pragma unroll
        for (int j = 0; j < 8; j += 2) sts128(slot + j * 256 + lane * 16, f[1][j][1], f[2][j][1], f[1][j + 1][1], f[2][j + 1][1]);
        sts64(slot + 2048 + lane * 8, f[1][8][1], f[2][8][1]);
        bar_sync(1 + wg, 128);
        ASTAMP(24 + max(p, 0) + wg * 16);
        uint32_t pv[9][2];
#pragma unroll
        for (int j = 0; j < 9; j++) pv[j][0] = pv[j][1] = 0;
        if (w) {
#pragma unroll
          for (int j = 0; j < 8; j += 2) lds128(slot - 2304 + j * 256 + lane * 16, pv[j]);
          lds64(slot - 256 + lane * 8, pv[8][0], pv[8][1]);
        }
        float a[4][4], m[4][2];
#pragma unroll
        for (int h = 0; h < 4; h++) {
          const int j = 2 * h;
          const uint32_t qa[4] = {t >= h ? f[0][j][0] : 0, t >= h ? f[0][j][1] : 0, f[0][j + 1][0], f[0][j + 1][1]};
          const uint32_t qb0 = t <= h ? f[0][j + 2][0] : 0, qb1 = t <= h ? f[0][j + 2][1] : 0;
          float s0[4], s1[4], s2[4];
          mma16816z(s1, qa, f[1][j][0], f[1][j + 1][0]); mma16816z(s2, qa, f[1][j][1], f[1][j + 1][1]); mma16816z(s0, qa, pv[j][0], pv[j + 1][0]);
          mma1688(s1, qb0, qb1, f[1][j + 2][0]); mma1688(s2, qb0, qb1, f[1][j + 2][1]); mma1688(s0, qb0, qb1, pv[j + 2][0]);
          a[h][0] = 2 * t > g ? s0[0] : s1[0]; a[h][1] = 2 * t + 1 > g ? s0[1] : s1[1]; a[h][2] = 2 * t > g ? s1[2] : s2[2]; a[h][3] = 2 * t + 1 > g ? s1[3] : s2[3];
        }
#pragma unroll
        for (int h = 0; h < 4; h++) {
#pragma unroll
          for (int i = 0; i < 4; i++) a[h][i] = (i & 1 ? k1 : k0) + (i & 2) * 4 >= 0 ? a[h][i] * (0.23570226039551584f * LOG2E) : -1.0e9f * LOG2E;
          m[h][0] = fmaxf(a[h][0], a[h][1]); m[h][1] = fmaxf(a[h][2], a[h][3]);
        }
#pragma unroll
        for (int x = 1; x < 4; x <<= 1)
#pragma unroll
          for (int i = 0; i < 8; i++) m[i >> 1][i & 1] = fmaxf(m[i >> 1][i & 1], __shfl_xor_sync(0xffffffffu, m[i >> 1][i & 1], x));
#pragma unroll
        for (int h = 0; h < 4; h++) {
#pragma unroll
          for (int i = 0; i < 4; i++) a[h][i] = ex2(a[h][i] - m[h][i >> 1]);
          m[h][0] = a[h][0] + a[h][1]; m[h][1] = a[h][2] + a[h][3];
        }
#pragma unroll
        for (int x = 1; x < 4; x <<= 1)
#pragma unroll
          for (int i = 0; i < 8; i++) m[i >> 1][i & 1] += __shfl_xor_sync(0xffffffffu, m[i >> 1][i & 1], x);
        uint32_t o[9][2];
#pragma unroll
        for (int h = 0; h < 4; h++) {
          const int j = 2 * h;
          const float z0 = gl * rcp(m[h][0]), z1 = gh * rcp(m[h][1]);
          const uint32_t pl = pack_bf16(a[h][0] * z0, a[h][1] * z0), pu = pack_bf16(a[h][2] * z1, a[h][3] * z1);
          const uint32_t pa[4] = {pl & prev, 0, pl & ~prev, pu & prev};
          float d[3][4];
#pragma unroll
          for (int i = 0; i < 3; i++) mma16816z(d[i], pa, pv[j + i][1], f[2][j + i][0]);
#pragma unroll
          for (int i = 0; i < 3; i++) mma1688(d[i], 0, pu & ~prev, f[2][j + i][1]);
#pragma unroll
          for (int i = 0; i < 3; i++) {
            const uint32_t d0 = pack_bf16(d[i][0], d[i][1]), d1 = pack_bf16(d[i][2], d[i][3]);
            o[j + i][0] = i == 0 && h > 0 && t < h ? o[j][0] : d0;
            o[j + i][1] = i == 0 && h > 0 && t < h ? o[j][1] : d1;
          }
        }
        ASTAMP(28 + max(p, 0) + wg * 16);
        bar_sync(1 + wg, 128);
        const uint32_t oa = slot + (lane & 15) * 144 + (lane >> 4) * 16;
#pragma unroll
        for (int j = 0; j < 8; j += 2) stsm4(oa + j * 16, o[j][0], o[j][1], o[j + 1][0], o[j + 1][1]);
        asm volatile("stmatrix.sync.aligned.m8n8.x2.shared.b16 [%0], {%1,%2};" :: "r"(oa + 128), "r"(o[8][0]), "r"(o[8][1]) : "memory");
        fence_async();
        __syncwarp();
        if (QM & 64) quiet_wait(pace);
        if (lane < 16 && w * 16 + lane >= 7 && r0 + lane < S_LEN / 2 && p >= 0)
          asm volatile("cp.async.bulk.global.shared::cta.bulk_group [%0], [%1], 144;"
                       :: "l"(g_Ocat + (size_t)((r0 + lane) * 2 + wg) * KCAT + 4096 + (cta & 1) * (DM / 2) + p * 72), "r"(slot + lane * 144) : "memory");
        asm volatile("cp.async.bulk.commit_group;" ::: "memory");
        ASTAMP(20 + max(p, 0) + wg * 16);
      }
      if (XP & 256) bar_sync(8, 288);
      asm volatile("cp.async.bulk.wait_group 0;" ::: "memory");
    }
    ASTAMP(3);
    bar_arrive(6, 288);
    uint32_t wa[37][4];
    mbar_wait(fullw, 0);
    const uint32_t la = sb + ((lane & 7) + ((lane >> 4) << 3)) * 128 + (((2 * w + ((lane >> 3) & 1)) ^ (lane & 7)) << 4);
#pragma unroll
    for (int k = 0; k < 32; k++) ldsm4t(wa[k], la + wg * 65536 + k * 2048);
    mbar_wait(fullw + 8, 0);
#pragma unroll
    for (int k = 32; k < 36; k++) ldsm4t(wa[k], la + wg * 8192 + 65536 + k * 2048);
    ldsm4t(wa[36], la + A_XW + wg * 2048);
    fence_async();
    if (XP & 2048) bar_sync(6, 288); else bar_arrive(6, 288);
    ASTAMP(4);
    const int ks = p3_ks(wg), mt = p3_mt(wg);
    uint32_t v[16];
    auto fetch = [&](int seg) { ldg8x64<1024>(v, g_part + (((seg & 7) * 9 + mt) * 4 + (ks & 3)) * 1024 + (tid & 127)); };
    auto finish = [&](int seg) {
      const uint32_t tagv = (~seg >> 3) & 1;
      int n = 0;
#pragma unroll 1
      while (!(YP & 512) && stale<8, 2>(v, tagv) && ++n < SPIN_LIMIT) {
        if (seg < NSEG - 2) __nanosleep(RSL);
        fetch(seg);
      }
      float own[4] = {bf_lo(v[0]), bf_hi(v[0]), bf_lo(v[1]), bf_hi(v[1])};
#pragma unroll
      for (int j = 1; j < 8; j++) { own[0] += bf_lo(v[2 * j]); own[1] += bf_hi(v[2 * j]); own[2] += bf_lo(v[2 * j + 1]); own[3] += bf_hi(v[2 * j + 1]); }
      uint32_t p0 = pack_bf16(own[0], own[1]), p1 = pack_bf16(own[2], own[3]);
      asm volatile("movmatrix.sync.aligned.m8n8.trans.b16 %0, %0;" : "+r"(p0));
      asm volatile("movmatrix.sync.aligned.m8n8.trans.b16 %0, %0;" : "+r"(p1));
      const uint32_t r2 = __shfl_xor_sync(0xffffffffu, lane & 2 ? p0 : p1, 2);
      if (lane & 2) p0 = r2; else p1 = r2;
      const uint32_t r1 = __shfl_xor_sync(0xffffffffu, lane & 1 ? p0 : p1, 1);
      if (lane & 1) p0 = r1; else p1 = r1;
      if (!(YP & 256) || p0 == 0x12345678)
        *((uint2*)(out + (size_t)(seg * 32 + (ks & 3) * 8 + (lane >> 2)) * DM + mt * 64 + w * 16) + (lane & 3)) = make_uint2(p0, p1);
      SSTAMP(seg, 7);
    };
    float acc[16], acc2[16];
#pragma unroll
    for (int i = 0; i < 16; i++) acc[i] = acc2[i] = 0.f;
    int pend = -1, sl = wide ? 0 : wg, ph = 0;
    if (PING && wg) bar_arrive(1, 256);
    CDECL;
    auto run = [&](auto extra) {
#pragma unroll 1
    for (int seg = 0; seg <= ((XP & 2048) ? -1 : NSEG); seg++) {
      CSTAMP(0);
      const bool fin = pend >= 0 && (seg - pend >= FLAG || seg == NSEG);
      if (seg < NSEG) mbar_wait(full3 + 8 * sl, ph);
      if (FPOS == 1 && fin) fetch(pend);
      if (SDLY) {
        uint32_t n, d;
        asm volatile("ld.volatile.shared.v2.b32 {%0,%1}, [%2];" : "=r"(n), "=r"(d) : "r"(pace) : "memory");
        if ((int)n <= seg + 3) sleep_until(d + SDLY);
      }
      CSTAMP(1);
      if (seg < NSEG) {
      if (wg) SSTAMP(seg, 5);
      if (seg < PING) bar_sync(1 + wg, 256);
      CSTAMP(7);
      const uint64_t db = make_desc(sb + sl * XT, 16, 1024, 1);
      WG_FENCE();
#pragma unroll
      for (int k = 0; k < ((XP & 1024) ? 1 : 36); k++)
        wgmma_n32_rs(TWO && (k & 1) ? acc2 : acc, wa[k][0], wa[k][1], wa[k][2], wa[k][3], db + (k >> 2) * 256 + (k & 3) * 2, k >> TWO);
      if (decltype(extra)::value) wgmma_n32_rs(acc, wa[36][0], wa[36][1], wa[36][2], wa[36][3], make_desc(sb + A_XT + sl * 1024, 16, 256, 3), 1);
      WG_COMMIT();
      if (seg < PING) bar_arrive(2 - wg, 256);
      CSTAMP(2);
      CSTAMP(3);
      WG_WAIT(0);
      CSTAMP(4);
      if (wg) SSTAMP(seg, 6);
      if (lane == 0) mbar_arrive(empty3 + 8 * sl);
      sl += wide ? 1 : 2;
      if (sl >= (wide ? 3 : 4)) { sl -= wide ? 3 : 4; ph ^= 1; }
      uint2* dst = g_part + (((seg & 7) * 9 + mt) * 32 + ks) * 128 + (tid & 127);
      uint32_t q[8];
      if (TWO)
#pragma unroll
        for (int j = 0; j < 16; j++) acc[j] += acc2[j];
#pragma unroll
      for (int j = 0; j < 8; j++) q[j] = j & 1 ? pack_bf16(acc[2 * j], acc[2 * j + 1]) : (pack_bf16(acc[2 * j], acc[2 * j + 1]) & ~1u) | ((~seg >> 3) & 1);
      if (QM & 32) tick_wait(pace, seg + (QM >> 4 & 1) + 2);
      if (!(YP & 1025) || q[0] == 0x12345678)
      asm volatile("st.relaxed.gpu.global.v2.b32 [%0], {%1,%2};\nst.relaxed.gpu.global.v2.b32 [%0 + 8192], {%3,%4};\n"
                   "st.relaxed.gpu.global.v2.b32 [%0 + 16384], {%5,%6};\nst.relaxed.gpu.global.v2.b32 [%0 + 24576], {%7,%8};"
                   :: "l"(dst), "r"(q[0]), "r"(q[1]), "r"(q[2]), "r"(q[3]), "r"(q[4]), "r"(q[5]), "r"(q[6]), "r"(q[7]) : "memory");
      }
      CSTAMP(5);
      if (fin) { finish(pend); pend = -1; }
      CSTAMP(6);
      if ((seg & 1) == ks >> 2 && !(YP & 1)) pend = seg;
      if (wg && (seg & 7) == 6) ASTAMP(5 + (seg >> 3));
    }
    };
    if (ks >= 4) run(BoolC<true>()); else run(BoolC<false>());
    if (PING && !wg) bar_sync(1, 256);
    CDUMP;
    ASTAMP(13);
    bar_sync(6, 288);
  }
}

typedef CUresult (*EncodeFn)(CUtensorMap*, CUtensorMapDataType, cuuint32_t, void*, const cuuint64_t*, const cuuint64_t*,
                             const cuuint32_t*, const cuuint32_t*, CUtensorMapInterleave, CUtensorMapSwizzle,
                             CUtensorMapL2promotion, CUtensorMapFloatOOBfill);
#define PROMO 2
static void make_map(EncodeFn enc, CUtensorMap* m, const void* p, int rows, int cols, int box_rows) {
  cuuint64_t dims[2] = {(cuuint64_t)cols, (cuuint64_t)rows};
  cuuint64_t strides[1] = {(cuuint64_t)cols * 2};
  cuuint32_t box[2] = {64, (cuuint32_t)box_rows};
  cuuint32_t es[2] = {1, 1};
  enc(m, CU_TENSOR_MAP_DATA_TYPE_BFLOAT16, 2, (void*)p, dims, strides, box, es, CU_TENSOR_MAP_INTERLEAVE_NONE,
      CU_TENSOR_MAP_SWIZZLE_128B, (CUtensorMapL2promotion)PROMO, CU_TENSOR_MAP_FLOAT_OOB_FILL_NONE);
}

constexpr int g_poll = POLL_NS;
extern "C" void kernel_launch(void* const* d_in, const int* in_sizes, int n_in, void* d_out, int out_size) {
  const bf16* x = (const bf16*)d_in[0];
  const bf16* wqkvA = (const bf16*)d_in[1];
  const bf16* woA = (const bf16*)d_in[2];
  const bf16* mem0 = (const bf16*)d_in[4];
  const bf16* Wq = (const bf16*)d_in[5];
  const bf16* Wk = (const bf16*)d_in[6];
  const bf16* Wv = (const bf16*)d_in[7];
  const bf16* Wo = (const bf16*)d_in[8];
  const bf16* gate_w = (const bf16*)d_in[10];
  static EncodeFn enc = nullptr;
  static void *pO = nullptr, *pR = nullptr, *pF = nullptr;
  if (!enc) {
    cudaDriverEntryPointQueryResult qr;
    cudaGetDriverEntryPoint("cuTensorMapEncodeTiled", (void**)&enc, cudaEnableDefault, &qr);
    cudaGetSymbolAddress(&pO, g_Ocat);
    cudaGetSymbolAddress(&pR, g_red_raw);
    cudaGetSymbolAddress(&pF, g_cflag);
    cudaFuncSetAttribute(rec_kernel, cudaFuncAttributeMaxDynamicSharedMemorySize, SM_TOTAL);
    cudaFuncSetAttribute(aux_kernel, cudaFuncAttributeMaxDynamicSharedMemorySize, A_TOTAL);
  }
  RMaps rm;
  rm.poll = g_poll;
  rm.oflag = (const unsigned char*)pF;
  rm.red = (unsigned char*)(((uintptr_t)pR + 262143) & ~(uintptr_t)262143);
  {
    cuuint64_t dims[3] = {64, S_LEN, 9}, strides[2] = {DM * 2, 128};
    cuuint32_t box[3] = {64, 32, 9}, es[3] = {1, 1, 1};
    enc(&rm.x, CU_TENSOR_MAP_DATA_TYPE_BFLOAT16, 3, (void*)x, dims, strides, box, es, CU_TENSOR_MAP_INTERLEAVE_NONE,
        CU_TENSOR_MAP_SWIZZLE_128B, CU_TENSOR_MAP_L2_PROMOTION_L2_128B, CU_TENSOR_MAP_FLOAT_OOB_FILL_NONE);
  }
  make_map(enc, &rm.wq, Wq, DM, 4096, 192);
  make_map(enc, &rm.wk, Wk, DM, 4096, 192);
  make_map(enc, &rm.wv, Wv, DM, 4096, 192);
  make_map(enc, &rm.wo, Wo, 4096, DM, 128);
  AMaps am;
  am.red = rm.red; am.poll = rm.poll;
  {
    cuuint64_t dims[3] = {DM, S_LEN / 2, 2}, strides[2] = {DM * 4, DM * 2};
    cuuint32_t box[3] = {32, 64, 2}, es[3] = {1, 1, 1};
    enc(&am.x, CU_TENSOR_MAP_DATA_TYPE_BFLOAT16, 3, (void*)x, dims, strides, box, es, CU_TENSOR_MAP_INTERLEAVE_NONE,
        CU_TENSOR_MAP_SWIZZLE_64B, CU_TENSOR_MAP_L2_PROMOTION_L2_128B, CU_TENSOR_MAP_FLOAT_OOB_FILL_NONE);
    cuuint64_t wdims[3] = {DM, DM, 3}, wstrides[2] = {DM * 6, DM * 2};
    cuuint32_t wbox[3] = {64, 32, 3}, wbox8[3] = {8, 32, 3};
    enc(&am.wa, CU_TENSOR_MAP_DATA_TYPE_BFLOAT16, 3, (void*)wqkvA, wdims, wstrides, wbox, es, CU_TENSOR_MAP_INTERLEAVE_NONE,
        CU_TENSOR_MAP_SWIZZLE_128B, CU_TENSOR_MAP_L2_PROMOTION_L2_128B, CU_TENSOR_MAP_FLOAT_OOB_FILL_NONE);
    enc(&am.wa8, CU_TENSOR_MAP_DATA_TYPE_BFLOAT16, 3, (void*)wqkvA, wdims, wstrides, wbox8, es, CU_TENSOR_MAP_INTERLEAVE_NONE,
        CU_TENSOR_MAP_SWIZZLE_NONE, CU_TENSOR_MAP_L2_PROMOTION_NONE, CU_TENSOR_MAP_FLOAT_OOB_FILL_NONE);
  }
  {
    cuuint64_t dims[3] = {64, S_LEN, KCAT / 64}, strides[2] = {KCAT * 2, 128};
    cuuint32_t box[3] = {64, 32, 9}, es[3] = {1, 1, 1};
    make_map(enc, &am.o, pO, S_LEN, KCAT, 32);
    enc(&am.o3, CU_TENSOR_MAP_DATA_TYPE_BFLOAT16, 3, pO, dims, strides, box, es, CU_TENSOR_MAP_INTERLEAVE_NONE,
        CU_TENSOR_MAP_SWIZZLE_128B, CU_TENSOR_MAP_L2_PROMOTION_L2_128B, CU_TENSOR_MAP_FLOAT_OOB_FILL_NONE);
  }
  make_map(enc, &am.wob, Wo, 4096, DM, 64);
  make_map(enc, &am.woa, woA, DM, DM, 64);
  make_map(enc, &am.woa16, woA, DM, DM, 16);
  {
    cuuint64_t dims[2] = {KCAT, S_LEN}, strides[1] = {KCAT * 2};
    cuuint32_t box[2] = {16, 32}, es[2] = {1, 1};
    enc(&am.o16, CU_TENSOR_MAP_DATA_TYPE_BFLOAT16, 2, pO, dims, strides, box, es, CU_TENSOR_MAP_INTERLEAVE_NONE,
        CU_TENSOR_MAP_SWIZZLE_32B, CU_TENSOR_MAP_L2_PROMOTION_NONE, CU_TENSOR_MAP_FLOAT_OOB_FILL_NONE);
  }

  rec_kernel<<<96, 384, SM_TOTAL, cudaStreamPerThread>>>(rm, x, mem0);
  cudaLaunchConfig_t cfg = {};
  cfg.gridDim = dim3(NAUX); cfg.blockDim = dim3(512); cfg.dynamicSmemBytes = A_TOTAL; cfg.stream = cudaStreamPerThread;
  cudaLaunchAttribute at[1];
  at[0].id = cudaLaunchAttributeProgrammaticStreamSerialization; at[0].val.programmaticStreamSerializationAllowed = 1;
  cfg.attrs = at; cfg.numAttrs = 1;
  if (XP & 16) cfg.numAttrs = 0;
  if (!(XP & 64)) cudaLaunchKernelEx(&cfg, aux_kernel, am, x, gate_w, (bf16*)d_out);
}
```

```cpp
#include <cuda_runtime.h>
#include <cuda_bf16.h>
#include <cuda_fp16.h>
#include <cuda.h>
#include <stdint.h>

typedef __nv_bfloat16 bf16;

constexpr int S_LEN = 2048, DM = 576, NH = 32, DH = 128, NSEG = 64, KCAT = 4096 + 576;
#define RED_LINE(i) (((i) >> 2) * 4096 + ((i) & 1) * 256 + ((i) & 2) * 512)
#define RED_SLOT(s) (((s) & 1) * 128 + ((s) & 2) * 256)

#define POLL_NS 896
#define NII 18
#define W3PRE 4
#define W3MID 4
#define GF 0
#define B5POS 0
#define NUP 4
#define UPF 1
#define B3Q 9
#define B3F 0
#define GATE 8
#define NTL 2
#define B7R 1
#define EXPOS 0
#define VW2 1
#define CLR 1
#define RFW 0
#define NIC 0
#define LEAD 0
#define FIN16 1
#define VXG 0
#define EXB 0
#define EXD 0
#define EXB2 8192
#define HDLY 0
#define F10 1
#define NPROBE 2
#define WPOS 1
#define CW 0
#define WOPF 0
#define YP 0
#define EF 4
#define MO 0
#define WE 3
#define FW 1
#define EXV 2
#define NOB 0
#define QM 60
#define N5 224
#define KP(i) (((i) >> 1) + 4 * ((i) & 1))
#define SPIN_LIMIT (1 << 14)
#define XP 0

__device__ __align__(1024) bf16 g_Ocat[S_LEN * KCAT];
__device__ __align__(1024) unsigned char g_red_raw[2 * 262144];
constexpr int HINT_OFF = 2048;
__device__ __align__(16) float g_gate[S_LEN];
__device__ __align__(128) uint4 g_stats[96 * 2];
__device__ unsigned g_epoch;
__device__ unsigned g_epoch2;
__device__ __align__(128) unsigned g_oflag[NH * 32];
__device__ unsigned g_abar[3 * 32];
__device__ __align__(128) unsigned g_cflag[96 * 32];
__device__ uint2 g_sflag[96 * 4];
__device__ __align__(1024) unsigned char g_seg[NSEG * 96 * 8192];
__device__ __align__(1024) unsigned char g_km[NSEG * NH * 4096];
__device__ __align__(1024) uint2 g_part[8 * 9 * 4 * 8 * 128];
__device__ int g_err;
#define SSTAMP(seg, idx)
#define TSTAMP(idx)
#define QSTAMP(idx)
#define PROF(idx)
#define PROFP(idx)
#define STAMP(idx)
#define ASTAMP(idx)
#define WSTAMP(idx)

#define CSTAMP(idx)
#define CDECL
#define CDUMP
#define DI __device__ __forceinline__
DI uint32_t smem_u32(const void* p) { return (uint32_t)__cvta_generic_to_shared(p); }
DI uint32_t clock32() { uint32_t c; asm volatile("mov.u32 %0, %%clock;" : "=r"(c) :: "memory"); return c; }
DI uint32_t gtime() { uint32_t c; asm volatile("mov.u32 %0, %%globaltimer_lo;" : "=r"(c) :: "memory"); return c; }
DI uint32_t ldg_relaxed32(const void* p) { uint32_t v; asm volatile("ld.relaxed.gpu.global.b32 %0, [%1];" : "=r"(v) : "l"(p) : "memory"); return v; }
DI uint32_t ldg_acquire32(const void* p) { uint32_t v; asm volatile("ld.acquire.gpu.global.b32 %0, [%1];" : "=r"(v) : "l"(p) : "memory"); return v; }
DI void stg_relaxed32(void* p, uint32_t v) { asm volatile("st.relaxed.gpu.global.b32 [%0], %1;" :: "l"(p), "r"(v) : "memory"); }
DI int head_id() { int c; asm volatile("mov.u32 %0, %%clusterid.x;" : "=r"(c)); return c; }
DI uint32_t mapa(uint32_t a, uint32_t r) { uint32_t o; asm("mapa.shared::cluster.u32 %0, %1, %2;" : "=r"(o) : "r"(a), "r"(r)); return o; }
DI void cluster_arrive() { asm volatile("barrier.cluster.arrive.relaxed.aligned;" ::: "memory"); }
DI void cluster_wait() { asm volatile("barrier.cluster.wait.aligned;" ::: "memory"); }
DI void cluster_sync() { asm volatile("barrier.cluster.arrive.release.aligned;\nbarrier.cluster.wait.acquire.aligned;" ::: "memory"); }
DI void mbar_init(uint32_t b, uint32_t c) { asm volatile("mbarrier.init.shared::cta.b64 [%0], %1;" :: "r"(b), "r"(c) : "memory"); }
DI void mbar_expect(uint32_t b, uint32_t tx) { asm volatile("mbarrier.arrive.expect_tx.shared::cta.b64 _, [%0], %1;" :: "r"(b), "r"(tx) : "memory"); }
DI void mbar_arrive(uint32_t b) { asm volatile("mbarrier.arrive.shared::cta.b64 _, [%0];" :: "r"(b) : "memory"); }
DI void mbar_wait(uint32_t b, uint32_t par) {
  asm volatile("{\n.reg .pred p;\n.reg .u32 n, q;\nmov.u32 n, 0;\n"
               "WL: add.u32 n, n, 1;\nshr.u32 q, n, 12;\nxor.b32 q, q, %1;\n"
               "mbarrier.try_wait.parity.shared::cta.b64 p, [%0], q;\n@!p bra.uni WL;\n}"
               :: "r"(b), "r"(par) : "memory");
}
DI void wait_until(uint32_t t) {
  const uint32_t now = gtime();
  t = min(t, now + 8192);
  asm volatile("{\n.reg .pred p;\n.reg .u32 c;\nTL: mov.u32 c, %%globaltimer_lo;\nsetp.lt.u32 p, c, %0;\n@p bra.uni TL;\n}" :: "r"(t) : "memory");
}
#define PIN(v) v = __shfl_xor_sync(0xffffffffu, v, 0)
#define SCHED_FENCE(k) asm volatile("{\n.reg .pred p;\nsetp.eq.u32 p, %0, %1;\n@p exit;\n}" :: "r"(fence_reg), "r"(k) : "memory")
#define MEM_ORDER(k) asm volatile("{\n.reg .pred p;\nsetp.eq.u32 p, %0, %1;\n@p st.shared.u32 [%0], %0;\n}" :: "r"(fence_reg), "r"(k + 64) : "memory")
DI void bar_sync(int id, int n) { asm volatile("bar.sync %0, %1;" :: "r"(id), "r"(n) : "memory"); }
DI void bar_arrive(int id, int n) { asm volatile("bar.arrive %0, %1;" :: "r"(id), "r"(n) : "memory"); }
DI void fence_async() { asm volatile("fence.proxy.async.shared::cta;" ::: "memory"); }
DI void st_async4(uint32_t a, uint32_t x, uint32_t y, uint32_t z, uint32_t w, uint32_t mb) {
  asm volatile("st.async.weak.shared::cluster.mbarrier::complete_tx::bytes.v4.b32 [%0], {%1,%2,%3,%4}, [%5];"
               :: "r"(a), "r"(x), "r"(y), "r"(z), "r"(w), "r"(mb) : "memory");
}
DI void st_async2(uint32_t a, uint32_t x, uint32_t y, uint32_t mb) {
  asm volatile("st.async.weak.shared::cluster.mbarrier::complete_tx::bytes.v2.b32 [%0], {%1,%2}, [%3];"
               :: "r"(a), "r"(x), "r"(y), "r"(mb) : "memory");
}
DI void sts32(uint32_t a, uint32_t x) { asm volatile("st.shared.b32 [%0], %1;" :: "r"(a), "r"(x) : "memory"); }
DI void sts64(uint32_t a, uint32_t x, uint32_t y) { asm volatile("st.shared.v2.b32 [%0], {%1,%2};" :: "r"(a), "r"(x), "r"(y) : "memory"); }
DI void sts128(uint32_t a, uint32_t x, uint32_t y, uint32_t z, uint32_t w) {
  asm volatile("st.shared.v4.b32 [%0], {%1,%2,%3,%4};" :: "r"(a), "r"(x), "r"(y), "r"(z), "r"(w) : "memory");
}
DI uint32_t lds32(uint32_t a) { uint32_t x; asm volatile("ld.shared.b32 %0, [%1];" : "=r"(x) : "r"(a) : "memory"); return x; }
DI uint32_t lds32v(uint32_t a) { uint32_t x; asm volatile("ld.volatile.shared.b32 %0, [%1];" : "=r"(x) : "r"(a) : "memory"); return x; }
DI void lds64(uint32_t a, uint32_t& x, uint32_t& y) { asm volatile("ld.shared.v2.b32 {%0,%1}, [%2];" : "=r"(x), "=r"(y) : "r"(a) : "memory"); }
DI void lds128(uint32_t a, uint32_t* r) {
  asm volatile("ld.shared.v4.b32 {%0,%1,%2,%3}, [%4];" : "=r"(r[0]), "=r"(r[1]), "=r"(r[2]), "=r"(r[3]) : "r"(a) : "memory");
}
DI void lds128f(uint32_t a, float* r) {
  asm volatile("ld.shared.v4.f32 {%0,%1,%2,%3}, [%4];" : "=f"(r[0]), "=f"(r[1]), "=f"(r[2]), "=f"(r[3]) : "r"(a) : "memory");
}
DI void lds64f(uint32_t a, float* r) { asm volatile("ld.shared.v2.f32 {%0,%1}, [%2];" : "=f"(r[0]), "=f"(r[1]) : "r"(a) : "memory"); }
DI void ldsm4t(uint32_t* r, uint32_t a) {
  asm volatile("ldmatrix.sync.aligned.m8n8.x4.trans.shared.b16 {%0,%1,%2,%3}, [%4];"
               : "=r"(r[0]), "=r"(r[1]), "=r"(r[2]), "=r"(r[3]) : "r"(a) : "memory");
}
DI void ldsm4t_in(uint32_t* r, uint32_t a, uint32_t t) {
  asm volatile("{\n.reg .pred p;\nsetp.ne.u32 p, %5, 0;\n@p ldmatrix.sync.aligned.m8n8.x4.trans.shared.b16 {%0,%1,%2,%3}, [%4];\n}"
               : "+r"(r[0]), "+r"(r[1]), "+r"(r[2]), "+r"(r[3]) : "r"(a), "r"(t) : "memory");
}
DI void lds128_in(uint32_t* r, uint32_t a, uint32_t t) {
  asm volatile("{\n.reg .pred p;\nsetp.ne.u32 p, %5, 0;\n@p ld.shared.v4.b32 {%0,%1,%2,%3}, [%4];\n}"
               : "+r"(r[0]), "+r"(r[1]), "+r"(r[2]), "+r"(r[3]) : "r"(a), "r"(t) : "memory");
}
DI void ldsm2t_in(uint32_t* r, uint32_t a, uint32_t t) {
  asm volatile("{\n.reg .pred p;\nsetp.ne.u32 p, %3, 0;\n@p ldmatrix.sync.aligned.m8n8.x2.trans.shared.b16 {%0,%1}, [%2];\n}" : "+r"(r[0]), "+r"(r[1]) : "r"(a), "r"(t) : "memory");
}
DI void reserve2(uint32_t* r) { asm volatile("{\n.reg .u64 t;\nmov.u64 t, %%clock64;\nmov.b64 {%0, %1}, t;\n}" : "=r"(r[0]), "=r"(r[1])); }
DI void scale_sum(float& x, float& y, float s, uint32_t t) {
  asm volatile("{\n.reg .pred p;\nsetp.ne.u32 p, %2, 0;\n@p mul.f32 %0, %0, %1;\n}" : "+f"(y) : "f"(s), "r"(t));
  asm volatile("{\n.reg .pred p;\nsetp.ne.u32 p, %3, 1;\n@p fma.rn.f32 %0, %0, %1, %2;\n}" : "+f"(x) : "f"(s), "f"(y), "r"(t));
}
DI void ldsm4(uint32_t* r, uint32_t a) {
  asm volatile("ldmatrix.sync.aligned.m8n8.x4.shared.b16 {%0,%1,%2,%3}, [%4];"
               : "=r"(r[0]), "=r"(r[1]), "=r"(r[2]), "=r"(r[3]) : "r"(a) : "memory");
}
DI void st_async1(uint32_t a, uint32_t x, uint32_t mb) {
  asm volatile("st.async.weak.shared::cluster.mbarrier::complete_tx::bytes.b32 [%0], %1, [%2];" :: "r"(a), "r"(x), "r"(mb) : "memory");
}
DI void stsm4(uint32_t a, uint32_t x, uint32_t y, uint32_t z, uint32_t w) {
  asm volatile("stmatrix.sync.aligned.m8n8.x4.shared.b16 [%0], {%1,%2,%3,%4};" :: "r"(a), "r"(x), "r"(y), "r"(z), "r"(w) : "memory");
}
DI void stsm4t(uint32_t a, uint32_t x, uint32_t y, uint32_t z, uint32_t w) {
  asm volatile("stmatrix.sync.aligned.m8n8.x4.trans.shared.b16 [%0], {%1,%2,%3,%4};" :: "r"(a), "r"(x), "r"(y), "r"(z), "r"(w) : "memory");
}
DI uint32_t pack_bf16(float lo, float hi) { uint32_t r; asm("cvt.rn.bf16x2.f32 %0, %1, %2;" : "=r"(r) : "f"(hi), "f"(lo)); return r; }
DI uint32_t pack_f16(float lo, float hi) { uint32_t r; asm("cvt.rn.f16x2.f32 %0, %1, %2;" : "=r"(r) : "f"(hi), "f"(lo)); return r; }
DI float ex2(float x) { float y; asm("ex2.approx.ftz.f32 %0, %1;" : "=f"(y) : "f"(x)); return y; }
DI float rcp(float x) { float y; asm("rcp.approx.ftz.f32 %0, %1;" : "=f"(y) : "f"(x)); return y; }
DI float bf_lo(uint32_t x) { return __uint_as_float(x << 16); }
DI float bf_hi(uint32_t x) { return __uint_as_float(x & 0xffff0000u); }
DI void mma16816(float* d, const uint32_t* a, uint32_t b0, uint32_t b1) {
  asm volatile("mma.sync.aligned.m16n8k16.row.col.f32.bf16.bf16.f32 {%0,%1,%2,%3}, {%4,%5,%6,%7}, {%8,%9}, {%0,%1,%2,%3};"
               : "+f"(d[0]), "+f"(d[1]), "+f"(d[2]), "+f"(d[3]) : "r"(a[0]), "r"(a[1]), "r"(a[2]), "r"(a[3]), "r"(b0), "r"(b1));
}
DI void mma16816z(float* d, const uint32_t* a, uint32_t b0, uint32_t b1) {
  asm volatile("mma.sync.aligned.m16n8k16.row.col.f32.bf16.bf16.f32 {%0,%1,%2,%3}, {%4,%5,%6,%7}, {%8,%9}, {%10,%10,%10,%10};"
               : "=f"(d[0]), "=f"(d[1]), "=f"(d[2]), "=f"(d[3]) : "r"(a[0]), "r"(a[1]), "r"(a[2]), "r"(a[3]), "r"(b0), "r"(b1), "f"(0.f));
}
DI void mma1688z(float* d, uint32_t a0, uint32_t a1, uint32_t b0) {
  asm volatile("mma.sync.aligned.m16n8k8.row.col.f32.bf16.bf16.f32 {%0,%1,%2,%3}, {%4,%5}, {%6}, {%7,%7,%7,%7};"
               : "=f"(d[0]), "=f"(d[1]), "=f"(d[2]), "=f"(d[3]) : "r"(a0), "r"(a1), "r"(b0), "f"(0.f));
}
DI void mma1688(float* d, uint32_t a0, uint32_t a1, uint32_t b0) {
  asm volatile("mma.sync.aligned.m16n8k8.row.col.f32.bf16.bf16.f32 {%0,%1,%2,%3}, {%4,%5}, {%6}, {%0,%1,%2,%3};"
               : "+f"(d[0]), "+f"(d[1]), "+f"(d[2]), "+f"(d[3]) : "r"(a0), "r"(a1), "r"(b0));
}
DI void ldsm2t(uint32_t* r, uint32_t a) {
  asm volatile("ldmatrix.sync.aligned.m8n8.x2.trans.shared.b16 {%0,%1}, [%2];" : "=r"(r[0]), "=r"(r[1]) : "r"(a) : "memory");
}
DI uint32_t add_bf16(uint32_t a, uint32_t b) { uint32_t r; asm("add.rn.bf16x2 %0, %1, %2;" : "=r"(r) : "r"(a), "r"(b)); return r; }
DI uint32_t mul_bf16(uint32_t a, uint32_t b) { uint32_t r; asm("mul.rn.bf16x2 %0, %1, %2;" : "=r"(r) : "r"(a), "r"(b)); return r; }
DI uint64_t make_desc(uint32_t addr, uint32_t lbo, uint32_t sbo, uint32_t swz) {
  return (uint64_t)((addr & 0x3FFFF) >> 4) | ((uint64_t)(lbo >> 4) << 16) | ((uint64_t)(sbo >> 4) << 32) | ((uint64_t)swz << 62);
}
#define WG_FENCE() asm volatile("wgmma.fence.sync.aligned;" ::: "memory")
#define WG_COMMIT() asm volatile("wgmma.commit_group.sync.aligned;" ::: "memory")
#define WG_WAIT(n) asm volatile("wgmma.wait_group.sync.aligned %0;" :: "n"(n) : "memory")
#define ACC8(d, o) "+f"(d[o]), "+f"(d[o + 1]), "+f"(d[o + 2]), "+f"(d[o + 3]), "+f"(d[o + 4]), "+f"(d[o + 5]), "+f"(d[o + 6]), "+f"(d[o + 7])
DI void wgmma_n32_rs(float* d, uint32_t a0, uint32_t a1, uint32_t a2, uint32_t a3, uint64_t db, int acc) {
  asm volatile("{\n.reg .pred p;\nsetp.ne.b32 p, %21, 0;\n"
               "wgmma.mma_async.sync.aligned.m64n32k16.f32.bf16.bf16 {%0,%1,%2,%3,%4,%5,%6,%7,%8,%9,%10,%11,%12,%13,%14,%15}, "
               "{%16,%17,%18,%19}, %20, p, 1, 1, 0;\n}\n"
               : ACC8(d, 0), ACC8(d, 8) : "r"(a0), "r"(a1), "r"(a2), "r"(a3), "l"(db), "r"(acc));
}
template <int TA>
DI void wgmma_n32_ss(float* d, uint64_t da, uint64_t db, int acc) {
  asm volatile("{\n.reg .pred p;\nsetp.ne.b32 p, %18, 0;\n"
               "wgmma.mma_async.sync.aligned.m64n32k16.f32.bf16.bf16 {%0,%1,%2,%3,%4,%5,%6,%7,%8,%9,%10,%11,%12,%13,%14,%15}, "
               "%16, %17, p, 1, 1, %19, 1;\n}\n"
               : ACC8(d, 0), ACC8(d, 8) : "l"(da), "l"(db), "r"(acc), "n"(TA));
}
DI void tma_load(uint32_t dst, const CUtensorMap* m, int c0, int c1, uint32_t mb) {
  asm volatile("cp.async.bulk.tensor.2d.shared::cluster.global.mbarrier::complete_tx::bytes [%0], [%1, {%3, %4}], [%2];"
               :: "r"(dst), "l"(m), "r"(mb), "r"(c0), "r"(c1) : "memory");
}
DI void tma_load3(uint32_t dst, const CUtensorMap* m, int row, uint32_t mb) {
  asm volatile("cp.async.bulk.tensor.3d.shared::cluster.global.mbarrier::complete_tx::bytes [%0], [%1, {%3, %4, %3}], [%2];"
               :: "r"(dst), "l"(m), "r"(mb), "r"(0), "r"(row) : "memory");
}
DI bool elect_one() {
  uint32_t p;
  asm volatile("{\n.reg .pred p;\nelect.sync _|p, 0xffffffff;\nselp.u32 %0, 1, 0, p;\n}" : "=r"(p));
  return p;
}
DI void bulk_s2s(uint32_t dst, uint32_t src, uint32_t bytes, uint32_t mb) {
  asm volatile("cp.async.bulk.shared::cluster.shared::cta.mbarrier::complete_tx::bytes [%0], [%1], %2, [%3];"
               :: "r"(dst), "r"(src), "r"(bytes), "r"(mb) : "memory");
}
DI void bulk_load(uint32_t dst, const void* src, uint32_t bytes, uint32_t mb) {
  asm volatile("cp.async.bulk.shared::cluster.global.mbarrier::complete_tx::bytes [%0], [%1], %2, [%3];" :: "r"(dst), "l"(src), "r"(bytes), "r"(mb) : "memory");
}
#define EVICT_FIRST ".reg .b64 pol;\ncreatepolicy.fractional.L2::evict_first.b64 pol, 1.0;\n"
DI void bulk_load_ef(uint32_t dst, const void* src, uint32_t bytes, uint32_t mb) {
  asm volatile("{\n" EVICT_FIRST "cp.async.bulk.shared::cluster.global.mbarrier::complete_tx::bytes.L2::cache_hint [%0], [%1], %2, [%3], pol;\n}"
               :: "r"(dst), "l"(src), "r"(bytes), "r"(mb) : "memory");
}
DI void tma_load_ef(uint32_t dst, const CUtensorMap* m, int c0, int c1, uint32_t mb) {
  asm volatile("{\n" EVICT_FIRST "cp.async.bulk.tensor.2d.shared::cluster.global.mbarrier::complete_tx::bytes.L2::cache_hint [%0], [%1, {%3, %4}], [%2], pol;\n}"
               :: "r"(dst), "l"(m), "r"(mb), "r"(c0), "r"(c1) : "memory");
}
DI void tma_prefetch(const CUtensorMap* m, int c0, int c1) {
  asm volatile("cp.async.bulk.prefetch.tensor.2d.L2.global.tile [%0, {%1, %2}];" :: "l"(m), "r"(c0), "r"(c1) : "memory");
}
DI void tma_store(const CUtensorMap* m, uint32_t src, int c0, int c1) {
  asm volatile("cp.async.bulk.tensor.2d.global.shared::cta.bulk_group [%0, {%2, %3}], [%1];" :: "l"(m), "r"(src), "r"(c0), "r"(c1) : "memory");
}
DI uint4 ldg_relaxed(const void* p) {
  uint4 v;
  asm volatile("ld.relaxed.gpu.global.v4.b32 {%0,%1,%2,%3}, [%4];" : "=r"(v.x), "=r"(v.y), "=r"(v.z), "=r"(v.w) : "l"(p) : "memory");
  return v;
}
DI void stg_relaxed(void* p, uint32_t x, uint32_t y, uint32_t z, uint32_t w) {
  asm volatile("st.relaxed.gpu.global.v4.b32 [%0], {%1,%2,%3,%4};" :: "l"(p), "r"(x), "r"(y), "r"(z), "r"(w) : "memory");
}
DI void red_f16x8(void* p, uint32_t x, uint32_t y, uint32_t z, uint32_t w) {
  asm volatile("red.relaxed.gpu.global.add.noftz.v4.f16x2 [%0], {%1,%2,%3,%4};" :: "l"(p), "r"(x), "r"(y), "r"(z), "r"(w) : "memory");
}
DI void sq_acc(uint32_t& a, uint32_t x) { asm("fma.rn.bf16x2 %0, %1, %1, %0;" : "+r"(a) : "r"(x)); }
DI __half2 amax4(__half2 h, const uint32_t* v) {
  h = __hmax2_nan(__hmax2_nan(h, __habs2(*(const __half2*)&v[0])), __habs2(*(const __half2*)&v[1]));
  return __hmax2_nan(__hmax2_nan(h, __habs2(*(const __half2*)&v[2])), __habs2(*(const __half2*)&v[3]));
}
DI uint32_t wexp(__half2 h) { const uint32_t u = *(const uint32_t*)&h; return __reduce_max_sync(0xffffffffu, max((u >> 16) & 0x7fffu, u & 0x7fffu)) >> 7; }
DI float max10(const float* a) {
  return fmaxf(fmaxf(fmaxf(fmaxf(a[0], a[1]), fmaxf(a[2], a[3])), fmaxf(fmaxf(a[4], a[5]), fmaxf(a[6], a[7]))), fmaxf(a[8], a[9]));
}
DI float quad_max(float m) {
  return fmaxf(fmaxf(m, __shfl_xor_sync(0xffffffffu, m, 1)), fmaxf(__shfl_xor_sync(0xffffffffu, m, 2), __shfl_xor_sync(0xffffffffu, m, 3)));
}
DI float warp_sum(float v) {
#pragma unroll
  for (int o = 16; o; o >>= 1) v += __shfl_xor_sync(0xffffffffu, v, o);
  return v;
}

constexpr int SM_WO3 = 0;
constexpr int SM_X = 16384;
constexpr int XT = 36864;
constexpr int SM_EXP = 126976;
constexpr int SEGB = 10240;
constexpr int SM_BLK = SM_EXP + 8192;
constexpr int SM_VC = SM_BLK + 4 * SEGB;
constexpr int SM_PART = SM_VC + 16384;
constexpr int SM_QM = SM_PART + 4096;
constexpr int SM_E = SM_QM + 1024;
constexpr int SM_VM = SM_E + 1536;
constexpr int SM_OB = SM_VM + 2048;
constexpr int SM_FB = SM_OB + 2048;
constexpr int SM_STAGE = SM_X + XT;
constexpr int SM_M0 = SM_STAGE + 3 * 49152;
constexpr int SM_MISC = 210944;
constexpr int SM_WOST = 212992;
constexpr int SM_MEM = SM_WOST;
constexpr int SM_MAX = SM_MEM + 11264;
#define MEM_BLK(q) ((q) / 3 * 4096 + (q) % 3 * 1024)
constexpr int SM_TOTAL = 229376;
constexpr int MB_W = SM_MISC;
constexpr int MB_WO = SM_MISC + 24;
constexpr int MB_WO3 = SM_MISC + 32;
constexpr int MB_X = SM_MISC + 40;
constexpr int MB_S = SM_MISC + 64;
constexpr int MB_F = SM_MISC + 72;
constexpr int MB_VX = SM_MISC + 80;
constexpr int SC_FPAR = SM_MISC + 136;
constexpr int SC_DEAD = SM_MISC + 96;
constexpr int SC_UNSC = SM_MISC + 112;
constexpr int SC_OFL = SM_MISC + 1024;
constexpr int SC_EXPW = SM_MISC + 132;
constexpr int SC_ONES = SM_MISC + 144;
constexpr int SC_SS = SM_MISC + 160;
constexpr int SC_LAT = SM_MISC + 224;
constexpr int SC_TAG = SM_MISC + 232;
constexpr int SC_EPO = SM_MISC + 240;
constexpr int MB_XS = SM_MISC + 248;
constexpr int SC_XMAX = SM_MISC + 256;
constexpr int SC_PROF = 229376;

constexpr float SM_SCALE = 0.08838834764831845f;
constexpr float LOG2E = 1.4426950408889634f;
constexpr float E_LIM = 20.f;

template <bool B> struct BoolC { static constexpr bool value = B; };
template <int I> struct IntC { static constexpr int value = I; };
struct RMaps { CUtensorMap x, wq, wk, wv, wo; unsigned char* red; uint32_t poll; const unsigned char* oflag; };

DI uint32_t latest_hint(uint32_t h, uint32_t d, int s) {
  const uint32_t x = (((h | 0xc0c0c0c0u) - ((d >> 5) & 63) * 0x01010101u) & 0x3f3f3f3fu) | ((h ^ (((s >> 2) + 1) & 3) * 0x40404040u) & 0xc0c0c0c0u);
  const uint32_t y = __vmaxu2(x & 0x00ff00ffu, (x >> 8) & 0x00ff00ffu);
  return __reduce_max_sync(0xffffffffu, max(y & 0xffffu, y >> 16));
}
DI uint32_t near_half(uint32_t sb) {
  uint32_t a, b; lds64(sb + SC_LAT, a, b);
  return a > b;
}

template <int RT, int K0, int K1, bool D32 = false>
DI void xproj(float* acc, const uint32_t (&wa)[2][18][4], uint64_t xd) {
  if (XP & 1) return;
  WG_FENCE();
#pragma unroll
  for (int k = K0; k < ((XP & 128) ? K0 + 1 : K1); k++)
  {
    uint64_t d = xd + (uint64_t)(((k >> 1) * 4096 + (k & 1) * 32) >> 4);
    if (D32) asm("mov.b64 %0, {%1, %2};" : "=l"(d) : "r"((uint32_t)xd + (((k >> 1) * 4096 + (k & 1) * 32) >> 4)), "r"((uint32_t)(xd >> 32)));
    wgmma_n32_rs(acc, wa[RT][k][0], wa[RT][k][1], wa[RT][k][2], wa[RT][k][3], d, k != 0);
  }
  WG_COMMIT();
}

DI void load_w(uint32_t sb, const RMaps& tm, uint32_t rank, int c) {
  const int h = blockIdx.x / 3;
  mbar_expect(sb + MB_W + 8 * c, 49152);
  ((EF & 4) ? tma_load_ef : tma_load)(sb + SM_STAGE + c * 49152, rank < 2 ? &tm.wk : &tm.wv, h * DH + (rank == 1 ? 64 : 0), c * 192, sb + MB_W + 8 * c);
  ((EF & 4) ? tma_load_ef : tma_load)(sb + SM_STAGE + c * 49152 + 24576, rank < 2 ? &tm.wq : &tm.wv, h * DH + (rank == 0 ? 0 : 64), c * 192, sb + MB_W + 8 * c);
}
DI void seg_store(int seg, uint32_t slot, uint32_t sb) {
  if (!FW) fence_async();
  asm volatile("cp.async.bulk.global.shared::cta.bulk_group [%0], [%1], 8192;"
               :: "l"(g_seg + ((size_t)slot * 96 + blockIdx.x) * 8192), "r"(sb + SM_BLK + (seg & 3) * SEGB) : "memory");
  asm volatile("cp.async.bulk.commit_group;" ::: "memory");
}
DI void seg_publish(int seg, uint32_t sb) {
  uint32_t v, own;
  lds64(sb + SC_EPO, v, own);
  asm volatile("cp.async.bulk.wait_group 0;" ::: "memory");
  asm volatile("st.relaxed.gpu.global.v2.b32 [%0], {%1,%2};" :: "l"(&g_sflag[blockIdx.x * 4]), "r"(v + seg), "r"(own) : "memory");
}

DI void proj_role(const uint32_t sb, const RMaps& tm, const bf16* __restrict__ x, const uint32_t rank, const int wg, const int w, const int lane) {
  const bool qk = rank < 2;
  uint32_t wa[2][18][4];
  float acc[16];
  const uint64_t xd0 = make_desc(sb + SM_X + wg * 64, 16, 1024, 1);
  {
    const int rr = (lane & 7) + ((lane >> 4) << 3);
    const uint32_t col = ((2 * w + ((lane >> 3) & 1)) ^ (lane & 7)) << 4;
    float ss = 0.f;
    bar_sync(3, 256);
    mbar_wait(sb + MB_X, 0);
    auto chunk = [&](auto cc) {
      constexpr int c = decltype(cc)::value;
      QSTAMP(2 + 2 * c);
      mbar_wait(sb + MB_W + 8 * c, 0);
      QSTAMP(3 + 2 * c);
#pragma unroll
      for (int rt = 1; rt >= 0; rt--)
#pragma unroll
        for (int k = 0; k < 6; k++)
          ldsm4t(wa[rt][c * 6 + k], sb + SM_STAGE + c * 49152 + (rt ^ wg) * 24576 + (64 * (k >> 1) + 32 * wg + 16 * (k & 1) + rr) * 128 + col);
      fence_async();
      if (c < 2) {
        bar_sync(3, 256);
        QSTAMP(17 + c);
        if (threadIdx.x == 0) {
          if (c == 0) tma_load(sb + SM_X + XT, &tm.wo, rank * 192, (blockIdx.x / 3) * DH, sb + MB_WO);
          else if (blockIdx.x < NSEG) bulk_load(sb + SM_X + 2 * XT, x + blockIdx.x * 32 * DM, XT, sb + MB_XS);
          else tma_load3(sb + SM_X + 2 * XT, &tm.x, 64, sb + MB_X + 16);
        }
        __syncwarp();
      } else {
        cluster_arrive();
      }
      xproj<1, 6 * c, 6 * c + 6>(acc, wa, xd0);
      if (!qk) {
        uint32_t q[4] = {0, 0, 0, 0};
#pragma unroll
        for (int rt = 0; rt < 2; rt++)
#pragma unroll
          for (int k = 0; k < 6; k++)
#pragma unroll
            for (int i = 0; i < 4; i++) sq_acc(q[i], wa[rt][c * 6 + k][i]);
#pragma unroll
        for (int i = 0; i < 4; i++) ss += bf_lo(q[i]) + bf_hi(q[i]);
      }
      if (c < 2 && CW) WG_WAIT(0);
    };
    chunk(IntC<0>()); chunk(IntC<1>()); chunk(IntC<2>());
    ss = warp_sum(ss);
    if (lane == 0) sts32(sb + SC_SS + 4 * (wg * 4 + w), __float_as_uint(ss));
    bar_arrive(11, 384);
  }
  STAMP(1);
  QSTAMP(8);
  STAMP(2);

  uint32_t t16 = sb + (w * 32 + lane) * 16;
  uint32_t mem_a = sb + SM_MEM + wg * 512 + lane * 16;
  uint32_t fin_a = sb + (lane & 7) * 16 + SM_BLK + (qk ? (wg ^ 1) * 4096 + w * 256 + (lane & 8) * 16 + (lane & 16) * 64
                                              : wg * 4096 + w * 1024 + (lane & 8) * 64 + (lane & 16) * 8);
  PIN(t16); PIN(mem_a); PIN(fin_a);
  const uint32_t fence_reg = mem_a;
  const uint32_t fin2 = qk ? 2048 : 256;
  auto do_export = [&](auto retire, uint32_t always) {
    WG_WAIT(0);
    uint32_t p[2];
#pragma unroll
    for (int i = 0; i < 2; i++) {
      p[i] = pack_bf16(acc[8 * i], acc[8 * i + 1]);
      sts128(t16 + SM_EXP + wg * 4096 + i * 2048, p[i], pack_bf16(acc[8 * i + 2], acc[8 * i + 3]),
             pack_bf16(acc[8 * i + 4], acc[8 * i + 5]), pack_bf16(acc[8 * i + 6], acc[8 * i + 7]));
    }
    if (decltype(retire)::value)
      asm volatile("{\n.reg .pred p, q;\nsetp.ne.u32 p, %2, 0;\nsetp.ne.u32 q, %2, 1;\n@p ld.shared.b32 %0, [%3];\n@q ld.shared.b32 %1, [%3 + 4];\n"
                   "setp.ne.u32 p, %0, %1;\n@p exit;\n}" : "+r"(p[0]), "+r"(p[1]) : "r"(always), "r"(sb + SC_DEAD) : "memory");
  };
  uint32_t o[8];
  auto import = [&]() { lds128(t16 + SM_EXP + (wg ^ 1) * 4096, o); lds128(t16 + SM_EXP + (wg ^ 1) * 4096 + 2048, o + 4); };
  auto finish_from = [&](int seg, const float* d) {
    const uint32_t a = fin_a + (seg & 3) * SEGB;
#pragma unroll
    for (int i = 0; i < 8; i++) o[i] = add_bf16(pack_bf16(d[2 * i], d[2 * i + 1]), o[i]);
    stsm4(a, o[0], o[1], o[2], o[3]);
    stsm4(a + fin2, o[4], o[5], o[6], o[7]);
    if (FW) fence_async();
  };
  auto finish = [&](int seg) { WG_WAIT(0); finish_from(seg, acc); };
  auto send_v = [&](int seg, int dst) {
    if (!FW) fence_async();
    if (seg < NSEG - 1 && !(XP & 2) && elect_one())
      bulk_s2s(mapa(sb + SM_VC + (seg & 1) * 8192, dst), sb + SM_BLK + (seg & 3) * SEGB, 8192, mapa(sb + MB_VX + (seg & 1) * 8, dst));
    __syncwarp();
  };
  auto wait_v = [&](int seg) {
    if (seg < NSEG - 1 && !(XP & 2)) {
      mbar_wait(sb + MB_VX + (seg & 1) * 8, (seg >> 1) & 1);
      if (elect_one()) mbar_expect(sb + MB_VX + (seg & 1) * 8, 8192);
      __syncwarp();
    }
  };
  auto export_seg = [&](int seg, uint32_t slot) { if (!(XP & (4 | 8192)) && elect_one()) seg_store(seg, slot, sb); __syncwarp(); };
  auto publish = [&](int seg) { if (!(XP & (4 | 16384)) && elect_one()) seg_publish(seg, sb); __syncwarp(); };
  do_export(BoolC<false>(), 0);
  QSTAMP(9);
  SCHED_FENCE(11);
  xproj<0, 0, 18>(acc, wa, xd0);
  bar_sync(3, 256);
  QSTAMP(10);
  cluster_wait();
  QSTAMP(11);
  mbar_wait(sb + MB_X + 8, 0);
  QSTAMP(12);
  import();
  finish(0);
  SCHED_FENCE(12);
  uint64_t dA = xd0 + (XT >> 4);
  xproj<1, 0, 18>(acc, wa, dA);
  bar_sync(3, 256);
  if (!qk && wg == 0 && w < 2) send_v(0, w);
  if (wg == 0 && w == 3) export_seg(0, 0);
  QSTAMP(13);
  if (qk && wg == 0 && w == 0) wait_v(0);
  QSTAMP(14);
  bar_arrive(13, 384);
  if (!qk) {
    do_export(BoolC<false>(), 0);
    SCHED_FENCE(15);
    xproj<0, 0, 18>(acc, wa, dA);
    if (threadIdx.x == 0 && !(XP & 8)) { mbar_expect(sb + MB_X, XT); tma_load3(sb + SM_X, &tm.x, 96, sb + MB_X); }
    bar_sync(3, 256);
    mbar_wait(sb + MB_X + 16, 0);
    import();
    finish(1);
    SCHED_FENCE(16);
    dA += XT >> 4;
    xproj<1, 0, 18>(acc, wa, dA);
  }
  QSTAMP(15);
  WG_WAIT(0);
  bar_sync(0, 384);
  if (wg == 0 && w == 3) publish(0);
  QSTAMP(16);
  const int ro = __shfl_sync(0xffffffffu, near_half(sb) ^ wg, 0);
  STAMP(5);
  const uint32_t always = __shfl_sync(0xffffffffu, lds32(sb + SC_DEAD + 12), 0);
  const int ah = qk ? 1 : 2;
  int b2 = qk ? 2 : 0;
  int s = 0;
  uint32_t hint_lo = (uint32_t)(uint64_t)tm.red + HINT_OFF + blockIdx.x + (lane & 1) * 4096 + (lane >> 1) * 16384;
  PIN(hint_lo);
  auto post_hint = [&]() {
    uint32_t t;
    asm volatile("{\n.reg .u64 g;\nmov.u64 g, %%globaltimer;\ncvt.u32.u64 %0, g;\n}" : "=r"(t) :: "memory");
    asm volatile("{\n.reg .pred p;\n.reg .b64 a;\n.reg .u32 t;\nsetp.lt.u32 p, %0, %1;\nmov.b64 a, {%2, %3};\n"
                 "bfe.u32 t, %5, 5, 6;\nor.b32 t, t, %4;\n@p st.relaxed.gpu.global.u8 [a], t;\n}"
                 :: "r"(t16), "r"(sb + 160), "r"(hint_lo + RED_SLOT(s)), "r"((uint32_t)((uint64_t)tm.red >> 32)), "r"(((s >> 2) + 1) << 6), "r"(t) : "memory");
  };
  auto memproj = [&](auto second, int id, uint32_t dep, float u0, float u1, float* r) {
    constexpr bool R1 = decltype(second)::value;
    uint32_t b[NUP][4], b0[4];
    if (R1) asm volatile("{\n.reg .pred p;\nsetp.eq.u32 p, %0, %1;\n@p exit;\n}" :: "r"(dep), "r"(id) : "memory");
    bar_sync(R1 ? 2 : 1, 256);
    PROF(0);
    ldsm4t(b0, mem_a);
#pragma unroll
    for (int q = 0; q < NUP; q++) {
      if (R1 && q == 2) {
        bar_sync(11, 256);
        SCHED_FENCE(id + 1);
      }
      ldsm4t(b[q], mem_a + MEM_BLK(q + 1));
    }
    mma16816z(&acc[0], wa[0][0], b0[0], b0[1]);
    mma16816z(&acc[4], wa[1][0], b0[0], b0[1]);
    mma16816z(&acc[8], wa[0][1], b0[2], b0[3]);
    mma16816z(&acc[12], wa[1][1], b0[2], b0[3]);
#pragma unroll
    for (int q = 1; q < 9; q++) {
      uint32_t* const c = b[(q - 1) % NUP];
      mma16816(&acc[0], wa[0][2 * q], c[0], c[1]);
      mma16816(&acc[4], wa[1][2 * q], c[0], c[1]);
      mma16816(&acc[8], wa[0][2 * q + 1], c[2], c[3]);
      mma16816(&acc[12], wa[1][2 * q + 1], c[2], c[3]);
      if (R1 && q + NUP == B3Q) bar_sync(3, 256);
      if (q + NUP < 9) ldsm4t_in(c, mem_a + MEM_BLK(q + NUP), always);
      else if (R1 && q + NUP < 11) lds128_in(c, t16 + SM_PART + (10 - q - NUP) * 2048, always);
      else if (!R1 && GATE && q == GATE) { bar_arrive(11, 256); lds128_in(c, sb + SC_DEAD, always); u0 = u1 = __uint_as_float(c[3]); }
    }
#pragma unroll
    for (int i = 0; i < 8; i++) {
      const float u = i < 4 ? u0 : u1;
      r[i] = R1 ? fmaf(acc[8 + i], u, (acc[i] + __uint_as_float(b[(8 + i / 4) % NUP][i & 3])) * u) : (GATE ? fmaf(acc[i], u, acc[8 + i]) : acc[i] + acc[8 + i]);
    }
  };
  if (ro == 0) {
#pragma unroll 1
    while (true) {
      do_export(BoolC<true>(), always);
      PROFP(3);
      if (s == 8) STAMP(6);
      float r[8];
      memproj(BoolC<false>(), 30, 0, 0.f, 0.f, r);
      sts128(t16 + SM_PART, __float_as_uint(r[0]), __float_as_uint(r[1]), __float_as_uint(r[2]), __float_as_uint(r[3]));
      sts128(t16 + SM_PART + 2048, __float_as_uint(r[4]), __float_as_uint(r[5]), __float_as_uint(r[6]), __float_as_uint(r[7]));
      bar_arrive(3, 256);
      PROF(1);
      bar_sync(9, 256);
      if (!(WE & 1) && s == NSEG - 1) break;
      post_hint();
      if (w == 3 && s) publish(s);
      if ((WE & 1) && s == NSEG - 1) break;
      if (w == 1) {
        uint32_t m[8];
        lds128(t16 + SM_MAX - 512, m); lds128(t16 + SM_MAX, m + 4);
        const int em = (wexp(amax4(amax4(*(const __half2*)&m[0], m), m + 4)) >> 3) + (int)(lds32(sb + SC_UNSC + (s & 1) * 8) >> 23) - 15;
        const int ex = max(s ? em : 0, (int)lds32(sb + SC_XMAX + 4 * s)) - 127 + (int)lds32(sb + SC_EXPW);
        sts32(sb + SC_UNSC + (~s & 1) * 8, (127 + min(max(ex, -120), 120)) << 23);
        __syncwarp();
        if (elect_one()) mbar_arrive(sb + MB_S);
      }
      SCHED_FENCE(9);
      bar_sync(5, qk ? N5 : 256);
      PROF(2);
      import();
      xproj<0, 0, NII>(acc, wa, dA);
      if (NII < 18) {
        if (qk) bar_sync(7, 384);
        xproj<0, NII, 18>(acc, wa, dA);
        if (!qk) bar_sync(7, 384);
      } else {
        if (F10) WG_WAIT(0);
        bar_sync(10, 256);
        if (F10) SCHED_FENCE(17);
      }
      dA += (int64_t)(b2 ? XT >> 4 : -(XT >> 3));
      finish(s + ah);
      if (w != 3) bar_arrive(13, 384);
      PROF(6);
      SCHED_FENCE(14);
      if (NOB & 2) bar_arrive(14, 256);
      bar_sync(12, 256);
      PROF(7);
      xproj<1, 0, 18, true>(acc, wa, dA);
      if (!(NOB & 2)) bar_arrive(14, 256);
      b2 = b2 == 2 ? 0 : b2 + 1;
      s++;
      if (w == 3) {
        const uint32_t slot = s < lds32(sb + SC_EPO + 4) ? s & 7 : s;
        bar_sync(13, 384);
        export_seg(s, slot);
      }
      PROFP(8);
    }
    if (!qk) bar_arrive(5, 256);
    if (!(WE & 1) && w == 3) publish(NSEG - 1);
  } else {
    uint32_t km[4];
    auto send_km = [&]() {
      if (XP & (4 | 4096)) return;
      uint32_t t, u;
      lds64(sb + SC_TAG, t, u);
      t |= km[0] & ~1u; u += s * (NH * 4096);
      if (qk)
        asm volatile("{\n.reg .u32 o;\n.reg .u64 a;\nshr.u32 o, %0, 1;\nadd.u32 o, o, %1;\nmad.wide.u32 a, o, 1, %2;\nst.relaxed.gpu.global.v2.b32 [a], {%3,%4};\n}"
                     :: "r"(t16), "r"(u), "l"(g_km), "r"(t), "r"(km[1]) : "memory");
      else
        asm volatile("{\n.reg .u32 o;\n.reg .u64 a;\nadd.u32 o, %0, %1;\nmad.wide.u32 a, o, 1, %2;\nst.relaxed.gpu.global.v4.b32 [a], {%3,%4,%5,%6};\n}"
                     :: "r"(t16), "r"(u), "l"(g_km), "r"(t), "r"(km[1]), "r"(km[2]), "r"(km[3]) : "memory");
    };
#pragma unroll 1
    while (true) {
      do_export(BoolC<true>(), always);
      if (!qk && w == 2) send_v(s + 1, 0);
      PROFP(3);
      if (s == 8) STAMP(6);
      const uint32_t tl = ((t16 >> 8) ^ wg) & 1, am = (t16 & ~256u) - w * 256;
      const float un = __uint_as_float(lds32(sb + SC_UNSC + (s & 1) * 8));
      float r[8];
      if (qk) {
        uint32_t a0 = am + (tl ? SM_QM : SM_BLK + 8192 + (s & 3) * SEGB);
        float u0 = wg ? un * (SM_SCALE * LOG2E) : un, u1 = wg ? un : un * (SM_SCALE * LOG2E);
        PIN(a0); PIN(u0); PIN(u1);
        memproj(BoolC<true>(), 32, a0, u0, u1, r);
        const uint32_t p0 = pack_bf16(r[0], r[1]), p1 = pack_bf16(r[2], r[3]), p2 = pack_bf16(r[4], r[5]), p3 = pack_bf16(r[6], r[7]);
        stsm4(a0, p0, p1, p2, p3);
        bar_arrive(4, 256);
        km[0] = wg ? p2 : p0; km[1] = wg ? p3 : p1;
      } else {
        const uint32_t d0 = s < NSEG - 1 ? 0 : 2, d1 = s < NSEG - 1 ? 1 : 2;
        uint32_t r0 = mapa(t16 + SM_VM, d0), r1 = mapa(t16 + SM_VM, d1);
        PIN(r0); PIN(r1);
        memproj(BoolC<true>(), 34, r0 | r1, un, un, r);
        const uint32_t p0 = pack_bf16(r[0], r[1]), p1 = pack_bf16(r[2], r[3]), p2 = pack_bf16(r[4], r[5]), p3 = pack_bf16(r[6], r[7]);
        const uint32_t v0 = wg ? p2 : p0, v1 = wg ? p3 : p1, v2 = wg ? p0 : p2, v3 = wg ? p1 : p3;
        st_async4(r0, v0, v1, v2, v3, mapa(sb + MB_S, d0));
        st_async4(r1, v0, v1, v2, v3, mapa(sb + MB_S, d1));
        bar_arrive(5, 256);
        sts128(t16 + SM_VM, v0, v1, v2, v3);
        __syncwarp();
        if (elect_one()) mbar_arrive(sb + MB_S);
        km[0] = v0; km[1] = v1; km[2] = v2; km[3] = v3;
      }
      if (!(WE & 2) && s == NSEG - 1) break;
      PROF(1);
      auto rearm = [&]() { mbar_wait(sb + MB_S, s & 1); if (elect_one()) mbar_expect(sb + MB_S, qk ? 640 + 2048 : 1280); __syncwarp(); };
      if ((WE & 2) && s == NSEG - 1 && w != 1) {
      } else if (w == 1) {
        if ((t16 & 384) == 0) stg_relaxed(tm.red + (RED_SLOT(s + 2) + RED_LINE(blockIdx.x)) + (t16 & 112), 0, 0, 0, 0);
        uint32_t base, own;
        lds64(sb + SC_EPO, base, own);
        if ((int)(lds32v(sb + SC_OFL) - base) < s - 7) sts32(sb + SC_EPO + 4, min(own, s + 1));
        if (elect_one()) bulk_load(sb + SC_OFL, tm.oflag + blockIdx.x * 128, 16, sb + MB_XS);
      } else if (w == 0) {
        const int tn = s + ah + 1;
        if (RFW) mbar_wait(sb + MB_S, s & 1);
        if (tn + 1 < NSEG && !(XP & 8) && elect_one()) {
          const int b0 = b2 == 2 ? 0 : b2 + 1;
          mbar_expect(sb + MB_X + 8 * b0, XT);
          tma_load3(sb + SM_X + b0 * XT, &tm.x, (tn + 1) * 32, sb + MB_X + 8 * b0);
        }
        if (tn < NSEG && (!(XP & 8) || tn < 3)) mbar_wait(sb + MB_X + 8 * b2, (tn / 3) & 1);
      } else if (w == 2) {
        if (!qk) { if (VW2 < 1) send_v(s + 1, 0); if (VW2 < 2) send_v(s + 1, 1); }
      } else if (qk || !NIC) {
        rearm();
      }
      __syncwarp();
      send_km();
      if ((WE & 2) && s == NSEG - 1) break;
      import();
      PROF(4);
      SCHED_FENCE(10);
      if (NIC) {
        if (qk) bar_sync(7, NII < 18 ? 384 : 256);
        xproj<0, 0, NIC>(acc, wa, dA);
        if (!qk) { if (w == 3) rearm(); bar_sync(7, NII < 18 ? 384 : 256); }
      } else {
        bar_sync(7, NII < 18 ? 384 : 256);
      }
      if (NOB & 1) bar_arrive(12, 256);
      xproj<0, NIC, 18>(acc, wa, dA);
      if (!(NOB & 1)) bar_arrive(12, 256);
      dA += (int64_t)(b2 ? XT >> 4 : -(XT >> 3));
      finish(s + ah);
      if (qk && w == 0) wait_v(s + 1);
      bar_arrive(13, 384);
      PROF(6);
      SCHED_FENCE(13);
      bar_sync(14, 256);
      PROF(7);
      xproj<1, 0, 18>(acc, wa, dA);
      b2 = b2 == 2 ? 0 : b2 + 1;
      s++;
      PROFP(8);
    }
    if (!(WE & 2)) {
      send_km();
      PIN(t16);
      if (t16 - sb < 128) stg_relaxed(tm.red + (RED_SLOT(NSEG + 1) + RED_LINE(head_id() * 3 + rank)) + (t16 & 112), 0, 0, 0, 0);
    }
  }
  bar_arrive(0, 384);
  STAMP(3);
  cluster_sync();
  STAMP(4);
}

DI void attn_role(const uint32_t sb, unsigned char* smem_raw, const RMaps& tm, const uint32_t RANK, const bf16* __restrict__ x, const bf16* __restrict__ mem0,
                  const int w, const int lane) {
  const int t2 = w * 32 + lane;
  uint32_t wo[8][4], w1[8][4];
  const uint32_t wo_lane = sb + ((lane & 7) + ((lane >> 4) << 3)) * 128 + (((w + 4 * ((lane >> 3) & 1)) ^ (lane & 7)) << 4);
  unsigned char* const g_red = tm.red;
  {
    const uint32_t tag = *(volatile unsigned*)&g_epoch + 1;
    QSTAMP(0);
    bar_sync(0, 160);
    QSTAMP(1);
    cluster_arrive();
    __half2 hx = __float2half2_rn(0.f);
    if (t2 == 0) { sts32(sb + SC_OFL, (tag - 1) * NSEG); sts64(sb + SC_EPO, (tag - 1) * NSEG + 1, NSEG); sts64(sb + SC_TAG, tag & 1, blockIdx.x / 3 * 4096 + (RANK < 2 ? RANK * 1024 - (sb >> 1) : 2048 - sb)); sts32(sb + SC_UNSC, __float_as_uint(1.f)); sts128(sb + SC_DEAD, 0, 0, 0, 0x3f800000u); sts64(sb + SC_FPAR, 0, 0); sts128(sb + SC_ONES, 0x3f803f80u, 0x3f803f80u, 0x3f803f80u, 0x3f803f80u); }
    WSTAMP(27);
    uint32_t q[8] = {0, 0, 0, 0, 0, 0, 0, 0};
    QSTAMP(2);
    mbar_wait(sb + MB_WO3, 0);
    QSTAMP(3);
    uint32_t mv[5][4];
#pragma unroll
    for (int i = 0; i < 5; i++) {
      ldsm4(mv[i], sb + SM_M0 + (lane & 7) * (DM * 2) + min(w + 4 * i, 17) * 64 + (lane >> 3) * 16);
      if (blockIdx.x == 0) hx = amax4(hx, mv[i]);
    }
#pragma unroll
    for (int k = 0; k < 8; k++) {
      ldsm4t(wo[k], wo_lane + SM_WO3 + k * 2048); ldsm4t(w1[k], wo_lane + SM_WOST + k * 2048);
#pragma unroll
      for (int i = 0; i < 4; i++) { sq_acc(q[i], wo[k][i]); sq_acc(q[i], w1[k][i]); }
    }
    bar_sync(6, 128);
#pragma unroll
    for (int k = 0; k < 8; k++) sts128(sb + SM_WO3 + t2 * 16 + k * 2048, wo[k][0], wo[k][1], wo[k][2], wo[k][3]);
#pragma unroll
    for (int i = 0; i < 5; i++) {
      const int c = (w + 4 * i) * 32;
      if (c < DM) stsm4t(sb + SM_MEM + (c + c / 192 * 64 + lane) * 16, mv[i][0], mv[i][1], mv[i][2], mv[i][3]);
    }
    bar_arrive(1, 256); bar_arrive(2, 256); bar_arrive(9, 256);
    QSTAMP(4);
    mbar_wait(sb + MB_WO, 0);
    QSTAMP(5);
#pragma unroll
    for (int k = 0; k < 8; k++) ldsm4t(wo[k], wo_lane + SM_X + XT + k * 2048);
    fence_async();
    bar_sync(6, 128);
    if (t2 == 32) tma_load3(sb + SM_X + XT, &tm.x, 32, sb + MB_X + 8);
    __syncwarp();
#pragma unroll
    for (int k = 0; k < 8; k++)
#pragma unroll
      for (int i = 0; i < 4; i++) sq_acc(q[4 + i], wo[k][i]);
    float ss = 0.f;
#pragma unroll
    for (int i = 0; i < 8; i++) ss += bf_lo(q[i]) + bf_hi(q[i]);
    ss = warp_sum(ss);
    if (lane == 0) sts32(sb + SC_SS + 4 * (8 + w), __float_as_uint(ss));
    if (blockIdx.x < NSEG) {
      mbar_wait(sb + MB_XS, 0);
#pragma unroll
      for (int i = 0; i < 18; i++) { uint32_t v[4]; lds128(sb + SM_X + 2 * XT + t2 * 16 + i * 2048, v); hx = amax4(hx, v); }
      fence_async();
      bar_sync(6, 128);
      if (t2 == 32) tma_load3(sb + SM_X + 2 * XT, &tm.x, 64, sb + MB_X + 16);
      __syncwarp();
    }
    sts32(sb + SC_SS + 4 * (12 + w), wexp(hx));
    QSTAMP(6);
    bar_sync(11, 384);
    QSTAMP(7);
    if (t2 == 0) {
      float a[16];
#pragma unroll
      for (int i = 0; i < 4; i++) lds128f(sb + SC_SS + 16 * i, &a[4 * i]);
      stg_relaxed(&g_stats[blockIdx.x * 2], __float_as_uint(((a[0] + a[1]) + (a[2] + a[3])) + ((a[4] + a[5]) + (a[6] + a[7]))),
                  __float_as_uint((a[8] + a[9]) + (a[10] + a[11])),
                  max(max(__float_as_uint(a[12]), __float_as_uint(a[13])), max(__float_as_uint(a[14]), __float_as_uint(a[15]))), tag);
    }
    __syncwarp();
    WSTAMP(24);
    QSTAMP(8);
    cluster_wait();
    QSTAMP(9);
    if (w == 0) {
      uint4 v[3];
      int n = 0;
      while (true) {
#pragma unroll
        for (int i = 0; i < 3; i++) v[i] = ldg_relaxed(&g_stats[(i * 32 + lane) * 2]);
        if (__all_sync(0xffffffffu, v[0].w == tag && v[1].w == tag && v[2].w == tag) || ++n > SPIN_LIMIT) break;
        __nanosleep(100);
      }
      WSTAMP(25);
      QSTAMP(10);
      const float sv = warp_sum(__uint_as_float(v[0].x) + __uint_as_float(v[1].x) + __uint_as_float(v[2].x));
      const float so = warp_sum(__uint_as_float(v[0].y) + __uint_as_float(v[1].y) + __uint_as_float(v[2].y));
      const int expW = ((int)(__float_as_uint(sv) >> 23) + (int)(__float_as_uint(so) >> 23) - 254 + 2 + 10 + 1) >> 1;
      sts32(sb + SC_XMAX + 4 * lane, v[0].z); sts32(sb + SC_XMAX + 128 + 4 * lane, v[1].z);
      sts32(sb + SC_EXPW, expW + 1 - 15);
      if (blockIdx.x == 0 && lane == 0) *(volatile unsigned*)&g_epoch = tag;
      sts32(sb + SC_FPAR + 4, 1);
    } else if (w < 3) {
      const uint32_t u = blockIdx.x >> 4;
      unsigned char* const z = g_red + 98304 + (blockIdx.x & 15) * 128 + (u & 1) * 2048 + (u & 6) * 4096 + (((u >> 1) ^ w) & 1) * 4096 + lane * 4;
      stg_relaxed32(z, 0);
      uint32_t best = 0xffffffffu;
#pragma unroll 1
      for (int i = 0; i < 64; i++) {
        uint32_t dt;
        asm volatile("{\n.reg .pred p;\n.reg .u32 c, v;\nmov.u32 c, %%clock;\n"
                     "atom.relaxed.gpu.global.exch.b32 v, [%1], 0;\nsetp.eq.u32 p, v, 0;\nmov.u32 %0, 0;\n@p mov.u32 %0, %%clock;\nsub.u32 %0, %0, c;\n}"
                     : "=r"(dt) : "l"(z) : "memory");
        best = min(best, dt);
        if (lds32v(sb + SC_FPAR + 4) && i >= NPROBE - 1) break;
      }
      sts32(sb + SC_LAT + (w - 1) * 4, best);
    }
    QSTAMP(11);
    bar_sync(13, 384);
    bar_arrive(0, 384);
    QSTAMP(12);
    WSTAMP(26);
  }

  const uint32_t nh = __shfl_sync(0xffffffffu, near_half(sb), 0);
  uint32_t l16 = sb + lane * 16;
  PIN(l16);
#define LV ((l16 >> 4) & 31)
#define fence_reg l16
  const uint32_t red_lo = (uint32_t)(uint64_t)g_red, red_hi = (uint32_t)((uint64_t)g_red >> 32);
  uint32_t lp;
  auto slot = [&](int s, uint32_t c, uint32_t ofs) {
    const uint32_t lo = lp | (red_lo + ((w >> 1) * 4 + (w & 1) * 2 + ((w ^ c) & 1)) * 4096 + RED_SLOT(s) + ofs);
    uint64_t a; asm("mov.b64 %0, {%1, %2};" : "=l"(a) : "r"(lo), "r"(red_hi));
    return (unsigned char*)a;
  };
  const uint32_t always = __shfl_sync(0xffffffffu, lds32(sb + SC_DEAD + 12), 0);
  const int mode0 = RANK < 2 ? w : w | 4;
  auto hint_addr = [&](int s) { return min(LV, 23u) * 4 + (red_lo + HINT_OFF + nh * 4096 + w * 16384 + RED_SLOT(s)); };
  auto load_hints = [&](uint32_t lo) {
    uint64_t a; asm("mov.b64 %0, {%1, %2};" : "=l"(a) : "r"(lo), "r"(red_hi));
    return ldg_relaxed32((const void*)a);
  };
  int s = 0;
  bool bad = false;
#pragma unroll 1
  while (true) {
    const uint32_t par = s & 1;
    uint32_t vx[4][4], hints;
    auto load_vx = [&]() {
      const uint32_t va = l16 + (RANK < 2 ? SM_VC + par * 8192 : SM_BLK + (s & 3) * SEGB) + w * 1024 + ((LV >> 3) & 1) * 384 - (LV >> 4) * 128;
#pragma unroll
      for (int i = 0; i < 4; i++) ldsm4(vx[i], va + (i & 1) * 4096 + (i >> 1) * 256);
    };
    auto retire = [&](uint32_t x) {
      asm volatile("{\n.reg .pred p;\nsetp.eq.u32 p, %0, 0;\n@p exit;\n}" :: "r"(vx[0][0] | vx[1][0] | vx[2][0] | vx[3][0] | x) : "memory");
    };
    auto scores = [&](auto memkeys, auto first, float* sc) {
      constexpr bool MK = decltype(memkeys)::value, FIRST = decltype(first)::value;
      uint32_t kb[4][4], qb[2][4];
      const uint32_t m = LV >> 3;
      uint32_t kaddr = l16 + SM_BLK + 4096 + (s & 3) * SEGB + w * 2048 + (m & 1) * (MK ? 128 : 896) - (m >> 1) * 128;
      if (MK) { PIN(kaddr); }
      else {
#pragma unroll
        for (int k = 0; k < 4; k++) ldsm4t(kb[k], kaddr + k * 256);
      }
      if (FIRST) { load_vx(); retire(MK ? kaddr : kb[0][0] | kb[1][0] | kb[2][0] | kb[3][0] | l16); bar_sync(4, 256); PROF(4); }
      ldsm4t(qb[0], l16 + SM_QM);
      if (MK) ldsm4t(kb[0], kaddr);
      ldsm4t(qb[1], l16 + SM_QM + 512);
      if (MK) ldsm4t(kb[2], kaddr + 512);
      float c[4][4];
      mma16816z(c[0], kb[0], qb[0][0], qb[0][1]); mma16816z(c[1], kb[MK ? 0 : 1], qb[0][2], qb[0][3]);
      mma16816z(c[2], kb[2], qb[1][0], qb[1][1]); mma16816z(c[3], kb[MK ? 2 : 3], qb[1][2], qb[1][3]);
      if (FIRST && B5POS == 0) bar_arrive(5, N5);
#pragma unroll
      for (int i = 0; i < (MK ? 2 : 4); i++) sc[i] = ((c[0][i] + c[1][MK ? i + 2 : i]) + c[2][i]) + c[3][MK ? i + 2 : i];
    };
    auto send = [&](auto memkeys) {
      constexpr bool MK = decltype(memkeys)::value;
      constexpr int N = MK ? 1 : 2;
      const uint32_t sa = sb + LV * 4 + SM_E + (MK ? 1024 + RANK * 128 : RANK * 512 + w * 256);
      uint32_t ra[N][2], mb[N][2];
#pragma unroll
      for (int i = 0; i < N; i++)
#pragma unroll
        for (int j = 0; j < 2; j++) {
          ra[i][j] = mapa(sa + i * 128, j ? 2 : RANK ^ 1); mb[i][j] = mapa(sb + MB_S, j ? 2 : RANK ^ 1);
          PIN(ra[i][j]);
        }
      float sc[4];
      scores(memkeys, BoolC<true>(), sc);
      uint32_t e[N];
#pragma unroll
      for (int i = 0; i < N; i++) {
        e[i] = pack_bf16(ex2(sc[2 * i]), ex2(sc[2 * i + 1]));
        if (!(fmaxf(fabsf(sc[2 * i]), fabsf(sc[2 * i + 1])) <= E_LIM)) e[i] = 0x7fff7fffu;
        st_async1(ra[i][0], e[i], mb[i][0]);
        st_async1(ra[i][1], e[i], mb[i][1]);
      }
#pragma unroll
      for (int i = 0; i < N; i++) sts32(sa + i * 128, e[i]);
      __syncwarp();
      if (l16 == sb) mbar_arrive(sb + MB_S);
      PROF(5);
    };
    const int mode = bad ? 8 : mode0;
    if (mode < 2) {
      send(BoolC<false>());
    } else if (mode == 2) {
      send(BoolC<true>());
    } else if (mode == 8) {
      load_vx();
      retire(l16);
      const uint32_t fp = lds32(sb + SC_FPAR);
      bar_sync(6, 128);
      if (w == 0 && l16 == sb) { sts32(sb + SC_FPAR, fp ^ 1); mbar_expect(sb + MB_F, 3072); }
      if (RANK < 2 && w < 3) {
        float sc[4] = {0.f, 0.f, 0.f, 0.f};
        if (w < 2) scores(BoolC<false>(), BoolC<false>(), sc); else scores(BoolC<true>(), BoolC<false>(), sc);
#pragma unroll 1
        for (int r = 0; r < 3; r++)
          st_async4(mapa(l16 + SM_FB + RANK * 1536 + w * 512, r), __float_as_uint(sc[0]), __float_as_uint(sc[1]), __float_as_uint(sc[2]), __float_as_uint(sc[3]), mapa(sb + MB_F, r));
      }
      mbar_wait(sb + MB_F, fp);
      float a[12];
#pragma unroll
      for (int j = 0; j < 3; j++) {
        float b[4];
        lds128f(l16 + SM_FB + j * 512, a + 4 * j); lds128f(l16 + SM_FB + 1536 + j * 512, b);
#pragma unroll
        for (int i = 0; i < 4; i++) a[4 * j + i] += b[i];
      }
      float m0 = fmaxf(fmaxf(fmaxf(a[0], a[2]), fmaxf(a[4], a[6])), a[8]), m1 = fmaxf(fmaxf(fmaxf(a[1], a[3]), fmaxf(a[5], a[7])), a[9]);
#pragma unroll
      for (int o = 4; o < 32; o <<= 1) { m0 = fmaxf(m0, __shfl_xor_sync(0xffffffffu, m0, o)); m1 = fmaxf(m1, __shfl_xor_sync(0xffffffffu, m1, o)); }
#pragma unroll
      for (int i = 0; i < 5; i++) {
        const uint32_t ea = sb + SM_E + LV * 4 + (i < 4 ? i * 128 : 1024);
        sts32(ea, pack_bf16(ex2(a[2 * i] - m0), ex2(a[2 * i + 1] - m1)));
        sts32(ea + (i < 4 ? 512 : 128), 0x3f803f80u);
      }
      __syncwarp();
    } else {
      load_vx();
      if (mode == 3) bar_arrive(4, 256);
      retire(l16 + 1);
    }
    {
      uint32_t wa[4], wb[4], oc[4];
      constexpr int WS = 2048;
      const uint32_t w3a = l16 + SM_WO3 + w * 512;
      lds128(w3a + KP(0) * WS, wa); lds128(w3a + KP(1) * WS, wb); lds128(sb + SC_ONES, oc);
      if (B5POS == 1 && mode < 3) bar_arrive(5, N5);
      uint32_t e[10], p[5], vm[4], ob[4];
      float o0[4], o1[4], f[3][2][4], rs[4];
      reserve2(vm); reserve2(vm + 2); reserve2(e + 8);
      hints = hint_addr(s);
      PIN(hints);
      if (CLR & 2) asm volatile("{\n.reg .pred p;\nsetp.eq.u32 p, %0, 0;\n@p exit;\n}" :: "r"(wa[0] | wb[0] | oc[0] | hints) : "memory");
      mbar_wait(sb + MB_S, par);
      PROF(6);
      ldsm4t(e, l16 + SM_E); ldsm2t_in(e + 8, l16 + SM_E + 1024, always); ldsm4t(e + 4, l16 + SM_E + 512);
      lds128_in(vm, l16 + w * 512 + SM_VM, always);
      const float scl = __uint_as_float(lds32(sb + SC_UNSC + 8 - par * 8));
      hints = load_hints(hints);
      if (GF & 1) SCHED_FENCE(4);
#pragma unroll
      for (int i = 0; i < 4; i++) p[i] = mul_bf16(e[i], e[4 + i]);
      p[4] = mul_bf16(e[8], e[9]);
      if (MO & 4) {
        float a0[4], a1[4];
        mma16816z(o0, vx[0], p[0], p[1]); mma16816z(o1, vx[1], p[0], p[1]);
        mma16816z(a0, vx[2], p[2], p[3]); lds128_in(vx[2], w3a + KP(2) * WS, always);
        mma16816z(a1, vx[3], p[2], p[3]); lds128_in(vx[3], w3a + KP(3) * WS, always);
        mma1688(o0, vm[0], vm[1], p[4]); mma1688(o1, vm[2], vm[3], p[4]);
        mma16816z(rs, oc, p[0], p[1]); mma16816(rs, oc, p[2], p[3]); mma1688(rs, oc[0], oc[1], p[4]);
#pragma unroll
        for (int i = 0; i < 4; i++) { o0[i] += a0[i]; o1[i] += a1[i]; }
      } else {
      mma16816z(o0, vx[0], p[0], p[1]); mma16816z(o1, vx[1], p[0], p[1]); mma16816z(rs, oc, p[0], p[1]);
      mma16816(o0, vx[2], p[2], p[3]); lds128_in(vx[2], w3a + KP(2) * WS, always);
      mma16816(o1, vx[3], p[2], p[3]); lds128_in(vx[3], w3a + KP(3) * WS, always);
      mma16816(rs, oc, p[2], p[3]);
      mma1688(o0, vm[0], vm[1], p[4]); mma1688(o1, vm[2], vm[3], p[4]); mma1688(rs, oc[0], oc[1], p[4]);
      }
      stsm4(l16 + w * 512 + SM_OB, pack_bf16(o0[0], o0[1]), pack_bf16(o0[2], o0[3]), pack_bf16(o1[0], o1[1]), pack_bf16(o1[2], o1[3]));
      bar_sync(6, 128);
      PROF(7);
      ldsm4t_in(oc, l16 + SM_OB, always);
      bad = __any_sync(0xffffffffu, !(rs[0] + rs[1] > 0.f) && !bad);
      rs[0] *= scl; rs[1] *= scl;
      asm volatile("{\n.reg .pred p;\nsetp.ne.u32 p, %1, 0;\n@p rcp.approx.ftz.f32 %0, %0;\n}" : "+f"(rs[0]) : "r"(always));
      asm volatile("{\n.reg .pred p;\nsetp.ne.u32 p, %1, 1;\n@p rcp.approx.ftz.f32 %0, %0;\n}" : "+f"(rs[1]) : "r"(always));
      asm volatile("lop3.b32 %0, %1, %2, %3, 0xfe;" : "=r"(lp) : "r"((l16 & 128) * 2), "r"((l16 & 256) * 4), "r"(l16 & 112));
      if (bad) continue;
      ldsm4t(ob, l16 + SM_OB + 512);
      mma16816z(f[2][0], wa, oc[0], oc[1]); mma16816z(f[2][1], wb, oc[2], oc[3]);
      mma16816z(f[0][0], wo[0], oc[0], oc[1]); mma16816z(f[0][1], wo[4], oc[2], oc[3]);
      mma16816z(f[1][0], w1[0], oc[0], oc[1]); mma16816z(f[1][1], w1[4], oc[2], oc[3]);
      ldsm4t_in(oc, l16 + SM_OB + 1024, always);
      mma16816(f[2][0], vx[2], ob[0], ob[1]); lds128_in(vx[2], w3a + KP(4) * WS, always);
      mma16816(f[2][1], vx[3], ob[2], ob[3]); lds128_in(vx[3], w3a + KP(5) * WS, always);
      mma16816(f[0][0], wo[1], ob[0], ob[1]); mma16816(f[0][1], wo[5], ob[2], ob[3]);
      mma16816(f[1][0], w1[1], ob[0], ob[1]); mma16816(f[1][1], w1[5], ob[2], ob[3]);
      ldsm4t_in(ob, l16 + SM_OB + 1536, always);
      mma16816(f[0][0], wo[2], oc[0], oc[1]); mma16816(f[0][1], wo[6], oc[2], oc[3]);
      mma16816(f[2][0], vx[2], oc[0], oc[1]); lds128_in(vx[2], w3a + KP(6) * WS, always);
      mma16816(f[2][1], vx[3], oc[2], oc[3]); lds128_in(vx[3], w3a + KP(7) * WS, always);
      mma16816(f[1][0], w1[2], oc[0], oc[1]); mma16816(f[1][1], w1[6], oc[2], oc[3]);
      mma16816(f[0][0], wo[3], ob[0], ob[1]); mma16816(f[0][1], wo[7], ob[2], ob[3]);
      mma16816(f[1][0], w1[3], ob[0], ob[1]); mma16816(f[1][1], w1[7], ob[2], ob[3]);
      mma16816(f[2][0], vx[2], ob[0], ob[1]); mma16816(f[2][1], vx[3], ob[2], ob[3]);
      bar_arrive(7, NII < 18 ? 384 : 256);
      lds128_in(ob, sb + SC_DEAD, always);
      uint32_t h[3][2];
#pragma unroll
      for (int j = 0; j < 3; j++)
#pragma unroll
        for (int i = 0; i < 2; i++)
        {
          scale_sum(f[j][1][2 * i], f[j][0][2 * i], rs[0], always); scale_sum(f[j][1][2 * i + 1], f[j][0][2 * i + 1], rs[1], always);
          h[j][i] = pack_f16(f[j][1][2 * i], f[j][1][2 * i + 1]);
        }
      const uint32_t rofs = RANK * 32768;
      red_f16x8(slot(s, RANK >> 1, rofs), h[0][0], h[1][0], h[2][0], 0x3c00u);
      red_f16x8(slot(s, (RANK >> 1) ^ 1, rofs), h[0][1], h[1][1], h[2][1], 0x3c00u);
      if (NII == 18) bar_arrive(10, 256);
      SCHED_FENCE(5);
      l16 += ob[B7R];
    }
    {
    PROF(8);
    const uint32_t ma0 = l16 + SM_MEM + w * 128 + (LV >> 3) * 896 + nh * 512;
    const unsigned char* const sl[2] = {slot(s, nh, 0), slot(s, nh ^ 1, 0)};
    uint32_t dl = gtime() - 1984;
    uint32_t late = latest_hint(hints, dl, s);
    if (late >= 64) {
      int n = 0;
#pragma unroll 1
      do {
        hints = load_hints(hint_addr(s));
        dl = gtime() - 1984;
        late = latest_hint(hints, dl, s);
      } while (late >= 64 && ++n < SPIN_LIMIT);
    }
    dl += late * 32 + tm.poll;
    PROF(9);
    {
      auto wait_until = [&](uint32_t t) {
        asm volatile("{\n.reg .pred p;\n.reg .s32 c;\n.reg .u64 t;\nTL: mov.u64 t, %%globaltimer;\ncvt.u32.u64 c, t;\nsub.s32 c, c, %0;\nsetp.lt.s32 p, c, 0;\n@p bra.uni TL;\n}" :: "r"(t + (l16 & 15)) : "memory");
      };
      uint4 v[2][3];
      auto load = [&](int c) {
#pragma unroll
        for (int r = 0; r < 3; r++) v[c][r] = ldg_relaxed(sl[c ^ (r >> 1)] + r * 32768);
      };
      auto decode = [&](int c, int n) {
        uint32_t q[9];
        __half2 hm;
        const uint32_t ma = ma0 ^ (c * 512);
#pragma unroll
        for (int i = 0; i < 9; i++) {
          const uint32_t h = i % 3 == 0 ? v[c][i / 3].x : (i % 3 == 1 ? v[c][i / 3].y : v[c][i / 3].z);
          const float2 f = __half22float2(*(const __half2*)&h);
          q[i] = pack_bf16(f.x, f.y);
          hm = i ? __hmax2(hm, __habs2(*(const __half2*)&h)) : __habs2(*(const __half2*)&h);
        }
#pragma unroll
        for (int r = 0; r < 3; r++) stsm4(ma + r * 4096, q[3 * r], q[3 * r + 1], q[3 * r + 2], r < 2 ? v[c][r].w : *(const uint32_t*)&hm);
        const bool done = __all_sync(0xffffffffu, v[c][0].w == 0x5000u && v[c][1].w == 0x5000u && v[c][2].w == 0x5000u) || n > SPIN_LIMIT;
        asm volatile("{\n.reg .pred p;\nsetp.ne.u32 p, %0, 0;\n@p bar.arrive %1, 256;\n}" :: "r"((int)done), "r"(1 + c) : "memory");
        return done;
      };
      if (LEAD) { wait_until(dl - LEAD); load(1); }
      int n = MO & 1 ? l16 & 15 : 0;
      if (MO & 1) PIN(n);
      if (MO & 2) {
        const uint32_t t = __shfl_sync(0xffffffffu, dl, 0);
        asm volatile("{\n.reg .pred p;\n.reg .s32 c;\nTL: mov.u32 c, %%globaltimer_lo;\nsub.s32 c, c, %0;\nsetp.lt.s32 p, c, 0;\n@p bra.uni TL;\n}" :: "r"(t) : "memory");
      } else wait_until(dl);
      PROF(10);
#pragma unroll 1
      do {
        load(0);
        if (!LEAD) load(1);
        asm volatile("{\n.reg .pred p;\nsetp.eq.u32 p, %0, 0;\n@p bar.sync 13, 384;\n}" :: "r"(n) : "memory");
      } while (!decode(0, n++));
      PROF(11);
#pragma unroll 1
      while (!decode(1, n++)) load(1);
      bar_arrive(9, 256);
      PROF(12);
    }
    PROF(13);
    if (++s == NSEG - 1) break;
    }
  }
#undef fence_reg
  if (RANK < 2) bar_arrive(4, 256);
  bar_sync(0, 384);
  cluster_sync();
}

__global__ void __cluster_dims__(3, 1, 1) __launch_bounds__(384, 1)
rec_kernel(const __grid_constant__ RMaps tm, const bf16* __restrict__ x, const bf16* __restrict__ mem0) {
  extern __shared__ __align__(1024) unsigned char smem_raw[];
  const uint32_t sb = smem_u32(smem_raw);
  const int tid = threadIdx.x, lane = tid & 31;
  const int wg = __shfl_sync(0xffffffffu, tid >> 7, 0);
  const int w = __shfl_sync(0xffffffffu, (tid >> 5) & 3, 0);
  uint32_t rank; asm("mov.u32 %0, %%cluster_ctarank;" : "=r"(rank));
  STAMP(0);
  asm volatile("griddepcontrol.launch_dependents;" ::: "memory");
    if (tid == 0) {
      const int h = blockIdx.x / 3;
      mbar_init(sb + MB_XS, 1);
      for (int i = 0; i < 3; i++) { mbar_init(sb + MB_W + 8 * i, 1); mbar_init(sb + MB_X + 8 * i, 1); }
      mbar_init(sb + MB_WO3, 1);
      fence_async();
      load_w(sb, tm, rank, 0);
      mbar_expect(sb + MB_X, XT);
      tma_load3(sb + SM_X, &tm.x, 0, sb + MB_X);
      if (WPOS == 2) load_w(sb, tm, rank, 1);
      mbar_expect(sb + MB_WO3, 32768 + 8 * DM * 2);
      tma_load(sb + SM_WOST, &tm.wo, rank * 192 + 64, h * DH, sb + MB_WO3);
      tma_load(sb + SM_WO3, &tm.wo, rank * 192 + 128, h * DH, sb + MB_WO3);
      bulk_load(sb + SM_M0, mem0, 8 * DM * 2, sb + MB_WO3);
      if (WOPF) tma_prefetch(&tm.wo, rank * 192, h * DH);
      if (WPOS == 1) load_w(sb, tm, rank, 1);
      load_w(sb, tm, rank, 2);
      mbar_init(sb + MB_WO, 1);
      mbar_init(sb + MB_S, rank < 2 ? 5 : 6);
      mbar_init(sb + MB_F, 1);
      mbar_init(sb + MB_VX, 1); mbar_init(sb + MB_VX + 8, 1);
      asm volatile("fence.mbarrier_init.release.cluster;" ::: "memory");
      fence_async();
      mbar_expect(sb + MB_X + 8, XT); mbar_expect(sb + MB_X + 16, XT);
      mbar_expect(sb + MB_WO, 16384); mbar_expect(sb + MB_XS, XT);
      mbar_expect(sb + MB_S, rank < 2 ? 640 + 2048 : 1280);
      mbar_expect(sb + MB_VX, 8192); mbar_expect(sb + MB_VX + 8, 8192);
    }
  __syncwarp();
  if (wg < 2) {
    asm volatile("setmaxnreg.inc.sync.aligned.u32 192;");
    __syncwarp();
    QSTAMP(0);
    if (tid < 32) bar_arrive(0, 160);
    QSTAMP(1);
    proj_role(sb, tm, x, rank, wg, w, lane);
  } else {
    asm volatile("setmaxnreg.dec.sync.aligned.u32 120;");
    attn_role(sb, smem_raw, tm, rank, x, mem0, w, lane);
  }
}

constexpr int NAUX = 36;
constexpr int A_ST = 6, A_STAGE = 8192 + 12288, A_W8 = A_ST * A_STAGE, A_EXC = A_W8 + A_ST * 1536, A_ROWS = 57;
constexpr int A_IN = A_EXC + 8 * 2304, A_INB = 3 * SEGB, A_OST = A_IN + 2 * A_INB, A_P = A_OST + 8192, A_G = A_P + 3072;
constexpr int A_BAR = A_G + 1024;
constexpr int A_XT = A_BAR + 1024, A_XW = A_XT;
constexpr int A_TOTAL = A_XT + 4096;
static_assert(A_IN % 1024 == 0 && A_XT % 1024 == 0 && A_IN >= 4 * XT && A_IN + 64 * DM * 2 <= A_BAR && A_TOTAL <= 232448, "side kernel shared memory");
struct AMaps { CUtensorMap x, wa, wa8, o, o3, o16, wob, woa, woa16; const unsigned char* red; uint32_t poll; };

DI void wgmma_n192_ss_nt(float* d, uint64_t da, uint64_t db, int acc) {
  asm volatile("{\n.reg .pred p;\nsetp.ne.b32 p, %98, 0;\n"
               "wgmma.mma_async.sync.aligned.m64n192k16.f32.bf16.bf16 {"
               "%0,%1,%2,%3,%4,%5,%6,%7,%8,%9,%10,%11,%12,%13,%14,%15,%16,%17,%18,%19,%20,%21,%22,%23,%24,%25,%26,%27,%28,%29,%30,%31,"
               "%32,%33,%34,%35,%36,%37,%38,%39,%40,%41,%42,%43,%44,%45,%46,%47,%48,%49,%50,%51,%52,%53,%54,%55,%56,%57,%58,%59,%60,%61,%62,%63,"
               "%64,%65,%66,%67,%68,%69,%70,%71,%72,%73,%74,%75,%76,%77,%78,%79,%80,%81,%82,%83,%84,%85,%86,%87,%88,%89,%90,%91,%92,%93,%94,%95"
               "}, %96, %97, p, 1, 1, 0, 1;\n}\n"
               : ACC8(d, 0), ACC8(d, 8), ACC8(d, 16), ACC8(d, 24), ACC8(d, 32), ACC8(d, 40), ACC8(d, 48), ACC8(d, 56),
                 ACC8(d, 64), ACC8(d, 72), ACC8(d, 80), ACC8(d, 88) : "l"(da), "l"(db), "r"(acc));
}
DI void wgmma_n24_ss_nt(float* d, uint64_t da, uint64_t db, int acc) {
  asm volatile("{\n.reg .pred p;\nsetp.ne.b32 p, %14, 0;\n"
               "wgmma.mma_async.sync.aligned.m64n24k16.f32.bf16.bf16 {%0,%1,%2,%3,%4,%5,%6,%7,%8,%9,%10,%11}, %12, %13, p, 1, 1, 0, 1;\n}\n"
               : ACC8(d, 0), "+f"(d[8]), "+f"(d[9]), "+f"(d[10]), "+f"(d[11]) : "l"(da), "l"(db), "r"(acc));
}
DI void tma_load3d(uint32_t dst, const CUtensorMap* m, int c0, int c1, int c2, uint32_t mb) {
  asm volatile("cp.async.bulk.tensor.3d.shared::cluster.global.mbarrier::complete_tx::bytes [%0], [%1, {%3, %4, %5}], [%2];"
               :: "r"(dst), "l"(m), "r"(mb), "r"(c0), "r"(c1), "r"(c2) : "memory");
}
DI uint32_t trans8(uint32_t x) { uint32_t r; asm("movmatrix.sync.aligned.m8n8.trans.b16 %0, %1;" : "=r"(r) : "r"(x)); return r; }
DI void wgmma_n40_ss(float* d, uint64_t da, uint64_t db, int acc) {
  asm volatile("{\n.reg .pred p;\nsetp.ne.b32 p, %22, 0;\n"
               "wgmma.mma_async.sync.aligned.m64n40k16.f32.bf16.bf16 {%0,%1,%2,%3,%4,%5,%6,%7,%8,%9,%10,%11,%12,%13,%14,%15,%16,%17,%18,%19}, "
               "%20, %21, p, 1, 1, 1, 1;\n}\n"
               : ACC8(d, 0), ACC8(d, 8), "+f"(d[16]), "+f"(d[17]), "+f"(d[18]), "+f"(d[19]) : "l"(da), "l"(db), "r"(acc));
}
DI uint2 ldg_relaxed64(const void* p) {
  uint2 v; asm volatile("ld.relaxed.gpu.global.v2.b32 {%0,%1}, [%2];" : "=r"(v.x), "=r"(v.y) : "l"(p) : "memory"); return v;
}
template <int ST> DI void ldg8x64(uint32_t* m, const void* p) {
  asm volatile("ld.relaxed.gpu.global.v2.b32 {%0,%1}, [%16];\nld.relaxed.gpu.global.v2.b32 {%2,%3}, [%16 + %17];\n"
               "ld.relaxed.gpu.global.v2.b32 {%4,%5}, [%16 + %18];\nld.relaxed.gpu.global.v2.b32 {%6,%7}, [%16 + %19];\n"
               "ld.relaxed.gpu.global.v2.b32 {%8,%9}, [%16 + %20];\nld.relaxed.gpu.global.v2.b32 {%10,%11}, [%16 + %21];\n"
               "ld.relaxed.gpu.global.v2.b32 {%12,%13}, [%16 + %22];\nld.relaxed.gpu.global.v2.b32 {%14,%15}, [%16 + %23];"
               : "=r"(m[0]), "=r"(m[1]), "=r"(m[2]), "=r"(m[3]), "=r"(m[4]), "=r"(m[5]), "=r"(m[6]), "=r"(m[7]),
                 "=r"(m[8]), "=r"(m[9]), "=r"(m[10]), "=r"(m[11]), "=r"(m[12]), "=r"(m[13]), "=r"(m[14]), "=r"(m[15])
               : "l"(p), "n"(ST), "n"(2 * ST), "n"(3 * ST), "n"(4 * ST), "n"(5 * ST), "n"(6 * ST), "n"(7 * ST) : "memory");
}
template <int ST> DI void ldg4x128(uint32_t* m, const void* p) {
  asm volatile("ld.relaxed.gpu.global.v4.b32 {%0,%1,%2,%3}, [%16];\nld.relaxed.gpu.global.v4.b32 {%4,%5,%6,%7}, [%16 + %17];\n"
               "ld.relaxed.gpu.global.v4.b32 {%8,%9,%10,%11}, [%16 + %18];\nld.relaxed.gpu.global.v4.b32 {%12,%13,%14,%15}, [%16 + %19];"
               : "=r"(m[0]), "=r"(m[1]), "=r"(m[2]), "=r"(m[3]), "=r"(m[4]), "=r"(m[5]), "=r"(m[6]), "=r"(m[7]),
                 "=r"(m[8]), "=r"(m[9]), "=r"(m[10]), "=r"(m[11]), "=r"(m[12]), "=r"(m[13]), "=r"(m[14]), "=r"(m[15])
               : "l"(p), "n"(ST), "n"(2 * ST), "n"(3 * ST) : "memory");
}
template <int N, int ST> DI bool stale(const uint32_t* m, uint32_t tag) {
  uint32_t x = m[0] ^ tag;
#pragma unroll
  for (int i = 1; i < N; i++) asm("lop3.b32 %0, %0, %1, %2, 0xf6;" : "+r"(x) : "r"(m[i * ST]), "r"(tag));
  return __any_sync(0xffffffffu, x & 1);
}
DI bool mbar_test(uint32_t b, uint32_t par) {
  uint32_t r; asm volatile("{\n.reg .pred p;\nmbarrier.test_wait.parity.shared::cta.b64 p, [%1], %2;\nselp.u32 %0, 1, 0, p;\n}" : "=r"(r) : "r"(b), "r"(par) : "memory");
  return r;
}
DI int wait_flags(const unsigned* p, bool active, unsigned base, int seg) {
  int n = 0, m;
  while (true) {
    m = __reduce_min_sync(0xffffffffu, active ? (int)(ldg_acquire32(p) - base) : NSEG);
    if (m > seg || ++n > SPIN_LIMIT) break;
    __nanosleep((YP & 32) ? 400 : 40);
  }
  return max(m, seg + 1);
}
DI void wait_count(const unsigned* p, unsigned target) {
  int n = 0;
  unsigned v;
  while (true) {
    asm volatile("ld.acquire.gpu.global.b32 %0, [%1];" : "=r"(v) : "l"(p) : "memory");
    if ((int)(v - target) >= 0 || ++n > SPIN_LIMIT) break;
    __nanosleep(64);
  }
}
#define PACE_NEXT 800
#define AWARM 0
#define WPF 3
#define UNP 64
#define ADLY 0
#define ODLY 100
#define SDLY 0
#define RSL 100
#define TWO 0
#define ALLW 1
#define AE 0
#define PING 60
#define FLAG 2
#define FPOS 1
#define QB 1
#define Q_LO 0
#define Q_HI 320
DI bool tick_wait(uint32_t pace, int step) {
  const int n = lds32v(pace);
  if (n <= step) mbar_wait(pace + 8, n & 1);
  return n <= step;
}
DI void quiet_wait(uint32_t pace) {
  uint32_t n, d;
  asm volatile("ld.volatile.shared.v2.b32 {%0,%1}, [%2];" : "=r"(n), "=r"(d) : "r"(pace) : "memory");
  if (n - 1 < NSEG - 2 && (int)(gtime() - d) > Q_HI) mbar_wait(pace + 8, n & 1);
}
DI void sleep_until(uint32_t t) {
  for (int n = 0; n < 64; n++) {
    const int r = t - gtime();
    if (r <= 0) break;
    __nanosleep(r >> 1);
  }
}
DI void aux_barrier(int i, unsigned epoch, bool wait = true) {
  asm volatile("fence.proxy.async;" ::: "memory");
  asm volatile("red.release.gpu.global.add.u32 [%0], 1;" :: "l"(&g_abar[i * 32]) : "memory");
  if (!wait) return;
  wait_count(&g_abar[i * 32], NAUX * (epoch + 1));
  asm volatile("fence.proxy.async;" ::: "memory");
}

__global__ void __launch_bounds__(512, 1)
aux_kernel(const __grid_constant__ AMaps tm, const bf16* __restrict__ x, const bf16* __restrict__ gate_w, bf16* __restrict__ out) {
  extern __shared__ __align__(1024) unsigned char smem_raw[];
  const uint32_t sb = smem_u32(smem_raw);
  const uint32_t full1 = sb + A_BAR, empty1 = full1 + 8 * A_ST, fullw = empty1 + 8 * A_ST, full3 = fullw + 16, empty3 = full3 + 32,
                 fulla = empty3 + 32, emptya = fulla + 32, fullg = emptya + 16, pace = fullg + 8;
  const int tid = threadIdx.x, lane = tid & 31, cta = blockIdx.x;
  const int wg = __shfl_sync(0xffffffffu, tid >> 7, 0), w = __shfl_sync(0xffffffffu, (tid >> 5) & 3, 0);
  ASTAMP(14);
  const unsigned epoch = *(volatile unsigned*)&g_epoch2;
  if (tid == 0) {
    for (int i = 0; i < A_ST; i++) { mbar_init(full1 + 8 * i, 1); mbar_init(empty1 + 8 * i, 8); }
    mbar_init(fullw, 1); mbar_init(fullw + 8, 1); mbar_init(fullg, 1);
    for (int i = 0; i < 2; i++) { mbar_init(fulla + 16 * i, 2); mbar_init(fulla + 16 * i + 8, 1); mbar_init(emptya + 8 * i, 4); }
    sts64(pace, 0, 0); mbar_init(pace + 8, 1); sts32(pace + 16, 0); sts64(pace + 24, 65536, 0xffff0000u);
    for (int i = 0; i < 4; i++) { mbar_init(full3 + 8 * i, 1); mbar_init(empty3 + 8 * i, cta < NH ? 8 : 4); }
    fence_async();
  }
  auto load_a = [&](int st, int k, int col) {
    mbar_expect(full1 + 8 * st, A_STAGE + 1536);
    tma_load3d(sb + st * A_STAGE, &tm.x, k, (cta >> 1) * A_ROWS - 7, 0, full1 + 8 * st);
    tma_load3d(sb + st * A_STAGE + 8192, &tm.wa, col, k, 0, full1 + 8 * st);
    tma_load3d(sb + A_W8 + st * 1536, &tm.wa8, col + 64, k, 0, full1 + 8 * st);
  };
  if (AE && tid < 32 && !(XP & 256)) {
    __syncwarp();
#pragma unroll 1
    for (int st = 0; st < A_ST; st++) if (elect_one()) load_a(st, st * 32, (cta & 1) * (DM / 2));
  }
  __syncthreads();
  ASTAMP(0);
  const bool wide = cta < NH;
  auto p3_ks = [&](int g) { return wide ? cta >> 2 : 2 * (cta - NH) + g; };
  auto p3_mt = [&](int g) { return wide ? 2 * (cta & 3) + g : 8; };
  const unsigned fbase = epoch * NSEG;
  if (wg == 3) {
    asm volatile("setmaxnreg.dec.sync.aligned.u32 %0;" :: "n"(TWO ? 32 : 48));
    if (w == 1 && cta < NH) {
#pragma unroll 1
      for (int seg = 0; seg < ((XP & 2048) ? 0 : NSEG); seg++) {
        bar_arrive(5, 160);
        if (seg > 0 && lane == 0) {
          asm volatile("cp.async.bulk.wait_group 0;" ::: "memory");
          stg_relaxed32(&g_oflag[cta * 32], fbase + seg);
        }
        if (lane < 3) stg_relaxed32(&g_cflag[(cta * 3 + lane) * 32], fbase + seg);
        __syncwarp();
        bar_sync(4, 160);
        if (QM & 16) tick_wait(pace, seg + 1);
        if (lane == 0) {
          fence_async();
          if (!(YP & 2)) {
          tma_store(&tm.o, sb + A_OST, cta * DH, seg * 32);
          tma_store(&tm.o, sb + A_OST + 4096, cta * DH + 64, seg * 32);
          }
          asm volatile("cp.async.bulk.commit_group;" ::: "memory");
          asm volatile("cp.async.bulk.wait_group.read 0;" ::: "memory");
        }
        __syncwarp();
      }
      if (lane == 0) {
        asm volatile("cp.async.bulk.wait_group 0;" ::: "memory");
        { const int seg = NSEG - 1; TSTAMP(2); }
        stg_relaxed32(&g_oflag[cta * 32], fbase + NSEG);
      }
    }
    if (w == 2 && cta < NH) {
      const uint32_t ktag = (epoch + 1) & 1, ma = sb + A_IN + 8192 + lane * 16;
      int avail = 0;
      int own = 0;
      bar_sync(10, 64);
#pragma unroll 1
      for (int seg = 0; seg < ((XP & 2048) ? 0 : NSEG); seg++) {
        if (avail <= seg) {
          int n = 0;
          while (true) {
            asm volatile("ld.acquire.gpu.global.v2.b32 {%0,%1}, [%2];" : "=r"(avail), "=r"(own) : "l"(&g_sflag[(cta * 3 + min(lane, 2)) * 4]) : "memory");
            avail = __reduce_min_sync(0xffffffffu, (int)(avail - fbase));
            if (avail > seg || ++n > SPIN_LIMIT) break;
            __nanosleep(40);
          }
        }
        if ((QM & 8) && seg < UNP) tick_wait(pace, seg);
        TSTAMP(0);
        const unsigned char* km = g_km + (size_t)(seg * NH + cta) * 4096 + lane * 8;
        uint32_t m[16];
        const float g = __ldcg(&g_gate[seg * 32 + lane]);
        ldg8x64<256>(m, km);
        const uint32_t b = seg & 1, full = fulla + 16 * b, mb = ma + b * A_INB;
        mbar_wait(emptya + 8 * b, (~seg >> 1) & 1);
        if (lane < 2) mbar_expect(full + 8 * lane, (YP & 8) ? 0 : 16384 >> lane);
        __syncwarp();
        const int slot = seg < own ? seg & 7 : seg;
        if (lane < 3 && !(YP & 8)) bulk_load(sb + A_IN + b * A_INB + lane * SEGB, g_seg + ((size_t)slot * 96 + cta * 3 + lane) * 8192, 8192, full + (lane & 2) * 4);
        int n = 0;
#pragma unroll 1
        while (stale<8, 2>(m, ktag) && ++n < SPIN_LIMIT) { if (seg < UNP - 1) __nanosleep(200); ldg8x64<256>(m, km); }
        TSTAMP(1);
#pragma unroll
        for (int i = 0; i < 4; i++) stsm4(mb + (i >> 1) * SEGB + (i & 1) * 512, m[4 * i], m[4 * i + 1], m[4 * i + 2], m[4 * i + 3]);
        sts32(sb + A_G + b * 128 + lane * 4, __float_as_uint(1.f - g));
        fence_async();
        __syncwarp();
        if (lane == 0) mbar_arrive(full);
      }
    }
    if (w == 3 && QM) {
      const unsigned char* const hp = tm.red + HINT_OFF + 65536 + (cta & 1) * 4096 + min(lane, 23) * 4;
      uint32_t d = 0;
      int s = 0, n = 0;
#pragma unroll 1
      while (s < NSEG - 1) {
        const uint32_t h = ldg_relaxed32(hp + RED_SLOT(s)), t = (gtime() - 1984) & ~31u, late = latest_hint(h, t, s);
        if (late < 64) {
          d = t + late * 32 + tm.poll + Q_LO;
          sleep_until(d);
          s++; n = 0;
          if (lane == 0) { mbar_arrive(pace + 8); sts64(pace, s < NSEG - 1 ? s : 2 * NSEG, d); }
          sleep_until(d + PACE_NEXT);
        } else {
          if (++n > (s ? 16 : 256) || lds32v(pace + 16)) break;
          if (!s) __nanosleep(100);
        }
      }
      if (s < NSEG - 1 && lane == 0) { mbar_arrive(pace + 8); sts64(pace, 2 * NSEG, d); }
    }
    if (w != 0) return;
    const bool lead = lane == 0;
#pragma unroll 1
    for (int it = AE * A_ST, st = 0, ph = !AE, k = AE * A_ST * 32, col = (cta & 1) * (DM / 2); it < ((XP & 256) ? 0 : 72); it++) {
      mbar_wait(empty1 + 8 * st, ph);
      if (QM & 1) quiet_wait(pace);
      if (elect_one()) load_a(st, k, col);
      __syncwarp();
      if (++st == A_ST) { st = 0; ph ^= 1; }
      k += 32;
      if (k == DM) { k = 0; col += 72; }
    }
    auto load_wo = [&](uint32_t dst, int g, int kb, uint32_t mb) {
      if (kb < 64) tma_load(dst, &tm.wob, p3_mt(g) * 64, kb * 64, mb);
      else tma_load(dst, &tm.woa, p3_mt(g) * 64, (kb - 64) * 64, mb);
    };
    if (lead) mbar_expect(fullw, 16 * 8192);
#pragma unroll 1
    for (int st = 0; st < A_ST; st++) {
      if (!(XP & 256)) mbar_wait(empty1 + 8 * st, 1);
      if (lane < 16 && min(((lane + 1) * 8192 - 1) / A_STAGE, A_ST - 1) == st) load_wo(sb + lane * 8192, lane >> 3, p3_ks(lane >> 3) * 9 + (lane & 7), fullw);
      __syncwarp();
    }
    __syncwarp(); bar_sync(6, 288);
    if (lead) mbar_expect(fullw + 8, 2 * 8192 + (p3_ks(0) >= 4 ? 4096 : 0));
    __syncwarp();
    if (lane < 2) {
      load_wo(sb + (16 + lane) * 8192, lane, p3_ks(lane) * 9 + 8, fullw + 8);
      if (p3_ks(0) >= 4) tma_load(sb + A_XW + lane * 2048, &tm.woa16, p3_mt(lane) * 64, 448 + p3_ks(lane) * 16, fullw + 8);
    }
    __syncwarp();
    if (lead) aux_barrier(1, epoch, ALLW || p3_ks(0) >= 4);
    __syncwarp(); bar_sync(6, 288);
    {
      int avail = 0, sl = 0, ph = 1;
      const int h = (9 * p3_ks(0) >> 1) + lane;
#pragma unroll 1
      for (int seg = 0; seg < ((XP & 2048) ? 0 : NSEG); seg++) {
        if (avail <= seg) avail = wait_flags(&g_oflag[min(h, NH - 1) * 32], lane < (wide ? 5 : 9), fbase, seg);
        SSTAMP(seg, 4);
        for (int g = 0; g < (wide ? 1 : 2); g++) {
          const int ks = p3_ks(g);
          mbar_wait(empty3 + 8 * sl, ph);
          if ((QM & 4) && tick_wait(pace, seg + (QM >> 4 & 1) + 1) && ODLY) __nanosleep(ODLY);
          if (YP & 4) { if (lead) mbar_arrive(full3 + 8 * sl); }
          else if (elect_one()) {
            mbar_expect(full3 + 8 * sl, XT + (ks >= 4 ? 1024 : 0));
            tma_load3d(sb + sl * XT, &tm.o3, 0, seg * 32, ks * 9, full3 + 8 * sl);
            if (ks >= 4) tma_load(sb + A_XT + sl * 1024, &tm.o16, 72 * 64 - 64 + ks * 16, seg * 32, full3 + 8 * sl);
          }
          __syncwarp();
          if (++sl == (wide ? 3 : 4)) { sl = 0; ph ^= 1; }
        }
      }
    }
    sts32(pace + 16, 1);
    __syncwarp(); bar_sync(6, 288);
    asm volatile("griddepcontrol.wait;" ::: "memory");
  } else if (wg == 2) {
    asm volatile("setmaxnreg.dec.sync.aligned.u32 64;");
    if (cta < NH) {
      if (tid == 256) { mbar_expect(fullg, 64 * DM * 2); bulk_load(sb + A_IN, x + cta * 64 * DM, 64 * DM * 2, fullg); }
      uint32_t gw[9];
#pragma unroll
      for (int j = 0; j < 9; j++) gw[j] = ((const uint32_t*)gate_w)[j * 32 + lane];
      mbar_wait(fullg, 0);
      float mine = 0.f;
#pragma unroll 4
      for (int u = 0; u < 16; u++) {
        float d0 = 0.f, d1 = 0.f;
#pragma unroll
        for (int j = 0; j < 9; j++) {
          const uint32_t a = lds32(sb + A_IN + (w * 16 + u) * (DM * 2) + j * 128 + lane * 4);
          d0 = fmaf(bf_lo(a), bf_lo(gw[j]), d0); d1 = fmaf(bf_hi(a), bf_hi(gw[j]), d1);
        }
        d0 = warp_sum(d0 + d1);
        if (lane == u) mine = d0;
      }
      if (lane < 16) g_gate[cta * 64 + w * 16 + lane] = 1.f / (1.f + __expf(-mine));
      fence_async();
    }
    bar_sync(3, 128);
    if (tid == 256) { aux_barrier(0, epoch); if (cta == 0) *(volatile unsigned*)&g_epoch2 = epoch + 1; }
    __syncwarp();
    bar_sync(3, 128);
    if (w == 0) bar_arrive(8, 288);
    if (w == 1 && cta < NH) bar_arrive(10, 64);
    if (cta < NH) {
      CDECL;
#pragma unroll 1
      for (int seg = 0; seg < ((XP & 2048) ? 0 : NSEG); seg++) {
        CSTAMP(0);
        const uint32_t in = sb + A_IN + (seg & 1) * A_INB;
        const uint64_t qd = make_desc(in, 128, 1024, 0);
        mbar_wait(fulla + 16 * (seg & 1), (seg >> 1) & 1);
        CSTAMP(3);
        SSTAMP(seg, 0);
        float d[2][16];
        {
          float a[20];
          uint32_t vm[16];
          const unsigned char* vp = g_km + (size_t)(seg * NH + cta) * 4096 + 2048 + lane * 16;
          if (w == 3) ldg4x128<512>(vm, vp);
          WG_FENCE();
#pragma unroll
          for (int k = 0; k < ((YP & 16) ? 1 : 8); k++) wgmma_n40_ss(a, qd + ((k >> 2) * SEGB + (k & 3) * 256 >> 4), qd + ((k >> 2) * SEGB + (k & 3) * 256 + 4096 >> 4), k > 0);
          const uint32_t ga = sb + A_G + (seg & 1) * 128 + (w & 1) * 64 + (lane >> 2) * 4;
          const float f0 = __uint_as_float(lds32(ga)), f1 = __uint_as_float(lds32(ga + 32));
          WG_COMMIT();
          WG_WAIT(0);
          CSTAMP(5);
          SSTAMP(seg, 1);
          if (w < 2) {
            const int lim = w * 16 + (lane >> 2) - 2 * (lane & 3);
            float m0 = -3.0e38f, m1 = -3.0e38f;
#pragma unroll
            for (int i = 0; i < 20; i++) {
              a[i] *= SM_SCALE * LOG2E;
              if (i < 16 && (i >> 2) * 8 + (i & 1) - (i & 2) * 4 > lim) a[i] = -1.0e9f * LOG2E;
              if (i & 2) m1 = fmaxf(m1, a[i]); else m0 = fmaxf(m0, a[i]);
            }
#pragma unroll
            for (int o = 1; o < 4; o <<= 1) { m0 = fmaxf(m0, __shfl_xor_sync(0xffffffffu, m0, o)); m1 = fmaxf(m1, __shfl_xor_sync(0xffffffffu, m1, o)); }
            float s0 = 0.f, s1 = 0.f;
#pragma unroll
            for (int i = 0; i < 20; i++) { a[i] = ex2(a[i] - (i & 2 ? m1 : m0)); if (i & 2) s1 += a[i]; else s0 += a[i]; }
#pragma unroll
            for (int o = 1; o < 4; o <<= 1) { s0 += __shfl_xor_sync(0xffffffffu, s0, o); s1 += __shfl_xor_sync(0xffffffffu, s1, o); }
            s0 = f0 * rcp(s0); s1 = f1 * rcp(s1);
            uint32_t p[10];
#pragma unroll
            for (int i = 0; i < 10; i++) p[i] = pack_bf16(a[2 * i] * (i & 1 ? s1 : s0), a[2 * i + 1] * (i & 1 ? s1 : s0));
            const uint32_t pa = sb + A_P + (2 * w + ((lane >> 3) & 1)) * 768 + (lane >> 4) * 128 + (lane & 7) * 16;
            stsm4t(pa, p[0], p[1], p[2], p[3]); stsm4t(pa + 256, p[4], p[5], p[6], p[7]); stsm4t(pa + 512, p[8], p[9], 0, 0);
            CSTAMP(6);
            fence_async();
            CSTAMP(7);
          } else if (w == 3) {
            int n = 0;
#pragma unroll 1
            while (stale<4, 4>(vm, (epoch + 1) & 1) && ++n < SPIN_LIMIT) ldg4x128<512>(vm, vp);
#pragma unroll
            for (int i = 0; i < 4; i++) stsm4(in + 2 * SEGB + 8192 + (lane >> 4) * 1024 + (lane & 15) * 16 + i * 256, vm[4 * i], vm[4 * i + 1], vm[4 * i + 2], vm[4 * i + 3]);
            fence_async();
            mbar_wait(fulla + 16 * (seg & 1) + 8, (seg >> 1) & 1);
          }
        }
        CSTAMP(8);

        bar_sync(5, 160);
        CSTAMP(10);
        SSTAMP(seg, 2);
        const uint64_t pd = make_desc(sb + A_P, 128, 768, 0), vd = make_desc(in + 2 * SEGB, 128, 512, 0), md = make_desc(in + 2 * SEGB + 8192, 0, 128, 0);
        WG_FENCE();
#pragma unroll
        for (int i = 0; i < 2; i++) {
          wgmma_n32_ss<0>(d[i], vd + i * 256, pd, 0);
          wgmma_n32_ss<0>(d[i], vd + i * 256 + 16, pd + 16, 1);
          wgmma_n32_ss<0>(d[i], md + i * 64, pd + 32, 1);
        }
        WG_COMMIT();
        WG_WAIT(0);
        CSTAMP(11);
        if (lane == 0) mbar_arrive(emptya + 8 * (seg & 1));
#pragma unroll
        for (int i = 0; i < 2; i++) {
          const uint32_t oa = sb + A_OST + i * 4096 + ((lane & 7) + ((lane >> 4) << 3)) * 128 + (((2 * w + ((lane >> 3) & 1)) ^ (lane & 7)) << 4);
          stsm4t(oa, pack_bf16(d[i][0], d[i][1]), pack_bf16(d[i][2], d[i][3]), pack_bf16(d[i][4], d[i][5]), pack_bf16(d[i][6], d[i][7]));
          stsm4t(oa + 2048, pack_bf16(d[i][8], d[i][9]), pack_bf16(d[i][10], d[i][11]), pack_bf16(d[i][12], d[i][13]), pack_bf16(d[i][14], d[i][15]));
        }
        CSTAMP(12);
        bar_sync(4, 160);
        SSTAMP(seg, 3);
      }
      CDUMP;
    }
  } else {
    asm volatile("setmaxnreg.inc.sync.aligned.u32 %0;" :: "n"(TWO ? 208 : 200));
    {
      const int g = lane >> 2, t = lane & 3, r0 = (cta >> 1) * A_ROWS - 7 + w * 16;
      const uint32_t prev = (2 * t > g ? 0xffffu : 0u) | (2 * t + 1 > g ? 0xffff0000u : 0u);
      const int k0 = r0 + 2 * t - (2 * t > g ? 8 : 0), k1 = r0 + 2 * t + 1 - (2 * t + 1 > g ? 8 : 0);
      const uint32_t slot = sb + A_EXC + (wg * 4 + w) * 2304;
      float gl = 0.f, gh = 0.f;
      int st = 0, ph = 0;
#pragma unroll 1
      for (int p = -AWARM; p < ((XP & 256) ? 0 : 4); p++) {
        float big[96], sml[12];
        if (p == WPF && tid < 18) {
          const int kb = p3_ks(tid >= 9) * 9 + tid % 9;
          tma_prefetch(kb < 64 ? &tm.wob : &tm.woa, p3_mt(tid >= 9) * 64, (kb & 63) * 64);
        }
        __syncwarp();
#pragma unroll
        for (int i = 0; i < 96; i++) big[i] = 0.f;
#pragma unroll
        for (int i = 0; i < 12; i++) sml[i] = 0.f;
#pragma unroll 1
        for (int k = p < 0 ? 18 : 0; k < 18; k++) {
          mbar_wait(full1 + 8 * st, ph);
          const uint64_t da = make_desc(sb + st * A_STAGE + wg * 4096, 16, 512, 2);
          const uint64_t db = make_desc(sb + st * A_STAGE + 8192, 4096, 1024, 1), dc = make_desc(sb + A_W8 + st * 1536, 128, 512, 0);
          WG_FENCE();
#pragma unroll
          for (int j = 0; j < 2; j++) { wgmma_n192_ss_nt(big, da + j * 2, db + j * 128, 1); wgmma_n24_ss_nt(sml, da + j * 2, dc + j * 16, 1); }
          WG_COMMIT();
          WG_WAIT(1);
          if (k > 0 && lane == 0) mbar_arrive(empty1 + 8 * (st ? st - 1 : A_ST - 1));
          if (++st == A_ST) { st = 0; ph ^= 1; }
        }
        WG_WAIT(0);
        ASTAMP(16 + max(p, 0) + wg * 16);
        if (lane == 0 && p >= 0) mbar_arrive(empty1 + 8 * (st ? st - 1 : A_ST - 1));
        uint32_t f[3][9][2];
#pragma unroll
        for (int c = 0; c < 3; c++)
#pragma unroll
          for (int j = 0; j < 9; j++)
#pragma unroll
            for (int i = 0; i < 2; i++) {
              const float* a = j < 8 ? &big[(c * 8 + j) * 4 + 2 * i] : &sml[c * 4 + 2 * i];
              f[c][j][i] = c < 2 ? pack_bf16(a[0], a[1]) : trans8(pack_bf16(a[0], a[1]));
            }
        if (p == 0) {
          bar_sync(8, 288);
          gl = __ldcg(&g_gate[min(max(r0 + g, 0), S_LEN / 2 - 1) * 2 + wg]); gh = __ldcg(&g_gate[min(max(r0 + g + 8, 0), S_LEN / 2 - 1) * 2 + wg]);
        }
        asm volatile("cp.async.bulk.wait_group.read 0;" ::: "memory");
        __syncwarp();
#pragma unroll
        for (int j = 0; j < 8; j += 2) sts128(slot + j * 256 + lane * 16, f[1][j][1], f[2][j][1], f[1][j + 1][1], f[2][j + 1][1]);
        sts64(slot + 2048 + lane * 8, f[1][8][1], f[2][8][1]);
        bar_sync(1 + wg, 128);
        ASTAMP(24 + max(p, 0) + wg * 16);
        uint32_t pv[9][2];
#pragma unroll
        for (int j = 0; j < 9; j++) pv[j][0] = pv[j][1] = 0;
        if (w) {
#pragma unroll
          for (int j = 0; j < 8; j += 2) lds128(slot - 2304 + j * 256 + lane * 16, pv[j]);
          lds64(slot - 256 + lane * 8, pv[8][0], pv[8][1]);
        }
        float a[4][4], m[4][2];
#pragma unroll
        for (int h = 0; h < 4; h++) {
          const int j = 2 * h;
          const uint32_t qa[4] = {t >= h ? f[0][j][0] : 0, t >= h ? f[0][j][1] : 0, f[0][j + 1][0], f[0][j + 1][1]};
          const uint32_t qb0 = t <= h ? f[0][j + 2][0] : 0, qb1 = t <= h ? f[0][j + 2][1] : 0;
          float s0[4], s1[4], s2[4];
          mma16816z(s1, qa, f[1][j][0], f[1][j + 1][0]); mma16816z(s2, qa, f[1][j][1], f[1][j + 1][1]); mma16816z(s0, qa, pv[j][0], pv[j + 1][0]);
          mma1688(s1, qb0, qb1, f[1][j + 2][0]); mma1688(s2, qb0, qb1, f[1][j + 2][1]); mma1688(s0, qb0, qb1, pv[j + 2][0]);
          a[h][0] = 2 * t > g ? s0[0] : s1[0]; a[h][1] = 2 * t + 1 > g ? s0[1] : s1[1]; a[h][2] = 2 * t > g ? s1[2] : s2[2]; a[h][3] = 2 * t + 1 > g ? s1[3] : s2[3];
        }
#pragma unroll
        for (int h = 0; h < 4; h++) {
#pragma unroll
          for (int i = 0; i < 4; i++) a[h][i] = (i & 1 ? k1 : k0) + (i & 2) * 4 >= 0 ? a[h][i] * (0.23570226039551584f * LOG2E) : -1.0e9f * LOG2E;
          m[h][0] = fmaxf(a[h][0], a[h][1]); m[h][1] = fmaxf(a[h][2], a[h][3]);
        }
#pragma unroll
        for (int x = 1; x < 4; x <<= 1)
#pragma unroll
          for (int i = 0; i < 8; i++) m[i >> 1][i & 1] = fmaxf(m[i >> 1][i & 1], __shfl_xor_sync(0xffffffffu, m[i >> 1][i & 1], x));
#pragma unroll
        for (int h = 0; h < 4; h++) {
#pragma unroll
          for (int i = 0; i < 4; i++) a[h][i] = ex2(a[h][i] - m[h][i >> 1]);
          m[h][0] = a[h][0] + a[h][1]; m[h][1] = a[h][2] + a[h][3];
        }
#pragma unroll
        for (int x = 1; x < 4; x <<= 1)
#pragma unroll
          for (int i = 0; i < 8; i++) m[i >> 1][i & 1] += __shfl_xor_sync(0xffffffffu, m[i >> 1][i & 1], x);
        uint32_t o[9][2];
#pragma unroll
        for (int h = 0; h < 4; h++) {
          const int j = 2 * h;
          const float z0 = gl * rcp(m[h][0]), z1 = gh * rcp(m[h][1]);
          const uint32_t pl = pack_bf16(a[h][0] * z0, a[h][1] * z0), pu = pack_bf16(a[h][2] * z1, a[h][3] * z1);
          const uint32_t pa[4] = {pl & prev, 0, pl & ~prev, pu & prev};
          float d[3][4];
#pragma unroll
          for (int i = 0; i < 3; i++) mma16816z(d[i], pa, pv[j + i][1], f[2][j + i][0]);
#pragma unroll
          for (int i = 0; i < 3; i++) mma1688(d[i], 0, pu & ~prev, f[2][j + i][1]);
#pragma unroll
          for (int i = 0; i < 3; i++) {
            const uint32_t d0 = pack_bf16(d[i][0], d[i][1]), d1 = pack_bf16(d[i][2], d[i][3]);
            o[j + i][0] = i == 0 && h > 0 && t < h ? o[j][0] : d0;
            o[j + i][1] = i == 0 && h > 0 && t < h ? o[j][1] : d1;
          }
        }
        ASTAMP(28 + max(p, 0) + wg * 16);
        bar_sync(1 + wg, 128);
        const uint32_t oa = slot + (lane & 15) * 144 + (lane >> 4) * 16;
#pragma unroll
        for (int j = 0; j < 8; j += 2) stsm4(oa + j * 16, o[j][0], o[j][1], o[j + 1][0], o[j + 1][1]);
        asm volatile("stmatrix.sync.aligned.m8n8.x2.shared.b16 [%0], {%1,%2};" :: "r"(oa + 128), "r"(o[8][0]), "r"(o[8][1]) : "memory");
        fence_async();
        __syncwarp();
        if (QM & 64) quiet_wait(pace);
        if (lane < 16 && w * 16 + lane >= 7 && r0 + lane < S_LEN / 2 && p >= 0)
          asm volatile("cp.async.bulk.global.shared::cta.bulk_group [%0], [%1], 144;"
                       :: "l"(g_Ocat + (size_t)((r0 + lane) * 2 + wg) * KCAT + 4096 + (cta & 1) * (DM / 2) + p * 72), "r"(slot + lane * 144) : "memory");
        asm volatile("cp.async.bulk.commit_group;" ::: "memory");
        ASTAMP(20 + max(p, 0) + wg * 16);
      }
      if (XP & 256) bar_sync(8, 288);
      asm volatile("cp.async.bulk.wait_group 0;" ::: "memory");
    }
    ASTAMP(3);
    bar_arrive(6, 288);
    uint32_t wa[37][4];
    mbar_wait(fullw, 0);
    const uint32_t la = sb + ((lane & 7) + ((lane >> 4) << 3)) * 128 + (((2 * w + ((lane >> 3) & 1)) ^ (lane & 7)) << 4);
#pragma unroll
    for (int k = 0; k < 32; k++) ldsm4t(wa[k], la + wg * 65536 + k * 2048);
    mbar_wait(fullw + 8, 0);
#pragma unroll
    for (int k = 32; k < 36; k++) ldsm4t(wa[k], la + wg * 8192 + 65536 + k * 2048);
    ldsm4t(wa[36], la + A_XW + wg * 2048);
    fence_async();
    if (XP & 2048) bar_sync(6, 288); else bar_arrive(6, 288);
    ASTAMP(4);
    const int ks = p3_ks(wg), mt = p3_mt(wg);
    uint32_t v[16];
    auto fetch = [&](int seg) { ldg8x64<1024>(v, g_part + (((seg & 7) * 9 + mt) * 4 + (ks & 3)) * 1024 + (tid & 127)); };
    auto finish = [&](int seg) {
      const uint32_t tagv = (~seg >> 3) & 1;
      int n = 0;
#pragma unroll 1
      while (!(YP & 512) && stale<8, 2>(v, tagv) && ++n < SPIN_LIMIT) {
        if (seg < NSEG - 2) __nanosleep(RSL);
        fetch(seg);
      }
      float own[4] = {bf_lo(v[0]), bf_hi(v[0]), bf_lo(v[1]), bf_hi(v[1])};
#pragma unroll
      for (int j = 1; j < 8; j++) { own[0] += bf_lo(v[2 * j]); own[1] += bf_hi(v[2 * j]); own[2] += bf_lo(v[2 * j + 1]); own[3] += bf_hi(v[2 * j + 1]); }
      uint32_t p0 = pack_bf16(own[0], own[1]), p1 = pack_bf16(own[2], own[3]);
      asm volatile("movmatrix.sync.aligned.m8n8.trans.b16 %0, %0;" : "+r"(p0));
      asm volatile("movmatrix.sync.aligned.m8n8.trans.b16 %0, %0;" : "+r"(p1));
      const uint32_t r2 = __shfl_xor_sync(0xffffffffu, lane & 2 ? p0 : p1, 2);
      if (lane & 2) p0 = r2; else p1 = r2;
      const uint32_t r1 = __shfl_xor_sync(0xffffffffu, lane & 1 ? p0 : p1, 1);
      if (lane & 1) p0 = r1; else p1 = r1;
      if (!(YP & 256) || p0 == 0x12345678)
        *((uint2*)(out + (size_t)(seg * 32 + (ks & 3) * 8 + (lane >> 2)) * DM + mt * 64 + w * 16) + (lane & 3)) = make_uint2(p0, p1);
      SSTAMP(seg, 7);
    };
    float acc[16], acc2[16];
#pragma unroll
    for (int i = 0; i < 16; i++) acc[i] = acc2[i] = 0.f;
    int pend = -1, sl = wide ? 0 : wg, ph = 0;
    if (PING && wg) bar_arrive(1, 256);
    CDECL;
    auto run = [&](auto extra) {
#pragma unroll 1
    for (int seg = 0; seg <= ((XP & 2048) ? -1 : NSEG); seg++) {
      CSTAMP(0);
      const bool fin = pend >= 0 && (seg - pend >= FLAG || seg == NSEG);
      if (seg < NSEG) mbar_wait(full3 + 8 * sl, ph);
      if (FPOS == 1 && fin) fetch(pend);
      if (SDLY) {
        uint32_t n, d;
        asm volatile("ld.volatile.shared.v2.b32 {%0,%1}, [%2];" : "=r"(n), "=r"(d) : "r"(pace) : "memory");
        if ((int)n <= seg + 3) sleep_until(d + SDLY);
      }
      CSTAMP(1);
      if (seg < NSEG) {
      if (wg) SSTAMP(seg, 5);
      if (seg < PING) bar_sync(1 + wg, 256);
      CSTAMP(7);
      const uint64_t db = make_desc(sb + sl * XT, 16, 1024, 1);
      WG_FENCE();
#pragma unroll
      for (int k = 0; k < ((XP & 1024) ? 1 : 36); k++)
        wgmma_n32_rs(TWO && (k & 1) ? acc2 : acc, wa[k][0], wa[k][1], wa[k][2], wa[k][3], db + (k >> 2) * 256 + (k & 3) * 2, k >> TWO);
      if (decltype(extra)::value) wgmma_n32_rs(acc, wa[36][0], wa[36][1], wa[36][2], wa[36][3], make_desc(sb + A_XT + sl * 1024, 16, 256, 3), 1);
      WG_COMMIT();
      if (seg < PING) bar_arrive(2 - wg, 256);
      CSTAMP(2);
      CSTAMP(3);
      WG_WAIT(0);
      CSTAMP(4);
      if (wg) SSTAMP(seg, 6);
      if (lane == 0) mbar_arrive(empty3 + 8 * sl);
      sl += wide ? 1 : 2;
      if (sl >= (wide ? 3 : 4)) { sl -= wide ? 3 : 4; ph ^= 1; }
      uint2* dst = g_part + (((seg & 7) * 9 + mt) * 32 + ks) * 128 + (tid & 127);
      uint32_t q[8];
      if (TWO)
#pragma unroll
        for (int j = 0; j < 16; j++) acc[j] += acc2[j];
#pragma unroll
      for (int j = 0; j < 8; j++) q[j] = j & 1 ? pack_bf16(acc[2 * j], acc[2 * j + 1]) : (pack_bf16(acc[2 * j], acc[2 * j + 1]) & ~1u) | ((~seg >> 3) & 1);
      if (QM & 32) tick_wait(pace, seg + (QM >> 4 & 1) + 2);
      if (!(YP & 1025) || q[0] == 0x12345678)
      asm volatile("st.relaxed.gpu.global.v2.b32 [%0], {%1,%2};\nst.relaxed.gpu.global.v2.b32 [%0 + 8192], {%3,%4};\n"
                   "st.relaxed.gpu.global.v2.b32 [%0 + 16384], {%5,%6};\nst.relaxed.gpu.global.v2.b32 [%0 + 24576], {%7,%8};"
                   :: "l"(dst), "r"(q[0]), "r"(q[1]), "r"(q[2]), "r"(q[3]), "r"(q[4]), "r"(q[5]), "r"(q[6]), "r"(q[7]) : "memory");
      }
      CSTAMP(5);
      if (fin) { finish(pend); pend = -1; }
      CSTAMP(6);
      if ((seg & 1) == ks >> 2 && !(YP & 1)) pend = seg;
      if (wg && (seg & 7) == 6) ASTAMP(5 + (seg >> 3));
    }
    };
    if (ks >= 4) run(BoolC<true>()); else run(BoolC<false>());
    if (PING && !wg) bar_sync(1, 256);
    CDUMP;
    ASTAMP(13);
    bar_sync(6, 288);
  }
}

typedef CUresult (*EncodeFn)(CUtensorMap*, CUtensorMapDataType, cuuint32_t, void*, const cuuint64_t*, const cuuint64_t*,
                             const cuuint32_t*, const cuuint32_t*, CUtensorMapInterleave, CUtensorMapSwizzle,
                             CUtensorMapL2promotion, CUtensorMapFloatOOBfill);
#define PROMO 2
static void make_map(EncodeFn enc, CUtensorMap* m, const void* p, int rows, int cols, int box_rows) {
  cuuint64_t dims[2] = {(cuuint64_t)cols, (cuuint64_t)rows};
  cuuint64_t strides[1] = {(cuuint64_t)cols * 2};
  cuuint32_t box[2] = {64, (cuuint32_t)box_rows};
  cuuint32_t es[2] = {1, 1};
  enc(m, CU_TENSOR_MAP_DATA_TYPE_BFLOAT16, 2, (void*)p, dims, strides, box, es, CU_TENSOR_MAP_INTERLEAVE_NONE,
      CU_TENSOR_MAP_SWIZZLE_128B, (CUtensorMapL2promotion)PROMO, CU_TENSOR_MAP_FLOAT_OOB_FILL_NONE);
}

constexpr int g_poll = POLL_NS;
extern "C" void kernel_launch(void* const* d_in, const int* in_sizes, int n_in, void* d_out, int out_size) {
  const bf16* x = (const bf16*)d_in[0];
  const bf16* wqkvA = (const bf16*)d_in[1];
  const bf16* woA = (const bf16*)d_in[2];
  const bf16* mem0 = (const bf16*)d_in[4];
  const bf16* Wq = (const bf16*)d_in[5];
  const bf16* Wk = (const bf16*)d_in[6];
  const bf16* Wv = (const bf16*)d_in[7];
  const bf16* Wo = (const bf16*)d_in[8];
  const bf16* gate_w = (const bf16*)d_in[10];
  static EncodeFn enc = nullptr;
  static void *pO = nullptr, *pR = nullptr, *pF = nullptr;
  if (!enc) {
    cudaDriverEntryPointQueryResult qr;
    cudaGetDriverEntryPoint("cuTensorMapEncodeTiled", (void**)&enc, cudaEnableDefault, &qr);
    cudaGetSymbolAddress(&pO, g_Ocat);
    cudaGetSymbolAddress(&pR, g_red_raw);
    cudaGetSymbolAddress(&pF, g_cflag);
    cudaFuncSetAttribute(rec_kernel, cudaFuncAttributeMaxDynamicSharedMemorySize, SM_TOTAL);
    cudaFuncSetAttribute(aux_kernel, cudaFuncAttributeMaxDynamicSharedMemorySize, A_TOTAL);
  }
  RMaps rm;
  rm.poll = g_poll;
  rm.oflag = (const unsigned char*)pF;
  rm.red = (unsigned char*)(((uintptr_t)pR + 262143) & ~(uintptr_t)262143);
  {
    cuuint64_t dims[3] = {64, S_LEN, 9}, strides[2] = {DM * 2, 128};
    cuuint32_t box[3] = {64, 32, 9}, es[3] = {1, 1, 1};
    enc(&rm.x, CU_TENSOR_MAP_DATA_TYPE_BFLOAT16, 3, (void*)x, dims, strides, box, es, CU_TENSOR_MAP_INTERLEAVE_NONE,
        CU_TENSOR_MAP_SWIZZLE_128B, CU_TENSOR_MAP_L2_PROMOTION_L2_128B, CU_TENSOR_MAP_FLOAT_OOB_FILL_NONE);
  }
  make_map(enc, &rm.wq, Wq, DM, 4096, 192);
  make_map(enc, &rm.wk, Wk, DM, 4096, 192);
  make_map(enc, &rm.wv, Wv, DM, 4096, 192);
  make_map(enc, &rm.wo, Wo, 4096, DM, 128);
  AMaps am;
  am.red = rm.red; am.poll = rm.poll;
  {
    cuuint64_t dims[3] = {DM, S_LEN / 2, 2}, strides[2] = {DM * 4, DM * 2};
    cuuint32_t box[3] = {32, 64, 2}, es[3] = {1, 1, 1};
    enc(&am.x, CU_TENSOR_MAP_DATA_TYPE_BFLOAT16, 3, (void*)x, dims, strides, box, es, CU_TENSOR_MAP_INTERLEAVE_NONE,
        CU_TENSOR_MAP_SWIZZLE_64B, CU_TENSOR_MAP_L2_PROMOTION_L2_128B, CU_TENSOR_MAP_FLOAT_OOB_FILL_NONE);
    cuuint64_t wdims[3] = {DM, DM, 3}, wstrides[2] = {DM * 6, DM * 2};
    cuuint32_t wbox[3] = {64, 32, 3}, wbox8[3] = {8, 32, 3};
    enc(&am.wa, CU_TENSOR_MAP_DATA_TYPE_BFLOAT16, 3, (void*)wqkvA, wdims, wstrides, wbox, es, CU_TENSOR_MAP_INTERLEAVE_NONE,
        CU_TENSOR_MAP_SWIZZLE_128B, CU_TENSOR_MAP_L2_PROMOTION_L2_128B, CU_TENSOR_MAP_FLOAT_OOB_FILL_NONE);
    enc(&am.wa8, CU_TENSOR_MAP_DATA_TYPE_BFLOAT16, 3, (void*)wqkvA, wdims, wstrides, wbox8, es, CU_TENSOR_MAP_INTERLEAVE_NONE,
        CU_TENSOR_MAP_SWIZZLE_NONE, CU_TENSOR_MAP_L2_PROMOTION_NONE, CU_TENSOR_MAP_FLOAT_OOB_FILL_NONE);
  }
  {
    cuuint64_t dims[3] = {64, S_LEN, KCAT / 64}, strides[2] = {KCAT * 2, 128};
    cuuint32_t box[3] = {64, 32, 9}, es[3] = {1, 1, 1};
    make_map(enc, &am.o, pO, S_LEN, KCAT, 32);
    enc(&am.o3, CU_TENSOR_MAP_DATA_TYPE_BFLOAT16, 3, pO, dims, strides, box, es, CU_TENSOR_MAP_INTERLEAVE_NONE,
        CU_TENSOR_MAP_SWIZZLE_128B, CU_TENSOR_MAP_L2_PROMOTION_L2_128B, CU_TENSOR_MAP_FLOAT_OOB_FILL_NONE);
  }
  make_map(enc, &am.wob, Wo, 4096, DM, 64);
  make_map(enc, &am.woa, woA, DM, DM, 64);
  make_map(enc, &am.woa16, woA, DM, DM, 16);
  {
    cuuint64_t dims[2] = {KCAT, S_LEN}, strides[1] = {KCAT * 2};
    cuuint32_t box[2] = {16, 32}, es[2] = {1, 1};
    enc(&am.o16, CU_TENSOR_MAP_DATA_TYPE_BFLOAT16, 2, pO, dims, strides, box, es, CU_TENSOR_MAP_INTERLEAVE_NONE,
        CU_TENSOR_MAP_SWIZZLE_32B, CU_TENSOR_MAP_L2_PROMOTION_NONE, CU_TENSOR_MAP_FLOAT_OOB_FILL_NONE);
  }

  rec_kernel<<<96, 384, SM_TOTAL, cudaStreamPerThread>>>(rm, x, mem0);
  cudaLaunchConfig_t cfg = {};
  cfg.gridDim = dim3(NAUX); cfg.blockDim = dim3(512); cfg.dynamicSmemBytes = A_TOTAL; cfg.stream = cudaStreamPerThread;
  cudaLaunchAttribute at[1];
  at[0].id = cudaLaunchAttributeProgrammaticStreamSerialization; at[0].val.programmaticStreamSerializationAllowed = 1;
  cfg.attrs = at; cfg.numAttrs = 1;
  if (XP & 16) cfg.numAttrs = 0;
  if (!(XP & 64)) cudaLaunchKernelEx(&cfg, aux_kernel, am, x, gate_w, (bf16*)d_out);
}
```

```cpp
#include <cuda_runtime.h>
#include <cuda_bf16.h>
#include <cuda_fp16.h>
#include <cuda.h>
#include <stdint.h>

typedef __nv_bfloat16 bf16;

constexpr int S_LEN = 2048, DM = 576, NH = 32, DH = 128, NSEG = 64, KCAT = 4096 + 576;
#define RED_LINE(i) (((i) >> 2) * 4096 + ((i) & 1) * 256 + ((i) & 2) * 512)
#define RED_SLOT(s) (((s) & 1) * 128 + ((s) & 2) * 256)

#define POLL_NS 896
#define NII 18
#define W3PRE 4
#define W3MID 4
#define GF 0
#define B5POS 0
#define NUP 4
#define UPF 1
#define B3Q 9
#define B3F 0
#define GATE 8
#define NTL 2
#define B7R 1
#define EXPOS 0
#define VW2 1
#define CLR 1
#define RFW 0
#define NIC 0
#define LEAD 0
#define FIN16 1
#define VXG 0
#define EXB 0
#define EXD 0
#define EXB2 8192
#define HDLY 0
#define F10 1
#define NPROBE 2
#define WPOS 1
#define CW 0
#define WOPF 0
#define YP 0
#define EF 4
#define MO 0
#define WE 3
#define FW 1
#define HR1 0
#define HLP 0
#define EXV 2
#define NOB 0
#define QM 60
#define N5 224
#define KP(i) (((i) >> 1) + 4 * ((i) & 1))
#define SPIN_LIMIT (1 << 14)
#define XP 0

__device__ __align__(1024) bf16 g_Ocat[S_LEN * KCAT];
__device__ __align__(1024) unsigned char g_red_raw[2 * 262144];
constexpr int HINT_OFF = 2048;
__device__ __align__(16) float g_gate[S_LEN];
__device__ __align__(128) uint4 g_stats[96 * 2];
__device__ unsigned g_epoch;
__device__ unsigned g_epoch2;
__device__ __align__(128) unsigned g_oflag[NH * 32];
__device__ unsigned g_abar[3 * 32];
__device__ __align__(128) unsigned g_cflag[96 * 32];
__device__ uint2 g_sflag[96 * 4];
__device__ __align__(1024) unsigned char g_seg[NSEG * 96 * 8192];
__device__ __align__(1024) unsigned char g_km[NSEG * NH * 4096];
__device__ __align__(1024) uint2 g_part[8 * 9 * 4 * 8 * 128];
__device__ int g_err;
#define SSTAMP(seg, idx)
#define TSTAMP(idx)
#define QSTAMP(idx)
#define PROF(idx)
#define PROFP(idx)
#define STAMP(idx)
#define ASTAMP(idx)
#define WSTAMP(idx)

#define CSTAMP(idx)
#define CDECL
#define CDUMP
#define DI __device__ __forceinline__
DI uint32_t smem_u32(const void* p) { return (uint32_t)__cvta_generic_to_shared(p); }
DI uint32_t clock32() { uint32_t c; asm volatile("mov.u32 %0, %%clock;" : "=r"(c) :: "memory"); return c; }
DI uint32_t gtime() { uint32_t c; asm volatile("mov.u32 %0, %%globaltimer_lo;" : "=r"(c) :: "memory"); return c; }
DI uint32_t ldg_relaxed32(const void* p) { uint32_t v; asm volatile("ld.relaxed.gpu.global.b32 %0, [%1];" : "=r"(v) : "l"(p) : "memory"); return v; }
DI uint32_t ldg_acquire32(const void* p) { uint32_t v; asm volatile("ld.acquire.gpu.global.b32 %0, [%1];" : "=r"(v) : "l"(p) : "memory"); return v; }
DI void stg_relaxed32(void* p, uint32_t v) { asm volatile("st.relaxed.gpu.global.b32 [%0], %1;" :: "l"(p), "r"(v) : "memory"); }
DI int head_id() { int c; asm volatile("mov.u32 %0, %%clusterid.x;" : "=r"(c)); return c; }
DI uint32_t mapa(uint32_t a, uint32_t r) { uint32_t o; asm("mapa.shared::cluster.u32 %0, %1, %2;" : "=r"(o) : "r"(a), "r"(r)); return o; }
DI void cluster_arrive() { asm volatile("barrier.cluster.arrive.relaxed.aligned;" ::: "memory"); }
DI void cluster_wait() { asm volatile("barrier.cluster.wait.aligned;" ::: "memory"); }
DI void cluster_sync() { asm volatile("barrier.cluster.arrive.release.aligned;\nbarrier.cluster.wait.acquire.aligned;" ::: "memory"); }
DI void mbar_init(uint32_t b, uint32_t c) { asm volatile("mbarrier.init.shared::cta.b64 [%0], %1;" :: "r"(b), "r"(c) : "memory"); }
DI void mbar_expect(uint32_t b, uint32_t tx) { asm volatile("mbarrier.arrive.expect_tx.shared::cta.b64 _, [%0], %1;" :: "r"(b), "r"(tx) : "memory"); }
DI void mbar_arrive(uint32_t b) { asm volatile("mbarrier.arrive.shared::cta.b64 _, [%0];" :: "r"(b) : "memory"); }
DI void mbar_wait(uint32_t b, uint32_t par) {
  asm volatile("{\n.reg .pred p;\n.reg .u32 n, q;\nmov.u32 n, 0;\n"
               "WL: add.u32 n, n, 1;\nshr.u32 q, n, 12;\nxor.b32 q, q, %1;\n"
               "mbarrier.try_wait.parity.shared::cta.b64 p, [%0], q;\n@!p bra.uni WL;\n}"
               :: "r"(b), "r"(par) : "memory");
}
DI void wait_until(uint32_t t) {
  const uint32_t now = gtime();
  t = min(t, now + 8192);
  asm volatile("{\n.reg .pred p;\n.reg .u32 c;\nTL: mov.u32 c, %%globaltimer_lo;\nsetp.lt.u32 p, c, %0;\n@p bra.uni TL;\n}" :: "r"(t) : "memory");
}
#define PIN(v) v = __shfl_xor_sync(0xffffffffu, v, 0)
#define SCHED_FENCE(k) asm volatile("{\n.reg .pred p;\nsetp.eq.u32 p, %0, %1;\n@p exit;\n}" :: "r"(fence_reg), "r"(k) : "memory")
#define MEM_ORDER(k) asm volatile("{\n.reg .pred p;\nsetp.eq.u32 p, %0, %1;\n@p st.shared.u32 [%0], %0;\n}" :: "r"(fence_reg), "r"(k + 64) : "memory")
DI void bar_sync(int id, int n) { asm volatile("bar.sync %0, %1;" :: "r"(id), "r"(n) : "memory"); }
DI void bar_arrive(int id, int n) { asm volatile("bar.arrive %0, %1;" :: "r"(id), "r"(n) : "memory"); }
DI void fence_async() { asm volatile("fence.proxy.async.shared::cta;" ::: "memory"); }
DI void st_async4(uint32_t a, uint32_t x, uint32_t y, uint32_t z, uint32_t w, uint32_t mb) {
  asm volatile("st.async.weak.shared::cluster.mbarrier::complete_tx::bytes.v4.b32 [%0], {%1,%2,%3,%4}, [%5];"
               :: "r"(a), "r"(x), "r"(y), "r"(z), "r"(w), "r"(mb) : "memory");
}
DI void st_async2(uint32_t a, uint32_t x, uint32_t y, uint32_t mb) {
  asm volatile("st.async.weak.shared::cluster.mbarrier::complete_tx::bytes.v2.b32 [%0], {%1,%2}, [%3];"
               :: "r"(a), "r"(x), "r"(y), "r"(mb) : "memory");
}
DI void sts32(uint32_t a, uint32_t x) { asm volatile("st.shared.b32 [%0], %1;" :: "r"(a), "r"(x) : "memory"); }
DI void sts64(uint32_t a, uint32_t x, uint32_t y) { asm volatile("st.shared.v2.b32 [%0], {%1,%2};" :: "r"(a), "r"(x), "r"(y) : "memory"); }
DI void sts128(uint32_t a, uint32_t x, uint32_t y, uint32_t z, uint32_t w) {
  asm volatile("st.shared.v4.b32 [%0], {%1,%2,%3,%4};" :: "r"(a), "r"(x), "r"(y), "r"(z), "r"(w) : "memory");
}
DI uint32_t lds32(uint32_t a) { uint32_t x; asm volatile("ld.shared.b32 %0, [%1];" : "=r"(x) : "r"(a) : "memory"); return x; }
DI uint32_t lds32v(uint32_t a) { uint32_t x; asm volatile("ld.volatile.shared.b32 %0, [%1];" : "=r"(x) : "r"(a) : "memory"); return x; }
DI void lds64(uint32_t a, uint32_t& x, uint32_t& y) { asm volatile("ld.shared.v2.b32 {%0,%1}, [%2];" : "=r"(x), "=r"(y) : "r"(a) : "memory"); }
DI void lds128(uint32_t a, uint32_t* r) {
  asm volatile("ld.shared.v4.b32 {%0,%1,%2,%3}, [%4];" : "=r"(r[0]), "=r"(r[1]), "=r"(r[2]), "=r"(r[3]) : "r"(a) : "memory");
}
DI void lds128f(uint32_t a, float* r) {
  asm volatile("ld.shared.v4.f32 {%0,%1,%2,%3}, [%4];" : "=f"(r[0]), "=f"(r[1]), "=f"(r[2]), "=f"(r[3]) : "r"(a) : "memory");
}
DI void lds64f(uint32_t a, float* r) { asm volatile("ld.shared.v2.f32 {%0,%1}, [%2];" : "=f"(r[0]), "=f"(r[1]) : "r"(a) : "memory"); }
DI void ldsm4t(uint32_t* r, uint32_t a) {
  asm volatile("ldmatrix.sync.aligned.m8n8.x4.trans.shared.b16 {%0,%1,%2,%3}, [%4];"
               : "=r"(r[0]), "=r"(r[1]), "=r"(r[2]), "=r"(r[3]) : "r"(a) : "memory");
}
DI void ldsm4t_in(uint32_t* r, uint32_t a, uint32_t t) {
  asm volatile("{\n.reg .pred p;\nsetp.ne.u32 p, %5, 0;\n@p ldmatrix.sync.aligned.m8n8.x4.trans.shared.b16 {%0,%1,%2,%3}, [%4];\n}"
               : "+r"(r[0]), "+r"(r[1]), "+r"(r[2]), "+r"(r[3]) : "r"(a), "r"(t) : "memory");
}
DI void lds128_in(uint32_t* r, uint32_t a, uint32_t t) {
  asm volatile("{\n.reg .pred p;\nsetp.ne.u32 p, %5, 0;\n@p ld.shared.v4.b32 {%0,%1,%2,%3}, [%4];\n}"
               : "+r"(r[0]), "+r"(r[1]), "+r"(r[2]), "+r"(r[3]) : "r"(a), "r"(t) : "memory");
}
DI void ldsm2t_in(uint32_t* r, uint32_t a, uint32_t t) {
  asm volatile("{\n.reg .pred p;\nsetp.ne.u32 p, %3, 0;\n@p ldmatrix.sync.aligned.m8n8.x2.trans.shared.b16 {%0,%1}, [%2];\n}" : "+r"(r[0]), "+r"(r[1]) : "r"(a), "r"(t) : "memory");
}
DI void reserve2(uint32_t* r) { asm volatile("{\n.reg .u64 t;\nmov.u64 t, %%clock64;\nmov.b64 {%0, %1}, t;\n}" : "=r"(r[0]), "=r"(r[1])); }
DI void scale_sum(float& x, float& y, float s, uint32_t t) {
  asm volatile("{\n.reg .pred p;\nsetp.ne.u32 p, %2, 0;\n@p mul.f32 %0, %0, %1;\n}" : "+f"(y) : "f"(s), "r"(t));
  asm volatile("{\n.reg .pred p;\nsetp.ne.u32 p, %3, 1;\n@p fma.rn.f32 %0, %0, %1, %2;\n}" : "+f"(x) : "f"(s), "f"(y), "r"(t));
}
DI void ldsm4(uint32_t* r, uint32_t a) {
  asm volatile("ldmatrix.sync.aligned.m8n8.x4.shared.b16 {%0,%1,%2,%3}, [%4];"
               : "=r"(r[0]), "=r"(r[1]), "=r"(r[2]), "=r"(r[3]) : "r"(a) : "memory");
}
DI void st_async1(uint32_t a, uint32_t x, uint32_t mb) {
  asm volatile("st.async.weak.shared::cluster.mbarrier::complete_tx::bytes.b32 [%0], %1, [%2];" :: "r"(a), "r"(x), "r"(mb) : "memory");
}
DI void stsm4(uint32_t a, uint32_t x, uint32_t y, uint32_t z, uint32_t w) {
  asm volatile("stmatrix.sync.aligned.m8n8.x4.shared.b16 [%0], {%1,%2,%3,%4};" :: "r"(a), "r"(x), "r"(y), "r"(z), "r"(w) : "memory");
}
DI void stsm4t(uint32_t a, uint32_t x, uint32_t y, uint32_t z, uint32_t w) {
  asm volatile("stmatrix.sync.aligned.m8n8.x4.trans.shared.b16 [%0], {%1,%2,%3,%4};" :: "r"(a), "r"(x), "r"(y), "r"(z), "r"(w) : "memory");
}
DI uint32_t pack_bf16(float lo, float hi) { uint32_t r; asm("cvt.rn.bf16x2.f32 %0, %1, %2;" : "=r"(r) : "f"(hi), "f"(lo)); return r; }
DI uint32_t pack_f16(float lo, float hi) { uint32_t r; asm("cvt.rn.f16x2.f32 %0, %1, %2;" : "=r"(r) : "f"(hi), "f"(lo)); return r; }
DI float ex2(float x) { float y; asm("ex2.approx.ftz.f32 %0, %1;" : "=f"(y) : "f"(x)); return y; }
DI float rcp(float x) { float y; asm("rcp.approx.ftz.f32 %0, %1;" : "=f"(y) : "f"(x)); return y; }
DI float bf_lo(uint32_t x) { return __uint_as_float(x << 16); }
DI float bf_hi(uint32_t x) { return __uint_as_float(x & 0xffff0000u); }
DI void mma16816(float* d, const uint32_t* a, uint32_t b0, uint32_t b1) {
  asm volatile("mma.sync.aligned.m16n8k16.row.col.f32.bf16.bf16.f32 {%0,%1,%2,%3}, {%4,%5,%6,%7}, {%8,%9}, {%0,%1,%2,%3};"
               : "+f"(d[0]), "+f"(d[1]), "+f"(d[2]), "+f"(d[3]) : "r"(a[0]), "r"(a[1]), "r"(a[2]), "r"(a[3]), "r"(b0), "r"(b1));
}
DI void mma16816z(float* d, const uint32_t* a, uint32_t b0, uint32_t b1) {
  asm volatile("mma.sync.aligned.m16n8k16.row.col.f32.bf16.bf16.f32 {%0,%1,%2,%3}, {%4,%5,%6,%7}, {%8,%9}, {%10,%10,%10,%10};"
               : "=f"(d[0]), "=f"(d[1]), "=f"(d[2]), "=f"(d[3]) : "r"(a[0]), "r"(a[1]), "r"(a[2]), "r"(a[3]), "r"(b0), "r"(b1), "f"(0.f));
}
DI void mma1688z(float* d, uint32_t a0, uint32_t a1, uint32_t b0) {
  asm volatile("mma.sync.aligned.m16n8k8.row.col.f32.bf16.bf16.f32 {%0,%1,%2,%3}, {%4,%5}, {%6}, {%7,%7,%7,%7};"
               : "=f"(d[0]), "=f"(d[1]), "=f"(d[2]), "=f"(d[3]) : "r"(a0), "r"(a1), "r"(b0), "f"(0.f));
}
DI void mma1688(float* d, uint32_t a0, uint32_t a1, uint32_t b0) {
  asm volatile("mma.sync.aligned.m16n8k8.row.col.f32.bf16.bf16.f32 {%0,%1,%2,%3}, {%4,%5}, {%6}, {%0,%1,%2,%3};"
               : "+f"(d[0]), "+f"(d[1]), "+f"(d[2]), "+f"(d[3]) : "r"(a0), "r"(a1), "r"(b0));
}
DI void ldsm2t(uint32_t* r, uint32_t a) {
  asm volatile("ldmatrix.sync.aligned.m8n8.x2.trans.shared.b16 {%0,%1}, [%2];" : "=r"(r[0]), "=r"(r[1]) : "r"(a) : "memory");
}
DI uint32_t add_bf16(uint32_t a, uint32_t b) { uint32_t r; asm("add.rn.bf16x2 %0, %1, %2;" : "=r"(r) : "r"(a), "r"(b)); return r; }
DI uint32_t mul_bf16(uint32_t a, uint32_t b) { uint32_t r; asm("mul.rn.bf16x2 %0, %1, %2;" : "=r"(r) : "r"(a), "r"(b)); return r; }
DI uint64_t make_desc(uint32_t addr, uint32_t lbo, uint32_t sbo, uint32_t swz) {
  return (uint64_t)((addr & 0x3FFFF) >> 4) | ((uint64_t)(lbo >> 4) << 16) | ((uint64_t)(sbo >> 4) << 32) | ((uint64_t)swz << 62);
}
#define WG_FENCE() asm volatile("wgmma.fence.sync.aligned;" ::: "memory")
#define WG_COMMIT() asm volatile("wgmma.commit_group.sync.aligned;" ::: "memory")
#define WG_WAIT(n) asm volatile("wgmma.wait_group.sync.aligned %0;" :: "n"(n) : "memory")
#define ACC8(d, o) "+f"(d[o]), "+f"(d[o + 1]), "+f"(d[o + 2]), "+f"(d[o + 3]), "+f"(d[o + 4]), "+f"(d[o + 5]), "+f"(d[o + 6]), "+f"(d[o + 7])
DI void wgmma_n32_rs(float* d, uint32_t a0, uint32_t a1, uint32_t a2, uint32_t a3, uint64_t db, int acc) {
  asm volatile("{\n.reg .pred p;\nsetp.ne.b32 p, %21, 0;\n"
               "wgmma.mma_async.sync.aligned.m64n32k16.f32.bf16.bf16 {%0,%1,%2,%3,%4,%5,%6,%7,%8,%9,%10,%11,%12,%13,%14,%15}, "
               "{%16,%17,%18,%19}, %20, p, 1, 1, 0;\n}\n"
               : ACC8(d, 0), ACC8(d, 8) : "r"(a0), "r"(a1), "r"(a2), "r"(a3), "l"(db), "r"(acc));
}
template <int TA>
DI void wgmma_n32_ss(float* d, uint64_t da, uint64_t db, int acc) {
  asm volatile("{\n.reg .pred p;\nsetp.ne.b32 p, %18, 0;\n"
               "wgmma.mma_async.sync.aligned.m64n32k16.f32.bf16.bf16 {%0,%1,%2,%3,%4,%5,%6,%7,%8,%9,%10,%11,%12,%13,%14,%15}, "
               "%16, %17, p, 1, 1, %19, 1;\n}\n"
               : ACC8(d, 0), ACC8(d, 8) : "l"(da), "l"(db), "r"(acc), "n"(TA));
}
DI void tma_load(uint32_t dst, const CUtensorMap* m, int c0, int c1, uint32_t mb) {
  asm volatile("cp.async.bulk.tensor.2d.shared::cluster.global.mbarrier::complete_tx::bytes [%0], [%1, {%3, %4}], [%2];"
               :: "r"(dst), "l"(m), "r"(mb), "r"(c0), "r"(c1) : "memory");
}
DI void tma_load3(uint32_t dst, const CUtensorMap* m, int row, uint32_t mb) {
  asm volatile("cp.async.bulk.tensor.3d.shared::cluster.global.mbarrier::complete_tx::bytes [%0], [%1, {%3, %4, %3}], [%2];"
               :: "r"(dst), "l"(m), "r"(mb), "r"(0), "r"(row) : "memory");
}
DI bool elect_one() {
  uint32_t p;
  asm volatile("{\n.reg .pred p;\nelect.sync _|p, 0xffffffff;\nselp.u32 %0, 1, 0, p;\n}" : "=r"(p));
  return p;
}
DI void bulk_s2s(uint32_t dst, uint32_t src, uint32_t bytes, uint32_t mb) {
  asm volatile("cp.async.bulk.shared::cluster.shared::cta.mbarrier::complete_tx::bytes [%0], [%1], %2, [%3];"
               :: "r"(dst), "r"(src), "r"(bytes), "r"(mb) : "memory");
}
DI void bulk_load(uint32_t dst, const void* src, uint32_t bytes, uint32_t mb) {
  asm volatile("cp.async.bulk.shared::cluster.global.mbarrier::complete_tx::bytes [%0], [%1], %2, [%3];" :: "r"(dst), "l"(src), "r"(bytes), "r"(mb) : "memory");
}
#define EVICT_FIRST ".reg .b64 pol;\ncreatepolicy.fractional.L2::evict_first.b64 pol, 1.0;\n"
DI void bulk_load_ef(uint32_t dst, const void* src, uint32_t bytes, uint32_t mb) {
  asm volatile("{\n" EVICT_FIRST "cp.async.bulk.shared::cluster.global.mbarrier::complete_tx::bytes.L2::cache_hint [%0], [%1], %2, [%3], pol;\n}"
               :: "r"(dst), "l"(src), "r"(bytes), "r"(mb) : "memory");
}
DI void tma_load_ef(uint32_t dst, const CUtensorMap* m, int c0, int c1, uint32_t mb) {
  asm volatile("{\n" EVICT_FIRST "cp.async.bulk.tensor.2d.shared::cluster.global.mbarrier::complete_tx::bytes.L2::cache_hint [%0], [%1, {%3, %4}], [%2], pol;\n}"
               :: "r"(dst), "l"(m), "r"(mb), "r"(c0), "r"(c1) : "memory");
}
DI void tma_prefetch(const CUtensorMap* m, int c0, int c1) {
  asm volatile("cp.async.bulk.prefetch.tensor.2d.L2.global.tile [%0, {%1, %2}];" :: "l"(m), "r"(c0), "r"(c1) : "memory");
}
DI void tma_store(const CUtensorMap* m, uint32_t src, int c0, int c1) {
  asm volatile("cp.async.bulk.tensor.2d.global.shared::cta.bulk_group [%0, {%2, %3}], [%1];" :: "l"(m), "r"(src), "r"(c0), "r"(c1) : "memory");
}
DI uint4 ldg_relaxed(const void* p) {
  uint4 v;
  asm volatile("ld.relaxed.gpu.global.v4.b32 {%0,%1,%2,%3}, [%4];" : "=r"(v.x), "=r"(v.y), "=r"(v.z), "=r"(v.w) : "l"(p) : "memory");
  return v;
}
DI void stg_relaxed(void* p, uint32_t x, uint32_t y, uint32_t z, uint32_t w) {
  asm volatile("st.relaxed.gpu.global.v4.b32 [%0], {%1,%2,%3,%4};" :: "l"(p), "r"(x), "r"(y), "r"(z), "r"(w) : "memory");
}
DI void red_f16x8(void* p, uint32_t x, uint32_t y, uint32_t z, uint32_t w) {
  asm volatile("red.relaxed.gpu.global.add.noftz.v4.f16x2 [%0], {%1,%2,%3,%4};" :: "l"(p), "r"(x), "r"(y), "r"(z), "r"(w) : "memory");
}
DI void sq_acc(uint32_t& a, uint32_t x) { asm("fma.rn.bf16x2 %0, %1, %1, %0;" : "+r"(a) : "r"(x)); }
DI __half2 amax4(__half2 h, const uint32_t* v) {
  h = __hmax2_nan(__hmax2_nan(h, __habs2(*(const __half2*)&v[0])), __habs2(*(const __half2*)&v[1]));
  return __hmax2_nan(__hmax2_nan(h, __habs2(*(const __half2*)&v[2])), __habs2(*(const __half2*)&v[3]));
}
DI uint32_t wexp(__half2 h) { const uint32_t u = *(const uint32_t*)&h; return __reduce_max_sync(0xffffffffu, max((u >> 16) & 0x7fffu, u & 0x7fffu)) >> 7; }
DI float max10(const float* a) {
  return fmaxf(fmaxf(fmaxf(fmaxf(a[0], a[1]), fmaxf(a[2], a[3])), fmaxf(fmaxf(a[4], a[5]), fmaxf(a[6], a[7]))), fmaxf(a[8], a[9]));
}
DI float quad_max(float m) {
  return fmaxf(fmaxf(m, __shfl_xor_sync(0xffffffffu, m, 1)), fmaxf(__shfl_xor_sync(0xffffffffu, m, 2), __shfl_xor_sync(0xffffffffu, m, 3)));
}
DI float warp_sum(float v) {
#pragma unroll
  for (int o = 16; o; o >>= 1) v += __shfl_xor_sync(0xffffffffu, v, o);
  return v;
}

constexpr int SM_WO3 = 0;
constexpr int SM_X = 16384;
constexpr int XT = 36864;
constexpr int SM_EXP = 126976;
constexpr int SEGB = 10240;
constexpr int SM_BLK = SM_EXP + 8192;
constexpr int SM_VC = SM_BLK + 4 * SEGB;
constexpr int SM_PART = SM_VC + 16384;
constexpr int SM_QM = SM_PART + 4096;
constexpr int SM_E = SM_QM + 1024;
constexpr int SM_VM = SM_E + 1536;
constexpr int SM_OB = SM_VM + 2048;
constexpr int SM_FB = SM_OB + 2048;
constexpr int SM_STAGE = SM_X + XT;
constexpr int SM_M0 = SM_STAGE + 3 * 49152;
constexpr int SM_MISC = 210944;
constexpr int SM_WOST = 212992;
constexpr int SM_MEM = SM_WOST;
constexpr int SM_MAX = SM_MEM + 11264;
#define MEM_BLK(q) ((q) / 3 * 4096 + (q) % 3 * 1024)
constexpr int SM_TOTAL = 229376;
constexpr int MB_W = SM_MISC;
constexpr int MB_WO = SM_MISC + 24;
constexpr int MB_WO3 = SM_MISC + 32;
constexpr int MB_X = SM_MISC + 40;
constexpr int MB_S = SM_MISC + 64;
constexpr int MB_F = SM_MISC + 72;
constexpr int MB_VX = SM_MISC + 80;
constexpr int SC_FPAR = SM_MISC + 136;
constexpr int SC_DEAD = SM_MISC + 96;
constexpr int SC_UNSC = SM_MISC + 112;
constexpr int SC_OFL = SM_MISC + 1024;
constexpr int SC_EXPW = SM_MISC + 132;
constexpr int SC_ONES = SM_MISC + 144;
constexpr int SC_SS = SM_MISC + 160;
constexpr int SC_LAT = SM_MISC + 224;
constexpr int SC_TAG = SM_MISC + 232;
constexpr int SC_EPO = SM_MISC + 240;
constexpr int MB_XS = SM_MISC + 248;
constexpr int SC_XMAX = SM_MISC + 256;
constexpr int SC_PROF = 229376;

constexpr float SM_SCALE = 0.08838834764831845f;
constexpr float LOG2E = 1.4426950408889634f;
constexpr float E_LIM = 20.f;

template <bool B> struct BoolC { static constexpr bool value = B; };
template <int I> struct IntC { static constexpr int value = I; };
struct RMaps { CUtensorMap x, wq, wk, wv, wo; unsigned char* red; uint32_t poll; const unsigned char* oflag; };

DI uint32_t latest_hint(uint32_t h, uint32_t d, int s) {
  const uint32_t x = (((h | 0xc0c0c0c0u) - ((d >> 5) & 63) * 0x01010101u) & 0x3f3f3f3fu) | ((h ^ (((s >> 2) + 1) & 3) * 0x40404040u) & 0xc0c0c0c0u);
  const uint32_t y = __vmaxu2(x & 0x00ff00ffu, (x >> 8) & 0x00ff00ffu);
  return __reduce_max_sync(0xffffffffu, max(y & 0xffffu, y >> 16));
}
DI uint32_t near_half(uint32_t sb) {
  uint32_t a, b; lds64(sb + SC_LAT, a, b);
  return a > b;
}

template <int RT, int K0, int K1, bool D32 = false>
DI void xproj(float* acc, const uint32_t (&wa)[2][18][4], uint64_t xd) {
  if (XP & 1) return;
  WG_FENCE();
#pragma unroll
  for (int k = K0; k < ((XP & 128) ? K0 + 1 : K1); k++)
  {
    uint64_t d = xd + (uint64_t)(((k >> 1) * 4096 + (k & 1) * 32) >> 4);
    if (D32) asm("mov.b64 %0, {%1, %2};" : "=l"(d) : "r"((uint32_t)xd + (((k >> 1) * 4096 + (k & 1) * 32) >> 4)), "r"((uint32_t)(xd >> 32)));
    wgmma_n32_rs(acc, wa[RT][k][0], wa[RT][k][1], wa[RT][k][2], wa[RT][k][3], d, k != 0);
  }
  WG_COMMIT();
}

DI void load_w(uint32_t sb, const RMaps& tm, uint32_t rank, int c) {
  const int h = blockIdx.x / 3;
  mbar_expect(sb + MB_W + 8 * c, 49152);
  ((EF & 4) ? tma_load_ef : tma_load)(sb + SM_STAGE + c * 49152, rank < 2 ? &tm.wk : &tm.wv, h * DH + (rank == 1 ? 64 : 0), c * 192, sb + MB_W + 8 * c);
  ((EF & 4) ? tma_load_ef : tma_load)(sb + SM_STAGE + c * 49152 + 24576, rank < 2 ? &tm.wq : &tm.wv, h * DH + (rank == 0 ? 0 : 64), c * 192, sb + MB_W + 8 * c);
}
DI void seg_store(int seg, uint32_t slot, uint32_t sb) {
  if (!FW) fence_async();
  asm volatile("cp.async.bulk.global.shared::cta.bulk_group [%0], [%1], 8192;"
               :: "l"(g_seg + ((size_t)slot * 96 + blockIdx.x) * 8192), "r"(sb + SM_BLK + (seg & 3) * SEGB) : "memory");
  asm volatile("cp.async.bulk.commit_group;" ::: "memory");
}
DI void seg_publish(int seg, uint32_t sb) {
  uint32_t v, own;
  lds64(sb + SC_EPO, v, own);
  asm volatile("cp.async.bulk.wait_group 0;" ::: "memory");
  asm volatile("st.relaxed.gpu.global.v2.b32 [%0], {%1,%2};" :: "l"(&g_sflag[blockIdx.x * 4]), "r"(v + seg), "r"(own) : "memory");
}

DI void proj_role(const uint32_t sb, const RMaps& tm, const bf16* __restrict__ x, const uint32_t rank, const int wg, const int w, const int lane) {
  const bool qk = rank < 2;
  uint32_t wa[2][18][4];
  float acc[16];
  const uint64_t xd0 = make_desc(sb + SM_X + wg * 64, 16, 1024, 1);
  {
    const int rr = (lane & 7) + ((lane >> 4) << 3);
    const uint32_t col = ((2 * w + ((lane >> 3) & 1)) ^ (lane & 7)) << 4;
    float ss = 0.f;
    bar_sync(3, 256);
    mbar_wait(sb + MB_X, 0);
    auto chunk = [&](auto cc) {
      constexpr int c = decltype(cc)::value;
      QSTAMP(2 + 2 * c);
      mbar_wait(sb + MB_W + 8 * c, 0);
      QSTAMP(3 + 2 * c);
#pragma unroll
      for (int rt = 1; rt >= 0; rt--)
#pragma unroll
        for (int k = 0; k < 6; k++)
          ldsm4t(wa[rt][c * 6 + k], sb + SM_STAGE + c * 49152 + (rt ^ wg) * 24576 + (64 * (k >> 1) + 32 * wg + 16 * (k & 1) + rr) * 128 + col);
      fence_async();
      if (c < 2) {
        bar_sync(3, 256);
        QSTAMP(17 + c);
        if (threadIdx.x == 0) {
          if (c == 0) tma_load(sb + SM_X + XT, &tm.wo, rank * 192, (blockIdx.x / 3) * DH, sb + MB_WO);
          else if (blockIdx.x < NSEG) bulk_load(sb + SM_X + 2 * XT, x + blockIdx.x * 32 * DM, XT, sb + MB_XS);
          else tma_load3(sb + SM_X + 2 * XT, &tm.x, 64, sb + MB_X + 16);
        }
        __syncwarp();
      } else {
        cluster_arrive();
      }
      xproj<1, 6 * c, 6 * c + 6>(acc, wa, xd0);
      if (!qk) {
        uint32_t q[4] = {0, 0, 0, 0};
#pragma unroll
        for (int rt = 0; rt < 2; rt++)
#pragma unroll
          for (int k = 0; k < 6; k++)
#pragma unroll
            for (int i = 0; i < 4; i++) sq_acc(q[i], wa[rt][c * 6 + k][i]);
#pragma unroll
        for (int i = 0; i < 4; i++) ss += bf_lo(q[i]) + bf_hi(q[i]);
      }
      if (c < 2 && CW) WG_WAIT(0);
    };
    chunk(IntC<0>()); chunk(IntC<1>()); chunk(IntC<2>());
    ss = warp_sum(ss);
    if (lane == 0) sts32(sb + SC_SS + 4 * (wg * 4 + w), __float_as_uint(ss));
    bar_arrive(11, 384);
  }
  STAMP(1);
  QSTAMP(8);
  STAMP(2);

  uint32_t t16 = sb + (w * 32 + lane) * 16;
  uint32_t mem_a = sb + SM_MEM + wg * 512 + lane * 16;
  uint32_t fin_a = sb + (lane & 7) * 16 + SM_BLK + (qk ? (wg ^ 1) * 4096 + w * 256 + (lane & 8) * 16 + (lane & 16) * 64
                                              : wg * 4096 + w * 1024 + (lane & 8) * 64 + (lane & 16) * 8);
  PIN(t16); PIN(mem_a); PIN(fin_a);
  const uint32_t fence_reg = mem_a;
  const uint32_t fin2 = qk ? 2048 : 256;
  auto do_export = [&](auto retire, uint32_t always) {
    WG_WAIT(0);
    uint32_t p[2];
#pragma unroll
    for (int i = 0; i < 2; i++) {
      p[i] = pack_bf16(acc[8 * i], acc[8 * i + 1]);
      sts128(t16 + SM_EXP + wg * 4096 + i * 2048, p[i], pack_bf16(acc[8 * i + 2], acc[8 * i + 3]),
             pack_bf16(acc[8 * i + 4], acc[8 * i + 5]), pack_bf16(acc[8 * i + 6], acc[8 * i + 7]));
    }
    if (decltype(retire)::value)
      asm volatile("{\n.reg .pred p, q;\nsetp.ne.u32 p, %2, 0;\nsetp.ne.u32 q, %2, 1;\n@p ld.shared.b32 %0, [%3];\n@q ld.shared.b32 %1, [%3 + 4];\n"
                   "setp.ne.u32 p, %0, %1;\n@p exit;\n}" : "+r"(p[0]), "+r"(p[1]) : "r"(always), "r"(sb + SC_DEAD) : "memory");
  };
  uint32_t o[8];
  auto import = [&]() { lds128(t16 + SM_EXP + (wg ^ 1) * 4096, o); lds128(t16 + SM_EXP + (wg ^ 1) * 4096 + 2048, o + 4); };
  auto finish_from = [&](int seg, const float* d) {
    const uint32_t a = fin_a + (seg & 3) * SEGB;
#pragma unroll
    for (int i = 0; i < 8; i++) o[i] = add_bf16(pack_bf16(d[2 * i], d[2 * i + 1]), o[i]);
    stsm4(a, o[0], o[1], o[2], o[3]);
    stsm4(a + fin2, o[4], o[5], o[6], o[7]);
    if (FW) fence_async();
  };
  auto finish = [&](int seg) { WG_WAIT(0); finish_from(seg, acc); };
  auto send_v = [&](int seg, int dst) {
    if (!FW) fence_async();
    if (seg < NSEG - 1 && !(XP & 2) && elect_one())
      bulk_s2s(mapa(sb + SM_VC + (seg & 1) * 8192, dst), sb + SM_BLK + (seg & 3) * SEGB, 8192, mapa(sb + MB_VX + (seg & 1) * 8, dst));
    __syncwarp();
  };
  auto wait_v = [&](int seg) {
    if (seg < NSEG - 1 && !(XP & 2)) {
      mbar_wait(sb + MB_VX + (seg & 1) * 8, (seg >> 1) & 1);
      if (elect_one()) mbar_expect(sb + MB_VX + (seg & 1) * 8, 8192);
      __syncwarp();
    }
  };
  auto export_seg = [&](int seg, uint32_t slot) { if (!(XP & (4 | 8192)) && elect_one()) seg_store(seg, slot, sb); __syncwarp(); };
  auto publish = [&](int seg) { if (!(XP & (4 | 16384)) && elect_one()) seg_publish(seg, sb); __syncwarp(); };
  do_export(BoolC<false>(), 0);
  QSTAMP(9);
  SCHED_FENCE(11);
  xproj<0, 0, 18>(acc, wa, xd0);
  bar_sync(3, 256);
  QSTAMP(10);
  cluster_wait();
  QSTAMP(11);
  mbar_wait(sb + MB_X + 8, 0);
  QSTAMP(12);
  import();
  finish(0);
  SCHED_FENCE(12);
  uint64_t dA = xd0 + (XT >> 4);
  xproj<1, 0, 18>(acc, wa, dA);
  bar_sync(3, 256);
  if (!qk && wg == 0 && w < 2) send_v(0, w);
  if (wg == 0 && w == 3) export_seg(0, 0);
  QSTAMP(13);
  if (qk && wg == 0 && w == 0) wait_v(0);
  QSTAMP(14);
  bar_arrive(13, 384);
  if (!qk) {
    do_export(BoolC<false>(), 0);
    SCHED_FENCE(15);
    xproj<0, 0, 18>(acc, wa, dA);
    if (threadIdx.x == 0 && !(XP & 8)) { mbar_expect(sb + MB_X, XT); tma_load3(sb + SM_X, &tm.x, 96, sb + MB_X); }
    bar_sync(3, 256);
    mbar_wait(sb + MB_X + 16, 0);
    import();
    finish(1);
    SCHED_FENCE(16);
    dA += XT >> 4;
    xproj<1, 0, 18>(acc, wa, dA);
  }
  QSTAMP(15);
  WG_WAIT(0);
  bar_sync(0, 384);
  if (wg == 0 && w == 3) publish(0);
  QSTAMP(16);
  const int ro = __shfl_sync(0xffffffffu, near_half(sb) ^ wg, 0);
  STAMP(5);
  const uint32_t always = __shfl_sync(0xffffffffu, lds32(sb + SC_DEAD + 12), 0);
  const int ah = qk ? 1 : 2;
  int b2 = qk ? 2 : 0;
  int s = 0;
  uint32_t hint_lo = (uint32_t)(uint64_t)tm.red + HINT_OFF + blockIdx.x + (lane & 1) * 4096 + (lane >> 1) * 16384;
  PIN(hint_lo);
  auto post_hint = [&]() {
    uint32_t t;
    asm volatile("{\n.reg .u64 g;\nmov.u64 g, %%globaltimer;\ncvt.u32.u64 %0, g;\n}" : "=r"(t) :: "memory");
    asm volatile("{\n.reg .pred p;\n.reg .b64 a;\n.reg .u32 t;\nsetp.lt.u32 p, %0, %1;\nmov.b64 a, {%2, %3};\n"
                 "bfe.u32 t, %5, 5, 6;\nor.b32 t, t, %4;\n@p st.relaxed.gpu.global.u8 [a], t;\n}"
                 :: "r"(t16), "r"(sb + 160), "r"(hint_lo + RED_SLOT(s)), "r"((uint32_t)((uint64_t)tm.red >> 32)), "r"(((s >> 2) + 1) << 6), "r"(t) : "memory");
  };
  auto memproj = [&](auto second, int id, uint32_t dep, float u0, float u1, float* r) {
    constexpr bool R1 = decltype(second)::value;
    uint32_t b[NUP][4], b0[4];
    if (R1) asm volatile("{\n.reg .pred p;\nsetp.eq.u32 p, %0, %1;\n@p exit;\n}" :: "r"(dep), "r"(id) : "memory");
    bar_sync(R1 ? 2 : 1, 256);
    PROF(0);
    ldsm4t(b0, mem_a);
#pragma unroll
    for (int q = 0; q < NUP; q++) {
      if (R1 && q == 2) {
        bar_sync(11, 256);
        SCHED_FENCE(id + 1);
      }
      ldsm4t(b[q], mem_a + MEM_BLK(q + 1));
    }
    mma16816z(&acc[0], wa[0][0], b0[0], b0[1]);
    mma16816z(&acc[4], wa[1][0], b0[0], b0[1]);
    mma16816z(&acc[8], wa[0][1], b0[2], b0[3]);
    mma16816z(&acc[12], wa[1][1], b0[2], b0[3]);
#pragma unroll
    for (int q = 1; q < 9; q++) {
      uint32_t* const c = b[(q - 1) % NUP];
      mma16816(&acc[0], wa[0][2 * q], c[0], c[1]);
      mma16816(&acc[4], wa[1][2 * q], c[0], c[1]);
      mma16816(&acc[8], wa[0][2 * q + 1], c[2], c[3]);
      mma16816(&acc[12], wa[1][2 * q + 1], c[2], c[3]);
      if (R1 && q + NUP == B3Q) bar_sync(3, 256);
      if (q + NUP < 9) ldsm4t_in(c, mem_a + MEM_BLK(q + NUP), always);
      else if (R1 && q + NUP < 11) lds128_in(c, t16 + SM_PART + (10 - q - NUP) * 2048, always);
      else if (!R1 && GATE && q == GATE) { bar_arrive(11, 256); lds128_in(c, sb + SC_DEAD, always); u0 = u1 = __uint_as_float(c[3]); }
    }
#pragma unroll
    for (int i = 0; i < 8; i++) {
      const float u = i < 4 ? u0 : u1;
      r[i] = R1 ? fmaf(acc[8 + i], u, (acc[i] + __uint_as_float(b[(8 + i / 4) % NUP][i & 3])) * u) : (GATE ? fmaf(acc[i], u, acc[8 + i]) : acc[i] + acc[8 + i]);
    }
  };
  if (ro == 0) {
#pragma unroll 1
    while (true) {
      do_export(BoolC<true>(), always);
      PROFP(3);
      if (s == 8) STAMP(6);
      float r[8];
      memproj(BoolC<false>(), 30, 0, 0.f, 0.f, r);
      sts128(t16 + SM_PART, __float_as_uint(r[0]), __float_as_uint(r[1]), __float_as_uint(r[2]), __float_as_uint(r[3]));
      sts128(t16 + SM_PART + 2048, __float_as_uint(r[4]), __float_as_uint(r[5]), __float_as_uint(r[6]), __float_as_uint(r[7]));
      bar_arrive(3, 256);
      PROF(1);
      bar_sync(9, 256);
      if (!(WE & 1) && s == NSEG - 1) break;
      if (!HR1) post_hint();
      if (w == 3 && s) publish(s);
      if ((WE & 1) && s == NSEG - 1) break;
      if (w == 1) {
        uint32_t m[8];
        lds128(t16 + SM_MAX - 512, m); lds128(t16 + SM_MAX, m + 4);
        const int em = (wexp(amax4(amax4(*(const __half2*)&m[0], m), m + 4)) >> 3) + (int)(lds32(sb + SC_UNSC + (s & 1) * 8) >> 23) - 15;
        const int ex = max(s ? em : 0, (int)lds32(sb + SC_XMAX + 4 * s)) - 127 + (int)lds32(sb + SC_EXPW);
        sts32(sb + SC_UNSC + (~s & 1) * 8, (127 + min(max(ex, -120), 120)) << 23);
        __syncwarp();
        if (elect_one()) mbar_arrive(sb + MB_S);
      }
      SCHED_FENCE(9);
      bar_sync(5, qk ? N5 : 256);
      PROF(2);
      import();
      xproj<0, 0, NII>(acc, wa, dA);
      if (NII < 18) {
        if (qk) bar_sync(7, 384);
        xproj<0, NII, 18>(acc, wa, dA);
        if (!qk) bar_sync(7, 384);
      } else {
        if (F10) WG_WAIT(0);
        bar_sync(10, 256);
        if (F10) SCHED_FENCE(17);
      }
      dA += (int64_t)(b2 ? XT >> 4 : -(XT >> 3));
      finish(s + ah);
      if (w != 3) bar_arrive(13, 384);
      PROF(6);
      SCHED_FENCE(14);
      if (NOB & 2) bar_arrive(14, 256);
      bar_sync(12, 256);
      PROF(7);
      xproj<1, 0, 18, true>(acc, wa, dA);
      if (!(NOB & 2)) bar_arrive(14, 256);
      b2 = b2 == 2 ? 0 : b2 + 1;
      s++;
      if (w == 3) {
        const uint32_t slot = s < lds32(sb + SC_EPO + 4) ? s & 7 : s;
        bar_sync(13, 384);
        export_seg(s, slot);
      }
      PROFP(8);
    }
    if (!qk) bar_arrive(5, 256);
    if (!(WE & 1) && w == 3) publish(NSEG - 1);
  } else {
    uint32_t km[4];
    auto send_km = [&]() {
      if (XP & (4 | 4096)) return;
      uint32_t t, u;
      lds64(sb + SC_TAG, t, u);
      t |= km[0] & ~1u; u += s * (NH * 4096);
      if (qk)
        asm volatile("{\n.reg .u32 o;\n.reg .u64 a;\nshr.u32 o, %0, 1;\nadd.u32 o, o, %1;\nmad.wide.u32 a, o, 1, %2;\nst.relaxed.gpu.global.v2.b32 [a], {%3,%4};\n}"
                     :: "r"(t16), "r"(u), "l"(g_km), "r"(t), "r"(km[1]) : "memory");
      else
        asm volatile("{\n.reg .u32 o;\n.reg .u64 a;\nadd.u32 o, %0, %1;\nmad.wide.u32 a, o, 1, %2;\nst.relaxed.gpu.global.v4.b32 [a], {%3,%4,%5,%6};\n}"
                     :: "r"(t16), "r"(u), "l"(g_km), "r"(t), "r"(km[1]), "r"(km[2]), "r"(km[3]) : "memory");
    };
#pragma unroll 1
    while (true) {
      do_export(BoolC<true>(), always);
      if (!qk && w == 2) send_v(s + 1, 0);
      PROFP(3);
      if (s == 8) STAMP(6);
      const uint32_t tl = ((t16 >> 8) ^ wg) & 1, am = (t16 & ~256u) - w * 256;
      const float un = __uint_as_float(lds32(sb + SC_UNSC + (s & 1) * 8));
      float r[8];
      if (qk) {
        uint32_t a0 = am + (tl ? SM_QM : SM_BLK + 8192 + (s & 3) * SEGB);
        float u0 = wg ? un * (SM_SCALE * LOG2E) : un, u1 = wg ? un : un * (SM_SCALE * LOG2E);
        PIN(a0); PIN(u0); PIN(u1);
        memproj(BoolC<true>(), 32, a0, u0, u1, r);
        const uint32_t p0 = pack_bf16(r[0], r[1]), p1 = pack_bf16(r[2], r[3]), p2 = pack_bf16(r[4], r[5]), p3 = pack_bf16(r[6], r[7]);
        stsm4(a0, p0, p1, p2, p3);
        bar_arrive(4, 256);
        km[0] = wg ? p2 : p0; km[1] = wg ? p3 : p1;
      } else {
        const uint32_t d0 = s < NSEG - 1 ? 0 : 2, d1 = s < NSEG - 1 ? 1 : 2;
        uint32_t r0 = mapa(t16 + SM_VM, d0), r1 = mapa(t16 + SM_VM, d1);
        PIN(r0); PIN(r1);
        memproj(BoolC<true>(), 34, r0 | r1, un, un, r);
        const uint32_t p0 = pack_bf16(r[0], r[1]), p1 = pack_bf16(r[2], r[3]), p2 = pack_bf16(r[4], r[5]), p3 = pack_bf16(r[6], r[7]);
        const uint32_t v0 = wg ? p2 : p0, v1 = wg ? p3 : p1, v2 = wg ? p0 : p2, v3 = wg ? p1 : p3;
        st_async4(r0, v0, v1, v2, v3, mapa(sb + MB_S, d0));
        st_async4(r1, v0, v1, v2, v3, mapa(sb + MB_S, d1));
        bar_arrive(5, 256);
        sts128(t16 + SM_VM, v0, v1, v2, v3);
        __syncwarp();
        if (elect_one()) mbar_arrive(sb + MB_S);
        km[0] = v0; km[1] = v1; km[2] = v2; km[3] = v3;
      }
      if (HR1) post_hint();
      if (!(WE & 2) && s == NSEG - 1) break;
      PROF(1);
      auto rearm = [&]() { mbar_wait(sb + MB_S, s & 1); if (elect_one()) mbar_expect(sb + MB_S, qk ? 640 + 2048 : 1280); __syncwarp(); };
      if ((WE & 2) && s == NSEG - 1 && w != 1) {
      } else if (w == 1) {
        if ((t16 & 384) == 0) stg_relaxed(tm.red + (RED_SLOT(s + 2) + RED_LINE(blockIdx.x)) + (t16 & 112), 0, 0, 0, 0);
        uint32_t base, own;
        lds64(sb + SC_EPO, base, own);
        if ((int)(lds32v(sb + SC_OFL) - base) < s - 7) sts32(sb + SC_EPO + 4, min(own, s + 1));
        if (elect_one()) bulk_load(sb + SC_OFL, tm.oflag + blockIdx.x * 128, 16, sb + MB_XS);
      } else if (w == 0) {
        const int tn = s + ah + 1;
        if (RFW) mbar_wait(sb + MB_S, s & 1);
        if (tn + 1 < NSEG && !(XP & 8) && elect_one()) {
          const int b0 = b2 == 2 ? 0 : b2 + 1;
          mbar_expect(sb + MB_X + 8 * b0, XT);
          tma_load3(sb + SM_X + b0 * XT, &tm.x, (tn + 1) * 32, sb + MB_X + 8 * b0);
        }
        if (tn < NSEG && (!(XP & 8) || tn < 3)) mbar_wait(sb + MB_X + 8 * b2, (tn / 3) & 1);
      } else if (w == 2) {
        if (!qk) { if (VW2 < 1) send_v(s + 1, 0); if (VW2 < 2) send_v(s + 1, 1); }
      } else if (qk || !NIC) {
        rearm();
      }
      __syncwarp();
      send_km();
      if ((WE & 2) && s == NSEG - 1) break;
      import();
      PROF(4);
      SCHED_FENCE(10);
      if (NIC) {
        if (qk) bar_sync(7, NII < 18 ? 384 : 256);
        xproj<0, 0, NIC>(acc, wa, dA);
        if (!qk) { if (w == 3) rearm(); bar_sync(7, NII < 18 ? 384 : 256); }
      } else {
        bar_sync(7, NII < 18 ? 384 : 256);
      }
      if (NOB & 1) bar_arrive(12, 256);
      xproj<0, NIC, 18>(acc, wa, dA);
      if (!(NOB & 1)) bar_arrive(12, 256);
      dA += (int64_t)(b2 ? XT >> 4 : -(XT >> 3));
      finish(s + ah);
      if (qk && w == 0) wait_v(s + 1);
      bar_arrive(13, 384);
      PROF(6);
      SCHED_FENCE(13);
      bar_sync(14, 256);
      PROF(7);
      xproj<1, 0, 18>(acc, wa, dA);
      b2 = b2 == 2 ? 0 : b2 + 1;
      s++;
      PROFP(8);
    }
    if (!(WE & 2)) {
      send_km();
      PIN(t16);
      if (t16 - sb < 128) stg_relaxed(tm.red + (RED_SLOT(NSEG + 1) + RED_LINE(head_id() * 3 + rank)) + (t16 & 112), 0, 0, 0, 0);
    }
  }
  bar_arrive(0, 384);
  STAMP(3);
  cluster_sync();
  STAMP(4);
}

DI void attn_role(const uint32_t sb, unsigned char* smem_raw, const RMaps& tm, const uint32_t RANK, const bf16* __restrict__ x, const bf16* __restrict__ mem0,
                  const int w, const int lane) {
  const int t2 = w * 32 + lane;
  uint32_t wo[8][4], w1[8][4];
  const uint32_t wo_lane = sb + ((lane & 7) + ((lane >> 4) << 3)) * 128 + (((w + 4 * ((lane >> 3) & 1)) ^ (lane & 7)) << 4);
  unsigned char* const g_red = tm.red;
  {
    const uint32_t tag = *(volatile unsigned*)&g_epoch + 1;
    QSTAMP(0);
    bar_sync(0, 160);
    QSTAMP(1);
    cluster_arrive();
    __half2 hx = __float2half2_rn(0.f);
    if (t2 == 0) { sts32(sb + SC_OFL, (tag - 1) * NSEG); sts64(sb + SC_EPO, (tag - 1) * NSEG + 1, NSEG); sts64(sb + SC_TAG, tag & 1, blockIdx.x / 3 * 4096 + (RANK < 2 ? RANK * 1024 - (sb >> 1) : 2048 - sb)); sts32(sb + SC_UNSC, __float_as_uint(1.f)); sts128(sb + SC_DEAD, 0, 0, 0, 0x3f800000u); sts64(sb + SC_FPAR, 0, 0); sts128(sb + SC_ONES, 0x3f803f80u, 0x3f803f80u, 0x3f803f80u, 0x3f803f80u); }
    WSTAMP(27);
    uint32_t q[8] = {0, 0, 0, 0, 0, 0, 0, 0};
    QSTAMP(2);
    mbar_wait(sb + MB_WO3, 0);
    QSTAMP(3);
    uint32_t mv[5][4];
#pragma unroll
    for (int i = 0; i < 5; i++) {
      ldsm4(mv[i], sb + SM_M0 + (lane & 7) * (DM * 2) + min(w + 4 * i, 17) * 64 + (lane >> 3) * 16);
      if (blockIdx.x == 0) hx = amax4(hx, mv[i]);
    }
#pragma unroll
    for (int k = 0; k < 8; k++) {
      ldsm4t(wo[k], wo_lane + SM_WO3 + k * 2048); ldsm4t(w1[k], wo_lane + SM_WOST + k * 2048);
#pragma unroll
      for (int i = 0; i < 4; i++) { sq_acc(q[i], wo[k][i]); sq_acc(q[i], w1[k][i]); }
    }
    bar_sync(6, 128);
#pragma unroll
    for (int k = 0; k < 8; k++) sts128(sb + SM_WO3 + t2 * 16 + k * 2048, wo[k][0], wo[k][1], wo[k][2], wo[k][3]);
#pragma unroll
    for (int i = 0; i < 5; i++) {
      const int c = (w + 4 * i) * 32;
      if (c < DM) stsm4t(sb + SM_MEM + (c + c / 192 * 64 + lane) * 16, mv[i][0], mv[i][1], mv[i][2], mv[i][3]);
    }
    bar_arrive(1, 256); bar_arrive(2, 256); bar_arrive(9, 256);
    QSTAMP(4);
    mbar_wait(sb + MB_WO, 0);
    QSTAMP(5);
#pragma unroll
    for (int k = 0; k < 8; k++) ldsm4t(wo[k], wo_lane + SM_X + XT + k * 2048);
    fence_async();
    bar_sync(6, 128);
    if (t2 == 32) tma_load3(sb + SM_X + XT, &tm.x, 32, sb + MB_X + 8);
    __syncwarp();
#pragma unroll
    for (int k = 0; k < 8; k++)
#pragma unroll
      for (int i = 0; i < 4; i++) sq_acc(q[4 + i], wo[k][i]);
    float ss = 0.f;
#pragma unroll
    for (int i = 0; i < 8; i++) ss += bf_lo(q[i]) + bf_hi(q[i]);
    ss = warp_sum(ss);
    if (lane == 0) sts32(sb + SC_SS + 4 * (8 + w), __float_as_uint(ss));
    if (blockIdx.x < NSEG) {
      mbar_wait(sb + MB_XS, 0);
#pragma unroll
      for (int i = 0; i < 18; i++) { uint32_t v[4]; lds128(sb + SM_X + 2 * XT + t2 * 16 + i * 2048, v); hx = amax4(hx, v); }
      fence_async();
      bar_sync(6, 128);
      if (t2 == 32) tma_load3(sb + SM_X + 2 * XT, &tm.x, 64, sb + MB_X + 16);
      __syncwarp();
    }
    sts32(sb + SC_SS + 4 * (12 + w), wexp(hx));
    QSTAMP(6);
    bar_sync(11, 384);
    QSTAMP(7);
    if (t2 == 0) {
      float a[16];
#pragma unroll
      for (int i = 0; i < 4; i++) lds128f(sb + SC_SS + 16 * i, &a[4 * i]);
      stg_relaxed(&g_stats[blockIdx.x * 2], __float_as_uint(((a[0] + a[1]) + (a[2] + a[3])) + ((a[4] + a[5]) + (a[6] + a[7]))),
                  __float_as_uint((a[8] + a[9]) + (a[10] + a[11])),
                  max(max(__float_as_uint(a[12]), __float_as_uint(a[13])), max(__float_as_uint(a[14]), __float_as_uint(a[15]))), tag);
    }
    __syncwarp();
    WSTAMP(24);
    QSTAMP(8);
    cluster_wait();
    QSTAMP(9);
    if (w == 0) {
      uint4 v[3];
      int n = 0;
      while (true) {
#pragma unroll
        for (int i = 0; i < 3; i++) v[i] = ldg_relaxed(&g_stats[(i * 32 + lane) * 2]);
        if (__all_sync(0xffffffffu, v[0].w == tag && v[1].w == tag && v[2].w == tag) || ++n > SPIN_LIMIT) break;
        __nanosleep(100);
      }
      WSTAMP(25);
      QSTAMP(10);
      const float sv = warp_sum(__uint_as_float(v[0].x) + __uint_as_float(v[1].x) + __uint_as_float(v[2].x));
      const float so = warp_sum(__uint_as_float(v[0].y) + __uint_as_float(v[1].y) + __uint_as_float(v[2].y));
      const int expW = ((int)(__float_as_uint(sv) >> 23) + (int)(__float_as_uint(so) >> 23) - 254 + 2 + 10 + 1) >> 1;
      sts32(sb + SC_XMAX + 4 * lane, v[0].z); sts32(sb + SC_XMAX + 128 + 4 * lane, v[1].z);
      sts32(sb + SC_EXPW, expW + 1 - 15);
      if (blockIdx.x == 0 && lane == 0) *(volatile unsigned*)&g_epoch = tag;
      sts32(sb + SC_FPAR + 4, 1);
    } else if (w < 3) {
      const uint32_t u = blockIdx.x >> 4;
      unsigned char* const z = g_red + 98304 + (blockIdx.x & 15) * 128 + (u & 1) * 2048 + (u & 6) * 4096 + (((u >> 1) ^ w) & 1) * 4096 + lane * 4;
      stg_relaxed32(z, 0);
      uint32_t best = 0xffffffffu;
#pragma unroll 1
      for (int i = 0; i < 64; i++) {
        uint32_t dt;
        asm volatile("{\n.reg .pred p;\n.reg .u32 c, v;\nmov.u32 c, %%clock;\n"
                     "atom.relaxed.gpu.global.exch.b32 v, [%1], 0;\nsetp.eq.u32 p, v, 0;\nmov.u32 %0, 0;\n@p mov.u32 %0, %%clock;\nsub.u32 %0, %0, c;\n}"
                     : "=r"(dt) : "l"(z) : "memory");
        best = min(best, dt);
        if (lds32v(sb + SC_FPAR + 4) && i >= NPROBE - 1) break;
      }
      sts32(sb + SC_LAT + (w - 1) * 4, best);
    }
    QSTAMP(11);
    bar_sync(13, 384);
    bar_arrive(0, 384);
    QSTAMP(12);
    WSTAMP(26);
  }

  const uint32_t nh = __shfl_sync(0xffffffffu, near_half(sb), 0);
  uint32_t l16 = sb + lane * 16;
  PIN(l16);
#define LV ((l16 >> 4) & 31)
#define fence_reg l16
  const uint32_t red_lo = (uint32_t)(uint64_t)g_red, red_hi = (uint32_t)((uint64_t)g_red >> 32);
  uint32_t lp;
  auto slot = [&](int s, uint32_t c, uint32_t ofs) {
    const uint32_t lo = lp | (red_lo + ((w >> 1) * 4 + (w & 1) * 2 + ((w ^ c) & 1)) * 4096 + RED_SLOT(s) + ofs);
    uint64_t a; asm("mov.b64 %0, {%1, %2};" : "=l"(a) : "r"(lo), "r"(red_hi));
    return (unsigned char*)a;
  };
  const uint32_t always = __shfl_sync(0xffffffffu, lds32(sb + SC_DEAD + 12), 0);
  const int mode0 = RANK < 2 ? w : w | 4;
  auto hint_addr = [&](int s) { return min(LV, 23u) * 4 + (red_lo + HINT_OFF + nh * 4096 + w * 16384 + RED_SLOT(s)); };
  auto load_hints = [&](uint32_t lo) {
    uint64_t a; asm("mov.b64 %0, {%1, %2};" : "=l"(a) : "r"(lo), "r"(red_hi));
    return ldg_relaxed32((const void*)a);
  };
  int s = 0;
  bool bad = false;
#pragma unroll 1
  while (true) {
    const uint32_t par = s & 1;
    uint32_t vx[4][4], hints;
    auto load_vx = [&]() {
      const uint32_t va = l16 + (RANK < 2 ? SM_VC + par * 8192 : SM_BLK + (s & 3) * SEGB) + w * 1024 + ((LV >> 3) & 1) * 384 - (LV >> 4) * 128;
#pragma unroll
      for (int i = 0; i < 4; i++) ldsm4(vx[i], va + (i & 1) * 4096 + (i >> 1) * 256);
    };
    auto retire = [&](uint32_t x) {
      asm volatile("{\n.reg .pred p;\nsetp.eq.u32 p, %0, 0;\n@p exit;\n}" :: "r"(vx[0][0] | vx[1][0] | vx[2][0] | vx[3][0] | x) : "memory");
    };
    auto scores = [&](auto memkeys, auto first, float* sc) {
      constexpr bool MK = decltype(memkeys)::value, FIRST = decltype(first)::value;
      uint32_t kb[4][4], qb[2][4];
      const uint32_t m = LV >> 3;
      uint32_t kaddr = l16 + SM_BLK + 4096 + (s & 3) * SEGB + w * 2048 + (m & 1) * (MK ? 128 : 896) - (m >> 1) * 128;
      if (MK) { PIN(kaddr); }
      else {
#pragma unroll
        for (int k = 0; k < 4; k++) ldsm4t(kb[k], kaddr + k * 256);
      }
      if (FIRST) { load_vx(); retire(MK ? kaddr : kb[0][0] | kb[1][0] | kb[2][0] | kb[3][0] | l16); bar_sync(4, 256); PROF(4); }
      ldsm4t(qb[0], l16 + SM_QM);
      if (MK) ldsm4t(kb[0], kaddr);
      ldsm4t(qb[1], l16 + SM_QM + 512);
      if (MK) ldsm4t(kb[2], kaddr + 512);
      float c[4][4];
      mma16816z(c[0], kb[0], qb[0][0], qb[0][1]); mma16816z(c[1], kb[MK ? 0 : 1], qb[0][2], qb[0][3]);
      mma16816z(c[2], kb[2], qb[1][0], qb[1][1]); mma16816z(c[3], kb[MK ? 2 : 3], qb[1][2], qb[1][3]);
      if (FIRST && B5POS == 0) bar_arrive(5, N5);
#pragma unroll
      for (int i = 0; i < (MK ? 2 : 4); i++) sc[i] = ((c[0][i] + c[1][MK ? i + 2 : i]) + c[2][i]) + c[3][MK ? i + 2 : i];
    };
    auto send = [&](auto memkeys) {
      constexpr bool MK = decltype(memkeys)::value;
      constexpr int N = MK ? 1 : 2;
      const uint32_t sa = sb + LV * 4 + SM_E + (MK ? 1024 + RANK * 128 : RANK * 512 + w * 256);
      uint32_t ra[N][2], mb[N][2];
#pragma unroll
      for (int i = 0; i < N; i++)
#pragma unroll
        for (int j = 0; j < 2; j++) {
          ra[i][j] = mapa(sa + i * 128, j ? 2 : RANK ^ 1); mb[i][j] = mapa(sb + MB_S, j ? 2 : RANK ^ 1);
          PIN(ra[i][j]);
        }
      float sc[4];
      scores(memkeys, BoolC<true>(), sc);
      uint32_t e[N];
#pragma unroll
      for (int i = 0; i < N; i++) {
        e[i] = pack_bf16(ex2(sc[2 * i]), ex2(sc[2 * i + 1]));
        if (!(fmaxf(fabsf(sc[2 * i]), fabsf(sc[2 * i + 1])) <= E_LIM)) e[i] = 0x7fff7fffu;
        st_async1(ra[i][0], e[i], mb[i][0]);
        st_async1(ra[i][1], e[i], mb[i][1]);
      }
#pragma unroll
      for (int i = 0; i < N; i++) sts32(sa + i * 128, e[i]);
      __syncwarp();
      if (l16 == sb) mbar_arrive(sb + MB_S);
      PROF(5);
    };
    const int mode = bad ? 8 : mode0;
    if (mode < 2) {
      send(BoolC<false>());
    } else if (mode == 2) {
      send(BoolC<true>());
    } else if (mode == 8) {
      load_vx();
      retire(l16);
      const uint32_t fp = lds32(sb + SC_FPAR);
      bar_sync(6, 128);
      if (w == 0 && l16 == sb) { sts32(sb + SC_FPAR, fp ^ 1); mbar_expect(sb + MB_F, 3072); }
      if (RANK < 2 && w < 3) {
        float sc[4] = {0.f, 0.f, 0.f, 0.f};
        if (w < 2) scores(BoolC<false>(), BoolC<false>(), sc); else scores(BoolC<true>(), BoolC<false>(), sc);
#pragma unroll 1
        for (int r = 0; r < 3; r++)
          st_async4(mapa(l16 + SM_FB + RANK * 1536 + w * 512, r), __float_as_uint(sc[0]), __float_as_uint(sc[1]), __float_as_uint(sc[2]), __float_as_uint(sc[3]), mapa(sb + MB_F, r));
      }
      mbar_wait(sb + MB_F, fp);
      float a[12];
#pragma unroll
      for (int j = 0; j < 3; j++) {
        float b[4];
        lds128f(l16 + SM_FB + j * 512, a + 4 * j); lds128f(l16 + SM_FB + 1536 + j * 512, b);
#pragma unroll
        for (int i = 0; i < 4; i++) a[4 * j + i] += b[i];
      }
      float m0 = fmaxf(fmaxf(fmaxf(a[0], a[2]), fmaxf(a[4], a[6])), a[8]), m1 = fmaxf(fmaxf(fmaxf(a[1], a[3]), fmaxf(a[5], a[7])), a[9]);
#pragma unroll
      for (int o = 4; o < 32; o <<= 1) { m0 = fmaxf(m0, __shfl_xor_sync(0xffffffffu, m0, o)); m1 = fmaxf(m1, __shfl_xor_sync(0xffffffffu, m1, o)); }
#pragma unroll
      for (int i = 0; i < 5; i++) {
        const uint32_t ea = sb + SM_E + LV * 4 + (i < 4 ? i * 128 : 1024);
        sts32(ea, pack_bf16(ex2(a[2 * i] - m0), ex2(a[2 * i + 1] - m1)));
        sts32(ea + (i < 4 ? 512 : 128), 0x3f803f80u);
      }
      __syncwarp();
    } else {
      load_vx();
      if (mode == 3) bar_arrive(4, 256);
      retire(l16 + 1);
    }
    {
      uint32_t wa[4], wb[4], oc[4];
      constexpr int WS = 2048;
      const uint32_t w3a = l16 + SM_WO3 + w * 512;
      lds128(w3a + KP(0) * WS, wa); lds128(w3a + KP(1) * WS, wb); lds128(sb + SC_ONES, oc);
      if (B5POS == 1 && mode < 3) bar_arrive(5, N5);
      uint32_t e[10], p[5], vm[4], ob[4];
      float o0[4], o1[4], f[3][2][4], rs[4];
      reserve2(vm); reserve2(vm + 2); reserve2(e + 8);
      hints = hint_addr(s);
      PIN(hints);
      if (CLR & 2) asm volatile("{\n.reg .pred p;\nsetp.eq.u32 p, %0, 0;\n@p exit;\n}" :: "r"(wa[0] | wb[0] | oc[0] | hints) : "memory");
      mbar_wait(sb + MB_S, par);
      PROF(6);
      ldsm4t(e, l16 + SM_E); ldsm2t_in(e + 8, l16 + SM_E + 1024, always); ldsm4t(e + 4, l16 + SM_E + 512);
      lds128_in(vm, l16 + w * 512 + SM_VM, always);
      const float scl = __uint_as_float(lds32(sb + SC_UNSC + 8 - par * 8));
      if (HLP == 0) hints = load_hints(hints);
      if (GF & 1) SCHED_FENCE(4);
#pragma unroll
      for (int i = 0; i < 4; i++) p[i] = mul_bf16(e[i], e[4 + i]);
      p[4] = mul_bf16(e[8], e[9]);
      if (MO & 4) {
        float a0[4], a1[4];
        mma16816z(o0, vx[0], p[0], p[1]); mma16816z(o1, vx[1], p[0], p[1]);
        mma16816z(a0, vx[2], p[2], p[3]); lds128_in(vx[2], w3a + KP(2) * WS, always);
        mma16816z(a1, vx[3], p[2], p[3]); lds128_in(vx[3], w3a + KP(3) * WS, always);
        mma1688(o0, vm[0], vm[1], p[4]); mma1688(o1, vm[2], vm[3], p[4]);
        mma16816z(rs, oc, p[0], p[1]); mma16816(rs, oc, p[2], p[3]); mma1688(rs, oc[0], oc[1], p[4]);
#pragma unroll
        for (int i = 0; i < 4; i++) { o0[i] += a0[i]; o1[i] += a1[i]; }
      } else {
      mma16816z(o0, vx[0], p[0], p[1]); mma16816z(o1, vx[1], p[0], p[1]); mma16816z(rs, oc, p[0], p[1]);
      mma16816(o0, vx[2], p[2], p[3]); lds128_in(vx[2], w3a + KP(2) * WS, always);
      mma16816(o1, vx[3], p[2], p[3]); lds128_in(vx[3], w3a + KP(3) * WS, always);
      mma16816(rs, oc, p[2], p[3]);
      mma1688(o0, vm[0], vm[1], p[4]); mma1688(o1, vm[2], vm[3], p[4]); mma1688(rs, oc[0], oc[1], p[4]);
      }
      stsm4(l16 + w * 512 + SM_OB, pack_bf16(o0[0], o0[1]), pack_bf16(o0[2], o0[3]), pack_bf16(o1[0], o1[1]), pack_bf16(o1[2], o1[3]));
      bar_sync(6, 128);
      PROF(7);
      ldsm4t_in(oc, l16 + SM_OB, always);
      bad = __any_sync(0xffffffffu, !(rs[0] + rs[1] > 0.f) && !bad);
      rs[0] *= scl; rs[1] *= scl;
      asm volatile("{\n.reg .pred p;\nsetp.ne.u32 p, %1, 0;\n@p rcp.approx.ftz.f32 %0, %0;\n}" : "+f"(rs[0]) : "r"(always));
      asm volatile("{\n.reg .pred p;\nsetp.ne.u32 p, %1, 1;\n@p rcp.approx.ftz.f32 %0, %0;\n}" : "+f"(rs[1]) : "r"(always));
      asm volatile("lop3.b32 %0, %1, %2, %3, 0xfe;" : "=r"(lp) : "r"((l16 & 128) * 2), "r"((l16 & 256) * 4), "r"(l16 & 112));
      if (bad) continue;
      ldsm4t(ob, l16 + SM_OB + 512);
      if (HLP == 1) hints = load_hints(hints);
      mma16816z(f[2][0], wa, oc[0], oc[1]); mma16816z(f[2][1], wb, oc[2], oc[3]);
      mma16816z(f[0][0], wo[0], oc[0], oc[1]); mma16816z(f[0][1], wo[4], oc[2], oc[3]);
      mma16816z(f[1][0], w1[0], oc[0], oc[1]); mma16816z(f[1][1], w1[4], oc[2], oc[3]);
      ldsm4t_in(oc, l16 + SM_OB + 1024, always);
      mma16816(f[2][0], vx[2], ob[0], ob[1]); lds128_in(vx[2], w3a + KP(4) * WS, always);
      mma16816(f[2][1], vx[3], ob[2], ob[3]); lds128_in(vx[3], w3a + KP(5) * WS, always);
      mma16816(f[0][0], wo[1], ob[0], ob[1]); mma16816(f[0][1], wo[5], ob[2], ob[3]);
      mma16816(f[1][0], w1[1], ob[0], ob[1]); mma16816(f[1][1], w1[5], ob[2], ob[3]);
      ldsm4t_in(ob, l16 + SM_OB + 1536, always);
      mma16816(f[0][0], wo[2], oc[0], oc[1]); mma16816(f[0][1], wo[6], oc[2], oc[3]);
      mma16816(f[2][0], vx[2], oc[0], oc[1]); lds128_in(vx[2], w3a + KP(6) * WS, always);
      mma16816(f[2][1], vx[3], oc[2], oc[3]); lds128_in(vx[3], w3a + KP(7) * WS, always);
      mma16816(f[1][0], w1[2], oc[0], oc[1]); mma16816(f[1][1], w1[6], oc[2], oc[3]);
      mma16816(f[0][0], wo[3], ob[0], ob[1]); mma16816(f[0][1], wo[7], ob[2], ob[3]);
      mma16816(f[1][0], w1[3], ob[0], ob[1]); mma16816(f[1][1], w1[7], ob[2], ob[3]);
      mma16816(f[2][0], vx[2], ob[0], ob[1]); mma16816(f[2][1], vx[3], ob[2], ob[3]);
      bar_arrive(7, NII < 18 ? 384 : 256);
      lds128_in(ob, sb + SC_DEAD, always);
      uint32_t h[3][2];
#pragma unroll
      for (int j = 0; j < 3; j++)
#pragma unroll
        for (int i = 0; i < 2; i++)
        {
          scale_sum(f[j][1][2 * i], f[j][0][2 * i], rs[0], always); scale_sum(f[j][1][2 * i + 1], f[j][0][2 * i + 1], rs[1], always);
          h[j][i] = pack_f16(f[j][1][2 * i], f[j][1][2 * i + 1]);
        }
      const uint32_t rofs = RANK * 32768;
      red_f16x8(slot(s, RANK >> 1, rofs), h[0][0], h[1][0], h[2][0], 0x3c00u);
      red_f16x8(slot(s, (RANK >> 1) ^ 1, rofs), h[0][1], h[1][1], h[2][1], 0x3c00u);
      if (HLP == 2) hints = load_hints(hints);
      if (NII == 18) bar_arrive(10, 256);
      SCHED_FENCE(5);
      l16 += ob[B7R];
    }
    {
    PROF(8);
    const uint32_t ma0 = l16 + SM_MEM + w * 128 + (LV >> 3) * 896 + nh * 512;
    const unsigned char* const sl[2] = {slot(s, nh, 0), slot(s, nh ^ 1, 0)};
    uint32_t dl = gtime() - 1984;
    uint32_t late = latest_hint(hints, dl, s);
    if (late >= 64) {
      int n = 0;
#pragma unroll 1
      do {
        hints = load_hints(hint_addr(s));
        dl = gtime() - 1984;
        late = latest_hint(hints, dl, s);
      } while (late >= 64 && ++n < SPIN_LIMIT);
    }
    dl += late * 32 + tm.poll;
    PROF(9);
    {
      auto wait_until = [&](uint32_t t) {
        asm volatile("{\n.reg .pred p;\n.reg .s32 c;\n.reg .u64 t;\nTL: mov.u64 t, %%globaltimer;\ncvt.u32.u64 c, t;\nsub.s32 c, c, %0;\nsetp.lt.s32 p, c, 0;\n@p bra.uni TL;\n}" :: "r"(t + (l16 & 15)) : "memory");
      };
      uint4 v[2][3];
      auto load = [&](int c) {
#pragma unroll
        for (int r = 0; r < 3; r++) v[c][r] = ldg_relaxed(sl[c ^ (r >> 1)] + r * 32768);
      };
      auto decode = [&](int c, int n) {
        uint32_t q[9];
        __half2 hm;
        const uint32_t ma = ma0 ^ (c * 512);
#pragma unroll
        for (int i = 0; i < 9; i++) {
          const uint32_t h = i % 3 == 0 ? v[c][i / 3].x : (i % 3 == 1 ? v[c][i / 3].y : v[c][i / 3].z);
          const float2 f = __half22float2(*(const __half2*)&h);
          q[i] = pack_bf16(f.x, f.y);
          hm = i ? __hmax2(hm, __habs2(*(const __half2*)&h)) : __habs2(*(const __half2*)&h);
        }
#pragma unroll
        for (int r = 0; r < 3; r++) stsm4(ma + r * 4096, q[3 * r], q[3 * r + 1], q[3 * r + 2], r < 2 ? v[c][r].w : *(const uint32_t*)&hm);
        const bool done = __all_sync(0xffffffffu, v[c][0].w == 0x5000u && v[c][1].w == 0x5000u && v[c][2].w == 0x5000u) || n > SPIN_LIMIT;
        asm volatile("{\n.reg .pred p;\nsetp.ne.u32 p, %0, 0;\n@p bar.arrive %1, 256;\n}" :: "r"((int)done), "r"(1 + c) : "memory");
        return done;
      };
      if (LEAD) { wait_until(dl - LEAD); load(1); }
      int n = MO & 1 ? l16 & 15 : 0;
      if (MO & 1) PIN(n);
      if (MO & 2) {
        const uint32_t t = __shfl_sync(0xffffffffu, dl, 0);
        asm volatile("{\n.reg .pred p;\n.reg .s32 c;\nTL: mov.u32 c, %%globaltimer_lo;\nsub.s32 c, c, %0;\nsetp.lt.s32 p, c, 0;\n@p bra.uni TL;\n}" :: "r"(t) : "memory");
      } else wait_until(dl);
      PROF(10);
#pragma unroll 1
      do {
        load(0);
        if (!LEAD) load(1);
        asm volatile("{\n.reg .pred p;\nsetp.eq.u32 p, %0, 0;\n@p bar.sync 13, 384;\n}" :: "r"(n) : "memory");
      } while (!decode(0, n++));
      PROF(11);
#pragma unroll 1
      while (!decode(1, n++)) load(1);
      bar_arrive(9, 256);
      PROF(12);
    }
    PROF(13);
    if (++s == NSEG - 1) break;
    }
  }
#undef fence_reg
  if (RANK < 2) bar_arrive(4, 256);
  bar_sync(0, 384);
  cluster_sync();
}

__global__ void __cluster_dims__(3, 1, 1) __launch_bounds__(384, 1)
rec_kernel(const __grid_constant__ RMaps tm, const bf16* __restrict__ x, const bf16* __restrict__ mem0) {
  extern __shared__ __align__(1024) unsigned char smem_raw[];
  const uint32_t sb = smem_u32(smem_raw);
  const int tid = threadIdx.x, lane = tid & 31;
  const int wg = __shfl_sync(0xffffffffu, tid >> 7, 0);
  const int w = __shfl_sync(0xffffffffu, (tid >> 5) & 3, 0);
  uint32_t rank; asm("mov.u32 %0, %%cluster_ctarank;" : "=r"(rank));
  STAMP(0);
  asm volatile("griddepcontrol.launch_dependents;" ::: "memory");
    if (tid == 0) {
      const int h = blockIdx.x / 3;
      mbar_init(sb + MB_XS, 1);
      for (int i = 0; i < 3; i++) { mbar_init(sb + MB_W + 8 * i, 1); mbar_init(sb + MB_X + 8 * i, 1); }
      mbar_init(sb + MB_WO3, 1);
      fence_async();
      load_w(sb, tm, rank, 0);
      mbar_expect(sb + MB_X, XT);
      tma_load3(sb + SM_X, &tm.x, 0, sb + MB_X);
      if (WPOS == 2) load_w(sb, tm, rank, 1);
      mbar_expect(sb + MB_WO3, 32768 + 8 * DM * 2);
      tma_load(sb + SM_WOST, &tm.wo, rank * 192 + 64, h * DH, sb + MB_WO3);
      tma_load(sb + SM_WO3, &tm.wo, rank * 192 + 128, h * DH, sb + MB_WO3);
      bulk_load(sb + SM_M0, mem0, 8 * DM * 2, sb + MB_WO3);
      if (WOPF) tma_prefetch(&tm.wo, rank * 192, h * DH);
      if (WPOS == 1) load_w(sb, tm, rank, 1);
      load_w(sb, tm, rank, 2);
      mbar_init(sb + MB_WO, 1);
      mbar_init(sb + MB_S, rank < 2 ? 5 : 6);
      mbar_init(sb + MB_F, 1);
      mbar_init(sb + MB_VX, 1); mbar_init(sb + MB_VX + 8, 1);
      asm volatile("fence.mbarrier_init.release.cluster;" ::: "memory");
      fence_async();
      mbar_expect(sb + MB_X + 8, XT); mbar_expect(sb + MB_X + 16, XT);
      mbar_expect(sb + MB_WO, 16384); mbar_expect(sb + MB_XS, XT);
      mbar_expect(sb + MB_S, rank < 2 ? 640 + 2048 : 1280);
      mbar_expect(sb + MB_VX, 8192); mbar_expect(sb + MB_VX + 8, 8192);
    }
  __syncwarp();
  if (wg < 2) {
    asm volatile("setmaxnreg.inc.sync.aligned.u32 192;");
    __syncwarp();
    QSTAMP(0);
    if (tid < 32) bar_arrive(0, 160);
    QSTAMP(1);
    proj_role(sb, tm, x, rank, wg, w, lane);
  } else {
    asm volatile("setmaxnreg.dec.sync.aligned.u32 120;");
    attn_role(sb, smem_raw, tm, rank, x, mem0, w, lane);
  }
}

constexpr int NAUX = 36;
constexpr int A_ST = 6, A_STAGE = 8192 + 12288, A_W8 = A_ST * A_STAGE, A_EXC = A_W8 + A_ST * 1536, A_ROWS = 57;
constexpr int A_IN = A_EXC + 8 * 2304, A_INB = 3 * SEGB, A_OST = A_IN + 2 * A_INB, A_P = A_OST + 8192, A_G = A_P + 3072;
constexpr int A_BAR = A_G + 1024;
constexpr int A_XT = A_BAR + 1024, A_XW = A_XT;
constexpr int A_TOTAL = A_XT + 4096;
static_assert(A_IN % 1024 == 0 && A_XT % 1024 == 0 && A_IN >= 4 * XT && A_IN + 64 * DM * 2 <= A_BAR && A_TOTAL <= 232448, "side kernel shared memory");
struct AMaps { CUtensorMap x, wa, wa8, o, o3, o16, wob, woa, woa16; const unsigned char* red; uint32_t poll; };

DI void wgmma_n192_ss_nt(float* d, uint64_t da, uint64_t db, int acc) {
  asm volatile("{\n.reg .pred p;\nsetp.ne.b32 p, %98, 0;\n"
               "wgmma.mma_async.sync.aligned.m64n192k16.f32.bf16.bf16 {"
               "%0,%1,%2,%3,%4,%5,%6,%7,%8,%9,%10,%11,%12,%13,%14,%15,%16,%17,%18,%19,%20,%21,%22,%23,%24,%25,%26,%27,%28,%29,%30,%31,"
               "%32,%33,%34,%35,%36,%37,%38,%39,%40,%41,%42,%43,%44,%45,%46,%47,%48,%49,%50,%51,%52,%53,%54,%55,%56,%57,%58,%59,%60,%61,%62,%63,"
               "%64,%65,%66,%67,%68,%69,%70,%71,%72,%73,%74,%75,%76,%77,%78,%79,%80,%81,%82,%83,%84,%85,%86,%87,%88,%89,%90,%91,%92,%93,%94,%95"
               "}, %96, %97, p, 1, 1, 0, 1;\n}\n"
               : ACC8(d, 0), ACC8(d, 8), ACC8(d, 16), ACC8(d, 24), ACC8(d, 32), ACC8(d, 40), ACC8(d, 48), ACC8(d, 56),
                 ACC8(d, 64), ACC8(d, 72), ACC8(d, 80), ACC8(d, 88) : "l"(da), "l"(db), "r"(acc));
}
DI void wgmma_n24_ss_nt(float* d, uint64_t da, uint64_t db, int acc) {
  asm volatile("{\n.reg .pred p;\nsetp.ne.b32 p, %14, 0;\n"
               "wgmma.mma_async.sync.aligned.m64n24k16.f32.bf16.bf16 {%0,%1,%2,%3,%4,%5,%6,%7,%8,%9,%10,%11}, %12, %13, p, 1, 1, 0, 1;\n}\n"
               : ACC8(d, 0), "+f"(d[8]), "+f"(d[9]), "+f"(d[10]), "+f"(d[11]) : "l"(da), "l"(db), "r"(acc));
}
DI void tma_load3d(uint32_t dst, const CUtensorMap* m, int c0, int c1, int c2, uint32_t mb) {
  asm volatile("cp.async.bulk.tensor.3d.shared::cluster.global.mbarrier::complete_tx::bytes [%0], [%1, {%3, %4, %5}], [%2];"
               :: "r"(dst), "l"(m), "r"(mb), "r"(c0), "r"(c1), "r"(c2) : "memory");
}
DI uint32_t trans8(uint32_t x) { uint32_t r; asm("movmatrix.sync.aligned.m8n8.trans.b16 %0, %1;" : "=r"(r) : "r"(x)); return r; }
DI void wgmma_n40_ss(float* d, uint64_t da, uint64_t db, int acc) {
  asm volatile("{\n.reg .pred p;\nsetp.ne.b32 p, %22, 0;\n"
               "wgmma.mma_async.sync.aligned.m64n40k16.f32.bf16.bf16 {%0,%1,%2,%3,%4,%5,%6,%7,%8,%9,%10,%11,%12,%13,%14,%15,%16,%17,%18,%19}, "
               "%20, %21, p, 1, 1, 1, 1;\n}\n"
               : ACC8(d, 0), ACC8(d, 8), "+f"(d[16]), "+f"(d[17]), "+f"(d[18]), "+f"(d[19]) : "l"(da), "l"(db), "r"(acc));
}
DI uint2 ldg_relaxed64(const void* p) {
  uint2 v; asm volatile("ld.relaxed.gpu.global.v2.b32 {%0,%1}, [%2];" : "=r"(v.x), "=r"(v.y) : "l"(p) : "memory"); return v;
}
template <int ST> DI void ldg8x64(uint32_t* m, const void* p) {
  asm volatile("ld.relaxed.gpu.global.v2.b32 {%0,%1}, [%16];\nld.relaxed.gpu.global.v2.b32 {%2,%3}, [%16 + %17];\n"
               "ld.relaxed.gpu.global.v2.b32 {%4,%5}, [%16 + %18];\nld.relaxed.gpu.global.v2.b32 {%6,%7}, [%16 + %19];\n"
               "ld.relaxed.gpu.global.v2.b32 {%8,%9}, [%16 + %20];\nld.relaxed.gpu.global.v2.b32 {%10,%11}, [%16 + %21];\n"
               "ld.relaxed.gpu.global.v2.b32 {%12,%13}, [%16 + %22];\nld.relaxed.gpu.global.v2.b32 {%14,%15}, [%16 + %23];"
               : "=r"(m[0]), "=r"(m[1]), "=r"(m[2]), "=r"(m[3]), "=r"(m[4]), "=r"(m[5]), "=r"(m[6]), "=r"(m[7]),
                 "=r"(m[8]), "=r"(m[9]), "=r"(m[10]), "=r"(m[11]), "=r"(m[12]), "=r"(m[13]), "=r"(m[14]), "=r"(m[15])
               : "l"(p), "n"(ST), "n"(2 * ST), "n"(3 * ST), "n"(4 * ST), "n"(5 * ST), "n"(6 * ST), "n"(7 * ST) : "memory");
}
template <int ST> DI void ldg4x128(uint32_t* m, const void* p) {
  asm volatile("ld.relaxed.gpu.global.v4.b32 {%0,%1,%2,%3}, [%16];\nld.relaxed.gpu.global.v4.b32 {%4,%5,%6,%7}, [%16 + %17];\n"
               "ld.relaxed.gpu.global.v4.b32 {%8,%9,%10,%11}, [%16 + %18];\nld.relaxed.gpu.global.v4.b32 {%12,%13,%14,%15}, [%16 + %19];"
               : "=r"(m[0]), "=r"(m[1]), "=r"(m[2]), "=r"(m[3]), "=r"(m[4]), "=r"(m[5]), "=r"(m[6]), "=r"(m[7]),
                 "=r"(m[8]), "=r"(m[9]), "=r"(m[10]), "=r"(m[11]), "=r"(m[12]), "=r"(m[13]), "=r"(m[14]), "=r"(m[15])
               : "l"(p), "n"(ST), "n"(2 * ST), "n"(3 * ST) : "memory");
}
template <int N, int ST> DI bool stale(const uint32_t* m, uint32_t tag) {
  uint32_t x = m[0] ^ tag;
#pragma unroll
  for (int i = 1; i < N; i++) asm("lop3.b32 %0, %0, %1, %2, 0xf6;" : "+r"(x) : "r"(m[i * ST]), "r"(tag));
  return __any_sync(0xffffffffu, x & 1);
}
DI bool mbar_test(uint32_t b, uint32_t par) {
  uint32_t r; asm volatile("{\n.reg .pred p;\nmbarrier.test_wait.parity.shared::cta.b64 p, [%1], %2;\nselp.u32 %0, 1, 0, p;\n}" : "=r"(r) : "r"(b), "r"(par) : "memory");
  return r;
}
DI int wait_flags(const unsigned* p, bool active, unsigned base, int seg) {
  int n = 0, m;
  while (true) {
    m = __reduce_min_sync(0xffffffffu, active ? (int)(ldg_acquire32(p) - base) : NSEG);
    if (m > seg || ++n > SPIN_LIMIT) break;
    __nanosleep((YP & 32) ? 400 : 40);
  }
  return max(m, seg + 1);
}
DI void wait_count(const unsigned* p, unsigned target) {
  int n = 0;
  unsigned v;
  while (true) {
    asm volatile("ld.acquire.gpu.global.b32 %0, [%1];" : "=r"(v) : "l"(p) : "memory");
    if ((int)(v - target) >= 0 || ++n > SPIN_LIMIT) break;
    __nanosleep(64);
  }
}
#define PACE_NEXT 800
#define AWARM 0
#define WPF 3
#define UNP 64
#define ADLY 0
#define ODLY 100
#define SDLY 0
#define RSL 100
#define TWO 0
#define ALLW 1
#define AE 0
#define PING 60
#define FLAG 2
#define FPOS 1
#define QB 1
#define Q_LO 0
#define Q_HI 320
DI bool tick_wait(uint32_t pace, int step) {
  const int n = lds32v(pace);
  if (n <= step) mbar_wait(pace + 8, n & 1);
  return n <= step;
}
DI void quiet_wait(uint32_t pace) {
  uint32_t n, d;
  asm volatile("ld.volatile.shared.v2.b32 {%0,%1}, [%2];" : "=r"(n), "=r"(d) : "r"(pace) : "memory");
  if (n - 1 < NSEG - 2 && (int)(gtime() - d) > Q_HI) mbar_wait(pace + 8, n & 1);
}
DI void sleep_until(uint32_t t) {
  for (int n = 0; n < 64; n++) {
    const int r = t - gtime();
    if (r <= 0) break;
    __nanosleep(r >> 1);
  }
}
DI void aux_barrier(int i, unsigned epoch, bool wait = true) {
  asm volatile("fence.proxy.async;" ::: "memory");
  asm volatile("red.release.gpu.global.add.u32 [%0], 1;" :: "l"(&g_abar[i * 32]) : "memory");
  if (!wait) return;
  wait_count(&g_abar[i * 32], NAUX * (epoch + 1));
  asm volatile("fence.proxy.async;" ::: "memory");
}

__global__ void __launch_bounds__(512, 1)
aux_kernel(const __grid_constant__ AMaps tm, const bf16* __restrict__ x, const bf16* __restrict__ gate_w, bf16* __restrict__ out) {
  extern __shared__ __align__(1024) unsigned char smem_raw[];
  const uint32_t sb = smem_u32(smem_raw);
  const uint32_t full1 = sb + A_BAR, empty1 = full1 + 8 * A_ST, fullw = empty1 + 8 * A_ST, full3 = fullw + 16, empty3 = full3 + 32,
                 fulla = empty3 + 32, emptya = fulla + 32, fullg = emptya + 16, pace = fullg + 8;
  const int tid = threadIdx.x, lane = tid & 31, cta = blockIdx.x;
  const int wg = __shfl_sync(0xffffffffu, tid >> 7, 0), w = __shfl_sync(0xffffffffu, (tid >> 5) & 3, 0);
  ASTAMP(14);
  const unsigned epoch = *(volatile unsigned*)&g_epoch2;
  if (tid == 0) {
    for (int i = 0; i < A_ST; i++) { mbar_init(full1 + 8 * i, 1); mbar_init(empty1 + 8 * i, 8); }
    mbar_init(fullw, 1); mbar_init(fullw + 8, 1); mbar_init(fullg, 1);
    for (int i = 0; i < 2; i++) { mbar_init(fulla + 16 * i, 2); mbar_init(fulla + 16 * i + 8, 1); mbar_init(emptya + 8 * i, 4); }
    sts64(pace, 0, 0); mbar_init(pace + 8, 1); sts32(pace + 16, 0); sts64(pace + 24, 65536, 0xffff0000u);
    for (int i = 0; i < 4; i++) { mbar_init(full3 + 8 * i, 1); mbar_init(empty3 + 8 * i, cta < NH ? 8 : 4); }
    fence_async();
  }
  auto load_a = [&](int st, int k, int col) {
    mbar_expect(full1 + 8 * st, A_STAGE + 1536);
    tma_load3d(sb + st * A_STAGE, &tm.x, k, (cta >> 1) * A_ROWS - 7, 0, full1 + 8 * st);
    tma_load3d(sb + st * A_STAGE + 8192, &tm.wa, col, k, 0, full1 + 8 * st);
    tma_load3d(sb + A_W8 + st * 1536, &tm.wa8, col + 64, k, 0, full1 + 8 * st);
  };
  if (AE && tid < 32 && !(XP & 256)) {
    __syncwarp();
#pragma unroll 1
    for (int st = 0; st < A_ST; st++) if (elect_one()) load_a(st, st * 32, (cta & 1) * (DM / 2));
  }
  __syncthreads();
  ASTAMP(0);
  const bool wide = cta < NH;
  auto p3_ks = [&](int g) { return wide ? cta >> 2 : 2 * (cta - NH) + g; };
  auto p3_mt = [&](int g) { return wide ? 2 * (cta & 3) + g : 8; };
  const unsigned fbase = epoch * NSEG;
  if (wg == 3) {
    asm volatile("setmaxnreg.dec.sync.aligned.u32 %0;" :: "n"(TWO ? 32 : 48));
    if (w == 1 && cta < NH) {
#pragma unroll 1
      for (int seg = 0; seg < ((XP & 2048) ? 0 : NSEG); seg++) {
        bar_arrive(5, 160);
        if (seg > 0 && lane == 0) {
          asm volatile("cp.async.bulk.wait_group 0;" ::: "memory");
          stg_relaxed32(&g_oflag[cta * 32], fbase + seg);
        }
        if (lane < 3) stg_relaxed32(&g_cflag[(cta * 3 + lane) * 32], fbase + seg);
        __syncwarp();
        bar_sync(4, 160);
        if (QM & 16) tick_wait(pace, seg + 1);
        if (lane == 0) {
          fence_async();
          if (!(YP & 2)) {
          tma_store(&tm.o, sb + A_OST, cta * DH, seg * 32);
          tma_store(&tm.o, sb + A_OST + 4096, cta * DH + 64, seg * 32);
          }
          asm volatile("cp.async.bulk.commit_group;" ::: "memory");
          asm volatile("cp.async.bulk.wait_group.read 0;" ::: "memory");
        }
        __syncwarp();
      }
      if (lane == 0) {
        asm volatile("cp.async.bulk.wait_group 0;" ::: "memory");
        { const int seg = NSEG - 1; TSTAMP(2); }
        stg_relaxed32(&g_oflag[cta * 32], fbase + NSEG);
      }
    }
    if (w == 2 && cta < NH) {
      const uint32_t ktag = (epoch + 1) & 1, ma = sb + A_IN + 8192 + lane * 16;
      int avail = 0;
      int own = 0;
      bar_sync(10, 64);
#pragma unroll 1
      for (int seg = 0; seg < ((XP & 2048) ? 0 : NSEG); seg++) {
        if (avail <= seg) {
          int n = 0;
          while (true) {
            asm volatile("ld.acquire.gpu.global.v2.b32 {%0,%1}, [%2];" : "=r"(avail), "=r"(own) : "l"(&g_sflag[(cta * 3 + min(lane, 2)) * 4]) : "memory");
            avail = __reduce_min_sync(0xffffffffu, (int)(avail - fbase));
            if (avail > seg || ++n > SPIN_LIMIT) break;
            __nanosleep(40);
          }
        }
        if ((QM & 8) && seg < UNP) tick_wait(pace, seg);
        TSTAMP(0);
        const unsigned char* km = g_km + (size_t)(seg * NH + cta) * 4096 + lane * 8;
        uint32_t m[16];
        const float g = __ldcg(&g_gate[seg * 32 + lane]);
        ldg8x64<256>(m, km);
        const uint32_t b = seg & 1, full = fulla + 16 * b, mb = ma + b * A_INB;
        mbar_wait(emptya + 8 * b, (~seg >> 1) & 1);
        if (lane < 2) mbar_expect(full + 8 * lane, (YP & 8) ? 0 : 16384 >> lane);
        __syncwarp();
        const int slot = seg < own ? seg & 7 : seg;
        if (lane < 3 && !(YP & 8)) bulk_load(sb + A_IN + b * A_INB + lane * SEGB, g_seg + ((size_t)slot * 96 + cta * 3 + lane) * 8192, 8192, full + (lane & 2) * 4);
        int n = 0;
#pragma unroll 1
        while (stale<8, 2>(m, ktag) && ++n < SPIN_LIMIT) { if (seg < UNP - 1) __nanosleep(200); ldg8x64<256>(m, km); }
        TSTAMP(1);
#pragma unroll
        for (int i = 0; i < 4; i++) stsm4(mb + (i >> 1) * SEGB + (i & 1) * 512, m[4 * i], m[4 * i + 1], m[4 * i + 2], m[4 * i + 3]);
        sts32(sb + A_G + b * 128 + lane * 4, __float_as_uint(1.f - g));
        fence_async();
        __syncwarp();
        if (lane == 0) mbar_arrive(full);
      }
    }
    if (w == 3 && QM) {
      const unsigned char* const hp = tm.red + HINT_OFF + 65536 + (cta & 1) * 4096 + min(lane, 23) * 4;
      uint32_t d = 0;
      int s = 0, n = 0;
#pragma unroll 1
      while (s < NSEG - 1) {
        const uint32_t h = ldg_relaxed32(hp + RED_SLOT(s)), t = (gtime() - 1984) & ~31u, late = latest_hint(h, t, s);
        if (late < 64) {
          d = t + late * 32 + tm.poll + Q_LO;
          sleep_until(d);
          s++; n = 0;
          if (lane == 0) { mbar_arrive(pace + 8); sts64(pace, s < NSEG - 1 ? s : 2 * NSEG, d); }
          sleep_until(d + PACE_NEXT);
        } else {
          if (++n > (s ? 16 : 256) || lds32v(pace + 16)) break;
          if (!s) __nanosleep(100);
        }
      }
      if (s < NSEG - 1 && lane == 0) { mbar_arrive(pace + 8); sts64(pace, 2 * NSEG, d); }
    }
    if (w != 0) return;
    const bool lead = lane == 0;
#pragma unroll 1
    for (int it = AE * A_ST, st = 0, ph = !AE, k = AE * A_ST * 32, col = (cta & 1) * (DM / 2); it < ((XP & 256) ? 0 : 72); it++) {
      mbar_wait(empty1 + 8 * st, ph);
      if (QM & 1) quiet_wait(pace);
      if (elect_one()) load_a(st, k, col);
      __syncwarp();
      if (++st == A_ST) { st = 0; ph ^= 1; }
      k += 32;
      if (k == DM) { k = 0; col += 72; }
    }
    auto load_wo = [&](uint32_t dst, int g, int kb, uint32_t mb) {
      if (kb < 64) tma_load(dst, &tm.wob, p3_mt(g) * 64, kb * 64, mb);
      else tma_load(dst, &tm.woa, p3_mt(g) * 64, (kb - 64) * 64, mb);
    };
    if (lead) mbar_expect(fullw, 16 * 8192);
#pragma unroll 1
    for (int st = 0; st < A_ST; st++) {
      if (!(XP & 256)) mbar_wait(empty1 + 8 * st, 1);
      if (lane < 16 && min(((lane + 1) * 8192 - 1) / A_STAGE, A_ST - 1) == st) load_wo(sb + lane * 8192, lane >> 3, p3_ks(lane >> 3) * 9 + (lane & 7), fullw);
      __syncwarp();
    }
    __syncwarp(); bar_sync(6, 288);
    if (lead) mbar_expect(fullw + 8, 2 * 8192 + (p3_ks(0) >= 4 ? 4096 : 0));
    __syncwarp();
    if (lane < 2) {
      load_wo(sb + (16 + lane) * 8192, lane, p3_ks(lane) * 9 + 8, fullw + 8);
      if (p3_ks(0) >= 4) tma_load(sb + A_XW + lane * 2048, &tm.woa16, p3_mt(lane) * 64, 448 + p3_ks(lane) * 16, fullw + 8);
    }
    __syncwarp();
    if (lead) aux_barrier(1, epoch, ALLW || p3_ks(0) >= 4);
    __syncwarp(); bar_sync(6, 288);
    {
      int avail = 0, sl = 0, ph = 1;
      const int h = (9 * p3_ks(0) >> 1) + lane;
#pragma unroll 1
      for (int seg = 0; seg < ((XP & 2048) ? 0 : NSEG); seg++) {
        if (avail <= seg) avail = wait_flags(&g_oflag[min(h, NH - 1) * 32], lane < (wide ? 5 : 9), fbase, seg);
        SSTAMP(seg, 4);
        for (int g = 0; g < (wide ? 1 : 2); g++) {
          const int ks = p3_ks(g);
          mbar_wait(empty3 + 8 * sl, ph);
          if ((QM & 4) && tick_wait(pace, seg + (QM >> 4 & 1) + 1) && ODLY) __nanosleep(ODLY);
          if (YP & 4) { if (lead) mbar_arrive(full3 + 8 * sl); }
          else if (elect_one()) {
            mbar_expect(full3 + 8 * sl, XT + (ks >= 4 ? 1024 : 0));
            tma_load3d(sb + sl * XT, &tm.o3, 0, seg * 32, ks * 9, full3 + 8 * sl);
            if (ks >= 4) tma_load(sb + A_XT + sl * 1024, &tm.o16, 72 * 64 - 64 + ks * 16, seg * 32, full3 + 8 * sl);
          }
          __syncwarp();
          if (++sl == (wide ? 3 : 4)) { sl = 0; ph ^= 1; }
        }
      }
    }
    sts32(pace + 16, 1);
    __syncwarp(); bar_sync(6, 288);
    asm volatile("griddepcontrol.wait;" ::: "memory");
  } else if (wg == 2) {
    asm volatile("setmaxnreg.dec.sync.aligned.u32 64;");
    if (cta < NH) {
      if (tid == 256) { mbar_expect(fullg, 64 * DM * 2); bulk_load(sb + A_IN, x + cta * 64 * DM, 64 * DM * 2, fullg); }
      uint32_t gw[9];
#pragma unroll
      for (int j = 0; j < 9; j++) gw[j] = ((const uint32_t*)gate_w)[j * 32 + lane];
      mbar_wait(fullg, 0);
      float mine = 0.f;
#pragma unroll 4
      for (int u = 0; u < 16; u++) {
        float d0 = 0.f, d1 = 0.f;
#pragma unroll
        for (int j = 0; j < 9; j++) {
          const uint32_t a = lds32(sb + A_IN + (w * 16 + u) * (DM * 2) + j * 128 + lane * 4);
          d0 = fmaf(bf_lo(a), bf_lo(gw[j]), d0); d1 = fmaf(bf_hi(a), bf_hi(gw[j]), d1);
        }
        d0 = warp_sum(d0 + d1);
        if (lane == u) mine = d0;
      }
      if (lane < 16) g_gate[cta * 64 + w * 16 + lane] = 1.f / (1.f + __expf(-mine));
      fence_async();
    }
    bar_sync(3, 128);
    if (tid == 256) { aux_barrier(0, epoch); if (cta == 0) *(volatile unsigned*)&g_epoch2 = epoch + 1; }
    __syncwarp();
    bar_sync(3, 128);
    if (w == 0) bar_arrive(8, 288);
    if (w == 1 && cta < NH) bar_arrive(10, 64);
    if (cta < NH) {
      CDECL;
#pragma unroll 1
      for (int seg = 0; seg < ((XP & 2048) ? 0 : NSEG); seg++) {
        CSTAMP(0);
        const uint32_t in = sb + A_IN + (seg & 1) * A_INB;
        const uint64_t qd = make_desc(in, 128, 1024, 0);
        mbar_wait(fulla + 16 * (seg & 1), (seg >> 1) & 1);
        CSTAMP(3);
        SSTAMP(seg, 0);
        float d[2][16];
        {
          float a[20];
          uint32_t vm[16];
          const unsigned char* vp = g_km + (size_t)(seg * NH + cta) * 4096 + 2048 + lane * 16;
          if (w == 3) ldg4x128<512>(vm, vp);
          WG_FENCE();
#pragma unroll
          for (int k = 0; k < ((YP & 16) ? 1 : 8); k++) wgmma_n40_ss(a, qd + ((k >> 2) * SEGB + (k & 3) * 256 >> 4), qd + ((k >> 2) * SEGB + (k & 3) * 256 + 4096 >> 4), k > 0);
          const uint32_t ga = sb + A_G + (seg & 1) * 128 + (w & 1) * 64 + (lane >> 2) * 4;
          const float f0 = __uint_as_float(lds32(ga)), f1 = __uint_as_float(lds32(ga + 32));
          WG_COMMIT();
          WG_WAIT(0);
          CSTAMP(5);
          SSTAMP(seg, 1);
          if (w < 2) {
            const int lim = w * 16 + (lane >> 2) - 2 * (lane & 3);
            float m0 = -3.0e38f, m1 = -3.0e38f;
#pragma unroll
            for (int i = 0; i < 20; i++) {
              a[i] *= SM_SCALE * LOG2E;
              if (i < 16 && (i >> 2) * 8 + (i & 1) - (i & 2) * 4 > lim) a[i] = -1.0e9f * LOG2E;
              if (i & 2) m1 = fmaxf(m1, a[i]); else m0 = fmaxf(m0, a[i]);
            }
#pragma unroll
            for (int o = 1; o < 4; o <<= 1) { m0 = fmaxf(m0, __shfl_xor_sync(0xffffffffu, m0, o)); m1 = fmaxf(m1, __shfl_xor_sync(0xffffffffu, m1, o)); }
            float s0 = 0.f, s1 = 0.f;
#pragma unroll
            for (int i = 0; i < 20; i++) { a[i] = ex2(a[i] - (i & 2 ? m1 : m0)); if (i & 2) s1 += a[i]; else s0 += a[i]; }
#pragma unroll
            for (int o = 1; o < 4; o <<= 1) { s0 += __shfl_xor_sync(0xffffffffu, s0, o); s1 += __shfl_xor_sync(0xffffffffu, s1, o); }
            s0 = f0 * rcp(s0); s1 = f1 * rcp(s1);
            uint32_t p[10];
#pragma unroll
            for (int i = 0; i < 10; i++) p[i] = pack_bf16(a[2 * i] * (i & 1 ? s1 : s0), a[2 * i + 1] * (i & 1 ? s1 : s0));
            const uint32_t pa = sb + A_P + (2 * w + ((lane >> 3) & 1)) * 768 + (lane >> 4) * 128 + (lane & 7) * 16;
            stsm4t(pa, p[0], p[1], p[2], p[3]); stsm4t(pa + 256, p[4], p[5], p[6], p[7]); stsm4t(pa + 512, p[8], p[9], 0, 0);
            CSTAMP(6);
            fence_async();
            CSTAMP(7);
          } else if (w == 3) {
            int n = 0;
#pragma unroll 1
            while (stale<4, 4>(vm, (epoch + 1) & 1) && ++n < SPIN_LIMIT) ldg4x128<512>(vm, vp);
#pragma unroll
            for (int i = 0; i < 4; i++) stsm4(in + 2 * SEGB + 8192 + (lane >> 4) * 1024 + (lane & 15) * 16 + i * 256, vm[4 * i], vm[4 * i + 1], vm[4 * i + 2], vm[4 * i + 3]);
            fence_async();
            mbar_wait(fulla + 16 * (seg & 1) + 8, (seg >> 1) & 1);
          }
        }
        CSTAMP(8);

        bar_sync(5, 160);
        CSTAMP(10);
        SSTAMP(seg, 2);
        const uint64_t pd = make_desc(sb + A_P, 128, 768, 0), vd = make_desc(in + 2 * SEGB, 128, 512, 0), md = make_desc(in + 2 * SEGB + 8192, 0, 128, 0);
        WG_FENCE();
#pragma unroll
        for (int i = 0; i < 2; i++) {
          wgmma_n32_ss<0>(d[i], vd + i * 256, pd, 0);
          wgmma_n32_ss<0>(d[i], vd + i * 256 + 16, pd + 16, 1);
          wgmma_n32_ss<0>(d[i], md + i * 64, pd + 32, 1);
        }
        WG_COMMIT();
        WG_WAIT(0);
        CSTAMP(11);
        if (lane == 0) mbar_arrive(emptya + 8 * (seg & 1));
#pragma unroll
        for (int i = 0; i < 2; i++) {
          const uint32_t oa = sb + A_OST + i * 4096 + ((lane & 7) + ((lane >> 4) << 3)) * 128 + (((2 * w + ((lane >> 3) & 1)) ^ (lane & 7)) << 4);
          stsm4t(oa, pack_bf16(d[i][0], d[i][1]), pack_bf16(d[i][2], d[i][3]), pack_bf16(d[i][4], d[i][5]), pack_bf16(d[i][6], d[i][7]));
          stsm4t(oa + 2048, pack_bf16(d[i][8], d[i][9]), pack_bf16(d[i][10], d[i][11]), pack_bf16(d[i][12], d[i][13]), pack_bf16(d[i][14], d[i][15]));
        }
        CSTAMP(12);
        bar_sync(4, 160);
        SSTAMP(seg, 3);
      }
      CDUMP;
    }
  } else {
    asm volatile("setmaxnreg.inc.sync.aligned.u32 %0;" :: "n"(TWO ? 208 : 200));
    {
      const int g = lane >> 2, t = lane & 3, r0 = (cta >> 1) * A_ROWS - 7 + w * 16;
      const uint32_t prev = (2 * t > g ? 0xffffu : 0u) | (2 * t + 1 > g ? 0xffff0000u : 0u);
      const int k0 = r0 + 2 * t - (2 * t > g ? 8 : 0), k1 = r0 + 2 * t + 1 - (2 * t + 1 > g ? 8 : 0);
      const uint32_t slot = sb + A_EXC + (wg * 4 + w) * 2304;
      float gl = 0.f, gh = 0.f;
      int st = 0, ph = 0;
#pragma unroll 1
      for (int p = -AWARM; p < ((XP & 256) ? 0 : 4); p++) {
        float big[96], sml[12];
        if (p == WPF && tid < 18) {
          const int kb = p3_ks(tid >= 9) * 9 + tid % 9;
          tma_prefetch(kb < 64 ? &tm.wob : &tm.woa, p3_mt(tid >= 9) * 64, (kb & 63) * 64);
        }
        __syncwarp();
#pragma unroll
        for (int i = 0; i < 96; i++) big[i] = 0.f;
#pragma unroll
        for (int i = 0; i < 12; i++) sml[i] = 0.f;
#pragma unroll 1
        for (int k = p < 0 ? 18 : 0; k < 18; k++) {
          mbar_wait(full1 + 8 * st, ph);
          const uint64_t da = make_desc(sb + st * A_STAGE + wg * 4096, 16, 512, 2);
          const uint64_t db = make_desc(sb + st * A_STAGE + 8192, 4096, 1024, 1), dc = make_desc(sb + A_W8 + st * 1536, 128, 512, 0);
          WG_FENCE();
#pragma unroll
          for (int j = 0; j < 2; j++) { wgmma_n192_ss_nt(big, da + j * 2, db + j * 128, 1); wgmma_n24_ss_nt(sml, da + j * 2, dc + j * 16, 1); }
          WG_COMMIT();
          WG_WAIT(1);
          if (k > 0 && lane == 0) mbar_arrive(empty1 + 8 * (st ? st - 1 : A_ST - 1));
          if (++st == A_ST) { st = 0; ph ^= 1; }
        }
        WG_WAIT(0);
        ASTAMP(16 + max(p, 0) + wg * 16);
        if (lane == 0 && p >= 0) mbar_arrive(empty1 + 8 * (st ? st - 1 : A_ST - 1));
        uint32_t f[3][9][2];
#pragma unroll
        for (int c = 0; c < 3; c++)
#pragma unroll
          for (int j = 0; j < 9; j++)
#pragma unroll
            for (int i = 0; i < 2; i++) {
              const float* a = j < 8 ? &big[(c * 8 + j) * 4 + 2 * i] : &sml[c * 4 + 2 * i];
              f[c][j][i] = c < 2 ? pack_bf16(a[0], a[1]) : trans8(pack_bf16(a[0], a[1]));
            }
        if (p == 0) {
          bar_sync(8, 288);
          gl = __ldcg(&g_gate[min(max(r0 + g, 0), S_LEN / 2 - 1) * 2 + wg]); gh = __ldcg(&g_gate[min(max(r0 + g + 8, 0), S_LEN / 2 - 1) * 2 + wg]);
        }
        asm volatile("cp.async.bulk.wait_group.read 0;" ::: "memory");
        __syncwarp();
#pragma unroll
        for (int j = 0; j < 8; j += 2) sts128(slot + j * 256 + lane * 16, f[1][j][1], f[2][j][1], f[1][j + 1][1], f[2][j + 1][1]);
        sts64(slot + 2048 + lane * 8, f[1][8][1], f[2][8][1]);
        bar_sync(1 + wg, 128);
        ASTAMP(24 + max(p, 0) + wg * 16);
        uint32_t pv[9][2];
#pragma unroll
        for (int j = 0; j < 9; j++) pv[j][0] = pv[j][1] = 0;
        if (w) {
#pragma unroll
          for (int j = 0; j < 8; j += 2) lds128(slot - 2304 + j * 256 + lane * 16, pv[j]);
          lds64(slot - 256 + lane * 8, pv[8][0], pv[8][1]);
        }
        float a[4][4], m[4][2];
#pragma unroll
        for (int h = 0; h < 4; h++) {
          const int j = 2 * h;
          const uint32_t qa[4] = {t >= h ? f[0][j][0] : 0, t >= h ? f[0][j][1] : 0, f[0][j + 1][0], f[0][j + 1][1]};
          const uint32_t qb0 = t <= h ? f[0][j + 2][0] : 0, qb1 = t <= h ? f[0][j + 2][1] : 0;
          float s0[4], s1[4], s2[4];
          mma16816z(s1, qa, f[1][j][0], f[1][j + 1][0]); mma16816z(s2, qa, f[1][j][1], f[1][j + 1][1]); mma16816z(s0, qa, pv[j][0], pv[j + 1][0]);
          mma1688(s1, qb0, qb1, f[1][j + 2][0]); mma1688(s2, qb0, qb1, f[1][j + 2][1]); mma1688(s0, qb0, qb1, pv[j + 2][0]);
          a[h][0] = 2 * t > g ? s0[0] : s1[0]; a[h][1] = 2 * t + 1 > g ? s0[1] : s1[1]; a[h][2] = 2 * t > g ? s1[2] : s2[2]; a[h][3] = 2 * t + 1 > g ? s1[3] : s2[3];
        }
#pragma unroll
        for (int h = 0; h < 4; h++) {
#pragma unroll
          for (int i = 0; i < 4; i++) a[h][i] = (i & 1 ? k1 : k0) + (i & 2) * 4 >= 0 ? a[h][i] * (0.23570226039551584f * LOG2E) : -1.0e9f * LOG2E;
          m[h][0] = fmaxf(a[h][0], a[h][1]); m[h][1] = fmaxf(a[h][2], a[h][3]);
        }
#pragma unroll
        for (int x = 1; x < 4; x <<= 1)
#pragma unroll
          for (int i = 0; i < 8; i++) m[i >> 1][i & 1] = fmaxf(m[i >> 1][i & 1], __shfl_xor_sync(0xffffffffu, m[i >> 1][i & 1], x));
#pragma unroll
        for (int h = 0; h < 4; h++) {
#pragma unroll
          for (int i = 0; i < 4; i++) a[h][i] = ex2(a[h][i] - m[h][i >> 1]);
          m[h][0] = a[h][0] + a[h][1]; m[h][1] = a[h][2] + a[h][3];
        }
#pragma unroll
        for (int x = 1; x < 4; x <<= 1)
#pragma unroll
          for (int i = 0; i < 8; i++) m[i >> 1][i & 1] += __shfl_xor_sync(0xffffffffu, m[i >> 1][i & 1], x);
        uint32_t o[9][2];
#pragma unroll
        for (int h = 0; h < 4; h++) {
          const int j = 2 * h;
          const float z0 = gl * rcp(m[h][0]), z1 = gh * rcp(m[h][1]);
          const uint32_t pl = pack_bf16(a[h][0] * z0, a[h][1] * z0), pu = pack_bf16(a[h][2] * z1, a[h][3] * z1);
          const uint32_t pa[4] = {pl & prev, 0, pl & ~prev, pu & prev};
          float d[3][4];
#pragma unroll
          for (int i = 0; i < 3; i++) mma16816z(d[i], pa, pv[j + i][1], f[2][j + i][0]);
#pragma unroll
          for (int i = 0; i < 3; i++) mma1688(d[i], 0, pu & ~prev, f[2][j + i][1]);
#pragma unroll
          for (int i = 0; i < 3; i++) {
            const uint32_t d0 = pack_bf16(d[i][0], d[i][1]), d1 = pack_bf16(d[i][2], d[i][3]);
            o[j + i][0] = i == 0 && h > 0 && t < h ? o[j][0] : d0;
            o[j + i][1] = i == 0 && h > 0 && t < h ? o[j][1] : d1;
          }
        }
        ASTAMP(28 + max(p, 0) + wg * 16);
        bar_sync(1 + wg, 128);
        const uint32_t oa = slot + (lane & 15) * 144 + (lane >> 4) * 16;
#pragma unroll
        for (int j = 0; j < 8; j += 2) stsm4(oa + j * 16, o[j][0], o[j][1], o[j + 1][0], o[j + 1][1]);
        asm volatile("stmatrix.sync.aligned.m8n8.x2.shared.b16 [%0], {%1,%2};" :: "r"(oa + 128), "r"(o[8][0]), "r"(o[8][1]) : "memory");
        fence_async();
        __syncwarp();
        if (QM & 64) quiet_wait(pace);
        if (lane < 16 && w * 16 + lane >= 7 && r0 + lane < S_LEN / 2 && p >= 0)
          asm volatile("cp.async.bulk.global.shared::cta.bulk_group [%0], [%1], 144;"
                       :: "l"(g_Ocat + (size_t)((r0 + lane) * 2 + wg) * KCAT + 4096 + (cta & 1) * (DM / 2) + p * 72), "r"(slot + lane * 144) : "memory");
        asm volatile("cp.async.bulk.commit_group;" ::: "memory");
        ASTAMP(20 + max(p, 0) + wg * 16);
      }
      if (XP & 256) bar_sync(8, 288);
      asm volatile("cp.async.bulk.wait_group 0;" ::: "memory");
    }
    ASTAMP(3);
    bar_arrive(6, 288);
    uint32_t wa[37][4];
    mbar_wait(fullw, 0);
    const uint32_t la = sb + ((lane & 7) + ((lane >> 4) << 3)) * 128 + (((2 * w + ((lane >> 3) & 1)) ^ (lane & 7)) << 4);
#pragma unroll
    for (int k = 0; k < 32; k++) ldsm4t(wa[k], la + wg * 65536 + k * 2048);
    mbar_wait(fullw + 8, 0);
#pragma unroll
    for (int k = 32; k < 36; k++) ldsm4t(wa[k], la + wg * 8192 + 65536 + k * 2048);
    ldsm4t(wa[36], la + A_XW + wg * 2048);
    fence_async();
    if (XP & 2048) bar_sync(6, 288); else bar_arrive(6, 288);
    ASTAMP(4);
    const int ks = p3_ks(wg), mt = p3_mt(wg);
    uint32_t v[16];
    auto fetch = [&](int seg) { ldg8x64<1024>(v, g_part + (((seg & 7) * 9 + mt) * 4 + (ks & 3)) * 1024 + (tid & 127)); };
    auto finish = [&](int seg) {
      const uint32_t tagv = (~seg >> 3) & 1;
      int n = 0;
#pragma unroll 1
      while (!(YP & 512) && stale<8, 2>(v, tagv) && ++n < SPIN_LIMIT) {
        if (seg < NSEG - 2) __nanosleep(RSL);
        fetch(seg);
      }
      float own[4] = {bf_lo(v[0]), bf_hi(v[0]), bf_lo(v[1]), bf_hi(v[1])};
#pragma unroll
      for (int j = 1; j < 8; j++) { own[0] += bf_lo(v[2 * j]); own[1] += bf_hi(v[2 * j]); own[2] += bf_lo(v[2 * j + 1]); own[3] += bf_hi(v[2 * j + 1]); }
      uint32_t p0 = pack_bf16(own[0], own[1]), p1 = pack_bf16(own[2], own[3]);
      asm volatile("movmatrix.sync.aligned.m8n8.trans.b16 %0, %0;" : "+r"(p0));
      asm volatile("movmatrix.sync.aligned.m8n8.trans.b16 %0, %0;" : "+r"(p1));
      const uint32_t r2 = __shfl_xor_sync(0xffffffffu, lane & 2 ? p0 : p1, 2);
      if (lane & 2) p0 = r2; else p1 = r2;
      const uint32_t r1 = __shfl_xor_sync(0xffffffffu, lane & 1 ? p0 : p1, 1);
      if (lane & 1) p0 = r1; else p1 = r1;
      if (!(YP & 256) || p0 == 0x12345678)
        *((uint2*)(out + (size_t)(seg * 32 + (ks & 3) * 8 + (lane >> 2)) * DM + mt * 64 + w * 16) + (lane & 3)) = make_uint2(p0, p1);
      SSTAMP(seg, 7);
    };
    float acc[16], acc2[16];
#pragma unroll
    for (int i = 0; i < 16; i++) acc[i] = acc2[i] = 0.f;
    int pend = -1, sl = wide ? 0 : wg, ph = 0;
    if (PING && wg) bar_arrive(1, 256);
    CDECL;
    auto run = [&](auto extra) {
#pragma unroll 1
    for (int seg = 0; seg <= ((XP & 2048) ? -1 : NSEG); seg++) {
      CSTAMP(0);
      const bool fin = pend >= 0 && (seg - pend >= FLAG || seg == NSEG);
      if (seg < NSEG) mbar_wait(full3 + 8 * sl, ph);
      if (FPOS == 1 && fin) fetch(pend);
      if (SDLY) {
        uint32_t n, d;
        asm volatile("ld.volatile.shared.v2.b32 {%0,%1}, [%2];" : "=r"(n), "=r"(d) : "r"(pace) : "memory");
        if ((int)n <= seg + 3) sleep_until(d + SDLY);
      }
      CSTAMP(1);
      if (seg < NSEG) {
      if (wg) SSTAMP(seg, 5);
      if (seg < PING) bar_sync(1 + wg, 256);
      CSTAMP(7);
      const uint64_t db = make_desc(sb + sl * XT, 16, 1024, 1);
      WG_FENCE();
#pragma unroll
      for (int k = 0; k < ((XP & 1024) ? 1 : 36); k++)
        wgmma_n32_rs(TWO && (k & 1) ? acc2 : acc, wa[k][0], wa[k][1], wa[k][2], wa[k][3], db + (k >> 2) * 256 + (k & 3) * 2, k >> TWO);
      if (decltype(extra)::value) wgmma_n32_rs(acc, wa[36][0], wa[36][1], wa[36][2], wa[36][3], make_desc(sb + A_XT + sl * 1024, 16, 256, 3), 1);
      WG_COMMIT();
      if (seg < PING) bar_arrive(2 - wg, 256);
      CSTAMP(2);
      CSTAMP(3);
      WG_WAIT(0);
      CSTAMP(4);
      if (wg) SSTAMP(seg, 6);
      if (lane == 0) mbar_arrive(empty3 + 8 * sl);
      sl += wide ? 1 : 2;
      if (sl >= (wide ? 3 : 4)) { sl -= wide ? 3 : 4; ph ^= 1; }
      uint2* dst = g_part + (((seg & 7) * 9 + mt) * 32 + ks) * 128 + (tid & 127);
      uint32_t q[8];
      if (TWO)
#pragma unroll
        for (int j = 0; j < 16; j++) acc[j] += acc2[j];
#pragma unroll
      for (int j = 0; j < 8; j++) q[j] = j & 1 ? pack_bf16(acc[2 * j], acc[2 * j + 1]) : (pack_bf16(acc[2 * j], acc[2 * j + 1]) & ~1u) | ((~seg >> 3) & 1);
      if (QM & 32) tick_wait(pace, seg + (QM >> 4 & 1) + 2);
      if (!(YP & 1025) || q[0] == 0x12345678)
      asm volatile("st.relaxed.gpu.global.v2.b32 [%0], {%1,%2};\nst.relaxed.gpu.global.v2.b32 [%0 + 8192], {%3,%4};\n"
                   "st.relaxed.gpu.global.v2.b32 [%0 + 16384], {%5,%6};\nst.relaxed.gpu.global.v2.b32 [%0 + 24576], {%7,%8};"
                   :: "l"(dst), "r"(q[0]), "r"(q[1]), "r"(q[2]), "r"(q[3]), "r"(q[4]), "r"(q[5]), "r"(q[6]), "r"(q[7]) : "memory");
      }
      CSTAMP(5);
      if (fin) { finish(pend); pend = -1; }
      CSTAMP(6);
      if ((seg & 1) == ks >> 2 && !(YP & 1)) pend = seg;
      if (wg && (seg & 7) == 6) ASTAMP(5 + (seg >> 3));
    }
    };
    if (ks >= 4) run(BoolC<true>()); else run(BoolC<false>());
    if (PING && !wg) bar_sync(1, 256);
    CDUMP;
    ASTAMP(13);
    bar_sync(6, 288);
  }
}

typedef CUresult (*EncodeFn)(CUtensorMap*, CUtensorMapDataType, cuuint32_t, void*, const cuuint64_t*, const cuuint64_t*,
                             const cuuint32_t*, const cuuint32_t*, CUtensorMapInterleave, CUtensorMapSwizzle,
                             CUtensorMapL2promotion, CUtensorMapFloatOOBfill);
#define PROMO 2
static void make_map(EncodeFn enc, CUtensorMap* m, const void* p, int rows, int cols, int box_rows) {
  cuuint64_t dims[2] = {(cuuint64_t)cols, (cuuint64_t)rows};
  cuuint64_t strides[1] = {(cuuint64_t)cols * 2};
  cuuint32_t box[2] = {64, (cuuint32_t)box_rows};
  cuuint32_t es[2] = {1, 1};
  enc(m, CU_TENSOR_MAP_DATA_TYPE_BFLOAT16, 2, (void*)p, dims, strides, box, es, CU_TENSOR_MAP_INTERLEAVE_NONE,
      CU_TENSOR_MAP_SWIZZLE_128B, (CUtensorMapL2promotion)PROMO, CU_TENSOR_MAP_FLOAT_OOB_FILL_NONE);
}

constexpr int g_poll = POLL_NS;
extern "C" void kernel_launch(void* const* d_in, const int* in_sizes, int n_in, void* d_out, int out_size) {
  const bf16* x = (const bf16*)d_in[0];
  const bf16* wqkvA = (const bf16*)d_in[1];
  const bf16* woA = (const bf16*)d_in[2];
  const bf16* mem0 = (const bf16*)d_in[4];
  const bf16* Wq = (const bf16*)d_in[5];
  const bf16* Wk = (const bf16*)d_in[6];
  const bf16* Wv = (const bf16*)d_in[7];
  const bf16* Wo = (const bf16*)d_in[8];
  const bf16* gate_w = (const bf16*)d_in[10];
  static EncodeFn enc = nullptr;
  static void *pO = nullptr, *pR = nullptr, *pF = nullptr;
  if (!enc) {
    cudaDriverEntryPointQueryResult qr;
    cudaGetDriverEntryPoint("cuTensorMapEncodeTiled", (void**)&enc, cudaEnableDefault, &qr);
    cudaGetSymbolAddress(&pO, g_Ocat);
    cudaGetSymbolAddress(&pR, g_red_raw);
    cudaGetSymbolAddress(&pF, g_cflag);
    cudaFuncSetAttribute(rec_kernel, cudaFuncAttributeMaxDynamicSharedMemorySize, SM_TOTAL);
    cudaFuncSetAttribute(aux_kernel, cudaFuncAttributeMaxDynamicSharedMemorySize, A_TOTAL);
  }
  RMaps rm;
  rm.poll = g_poll;
  rm.oflag = (const unsigned char*)pF;
  rm.red = (unsigned char*)(((uintptr_t)pR + 262143) & ~(uintptr_t)262143);
  {
    cuuint64_t dims[3] = {64, S_LEN, 9}, strides[2] = {DM * 2, 128};
    cuuint32_t box[3] = {64, 32, 9}, es[3] = {1, 1, 1};
    enc(&rm.x, CU_TENSOR_MAP_DATA_TYPE_BFLOAT16, 3, (void*)x, dims, strides, box, es, CU_TENSOR_MAP_INTERLEAVE_NONE,
        CU_TENSOR_MAP_SWIZZLE_128B, CU_TENSOR_MAP_L2_PROMOTION_L2_128B, CU_TENSOR_MAP_FLOAT_OOB_FILL_NONE);
  }
  make_map(enc, &rm.wq, Wq, DM, 4096, 192);
  make_map(enc, &rm.wk, Wk, DM, 4096, 192);
  make_map(enc, &rm.wv, Wv, DM, 4096, 192);
  make_map(enc, &rm.wo, Wo, 4096, DM, 128);
  AMaps am;
  am.red = rm.red; am.poll = rm.poll;
  {
    cuuint64_t dims[3] = {DM, S_LEN / 2, 2}, strides[2] = {DM * 4, DM * 2};
    cuuint32_t box[3] = {32, 64, 2}, es[3] = {1, 1, 1};
    enc(&am.x, CU_TENSOR_MAP_DATA_TYPE_BFLOAT16, 3, (void*)x, dims, strides, box, es, CU_TENSOR_MAP_INTERLEAVE_NONE,
        CU_TENSOR_MAP_SWIZZLE_64B, CU_TENSOR_MAP_L2_PROMOTION_L2_128B, CU_TENSOR_MAP_FLOAT_OOB_FILL_NONE);
    cuuint64_t wdims[3] = {DM, DM, 3}, wstrides[2] = {DM * 6, DM * 2};
    cuuint32_t wbox[3] = {64, 32, 3}, wbox8[3] = {8, 32, 3};
    enc(&am.wa, CU_TENSOR_MAP_DATA_TYPE_BFLOAT16, 3, (void*)wqkvA, wdims, wstrides, wbox, es, CU_TENSOR_MAP_INTERLEAVE_NONE,
        CU_TENSOR_MAP_SWIZZLE_128B, CU_TENSOR_MAP_L2_PROMOTION_L2_128B, CU_TENSOR_MAP_FLOAT_OOB_FILL_NONE);
    enc(&am.wa8, CU_TENSOR_MAP_DATA_TYPE_BFLOAT16, 3, (void*)wqkvA, wdims, wstrides, wbox8, es, CU_TENSOR_MAP_INTERLEAVE_NONE,
        CU_TENSOR_MAP_SWIZZLE_NONE, CU_TENSOR_MAP_L2_PROMOTION_NONE, CU_TENSOR_MAP_FLOAT_OOB_FILL_NONE);
  }
  {
    cuuint64_t dims[3] = {64, S_LEN, KCAT / 64}, strides[2] = {KCAT * 2, 128};
    cuuint32_t box[3] = {64, 32, 9}, es[3] = {1, 1, 1};
    make_map(enc, &am.o, pO, S_LEN, KCAT, 32);
    enc(&am.o3, CU_TENSOR_MAP_DATA_TYPE_BFLOAT16, 3, pO, dims, strides, box, es, CU_TENSOR_MAP_INTERLEAVE_NONE,
        CU_TENSOR_MAP_SWIZZLE_128B, CU_TENSOR_MAP_L2_PROMOTION_L2_128B, CU_TENSOR_MAP_FLOAT_OOB_FILL_NONE);
  }
  make_map(enc, &am.wob, Wo, 4096, DM, 64);
  make_map(enc, &am.woa, woA, DM, DM, 64);
  make_map(enc, &am.woa16, woA, DM, DM, 16);
  {
    cuuint64_t dims[2] = {KCAT, S_LEN}, strides[1] = {KCAT * 2};
    cuuint32_t box[2] = {16, 32}, es[2] = {1, 1};
    enc(&am.o16, CU_TENSOR_MAP_DATA_TYPE_BFLOAT16, 2, pO, dims, strides, box, es, CU_TENSOR_MAP_INTERLEAVE_NONE,
        CU_TENSOR_MAP_SWIZZLE_32B, CU_TENSOR_MAP_L2_PROMOTION_NONE, CU_TENSOR_MAP_FLOAT_OOB_FILL_NONE);
  }

  rec_kernel<<<96, 384, SM_TOTAL, cudaStreamPerThread>>>(rm, x, mem0);
  cudaLaunchConfig_t cfg = {};
  cfg.gridDim = dim3(NAUX); cfg.blockDim = dim3(512); cfg.dynamicSmemBytes = A_TOTAL; cfg.stream = cudaStreamPerThread;
  cudaLaunchAttribute at[1];
  at[0].id = cudaLaunchAttributeProgrammaticStreamSerialization; at[0].val.programmaticStreamSerializationAllowed = 1;
  cfg.attrs = at; cfg.numAttrs = 1;
  if (XP & 16) cfg.numAttrs = 0;
  if (!(XP & 64)) cudaLaunchKernelEx(&cfg, aux_kernel, am, x, gate_w, (bf16*)d_out);
}
```

```cpp
#include <cuda_runtime.h>
#include <cuda_bf16.h>
#include <cuda_fp16.h>
#include <cuda.h>
#include <stdint.h>

typedef __nv_bfloat16 bf16;

constexpr int S_LEN = 2048, DM = 576, NH = 32, DH = 128, NSEG = 64, KCAT = 4096 + 576;
#define RED_LINE(i) (((i) >> 2) * 4096 + ((i) & 1) * 256 + ((i) & 2) * 512)
#define RED_SLOT(s) (((s) & 1) * 128 + ((s) & 2) * 256)

#define POLL_NS 896
#define QM 60
constexpr int NUP = 4;
#define N5 224
#define KP(i) (((i) >> 1) + 4 * ((i) & 1))
#define SPIN_LIMIT (1 << 14)
#define XP 0
#define YP 0

__device__ __align__(1024) bf16 g_Ocat[S_LEN * KCAT];
__device__ __align__(1024) unsigned char g_red_raw[2 * 262144];
constexpr int HINT_OFF = 2048;
__device__ __align__(16) float g_gate[S_LEN];
__device__ __align__(128) uint4 g_stats[96 * 2];
__device__ unsigned g_epoch;
__device__ unsigned g_epoch2;
__device__ __align__(128) unsigned g_oflag[NH * 32];
__device__ unsigned g_abar[3 * 32];
__device__ __align__(128) unsigned g_cflag[96 * 32];
__device__ uint2 g_sflag[96 * 4];
__device__ __align__(1024) unsigned char g_seg[NSEG * 96 * 8192];
__device__ __align__(1024) unsigned char g_km[NSEG * NH * 4096];
__device__ __align__(1024) uint2 g_part[8 * 9 * 4 * 8 * 128];
__device__ int g_err;
#define SSTAMP(seg, idx)
#define TSTAMP(idx)
#define QSTAMP(idx)
#define PROF(idx)
#define PROFP(idx)
#define STAMP(idx)
#define ASTAMP(idx)
#define WSTAMP(idx)

#define CSTAMP(idx)
#define CDECL
#define CDUMP
#define DI __device__ __forceinline__
DI uint32_t smem_u32(const void* p) { return (uint32_t)__cvta_generic_to_shared(p); }
DI uint32_t clock32() { uint32_t c; asm volatile("mov.u32 %0, %%clock;" : "=r"(c) :: "memory"); return c; }
DI uint32_t gtime() { uint32_t c; asm volatile("mov.u32 %0, %%globaltimer_lo;" : "=r"(c) :: "memory"); return c; }
DI uint32_t ldg_relaxed32(const void* p) { uint32_t v; asm volatile("ld.relaxed.gpu.global.b32 %0, [%1];" : "=r"(v) : "l"(p) : "memory"); return v; }
DI uint32_t ldg_acquire32(const void* p) { uint32_t v; asm volatile("ld.acquire.gpu.global.b32 %0, [%1];" : "=r"(v) : "l"(p) : "memory"); return v; }
DI void stg_relaxed32(void* p, uint32_t v) { asm volatile("st.relaxed.gpu.global.b32 [%0], %1;" :: "l"(p), "r"(v) : "memory"); }
DI uint32_t mapa(uint32_t a, uint32_t r) { uint32_t o; asm("mapa.shared::cluster.u32 %0, %1, %2;" : "=r"(o) : "r"(a), "r"(r)); return o; }
DI void cluster_arrive() { asm volatile("barrier.cluster.arrive.relaxed.aligned;" ::: "memory"); }
DI void cluster_wait() { asm volatile("barrier.cluster.wait.aligned;" ::: "memory"); }
DI void cluster_sync() { asm volatile("barrier.cluster.arrive.release.aligned;\nbarrier.cluster.wait.acquire.aligned;" ::: "memory"); }
DI void mbar_init(uint32_t b, uint32_t c) { asm volatile("mbarrier.init.shared::cta.b64 [%0], %1;" :: "r"(b), "r"(c) : "memory"); }
DI void mbar_expect(uint32_t b, uint32_t tx) { asm volatile("mbarrier.arrive.expect_tx.shared::cta.b64 _, [%0], %1;" :: "r"(b), "r"(tx) : "memory"); }
DI void mbar_arrive(uint32_t b) { asm volatile("mbarrier.arrive.shared::cta.b64 _, [%0];" :: "r"(b) : "memory"); }
DI void mbar_wait(uint32_t b, uint32_t par) {
  asm volatile("{\n.reg .pred p;\n.reg .u32 n, q;\nmov.u32 n, 0;\n"
               "WL: add.u32 n, n, 1;\nshr.u32 q, n, 12;\nxor.b32 q, q, %1;\n"
               "mbarrier.try_wait.parity.shared::cta.b64 p, [%0], q;\n@!p bra.uni WL;\n}"
               :: "r"(b), "r"(par) : "memory");
}
DI void wait_until(uint32_t t) {
  const uint32_t now = gtime();
  t = min(t, now + 8192);
  asm volatile("{\n.reg .pred p;\n.reg .u32 c;\nTL: mov.u32 c, %%globaltimer_lo;\nsetp.lt.u32 p, c, %0;\n@p bra.uni TL;\n}" :: "r"(t) : "memory");
}
#define PIN(v) v = __shfl_xor_sync(0xffffffffu, v, 0)
#define SCHED_FENCE(k) asm volatile("{\n.reg .pred p;\nsetp.eq.u32 p, %0, %1;\n@p exit;\n}" :: "r"(fence_reg), "r"(k) : "memory")
DI void bar_sync(int id, int n) { asm volatile("bar.sync %0, %1;" :: "r"(id), "r"(n) : "memory"); }
DI void bar_arrive(int id, int n) { asm volatile("bar.arrive %0, %1;" :: "r"(id), "r"(n) : "memory"); }
DI void fence_async() { asm volatile("fence.proxy.async.shared::cta;" ::: "memory"); }
DI void st_async4(uint32_t a, uint32_t x, uint32_t y, uint32_t z, uint32_t w, uint32_t mb) {
  asm volatile("st.async.weak.shared::cluster.mbarrier::complete_tx::bytes.v4.b32 [%0], {%1,%2,%3,%4}, [%5];"
               :: "r"(a), "r"(x), "r"(y), "r"(z), "r"(w), "r"(mb) : "memory");
}
DI void sts32(uint32_t a, uint32_t x) { asm volatile("st.shared.b32 [%0], %1;" :: "r"(a), "r"(x) : "memory"); }
DI void sts64(uint32_t a, uint32_t x, uint32_t y) { asm volatile("st.shared.v2.b32 [%0], {%1,%2};" :: "r"(a), "r"(x), "r"(y) : "memory"); }
DI void sts128(uint32_t a, uint32_t x, uint32_t y, uint32_t z, uint32_t w) {
  asm volatile("st.shared.v4.b32 [%0], {%1,%2,%3,%4};" :: "r"(a), "r"(x), "r"(y), "r"(z), "r"(w) : "memory");
}
DI uint32_t lds32(uint32_t a) { uint32_t x; asm volatile("ld.shared.b32 %0, [%1];" : "=r"(x) : "r"(a) : "memory"); return x; }
DI uint32_t lds32v(uint32_t a) { uint32_t x; asm volatile("ld.volatile.shared.b32 %0, [%1];" : "=r"(x) : "r"(a) : "memory"); return x; }
DI void lds64(uint32_t a, uint32_t& x, uint32_t& y) { asm volatile("ld.shared.v2.b32 {%0,%1}, [%2];" : "=r"(x), "=r"(y) : "r"(a) : "memory"); }
DI void lds128(uint32_t a, uint32_t* r) {
  asm volatile("ld.shared.v4.b32 {%0,%1,%2,%3}, [%4];" : "=r"(r[0]), "=r"(r[1]), "=r"(r[2]), "=r"(r[3]) : "r"(a) : "memory");
}
DI void lds128f(uint32_t a, float* r) {
  asm volatile("ld.shared.v4.f32 {%0,%1,%2,%3}, [%4];" : "=f"(r[0]), "=f"(r[1]), "=f"(r[2]), "=f"(r[3]) : "r"(a) : "memory");
}
DI void ldsm4t(uint32_t* r, uint32_t a) {
  asm volatile("ldmatrix.sync.aligned.m8n8.x4.trans.shared.b16 {%0,%1,%2,%3}, [%4];"
               : "=r"(r[0]), "=r"(r[1]), "=r"(r[2]), "=r"(r[3]) : "r"(a) : "memory");
}
DI void ldsm4t_in(uint32_t* r, uint32_t a, uint32_t t) {
  asm volatile("{\n.reg .pred p;\nsetp.ne.u32 p, %5, 0;\n@p ldmatrix.sync.aligned.m8n8.x4.trans.shared.b16 {%0,%1,%2,%3}, [%4];\n}"
               : "+r"(r[0]), "+r"(r[1]), "+r"(r[2]), "+r"(r[3]) : "r"(a), "r"(t) : "memory");
}
DI void lds128_in(uint32_t* r, uint32_t a, uint32_t t) {
  asm volatile("{\n.reg .pred p;\nsetp.ne.u32 p, %5, 0;\n@p ld.shared.v4.b32 {%0,%1,%2,%3}, [%4];\n}"
               : "+r"(r[0]), "+r"(r[1]), "+r"(r[2]), "+r"(r[3]) : "r"(a), "r"(t) : "memory");
}
DI void ldsm2t_in(uint32_t* r, uint32_t a, uint32_t t) {
  asm volatile("{\n.reg .pred p;\nsetp.ne.u32 p, %3, 0;\n@p ldmatrix.sync.aligned.m8n8.x2.trans.shared.b16 {%0,%1}, [%2];\n}" : "+r"(r[0]), "+r"(r[1]) : "r"(a), "r"(t) : "memory");
}
DI void reserve2(uint32_t* r) { asm volatile("{\n.reg .u64 t;\nmov.u64 t, %%clock64;\nmov.b64 {%0, %1}, t;\n}" : "=r"(r[0]), "=r"(r[1])); }
DI void scale_sum(float& x, float& y, float s, uint32_t t) {
  asm volatile("{\n.reg .pred p;\nsetp.ne.u32 p, %2, 0;\n@p mul.f32 %0, %0, %1;\n}" : "+f"(y) : "f"(s), "r"(t));
  asm volatile("{\n.reg .pred p;\nsetp.ne.u32 p, %3, 1;\n@p fma.rn.f32 %0, %0, %1, %2;\n}" : "+f"(x) : "f"(s), "f"(y), "r"(t));
}
DI void ldsm4(uint32_t* r, uint32_t a) {
  asm volatile("ldmatrix.sync.aligned.m8n8.x4.shared.b16 {%0,%1,%2,%3}, [%4];"
               : "=r"(r[0]), "=r"(r[1]), "=r"(r[2]), "=r"(r[3]) : "r"(a) : "memory");
}
DI void st_async1(uint32_t a, uint32_t x, uint32_t mb) {
  asm volatile("st.async.weak.shared::cluster.mbarrier::complete_tx::bytes.b32 [%0], %1, [%2];" :: "r"(a), "r"(x), "r"(mb) : "memory");
}
DI void stsm4(uint32_t a, uint32_t x, uint32_t y, uint32_t z, uint32_t w) {
  asm volatile("stmatrix.sync.aligned.m8n8.x4.shared.b16 [%0], {%1,%2,%3,%4};" :: "r"(a), "r"(x), "r"(y), "r"(z), "r"(w) : "memory");
}
DI void stsm4t(uint32_t a, uint32_t x, uint32_t y, uint32_t z, uint32_t w) {
  asm volatile("stmatrix.sync.aligned.m8n8.x4.trans.shared.b16 [%0], {%1,%2,%3,%4};" :: "r"(a), "r"(x), "r"(y), "r"(z), "r"(w) : "memory");
}
DI uint32_t pack_bf16(float lo, float hi) { uint32_t r; asm("cvt.rn.bf16x2.f32 %0, %1, %2;" : "=r"(r) : "f"(hi), "f"(lo)); return r; }
DI uint32_t pack_f16(float lo, float hi) { uint32_t r; asm("cvt.rn.f16x2.f32 %0, %1, %2;" : "=r"(r) : "f"(hi), "f"(lo)); return r; }
DI float ex2(float x) { float y; asm("ex2.approx.ftz.f32 %0, %1;" : "=f"(y) : "f"(x)); return y; }
DI float rcp(float x) { float y; asm("rcp.approx.ftz.f32 %0, %1;" : "=f"(y) : "f"(x)); return y; }
DI float bf_lo(uint32_t x) { return __uint_as_float(x << 16); }
DI float bf_hi(uint32_t x) { return __uint_as_float(x & 0xffff0000u); }
DI void mma16816(float* d, const uint32_t* a, uint32_t b0, uint32_t b1) {
  asm volatile("mma.sync.aligned.m16n8k16.row.col.f32.bf16.bf16.f32 {%0,%1,%2,%3}, {%4,%5,%6,%7}, {%8,%9}, {%0,%1,%2,%3};"
               : "+f"(d[0]), "+f"(d[1]), "+f"(d[2]), "+f"(d[3]) : "r"(a[0]), "r"(a[1]), "r"(a[2]), "r"(a[3]), "r"(b0), "r"(b1));
}
DI void mma16816z(float* d, const uint32_t* a, uint32_t b0, uint32_t b1) {
  asm volatile("mma.sync.aligned.m16n8k16.row.col.f32.bf16.bf16.f32 {%0,%1,%2,%3}, {%4,%5,%6,%7}, {%8,%9}, {%10,%10,%10,%10};"
               : "=f"(d[0]), "=f"(d[1]), "=f"(d[2]), "=f"(d[3]) : "r"(a[0]), "r"(a[1]), "r"(a[2]), "r"(a[3]), "r"(b0), "r"(b1), "f"(0.f));
}
DI void mma1688(float* d, uint32_t a0, uint32_t a1, uint32_t b0) {
  asm volatile("mma.sync.aligned.m16n8k8.row.col.f32.bf16.bf16.f32 {%0,%1,%2,%3}, {%4,%5}, {%6}, {%0,%1,%2,%3};"
               : "+f"(d[0]), "+f"(d[1]), "+f"(d[2]), "+f"(d[3]) : "r"(a0), "r"(a1), "r"(b0));
}
DI uint32_t add_bf16(uint32_t a, uint32_t b) { uint32_t r; asm("add.rn.bf16x2 %0, %1, %2;" : "=r"(r) : "r"(a), "r"(b)); return r; }
DI uint32_t mul_bf16(uint32_t a, uint32_t b) { uint32_t r; asm("mul.rn.bf16x2 %0, %1, %2;" : "=r"(r) : "r"(a), "r"(b)); return r; }
DI uint64_t make_desc(uint32_t addr, uint32_t lbo, uint32_t sbo, uint32_t swz) {
  return (uint64_t)((addr & 0x3FFFF) >> 4) | ((uint64_t)(lbo >> 4) << 16) | ((uint64_t)(sbo >> 4) << 32) | ((uint64_t)swz << 62);
}
#define WG_FENCE() asm volatile("wgmma.fence.sync.aligned;" ::: "memory")
#define WG_COMMIT() asm volatile("wgmma.commit_group.sync.aligned;" ::: "memory")
#define WG_WAIT(n) asm volatile("wgmma.wait_group.sync.aligned %0;" :: "n"(n) : "memory")
#define ACC8(d, o) "+f"(d[o]), "+f"(d[o + 1]), "+f"(d[o + 2]), "+f"(d[o + 3]), "+f"(d[o + 4]), "+f"(d[o + 5]), "+f"(d[o + 6]), "+f"(d[o + 7])
DI void wgmma_n32_rs(float* d, uint32_t a0, uint32_t a1, uint32_t a2, uint32_t a3, uint64_t db, int acc) {
  asm volatile("{\n.reg .pred p;\nsetp.ne.b32 p, %21, 0;\n"
               "wgmma.mma_async.sync.aligned.m64n32k16.f32.bf16.bf16 {%0,%1,%2,%3,%4,%5,%6,%7,%8,%9,%10,%11,%12,%13,%14,%15}, "
               "{%16,%17,%18,%19}, %20, p, 1, 1, 0;\n}\n"
               : ACC8(d, 0), ACC8(d, 8) : "r"(a0), "r"(a1), "r"(a2), "r"(a3), "l"(db), "r"(acc));
}
template <int TA>
DI void wgmma_n32_ss(float* d, uint64_t da, uint64_t db, int acc) {
  asm volatile("{\n.reg .pred p;\nsetp.ne.b32 p, %18, 0;\n"
               "wgmma.mma_async.sync.aligned.m64n32k16.f32.bf16.bf16 {%0,%1,%2,%3,%4,%5,%6,%7,%8,%9,%10,%11,%12,%13,%14,%15}, "
               "%16, %17, p, 1, 1, %19, 1;\n}\n"
               : ACC8(d, 0), ACC8(d, 8) : "l"(da), "l"(db), "r"(acc), "n"(TA));
}
DI void tma_load(uint32_t dst, const CUtensorMap* m, int c0, int c1, uint32_t mb) {
  asm volatile("cp.async.bulk.tensor.2d.shared::cluster.global.mbarrier::complete_tx::bytes [%0], [%1, {%3, %4}], [%2];"
               :: "r"(dst), "l"(m), "r"(mb), "r"(c0), "r"(c1) : "memory");
}
DI void tma_load3(uint32_t dst, const CUtensorMap* m, int row, uint32_t mb) {
  asm volatile("cp.async.bulk.tensor.3d.shared::cluster.global.mbarrier::complete_tx::bytes [%0], [%1, {%3, %4, %3}], [%2];"
               :: "r"(dst), "l"(m), "r"(mb), "r"(0), "r"(row) : "memory");
}
DI bool elect_one() {
  uint32_t p;
  asm volatile("{\n.reg .pred p;\nelect.sync _|p, 0xffffffff;\nselp.u32 %0, 1, 0, p;\n}" : "=r"(p));
  return p;
}
DI void bulk_s2s(uint32_t dst, uint32_t src, uint32_t bytes, uint32_t mb) {
  asm volatile("cp.async.bulk.shared::cluster.shared::cta.mbarrier::complete_tx::bytes [%0], [%1], %2, [%3];"
               :: "r"(dst), "r"(src), "r"(bytes), "r"(mb) : "memory");
}
DI void bulk_load(uint32_t dst, const void* src, uint32_t bytes, uint32_t mb) {
  asm volatile("cp.async.bulk.shared::cluster.global.mbarrier::complete_tx::bytes [%0], [%1], %2, [%3];" :: "r"(dst), "l"(src), "r"(bytes), "r"(mb) : "memory");
}
#define EVICT_FIRST ".reg .b64 pol;\ncreatepolicy.fractional.L2::evict_first.b64 pol, 1.0;\n"
DI void tma_load_ef(uint32_t dst, const CUtensorMap* m, int c0, int c1, uint32_t mb) {
  asm volatile("{\n" EVICT_FIRST "cp.async.bulk.tensor.2d.shared::cluster.global.mbarrier::complete_tx::bytes.L2::cache_hint [%0], [%1, {%3, %4}], [%2], pol;\n}"
               :: "r"(dst), "l"(m), "r"(mb), "r"(c0), "r"(c1) : "memory");
}
DI void tma_prefetch(const CUtensorMap* m, int c0, int c1) {
  asm volatile("cp.async.bulk.prefetch.tensor.2d.L2.global.tile [%0, {%1, %2}];" :: "l"(m), "r"(c0), "r"(c1) : "memory");
}
DI void tma_store(const CUtensorMap* m, uint32_t src, int c0, int c1) {
  asm volatile("cp.async.bulk.tensor.2d.global.shared::cta.bulk_group [%0, {%2, %3}], [%1];" :: "l"(m), "r"(src), "r"(c0), "r"(c1) : "memory");
}
DI uint4 ldg_relaxed(const void* p) {
  uint4 v;
  asm volatile("ld.relaxed.gpu.global.v4.b32 {%0,%1,%2,%3}, [%4];" : "=r"(v.x), "=r"(v.y), "=r"(v.z), "=r"(v.w) : "l"(p) : "memory");
  return v;
}
DI void stg_relaxed(void* p, uint32_t x, uint32_t y, uint32_t z, uint32_t w) {
  asm volatile("st.relaxed.gpu.global.v4.b32 [%0], {%1,%2,%3,%4};" :: "l"(p), "r"(x), "r"(y), "r"(z), "r"(w) : "memory");
}
DI void red_f16x8(void* p, uint32_t x, uint32_t y, uint32_t z, uint32_t w) {
  asm volatile("red.relaxed.gpu.global.add.noftz.v4.f16x2 [%0], {%1,%2,%3,%4};" :: "l"(p), "r"(x), "r"(y), "r"(z), "r"(w) : "memory");
}
DI void sq_acc(uint32_t& a, uint32_t x) { asm("fma.rn.bf16x2 %0, %1, %1, %0;" : "+r"(a) : "r"(x)); }
DI __half2 amax4(__half2 h, const uint32_t* v) {
  h = __hmax2_nan(__hmax2_nan(h, __habs2(*(const __half2*)&v[0])), __habs2(*(const __half2*)&v[1]));
  return __hmax2_nan(__hmax2_nan(h, __habs2(*(const __half2*)&v[2])), __habs2(*(const __half2*)&v[3]));
}
DI uint32_t wexp(__half2 h) { const uint32_t u = *(const uint32_t*)&h; return __reduce_max_sync(0xffffffffu, max((u >> 16) & 0x7fffu, u & 0x7fffu)) >> 7; }
DI float warp_sum(float v) {
#pragma unroll
  for (int o = 16; o; o >>= 1) v += __shfl_xor_sync(0xffffffffu, v, o);
  return v;
}

constexpr int SM_WO3 = 0;
constexpr int SM_X = 16384;
constexpr int XT = 36864;
constexpr int SM_EXP = 126976;
constexpr int SEGB = 10240;
constexpr int SM_BLK = SM_EXP + 8192;
constexpr int SM_VC = SM_BLK + 4 * SEGB;
constexpr int SM_PART = SM_VC + 16384;
constexpr int SM_QM = SM_PART + 4096;
constexpr int SM_E = SM_QM + 1024;
constexpr int SM_VM = SM_E + 1536;
constexpr int SM_OB = SM_VM + 2048;
constexpr int SM_FB = SM_OB + 2048;
constexpr int SM_STAGE = SM_X + XT;
constexpr int SM_M0 = SM_STAGE + 3 * 49152;
constexpr int SM_MISC = 210944;
constexpr int SM_WOST = 212992;
constexpr int SM_MEM = SM_WOST;
constexpr int SM_MAX = SM_MEM + 11264;
#define MEM_BLK(q) ((q) / 3 * 4096 + (q) % 3 * 1024)
constexpr int SM_TOTAL = 229376;
constexpr int MB_W = SM_MISC;
constexpr int MB_WO = SM_MISC + 24;
constexpr int MB_WO3 = SM_MISC + 32;
constexpr int MB_X = SM_MISC + 40;
constexpr int MB_S = SM_MISC + 64;
constexpr int MB_F = SM_MISC + 72;
constexpr int MB_VX = SM_MISC + 80;
constexpr int SC_FPAR = SM_MISC + 136;
constexpr int SC_DEAD = SM_MISC + 96;
constexpr int SC_UNSC = SM_MISC + 112;
constexpr int SC_OFL = SM_MISC + 1024;
constexpr int SC_EXPW = SM_MISC + 132;
constexpr int SC_ONES = SM_MISC + 144;
constexpr int SC_SS = SM_MISC + 160;
constexpr int SC_LAT = SM_MISC + 224;
constexpr int SC_TAG = SM_MISC + 232;
constexpr int SC_EPO = SM_MISC + 240;
constexpr int MB_XS = SM_MISC + 248;
constexpr int SC_XMAX = SM_MISC + 256;
constexpr int SC_PROF = 229376;

constexpr float SM_SCALE = 0.08838834764831845f;
constexpr float LOG2E = 1.4426950408889634f;
constexpr float E_LIM = 20.f;

template <bool B> struct BoolC { static constexpr bool value = B; };
template <int I> struct IntC { static constexpr int value = I; };
struct RMaps { CUtensorMap x, wq, wk, wv, wo; unsigned char* red; uint32_t poll; const unsigned char* oflag; };

DI uint32_t latest_hint(uint32_t h, uint32_t d, int s) {
  const uint32_t x = (((h | 0xc0c0c0c0u) - ((d >> 5) & 63) * 0x01010101u) & 0x3f3f3f3fu) | ((h ^ (((s >> 2) + 1) & 3) * 0x40404040u) & 0xc0c0c0c0u);
  const uint32_t y = __vmaxu2(x & 0x00ff00ffu, (x >> 8) & 0x00ff00ffu);
  return __reduce_max_sync(0xffffffffu, max(y & 0xffffu, y >> 16));
}
DI uint32_t near_half(uint32_t sb) {
  uint32_t a, b; lds64(sb + SC_LAT, a, b);
  return a > b;
}

template <int RT, int K0, int K1, bool D32 = false>
DI void xproj(float* acc, const uint32_t (&wa)[2][18][4], uint64_t xd) {
  if (XP & 1) return;
  WG_FENCE();
#pragma unroll
  for (int k = K0; k < ((XP & 128) ? K0 + 1 : K1); k++)
  {
    uint64_t d = xd + (uint64_t)(((k >> 1) * 4096 + (k & 1) * 32) >> 4);
    if (D32) asm("mov.b64 %0, {%1, %2};" : "=l"(d) : "r"((uint32_t)xd + (((k >> 1) * 4096 + (k & 1) * 32) >> 4)), "r"((uint32_t)(xd >> 32)));
    wgmma_n32_rs(acc, wa[RT][k][0], wa[RT][k][1], wa[RT][k][2], wa[RT][k][3], d, k != 0);
  }
  WG_COMMIT();
}

DI void load_w(uint32_t sb, const RMaps& tm, uint32_t rank, int c) {
  const int h = blockIdx.x / 3;
  mbar_expect(sb + MB_W + 8 * c, 49152);
  tma_load_ef(sb + SM_STAGE + c * 49152, rank < 2 ? &tm.wk : &tm.wv, h * DH + (rank == 1 ? 64 : 0), c * 192, sb + MB_W + 8 * c);
  tma_load_ef(sb + SM_STAGE + c * 49152 + 24576, rank < 2 ? &tm.wq : &tm.wv, h * DH + (rank == 0 ? 0 : 64), c * 192, sb + MB_W + 8 * c);
}
DI void seg_store(int seg, uint32_t slot, uint32_t sb) {
  asm volatile("cp.async.bulk.global.shared::cta.bulk_group [%0], [%1], 8192;"
               :: "l"(g_seg + ((size_t)slot * 96 + blockIdx.x) * 8192), "r"(sb + SM_BLK + (seg & 3) * SEGB) : "memory");
  asm volatile("cp.async.bulk.commit_group;" ::: "memory");
}
DI void seg_publish(int seg, uint32_t sb) {
  uint32_t v, own;
  lds64(sb + SC_EPO, v, own);
  asm volatile("cp.async.bulk.wait_group 0;" ::: "memory");
  asm volatile("st.relaxed.gpu.global.v2.b32 [%0], {%1,%2};" :: "l"(&g_sflag[blockIdx.x * 4]), "r"(v + seg), "r"(own) : "memory");
}

DI void proj_role(const uint32_t sb, const RMaps& tm, const bf16* __restrict__ x, const uint32_t rank, const int wg, const int w, const int lane) {
  const bool qk = rank < 2;
  uint32_t wa[2][18][4];
  float acc[16];
  const uint64_t xd0 = make_desc(sb + SM_X + wg * 64, 16, 1024, 1);
  {
    const int rr = (lane & 7) + ((lane >> 4) << 3);
    const uint32_t col = ((2 * w + ((lane >> 3) & 1)) ^ (lane & 7)) << 4;
    float ss = 0.f;
    bar_sync(3, 256);
    mbar_wait(sb + MB_X, 0);
    auto chunk = [&](auto cc) {
      constexpr int c = decltype(cc)::value;
      QSTAMP(2 + 2 * c);
      mbar_wait(sb + MB_W + 8 * c, 0);
      QSTAMP(3 + 2 * c);
#pragma unroll
      for (int rt = 1; rt >= 0; rt--)
#pragma unroll
        for (int k = 0; k < 6; k++)
          ldsm4t(wa[rt][c * 6 + k], sb + SM_STAGE + c * 49152 + (rt ^ wg) * 24576 + (64 * (k >> 1) + 32 * wg + 16 * (k & 1) + rr) * 128 + col);
      fence_async();
      if (c < 2) {
        bar_sync(3, 256);
        QSTAMP(17 + c);
        if (threadIdx.x == 0) {
          if (c == 0) tma_load(sb + SM_X + XT, &tm.wo, rank * 192, (blockIdx.x / 3) * DH, sb + MB_WO);
          else if (blockIdx.x < NSEG) bulk_load(sb + SM_X + 2 * XT, x + blockIdx.x * 32 * DM, XT, sb + MB_XS);
          else tma_load3(sb + SM_X + 2 * XT, &tm.x, 64, sb + MB_X + 16);
        }
        __syncwarp();
      } else {
        cluster_arrive();
      }
      xproj<1, 6 * c, 6 * c + 6>(acc, wa, xd0);
      if (!qk) {
        uint32_t q[4] = {0, 0, 0, 0};
#pragma unroll
        for (int rt = 0; rt < 2; rt++)
#pragma unroll
          for (int k = 0; k < 6; k++)
#pragma unroll
            for (int i = 0; i < 4; i++) sq_acc(q[i], wa[rt][c * 6 + k][i]);
#pragma unroll
        for (int i = 0; i < 4; i++) ss += bf_lo(q[i]) + bf_hi(q[i]);
      }
    };
    chunk(IntC<0>()); chunk(IntC<1>()); chunk(IntC<2>());
    ss = warp_sum(ss);
    if (lane == 0) sts32(sb + SC_SS + 4 * (wg * 4 + w), __float_as_uint(ss));
    bar_arrive(11, 384);
  }
  STAMP(1);
  QSTAMP(8);
  STAMP(2);

  uint32_t t16 = sb + (w * 32 + lane) * 16;
  uint32_t mem_a = sb + SM_MEM + wg * 512 + lane * 16;
  uint32_t fin_a = sb + (lane & 7) * 16 + SM_BLK + (qk ? (wg ^ 1) * 4096 + w * 256 + (lane & 8) * 16 + (lane & 16) * 64
                                              : wg * 4096 + w * 1024 + (lane & 8) * 64 + (lane & 16) * 8);
  PIN(t16); PIN(mem_a); PIN(fin_a);
  const uint32_t fence_reg = mem_a;
  const uint32_t fin2 = qk ? 2048 : 256;
  auto do_export = [&](auto retire, uint32_t always) {
    WG_WAIT(0);
    uint32_t p[2];
#pragma unroll
    for (int i = 0; i < 2; i++) {
      p[i] = pack_bf16(acc[8 * i], acc[8 * i + 1]);
      sts128(t16 + SM_EXP + wg * 4096 + i * 2048, p[i], pack_bf16(acc[8 * i + 2], acc[8 * i + 3]),
             pack_bf16(acc[8 * i + 4], acc[8 * i + 5]), pack_bf16(acc[8 * i + 6], acc[8 * i + 7]));
    }
    if (decltype(retire)::value)
      asm volatile("{\n.reg .pred p, q;\nsetp.ne.u32 p, %2, 0;\nsetp.ne.u32 q, %2, 1;\n@p ld.shared.b32 %0, [%3];\n@q ld.shared.b32 %1, [%3 + 4];\n"
                   "setp.ne.u32 p, %0, %1;\n@p exit;\n}" : "+r"(p[0]), "+r"(p[1]) : "r"(always), "r"(sb + SC_DEAD) : "memory");
  };
  uint32_t o[8];
  auto import = [&]() { lds128(t16 + SM_EXP + (wg ^ 1) * 4096, o); lds128(t16 + SM_EXP + (wg ^ 1) * 4096 + 2048, o + 4); };
  auto finish_from = [&](int seg, const float* d) {
    const uint32_t a = fin_a + (seg & 3) * SEGB;
#pragma unroll
    for (int i = 0; i < 8; i++) o[i] = add_bf16(pack_bf16(d[2 * i], d[2 * i + 1]), o[i]);
    stsm4(a, o[0], o[1], o[2], o[3]);
    stsm4(a + fin2, o[4], o[5], o[6], o[7]);
    fence_async();
  };
  auto finish = [&](int seg) { WG_WAIT(0); finish_from(seg, acc); };
  auto send_v = [&](int seg, int dst) {
    if (seg < NSEG - 1 && !(XP & 2) && elect_one())
      bulk_s2s(mapa(sb + SM_VC + (seg & 1) * 8192, dst), sb + SM_BLK + (seg & 3) * SEGB, 8192, mapa(sb + MB_VX + (seg & 1) * 8, dst));
    __syncwarp();
  };
  auto wait_v = [&](int seg) {
    if (seg < NSEG - 1 && !(XP & 2)) {
      mbar_wait(sb + MB_VX + (seg & 1) * 8, (seg >> 1) & 1);
      if (elect_one()) mbar_expect(sb + MB_VX + (seg & 1) * 8, 8192);
      __syncwarp();
    }
  };
  auto export_seg = [&](int seg, uint32_t slot) { if (!(XP & (4 | 8192)) && elect_one()) seg_store(seg, slot, sb); __syncwarp(); };
  auto publish = [&](int seg) { if (!(XP & (4 | 16384)) && elect_one()) seg_publish(seg, sb); __syncwarp(); };
  do_export(BoolC<false>(), 0);
  QSTAMP(9);
  SCHED_FENCE(11);
  xproj<0, 0, 18>(acc, wa, xd0);
  bar_sync(3, 256);
  QSTAMP(10);
  cluster_wait();
  QSTAMP(11);
  mbar_wait(sb + MB_X + 8, 0);
  QSTAMP(12);
  import();
  finish(0);
  SCHED_FENCE(12);
  uint64_t dA = xd0 + (XT >> 4);
  xproj<1, 0, 18>(acc, wa, dA);
  bar_sync(3, 256);
  if (!qk && wg == 0 && w < 2) send_v(0, w);
  if (wg == 0 && w == 3) export_seg(0, 0);
  QSTAMP(13);
  if (qk && wg == 0 && w == 0) wait_v(0);
  QSTAMP(14);
  bar_arrive(13, 384);
  if (!qk) {
    do_export(BoolC<false>(), 0);
    SCHED_FENCE(15);
    xproj<0, 0, 18>(acc, wa, dA);
    if (threadIdx.x == 0 && !(XP & 8)) { mbar_expect(sb + MB_X, XT); tma_load3(sb + SM_X, &tm.x, 96, sb + MB_X); }
    bar_sync(3, 256);
    mbar_wait(sb + MB_X + 16, 0);
    import();
    finish(1);
    SCHED_FENCE(16);
    dA += XT >> 4;
    xproj<1, 0, 18>(acc, wa, dA);
  }
  QSTAMP(15);
  WG_WAIT(0);
  bar_sync(0, 384);
  if (wg == 0 && w == 3) publish(0);
  QSTAMP(16);
  const int ro = __shfl_sync(0xffffffffu, near_half(sb) ^ wg, 0);
  STAMP(5);
  const uint32_t always = __shfl_sync(0xffffffffu, lds32(sb + SC_DEAD + 12), 0);
  const int ah = qk ? 1 : 2;
  int b2 = qk ? 2 : 0;
  int s = 0;
  uint32_t hint_lo = (uint32_t)(uint64_t)tm.red + HINT_OFF + blockIdx.x + (lane & 1) * 4096 + (lane >> 1) * 16384;
  PIN(hint_lo);
  auto post_hint = [&]() {
    uint32_t t;
    asm volatile("{\n.reg .u64 g;\nmov.u64 g, %%globaltimer;\ncvt.u32.u64 %0, g;\n}" : "=r"(t) :: "memory");
    asm volatile("{\n.reg .pred p;\n.reg .b64 a;\n.reg .u32 t;\nsetp.lt.u32 p, %0, %1;\nmov.b64 a, {%2, %3};\n"
                 "bfe.u32 t, %5, 5, 6;\nor.b32 t, t, %4;\n@p st.relaxed.gpu.global.u8 [a], t;\n}"
                 :: "r"(t16), "r"(sb + 160), "r"(hint_lo + RED_SLOT(s)), "r"((uint32_t)((uint64_t)tm.red >> 32)), "r"(((s >> 2) + 1) << 6), "r"(t) : "memory");
  };
  auto memproj = [&](auto second, int id, uint32_t dep, float u0, float u1, float* r) {
    constexpr bool R1 = decltype(second)::value;
    uint32_t b[NUP][4], b0[4];
    if (R1) asm volatile("{\n.reg .pred p;\nsetp.eq.u32 p, %0, %1;\n@p exit;\n}" :: "r"(dep), "r"(id) : "memory");
    bar_sync(R1 ? 2 : 1, 256);
    PROF(0);
    ldsm4t(b0, mem_a);
#pragma unroll
    for (int q = 0; q < NUP; q++) {
      if (R1 && q == 2) {
        bar_sync(11, 256);
        SCHED_FENCE(id + 1);
      }
      ldsm4t(b[q], mem_a + MEM_BLK(q + 1));
    }
    mma16816z(&acc[0], wa[0][0], b0[0], b0[1]);
    mma16816z(&acc[4], wa[1][0], b0[0], b0[1]);
    mma16816z(&acc[8], wa[0][1], b0[2], b0[3]);
    mma16816z(&acc[12], wa[1][1], b0[2], b0[3]);
#pragma unroll
    for (int q = 1; q < 9; q++) {
      uint32_t* const c = b[(q - 1) % NUP];
      mma16816(&acc[0], wa[0][2 * q], c[0], c[1]);
      mma16816(&acc[4], wa[1][2 * q], c[0], c[1]);
      mma16816(&acc[8], wa[0][2 * q + 1], c[2], c[3]);
      mma16816(&acc[12], wa[1][2 * q + 1], c[2], c[3]);
      if (R1 && q + NUP == 9) bar_sync(3, 256);
      if (q + NUP < 9) ldsm4t_in(c, mem_a + MEM_BLK(q + NUP), always);
      else if (R1 && q + NUP < 11) lds128_in(c, t16 + SM_PART + (10 - q - NUP) * 2048, always);
      else if (!R1 && q == 8) { bar_arrive(11, 256); lds128_in(c, sb + SC_DEAD, always); u0 = u1 = __uint_as_float(c[3]); }
    }
#pragma unroll
    for (int i = 0; i < 8; i++) {
      const float u = i < 4 ? u0 : u1;
      r[i] = R1 ? fmaf(acc[8 + i], u, (acc[i] + __uint_as_float(b[(8 + i / 4) % NUP][i & 3])) * u) : fmaf(acc[i], u, acc[8 + i]);
    }
  };
  if (ro == 0) {
#pragma unroll 1
    while (true) {
      do_export(BoolC<true>(), always);
      PROFP(3);
      if (s == 8) STAMP(6);
      float r[8];
      memproj(BoolC<false>(), 30, 0, 0.f, 0.f, r);
      sts128(t16 + SM_PART, __float_as_uint(r[0]), __float_as_uint(r[1]), __float_as_uint(r[2]), __float_as_uint(r[3]));
      sts128(t16 + SM_PART + 2048, __float_as_uint(r[4]), __float_as_uint(r[5]), __float_as_uint(r[6]), __float_as_uint(r[7]));
      bar_arrive(3, 256);
      PROF(1);
      bar_sync(9, 256);
      post_hint();
      if (w == 3 && s) publish(s);
      if (s == NSEG - 1) break;
      if (w == 1) {
        uint32_t m[8];
        lds128(t16 + SM_MAX - 512, m); lds128(t16 + SM_MAX, m + 4);
        const int em = (wexp(amax4(amax4(*(const __half2*)&m[0], m), m + 4)) >> 3) + (int)(lds32(sb + SC_UNSC + (s & 1) * 8) >> 23) - 15;
        const int ex = max(s ? em : 0, (int)lds32(sb + SC_XMAX + 4 * s)) - 127 + (int)lds32(sb + SC_EXPW);
        sts32(sb + SC_UNSC + (~s & 1) * 8, (127 + min(max(ex, -120), 120)) << 23);
        __syncwarp();
        if (elect_one()) mbar_arrive(sb + MB_S);
      }
      SCHED_FENCE(9);
      bar_sync(5, qk ? N5 : 256);
      PROF(2);
      import();
      xproj<0, 0, 18>(acc, wa, dA);
      WG_WAIT(0);
      bar_sync(10, 256);
      SCHED_FENCE(17);
      dA += (int64_t)(b2 ? XT >> 4 : -(XT >> 3));
      finish(s + ah);
      if (w != 3) bar_arrive(13, 384);
      PROF(6);
      SCHED_FENCE(14);
      bar_sync(12, 256);
      PROF(7);
      xproj<1, 0, 18, true>(acc, wa, dA);
      bar_arrive(14, 256);
      b2 = b2 == 2 ? 0 : b2 + 1;
      s++;
      if (w == 3) {
        const uint32_t slot = s < lds32(sb + SC_EPO + 4) ? s & 7 : s;
        bar_sync(13, 384);
        export_seg(s, slot);
      }
      PROFP(8);
    }
    if (!qk) bar_arrive(5, 256);
  } else {
    uint32_t km[4];
    auto send_km = [&]() {
      if (XP & (4 | 4096)) return;
      uint32_t t, u;
      lds64(sb + SC_TAG, t, u);
      t |= km[0] & ~1u; u += s * (NH * 4096);
      if (qk)
        asm volatile("{\n.reg .u32 o;\n.reg .u64 a;\nshr.u32 o, %0, 1;\nadd.u32 o, o, %1;\nmad.wide.u32 a, o, 1, %2;\nst.relaxed.gpu.global.v2.b32 [a], {%3,%4};\n}"
                     :: "r"(t16), "r"(u), "l"(g_km), "r"(t), "r"(km[1]) : "memory");
      else
        asm volatile("{\n.reg .u32 o;\n.reg .u64 a;\nadd.u32 o, %0, %1;\nmad.wide.u32 a, o, 1, %2;\nst.relaxed.gpu.global.v4.b32 [a], {%3,%4,%5,%6};\n}"
                     :: "r"(t16), "r"(u), "l"(g_km), "r"(t), "r"(km[1]), "r"(km[2]), "r"(km[3]) : "memory");
    };
#pragma unroll 1
    while (true) {
      do_export(BoolC<true>(), always);
      if (!qk && w == 2) send_v(s + 1, 0);
      PROFP(3);
      if (s == 8) STAMP(6);
      const uint32_t tl = ((t16 >> 8) ^ wg) & 1, am = (t16 & ~256u) - w * 256;
      const float un = __uint_as_float(lds32(sb + SC_UNSC + (s & 1) * 8));
      float r[8];
      if (qk) {
        uint32_t a0 = am + (tl ? SM_QM : SM_BLK + 8192 + (s & 3) * SEGB);
        float u0 = wg ? un * (SM_SCALE * LOG2E) : un, u1 = wg ? un : un * (SM_SCALE * LOG2E);
        PIN(a0); PIN(u0); PIN(u1);
        memproj(BoolC<true>(), 32, a0, u0, u1, r);
        const uint32_t p0 = pack_bf16(r[0], r[1]), p1 = pack_bf16(r[2], r[3]), p2 = pack_bf16(r[4], r[5]), p3 = pack_bf16(r[6], r[7]);
        stsm4(a0, p0, p1, p2, p3);
        bar_arrive(4, 256);
        km[0] = wg ? p2 : p0; km[1] = wg ? p3 : p1;
      } else {
        const uint32_t d0 = s < NSEG - 1 ? 0 : 2, d1 = s < NSEG - 1 ? 1 : 2;
        uint32_t r0 = mapa(t16 + SM_VM, d0), r1 = mapa(t16 + SM_VM, d1);
        PIN(r0); PIN(r1);
        memproj(BoolC<true>(), 34, r0 | r1, un, un, r);
        const uint32_t p0 = pack_bf16(r[0], r[1]), p1 = pack_bf16(r[2], r[3]), p2 = pack_bf16(r[4], r[5]), p3 = pack_bf16(r[6], r[7]);
        const uint32_t v0 = wg ? p2 : p0, v1 = wg ? p3 : p1, v2 = wg ? p0 : p2, v3 = wg ? p1 : p3;
        st_async4(r0, v0, v1, v2, v3, mapa(sb + MB_S, d0));
        st_async4(r1, v0, v1, v2, v3, mapa(sb + MB_S, d1));
        bar_arrive(5, 256);
        sts128(t16 + SM_VM, v0, v1, v2, v3);
        __syncwarp();
        if (elect_one()) mbar_arrive(sb + MB_S);
        km[0] = v0; km[1] = v1; km[2] = v2; km[3] = v3;
      }
      PROF(1);
      auto rearm = [&]() { mbar_wait(sb + MB_S, s & 1); if (elect_one()) mbar_expect(sb + MB_S, qk ? 640 + 2048 : 1280); __syncwarp(); };
      if (s == NSEG - 1 && w != 1) {
      } else if (w == 1) {
        if ((t16 & 384) == 0) stg_relaxed(tm.red + (RED_SLOT(s + 2) + RED_LINE(blockIdx.x)) + (t16 & 112), 0, 0, 0, 0);
        uint32_t base, own;
        lds64(sb + SC_EPO, base, own);
        if ((int)(lds32v(sb + SC_OFL) - base) < s - 7) sts32(sb + SC_EPO + 4, min(own, s + 1));
        if (elect_one()) bulk_load(sb + SC_OFL, tm.oflag + blockIdx.x * 128, 16, sb + MB_XS);
      } else if (w == 0) {
        const int tn = s + ah + 1;
        if (tn + 1 < NSEG && !(XP & 8) && elect_one()) {
          const int b0 = b2 == 2 ? 0 : b2 + 1;
          mbar_expect(sb + MB_X + 8 * b0, XT);
          tma_load3(sb + SM_X + b0 * XT, &tm.x, (tn + 1) * 32, sb + MB_X + 8 * b0);
        }
        if (tn < NSEG && (!(XP & 8) || tn < 3)) mbar_wait(sb + MB_X + 8 * b2, (tn / 3) & 1);
      } else if (w == 2) {
        if (!qk) send_v(s + 1, 1);
      } else {
        rearm();
      }
      __syncwarp();
      send_km();
      if (s == NSEG - 1) break;
      import();
      PROF(4);
      SCHED_FENCE(10);
      bar_sync(7, 256);
      xproj<0, 0, 18>(acc, wa, dA);
      bar_arrive(12, 256);
      dA += (int64_t)(b2 ? XT >> 4 : -(XT >> 3));
      finish(s + ah);
      if (qk && w == 0) wait_v(s + 1);
      bar_arrive(13, 384);
      PROF(6);
      SCHED_FENCE(13);
      bar_sync(14, 256);
      PROF(7);
      xproj<1, 0, 18>(acc, wa, dA);
      b2 = b2 == 2 ? 0 : b2 + 1;
      s++;
      PROFP(8);
    }
  }
  bar_arrive(0, 384);
  STAMP(3);
  cluster_sync();
  STAMP(4);
}

DI void attn_role(const uint32_t sb, unsigned char* smem_raw, const RMaps& tm, const uint32_t RANK, const bf16* __restrict__ x, const bf16* __restrict__ mem0,
                  const int w, const int lane) {
  const int t2 = w * 32 + lane;
  uint32_t wo[8][4], w1[8][4];
  const uint32_t wo_lane = sb + ((lane & 7) + ((lane >> 4) << 3)) * 128 + (((w + 4 * ((lane >> 3) & 1)) ^ (lane & 7)) << 4);
  unsigned char* const g_red = tm.red;
  {
    const uint32_t tag = *(volatile unsigned*)&g_epoch + 1;
    QSTAMP(0);
    bar_sync(0, 160);
    QSTAMP(1);
    cluster_arrive();
    __half2 hx = __float2half2_rn(0.f);
    if (t2 == 0) { sts32(sb + SC_OFL, (tag - 1) * NSEG); sts64(sb + SC_EPO, (tag - 1) * NSEG + 1, NSEG); sts64(sb + SC_TAG, tag & 1, blockIdx.x / 3 * 4096 + (RANK < 2 ? RANK * 1024 - (sb >> 1) : 2048 - sb)); sts32(sb + SC_UNSC, __float_as_uint(1.f)); sts128(sb + SC_DEAD, 0, 0, 0, 0x3f800000u); sts64(sb + SC_FPAR, 0, 0); sts128(sb + SC_ONES, 0x3f803f80u, 0x3f803f80u, 0x3f803f80u, 0x3f803f80u); }
    WSTAMP(27);
    uint32_t q[8] = {0, 0, 0, 0, 0, 0, 0, 0};
    QSTAMP(2);
    mbar_wait(sb + MB_WO3, 0);
    QSTAMP(3);
    uint32_t mv[5][4];
#pragma unroll
    for (int i = 0; i < 5; i++) {
      ldsm4(mv[i], sb + SM_M0 + (lane & 7) * (DM * 2) + min(w + 4 * i, 17) * 64 + (lane >> 3) * 16);
      if (blockIdx.x == 0) hx = amax4(hx, mv[i]);
    }
#pragma unroll
    for (int k = 0; k < 8; k++) {
      ldsm4t(wo[k], wo_lane + SM_WO3 + k * 2048); ldsm4t(w1[k], wo_lane + SM_WOST + k * 2048);
#pragma unroll
      for (int i = 0; i < 4; i++) { sq_acc(q[i], wo[k][i]); sq_acc(q[i], w1[k][i]); }
    }
    bar_sync(6, 128);
#pragma unroll
    for (int k = 0; k < 8; k++) sts128(sb + SM_WO3 + t2 * 16 + k * 2048, wo[k][0], wo[k][1], wo[k][2], wo[k][3]);
#pragma unroll
    for (int i = 0; i < 5; i++) {
      const int c = (w + 4 * i) * 32;
      if (c < DM) stsm4t(sb + SM_MEM + (c + c / 192 * 64 + lane) * 16, mv[i][0], mv[i][1], mv[i][2], mv[i][3]);
    }
    bar_arrive(1, 256); bar_arrive(2, 256); bar_arrive(9, 256);
    QSTAMP(4);
    mbar_wait(sb + MB_WO, 0);
    QSTAMP(5);
#pragma unroll
    for (int k = 0; k < 8; k++) ldsm4t(wo[k], wo_lane + SM_X + XT + k * 2048);
    fence_async();
    bar_sync(6, 128);
    if (t2 == 32) tma_load3(sb + SM_X + XT, &tm.x, 32, sb + MB_X + 8);
    __syncwarp();
#pragma unroll
    for (int k = 0; k < 8; k++)
#pragma unroll
      for (int i = 0; i < 4; i++) sq_acc(q[4 + i], wo[k][i]);
    float ss = 0.f;
#pragma unroll
    for (int i = 0; i < 8; i++) ss += bf_lo(q[i]) + bf_hi(q[i]);
    ss = warp_sum(ss);
    if (lane == 0) sts32(sb + SC_SS + 4 * (8 + w), __float_as_uint(ss));
    if (blockIdx.x < NSEG) {
      mbar_wait(sb + MB_XS, 0);
#pragma unroll
      for (int i = 0; i < 18; i++) { uint32_t v[4]; lds128(sb + SM_X + 2 * XT + t2 * 16 + i * 2048, v); hx = amax4(hx, v); }
      fence_async();
      bar_sync(6, 128);
      if (t2 == 32) tma_load3(sb + SM_X + 2 * XT, &tm.x, 64, sb + MB_X + 16);
      __syncwarp();
    }
    sts32(sb + SC_SS + 4 * (12 + w), wexp(hx));
    QSTAMP(6);
    bar_sync(11, 384);
    QSTAMP(7);
    if (t2 == 0) {
      float a[16];
#pragma unroll
      for (int i = 0; i < 4; i++) lds128f(sb + SC_SS + 16 * i, &a[4 * i]);
      stg_relaxed(&g_stats[blockIdx.x * 2], __float_as_uint(((a[0] + a[1]) + (a[2] + a[3])) + ((a[4] + a[5]) + (a[6] + a[7]))),
                  __float_as_uint((a[8] + a[9]) + (a[10] + a[11])),
                  max(max(__float_as_uint(a[12]), __float_as_uint(a[13])), max(__float_as_uint(a[14]), __float_as_uint(a[15]))), tag);
    }
    __syncwarp();
    WSTAMP(24);
    QSTAMP(8);
    cluster_wait();
    QSTAMP(9);
    if (w == 0) {
      uint4 v[3];
      int n = 0;
      while (true) {
#pragma unroll
        for (int i = 0; i < 3; i++) v[i] = ldg_relaxed(&g_stats[(i * 32 + lane) * 2]);
        if (__all_sync(0xffffffffu, v[0].w == tag && v[1].w == tag && v[2].w == tag) || ++n > SPIN_LIMIT) break;
        __nanosleep(100);
      }
      WSTAMP(25);
      QSTAMP(10);
      const float sv = warp_sum(__uint_as_float(v[0].x) + __uint_as_float(v[1].x) + __uint_as_float(v[2].x));
      const float so = warp_sum(__uint_as_float(v[0].y) + __uint_as_float(v[1].y) + __uint_as_float(v[2].y));
      const int expW = ((int)(__float_as_uint(sv) >> 23) + (int)(__float_as_uint(so) >> 23) - 254 + 2 + 10 + 1) >> 1;
      sts32(sb + SC_XMAX + 4 * lane, v[0].z); sts32(sb + SC_XMAX + 128 + 4 * lane, v[1].z);
      sts32(sb + SC_EXPW, expW + 1 - 15);
      if (blockIdx.x == 0 && lane == 0) *(volatile unsigned*)&g_epoch = tag;
      sts32(sb + SC_FPAR + 4, 1);
    } else if (w < 3) {
      const uint32_t u = blockIdx.x >> 4;
      unsigned char* const z = g_red + 98304 + (blockIdx.x & 15) * 128 + (u & 1) * 2048 + (u & 6) * 4096 + (((u >> 1) ^ w) & 1) * 4096 + lane * 4;
      stg_relaxed32(z, 0);
      uint32_t best = 0xffffffffu;
#pragma unroll 1
      for (int i = 0; i < 64; i++) {
        uint32_t dt;
        asm volatile("{\n.reg .pred p;\n.reg .u32 c, v;\nmov.u32 c, %%clock;\n"
                     "atom.relaxed.gpu.global.exch.b32 v, [%1], 0;\nsetp.eq.u32 p, v, 0;\nmov.u32 %0, 0;\n@p mov.u32 %0, %%clock;\nsub.u32 %0, %0, c;\n}"
                     : "=r"(dt) : "l"(z) : "memory");
        best = min(best, dt);
        if (lds32v(sb + SC_FPAR + 4) && i >= 1) break;
      }
      sts32(sb + SC_LAT + (w - 1) * 4, best);
    }
    QSTAMP(11);
    bar_sync(13, 384);
    bar_arrive(0, 384);
    QSTAMP(12);
    WSTAMP(26);
  }

  const uint32_t nh = __shfl_sync(0xffffffffu, near_half(sb), 0);
  uint32_t l16 = sb + lane * 16;
  PIN(l16);
#define LV ((l16 >> 4) & 31)
#define fence_reg l16
  const uint32_t red_lo = (uint32_t)(uint64_t)g_red, red_hi = (uint32_t)((uint64_t)g_red >> 32);
  uint32_t lp;
  auto slot = [&](int s, uint32_t c, uint32_t ofs) {
    const uint32_t lo = lp | (red_lo + ((w >> 1) * 4 + (w & 1) * 2 + ((w ^ c) & 1)) * 4096 + RED_SLOT(s) + ofs);
    uint64_t a; asm("mov.b64 %0, {%1, %2};" : "=l"(a) : "r"(lo), "r"(red_hi));
    return (unsigned char*)a;
  };
  const uint32_t always = __shfl_sync(0xffffffffu, lds32(sb + SC_DEAD + 12), 0);
  const int mode0 = RANK < 2 ? w : w | 4;
  auto hint_addr = [&](int s) { return min(LV, 23u) * 4 + (red_lo + HINT_OFF + nh * 4096 + w * 16384 + RED_SLOT(s)); };
  auto load_hints = [&](uint32_t lo) {
    uint64_t a; asm("mov.b64 %0, {%1, %2};" : "=l"(a) : "r"(lo), "r"(red_hi));
    return ldg_relaxed32((const void*)a);
  };
  int s = 0;
  bool bad = false;
#pragma unroll 1
  while (true) {
    const uint32_t par = s & 1;
    uint32_t vx[4][4], hints;
    auto load_vx = [&]() {
      const uint32_t va = l16 + (RANK < 2 ? SM_VC + par * 8192 : SM_BLK + (s & 3) * SEGB) + w * 1024 + ((LV >> 3) & 1) * 384 - (LV >> 4) * 128;
#pragma unroll
      for (int i = 0; i < 4; i++) ldsm4(vx[i], va + (i & 1) * 4096 + (i >> 1) * 256);
    };
    auto retire = [&](uint32_t x) {
      asm volatile("{\n.reg .pred p;\nsetp.eq.u32 p, %0, 0;\n@p exit;\n}" :: "r"(vx[0][0] | vx[1][0] | vx[2][0] | vx[3][0] | x) : "memory");
    };
    auto scores = [&](auto memkeys, auto first, float* sc) {
      constexpr bool MK = decltype(memkeys)::value, FIRST = decltype(first)::value;
      uint32_t kb[4][4], qb[2][4];
      const uint32_t m = LV >> 3;
      uint32_t kaddr = l16 + SM_BLK + 4096 + (s & 3) * SEGB + w * 2048 + (m & 1) * (MK ? 128 : 896) - (m >> 1) * 128;
      if (MK) { PIN(kaddr); }
      else {
#pragma unroll
        for (int k = 0; k < 4; k++) ldsm4t(kb[k], kaddr + k * 256);
      }
      if (FIRST) { load_vx(); retire(MK ? kaddr : kb[0][0] | kb[1][0] | kb[2][0] | kb[3][0] | l16); bar_sync(4, 256); PROF(4); }
      ldsm4t(qb[0], l16 + SM_QM);
      if (MK) ldsm4t(kb[0], kaddr);
      ldsm4t(qb[1], l16 + SM_QM + 512);
      if (MK) ldsm4t(kb[2], kaddr + 512);
      float c[4][4];
      mma16816z(c[0], kb[0], qb[0][0], qb[0][1]); mma16816z(c[1], kb[MK ? 0 : 1], qb[0][2], qb[0][3]);
      mma16816z(c[2], kb[2], qb[1][0], qb[1][1]); mma16816z(c[3], kb[MK ? 2 : 3], qb[1][2], qb[1][3]);
      if (FIRST) bar_arrive(5, N5);
#pragma unroll
      for (int i = 0; i < (MK ? 2 : 4); i++) sc[i] = ((c[0][i] + c[1][MK ? i + 2 : i]) + c[2][i]) + c[3][MK ? i + 2 : i];
    };
    auto send = [&](auto memkeys) {
      constexpr bool MK = decltype(memkeys)::value;
      constexpr int N = MK ? 1 : 2;
      const uint32_t sa = sb + LV * 4 + SM_E + (MK ? 1024 + RANK * 128 : RANK * 512 + w * 256);
      uint32_t ra[N][2], mb[N][2];
#pragma unroll
      for (int i = 0; i < N; i++)
#pragma unroll
        for (int j = 0; j < 2; j++) {
          ra[i][j] = mapa(sa + i * 128, j ? 2 : RANK ^ 1); mb[i][j] = mapa(sb + MB_S, j ? 2 : RANK ^ 1);
          PIN(ra[i][j]);
        }
      float sc[4];
      scores(memkeys, BoolC<true>(), sc);
      uint32_t e[N];
#pragma unroll
      for (int i = 0; i < N; i++) {
        e[i] = pack_bf16(ex2(sc[2 * i]), ex2(sc[2 * i + 1]));
        if (!(fmaxf(fabsf(sc[2 * i]), fabsf(sc[2 * i + 1])) <= E_LIM)) e[i] = 0x7fff7fffu;
        st_async1(ra[i][0], e[i], mb[i][0]);
        st_async1(ra[i][1], e[i], mb[i][1]);
      }
#pragma unroll
      for (int i = 0; i < N; i++) sts32(sa + i * 128, e[i]);
      __syncwarp();
      if (l16 == sb) mbar_arrive(sb + MB_S);
      PROF(5);
    };
    const int mode = bad ? 8 : mode0;
    if (mode < 2) {
      send(BoolC<false>());
    } else if (mode == 2) {
      send(BoolC<true>());
    } else if (mode == 8) {
      load_vx();
      retire(l16);
      const uint32_t fp = lds32(sb + SC_FPAR);
      bar_sync(6, 128);
      if (w == 0 && l16 == sb) { sts32(sb + SC_FPAR, fp ^ 1); mbar_expect(sb + MB_F, 3072); }
      if (RANK < 2 && w < 3) {
        float sc[4] = {0.f, 0.f, 0.f, 0.f};
        if (w < 2) scores(BoolC<false>(), BoolC<false>(), sc); else scores(BoolC<true>(), BoolC<false>(), sc);
#pragma unroll 1
        for (int r = 0; r < 3; r++)
          st_async4(mapa(l16 + SM_FB + RANK * 1536 + w * 512, r), __float_as_uint(sc[0]), __float_as_uint(sc[1]), __float_as_uint(sc[2]), __float_as_uint(sc[3]), mapa(sb + MB_F, r));
      }
      mbar_wait(sb + MB_F, fp);
      float a[12];
#pragma unroll
      for (int j = 0; j < 3; j++) {
        float b[4];
        lds128f(l16 + SM_FB + j * 512, a + 4 * j); lds128f(l16 + SM_FB + 1536 + j * 512, b);
#pragma unroll
        for (int i = 0; i < 4; i++) a[4 * j + i] += b[i];
      }
      float m0 = fmaxf(fmaxf(fmaxf(a[0], a[2]), fmaxf(a[4], a[6])), a[8]), m1 = fmaxf(fmaxf(fmaxf(a[1], a[3]), fmaxf(a[5], a[7])), a[9]);
#pragma unroll
      for (int o = 4; o < 32; o <<= 1) { m0 = fmaxf(m0, __shfl_xor_sync(0xffffffffu, m0, o)); m1 = fmaxf(m1, __shfl_xor_sync(0xffffffffu, m1, o)); }
#pragma unroll
      for (int i = 0; i < 5; i++) {
        const uint32_t ea = sb + SM_E + LV * 4 + (i < 4 ? i * 128 : 1024);
        sts32(ea, pack_bf16(ex2(a[2 * i] - m0), ex2(a[2 * i + 1] - m1)));
        sts32(ea + (i < 4 ? 512 : 128), 0x3f803f80u);
      }
      __syncwarp();
    } else {
      load_vx();
      if (mode == 3) bar_arrive(4, 256);
      retire(l16 + 1);
    }
    {
      uint32_t wa[4], wb[4], oc[4];
      constexpr int WS = 2048;
      const uint32_t w3a = l16 + SM_WO3 + w * 512;
      lds128(w3a + KP(0) * WS, wa); lds128(w3a + KP(1) * WS, wb); lds128(sb + SC_ONES, oc);
      uint32_t e[10], p[5], vm[4], ob[4];
      float o0[4], o1[4], f[3][2][4], rs[4];
      reserve2(vm); reserve2(vm + 2); reserve2(e + 8);
      hints = hint_addr(s);
      PIN(hints);
      mbar_wait(sb + MB_S, par);
      PROF(6);
      ldsm4t(e, l16 + SM_E); ldsm2t_in(e + 8, l16 + SM_E + 1024, always); ldsm4t(e + 4, l16 + SM_E + 512);
      lds128_in(vm, l16 + w * 512 + SM_VM, always);
      const float scl = __uint_as_float(lds32(sb + SC_UNSC + 8 - par * 8));
      hints = load_hints(hints);
#pragma unroll
      for (int i = 0; i < 4; i++) p[i] = mul_bf16(e[i], e[4 + i]);
      p[4] = mul_bf16(e[8], e[9]);
      mma16816z(o0, vx[0], p[0], p[1]); mma16816z(o1, vx[1], p[0], p[1]); mma16816z(rs, oc, p[0], p[1]);
      mma16816(o0, vx[2], p[2], p[3]); lds128_in(vx[2], w3a + KP(2) * WS, always);
      mma16816(o1, vx[3], p[2], p[3]); lds128_in(vx[3], w3a + KP(3) * WS, always);
      mma16816(rs, oc, p[2], p[3]);
      mma1688(o0, vm[0], vm[1], p[4]); mma1688(o1, vm[2], vm[3], p[4]); mma1688(rs, oc[0], oc[1], p[4]);
      stsm4(l16 + w * 512 + SM_OB, pack_bf16(o0[0], o0[1]), pack_bf16(o0[2], o0[3]), pack_bf16(o1[0], o1[1]), pack_bf16(o1[2], o1[3]));
      bar_sync(6, 128);
      PROF(7);
      ldsm4t_in(oc, l16 + SM_OB, always);
      bad = __any_sync(0xffffffffu, !(rs[0] + rs[1] > 0.f) && !bad);
      rs[0] *= scl; rs[1] *= scl;
      asm volatile("{\n.reg .pred p;\nsetp.ne.u32 p, %1, 0;\n@p rcp.approx.ftz.f32 %0, %0;\n}" : "+f"(rs[0]) : "r"(always));
      asm volatile("{\n.reg .pred p;\nsetp.ne.u32 p, %1, 1;\n@p rcp.approx.ftz.f32 %0, %0;\n}" : "+f"(rs[1]) : "r"(always));
      asm volatile("lop3.b32 %0, %1, %2, %3, 0xfe;" : "=r"(lp) : "r"((l16 & 128) * 2), "r"((l16 & 256) * 4), "r"(l16 & 112));
      if (bad) continue;
      ldsm4t(ob, l16 + SM_OB + 512);
      mma16816z(f[2][0], wa, oc[0], oc[1]); mma16816z(f[2][1], wb, oc[2], oc[3]);
      mma16816z(f[0][0], wo[0], oc[0], oc[1]); mma16816z(f[0][1], wo[4], oc[2], oc[3]);
      mma16816z(f[1][0], w1[0], oc[0], oc[1]); mma16816z(f[1][1], w1[4], oc[2], oc[3]);
      ldsm4t_in(oc, l16 + SM_OB + 1024, always);
      mma16816(f[2][0], vx[2], ob[0], ob[1]); lds128_in(vx[2], w3a + KP(4) * WS, always);
      mma16816(f[2][1], vx[3], ob[2], ob[3]); lds128_in(vx[3], w3a + KP(5) * WS, always);
      mma16816(f[0][0], wo[1], ob[0], ob[1]); mma16816(f[0][1], wo[5], ob[2], ob[3]);
      mma16816(f[1][0], w1[1], ob[0], ob[1]); mma16816(f[1][1], w1[5], ob[2], ob[3]);
      ldsm4t_in(ob, l16 + SM_OB + 1536, always);
      mma16816(f[0][0], wo[2], oc[0], oc[1]); mma16816(f[0][1], wo[6], oc[2], oc[3]);
      mma16816(f[2][0], vx[2], oc[0], oc[1]); lds128_in(vx[2], w3a + KP(6) * WS, always);
      mma16816(f[2][1], vx[3], oc[2], oc[3]); lds128_in(vx[3], w3a + KP(7) * WS, always);
      mma16816(f[1][0], w1[2], oc[0], oc[1]); mma16816(f[1][1], w1[6], oc[2], oc[3]);
      mma16816(f[0][0], wo[3], ob[0], ob[1]); mma16816(f[0][1], wo[7], ob[2], ob[3]);
      mma16816(f[1][0], w1[3], ob[0], ob[1]); mma16816(f[1][1], w1[7], ob[2], ob[3]);
      mma16816(f[2][0], vx[2], ob[0], ob[1]); mma16816(f[2][1], vx[3], ob[2], ob[3]);
      bar_arrive(7, 256);
      lds128_in(ob, sb + SC_DEAD, always);
      uint32_t h[3][2];
#pragma unroll
      for (int j = 0; j < 3; j++)
#pragma unroll
        for (int i = 0; i < 2; i++)
        {
          scale_sum(f[j][1][2 * i], f[j][0][2 * i], rs[0], always); scale_sum(f[j][1][2 * i + 1], f[j][0][2 * i + 1], rs[1], always);
          h[j][i] = pack_f16(f[j][1][2 * i], f[j][1][2 * i + 1]);
        }
      const uint32_t rofs = RANK * 32768;
      red_f16x8(slot(s, RANK >> 1, rofs), h[0][0], h[1][0], h[2][0], 0x3c00u);
      red_f16x8(slot(s, (RANK >> 1) ^ 1, rofs), h[0][1], h[1][1], h[2][1], 0x3c00u);
      bar_arrive(10, 256);
      SCHED_FENCE(5);
      l16 += ob[1];
    }
    {
    PROF(8);
    const uint32_t ma0 = l16 + SM_MEM + w * 128 + (LV >> 3) * 896 + nh * 512;
    const unsigned char* const sl[2] = {slot(s, nh, 0), slot(s, nh ^ 1, 0)};
    uint32_t dl = gtime() - 1984;
    uint32_t late = latest_hint(hints, dl, s);
    if (late >= 64) {
      int n = 0;
#pragma unroll 1
      do {
        hints = load_hints(hint_addr(s));
        dl = gtime() - 1984;
        late = latest_hint(hints, dl, s);
      } while (late >= 64 && ++n < SPIN_LIMIT);
    }
    dl += late * 32 + tm.poll;
    PROF(9);
    {
      auto wait_until = [&](uint32_t t) {
        asm volatile("{\n.reg .pred p;\n.reg .s32 c;\n.reg .u64 t;\nTL: mov.u64 t, %%globaltimer;\ncvt.u32.u64 c, t;\nsub.s32 c, c, %0;\nsetp.lt.s32 p, c, 0;\n@p bra.uni TL;\n}" :: "r"(t + (l16 & 15)) : "memory");
      };
      uint4 v[2][3];
      auto load = [&](int c) {
#pragma unroll
        for (int r = 0; r < 3; r++) v[c][r] = ldg_relaxed(sl[c ^ (r >> 1)] + r * 32768);
      };
      auto decode = [&](int c, int n) {
        uint32_t q[9];
        __half2 hm;
        const uint32_t ma = ma0 ^ (c * 512);
#pragma unroll
        for (int i = 0; i < 9; i++) {
          const uint32_t h = i % 3 == 0 ? v[c][i / 3].x : (i % 3 == 1 ? v[c][i / 3].y : v[c][i / 3].z);
          const float2 f = __half22float2(*(const __half2*)&h);
          q[i] = pack_bf16(f.x, f.y);
          hm = i ? __hmax2(hm, __habs2(*(const __half2*)&h)) : __habs2(*(const __half2*)&h);
        }
#pragma unroll
        for (int r = 0; r < 3; r++) stsm4(ma + r * 4096, q[3 * r], q[3 * r + 1], q[3 * r + 2], r < 2 ? v[c][r].w : *(const uint32_t*)&hm);
        const bool done = __all_sync(0xffffffffu, v[c][0].w == 0x5000u && v[c][1].w == 0x5000u && v[c][2].w == 0x5000u) || n > SPIN_LIMIT;
        asm volatile("{\n.reg .pred p;\nsetp.ne.u32 p, %0, 0;\n@p bar.arrive %1, 256;\n}" :: "r"((int)done), "r"(1 + c) : "memory");
        return done;
      };
      int n = 0;
      wait_until(dl);
      PROF(10);
#pragma unroll 1
      do {
        load(0);
        load(1);
        asm volatile("{\n.reg .pred p;\nsetp.eq.u32 p, %0, 0;\n@p bar.sync 13, 384;\n}" :: "r"(n) : "memory");
      } while (!decode(0, n++));
      PROF(11);
#pragma unroll 1
      while (!decode(1, n++)) load(1);
      bar_arrive(9, 256);
      PROF(12);
    }
    PROF(13);
    if (++s == NSEG - 1) break;
    }
  }
#undef fence_reg
  if (RANK < 2) bar_arrive(4, 256);
  bar_sync(0, 384);
  cluster_sync();
}

__global__ void __cluster_dims__(3, 1, 1) __launch_bounds__(384, 1)
rec_kernel(const __grid_constant__ RMaps tm, const bf16* __restrict__ x, const bf16* __restrict__ mem0) {
  extern __shared__ __align__(1024) unsigned char smem_raw[];
  const uint32_t sb = smem_u32(smem_raw);
  const int tid = threadIdx.x, lane = tid & 31;
  const int wg = __shfl_sync(0xffffffffu, tid >> 7, 0);
  const int w = __shfl_sync(0xffffffffu, (tid >> 5) & 3, 0);
  uint32_t rank; asm("mov.u32 %0, %%cluster_ctarank;" : "=r"(rank));
  STAMP(0);
  asm volatile("griddepcontrol.launch_dependents;" ::: "memory");
    if (tid == 0) {
      const int h = blockIdx.x / 3;
      mbar_init(sb + MB_XS, 1);
      for (int i = 0; i < 3; i++) { mbar_init(sb + MB_W + 8 * i, 1); mbar_init(sb + MB_X + 8 * i, 1); }
      mbar_init(sb + MB_WO3, 1);
      fence_async();
      load_w(sb, tm, rank, 0);
      mbar_expect(sb + MB_X, XT);
      tma_load3(sb + SM_X, &tm.x, 0, sb + MB_X);
      mbar_expect(sb + MB_WO3, 32768 + 8 * DM * 2);
      tma_load(sb + SM_WOST, &tm.wo, rank * 192 + 64, h * DH, sb + MB_WO3);
      tma_load(sb + SM_WO3, &tm.wo, rank * 192 + 128, h * DH, sb + MB_WO3);
      bulk_load(sb + SM_M0, mem0, 8 * DM * 2, sb + MB_WO3);
      load_w(sb, tm, rank, 1);
      load_w(sb, tm, rank, 2);
      mbar_init(sb + MB_WO, 1);
      mbar_init(sb + MB_S, rank < 2 ? 5 : 6);
      mbar_init(sb + MB_F, 1);
      mbar_init(sb + MB_VX, 1); mbar_init(sb + MB_VX + 8, 1);
      asm volatile("fence.mbarrier_init.release.cluster;" ::: "memory");
      fence_async();
      mbar_expect(sb + MB_X + 8, XT); mbar_expect(sb + MB_X + 16, XT);
      mbar_expect(sb + MB_WO, 16384); mbar_expect(sb + MB_XS, XT);
      mbar_expect(sb + MB_S, rank < 2 ? 640 + 2048 : 1280);
      mbar_expect(sb + MB_VX, 8192); mbar_expect(sb + MB_VX + 8, 8192);
    }
  __syncwarp();
  if (wg < 2) {
    asm volatile("setmaxnreg.inc.sync.aligned.u32 192;");
    __syncwarp();
    QSTAMP(0);
    if (tid < 32) bar_arrive(0, 160);
    QSTAMP(1);
    proj_role(sb, tm, x, rank, wg, w, lane);
  } else {
    asm volatile("setmaxnreg.dec.sync.aligned.u32 120;");
    attn_role(sb, smem_raw, tm, rank, x, mem0, w, lane);
  }
}

constexpr int NAUX = 36;
constexpr int A_ST = 6, A_STAGE = 8192 + 12288, A_W8 = A_ST * A_STAGE, A_EXC = A_W8 + A_ST * 1536, A_ROWS = 57;
constexpr int A_IN = A_EXC + 8 * 2304, A_INB = 3 * SEGB, A_OST = A_IN + 2 * A_INB, A_P = A_OST + 8192, A_G = A_P + 3072;
constexpr int A_BAR = A_G + 1024;
constexpr int A_XT = A_BAR + 1024, A_XW = A_XT;
constexpr int A_TOTAL = A_XT + 4096;
static_assert(A_IN % 1024 == 0 && A_XT % 1024 == 0 && A_IN >= 4 * XT && A_IN + 64 * DM * 2 <= A_BAR && A_TOTAL <= 232448, "side kernel shared memory");
struct AMaps { CUtensorMap x, wa, wa8, o, o3, o16, wob, woa, woa16; const unsigned char* red; uint32_t poll; };

DI void wgmma_n192_ss_nt(float* d, uint64_t da, uint64_t db, int acc) {
  asm volatile("{\n.reg .pred p;\nsetp.ne.b32 p, %98, 0;\n"
               "wgmma.mma_async.sync.aligned.m64n192k16.f32.bf16.bf16 {"
               "%0,%1,%2,%3,%4,%5,%6,%7,%8,%9,%10,%11,%12,%13,%14,%15,%16,%17,%18,%19,%20,%21,%22,%23,%24,%25,%26,%27,%28,%29,%30,%31,"
               "%32,%33,%34,%35,%36,%37,%38,%39,%40,%41,%42,%43,%44,%45,%46,%47,%48,%49,%50,%51,%52,%53,%54,%55,%56,%57,%58,%59,%60,%61,%62,%63,"
               "%64,%65,%66,%67,%68,%69,%70,%71,%72,%73,%74,%75,%76,%77,%78,%79,%80,%81,%82,%83,%84,%85,%86,%87,%88,%89,%90,%91,%92,%93,%94,%95"
               "}, %96, %97, p, 1, 1, 0, 1;\n}\n"
               : ACC8(d, 0), ACC8(d, 8), ACC8(d, 16), ACC8(d, 24), ACC8(d, 32), ACC8(d, 40), ACC8(d, 48), ACC8(d, 56),
                 ACC8(d, 64), ACC8(d, 72), ACC8(d, 80), ACC8(d, 88) : "l"(da), "l"(db), "r"(acc));
}
DI void wgmma_n24_ss_nt(float* d, uint64_t da, uint64_t db, int acc) {
  asm volatile("{\n.reg .pred p;\nsetp.ne.b32 p, %14, 0;\n"
               "wgmma.mma_async.sync.aligned.m64n24k16.f32.bf16.bf16 {%0,%1,%2,%3,%4,%5,%6,%7,%8,%9,%10,%11}, %12, %13, p, 1, 1, 0, 1;\n}\n"
               : ACC8(d, 0), "+f"(d[8]), "+f"(d[9]), "+f"(d[10]), "+f"(d[11]) : "l"(da), "l"(db), "r"(acc));
}
DI void tma_load3d(uint32_t dst, const CUtensorMap* m, int c0, int c1, int c2, uint32_t mb) {
  asm volatile("cp.async.bulk.tensor.3d.shared::cluster.global.mbarrier::complete_tx::bytes [%0], [%1, {%3, %4, %5}], [%2];"
               :: "r"(dst), "l"(m), "r"(mb), "r"(c0), "r"(c1), "r"(c2) : "memory");
}
DI uint32_t trans8(uint32_t x) { uint32_t r; asm("movmatrix.sync.aligned.m8n8.trans.b16 %0, %1;" : "=r"(r) : "r"(x)); return r; }
DI void wgmma_n40_ss(float* d, uint64_t da, uint64_t db, int acc) {
  asm volatile("{\n.reg .pred p;\nsetp.ne.b32 p, %22, 0;\n"
               "wgmma.mma_async.sync.aligned.m64n40k16.f32.bf16.bf16 {%0,%1,%2,%3,%4,%5,%6,%7,%8,%9,%10,%11,%12,%13,%14,%15,%16,%17,%18,%19}, "
               "%20, %21, p, 1, 1, 1, 1;\n}\n"
               : ACC8(d, 0), ACC8(d, 8), "+f"(d[16]), "+f"(d[17]), "+f"(d[18]), "+f"(d[19]) : "l"(da), "l"(db), "r"(acc));
}
template <int ST> DI void ldg8x64(uint32_t* m, const void* p) {
  asm volatile("ld.relaxed.gpu.global.v2.b32 {%0,%1}, [%16];\nld.relaxed.gpu.global.v2.b32 {%2,%3}, [%16 + %17];\n"
               "ld.relaxed.gpu.global.v2.b32 {%4,%5}, [%16 + %18];\nld.relaxed.gpu.global.v2.b32 {%6,%7}, [%16 + %19];\n"
               "ld.relaxed.gpu.global.v2.b32 {%8,%9}, [%16 + %20];\nld.relaxed.gpu.global.v2.b32 {%10,%11}, [%16 + %21];\n"
               "ld.relaxed.gpu.global.v2.b32 {%12,%13}, [%16 + %22];\nld.relaxed.gpu.global.v2.b32 {%14,%15}, [%16 + %23];"
               : "=r"(m[0]), "=r"(m[1]), "=r"(m[2]), "=r"(m[3]), "=r"(m[4]), "=r"(m[5]), "=r"(m[6]), "=r"(m[7]),
                 "=r"(m[8]), "=r"(m[9]), "=r"(m[10]), "=r"(m[11]), "=r"(m[12]), "=r"(m[13]), "=r"(m[14]), "=r"(m[15])
               : "l"(p), "n"(ST), "n"(2 * ST), "n"(3 * ST), "n"(4 * ST), "n"(5 * ST), "n"(6 * ST), "n"(7 * ST) : "memory");
}
template <int ST> DI void ldg4x128(uint32_t* m, const void* p) {
  asm volatile("ld.relaxed.gpu.global.v4.b32 {%0,%1,%2,%3}, [%16];\nld.relaxed.gpu.global.v4.b32 {%4,%5,%6,%7}, [%16 + %17];\n"
               "ld.relaxed.gpu.global.v4.b32 {%8,%9,%10,%11}, [%16 + %18];\nld.relaxed.gpu.global.v4.b32 {%12,%13,%14,%15}, [%16 + %19];"
               : "=r"(m[0]), "=r"(m[1]), "=r"(m[2]), "=r"(m[3]), "=r"(m[4]), "=r"(m[5]), "=r"(m[6]), "=r"(m[7]),
                 "=r"(m[8]), "=r"(m[9]), "=r"(m[10]), "=r"(m[11]), "=r"(m[12]), "=r"(m[13]), "=r"(m[14]), "=r"(m[15])
               : "l"(p), "n"(ST), "n"(2 * ST), "n"(3 * ST) : "memory");
}
template <int N, int ST> DI bool stale(const uint32_t* m, uint32_t tag) {
  uint32_t x = m[0] ^ tag;
#pragma unroll
  for (int i = 1; i < N; i++) asm("lop3.b32 %0, %0, %1, %2, 0xf6;" : "+r"(x) : "r"(m[i * ST]), "r"(tag));
  return __any_sync(0xffffffffu, x & 1);
}
DI int wait_flags(const unsigned* p, bool active, unsigned base, int seg) {
  int n = 0, m;
  while (true) {
    m = __reduce_min_sync(0xffffffffu, active ? (int)(ldg_acquire32(p) - base) : NSEG);
    if (m > seg || ++n > SPIN_LIMIT) break;
    __nanosleep((YP & 32) ? 400 : 40);
  }
  return max(m, seg + 1);
}
DI void wait_count(const unsigned* p, unsigned target) {
  int n = 0;
  unsigned v;
  while (true) {
    asm volatile("ld.acquire.gpu.global.b32 %0, [%1];" : "=r"(v) : "l"(p) : "memory");
    if ((int)(v - target) >= 0 || ++n > SPIN_LIMIT) break;
    __nanosleep(64);
  }
}
#define PACE_NEXT 1024
#define PING 60
DI bool tick_wait(uint32_t pace, int step) {
  const int n = lds32v(pace);
  if (n <= step) mbar_wait(pace + 8, n & 1);
  return n <= step;
}
DI void sleep_until(uint32_t t) {
  for (int n = 0; n < 64; n++) {
    const int r = t - gtime();
    if (r <= 0) break;
    __nanosleep(r >> 1);
  }
}
DI void aux_barrier(int i, unsigned epoch) {
  asm volatile("fence.proxy.async;" ::: "memory");
  asm volatile("red.release.gpu.global.add.u32 [%0], 1;" :: "l"(&g_abar[i * 32]) : "memory");
  wait_count(&g_abar[i * 32], NAUX * (epoch + 1));
  asm volatile("fence.proxy.async;" ::: "memory");
}

__global__ void __launch_bounds__(512, 1)
aux_kernel(const __grid_constant__ AMaps tm, const bf16* __restrict__ x, const bf16* __restrict__ gate_w, bf16* __restrict__ out) {
  extern __shared__ __align__(1024) unsigned char smem_raw[];
  const uint32_t sb = smem_u32(smem_raw);
  const uint32_t full1 = sb + A_BAR, empty1 = full1 + 8 * A_ST, fullw = empty1 + 8 * A_ST, full3 = fullw + 16, empty3 = full3 + 32,
                 fulla = empty3 + 32, emptya = fulla + 32, fullg = emptya + 16, pace = fullg + 8;
  const int tid = threadIdx.x, lane = tid & 31, cta = blockIdx.x;
  const int wg = __shfl_sync(0xffffffffu, tid >> 7, 0), w = __shfl_sync(0xffffffffu, (tid >> 5) & 3, 0);
  ASTAMP(14);
  const unsigned epoch = *(volatile unsigned*)&g_epoch2;
  if (tid == 0) {
    for (int i = 0; i < A_ST; i++) { mbar_init(full1 + 8 * i, 1); mbar_init(empty1 + 8 * i, 8); }
    mbar_init(fullw, 1); mbar_init(fullw + 8, 1); mbar_init(fullg, 1);
    for (int i = 0; i < 2; i++) { mbar_init(fulla + 16 * i, 2); mbar_init(fulla + 16 * i + 8, 1); mbar_init(emptya + 8 * i, 4); }
    sts64(pace, 0, 0); mbar_init(pace + 8, 1); sts32(pace + 16, 0); sts64(pace + 24, 65536, 0xffff0000u);
    for (int i = 0; i < 4; i++) { mbar_init(full3 + 8 * i, 1); mbar_init(empty3 + 8 * i, cta < NH ? 8 : 4); }
    fence_async();
  }
  auto load_a = [&](int st, int k, int col) {
    mbar_expect(full1 + 8 * st, A_STAGE + 1536);
    tma_load3d(sb + st * A_STAGE, &tm.x, k, (cta >> 1) * A_ROWS - 7, 0, full1 + 8 * st);
    tma_load3d(sb + st * A_STAGE + 8192, &tm.wa, col, k, 0, full1 + 8 * st);
    tma_load3d(sb + A_W8 + st * 1536, &tm.wa8, col + 64, k, 0, full1 + 8 * st);
  };
  __syncthreads();
  ASTAMP(0);
  const bool wide = cta < NH;
  auto p3_ks = [&](int g) { return wide ? cta >> 2 : 2 * (cta - NH) + g; };
  auto p3_mt = [&](int g) { return wide ? 2 * (cta & 3) + g : 8; };
  const unsigned fbase = epoch * NSEG;
  if (wg == 3) {
    asm volatile("setmaxnreg.dec.sync.aligned.u32 48;");
    if (w == 1 && cta < NH) {
#pragma unroll 1
      for (int seg = 0; seg < ((XP & 2048) ? 0 : NSEG); seg++) {
        bar_arrive(5, 160);
        if (seg > 0 && lane == 0) {
          asm volatile("cp.async.bulk.wait_group 0;" ::: "memory");
          stg_relaxed32(&g_oflag[cta * 32], fbase + seg);
        }
        if (lane < 3) stg_relaxed32(&g_cflag[(cta * 3 + lane) * 32], fbase + seg);
        __syncwarp();
        bar_sync(4, 160);
        if (QM & 16) tick_wait(pace, seg + 1);
        if (lane == 0) {
          fence_async();
          if (!(YP & 2)) {
          tma_store(&tm.o, sb + A_OST, cta * DH, seg * 32);
          tma_store(&tm.o, sb + A_OST + 4096, cta * DH + 64, seg * 32);
          }
          asm volatile("cp.async.bulk.commit_group;" ::: "memory");
          asm volatile("cp.async.bulk.wait_group.read 0;" ::: "memory");
        }
        __syncwarp();
      }
      if (lane == 0) {
        asm volatile("cp.async.bulk.wait_group 0;" ::: "memory");
        { const int seg = NSEG - 1; TSTAMP(2); }
        stg_relaxed32(&g_oflag[cta * 32], fbase + NSEG);
      }
    }
    if (w == 2 && cta < NH) {
      const uint32_t ktag = (epoch + 1) & 1, ma = sb + A_IN + 8192 + lane * 16;
      int avail = 0;
      int own = 0;
      bar_sync(10, 64);
#pragma unroll 1
      for (int seg = 0; seg < ((XP & 2048) ? 0 : NSEG); seg++) {
        if (avail <= seg) {
          int n = 0;
          while (true) {
            asm volatile("ld.acquire.gpu.global.v2.b32 {%0,%1}, [%2];" : "=r"(avail), "=r"(own) : "l"(&g_sflag[(cta * 3 + min(lane, 2)) * 4]) : "memory");
            avail = __reduce_min_sync(0xffffffffu, (int)(avail - fbase));
            if (avail > seg || ++n > SPIN_LIMIT) break;
            __nanosleep(40);
          }
        }
        if (QM & 8) tick_wait(pace, seg);
        TSTAMP(0);
        const unsigned char* km = g_km + (size_t)(seg * NH + cta) * 4096 + lane * 8;
        uint32_t m[16];
        const float g = __ldcg(&g_gate[seg * 32 + lane]);
        ldg8x64<256>(m, km);
        const uint32_t b = seg & 1, full = fulla + 16 * b, mb = ma + b * A_INB;
        mbar_wait(emptya + 8 * b, (~seg >> 1) & 1);
        if (lane < 2) mbar_expect(full + 8 * lane, (YP & 8) ? 0 : 16384 >> lane);
        __syncwarp();
        const int slot = seg < own ? seg & 7 : seg;
        if (lane < 3 && !(YP & 8)) bulk_load(sb + A_IN + b * A_INB + lane * SEGB, g_seg + ((size_t)slot * 96 + cta * 3 + lane) * 8192, 8192, full + (lane & 2) * 4);
        int n = 0;
#pragma unroll 1
        while (stale<8, 2>(m, ktag) && ++n < SPIN_LIMIT) { if (seg < NSEG - 1) __nanosleep(200); ldg8x64<256>(m, km); }
        TSTAMP(1);
#pragma unroll
        for (int i = 0; i < 4; i++) stsm4(mb + (i >> 1) * SEGB + (i & 1) * 512, m[4 * i], m[4 * i + 1], m[4 * i + 2], m[4 * i + 3]);
        sts32(sb + A_G + b * 128 + lane * 4, __float_as_uint(1.f - g));
        fence_async();
        __syncwarp();
        if (lane == 0) mbar_arrive(full);
      }
    }
    if (w == 3 && QM) {
      const unsigned char* const hp = tm.red + HINT_OFF + 65536 + (cta & 1) * 4096 + min(lane, 23) * 4;
      uint32_t d = 0;
      int s = 0, n = 0;
#pragma unroll 1
      while (s < NSEG - 1) {
        const uint32_t h = ldg_relaxed32(hp + RED_SLOT(s)), t = (gtime() - 1984) & ~31u, late = latest_hint(h, t, s);
        if (late < 64) {
          d = t + late * 32 + tm.poll;
          sleep_until(d);
          s++; n = 0;
          if (lane == 0) { mbar_arrive(pace + 8); sts64(pace, s < NSEG - 1 ? s : 2 * NSEG, d); }
          sleep_until(d + PACE_NEXT);
        } else {
          if (++n > (s ? 16 : 256) || lds32v(pace + 16)) break;
          if (!s) __nanosleep(100);
        }
      }
      if (s < NSEG - 1 && lane == 0) { mbar_arrive(pace + 8); sts64(pace, 2 * NSEG, d); }
    }
    if (w != 0) return;
    const bool lead = lane == 0;
#pragma unroll 1
    for (int it = 0, st = 0, ph = 1, k = 0, col = (cta & 1) * (DM / 2); it < ((XP & 256) ? 0 : 72); it++) {
      mbar_wait(empty1 + 8 * st, ph);
      if (elect_one()) load_a(st, k, col);
      __syncwarp();
      if (++st == A_ST) { st = 0; ph ^= 1; }
      k += 32;
      if (k == DM) { k = 0; col += 72; }
    }
    auto load_wo = [&](uint32_t dst, int g, int kb, uint32_t mb) {
      if (kb < 64) tma_load(dst, &tm.wob, p3_mt(g) * 64, kb * 64, mb);
      else tma_load(dst, &tm.woa, p3_mt(g) * 64, (kb - 64) * 64, mb);
    };
    if (lead) mbar_expect(fullw, 16 * 8192);
#pragma unroll 1
    for (int st = 0; st < A_ST; st++) {
      if (!(XP & 256)) mbar_wait(empty1 + 8 * st, 1);
      if (lane < 16 && min(((lane + 1) * 8192 - 1) / A_STAGE, A_ST - 1) == st) load_wo(sb + lane * 8192, lane >> 3, p3_ks(lane >> 3) * 9 + (lane & 7), fullw);
      __syncwarp();
    }
    __syncwarp(); bar_sync(6, 288);
    if (lead) mbar_expect(fullw + 8, 2 * 8192 + (p3_ks(0) >= 4 ? 4096 : 0));
    __syncwarp();
    if (lane < 2) {
      load_wo(sb + (16 + lane) * 8192, lane, p3_ks(lane) * 9 + 8, fullw + 8);
      if (p3_ks(0) >= 4) tma_load(sb + A_XW + lane * 2048, &tm.woa16, p3_mt(lane) * 64, 448 + p3_ks(lane) * 16, fullw + 8);
    }
    __syncwarp();
    if (lead) aux_barrier(1, epoch);
    __syncwarp(); bar_sync(6, 288);
    {
      int avail = 0, sl = 0, ph = 1;
      const int h = (9 * p3_ks(0) >> 1) + lane;
#pragma unroll 1
      for (int seg = 0; seg < ((XP & 2048) ? 0 : NSEG); seg++) {
        if (avail <= seg) avail = wait_flags(&g_oflag[min(h, NH - 1) * 32], lane < (wide ? 5 : 9), fbase, seg);
        SSTAMP(seg, 4);
        for (int g = 0; g < (wide ? 1 : 2); g++) {
          const int ks = p3_ks(g);
          mbar_wait(empty3 + 8 * sl, ph);
          if ((QM & 4) && tick_wait(pace, seg + (QM >> 4 & 1) + 1)) __nanosleep(100);
          if (YP & 4) { if (lead) mbar_arrive(full3 + 8 * sl); }
          else if (elect_one()) {
            mbar_expect(full3 + 8 * sl, XT + (ks >= 4 ? 1024 : 0));
            tma_load3d(sb + sl * XT, &tm.o3, 0, seg * 32, ks * 9, full3 + 8 * sl);
            if (ks >= 4) tma_load(sb + A_XT + sl * 1024, &tm.o16, 72 * 64 - 64 + ks * 16, seg * 32, full3 + 8 * sl);
          }
          __syncwarp();
          if (++sl == (wide ? 3 : 4)) { sl = 0; ph ^= 1; }
        }
      }
    }
    sts32(pace + 16, 1);
    __syncwarp(); bar_sync(6, 288);
    asm volatile("griddepcontrol.wait;" ::: "memory");
  } else if (wg == 2) {
    asm volatile("setmaxnreg.dec.sync.aligned.u32 64;");
    if (cta < NH) {
      if (tid == 256) { mbar_expect(fullg, 64 * DM * 2); bulk_load(sb + A_IN, x + cta * 64 * DM, 64 * DM * 2, fullg); }
      uint32_t gw[9];
#pragma unroll
      for (int j = 0; j < 9; j++) gw[j] = ((const uint32_t*)gate_w)[j * 32 + lane];
      mbar_wait(fullg, 0);
      float mine = 0.f;
#pragma unroll 4
      for (int u = 0; u < 16; u++) {
        float d0 = 0.f, d1 = 0.f;
#pragma unroll
        for (int j = 0; j < 9; j++) {
          const uint32_t a = lds32(sb + A_IN + (w * 16 + u) * (DM * 2) + j * 128 + lane * 4);
          d0 = fmaf(bf_lo(a), bf_lo(gw[j]), d0); d1 = fmaf(bf_hi(a), bf_hi(gw[j]), d1);
        }
        d0 = warp_sum(d0 + d1);
        if (lane == u) mine = d0;
      }
      if (lane < 16) g_gate[cta * 64 + w * 16 + lane] = 1.f / (1.f + __expf(-mine));
      fence_async();
    }
    bar_sync(3, 128);
    if (tid == 256) { aux_barrier(0, epoch); if (cta == 0) *(volatile unsigned*)&g_epoch2 = epoch + 1; }
    __syncwarp();
    bar_sync(3, 128);
    if (w == 0) bar_arrive(8, 288);
    if (w == 1 && cta < NH) bar_arrive(10, 64);
    if (cta < NH) {
      CDECL;
#pragma unroll 1
      for (int seg = 0; seg < ((XP & 2048) ? 0 : NSEG); seg++) {
        CSTAMP(0);
        const uint32_t in = sb + A_IN + (seg & 1) * A_INB;
        const uint64_t qd = make_desc(in, 128, 1024, 0);
        mbar_wait(fulla + 16 * (seg & 1), (seg >> 1) & 1);
        CSTAMP(3);
        SSTAMP(seg, 0);
        float d[2][16];
        {
          float a[20];
          uint32_t vm[16];
          const unsigned char* vp = g_km + (size_t)(seg * NH + cta) * 4096 + 2048 + lane * 16;
          if (w == 3) ldg4x128<512>(vm, vp);
          WG_FENCE();
#pragma unroll
          for (int k = 0; k < ((YP & 16) ? 1 : 8); k++) wgmma_n40_ss(a, qd + ((k >> 2) * SEGB + (k & 3) * 256 >> 4), qd + ((k >> 2) * SEGB + (k & 3) * 256 + 4096 >> 4), k > 0);
          const uint32_t ga = sb + A_G + (seg & 1) * 128 + (w & 1) * 64 + (lane >> 2) * 4;
          const float f0 = __uint_as_float(lds32(ga)), f1 = __uint_as_float(lds32(ga + 32));
          WG_COMMIT();
          WG_WAIT(0);
          CSTAMP(5);
          SSTAMP(seg, 1);
          if (w < 2) {
            const int lim = w * 16 + (lane >> 2) - 2 * (lane & 3);
            float m0 = -3.0e38f, m1 = -3.0e38f;
#pragma unroll
            for (int i = 0; i < 20; i++) {
              a[i] *= SM_SCALE * LOG2E;
              if (i < 16 && (i >> 2) * 8 + (i & 1) - (i & 2) * 4 > lim) a[i] = -1.0e9f * LOG2E;
              if (i & 2) m1 = fmaxf(m1, a[i]); else m0 = fmaxf(m0, a[i]);
            }
#pragma unroll
            for (int o = 1; o < 4; o <<= 1) { m0 = fmaxf(m0, __shfl_xor_sync(0xffffffffu, m0, o)); m1 = fmaxf(m1, __shfl_xor_sync(0xffffffffu, m1, o)); }
            float s0 = 0.f, s1 = 0.f;
#pragma unroll
            for (int i = 0; i < 20; i++) { a[i] = ex2(a[i] - (i & 2 ? m1 : m0)); if (i & 2) s1 += a[i]; else s0 += a[i]; }
#pragma unroll
            for (int o = 1; o < 4; o <<= 1) { s0 += __shfl_xor_sync(0xffffffffu, s0, o); s1 += __shfl_xor_sync(0xffffffffu, s1, o); }
            s0 = f0 * rcp(s0); s1 = f1 * rcp(s1);
            uint32_t p[10];
#pragma unroll
            for (int i = 0; i < 10; i++) p[i] = pack_bf16(a[2 * i] * (i & 1 ? s1 : s0), a[2 * i + 1] * (i & 1 ? s1 : s0));
            const uint32_t pa = sb + A_P + (2 * w + ((lane >> 3) & 1)) * 768 + (lane >> 4) * 128 + (lane & 7) * 16;
            stsm4t(pa, p[0], p[1], p[2], p[3]); stsm4t(pa + 256, p[4], p[5], p[6], p[7]); stsm4t(pa + 512, p[8], p[9], 0, 0);
            CSTAMP(6);
            fence_async();
            CSTAMP(7);
          } else if (w == 3) {
            int n = 0;
#pragma unroll 1
            while (stale<4, 4>(vm, (epoch + 1) & 1) && ++n < SPIN_LIMIT) ldg4x128<512>(vm, vp);
#pragma unroll
            for (int i = 0; i < 4; i++) stsm4(in + 2 * SEGB + 8192 + (lane >> 4) * 1024 + (lane & 15) * 16 + i * 256, vm[4 * i], vm[4 * i + 1], vm[4 * i + 2], vm[4 * i + 3]);
            fence_async();
            mbar_wait(fulla + 16 * (seg & 1) + 8, (seg >> 1) & 1);
          }
        }
        CSTAMP(8);

        bar_sync(5, 160);
        CSTAMP(10);
        SSTAMP(seg, 2);
        const uint64_t pd = make_desc(sb + A_P, 128, 768, 0), vd = make_desc(in + 2 * SEGB, 128, 512, 0), md = make_desc(in + 2 * SEGB + 8192, 0, 128, 0);
        WG_FENCE();
#pragma unroll
        for (int i = 0; i < 2; i++) {
          wgmma_n32_ss<0>(d[i], vd + i * 256, pd, 0);
          wgmma_n32_ss<0>(d[i], vd + i * 256 + 16, pd + 16, 1);
          wgmma_n32_ss<0>(d[i], md + i * 64, pd + 32, 1);
        }
        WG_COMMIT();
        WG_WAIT(0);
        CSTAMP(11);
        if (lane == 0) mbar_arrive(emptya + 8 * (seg & 1));
#pragma unroll
        for (int i = 0; i < 2; i++) {
          const uint32_t oa = sb + A_OST + i * 4096 + ((lane & 7) + ((lane >> 4) << 3)) * 128 + (((2 * w + ((lane >> 3) & 1)) ^ (lane & 7)) << 4);
          stsm4t(oa, pack_bf16(d[i][0], d[i][1]), pack_bf16(d[i][2], d[i][3]), pack_bf16(d[i][4], d[i][5]), pack_bf16(d[i][6], d[i][7]));
          stsm4t(oa + 2048, pack_bf16(d[i][8], d[i][9]), pack_bf16(d[i][10], d[i][11]), pack_bf16(d[i][12], d[i][13]), pack_bf16(d[i][14], d[i][15]));
        }
        CSTAMP(12);
        bar_sync(4, 160);
        SSTAMP(seg, 3);
      }
      CDUMP;
    }
  } else {
    asm volatile("setmaxnreg.inc.sync.aligned.u32 200;");
    {
      const int g = lane >> 2, t = lane & 3, r0 = (cta >> 1) * A_ROWS - 7 + w * 16;
      const uint32_t prev = (2 * t > g ? 0xffffu : 0u) | (2 * t + 1 > g ? 0xffff0000u : 0u);
      const int k0 = r0 + 2 * t - (2 * t > g ? 8 : 0), k1 = r0 + 2 * t + 1 - (2 * t + 1 > g ? 8 : 0);
      const uint32_t slot = sb + A_EXC + (wg * 4 + w) * 2304;
      float gl = 0.f, gh = 0.f;
      int st = 0, ph = 0;
#pragma unroll 1
      for (int p = 0; p < ((XP & 256) ? 0 : 4); p++) {
        float big[96], sml[12];
        if (p == 3 && tid < 18) {
          const int kb = p3_ks(tid >= 9) * 9 + tid % 9;
          tma_prefetch(kb < 64 ? &tm.wob : &tm.woa, p3_mt(tid >= 9) * 64, (kb & 63) * 64);
        }
        __syncwarp();
#pragma unroll
        for (int i = 0; i < 96; i++) big[i] = 0.f;
#pragma unroll
        for (int i = 0; i < 12; i++) sml[i] = 0.f;
#pragma unroll 1
        for (int k = 0; k < 18; k++) {
          mbar_wait(full1 + 8 * st, ph);
          const uint64_t da = make_desc(sb + st * A_STAGE + wg * 4096, 16, 512, 2);
          const uint64_t db = make_desc(sb + st * A_STAGE + 8192, 4096, 1024, 1), dc = make_desc(sb + A_W8 + st * 1536, 128, 512, 0);
          WG_FENCE();
#pragma unroll
          for (int j = 0; j < 2; j++) { wgmma_n192_ss_nt(big, da + j * 2, db + j * 128, 1); wgmma_n24_ss_nt(sml, da + j * 2, dc + j * 16, 1); }
          WG_COMMIT();
          WG_WAIT(1);
          if (k > 0 && lane == 0) mbar_arrive(empty1 + 8 * (st ? st - 1 : A_ST - 1));
          if (++st == A_ST) { st = 0; ph ^= 1; }
        }
        WG_WAIT(0);
        ASTAMP(16 + p + wg * 16);
        if (lane == 0) mbar_arrive(empty1 + 8 * (st ? st - 1 : A_ST - 1));
        uint32_t f[3][9][2];
#pragma unroll
        for (int c = 0; c < 3; c++)
#pragma unroll
          for (int j = 0; j < 9; j++)
#pragma unroll
            for (int i = 0; i < 2; i++) {
              const float* a = j < 8 ? &big[(c * 8 + j) * 4 + 2 * i] : &sml[c * 4 + 2 * i];
              f[c][j][i] = c < 2 ? pack_bf16(a[0], a[1]) : trans8(pack_bf16(a[0], a[1]));
            }
        if (p == 0) {
          bar_sync(8, 288);
          gl = __ldcg(&g_gate[min(max(r0 + g, 0), S_LEN / 2 - 1) * 2 + wg]); gh = __ldcg(&g_gate[min(max(r0 + g + 8, 0), S_LEN / 2 - 1) * 2 + wg]);
        }
        asm volatile("cp.async.bulk.wait_group.read 0;" ::: "memory");
        __syncwarp();
#pragma unroll
        for (int j = 0; j < 8; j += 2) sts128(slot + j * 256 + lane * 16, f[1][j][1], f[2][j][1], f[1][j + 1][1], f[2][j + 1][1]);
        sts64(slot + 2048 + lane * 8, f[1][8][1], f[2][8][1]);
        bar_sync(1 + wg, 128);
        ASTAMP(24 + p + wg * 16);
        uint32_t pv[9][2];
#pragma unroll
        for (int j = 0; j < 9; j++) pv[j][0] = pv[j][1] = 0;
        if (w) {
#pragma unroll
          for (int j = 0; j < 8; j += 2) lds128(slot - 2304 + j * 256 + lane * 16, pv[j]);
          lds64(slot - 256 + lane * 8, pv[8][0], pv[8][1]);
        }
        float a[4][4], m[4][2];
#pragma unroll
        for (int h = 0; h < 4; h++) {
          const int j = 2 * h;
          const uint32_t qa[4] = {t >= h ? f[0][j][0] : 0, t >= h ? f[0][j][1] : 0, f[0][j + 1][0], f[0][j + 1][1]};
          const uint32_t qb0 = t <= h ? f[0][j + 2][0] : 0, qb1 = t <= h ? f[0][j + 2][1] : 0;
          float s0[4], s1[4], s2[4];
          mma16816z(s1, qa, f[1][j][0], f[1][j + 1][0]); mma16816z(s2, qa, f[1][j][1], f[1][j + 1][1]); mma16816z(s0, qa, pv[j][0], pv[j + 1][0]);
          mma1688(s1, qb0, qb1, f[1][j + 2][0]); mma1688(s2, qb0, qb1, f[1][j + 2][1]); mma1688(s0, qb0, qb1, pv[j + 2][0]);
          a[h][0] = 2 * t > g ? s0[0] : s1[0]; a[h][1] = 2 * t + 1 > g ? s0[1] : s1[1]; a[h][2] = 2 * t > g ? s1[2] : s2[2]; a[h][3] = 2 * t + 1 > g ? s1[3] : s2[3];
        }
#pragma unroll
        for (int h = 0; h < 4; h++) {
#pragma unroll
          for (int i = 0; i < 4; i++) a[h][i] = (i & 1 ? k1 : k0) + (i & 2) * 4 >= 0 ? a[h][i] * (0.23570226039551584f * LOG2E) : -1.0e9f * LOG2E;
          m[h][0] = fmaxf(a[h][0], a[h][1]); m[h][1] = fmaxf(a[h][2], a[h][3]);
        }
#pragma unroll
        for (int x = 1; x < 4; x <<= 1)
#pragma unroll
          for (int i = 0; i < 8; i++) m[i >> 1][i & 1] = fmaxf(m[i >> 1][i & 1], __shfl_xor_sync(0xffffffffu, m[i >> 1][i & 1], x));
#pragma unroll
        for (int h = 0; h < 4; h++) {
#pragma unroll
          for (int i = 0; i < 4; i++) a[h][i] = ex2(a[h][i] - m[h][i >> 1]);
          m[h][0] = a[h][0] + a[h][1]; m[h][1] = a[h][2] + a[h][3];
        }
#pragma unroll
        for (int x = 1; x < 4; x <<= 1)
#pragma unroll
          for (int i = 0; i < 8; i++) m[i >> 1][i & 1] += __shfl_xor_sync(0xffffffffu, m[i >> 1][i & 1], x);
        uint32_t o[9][2];
#pragma unroll
        for (int h = 0; h < 4; h++) {
          const int j = 2 * h;
          const float z0 = gl * rcp(m[h][0]), z1 = gh * rcp(m[h][1]);
          const uint32_t pl = pack_bf16(a[h][0] * z0, a[h][1] * z0), pu = pack_bf16(a[h][2] * z1, a[h][3] * z1);
          const uint32_t pa[4] = {pl & prev, 0, pl & ~prev, pu & prev};
          float d[3][4];
#pragma unroll
          for (int i = 0; i < 3; i++) mma16816z(d[i], pa, pv[j + i][1], f[2][j + i][0]);
#pragma unroll
          for (int i = 0; i < 3; i++) mma1688(d[i], 0, pu & ~prev, f[2][j + i][1]);
#pragma unroll
          for (int i = 0; i < 3; i++) {
            const uint32_t d0 = pack_bf16(d[i][0], d[i][1]), d1 = pack_bf16(d[i][2], d[i][3]);
            o[j + i][0] = i == 0 && h > 0 && t < h ? o[j][0] : d0;
            o[j + i][1] = i == 0 && h > 0 && t < h ? o[j][1] : d1;
          }
        }
        ASTAMP(28 + p + wg * 16);
        bar_sync(1 + wg, 128);
        const uint32_t oa = slot + (lane & 15) * 144 + (lane >> 4) * 16;
#pragma unroll
        for (int j = 0; j < 8; j += 2) stsm4(oa + j * 16, o[j][0], o[j][1], o[j + 1][0], o[j + 1][1]);
        asm volatile("stmatrix.sync.aligned.m8n8.x2.shared.b16 [%0], {%1,%2};" :: "r"(oa + 128), "r"(o[8][0]), "r"(o[8][1]) : "memory");
        fence_async();
        __syncwarp();
        if (lane < 16 && w * 16 + lane >= 7 && r0 + lane < S_LEN / 2)
          asm volatile("cp.async.bulk.global.shared::cta.bulk_group [%0], [%1], 144;"
                       :: "l"(g_Ocat + (size_t)((r0 + lane) * 2 + wg) * KCAT + 4096 + (cta & 1) * (DM / 2) + p * 72), "r"(slot + lane * 144) : "memory");
        asm volatile("cp.async.bulk.commit_group;" ::: "memory");
        ASTAMP(20 + p + wg * 16);
      }
      if (XP & 256) bar_sync(8, 288);
      asm volatile("cp.async.bulk.wait_group 0;" ::: "memory");
    }
    ASTAMP(3);
    bar_arrive(6, 288);
    uint32_t wa[37][4];
    mbar_wait(fullw, 0);
    const uint32_t la = sb + ((lane & 7) + ((lane >> 4) << 3)) * 128 + (((2 * w + ((lane >> 3) & 1)) ^ (lane & 7)) << 4);
#pragma unroll
    for (int k = 0; k < 32; k++) ldsm4t(wa[k], la + wg * 65536 + k * 2048);
    mbar_wait(fullw + 8, 0);
#pragma unroll
    for (int k = 32; k < 36; k++) ldsm4t(wa[k], la + wg * 8192 + 65536 + k * 2048);
    ldsm4t(wa[36], la + A_XW + wg * 2048);
    fence_async();
    if (XP & 2048) bar_sync(6, 288); else bar_arrive(6, 288);
    ASTAMP(4);
    const int ks = p3_ks(wg), mt = p3_mt(wg);
    uint32_t v[16];
    auto fetch = [&](int seg) { ldg8x64<1024>(v, g_part + (((seg & 7) * 9 + mt) * 4 + (ks & 3)) * 1024 + (tid & 127)); };
    auto finish = [&](int seg) {
      const uint32_t tagv = (~seg >> 3) & 1;
      int n = 0;
#pragma unroll 1
      while (!(YP & 512) && stale<8, 2>(v, tagv) && ++n < SPIN_LIMIT) {
        if (seg < NSEG - 2) __nanosleep(100);
        fetch(seg);
      }
      float own[4] = {bf_lo(v[0]), bf_hi(v[0]), bf_lo(v[1]), bf_hi(v[1])};
#pragma unroll
      for (int j = 1; j < 8; j++) { own[0] += bf_lo(v[2 * j]); own[1] += bf_hi(v[2 * j]); own[2] += bf_lo(v[2 * j + 1]); own[3] += bf_hi(v[2 * j + 1]); }
      uint32_t p0 = pack_bf16(own[0], own[1]), p1 = pack_bf16(own[2], own[3]);
      asm volatile("movmatrix.sync.aligned.m8n8.trans.b16 %0, %0;" : "+r"(p0));
      asm volatile("movmatrix.sync.aligned.m8n8.trans.b16 %0, %0;" : "+r"(p1));
      const uint32_t r2 = __shfl_xor_sync(0xffffffffu, lane & 2 ? p0 : p1, 2);
      if (lane & 2) p0 = r2; else p1 = r2;
      const uint32_t r1 = __shfl_xor_sync(0xffffffffu, lane & 1 ? p0 : p1, 1);
      if (lane & 1) p0 = r1; else p1 = r1;
      if (!(YP & 256) || p0 == 0x12345678)
        *((uint2*)(out + (size_t)(seg * 32 + (ks & 3) * 8 + (lane >> 2)) * DM + mt * 64 + w * 16) + (lane & 3)) = make_uint2(p0, p1);
      SSTAMP(seg, 7);
    };
    float acc[16];
#pragma unroll
    for (int i = 0; i < 16; i++) acc[i] = 0.f;
    int pend = -1, sl = wide ? 0 : wg, ph = 0;
    if (PING && wg) bar_arrive(1, 256);
    CDECL;
    auto run = [&](auto extra) {
#pragma unroll 1
    for (int seg = 0; seg <= ((XP & 2048) ? -1 : NSEG); seg++) {
      CSTAMP(0);
      const bool fin = pend >= 0 && (seg - pend >= 2 || seg == NSEG);
      if (seg < NSEG) mbar_wait(full3 + 8 * sl, ph);
      if (fin) fetch(pend);
      CSTAMP(1);
      if (seg < NSEG) {
      if (wg) SSTAMP(seg, 5);
      if (seg < PING) bar_sync(1 + wg, 256);
      CSTAMP(7);
      const uint64_t db = make_desc(sb + sl * XT, 16, 1024, 1);
      WG_FENCE();
#pragma unroll
      for (int k = 0; k < ((XP & 1024) ? 1 : 36); k++) wgmma_n32_rs(acc, wa[k][0], wa[k][1], wa[k][2], wa[k][3], db + (k >> 2) * 256 + (k & 3) * 2, k);
      if (decltype(extra)::value) wgmma_n32_rs(acc, wa[36][0], wa[36][1], wa[36][2], wa[36][3], make_desc(sb + A_XT + sl * 1024, 16, 256, 3), 1);
      WG_COMMIT();
      if (seg < PING) bar_arrive(2 - wg, 256);
      CSTAMP(2);
      CSTAMP(3);
      WG_WAIT(0);
      CSTAMP(4);
      if (wg) SSTAMP(seg, 6);
      if (lane == 0) mbar_arrive(empty3 + 8 * sl);
      sl += wide ? 1 : 2;
      if (sl >= (wide ? 3 : 4)) { sl -= wide ? 3 : 4; ph ^= 1; }
      uint2* dst = g_part + (((seg & 7) * 9 + mt) * 32 + ks) * 128 + (tid & 127);
      uint32_t q[8];
#pragma unroll
      for (int j = 0; j < 8; j++) q[j] = j & 1 ? pack_bf16(acc[2 * j], acc[2 * j + 1]) : (pack_bf16(acc[2 * j], acc[2 * j + 1]) & ~1u) | ((~seg >> 3) & 1);
      if (QM & 32) tick_wait(pace, seg + (QM >> 4 & 1) + 2);
      if (!(YP & 1025) || q[0] == 0x12345678)
      asm volatile("st.relaxed.gpu.global.v2.b32 [%0], {%1,%2};\nst.relaxed.gpu.global.v2.b32 [%0 + 8192], {%3,%4};\n"
                   "st.relaxed.gpu.global.v2.b32 [%0 + 16384], {%5,%6};\nst.relaxed.gpu.global.v2.b32 [%0 + 24576], {%7,%8};"
                   :: "l"(dst), "r"(q[0]), "r"(q[1]), "r"(q[2]), "r"(q[3]), "r"(q[4]), "r"(q[5]), "r"(q[6]), "r"(q[7]) : "memory");
      }
      CSTAMP(5);
      if (fin) { finish(pend); pend = -1; }
      CSTAMP(6);
      if ((seg & 1) == ks >> 2 && !(YP & 1)) pend = seg;
      if (wg && (seg & 7) == 6) ASTAMP(5 + (seg >> 3));
    }
    };
    if (ks >= 4) run(BoolC<true>()); else run(BoolC<false>());
    if (PING && !wg) bar_sync(1, 256);
    CDUMP;
    ASTAMP(13);
    bar_sync(6, 288);
  }
}

typedef CUresult (*EncodeFn)(CUtensorMap*, CUtensorMapDataType, cuuint32_t, void*, const cuuint64_t*, const cuuint64_t*,
                             const cuuint32_t*, const cuuint32_t*, CUtensorMapInterleave, CUtensorMapSwizzle,
                             CUtensorMapL2promotion, CUtensorMapFloatOOBfill);
static void make_map(EncodeFn enc, CUtensorMap* m, const void* p, int rows, int cols, int box_rows) {
  cuuint64_t dims[2] = {(cuuint64_t)cols, (cuuint64_t)rows};
  cuuint64_t strides[1] = {(cuuint64_t)cols * 2};
  cuuint32_t box[2] = {64, (cuuint32_t)box_rows};
  cuuint32_t es[2] = {1, 1};
  enc(m, CU_TENSOR_MAP_DATA_TYPE_BFLOAT16, 2, (void*)p, dims, strides, box, es, CU_TENSOR_MAP_INTERLEAVE_NONE,
      CU_TENSOR_MAP_SWIZZLE_128B, CU_TENSOR_MAP_L2_PROMOTION_L2_128B, CU_TENSOR_MAP_FLOAT_OOB_FILL_NONE);
}

constexpr int g_poll = POLL_NS;
extern "C" void kernel_launch(void* const* d_in, const int* in_sizes, int n_in, void* d_out, int out_size) {
  const bf16* x = (const bf16*)d_in[0];
  const bf16* wqkvA = (const bf16*)d_in[1];
  const bf16* woA = (const bf16*)d_in[2];
  const bf16* mem0 = (const bf16*)d_in[4];
  const bf16* Wq = (const bf16*)d_in[5];
  const bf16* Wk = (const bf16*)d_in[6];
  const bf16* Wv = (const bf16*)d_in[7];
  const bf16* Wo = (const bf16*)d_in[8];
  const bf16* gate_w = (const bf16*)d_in[10];
  static EncodeFn enc = nullptr;
  static void *pO = nullptr, *pR = nullptr, *pF = nullptr;
  if (!enc) {
    cudaDriverEntryPointQueryResult qr;
    cudaGetDriverEntryPoint("cuTensorMapEncodeTiled", (void**)&enc, cudaEnableDefault, &qr);
    cudaGetSymbolAddress(&pO, g_Ocat);
    cudaGetSymbolAddress(&pR, g_red_raw);
    cudaGetSymbolAddress(&pF, g_cflag);
    cudaFuncSetAttribute(rec_kernel, cudaFuncAttributeMaxDynamicSharedMemorySize, SM_TOTAL);
    cudaFuncSetAttribute(aux_kernel, cudaFuncAttributeMaxDynamicSharedMemorySize, A_TOTAL);
  }
  RMaps rm;
  rm.poll = g_poll;
  rm.oflag = (const unsigned char*)pF;
  rm.red = (unsigned char*)(((uintptr_t)pR + 262143) & ~(uintptr_t)262143);
  {
    cuuint64_t dims[3] = {64, S_LEN, 9}, strides[2] = {DM * 2, 128};
    cuuint32_t box[3] = {64, 32, 9}, es[3] = {1, 1, 1};
    enc(&rm.x, CU_TENSOR_MAP_DATA_TYPE_BFLOAT16, 3, (void*)x, dims, strides, box, es, CU_TENSOR_MAP_INTERLEAVE_NONE,
        CU_TENSOR_MAP_SWIZZLE_128B, CU_TENSOR_MAP_L2_PROMOTION_L2_128B, CU_TENSOR_MAP_FLOAT_OOB_FILL_NONE);
  }
  make_map(enc, &rm.wq, Wq, DM, 4096, 192);
  make_map(enc, &rm.wk, Wk, DM, 4096, 192);
  make_map(enc, &rm.wv, Wv, DM, 4096, 192);
  make_map(enc, &rm.wo, Wo, 4096, DM, 128);
  AMaps am;
  am.red = rm.red; am.poll = rm.poll;
  {
    cuuint64_t dims[3] = {DM, S_LEN / 2, 2}, strides[2] = {DM * 4, DM * 2};
    cuuint32_t box[3] = {32, 64, 2}, es[3] = {1, 1, 1};
    enc(&am.x, CU_TENSOR_MAP_DATA_TYPE_BFLOAT16, 3, (void*)x, dims, strides, box, es, CU_TENSOR_MAP_INTERLEAVE_NONE,
        CU_TENSOR_MAP_SWIZZLE_64B, CU_TENSOR_MAP_L2_PROMOTION_L2_128B, CU_TENSOR_MAP_FLOAT_OOB_FILL_NONE);
    cuuint64_t wdims[3] = {DM, DM, 3}, wstrides[2] = {DM * 6, DM * 2};
    cuuint32_t wbox[3] = {64, 32, 3}, wbox8[3] = {8, 32, 3};
    enc(&am.wa, CU_TENSOR_MAP_DATA_TYPE_BFLOAT16, 3, (void*)wqkvA, wdims, wstrides, wbox, es, CU_TENSOR_MAP_INTERLEAVE_NONE,
        CU_TENSOR_MAP_SWIZZLE_128B, CU_TENSOR_MAP_L2_PROMOTION_L2_128B, CU_TENSOR_MAP_FLOAT_OOB_FILL_NONE);
    enc(&am.wa8, CU_TENSOR_MAP_DATA_TYPE_BFLOAT16, 3, (void*)wqkvA, wdims, wstrides, wbox8, es, CU_TENSOR_MAP_INTERLEAVE_NONE,
        CU_TENSOR_MAP_SWIZZLE_NONE, CU_TENSOR_MAP_L2_PROMOTION_NONE, CU_TENSOR_MAP_FLOAT_OOB_FILL_NONE);
  }
  {
    cuuint64_t dims[3] = {64, S_LEN, KCAT / 64}, strides[2] = {KCAT * 2, 128};
    cuuint32_t box[3] = {64, 32, 9}, es[3] = {1, 1, 1};
    make_map(enc, &am.o, pO, S_LEN, KCAT, 32);
    enc(&am.o3, CU_TENSOR_MAP_DATA_TYPE_BFLOAT16, 3, pO, dims, strides, box, es, CU_TENSOR_MAP_INTERLEAVE_NONE,
        CU_TENSOR_MAP_SWIZZLE_128B, CU_TENSOR_MAP_L2_PROMOTION_L2_128B, CU_TENSOR_MAP_FLOAT_OOB_FILL_NONE);
  }
  make_map(enc, &am.wob, Wo, 4096, DM, 64);
  make_map(enc, &am.woa, woA, DM, DM, 64);
  make_map(enc, &am.woa16, woA, DM, DM, 16);
  {
    cuuint64_t dims[2] = {KCAT, S_LEN}, strides[1] = {KCAT * 2};
    cuuint32_t box[2] = {16, 32}, es[2] = {1, 1};
    enc(&am.o16, CU_TENSOR_MAP_DATA_TYPE_BFLOAT16, 2, pO, dims, strides, box, es, CU_TENSOR_MAP_INTERLEAVE_NONE,
        CU_TENSOR_MAP_SWIZZLE_32B, CU_TENSOR_MAP_L2_PROMOTION_NONE, CU_TENSOR_MAP_FLOAT_OOB_FILL_NONE);
  }

  rec_kernel<<<96, 384, SM_TOTAL, cudaStreamPerThread>>>(rm, x, mem0);
  cudaLaunchConfig_t cfg = {};
  cfg.gridDim = dim3(NAUX); cfg.blockDim = dim3(512); cfg.dynamicSmemBytes = A_TOTAL; cfg.stream = cudaStreamPerThread;
  cudaLaunchAttribute at[1];
  at[0].id = cudaLaunchAttributeProgrammaticStreamSerialization; at[0].val.programmaticStreamSerializationAllowed = 1;
  cfg.attrs = at; cfg.numAttrs = 1;
  if (XP & 16) cfg.numAttrs = 0;
  if (!(XP & 64)) cudaLaunchKernelEx(&cfg, aux_kernel, am, x, gate_w, (bf16*)d_out);
}
```

```cpp
#include <cuda_runtime.h>
#include <cuda_bf16.h>
#include <cuda_fp16.h>
#include <cuda.h>
#include <stdint.h>

typedef __nv_bfloat16 bf16;

constexpr int S_LEN = 2048, DM = 576, NH = 32, DH = 128, NSEG = 64, KCAT = 4096 + 576;
#define RED_LINE(i) (((i) >> 2) * 4096 + ((i) & 1) * 256 + ((i) & 2) * 512)
#define RED_SLOT(s) (((s) & 1) * 128 + ((s) & 2) * 256)

#define POLL_NS 896
#define QM 60
constexpr int NUP = 4;
#define N5 224
#define KP(i) (((i) >> 1) + 4 * ((i) & 1))
#define SPIN_LIMIT (1 << 14)
#define XP 0
#define YP 0

__device__ __align__(1024) bf16 g_Ocat[S_LEN * KCAT];
__device__ __align__(1024) unsigned char g_red_raw[2 * 262144];
constexpr int HINT_OFF = 2048;
__device__ __align__(16) float g_gate[S_LEN];
__device__ __align__(128) uint4 g_stats[96 * 2];
__device__ unsigned g_epoch;
__device__ unsigned g_epoch2;
__device__ __align__(128) unsigned g_oflag[NH * 32];
__device__ unsigned g_abar[3 * 32];
__device__ __align__(128) unsigned g_cflag[96 * 32];
__device__ uint2 g_sflag[96 * 4];
__device__ __align__(1024) unsigned char g_seg[NSEG * 96 * 8192];
__device__ __align__(1024) unsigned char g_km[NSEG * NH * 4096];
__device__ __align__(1024) uint2 g_part[8 * 9 * 4 * 8 * 128];
__device__ int g_err;
#define SSTAMP(seg, idx)
#define TSTAMP(idx)
#define QSTAMP(idx)
#define PROF(idx)
#define PROFP(idx)
#define STAMP(idx)
#define ASTAMP(idx)
#define WSTAMP(idx)

#define CSTAMP(idx)
#define CDECL
#define CDUMP
#define DI __device__ __forceinline__
DI uint32_t smem_u32(const void* p) { return (uint32_t)__cvta_generic_to_shared(p); }
DI uint32_t clock32() { uint32_t c; asm volatile("mov.u32 %0, %%clock;" : "=r"(c) :: "memory"); return c; }
DI uint32_t gtime() { uint32_t c; asm volatile("mov.u32 %0, %%globaltimer_lo;" : "=r"(c) :: "memory"); return c; }
DI uint32_t ldg_relaxed32(const void* p) { uint32_t v; asm volatile("ld.relaxed.gpu.global.b32 %0, [%1];" : "=r"(v) : "l"(p) : "memory"); return v; }
DI uint32_t ldg_acquire32(const void* p) { uint32_t v; asm volatile("ld.acquire.gpu.global.b32 %0, [%1];" : "=r"(v) : "l"(p) : "memory"); return v; }
DI void stg_relaxed32(void* p, uint32_t v) { asm volatile("st.relaxed.gpu.global.b32 [%0], %1;" :: "l"(p), "r"(v) : "memory"); }
DI uint32_t mapa(uint32_t a, uint32_t r) { uint32_t o; asm("mapa.shared::cluster.u32 %0, %1, %2;" : "=r"(o) : "r"(a), "r"(r)); return o; }
DI void cluster_arrive() { asm volatile("barrier.cluster.arrive.relaxed.aligned;" ::: "memory"); }
DI void cluster_wait() { asm volatile("barrier.cluster.wait.aligned;" ::: "memory"); }
DI void cluster_sync() { asm volatile("barrier.cluster.arrive.release.aligned;\nbarrier.cluster.wait.acquire.aligned;" ::: "memory"); }
DI void mbar_init(uint32_t b, uint32_t c) { asm volatile("mbarrier.init.shared::cta.b64 [%0], %1;" :: "r"(b), "r"(c) : "memory"); }
DI void mbar_expect(uint32_t b, uint32_t tx) { asm volatile("mbarrier.arrive.expect_tx.shared::cta.b64 _, [%0], %1;" :: "r"(b), "r"(tx) : "memory"); }
DI void mbar_arrive(uint32_t b) { asm volatile("mbarrier.arrive.shared::cta.b64 _, [%0];" :: "r"(b) : "memory"); }
DI void mbar_wait(uint32_t b, uint32_t par) {
  asm volatile("{\n.reg .pred p;\n.reg .u32 n, q;\nmov.u32 n, 0;\n"
               "WL: add.u32 n, n, 1;\nshr.u32 q, n, 12;\nxor.b32 q, q, %1;\n"
               "mbarrier.try_wait.parity.shared::cta.b64 p, [%0], q;\n@!p bra.uni WL;\n}"
               :: "r"(b), "r"(par) : "memory");
}
DI void wait_until(uint32_t t) {
  const uint32_t now = gtime();
  t = min(t, now + 8192);
  asm volatile("{\n.reg .pred p;\n.reg .u32 c;\nTL: mov.u32 c, %%globaltimer_lo;\nsetp.lt.u32 p, c, %0;\n@p bra.uni TL;\n}" :: "r"(t) : "memory");
}
#define PIN(v) v = __shfl_xor_sync(0xffffffffu, v, 0)
#define SCHED_FENCE(k) asm volatile("{\n.reg .pred p;\nsetp.eq.u32 p, %0, %1;\n@p exit;\n}" :: "r"(fence_reg), "r"(k) : "memory")
DI void bar_sync(int id, int n) { asm volatile("bar.sync %0, %1;" :: "r"(id), "r"(n) : "memory"); }
DI void bar_arrive(int id, int n) { asm volatile("bar.arrive %0, %1;" :: "r"(id), "r"(n) : "memory"); }
DI void fence_async() { asm volatile("fence.proxy.async.shared::cta;" ::: "memory"); }
DI void st_async4(uint32_t a, uint32_t x, uint32_t y, uint32_t z, uint32_t w, uint32_t mb) {
  asm volatile("st.async.weak.shared::cluster.mbarrier::complete_tx::bytes.v4.b32 [%0], {%1,%2,%3,%4}, [%5];"
               :: "r"(a), "r"(x), "r"(y), "r"(z), "r"(w), "r"(mb) : "memory");
}
DI void sts32(uint32_t a, uint32_t x) { asm volatile("st.shared.b32 [%0], %1;" :: "r"(a), "r"(x) : "memory"); }
DI void sts64(uint32_t a, uint32_t x, uint32_t y) { asm volatile("st.shared.v2.b32 [%0], {%1,%2};" :: "r"(a), "r"(x), "r"(y) : "memory"); }
DI void sts128(uint32_t a, uint32_t x, uint32_t y, uint32_t z, uint32_t w) {
  asm volatile("st.shared.v4.b32 [%0], {%1,%2,%3,%4};" :: "r"(a), "r"(x), "r"(y), "r"(z), "r"(w) : "memory");
}
DI uint32_t lds32(uint32_t a) { uint32_t x; asm volatile("ld.shared.b32 %0, [%1];" : "=r"(x) : "r"(a) : "memory"); return x; }
DI uint32_t lds32v(uint32_t a) { uint32_t x; asm volatile("ld.volatile.shared.b32 %0, [%1];" : "=r"(x) : "r"(a) : "memory"); return x; }
DI void lds64(uint32_t a, uint32_t& x, uint32_t& y) { asm volatile("ld.shared.v2.b32 {%0,%1}, [%2];" : "=r"(x), "=r"(y) : "r"(a) : "memory"); }
DI void lds128(uint32_t a, uint32_t* r) {
  asm volatile("ld.shared.v4.b32 {%0,%1,%2,%3}, [%4];" : "=r"(r[0]), "=r"(r[1]), "=r"(r[2]), "=r"(r[3]) : "r"(a) : "memory");
}
DI void lds128f(uint32_t a, float* r) {
  asm volatile("ld.shared.v4.f32 {%0,%1,%2,%3}, [%4];" : "=f"(r[0]), "=f"(r[1]), "=f"(r[2]), "=f"(r[3]) : "r"(a) : "memory");
}
DI void ldsm4t(uint32_t* r, uint32_t a) {
  asm volatile("ldmatrix.sync.aligned.m8n8.x4.trans.shared.b16 {%0,%1,%2,%3}, [%4];"
               : "=r"(r[0]), "=r"(r[1]), "=r"(r[2]), "=r"(r[3]) : "r"(a) : "memory");
}
DI void ldsm4t_in(uint32_t* r, uint32_t a, uint32_t t) {
  asm volatile("{\n.reg .pred p;\nsetp.ne.u32 p, %5, 0;\n@p ldmatrix.sync.aligned.m8n8.x4.trans.shared.b16 {%0,%1,%2,%3}, [%4];\n}"
               : "+r"(r[0]), "+r"(r[1]), "+r"(r[2]), "+r"(r[3]) : "r"(a), "r"(t) : "memory");
}
DI void lds128_in(uint32_t* r, uint32_t a, uint32_t t) {
  asm volatile("{\n.reg .pred p;\nsetp.ne.u32 p, %5, 0;\n@p ld.shared.v4.b32 {%0,%1,%2,%3}, [%4];\n}"
               : "+r"(r[0]), "+r"(r[1]), "+r"(r[2]), "+r"(r[3]) : "r"(a), "r"(t) : "memory");
}
DI void ldsm2t_in(uint32_t* r, uint32_t a, uint32_t t) {
  asm volatile("{\n.reg .pred p;\nsetp.ne.u32 p, %3, 0;\n@p ldmatrix.sync.aligned.m8n8.x2.trans.shared.b16 {%0,%1}, [%2];\n}" : "+r"(r[0]), "+r"(r[1]) : "r"(a), "r"(t) : "memory");
}
DI void reserve2(uint32_t* r) { asm volatile("{\n.reg .u64 t;\nmov.u64 t, %%clock64;\nmov.b64 {%0, %1}, t;\n}" : "=r"(r[0]), "=r"(r[1])); }
DI void scale_sum(float& x, float& y, float s, uint32_t t) {
  asm volatile("{\n.reg .pred p;\nsetp.ne.u32 p, %2, 0;\n@p mul.f32 %0, %0, %1;\n}" : "+f"(y) : "f"(s), "r"(t));
  asm volatile("{\n.reg .pred p;\nsetp.ne.u32 p, %3, 1;\n@p fma.rn.f32 %0, %0, %1, %2;\n}" : "+f"(x) : "f"(s), "f"(y), "r"(t));
}
DI void ldsm4(uint32_t* r, uint32_t a) {
  asm volatile("ldmatrix.sync.aligned.m8n8.x4.shared.b16 {%0,%1,%2,%3}, [%4];"
               : "=r"(r[0]), "=r"(r[1]), "=r"(r[2]), "=r"(r[3]) : "r"(a) : "memory");
}
DI void st_async1(uint32_t a, uint32_t x, uint32_t mb) {
  asm volatile("st.async.weak.shared::cluster.mbarrier::complete_tx::bytes.b32 [%0], %1, [%2];" :: "r"(a), "r"(x), "r"(mb) : "memory");
}
DI void stsm4(uint32_t a, uint32_t x, uint32_t y, uint32_t z, uint32_t w) {
  asm volatile("stmatrix.sync.aligned.m8n8.x4.shared.b16 [%0], {%1,%2,%3,%4};" :: "r"(a), "r"(x), "r"(y), "r"(z), "r"(w) : "memory");
}
DI void stsm4t(uint32_t a, uint32_t x, uint32_t y, uint32_t z, uint32_t w) {
  asm volatile("stmatrix.sync.aligned.m8n8.x4.trans.shared.b16 [%0], {%1,%2,%3,%4};" :: "r"(a), "r"(x), "r"(y), "r"(z), "r"(w) : "memory");
}
DI uint32_t pack_bf16(float lo, float hi) { uint32_t r; asm("cvt.rn.bf16x2.f32 %0, %1, %2;" : "=r"(r) : "f"(hi), "f"(lo)); return r; }
DI uint32_t pack_f16(float lo, float hi) { uint32_t r; asm("cvt.rn.f16x2.f32 %0, %1, %2;" : "=r"(r) : "f"(hi), "f"(lo)); return r; }
DI float ex2(float x) { float y; asm("ex2.approx.ftz.f32 %0, %1;" : "=f"(y) : "f"(x)); return y; }
DI float rcp(float x) { float y; asm("rcp.approx.ftz.f32 %0, %1;" : "=f"(y) : "f"(x)); return y; }
DI float bf_lo(uint32_t x) { return __uint_as_float(x << 16); }
DI float bf_hi(uint32_t x) { return __uint_as_float(x & 0xffff0000u); }
DI void mma16816(float* d, const uint32_t* a, uint32_t b0, uint32_t b1) {
  asm volatile("mma.sync.aligned.m16n8k16.row.col.f32.bf16.bf16.f32 {%0,%1,%2,%3}, {%4,%5,%6,%7}, {%8,%9}, {%0,%1,%2,%3};"
               : "+f"(d[0]), "+f"(d[1]), "+f"(d[2]), "+f"(d[3]) : "r"(a[0]), "r"(a[1]), "r"(a[2]), "r"(a[3]), "r"(b0), "r"(b1));
}
DI void mma16816z(float* d, const uint32_t* a, uint32_t b0, uint32_t b1) {
  asm volatile("mma.sync.aligned.m16n8k16.row.col.f32.bf16.bf16.f32 {%0,%1,%2,%3}, {%4,%5,%6,%7}, {%8,%9}, {%10,%10,%10,%10};"
               : "=f"(d[0]), "=f"(d[1]), "=f"(d[2]), "=f"(d[3]) : "r"(a[0]), "r"(a[1]), "r"(a[2]), "r"(a[3]), "r"(b0), "r"(b1), "f"(0.f));
}
DI void mma1688(float* d, uint32_t a0, uint32_t a1, uint32_t b0) {
  asm volatile("mma.sync.aligned.m16n8k8.row.col.f32.bf16.bf16.f32 {%0,%1,%2,%3}, {%4,%5}, {%6}, {%0,%1,%2,%3};"
               : "+f"(d[0]), "+f"(d[1]), "+f"(d[2]), "+f"(d[3]) : "r"(a0), "r"(a1), "r"(b0));
}
DI uint32_t add_bf16(uint32_t a, uint32_t b) { uint32_t r; asm("add.rn.bf16x2 %0, %1, %2;" : "=r"(r) : "r"(a), "r"(b)); return r; }
DI uint32_t mul_bf16(uint32_t a, uint32_t b) { uint32_t r; asm("mul.rn.bf16x2 %0, %1, %2;" : "=r"(r) : "r"(a), "r"(b)); return r; }
DI uint64_t make_desc(uint32_t addr, uint32_t lbo, uint32_t sbo, uint32_t swz) {
  return (uint64_t)((addr & 0x3FFFF) >> 4) | ((uint64_t)(lbo >> 4) << 16) | ((uint64_t)(sbo >> 4) << 32) | ((uint64_t)swz << 62);
}
#define WG_FENCE() asm volatile("wgmma.fence.sync.aligned;" ::: "memory")
#define WG_COMMIT() asm volatile("wgmma.commit_group.sync.aligned;" ::: "memory")
#define WG_WAIT(n) asm volatile("wgmma.wait_group.sync.aligned %0;" :: "n"(n) : "memory")
#define ACC8(d, o) "+f"(d[o]), "+f"(d[o + 1]), "+f"(d[o + 2]), "+f"(d[o + 3]), "+f"(d[o + 4]), "+f"(d[o + 5]), "+f"(d[o + 6]), "+f"(d[o + 7])
DI void wgmma_n32_rs(float* d, uint32_t a0, uint32_t a1, uint32_t a2, uint32_t a3, uint64_t db, int acc) {
  asm volatile("{\n.reg .pred p;\nsetp.ne.b32 p, %21, 0;\n"
               "wgmma.mma_async.sync.aligned.m64n32k16.f32.bf16.bf16 {%0,%1,%2,%3,%4,%5,%6,%7,%8,%9,%10,%11,%12,%13,%14,%15}, "
               "{%16,%17,%18,%19}, %20, p, 1, 1, 0;\n}\n"
               : ACC8(d, 0), ACC8(d, 8) : "r"(a0), "r"(a1), "r"(a2), "r"(a3), "l"(db), "r"(acc));
}
template <int TA>
DI void wgmma_n32_ss(float* d, uint64_t da, uint64_t db, int acc) {
  asm volatile("{\n.reg .pred p;\nsetp.ne.b32 p, %18, 0;\n"
               "wgmma.mma_async.sync.aligned.m64n32k16.f32.bf16.bf16 {%0,%1,%2,%3,%4,%5,%6,%7,%8,%9,%10,%11,%12,%13,%14,%15}, "
               "%16, %17, p, 1, 1, %19, 1;\n}\n"
               : ACC8(d, 0), ACC8(d, 8) : "l"(da), "l"(db), "r"(acc), "n"(TA));
}
DI void tma_load(uint32_t dst, const CUtensorMap* m, int c0, int c1, uint32_t mb) {
  asm volatile("cp.async.bulk.tensor.2d.shared::cluster.global.mbarrier::complete_tx::bytes [%0], [%1, {%3, %4}], [%2];"
               :: "r"(dst), "l"(m), "r"(mb), "r"(c0), "r"(c1) : "memory");
}
DI void tma_load3(uint32_t dst, const CUtensorMap* m, int row, uint32_t mb) {
  asm volatile("cp.async.bulk.tensor.3d.shared::cluster.global.mbarrier::complete_tx::bytes [%0], [%1, {%3, %4, %3}], [%2];"
               :: "r"(dst), "l"(m), "r"(mb), "r"(0), "r"(row) : "memory");
}
DI bool elect_one() {
  uint32_t p;
  asm volatile("{\n.reg .pred p;\nelect.sync _|p, 0xffffffff;\nselp.u32 %0, 1, 0, p;\n}" : "=r"(p));
  return p;
}
DI void bulk_s2s(uint32_t dst, uint32_t src, uint32_t bytes, uint32_t mb) {
  asm volatile("cp.async.bulk.shared::cluster.shared::cta.mbarrier::complete_tx::bytes [%0], [%1], %2, [%3];"
               :: "r"(dst), "r"(src), "r"(bytes), "r"(mb) : "memory");
}
DI void bulk_load(uint32_t dst, const void* src, uint32_t bytes, uint32_t mb) {
  asm volatile("cp.async.bulk.shared::cluster.global.mbarrier::complete_tx::bytes [%0], [%1], %2, [%3];" :: "r"(dst), "l"(src), "r"(bytes), "r"(mb) : "memory");
}
#define EVICT_FIRST ".reg .b64 pol;\ncreatepolicy.fractional.L2::evict_first.b64 pol, 1.0;\n"
DI void tma_load_ef(uint32_t dst, const CUtensorMap* m, int c0, int c1, uint32_t mb) {
  asm volatile("{\n" EVICT_FIRST "cp.async.bulk.tensor.2d.shared::cluster.global.mbarrier::complete_tx::bytes.L2::cache_hint [%0], [%1, {%3, %4}], [%2], pol;\n}"
               :: "r"(dst), "l"(m), "r"(mb), "r"(c0), "r"(c1) : "memory");
}
DI void tma_prefetch(const CUtensorMap* m, int c0, int c1) {
  asm volatile("cp.async.bulk.prefetch.tensor.2d.L2.global.tile [%0, {%1, %2}];" :: "l"(m), "r"(c0), "r"(c1) : "memory");
}
DI void tma_store(const CUtensorMap* m, uint32_t src, int c0, int c1) {
  asm volatile("cp.async.bulk.tensor.2d.global.shared::cta.bulk_group [%0, {%2, %3}], [%1];" :: "l"(m), "r"(src), "r"(c0), "r"(c1) : "memory");
}
DI uint4 ldg_relaxed(const void* p) {
  uint4 v;
  asm volatile("ld.relaxed.gpu.global.v4.b32 {%0,%1,%2,%3}, [%4];" : "=r"(v.x), "=r"(v.y), "=r"(v.z), "=r"(v.w) : "l"(p) : "memory");
  return v;
}
DI void stg_relaxed(void* p, uint32_t x, uint32_t y, uint32_t z, uint32_t w) {
  asm volatile("st.relaxed.gpu.global.v4.b32 [%0], {%1,%2,%3,%4};" :: "l"(p), "r"(x), "r"(y), "r"(z), "r"(w) : "memory");
}
DI void red_f16x8(void* p, uint32_t x, uint32_t y, uint32_t z, uint32_t w) {
  asm volatile("red.relaxed.gpu.global.add.noftz.v4.f16x2 [%0], {%1,%2,%3,%4};" :: "l"(p), "r"(x), "r"(y), "r"(z), "r"(w) : "memory");
}
DI void sq_acc(uint32_t& a, uint32_t x) { asm("fma.rn.bf16x2 %0, %1, %1, %0;" : "+r"(a) : "r"(x)); }
DI __half2 amax4(__half2 h, const uint32_t* v) {
  h = __hmax2_nan(__hmax2_nan(h, __habs2(*(const __half2*)&v[0])), __habs2(*(const __half2*)&v[1]));
  return __hmax2_nan(__hmax2_nan(h, __habs2(*(const __half2*)&v[2])), __habs2(*(const __half2*)&v[3]));
}
DI uint32_t wexp(__half2 h) { const uint32_t u = *(const uint32_t*)&h; return __reduce_max_sync(0xffffffffu, max((u >> 16) & 0x7fffu, u & 0x7fffu)) >> 7; }
DI float warp_sum(float v) {
#pragma unroll
  for (int o = 16; o; o >>= 1) v += __shfl_xor_sync(0xffffffffu, v, o);
  return v;
}

constexpr int SM_WO3 = 0;
constexpr int SM_X = 16384;
constexpr int XT = 36864;
constexpr int SM_EXP = 126976;
constexpr int SEGB = 10240;
constexpr int SM_BLK = SM_EXP + 8192;
constexpr int SM_VC = SM_BLK + 4 * SEGB;
constexpr int SM_PART = SM_VC + 16384;
constexpr int SM_QM = SM_PART + 4096;
constexpr int SM_E = SM_QM + 1024;
constexpr int SM_VM = SM_E + 1536;
constexpr int SM_OB = SM_VM + 2048;
constexpr int SM_FB = SM_OB + 2048;
constexpr int SM_STAGE = SM_X + XT;
constexpr int SM_M0 = SM_STAGE + 3 * 49152;
constexpr int SM_MISC = 210944;
constexpr int SM_WOST = 212992;
constexpr int SM_MEM = SM_WOST;
constexpr int SM_MAX = SM_MEM + 11264;
#define MEM_BLK(q) ((q) / 3 * 4096 + (q) % 3 * 1024)
constexpr int SM_TOTAL = 229376;
constexpr int MB_W = SM_MISC;
constexpr int MB_WO = SM_MISC + 24;
constexpr int MB_WO3 = SM_MISC + 32;
constexpr int MB_X = SM_MISC + 40;
constexpr int MB_S = SM_MISC + 64;
constexpr int MB_F = SM_MISC + 72;
constexpr int MB_VX = SM_MISC + 80;
constexpr int SC_FPAR = SM_MISC + 136;
constexpr int SC_DEAD = SM_MISC + 96;
constexpr int SC_UNSC = SM_MISC + 112;
constexpr int SC_OFL = SM_MISC + 1024;
constexpr int SC_EXPW = SM_MISC + 132;
constexpr int SC_ONES = SM_MISC + 144;
constexpr int SC_SS = SM_MISC + 160;
constexpr int SC_LAT = SM_MISC + 224;
constexpr int SC_TAG = SM_MISC + 232;
constexpr int SC_EPO = SM_MISC + 240;
constexpr int MB_XS = SM_MISC + 248;
constexpr int SC_XMAX = SM_MISC + 256;
constexpr int SC_PROF = 229376;

constexpr float SM_SCALE = 0.08838834764831845f;
constexpr float LOG2E = 1.4426950408889634f;
constexpr float E_LIM = 20.f;

template <bool B> struct BoolC { static constexpr bool value = B; };
template <int I> struct IntC { static constexpr int value = I; };
struct RMaps { CUtensorMap x, wq, wk, wv, wo; unsigned char* red; uint32_t poll; const unsigned char* oflag; };

DI uint32_t latest_hint(uint32_t h, uint32_t d, int s) {
  const uint32_t x = (((h | 0xc0c0c0c0u) - ((d >> 5) & 63) * 0x01010101u) & 0x3f3f3f3fu) | ((h ^ (((s >> 2) + 1) & 3) * 0x40404040u) & 0xc0c0c0c0u);
  const uint32_t y = __vmaxu2(x & 0x00ff00ffu, (x >> 8) & 0x00ff00ffu);
  return __reduce_max_sync(0xffffffffu, max(y & 0xffffu, y >> 16));
}
DI uint32_t near_half(uint32_t sb) {
  uint32_t a, b; lds64(sb + SC_LAT, a, b);
  return a > b;
}

template <int RT, int K0, int K1, bool D32 = false>
DI void xproj(float* acc, const uint32_t (&wa)[2][18][4], uint64_t xd) {
  if (XP & 1) return;
  WG_FENCE();
#pragma unroll
  for (int k = K0; k < ((XP & 128) ? K0 + 1 : K1); k++)
  {
    uint64_t d = xd + (uint64_t)(((k >> 1) * 4096 + (k & 1) * 32) >> 4);
    if (D32) asm("mov.b64 %0, {%1, %2};" : "=l"(d) : "r"((uint32_t)xd + (((k >> 1) * 4096 + (k & 1) * 32) >> 4)), "r"((uint32_t)(xd >> 32)));
    wgmma_n32_rs(acc, wa[RT][k][0], wa[RT][k][1], wa[RT][k][2], wa[RT][k][3], d, k != 0);
  }
  WG_COMMIT();
}

DI void load_w(uint32_t sb, const RMaps& tm, uint32_t rank, int c) {
  const int h = blockIdx.x / 3;
  mbar_expect(sb + MB_W + 8 * c, 49152);
  tma_load_ef(sb + SM_STAGE + c * 49152, rank < 2 ? &tm.wk : &tm.wv, h * DH + (rank == 1 ? 64 : 0), c * 192, sb + MB_W + 8 * c);
  tma_load_ef(sb + SM_STAGE + c * 49152 + 24576, rank < 2 ? &tm.wq : &tm.wv, h * DH + (rank == 0 ? 0 : 64), c * 192, sb + MB_W + 8 * c);
}
DI void seg_store(int seg, uint32_t slot, uint32_t sb) {
  asm volatile("cp.async.bulk.global.shared::cta.bulk_group [%0], [%1], 8192;"
               :: "l"(g_seg + ((size_t)slot * 96 + blockIdx.x) * 8192), "r"(sb + SM_BLK + (seg & 3) * SEGB) : "memory");
  asm volatile("cp.async.bulk.commit_group;" ::: "memory");
}
DI void seg_publish(int seg, uint32_t sb) {
  uint32_t v, own;
  lds64(sb + SC_EPO, v, own);
  asm volatile("cp.async.bulk.wait_group 0;" ::: "memory");
  asm volatile("st.relaxed.gpu.global.v2.b32 [%0], {%1,%2};" :: "l"(&g_sflag[blockIdx.x * 4]), "r"(v + seg), "r"(own) : "memory");
}

DI void proj_role(const uint32_t sb, const RMaps& tm, const bf16* __restrict__ x, const uint32_t rank, const int wg, const int w, const int lane) {
  const bool qk = rank < 2;
  uint32_t wa[2][18][4];
  float acc[16];
  const uint64_t xd0 = make_desc(sb + SM_X + wg * 64, 16, 1024, 1);
  {
    const int rr = (lane & 7) + ((lane >> 4) << 3);
    const uint32_t col = ((2 * w + ((lane >> 3) & 1)) ^ (lane & 7)) << 4;
    float ss = 0.f;
    bar_sync(3, 256);
    mbar_wait(sb + MB_X, 0);
    auto chunk = [&](auto cc) {
      constexpr int c = decltype(cc)::value;
      QSTAMP(2 + 2 * c);
      mbar_wait(sb + MB_W + 8 * c, 0);
      QSTAMP(3 + 2 * c);
#pragma unroll
      for (int rt = 1; rt >= 0; rt--)
#pragma unroll
        for (int k = 0; k < 6; k++)
          ldsm4t(wa[rt][c * 6 + k], sb + SM_STAGE + c * 49152 + (rt ^ wg) * 24576 + (64 * (k >> 1) + 32 * wg + 16 * (k & 1) + rr) * 128 + col);
      fence_async();
      if (c < 2) {
        bar_sync(3, 256);
        QSTAMP(17 + c);
        if (threadIdx.x == 0) {
          if (c == 0) tma_load(sb + SM_X + XT, &tm.wo, rank * 192, (blockIdx.x / 3) * DH, sb + MB_WO);
          else if (blockIdx.x < NSEG) bulk_load(sb + SM_X + 2 * XT, x + blockIdx.x * 32 * DM, XT, sb + MB_XS);
          else tma_load3(sb + SM_X + 2 * XT, &tm.x, 64, sb + MB_X + 16);
        }
        __syncwarp();
      } else {
        cluster_arrive();
      }
      xproj<1, 6 * c, 6 * c + 6>(acc, wa, xd0);
      if (!qk) {
        uint32_t q[4] = {0, 0, 0, 0};
#pragma unroll
        for (int rt = 0; rt < 2; rt++)
#pragma unroll
          for (int k = 0; k < 6; k++)
#pragma unroll
            for (int i = 0; i < 4; i++) sq_acc(q[i], wa[rt][c * 6 + k][i]);
#pragma unroll
        for (int i = 0; i < 4; i++) ss += bf_lo(q[i]) + bf_hi(q[i]);
      }
    };
    chunk(IntC<0>()); chunk(IntC<1>()); chunk(IntC<2>());
    ss = warp_sum(ss);
    if (lane == 0) sts32(sb + SC_SS + 4 * (wg * 4 + w), __float_as_uint(ss));
    bar_arrive(11, 384);
  }
  STAMP(1);
  QSTAMP(8);
  STAMP(2);

  uint32_t t16 = sb + (w * 32 + lane) * 16;
  uint32_t mem_a = sb + SM_MEM + wg * 512 + lane * 16;
  uint32_t fin_a = sb + (lane & 7) * 16 + SM_BLK + (qk ? (wg ^ 1) * 4096 + w * 256 + (lane & 8) * 16 + (lane & 16) * 64
                                              : wg * 4096 + w * 1024 + (lane & 8) * 64 + (lane & 16) * 8);
  PIN(t16); PIN(mem_a); PIN(fin_a);
  const uint32_t fence_reg = mem_a;
  const uint32_t fin2 = qk ? 2048 : 256;
  auto do_export = [&](auto retire, uint32_t always) {
    WG_WAIT(0);
    uint32_t p[2];
#pragma unroll
    for (int i = 0; i < 2; i++) {
      p[i] = pack_bf16(acc[8 * i], acc[8 * i + 1]);
      sts128(t16 + SM_EXP + wg * 4096 + i * 2048, p[i], pack_bf16(acc[8 * i + 2], acc[8 * i + 3]),
             pack_bf16(acc[8 * i + 4], acc[8 * i + 5]), pack_bf16(acc[8 * i + 6], acc[8 * i + 7]));
    }
    if (decltype(retire)::value)
      asm volatile("{\n.reg .pred p, q;\nsetp.ne.u32 p, %2, 0;\nsetp.ne.u32 q, %2, 1;\n@p ld.shared.b32 %0, [%3];\n@q ld.shared.b32 %1, [%3 + 4];\n"
                   "setp.ne.u32 p, %0, %1;\n@p exit;\n}" : "+r"(p[0]), "+r"(p[1]) : "r"(always), "r"(sb + SC_DEAD) : "memory");
  };
  uint32_t o[8];
  auto import = [&]() { lds128(t16 + SM_EXP + (wg ^ 1) * 4096, o); lds128(t16 + SM_EXP + (wg ^ 1) * 4096 + 2048, o + 4); };
  auto finish_from = [&](int seg, const float* d) {
    const uint32_t a = fin_a + (seg & 3) * SEGB;
#pragma unroll
    for (int i = 0; i < 8; i++) o[i] = add_bf16(pack_bf16(d[2 * i], d[2 * i + 1]), o[i]);
    stsm4(a, o[0], o[1], o[2], o[3]);
    stsm4(a + fin2, o[4], o[5], o[6], o[7]);
    fence_async();
  };
  auto finish = [&](int seg) { WG_WAIT(0); finish_from(seg, acc); };
  auto send_v = [&](int seg, int dst) {
    if (seg < NSEG - 1 && !(XP & 2) && elect_one())
      bulk_s2s(mapa(sb + SM_VC + (seg & 1) * 8192, dst), sb + SM_BLK + (seg & 3) * SEGB, 8192, mapa(sb + MB_VX + (seg & 1) * 8, dst));
    __syncwarp();
  };
  auto wait_v = [&](int seg) {
    if (seg < NSEG - 1 && !(XP & 2)) {
      mbar_wait(sb + MB_VX + (seg & 1) * 8, (seg >> 1) & 1);
      if (elect_one()) mbar_expect(sb + MB_VX + (seg & 1) * 8, 8192);
      __syncwarp();
    }
  };
  auto export_seg = [&](int seg, uint32_t slot) { if (!(XP & (4 | 8192)) && elect_one()) seg_store(seg, slot, sb); __syncwarp(); };
  auto publish = [&](int seg) { if (!(XP & (4 | 16384)) && elect_one()) seg_publish(seg, sb); __syncwarp(); };
  do_export(BoolC<false>(), 0);
  QSTAMP(9);
  SCHED_FENCE(11);
  xproj<0, 0, 18>(acc, wa, xd0);
  bar_sync(3, 256);
  QSTAMP(10);
  cluster_wait();
  QSTAMP(11);
  mbar_wait(sb + MB_X + 8, 0);
  QSTAMP(12);
  import();
  finish(0);
  SCHED_FENCE(12);
  uint64_t dA = xd0 + (XT >> 4);
  xproj<1, 0, 18>(acc, wa, dA);
  bar_sync(3, 256);
  if (!qk && wg == 0 && w < 2) send_v(0, w);
  if (wg == 0 && w == 3) export_seg(0, 0);
  QSTAMP(13);
  if (qk && wg == 0 && w == 0) wait_v(0);
  QSTAMP(14);
  bar_arrive(13, 384);
  if (!qk) {
    do_export(BoolC<false>(), 0);
    SCHED_FENCE(15);
    xproj<0, 0, 18>(acc, wa, dA);
    if (threadIdx.x == 0 && !(XP & 8)) { mbar_expect(sb + MB_X, XT); tma_load3(sb + SM_X, &tm.x, 96, sb + MB_X); }
    bar_sync(3, 256);
    mbar_wait(sb + MB_X + 16, 0);
    import();
    finish(1);
    SCHED_FENCE(16);
    dA += XT >> 4;
    xproj<1, 0, 18>(acc, wa, dA);
  }
  QSTAMP(15);
  WG_WAIT(0);
  bar_sync(0, 384);
  if (wg == 0 && w == 3) publish(0);
  QSTAMP(16);
  const int ro = __shfl_sync(0xffffffffu, near_half(sb) ^ wg, 0);
  STAMP(5);
  const uint32_t always = __shfl_sync(0xffffffffu, lds32(sb + SC_DEAD + 12), 0);
  const int ah = qk ? 1 : 2;
  int b2 = qk ? 2 : 0;
  int s = 0;
  uint32_t hint_lo = (uint32_t)(uint64_t)tm.red + HINT_OFF + blockIdx.x + (lane & 1) * 4096 + (lane >> 1) * 16384;
  PIN(hint_lo);
  auto post_hint = [&]() {
    uint32_t t;
    asm volatile("{\n.reg .u64 g;\nmov.u64 g, %%globaltimer;\ncvt.u32.u64 %0, g;\n}" : "=r"(t) :: "memory");
    asm volatile("{\n.reg .pred p;\n.reg .b64 a;\n.reg .u32 t;\nsetp.lt.u32 p, %0, %1;\nmov.b64 a, {%2, %3};\n"
                 "bfe.u32 t, %5, 5, 6;\nor.b32 t, t, %4;\n@p st.relaxed.gpu.global.u8 [a], t;\n}"
                 :: "r"(t16), "r"(sb + 160), "r"(hint_lo + RED_SLOT(s)), "r"((uint32_t)((uint64_t)tm.red >> 32)), "r"(((s >> 2) + 1) << 6), "r"(t) : "memory");
  };
  auto memproj = [&](auto second, int id, uint32_t dep, float u0, float u1, float* r) {
    constexpr bool R1 = decltype(second)::value;
    uint32_t b[NUP][4], b0[4];
    if (R1) asm volatile("{\n.reg .pred p;\nsetp.eq.u32 p, %0, %1;\n@p exit;\n}" :: "r"(dep), "r"(id) : "memory");
    bar_sync(R1 ? 2 : 1, 256);
    PROF(0);
    ldsm4t(b0, mem_a);
#pragma unroll
    for (int q = 0; q < NUP; q++) {
      if (R1 && q == 2) {
        bar_sync(11, 256);
        SCHED_FENCE(id + 1);
      }
      ldsm4t(b[q], mem_a + MEM_BLK(q + 1));
    }
    mma16816z(&acc[0], wa[0][0], b0[0], b0[1]);
    mma16816z(&acc[4], wa[1][0], b0[0], b0[1]);
    mma16816z(&acc[8], wa[0][1], b0[2], b0[3]);
    mma16816z(&acc[12], wa[1][1], b0[2], b0[3]);
#pragma unroll
    for (int q = 1; q < 9; q++) {
      uint32_t* const c = b[(q - 1) % NUP];
      mma16816(&acc[0], wa[0][2 * q], c[0], c[1]);
      mma16816(&acc[4], wa[1][2 * q], c[0], c[1]);
      mma16816(&acc[8], wa[0][2 * q + 1], c[2], c[3]);
      mma16816(&acc[12], wa[1][2 * q + 1], c[2], c[3]);
      if (R1 && q + NUP == 9) bar_sync(3, 256);
      if (q + NUP < 9) ldsm4t_in(c, mem_a + MEM_BLK(q + NUP), always);
      else if (R1 && q + NUP < 11) lds128_in(c, t16 + SM_PART + (10 - q - NUP) * 2048, always);
      else if (!R1 && q == 8) { bar_arrive(11, 256); lds128_in(c, sb + SC_DEAD, always); u0 = u1 = __uint_as_float(c[3]); }
    }
#pragma unroll
    for (int i = 0; i < 8; i++) {
      const float u = i < 4 ? u0 : u1;
      r[i] = R1 ? fmaf(acc[8 + i], u, (acc[i] + __uint_as_float(b[(8 + i / 4) % NUP][i & 3])) * u) : fmaf(acc[i], u, acc[8 + i]);
    }
  };
  if (ro == 0) {
#pragma unroll 1
    while (true) {
      do_export(BoolC<true>(), always);
      PROFP(3);
      if (s == 8) STAMP(6);
      float r[8];
      memproj(BoolC<false>(), 30, 0, 0.f, 0.f, r);
      sts128(t16 + SM_PART, __float_as_uint(r[0]), __float_as_uint(r[1]), __float_as_uint(r[2]), __float_as_uint(r[3]));
      sts128(t16 + SM_PART + 2048, __float_as_uint(r[4]), __float_as_uint(r[5]), __float_as_uint(r[6]), __float_as_uint(r[7]));
      bar_arrive(3, 256);
      PROF(1);
      bar_sync(9, 256);
      post_hint();
      if (w == 3 && s) publish(s);
      if (s == NSEG - 1) break;
      if (w == 1) {
        uint32_t m[8];
        lds128(t16 + SM_MAX - 512, m); lds128(t16 + SM_MAX, m + 4);
        const int em = (wexp(amax4(amax4(*(const __half2*)&m[0], m), m + 4)) >> 3) + (int)(lds32(sb + SC_UNSC + (s & 1) * 8) >> 23) - 15;
        const int ex = max(s ? em : 0, (int)lds32(sb + SC_XMAX + 4 * s)) - 127 + (int)lds32(sb + SC_EXPW);
        sts32(sb + SC_UNSC + (~s & 1) * 8, (127 + min(max(ex, -120), 120)) << 23);
        __syncwarp();
        if (elect_one()) mbar_arrive(sb + MB_S);
      }
      SCHED_FENCE(9);
      bar_sync(5, qk ? N5 : 256);
      PROF(2);
      import();
      xproj<0, 0, 18>(acc, wa, dA);
      WG_WAIT(0);
      bar_sync(10, 256);
      SCHED_FENCE(17);
      dA += (int64_t)(b2 ? XT >> 4 : -(XT >> 3));
      finish(s + ah);
      if (w != 3) bar_arrive(13, 384);
      PROF(6);
      SCHED_FENCE(14);
      bar_sync(12, 256);
      PROF(7);
      xproj<1, 0, 18, true>(acc, wa, dA);
      bar_arrive(14, 256);
      b2 = b2 == 2 ? 0 : b2 + 1;
      s++;
      if (w == 3) {
        const uint32_t slot = s < lds32(sb + SC_EPO + 4) ? s & 7 : s;
        bar_sync(13, 384);
        export_seg(s, slot);
      }
      PROFP(8);
    }
    if (!qk) bar_arrive(5, 256);
  } else {
    uint32_t km[4];
    auto send_km = [&]() {
      if (XP & (4 | 4096)) return;
      uint32_t t, u;
      lds64(sb + SC_TAG, t, u);
      t |= km[0] & ~1u; u += s * (NH * 4096);
      if (qk)
        asm volatile("{\n.reg .u32 o;\n.reg .u64 a;\nshr.u32 o, %0, 1;\nadd.u32 o, o, %1;\nmad.wide.u32 a, o, 1, %2;\nst.relaxed.gpu.global.v2.b32 [a], {%3,%4};\n}"
                     :: "r"(t16), "r"(u), "l"(g_km), "r"(t), "r"(km[1]) : "memory");
      else
        asm volatile("{\n.reg .u32 o;\n.reg .u64 a;\nadd.u32 o, %0, %1;\nmad.wide.u32 a, o, 1, %2;\nst.relaxed.gpu.global.v4.b32 [a], {%3,%4,%5,%6};\n}"
                     :: "r"(t16), "r"(u), "l"(g_km), "r"(t), "r"(km[1]), "r"(km[2]), "r"(km[3]) : "memory");
    };
#pragma unroll 1
    while (true) {
      do_export(BoolC<true>(), always);
      if (!qk && w == 2) send_v(s + 1, 0);
      PROFP(3);
      if (s == 8) STAMP(6);
      const uint32_t tl = ((t16 >> 8) ^ wg) & 1, am = (t16 & ~256u) - w * 256;
      const float un = __uint_as_float(lds32(sb + SC_UNSC + (s & 1) * 8));
      float r[8];
      if (qk) {
        uint32_t a0 = am + (tl ? SM_QM : SM_BLK + 8192 + (s & 3) * SEGB);
        float u0 = wg ? un * (SM_SCALE * LOG2E) : un, u1 = wg ? un : un * (SM_SCALE * LOG2E);
        PIN(a0); PIN(u0); PIN(u1);
        memproj(BoolC<true>(), 32, a0, u0, u1, r);
        const uint32_t p0 = pack_bf16(r[0], r[1]), p1 = pack_bf16(r[2], r[3]), p2 = pack_bf16(r[4], r[5]), p3 = pack_bf16(r[6], r[7]);
        stsm4(a0, p0, p1, p2, p3);
        bar_arrive(4, 256);
        km[0] = wg ? p2 : p0; km[1] = wg ? p3 : p1;
      } else {
        const uint32_t d0 = s < NSEG - 1 ? 0 : 2, d1 = s < NSEG - 1 ? 1 : 2;
        uint32_t r0 = mapa(t16 + SM_VM, d0), r1 = mapa(t16 + SM_VM, d1);
        PIN(r0); PIN(r1);
        memproj(BoolC<true>(), 34, r0 | r1, un, un, r);
        const uint32_t p0 = pack_bf16(r[0], r[1]), p1 = pack_bf16(r[2], r[3]), p2 = pack_bf16(r[4], r[5]), p3 = pack_bf16(r[6], r[7]);
        const uint32_t v0 = wg ? p2 : p0, v1 = wg ? p3 : p1, v2 = wg ? p0 : p2, v3 = wg ? p1 : p3;
        st_async4(r0, v0, v1, v2, v3, mapa(sb + MB_S, d0));
        st_async4(r1, v0, v1, v2, v3, mapa(sb + MB_S, d1));
        bar_arrive(5, 256);
        sts128(t16 + SM_VM, v0, v1, v2, v3);
        __syncwarp();
        if (elect_one()) mbar_arrive(sb + MB_S);
        km[0] = v0; km[1] = v1; km[2] = v2; km[3] = v3;
      }
      PROF(1);
      auto rearm = [&]() { mbar_wait(sb + MB_S, s & 1); if (elect_one()) mbar_expect(sb + MB_S, qk ? 640 + 2048 : 1280); __syncwarp(); };
      if (s == NSEG - 1 && w != 1) {
      } else if (w == 1) {
        if ((t16 & 384) == 0) stg_relaxed(tm.red + (RED_SLOT(s + 2) + RED_LINE(blockIdx.x)) + (t16 & 112), 0, 0, 0, 0);
        uint32_t base, own;
        lds64(sb + SC_EPO, base, own);
        if ((int)(lds32v(sb + SC_OFL) - base) < s - 7) sts32(sb + SC_EPO + 4, min(own, s + 1));
        if (elect_one()) bulk_load(sb + SC_OFL, tm.oflag + blockIdx.x * 128, 16, sb + MB_XS);
      } else if (w == 0) {
        const int tn = s + ah + 1;
        if (tn + 1 < NSEG && !(XP & 8) && elect_one()) {
          const int b0 = b2 == 2 ? 0 : b2 + 1;
          mbar_expect(sb + MB_X + 8 * b0, XT);
          tma_load3(sb + SM_X + b0 * XT, &tm.x, (tn + 1) * 32, sb + MB_X + 8 * b0);
        }
        if (tn < NSEG && (!(XP & 8) || tn < 3)) mbar_wait(sb + MB_X + 8 * b2, (tn / 3) & 1);
      } else if (w == 2) {
        if (!qk) send_v(s + 1, 1);
      } else {
        rearm();
      }
      __syncwarp();
      send_km();
      if (s == NSEG - 1) break;
      import();
      PROF(4);
      SCHED_FENCE(10);
      bar_sync(7, 256);
      xproj<0, 0, 18>(acc, wa, dA);
      bar_arrive(12, 256);
      dA += (int64_t)(b2 ? XT >> 4 : -(XT >> 3));
      finish(s + ah);
      if (qk && w == 0) wait_v(s + 1);
      bar_arrive(13, 384);
      PROF(6);
      SCHED_FENCE(13);
      bar_sync(14, 256);
      PROF(7);
      xproj<1, 0, 18>(acc, wa, dA);
      b2 = b2 == 2 ? 0 : b2 + 1;
      s++;
      PROFP(8);
    }
  }
  bar_arrive(0, 384);
  STAMP(3);
  cluster_sync();
  STAMP(4);
}

DI void attn_role(const uint32_t sb, unsigned char* smem_raw, const RMaps& tm, const uint32_t RANK, const bf16* __restrict__ x, const bf16* __restrict__ mem0,
                  const int w, const int lane) {
  const int t2 = w * 32 + lane;
  uint32_t wo[8][4], w1[8][4];
  const uint32_t wo_lane = sb + ((lane & 7) + ((lane >> 4) << 3)) * 128 + (((w + 4 * ((lane >> 3) & 1)) ^ (lane & 7)) << 4);
  unsigned char* const g_red = tm.red;
  {
    const uint32_t tag = *(volatile unsigned*)&g_epoch + 1;
    QSTAMP(0);
    bar_sync(0, 160);
    QSTAMP(1);
    cluster_arrive();
    __half2 hx = __float2half2_rn(0.f);
    if (t2 == 0) { sts32(sb + SC_OFL, (tag - 1) * NSEG); sts64(sb + SC_EPO, (tag - 1) * NSEG + 1, NSEG); sts64(sb + SC_TAG, tag & 1, blockIdx.x / 3 * 4096 + (RANK < 2 ? RANK * 1024 - (sb >> 1) : 2048 - sb)); sts32(sb + SC_UNSC, __float_as_uint(1.f)); sts128(sb + SC_DEAD, 0, 0, 0, 0x3f800000u); sts64(sb + SC_FPAR, 0, 0); sts128(sb + SC_ONES, 0x3f803f80u, 0x3f803f80u, 0x3f803f80u, 0x3f803f80u); }
    WSTAMP(27);
    uint32_t q[8] = {0, 0, 0, 0, 0, 0, 0, 0};
    QSTAMP(2);
    mbar_wait(sb + MB_WO3, 0);
    QSTAMP(3);
    uint32_t mv[5][4];
#pragma unroll
    for (int i = 0; i < 5; i++) {
      ldsm4(mv[i], sb + SM_M0 + (lane & 7) * (DM * 2) + min(w + 4 * i, 17) * 64 + (lane >> 3) * 16);
      if (blockIdx.x == 0) hx = amax4(hx, mv[i]);
    }
#pragma unroll
    for (int k = 0; k < 8; k++) {
      ldsm4t(wo[k], wo_lane + SM_WO3 + k * 2048); ldsm4t(w1[k], wo_lane + SM_WOST + k * 2048);
#pragma unroll
      for (int i = 0; i < 4; i++) { sq_acc(q[i], wo[k][i]); sq_acc(q[i], w1[k][i]); }
    }
    bar_sync(6, 128);
#pragma unroll
    for (int k = 0; k < 8; k++) sts128(sb + SM_WO3 + t2 * 16 + k * 2048, wo[k][0], wo[k][1], wo[k][2], wo[k][3]);
#pragma unroll
    for (int i = 0; i < 5; i++) {
      const int c = (w + 4 * i) * 32;
      if (c < DM) stsm4t(sb + SM_MEM + (c + c / 192 * 64 + lane) * 16, mv[i][0], mv[i][1], mv[i][2], mv[i][3]);
    }
    bar_arrive(1, 256); bar_arrive(2, 256); bar_arrive(9, 256);
    QSTAMP(4);
    mbar_wait(sb + MB_WO, 0);
    QSTAMP(5);
#pragma unroll
    for (int k = 0; k < 8; k++) ldsm4t(wo[k], wo_lane + SM_X + XT + k * 2048);
    fence_async();
    bar_sync(6, 128);
    if (t2 == 32) tma_load3(sb + SM_X + XT, &tm.x, 32, sb + MB_X + 8);
    __syncwarp();
#pragma unroll
    for (int k = 0; k < 8; k++)
#pragma unroll
      for (int i = 0; i < 4; i++) sq_acc(q[4 + i], wo[k][i]);
    float ss = 0.f;
#pragma unroll
    for (int i = 0; i < 8; i++) ss += bf_lo(q[i]) + bf_hi(q[i]);
    ss = warp_sum(ss);
    if (lane == 0) sts32(sb + SC_SS + 4 * (8 + w), __float_as_uint(ss));
    if (blockIdx.x < NSEG) {
      mbar_wait(sb + MB_XS, 0);
#pragma unroll
      for (int i = 0; i < 18; i++) { uint32_t v[4]; lds128(sb + SM_X + 2 * XT + t2 * 16 + i * 2048, v); hx = amax4(hx, v); }
      fence_async();
      bar_sync(6, 128);
      if (t2 == 32) tma_load3(sb + SM_X + 2 * XT, &tm.x, 64, sb + MB_X + 16);
      __syncwarp();
    }
    sts32(sb + SC_SS + 4 * (12 + w), wexp(hx));
    QSTAMP(6);
    bar_sync(11, 384);
    QSTAMP(7);
    if (t2 == 0) {
      float a[16];
#pragma unroll
      for (int i = 0; i < 4; i++) lds128f(sb + SC_SS + 16 * i, &a[4 * i]);
      stg_relaxed(&g_stats[blockIdx.x * 2], __float_as_uint(((a[0] + a[1]) + (a[2] + a[3])) + ((a[4] + a[5]) + (a[6] + a[7]))),
                  __float_as_uint((a[8] + a[9]) + (a[10] + a[11])),
                  max(max(__float_as_uint(a[12]), __float_as_uint(a[13])), max(__float_as_uint(a[14]), __float_as_uint(a[15]))), tag);
    }
    __syncwarp();
    WSTAMP(24);
    QSTAMP(8);
    cluster_wait();
    QSTAMP(9);
    if (w == 0) {
      uint4 v[3];
      int n = 0;
      while (true) {
#pragma unroll
        for (int i = 0; i < 3; i++) v[i] = ldg_relaxed(&g_stats[(i * 32 + lane) * 2]);
        if (__all_sync(0xffffffffu, v[0].w == tag && v[1].w == tag && v[2].w == tag) || ++n > SPIN_LIMIT) break;
        __nanosleep(100);
      }
      WSTAMP(25);
      QSTAMP(10);
      const float sv = warp_sum(__uint_as_float(v[0].x) + __uint_as_float(v[1].x) + __uint_as_float(v[2].x));
      const float so = warp_sum(__uint_as_float(v[0].y) + __uint_as_float(v[1].y) + __uint_as_float(v[2].y));
      const int expW = ((int)(__float_as_uint(sv) >> 23) + (int)(__float_as_uint(so) >> 23) - 254 + 2 + 10 + 1) >> 1;
      sts32(sb + SC_XMAX + 4 * lane, v[0].z); sts32(sb + SC_XMAX + 128 + 4 * lane, v[1].z);
      sts32(sb + SC_EXPW, expW + 1 - 15);
      if (blockIdx.x == 0 && lane == 0) *(volatile unsigned*)&g_epoch = tag;
      sts32(sb + SC_FPAR + 4, 1);
    } else if (w < 3) {
      const uint32_t u = blockIdx.x >> 4;
      unsigned char* const z = g_red + 98304 + (blockIdx.x & 15) * 128 + (u & 1) * 2048 + (u & 6) * 4096 + (((u >> 1) ^ w) & 1) * 4096 + lane * 4;
      stg_relaxed32(z, 0);
      uint32_t best = 0xffffffffu;
#pragma unroll 1
      for (int i = 0; i < 64; i++) {
        uint32_t dt;
        asm volatile("{\n.reg .pred p;\n.reg .u32 c, v;\nmov.u32 c, %%clock;\n"
                     "atom.relaxed.gpu.global.exch.b32 v, [%1], 0;\nsetp.eq.u32 p, v, 0;\nmov.u32 %0, 0;\n@p mov.u32 %0, %%clock;\nsub.u32 %0, %0, c;\n}"
                     : "=r"(dt) : "l"(z) : "memory");
        best = min(best, dt);
        if (lds32v(sb + SC_FPAR + 4) && i >= 1) break;
      }
      sts32(sb + SC_LAT + (w - 1) * 4, best);
    }
    QSTAMP(11);
    bar_sync(13, 384);
    bar_arrive(0, 384);
    QSTAMP(12);
    WSTAMP(26);
  }

  const uint32_t nh = __shfl_sync(0xffffffffu, near_half(sb), 0);
  uint32_t l16 = sb + lane * 16;
  PIN(l16);
#define LV ((l16 >> 4) & 31)
#define fence_reg l16
  const uint32_t red_lo = (uint32_t)(uint64_t)g_red, red_hi = (uint32_t)((uint64_t)g_red >> 32);
  uint32_t lp;
  auto slot = [&](int s, uint32_t c, uint32_t ofs) {
    const uint32_t lo = lp | (red_lo + ((w >> 1) * 4 + (w & 1) * 2 + ((w ^ c) & 1)) * 4096 + RED_SLOT(s) + ofs);
    uint64_t a; asm("mov.b64 %0, {%1, %2};" : "=l"(a) : "r"(lo), "r"(red_hi));
    return (unsigned char*)a;
  };
  const uint32_t always = __shfl_sync(0xffffffffu, lds32(sb + SC_DEAD + 12), 0);
  const int mode0 = RANK < 2 ? w : w | 4;
  auto hint_addr = [&](int s) { return min(LV, 23u) * 4 + (red_lo + HINT_OFF + nh * 4096 + w * 16384 + RED_SLOT(s)); };
  auto load_hints = [&](uint32_t lo) {
    uint64_t a; asm("mov.b64 %0, {%1, %2};" : "=l"(a) : "r"(lo), "r"(red_hi));
    return ldg_relaxed32((const void*)a);
  };
  int s = 0;
  bool bad = false;
#pragma unroll 1
  while (true) {
    const uint32_t par = s & 1;
    uint32_t vx[4][4], hints;
    auto load_vx = [&]() {
      const uint32_t va = l16 + (RANK < 2 ? SM_VC + par * 8192 : SM_BLK + (s & 3) * SEGB) + w * 1024 + ((LV >> 3) & 1) * 384 - (LV >> 4) * 128;
#pragma unroll
      for (int i = 0; i < 4; i++) ldsm4(vx[i], va + (i & 1) * 4096 + (i >> 1) * 256);
    };
    auto retire = [&](uint32_t x) {
      asm volatile("{\n.reg .pred p;\nsetp.eq.u32 p, %0, 0;\n@p exit;\n}" :: "r"(vx[0][0] | vx[1][0] | vx[2][0] | vx[3][0] | x) : "memory");
    };
    auto scores = [&](auto memkeys, auto first, float* sc) {
      constexpr bool MK = decltype(memkeys)::value, FIRST = decltype(first)::value;
      uint32_t kb[4][4], qb[2][4];
      const uint32_t m = LV >> 3;
      uint32_t kaddr = l16 + SM_BLK + 4096 + (s & 3) * SEGB + w * 2048 + (m & 1) * (MK ? 128 : 896) - (m >> 1) * 128;
      if (MK) { PIN(kaddr); }
      else {
#pragma unroll
        for (int k = 0; k < 4; k++) ldsm4t(kb[k], kaddr + k * 256);
      }
      if (FIRST) { load_vx(); retire(MK ? kaddr : kb[0][0] | kb[1][0] | kb[2][0] | kb[3][0] | l16); bar_sync(4, 256); PROF(4); }
      ldsm4t(qb[0], l16 + SM_QM);
      if (MK) ldsm4t(kb[0], kaddr);
      ldsm4t(qb[1], l16 + SM_QM + 512);
      if (MK) ldsm4t(kb[2], kaddr + 512);
      float c[4][4];
      mma16816z(c[0], kb[0], qb[0][0], qb[0][1]); mma16816z(c[1], kb[MK ? 0 : 1], qb[0][2], qb[0][3]);
      mma16816z(c[2], kb[2], qb[1][0], qb[1][1]); mma16816z(c[3], kb[MK ? 2 : 3], qb[1][2], qb[1][3]);
      if (FIRST) bar_arrive(5, N5);
#pragma unroll
      for (int i = 0; i < (MK ? 2 : 4); i++) sc[i] = ((c[0][i] + c[1][MK ? i + 2 : i]) + c[2][i]) + c[3][MK ? i + 2 : i];
    };
    auto send = [&](auto memkeys) {
      constexpr bool MK = decltype(memkeys)::value;
      constexpr int N = MK ? 1 : 2;
      const uint32_t sa = sb + LV * 4 + SM_E + (MK ? 1024 + RANK * 128 : RANK * 512 + w * 256);
      uint32_t ra[N][2], mb[N][2];
#pragma unroll
      for (int i = 0; i < N; i++)
#pragma unroll
        for (int j = 0; j < 2; j++) {
          ra[i][j] = mapa(sa + i * 128, j ? 2 : RANK ^ 1); mb[i][j] = mapa(sb + MB_S, j ? 2 : RANK ^ 1);
          PIN(ra[i][j]);
        }
      float sc[4];
      scores(memkeys, BoolC<true>(), sc);
      uint32_t e[N];
#pragma unroll
      for (int i = 0; i < N; i++) {
        e[i] = pack_bf16(ex2(sc[2 * i]), ex2(sc[2 * i + 1]));
        if (!(fmaxf(fabsf(sc[2 * i]), fabsf(sc[2 * i + 1])) <= E_LIM)) e[i] = 0x7fff7fffu;
        st_async1(ra[i][0], e[i], mb[i][0]);
        st_async1(ra[i][1], e[i], mb[i][1]);
      }
#pragma unroll
      for (int i = 0; i < N; i++) sts32(sa + i * 128, e[i]);
      __syncwarp();
      if (l16 == sb) mbar_arrive(sb + MB_S);
      PROF(5);
    };
    const int mode = bad ? 8 : mode0;
    if (mode < 2) {
      send(BoolC<false>());
    } else if (mode == 2) {
      send(BoolC<true>());
    } else if (mode == 8) {
      load_vx();
      retire(l16);
      const uint32_t fp = lds32(sb + SC_FPAR);
      bar_sync(6, 128);
      if (w == 0 && l16 == sb) { sts32(sb + SC_FPAR, fp ^ 1); mbar_expect(sb + MB_F, 3072); }
      if (RANK < 2 && w < 3) {
        float sc[4] = {0.f, 0.f, 0.f, 0.f};
        if (w < 2) scores(BoolC<false>(), BoolC<false>(), sc); else scores(BoolC<true>(), BoolC<false>(), sc);
#pragma unroll 1
        for (int r = 0; r < 3; r++)
          st_async4(mapa(l16 + SM_FB + RANK * 1536 + w * 512, r), __float_as_uint(sc[0]), __float_as_uint(sc[1]), __float_as_uint(sc[2]), __float_as_uint(sc[3]), mapa(sb + MB_F, r));
      }
      mbar_wait(sb + MB_F, fp);
      float a[12];
#pragma unroll
      for (int j = 0; j < 3; j++) {
        float b[4];
        lds128f(l16 + SM_FB + j * 512, a + 4 * j); lds128f(l16 + SM_FB + 1536 + j * 512, b);
#pragma unroll
        for (int i = 0; i < 4; i++) a[4 * j + i] += b[i];
      }
      float m0 = fmaxf(fmaxf(fmaxf(a[0], a[2]), fmaxf(a[4], a[6])), a[8]), m1 = fmaxf(fmaxf(fmaxf(a[1], a[3]), fmaxf(a[5], a[7])), a[9]);
#pragma unroll
      for (int o = 4; o < 32; o <<= 1) { m0 = fmaxf(m0, __shfl_xor_sync(0xffffffffu, m0, o)); m1 = fmaxf(m1, __shfl_xor_sync(0xffffffffu, m1, o)); }
#pragma unroll
      for (int i = 0; i < 5; i++) {
        const uint32_t ea = sb + SM_E + LV * 4 + (i < 4 ? i * 128 : 1024);
        sts32(ea, pack_bf16(ex2(a[2 * i] - m0), ex2(a[2 * i + 1] - m1)));
        sts32(ea + (i < 4 ? 512 : 128), 0x3f803f80u);
      }
      __syncwarp();
    } else {
      load_vx();
      if (mode == 3) bar_arrive(4, 256);
      retire(l16 + 1);
    }
    {
      uint32_t wa[4], wb[4], oc[4];
      constexpr int WS = 2048;
      const uint32_t w3a = l16 + SM_WO3 + w * 512;
      lds128(w3a + KP(0) * WS, wa); lds128(w3a + KP(1) * WS, wb); lds128(sb + SC_ONES, oc);
      uint32_t e[10], p[5], vm[4], ob[4];
      float o0[4], o1[4], f[3][2][4], rs[4];
      reserve2(vm); reserve2(vm + 2); reserve2(e + 8);
      hints = hint_addr(s);
      PIN(hints);
      mbar_wait(sb + MB_S, par);
      PROF(6);
      ldsm4t(e, l16 + SM_E); ldsm2t_in(e + 8, l16 + SM_E + 1024, always); ldsm4t(e + 4, l16 + SM_E + 512);
      lds128_in(vm, l16 + w * 512 + SM_VM, always);
      const float scl = __uint_as_float(lds32(sb + SC_UNSC + 8 - par * 8));
      hints = load_hints(hints);
#pragma unroll
      for (int i = 0; i < 4; i++) p[i] = mul_bf16(e[i], e[4 + i]);
      p[4] = mul_bf16(e[8], e[9]);
      mma16816z(o0, vx[0], p[0], p[1]); mma16816z(o1, vx[1], p[0], p[1]); mma16816z(rs, oc, p[0], p[1]);
      mma16816(o0, vx[2], p[2], p[3]); lds128_in(vx[2], w3a + KP(2) * WS, always);
      mma16816(o1, vx[3], p[2], p[3]); lds128_in(vx[3], w3a + KP(3) * WS, always);
      mma16816(rs, oc, p[2], p[3]);
      mma1688(o0, vm[0], vm[1], p[4]); mma1688(o1, vm[2], vm[3], p[4]); mma1688(rs, oc[0], oc[1], p[4]);
      stsm4(l16 + w * 512 + SM_OB, pack_bf16(o0[0], o0[1]), pack_bf16(o0[2], o0[3]), pack_bf16(o1[0], o1[1]), pack_bf16(o1[2], o1[3]));
      bar_sync(6, 128);
      PROF(7);
      ldsm4t_in(oc, l16 + SM_OB, always);
      bad = __any_sync(0xffffffffu, !(rs[0] + rs[1] > 0.f) && !bad);
      rs[0] *= scl; rs[1] *= scl;
      asm volatile("{\n.reg .pred p;\nsetp.ne.u32 p, %1, 0;\n@p rcp.approx.ftz.f32 %0, %0;\n}" : "+f"(rs[0]) : "r"(always));
      asm volatile("{\n.reg .pred p;\nsetp.ne.u32 p, %1, 1;\n@p rcp.approx.ftz.f32 %0, %0;\n}" : "+f"(rs[1]) : "r"(always));
      asm volatile("lop3.b32 %0, %1, %2, %3, 0xfe;" : "=r"(lp) : "r"((l16 & 128) * 2), "r"((l16 & 256) * 4), "r"(l16 & 112));
      if (bad) continue;
      ldsm4t(ob, l16 + SM_OB + 512);
      mma16816z(f[2][0], wa, oc[0], oc[1]); mma16816z(f[2][1], wb, oc[2], oc[3]);
      mma16816z(f[0][0], wo[0], oc[0], oc[1]); mma16816z(f[0][1], wo[4], oc[2], oc[3]);
      mma16816z(f[1][0], w1[0], oc[0], oc[1]); mma16816z(f[1][1], w1[4], oc[2], oc[3]);
      ldsm4t_in(oc, l16 + SM_OB + 1024, always);
      mma16816(f[2][0], vx[2], ob[0], ob[1]); lds128_in(vx[2], w3a + KP(4) * WS, always);
      mma16816(f[2][1], vx[3], ob[2], ob[3]); lds128_in(vx[3], w3a + KP(5) * WS, always);
      mma16816(f[0][0], wo[1], ob[0], ob[1]); mma16816(f[0][1], wo[5], ob[2], ob[3]);
      mma16816(f[1][0], w1[1], ob[0], ob[1]); mma16816(f[1][1], w1[5], ob[2], ob[3]);
      ldsm4t_in(ob, l16 + SM_OB + 1536, always);
      mma16816(f[0][0], wo[2], oc[0], oc[1]); mma16816(f[0][1], wo[6], oc[2], oc[3]);
      mma16816(f[2][0], vx[2], oc[0], oc[1]); lds128_in(vx[2], w3a + KP(6) * WS, always);
      mma16816(f[2][1], vx[3], oc[2], oc[3]); lds128_in(vx[3], w3a + KP(7) * WS, always);
      mma16816(f[1][0], w1[2], oc[0], oc[1]); mma16816(f[1][1], w1[6], oc[2], oc[3]);
      mma16816(f[0][0], wo[3], ob[0], ob[1]); mma16816(f[0][1], wo[7], ob[2], ob[3]);
      mma16816(f[1][0], w1[3], ob[0], ob[1]); mma16816(f[1][1], w1[7], ob[2], ob[3]);
      mma16816(f[2][0], vx[2], ob[0], ob[1]); mma16816(f[2][1], vx[3], ob[2], ob[3]);
      bar_arrive(7, 256);
      lds128_in(ob, sb + SC_DEAD, always);
      uint32_t h[3][2];
#pragma unroll
      for (int j = 0; j < 3; j++)
#pragma unroll
        for (int i = 0; i < 2; i++)
        {
          scale_sum(f[j][1][2 * i], f[j][0][2 * i], rs[0], always); scale_sum(f[j][1][2 * i + 1], f[j][0][2 * i + 1], rs[1], always);
          h[j][i] = pack_f16(f[j][1][2 * i], f[j][1][2 * i + 1]);
        }
      const uint32_t rofs = RANK * 32768;
      red_f16x8(slot(s, RANK >> 1, rofs), h[0][0], h[1][0], h[2][0], 0x3c00u);
      red_f16x8(slot(s, (RANK >> 1) ^ 1, rofs), h[0][1], h[1][1], h[2][1], 0x3c00u);
      bar_arrive(10, 256);
      SCHED_FENCE(5);
      l16 += ob[1];
    }
    {
    PROF(8);
    const uint32_t ma0 = l16 + SM_MEM + w * 128 + (LV >> 3) * 896 + nh * 512;
    const unsigned char* const sl[2] = {slot(s, nh, 0), slot(s, nh ^ 1, 0)};
    uint32_t dl = gtime() - 1984;
    uint32_t late = latest_hint(hints, dl, s);
    if (late >= 64) {
      int n = 0;
#pragma unroll 1
      do {
        hints = load_hints(hint_addr(s));
        dl = gtime() - 1984;
        late = latest_hint(hints, dl, s);
      } while (late >= 64 && ++n < SPIN_LIMIT);
    }
    dl += late * 32 + tm.poll;
    PROF(9);
    {
      auto wait_until = [&](uint32_t t) {
        asm volatile("{\n.reg .pred p;\n.reg .s32 c;\n.reg .u64 t;\nTL: mov.u64 t, %%globaltimer;\ncvt.u32.u64 c, t;\nsub.s32 c, c, %0;\nsetp.lt.s32 p, c, 0;\n@p bra.uni TL;\n}" :: "r"(t + (l16 & 15)) : "memory");
      };
      uint4 v[2][3];
      auto load = [&](int c) {
#pragma unroll
        for (int r = 0; r < 3; r++) v[c][r] = ldg_relaxed(sl[c ^ (r >> 1)] + r * 32768);
      };
      auto decode = [&](int c, int n) {
        uint32_t q[9];
        __half2 hm;
        const uint32_t ma = ma0 ^ (c * 512);
#pragma unroll
        for (int i = 0; i < 9; i++) {
          const uint32_t h = i % 3 == 0 ? v[c][i / 3].x : (i % 3 == 1 ? v[c][i / 3].y : v[c][i / 3].z);
          const float2 f = __half22float2(*(const __half2*)&h);
          q[i] = pack_bf16(f.x, f.y);
          hm = i ? __hmax2(hm, __habs2(*(const __half2*)&h)) : __habs2(*(const __half2*)&h);
        }
#pragma unroll
        for (int r = 0; r < 3; r++) stsm4(ma + r * 4096, q[3 * r], q[3 * r + 1], q[3 * r + 2], r < 2 ? v[c][r].w : *(const uint32_t*)&hm);
        const bool done = __all_sync(0xffffffffu, v[c][0].w == 0x5000u && v[c][1].w == 0x5000u && v[c][2].w == 0x5000u) || n > SPIN_LIMIT;
        asm volatile("{\n.reg .pred p;\nsetp.ne.u32 p, %0, 0;\n@p bar.arrive %1, 256;\n}" :: "r"((int)done), "r"(1 + c) : "memory");
        return done;
      };
      int n = 0;
      wait_until(dl);
      PROF(10);
#pragma unroll 1
      do {
        load(0);
        load(1);
        asm volatile("{\n.reg .pred p;\nsetp.eq.u32 p, %0, 0;\n@p bar.sync 13, 384;\n}" :: "r"(n) : "memory");
      } while (!decode(0, n++));
      PROF(11);
#pragma unroll 1
      while (!decode(1, n++)) load(1);
      bar_arrive(9, 256);
      PROF(12);
    }
    PROF(13);
    if (++s == NSEG - 1) break;
    }
  }
#undef fence_reg
  if (RANK < 2) bar_arrive(4, 256);
  bar_sync(0, 384);
  cluster_sync();
}

__global__ void __cluster_dims__(3, 1, 1) __launch_bounds__(384, 1)
rec_kernel(const __grid_constant__ RMaps tm, const bf16* __restrict__ x, const bf16* __restrict__ mem0) {
  extern __shared__ __align__(1024) unsigned char smem_raw[];
  const uint32_t sb = smem_u32(smem_raw);
  const int tid = threadIdx.x, lane = tid & 31;
  const int wg = __shfl_sync(0xffffffffu, tid >> 7, 0);
  const int w = __shfl_sync(0xffffffffu, (tid >> 5) & 3, 0);
  uint32_t rank; asm("mov.u32 %0, %%cluster_ctarank;" : "=r"(rank));
  STAMP(0);
  asm volatile("griddepcontrol.launch_dependents;" ::: "memory");
    if (tid == 0) {
      const int h = blockIdx.x / 3;
      mbar_init(sb + MB_XS, 1);
      for (int i = 0; i < 3; i++) { mbar_init(sb + MB_W + 8 * i, 1); mbar_init(sb + MB_X + 8 * i, 1); }
      mbar_init(sb + MB_WO3, 1);
      fence_async();
      load_w(sb, tm, rank, 0);
      mbar_expect(sb + MB_X, XT);
      tma_load3(sb + SM_X, &tm.x, 0, sb + MB_X);
      mbar_expect(sb + MB_WO3, 32768 + 8 * DM * 2);
      tma_load(sb + SM_WOST, &tm.wo, rank * 192 + 64, h * DH, sb + MB_WO3);
      tma_load(sb + SM_WO3, &tm.wo, rank * 192 + 128, h * DH, sb + MB_WO3);
      bulk_load(sb + SM_M0, mem0, 8 * DM * 2, sb + MB_WO3);
      load_w(sb, tm, rank, 1);
      load_w(sb, tm, rank, 2);
      mbar_init(sb + MB_WO, 1);
      mbar_init(sb + MB_S, rank < 2 ? 5 : 6);
      mbar_init(sb + MB_F, 1);
      mbar_init(sb + MB_VX, 1); mbar_init(sb + MB_VX + 8, 1);
      asm volatile("fence.mbarrier_init.release.cluster;" ::: "memory");
      fence_async();
      mbar_expect(sb + MB_X + 8, XT); mbar_expect(sb + MB_X + 16, XT);
      mbar_expect(sb + MB_WO, 16384); mbar_expect(sb + MB_XS, XT);
      mbar_expect(sb + MB_S, rank < 2 ? 640 + 2048 : 1280);
      mbar_expect(sb + MB_VX, 8192); mbar_expect(sb + MB_VX + 8, 8192);
    }
  __syncwarp();
  if (wg < 2) {
    asm volatile("setmaxnreg.inc.sync.aligned.u32 192;");
    __syncwarp();
    QSTAMP(0);
    if (tid < 32) bar_arrive(0, 160);
    QSTAMP(1);
    proj_role(sb, tm, x, rank, wg, w, lane);
  } else {
    asm volatile("setmaxnreg.dec.sync.aligned.u32 120;");
    attn_role(sb, smem_raw, tm, rank, x, mem0, w, lane);
  }
}

constexpr int NAUX = 36;
constexpr int A_ST = 6, A_STAGE = 8192 + 12288, A_W8 = A_ST * A_STAGE, A_EXC = A_W8 + A_ST * 1536, A_ROWS = 57;
constexpr int A_IN = A_EXC + 8 * 2304, A_INB = 3 * SEGB, A_OST = A_IN + 2 * A_INB, A_P = A_OST + 8192, A_G = A_P + 3072;
constexpr int A_BAR = A_G + 1024;
constexpr int A_XT = A_BAR + 1024, A_XW = A_XT;
constexpr int A_TOTAL = A_XT + 4096;
static_assert(A_IN % 1024 == 0 && A_XT % 1024 == 0 && A_IN >= 4 * XT && A_IN + 64 * DM * 2 <= A_BAR && A_TOTAL <= 232448, "side kernel shared memory");
struct AMaps { CUtensorMap x, wa, wa8, o, o3, o16, wob, woa, woa16; const unsigned char* red; uint32_t poll; };

DI void wgmma_n192_ss_nt(float* d, uint64_t da, uint64_t db, int acc) {
  asm volatile("{\n.reg .pred p;\nsetp.ne.b32 p, %98, 0;\n"
               "wgmma.mma_async.sync.aligned.m64n192k16.f32.bf16.bf16 {"
               "%0,%1,%2,%3,%4,%5,%6,%7,%8,%9,%10,%11,%12,%13,%14,%15,%16,%17,%18,%19,%20,%21,%22,%23,%24,%25,%26,%27,%28,%29,%30,%31,"
               "%32,%33,%34,%35,%36,%37,%38,%39,%40,%41,%42,%43,%44,%45,%46,%47,%48,%49,%50,%51,%52,%53,%54,%55,%56,%57,%58,%59,%60,%61,%62,%63,"
               "%64,%65,%66,%67,%68,%69,%70,%71,%72,%73,%74,%75,%76,%77,%78,%79,%80,%81,%82,%83,%84,%85,%86,%87,%88,%89,%90,%91,%92,%93,%94,%95"
               "}, %96, %97, p, 1, 1, 0, 1;\n}\n"
               : ACC8(d, 0), ACC8(d, 8), ACC8(d, 16), ACC8(d, 24), ACC8(d, 32), ACC8(d, 40), ACC8(d, 48), ACC8(d, 56),
                 ACC8(d, 64), ACC8(d, 72), ACC8(d, 80), ACC8(d, 88) : "l"(da), "l"(db), "r"(acc));
}
DI void wgmma_n24_ss_nt(float* d, uint64_t da, uint64_t db, int acc) {
  asm volatile("{\n.reg .pred p;\nsetp.ne.b32 p, %14, 0;\n"
               "wgmma.mma_async.sync.aligned.m64n24k16.f32.bf16.bf16 {%0,%1,%2,%3,%4,%5,%6,%7,%8,%9,%10,%11}, %12, %13, p, 1, 1, 0, 1;\n}\n"
               : ACC8(d, 0), "+f"(d[8]), "+f"(d[9]), "+f"(d[10]), "+f"(d[11]) : "l"(da), "l"(db), "r"(acc));
}
DI void tma_load3d(uint32_t dst, const CUtensorMap* m, int c0, int c1, int c2, uint32_t mb) {
  asm volatile("cp.async.bulk.tensor.3d.shared::cluster.global.mbarrier::complete_tx::bytes [%0], [%1, {%3, %4, %5}], [%2];"
               :: "r"(dst), "l"(m), "r"(mb), "r"(c0), "r"(c1), "r"(c2) : "memory");
}
DI uint32_t trans8(uint32_t x) { uint32_t r; asm("movmatrix.sync.aligned.m8n8.trans.b16 %0, %1;" : "=r"(r) : "r"(x)); return r; }
DI void wgmma_n40_ss(float* d, uint64_t da, uint64_t db, int acc) {
  asm volatile("{\n.reg .pred p;\nsetp.ne.b32 p, %22, 0;\n"
               "wgmma.mma_async.sync.aligned.m64n40k16.f32.bf16.bf16 {%0,%1,%2,%3,%4,%5,%6,%7,%8,%9,%10,%11,%12,%13,%14,%15,%16,%17,%18,%19}, "
               "%20, %21, p, 1, 1, 1, 1;\n}\n"
               : ACC8(d, 0), ACC8(d, 8), "+f"(d[16]), "+f"(d[17]), "+f"(d[18]), "+f"(d[19]) : "l"(da), "l"(db), "r"(acc));
}
template <int ST> DI void ldg8x64(uint32_t* m, const void* p) {
  asm volatile("ld.relaxed.gpu.global.v2.b32 {%0,%1}, [%16];\nld.relaxed.gpu.global.v2.b32 {%2,%3}, [%16 + %17];\n"
               "ld.relaxed.gpu.global.v2.b32 {%4,%5}, [%16 + %18];\nld.relaxed.gpu.global.v2.b32 {%6,%7}, [%16 + %19];\n"
               "ld.relaxed.gpu.global.v2.b32 {%8,%9}, [%16 + %20];\nld.relaxed.gpu.global.v2.b32 {%10,%11}, [%16 + %21];\n"
               "ld.relaxed.gpu.global.v2.b32 {%12,%13}, [%16 + %22];\nld.relaxed.gpu.global.v2.b32 {%14,%15}, [%16 + %23];"
               : "=r"(m[0]), "=r"(m[1]), "=r"(m[2]), "=r"(m[3]), "=r"(m[4]), "=r"(m[5]), "=r"(m[6]), "=r"(m[7]),
                 "=r"(m[8]), "=r"(m[9]), "=r"(m[10]), "=r"(m[11]), "=r"(m[12]), "=r"(m[13]), "=r"(m[14]), "=r"(m[15])
               : "l"(p), "n"(ST), "n"(2 * ST), "n"(3 * ST), "n"(4 * ST), "n"(5 * ST), "n"(6 * ST), "n"(7 * ST) : "memory");
}
template <int ST> DI void ldg4x128(uint32_t* m, const void* p) {
  asm volatile("ld.relaxed.gpu.global.v4.b32 {%0,%1,%2,%3}, [%16];\nld.relaxed.gpu.global.v4.b32 {%4,%5,%6,%7}, [%16 + %17];\n"
               "ld.relaxed.gpu.global.v4.b32 {%8,%9,%10,%11}, [%16 + %18];\nld.relaxed.gpu.global.v4.b32 {%12,%13,%14,%15}, [%16 + %19];"
               : "=r"(m[0]), "=r"(m[1]), "=r"(m[2]), "=r"(m[3]), "=r"(m[4]), "=r"(m[5]), "=r"(m[6]), "=r"(m[7]),
                 "=r"(m[8]), "=r"(m[9]), "=r"(m[10]), "=r"(m[11]), "=r"(m[12]), "=r"(m[13]), "=r"(m[14]), "=r"(m[15])
               : "l"(p), "n"(ST), "n"(2 * ST), "n"(3 * ST) : "memory");
}
template <int N, int ST> DI bool stale(const uint32_t* m, uint32_t tag) {
  uint32_t x = m[0] ^ tag;
#pragma unroll
  for (int i = 1; i < N; i++) asm("lop3.b32 %0, %0, %1, %2, 0xf6;" : "+r"(x) : "r"(m[i * ST]), "r"(tag));
  return __any_sync(0xffffffffu, x & 1);
}
DI int wait_flags(const unsigned* p, bool active, unsigned base, int seg) {
  int n = 0, m;
  while (true) {
    m = __reduce_min_sync(0xffffffffu, active ? (int)(ldg_acquire32(p) - base) : NSEG);
    if (m > seg || ++n > SPIN_LIMIT) break;
    __nanosleep((YP & 32) ? 400 : 40);
  }
  return max(m, seg + 1);
}
DI void wait_count(const unsigned* p, unsigned target) {
  int n = 0;
  unsigned v;
  while (true) {
    asm volatile("ld.acquire.gpu.global.b32 %0, [%1];" : "=r"(v) : "l"(p) : "memory");
    if ((int)(v - target) >= 0 || ++n > SPIN_LIMIT) break;
    __nanosleep(64);
  }
}
#define PACE_NEXT 1024
#define PD1 0
#define PD2 0
#define PING 60
DI bool tick_wait(uint32_t pace, int step) {
  const int n = lds32v(pace);
  if (n <= step) mbar_wait(pace + 8, n & 1);
  return n <= step;
}
DI void sleep_until(uint32_t t) {
  for (int n = 0; n < 64; n++) {
    const int r = t - gtime();
    if (r <= 0) break;
    __nanosleep(r >> 1);
  }
}
DI void poll_delay(uint32_t pace, int step, int t) {
  uint32_t n, d;
  asm volatile("ld.volatile.shared.v2.b32 {%0,%1}, [%2];" : "=r"(n), "=r"(d) : "r"(pace) : "memory");
  if (n && (int)n <= step) sleep_until(d + t);
}
DI void aux_barrier(int i, unsigned epoch) {
  asm volatile("fence.proxy.async;" ::: "memory");
  asm volatile("red.release.gpu.global.add.u32 [%0], 1;" :: "l"(&g_abar[i * 32]) : "memory");
  wait_count(&g_abar[i * 32], NAUX * (epoch + 1));
  asm volatile("fence.proxy.async;" ::: "memory");
}

__global__ void __launch_bounds__(512, 1)
aux_kernel(const __grid_constant__ AMaps tm, const bf16* __restrict__ x, const bf16* __restrict__ gate_w, bf16* __restrict__ out) {
  extern __shared__ __align__(1024) unsigned char smem_raw[];
  const uint32_t sb = smem_u32(smem_raw);
  const uint32_t full1 = sb + A_BAR, empty1 = full1 + 8 * A_ST, fullw = empty1 + 8 * A_ST, full3 = fullw + 16, empty3 = full3 + 32,
                 fulla = empty3 + 32, emptya = fulla + 32, fullg = emptya + 16, pace = fullg + 8;
  const int tid = threadIdx.x, lane = tid & 31, cta = blockIdx.x;
  const int wg = __shfl_sync(0xffffffffu, tid >> 7, 0), w = __shfl_sync(0xffffffffu, (tid >> 5) & 3, 0);
  ASTAMP(14);
  const unsigned epoch = *(volatile unsigned*)&g_epoch2;
  if (tid == 0) {
    for (int i = 0; i < A_ST; i++) { mbar_init(full1 + 8 * i, 1); mbar_init(empty1 + 8 * i, 8); }
    mbar_init(fullw, 1); mbar_init(fullw + 8, 1); mbar_init(fullg, 1);
    for (int i = 0; i < 2; i++) { mbar_init(fulla + 16 * i, 2); mbar_init(fulla + 16 * i + 8, 1); mbar_init(emptya + 8 * i, 4); }
    sts64(pace, 0, 0); mbar_init(pace + 8, 1); sts32(pace + 16, 0); sts64(pace + 24, 65536, 0xffff0000u);
    for (int i = 0; i < 4; i++) { mbar_init(full3 + 8 * i, 1); mbar_init(empty3 + 8 * i, cta < NH ? 8 : 4); }
    fence_async();
  }
  auto load_a = [&](int st, int k, int col) {
    mbar_expect(full1 + 8 * st, A_STAGE + 1536);
    tma_load3d(sb + st * A_STAGE, &tm.x, k, (cta >> 1) * A_ROWS - 7, 0, full1 + 8 * st);
    tma_load3d(sb + st * A_STAGE + 8192, &tm.wa, col, k, 0, full1 + 8 * st);
    tma_load3d(sb + A_W8 + st * 1536, &tm.wa8, col + 64, k, 0, full1 + 8 * st);
  };
  __syncthreads();
  ASTAMP(0);
  const bool wide = cta < NH;
  auto p3_ks = [&](int g) { return wide ? cta >> 2 : 2 * (cta - NH) + g; };
  auto p3_mt = [&](int g) { return wide ? 2 * (cta & 3) + g : 8; };
  const unsigned fbase = epoch * NSEG;
  if (wg == 3) {
    asm volatile("setmaxnreg.dec.sync.aligned.u32 48;");
    if (w == 1 && cta < NH) {
#pragma unroll 1
      for (int seg = 0; seg < ((XP & 2048) ? 0 : NSEG); seg++) {
        bar_arrive(5, 160);
        if (seg > 0 && lane == 0) {
          asm volatile("cp.async.bulk.wait_group 0;" ::: "memory");
          stg_relaxed32(&g_oflag[cta * 32], fbase + seg);
        }
        if (lane < 3) stg_relaxed32(&g_cflag[(cta * 3 + lane) * 32], fbase + seg);
        __syncwarp();
        bar_sync(4, 160);
        if (QM & 16) tick_wait(pace, seg + 1);
        if (lane == 0) {
          fence_async();
          if (!(YP & 2)) {
          tma_store(&tm.o, sb + A_OST, cta * DH, seg * 32);
          tma_store(&tm.o, sb + A_OST + 4096, cta * DH + 64, seg * 32);
          }
          asm volatile("cp.async.bulk.commit_group;" ::: "memory");
          asm volatile("cp.async.bulk.wait_group.read 0;" ::: "memory");
        }
        __syncwarp();
      }
      if (lane == 0) {
        asm volatile("cp.async.bulk.wait_group 0;" ::: "memory");
        { const int seg = NSEG - 1; TSTAMP(2); }
        stg_relaxed32(&g_oflag[cta * 32], fbase + NSEG);
      }
    }
    if (w == 2 && cta < NH) {
      const uint32_t ktag = (epoch + 1) & 1, ma = sb + A_IN + 8192 + lane * 16;
      int avail = 0;
      int own = 0;
      bar_sync(10, 64);
#pragma unroll 1
      for (int seg = 0; seg < ((XP & 2048) ? 0 : NSEG); seg++) {
        if (avail <= seg) {
          if (PD1) poll_delay(pace, seg, PD1);
          int n = 0;
          while (true) {
            asm volatile("ld.acquire.gpu.global.v2.b32 {%0,%1}, [%2];" : "=r"(avail), "=r"(own) : "l"(&g_sflag[(cta * 3 + min(lane, 2)) * 4]) : "memory");
            avail = __reduce_min_sync(0xffffffffu, (int)(avail - fbase));
            if (avail > seg || ++n > SPIN_LIMIT) break;
            __nanosleep(40);
          }
        }
        if (QM & 8) tick_wait(pace, seg);
        TSTAMP(0);
        const unsigned char* km = g_km + (size_t)(seg * NH + cta) * 4096 + lane * 8;
        uint32_t m[16];
        const float g = __ldcg(&g_gate[seg * 32 + lane]);
        ldg8x64<256>(m, km);
        const uint32_t b = seg & 1, full = fulla + 16 * b, mb = ma + b * A_INB;
        mbar_wait(emptya + 8 * b, (~seg >> 1) & 1);
        if (lane < 2) mbar_expect(full + 8 * lane, (YP & 8) ? 0 : 16384 >> lane);
        __syncwarp();
        const int slot = seg < own ? seg & 7 : seg;
        if (lane < 3 && !(YP & 8)) bulk_load(sb + A_IN + b * A_INB + lane * SEGB, g_seg + ((size_t)slot * 96 + cta * 3 + lane) * 8192, 8192, full + (lane & 2) * 4);
        int n = 0;
#pragma unroll 1
        while (stale<8, 2>(m, ktag) && ++n < SPIN_LIMIT) { if (seg < NSEG - 1) __nanosleep(200); ldg8x64<256>(m, km); }
        TSTAMP(1);
#pragma unroll
        for (int i = 0; i < 4; i++) stsm4(mb + (i >> 1) * SEGB + (i & 1) * 512, m[4 * i], m[4 * i + 1], m[4 * i + 2], m[4 * i + 3]);
        sts32(sb + A_G + b * 128 + lane * 4, __float_as_uint(1.f - g));
        fence_async();
        __syncwarp();
        if (lane == 0) mbar_arrive(full);
      }
    }
    if (w == 3 && QM) {
      const unsigned char* const hp = tm.red + HINT_OFF + 65536 + (cta & 1) * 4096 + min(lane, 23) * 4;
      uint32_t d = 0;
      int s = 0, n = 0;
#pragma unroll 1
      while (s < NSEG - 1) {
        const uint32_t h = ldg_relaxed32(hp + RED_SLOT(s)), t = (gtime() - 1984) & ~31u, late = latest_hint(h, t, s);
        if (late < 64) {
          d = t + late * 32 + tm.poll;
          sleep_until(d);
          s++; n = 0;
          if (lane == 0) { mbar_arrive(pace + 8); sts64(pace, s < NSEG - 1 ? s : 2 * NSEG, d); }
          sleep_until(d + PACE_NEXT);
        } else {
          if (++n > (s ? 16 : 256) || lds32v(pace + 16)) break;
          if (!s) __nanosleep(100);
        }
      }
      if (s < NSEG - 1 && lane == 0) { mbar_arrive(pace + 8); sts64(pace, 2 * NSEG, d); }
    }
    if (w != 0) return;
    const bool lead = lane == 0;
#pragma unroll 1
    for (int it = 0, st = 0, ph = 1, k = 0, col = (cta & 1) * (DM / 2); it < ((XP & 256) ? 0 : 72); it++) {
      mbar_wait(empty1 + 8 * st, ph);
      if (elect_one()) load_a(st, k, col);
      __syncwarp();
      if (++st == A_ST) { st = 0; ph ^= 1; }
      k += 32;
      if (k == DM) { k = 0; col += 72; }
    }
    auto load_wo = [&](uint32_t dst, int g, int kb, uint32_t mb) {
      if (kb < 64) tma_load(dst, &tm.wob, p3_mt(g) * 64, kb * 64, mb);
      else tma_load(dst, &tm.woa, p3_mt(g) * 64, (kb - 64) * 64, mb);
    };
    if (lead) mbar_expect(fullw, 16 * 8192);
#pragma unroll 1
    for (int st = 0; st < A_ST; st++) {
      if (!(XP & 256)) mbar_wait(empty1 + 8 * st, 1);
      if (lane < 16 && min(((lane + 1) * 8192 - 1) / A_STAGE, A_ST - 1) == st) load_wo(sb + lane * 8192, lane >> 3, p3_ks(lane >> 3) * 9 + (lane & 7), fullw);
      __syncwarp();
    }
    __syncwarp(); bar_sync(6, 288);
    if (lead) mbar_expect(fullw + 8, 2 * 8192 + (p3_ks(0) >= 4 ? 4096 : 0));
    __syncwarp();
    if (lane < 2) {
      load_wo(sb + (16 + lane) * 8192, lane, p3_ks(lane) * 9 + 8, fullw + 8);
      if (p3_ks(0) >= 4) tma_load(sb + A_XW + lane * 2048, &tm.woa16, p3_mt(lane) * 64, 448 + p3_ks(lane) * 16, fullw + 8);
    }
    __syncwarp();
    if (lead) aux_barrier(1, epoch);
    __syncwarp(); bar_sync(6, 288);
    {
      int avail = 0, sl = 0, ph = 1;
      const int h = (9 * p3_ks(0) >> 1) + lane;
#pragma unroll 1
      for (int seg = 0; seg < ((XP & 2048) ? 0 : NSEG); seg++) {
        if (PD2 && avail <= seg) poll_delay(pace, seg + 2, PD2);
        if (avail <= seg) avail = wait_flags(&g_oflag[min(h, NH - 1) * 32], lane < (wide ? 5 : 9), fbase, seg);
        SSTAMP(seg, 4);
        for (int g = 0; g < (wide ? 1 : 2); g++) {
          const int ks = p3_ks(g);
          mbar_wait(empty3 + 8 * sl, ph);
          if ((QM & 4) && tick_wait(pace, seg + (QM >> 4 & 1) + 1)) __nanosleep(100);
          if (YP & 4) { if (lead) mbar_arrive(full3 + 8 * sl); }
          else if (elect_one()) {
            mbar_expect(full3 + 8 * sl, XT + (ks >= 4 ? 1024 : 0));
            tma_load3d(sb + sl * XT, &tm.o3, 0, seg * 32, ks * 9, full3 + 8 * sl);
            if (ks >= 4) tma_load(sb + A_XT + sl * 1024, &tm.o16, 72 * 64 - 64 + ks * 16, seg * 32, full3 + 8 * sl);
          }
          __syncwarp();
          if (++sl == (wide ? 3 : 4)) { sl = 0; ph ^= 1; }
        }
      }
    }
    sts32(pace + 16, 1);
    __syncwarp(); bar_sync(6, 288);
    asm volatile("griddepcontrol.wait;" ::: "memory");
  } else if (wg == 2) {
    asm volatile("setmaxnreg.dec.sync.aligned.u32 64;");
    if (cta < NH) {
      if (tid == 256) { mbar_expect(fullg, 64 * DM * 2); bulk_load(sb + A_IN, x + cta * 64 * DM, 64 * DM * 2, fullg); }
      uint32_t gw[9];
#pragma unroll
      for (int j = 0; j < 9; j++) gw[j] = ((const uint32_t*)gate_w)[j * 32 + lane];
      mbar_wait(fullg, 0);
      float mine = 0.f;
#pragma unroll 4
      for (int u = 0; u < 16; u++) {
        float d0 = 0.f, d1 = 0.f;
#pragma unroll
        for (int j = 0; j < 9; j++) {
          const uint32_t a = lds32(sb + A_IN + (w * 16 + u) * (DM * 2) + j * 128 + lane * 4);
          d0 = fmaf(bf_lo(a), bf_lo(gw[j]), d0); d1 = fmaf(bf_hi(a), bf_hi(gw[j]), d1);
        }
        d0 = warp_sum(d0 + d1);
        if (lane == u) mine = d0;
      }
      if (lane < 16) g_gate[cta * 64 + w * 16 + lane] = 1.f / (1.f + __expf(-mine));
      fence_async();
    }
    bar_sync(3, 128);
    if (tid == 256) { aux_barrier(0, epoch); if (cta == 0) *(volatile unsigned*)&g_epoch2 = epoch + 1; }
    __syncwarp();
    bar_sync(3, 128);
    if (w == 0) bar_arrive(8, 288);
    if (w == 1 && cta < NH) bar_arrive(10, 64);
    if (cta < NH) {
      CDECL;
#pragma unroll 1
      for (int seg = 0; seg < ((XP & 2048) ? 0 : NSEG); seg++) {
        CSTAMP(0);
        const uint32_t in = sb + A_IN + (seg & 1) * A_INB;
        const uint64_t qd = make_desc(in, 128, 1024, 0);
        mbar_wait(fulla + 16 * (seg & 1), (seg >> 1) & 1);
        CSTAMP(3);
        SSTAMP(seg, 0);
        float d[2][16];
        {
          float a[20];
          uint32_t vm[16];
          const unsigned char* vp = g_km + (size_t)(seg * NH + cta) * 4096 + 2048 + lane * 16;
          if (w == 3) ldg4x128<512>(vm, vp);
          WG_FENCE();
#pragma unroll
          for (int k = 0; k < ((YP & 16) ? 1 : 8); k++) wgmma_n40_ss(a, qd + ((k >> 2) * SEGB + (k & 3) * 256 >> 4), qd + ((k >> 2) * SEGB + (k & 3) * 256 + 4096 >> 4), k > 0);
          const uint32_t ga = sb + A_G + (seg & 1) * 128 + (w & 1) * 64 + (lane >> 2) * 4;
          const float f0 = __uint_as_float(lds32(ga)), f1 = __uint_as_float(lds32(ga + 32));
          WG_COMMIT();
          WG_WAIT(0);
          CSTAMP(5);
          SSTAMP(seg, 1);
          if (w < 2) {
            const int lim = w * 16 + (lane >> 2) - 2 * (lane & 3);
            float m0 = -3.0e38f, m1 = -3.0e38f;
#pragma unroll
            for (int i = 0; i < 20; i++) {
              a[i] *= SM_SCALE * LOG2E;
              if (i < 16 && (i >> 2) * 8 + (i & 1) - (i & 2) * 4 > lim) a[i] = -1.0e9f * LOG2E;
              if (i & 2) m1 = fmaxf(m1, a[i]); else m0 = fmaxf(m0, a[i]);
            }
#pragma unroll
            for (int o = 1; o < 4; o <<= 1) { m0 = fmaxf(m0, __shfl_xor_sync(0xffffffffu, m0, o)); m1 = fmaxf(m1, __shfl_xor_sync(0xffffffffu, m1, o)); }
            float s0 = 0.f, s1 = 0.f;
#pragma unroll
            for (int i = 0; i < 20; i++) { a[i] = ex2(a[i] - (i & 2 ? m1 : m0)); if (i & 2) s1 += a[i]; else s0 += a[i]; }
#pragma unroll
            for (int o = 1; o < 4; o <<= 1) { s0 += __shfl_xor_sync(0xffffffffu, s0, o); s1 += __shfl_xor_sync(0xffffffffu, s1, o); }
            s0 = f0 * rcp(s0); s1 = f1 * rcp(s1);
            uint32_t p[10];
#pragma unroll
            for (int i = 0; i < 10; i++) p[i] = pack_bf16(a[2 * i] * (i & 1 ? s1 : s0), a[2 * i + 1] * (i & 1 ? s1 : s0));
            const uint32_t pa = sb + A_P + (2 * w + ((lane >> 3) & 1)) * 768 + (lane >> 4) * 128 + (lane & 7) * 16;
            stsm4t(pa, p[0], p[1], p[2], p[3]); stsm4t(pa + 256, p[4], p[5], p[6], p[7]); stsm4t(pa + 512, p[8], p[9], 0, 0);
            CSTAMP(6);
            fence_async();
            CSTAMP(7);
          } else if (w == 3) {
            int n = 0;
#pragma unroll 1
            while (stale<4, 4>(vm, (epoch + 1) & 1) && ++n < SPIN_LIMIT) ldg4x128<512>(vm, vp);
#pragma unroll
            for (int i = 0; i < 4; i++) stsm4(in + 2 * SEGB + 8192 + (lane >> 4) * 1024 + (lane & 15) * 16 + i * 256, vm[4 * i], vm[4 * i + 1], vm[4 * i + 2], vm[4 * i + 3]);
            fence_async();
            mbar_wait(fulla + 16 * (seg & 1) + 8, (seg >> 1) & 1);
          }
        }
        CSTAMP(8);

        bar_sync(5, 160);
        CSTAMP(10);
        SSTAMP(seg, 2);
        const uint64_t pd = make_desc(sb + A_P, 128, 768, 0), vd = make_desc(in + 2 * SEGB, 128, 512, 0), md = make_desc(in + 2 * SEGB + 8192, 0, 128, 0);
        WG_FENCE();
#pragma unroll
        for (int i = 0; i < 2; i++) {
          wgmma_n32_ss<0>(d[i], vd + i * 256, pd, 0);
          wgmma_n32_ss<0>(d[i], vd + i * 256 + 16, pd + 16, 1);
          wgmma_n32_ss<0>(d[i], md + i * 64, pd + 32, 1);
        }
        WG_COMMIT();
        WG_WAIT(0);
        CSTAMP(11);
        if (lane == 0) mbar_arrive(emptya + 8 * (seg & 1));
#pragma unroll
        for (int i = 0; i < 2; i++) {
          const uint32_t oa = sb + A_OST + i * 4096 + ((lane & 7) + ((lane >> 4) << 3)) * 128 + (((2 * w + ((lane >> 3) & 1)) ^ (lane & 7)) << 4);
          stsm4t(oa, pack_bf16(d[i][0], d[i][1]), pack_bf16(d[i][2], d[i][3]), pack_bf16(d[i][4], d[i][5]), pack_bf16(d[i][6], d[i][7]));
          stsm4t(oa + 2048, pack_bf16(d[i][8], d[i][9]), pack_bf16(d[i][10], d[i][11]), pack_bf16(d[i][12], d[i][13]), pack_bf16(d[i][14], d[i][15]));
        }
        CSTAMP(12);
        bar_sync(4, 160);
        SSTAMP(seg, 3);
      }
      CDUMP;
    }
  } else {
    asm volatile("setmaxnreg.inc.sync.aligned.u32 200;");
    {
      const int g = lane >> 2, t = lane & 3, r0 = (cta >> 1) * A_ROWS - 7 + w * 16;
      const uint32_t prev = (2 * t > g ? 0xffffu : 0u) | (2 * t + 1 > g ? 0xffff0000u : 0u);
      const int k0 = r0 + 2 * t - (2 * t > g ? 8 : 0), k1 = r0 + 2 * t + 1 - (2 * t + 1 > g ? 8 : 0);
      const uint32_t slot = sb + A_EXC + (wg * 4 + w) * 2304;
      float gl = 0.f, gh = 0.f;
      int st = 0, ph = 0;
#pragma unroll 1
      for (int p = 0; p < ((XP & 256) ? 0 : 4); p++) {
        float big[96], sml[12];
        if (p == 3 && tid < 18) {
          const int kb = p3_ks(tid >= 9) * 9 + tid % 9;
          tma_prefetch(kb < 64 ? &tm.wob : &tm.woa, p3_mt(tid >= 9) * 64, (kb & 63) * 64);
        }
        __syncwarp();
#pragma unroll
        for (int i = 0; i < 96; i++) big[i] = 0.f;
#pragma unroll
        for (int i = 0; i < 12; i++) sml[i] = 0.f;
#pragma unroll 1
        for (int k = 0; k < 18; k++) {
          mbar_wait(full1 + 8 * st, ph);
          const uint64_t da = make_desc(sb + st * A_STAGE + wg * 4096, 16, 512, 2);
          const uint64_t db = make_desc(sb + st * A_STAGE + 8192, 4096, 1024, 1), dc = make_desc(sb + A_W8 + st * 1536, 128, 512, 0);
          WG_FENCE();
#pragma unroll
          for (int j = 0; j < 2; j++) { wgmma_n192_ss_nt(big, da + j * 2, db + j * 128, 1); wgmma_n24_ss_nt(sml, da + j * 2, dc + j * 16, 1); }
          WG_COMMIT();
          WG_WAIT(1);
          if (k > 0 && lane == 0) mbar_arrive(empty1 + 8 * (st ? st - 1 : A_ST - 1));
          if (++st == A_ST) { st = 0; ph ^= 1; }
        }
        WG_WAIT(0);
        ASTAMP(16 + p + wg * 16);
        if (lane == 0) mbar_arrive(empty1 + 8 * (st ? st - 1 : A_ST - 1));
        uint32_t f[3][9][2];
#pragma unroll
        for (int c = 0; c < 3; c++)
#pragma unroll
          for (int j = 0; j < 9; j++)
#pragma unroll
            for (int i = 0; i < 2; i++) {
              const float* a = j < 8 ? &big[(c * 8 + j) * 4 + 2 * i] : &sml[c * 4 + 2 * i];
              f[c][j][i] = c < 2 ? pack_bf16(a[0], a[1]) : trans8(pack_bf16(a[0], a[1]));
            }
        if (p == 0) {
          bar_sync(8, 288);
          gl = __ldcg(&g_gate[min(max(r0 + g, 0), S_LEN / 2 - 1) * 2 + wg]); gh = __ldcg(&g_gate[min(max(r0 + g + 8, 0), S_LEN / 2 - 1) * 2 + wg]);
        }
        asm volatile("cp.async.bulk.wait_group.read 0;" ::: "memory");
        __syncwarp();
#pragma unroll
        for (int j = 0; j < 8; j += 2) sts128(slot + j * 256 + lane * 16, f[1][j][1], f[2][j][1], f[1][j + 1][1], f[2][j + 1][1]);
        sts64(slot + 2048 + lane * 8, f[1][8][1], f[2][8][1]);
        bar_sync(1 + wg, 128);
        ASTAMP(24 + p + wg * 16);
        uint32_t pv[9][2];
#pragma unroll
        for (int j = 0; j < 9; j++) pv[j][0] = pv[j][1] = 0;
        if (w) {
#pragma unroll
          for (int j = 0; j < 8; j += 2) lds128(slot - 2304 + j * 256 + lane * 16, pv[j]);
          lds64(slot - 256 + lane * 8, pv[8][0], pv[8][1]);
        }
        float a[4][4], m[4][2];
#pragma unroll
        for (int h = 0; h < 4; h++) {
          const int j = 2 * h;
          const uint32_t qa[4] = {t >= h ? f[0][j][0] : 0, t >= h ? f[0][j][1] : 0, f[0][j + 1][0], f[0][j + 1][1]};
          const uint32_t qb0 = t <= h ? f[0][j + 2][0] : 0, qb1 = t <= h ? f[0][j + 2][1] : 0;
          float s0[4], s1[4], s2[4];
          mma16816z(s1, qa, f[1][j][0], f[1][j + 1][0]); mma16816z(s2, qa, f[1][j][1], f[1][j + 1][1]); mma16816z(s0, qa, pv[j][0], pv[j + 1][0]);
          mma1688(s1, qb0, qb1, f[1][j + 2][0]); mma1688(s2, qb0, qb1, f[1][j + 2][1]); mma1688(s0, qb0, qb1, pv[j + 2][0]);
          a[h][0] = 2 * t > g ? s0[0] : s1[0]; a[h][1] = 2 * t + 1 > g ? s0[1] : s1[1]; a[h][2] = 2 * t > g ? s1[2] : s2[2]; a[h][3] = 2 * t + 1 > g ? s1[3] : s2[3];
        }
#pragma unroll
        for (int h = 0; h < 4; h++) {
#pragma unroll
          for (int i = 0; i < 4; i++) a[h][i] = (i & 1 ? k1 : k0) + (i & 2) * 4 >= 0 ? a[h][i] * (0.23570226039551584f * LOG2E) : -1.0e9f * LOG2E;
          m[h][0] = fmaxf(a[h][0], a[h][1]); m[h][1] = fmaxf(a[h][2], a[h][3]);
        }
#pragma unroll
        for (int x = 1; x < 4; x <<= 1)
#pragma unroll
          for (int i = 0; i < 8; i++) m[i >> 1][i & 1] = fmaxf(m[i >> 1][i & 1], __shfl_xor_sync(0xffffffffu, m[i >> 1][i & 1], x));
#pragma unroll
        for (int h = 0; h < 4; h++) {
#pragma unroll
          for (int i = 0; i < 4; i++) a[h][i] = ex2(a[h][i] - m[h][i >> 1]);
          m[h][0] = a[h][0] + a[h][1]; m[h][1] = a[h][2] + a[h][3];
        }
#pragma unroll
        for (int x = 1; x < 4; x <<= 1)
#pragma unroll
          for (int i = 0; i < 8; i++) m[i >> 1][i & 1] += __shfl_xor_sync(0xffffffffu, m[i >> 1][i & 1], x);
        uint32_t o[9][2];
#pragma unroll
        for (int h = 0; h < 4; h++) {
          const int j = 2 * h;
          const float z0 = gl * rcp(m[h][0]), z1 = gh * rcp(m[h][1]);
          const uint32_t pl = pack_bf16(a[h][0] * z0, a[h][1] * z0), pu = pack_bf16(a[h][2] * z1, a[h][3] * z1);
          const uint32_t pa[4] = {pl & prev, 0, pl & ~prev, pu & prev};
          float d[3][4];
#pragma unroll
          for (int i = 0; i < 3; i++) mma16816z(d[i], pa, pv[j + i][1], f[2][j + i][0]);
#pragma unroll
          for (int i = 0; i < 3; i++) mma1688(d[i], 0, pu & ~prev, f[2][j + i][1]);
#pragma unroll
          for (int i = 0; i < 3; i++) {
            const uint32_t d0 = pack_bf16(d[i][0], d[i][1]), d1 = pack_bf16(d[i][2], d[i][3]);
            o[j + i][0] = i == 0 && h > 0 && t < h ? o[j][0] : d0;
            o[j + i][1] = i == 0 && h > 0 && t < h ? o[j][1] : d1;
          }
        }
        ASTAMP(28 + p + wg * 16);
        bar_sync(1 + wg, 128);
        const uint32_t oa = slot + (lane & 15) * 144 + (lane >> 4) * 16;
#pragma unroll
        for (int j = 0; j < 8; j += 2) stsm4(oa + j * 16, o[j][0], o[j][1], o[j + 1][0], o[j + 1][1]);
        asm volatile("stmatrix.sync.aligned.m8n8.x2.shared.b16 [%0], {%1,%2};" :: "r"(oa + 128), "r"(o[8][0]), "r"(o[8][1]) : "memory");
        fence_async();
        __syncwarp();
        if (lane < 16 && w * 16 + lane >= 7 && r0 + lane < S_LEN / 2)
          asm volatile("cp.async.bulk.global.shared::cta.bulk_group [%0], [%1], 144;"
                       :: "l"(g_Ocat + (size_t)((r0 + lane) * 2 + wg) * KCAT + 4096 + (cta & 1) * (DM / 2) + p * 72), "r"(slot + lane * 144) : "memory");
        asm volatile("cp.async.bulk.commit_group;" ::: "memory");
        ASTAMP(20 + p + wg * 16);
      }
      if (XP & 256) bar_sync(8, 288);
      asm volatile("cp.async.bulk.wait_group 0;" ::: "memory");
    }
    ASTAMP(3);
    bar_arrive(6, 288);
    uint32_t wa[37][4];
    mbar_wait(fullw, 0);
    const uint32_t la = sb + ((lane & 7) + ((lane >> 4) << 3)) * 128 + (((2 * w + ((lane >> 3) & 1)) ^ (lane & 7)) << 4);
#pragma unroll
    for (int k = 0; k < 32; k++) ldsm4t(wa[k], la + wg * 65536 + k * 2048);
    mbar_wait(fullw + 8, 0);
#pragma unroll
    for (int k = 32; k < 36; k++) ldsm4t(wa[k], la + wg * 8192 + 65536 + k * 2048);
    ldsm4t(wa[36], la + A_XW + wg * 2048);
    fence_async();
    if (XP & 2048) bar_sync(6, 288); else bar_arrive(6, 288);
    ASTAMP(4);
    const int ks = p3_ks(wg), mt = p3_mt(wg);
    uint32_t v[16];
    auto fetch = [&](int seg) { ldg8x64<1024>(v, g_part + (((seg & 7) * 9 + mt) * 4 + (ks & 3)) * 1024 + (tid & 127)); };
    auto finish = [&](int seg) {
      const uint32_t tagv = (~seg >> 3) & 1;
      int n = 0;
#pragma unroll 1
      while (!(YP & 512) && stale<8, 2>(v, tagv) && ++n < SPIN_LIMIT) {
        if (seg < NSEG - 2) __nanosleep(100);
        fetch(seg);
      }
      float own[4] = {bf_lo(v[0]), bf_hi(v[0]), bf_lo(v[1]), bf_hi(v[1])};
#pragma unroll
      for (int j = 1; j < 8; j++) { own[0] += bf_lo(v[2 * j]); own[1] += bf_hi(v[2 * j]); own[2] += bf_lo(v[2 * j + 1]); own[3] += bf_hi(v[2 * j + 1]); }
      uint32_t p0 = pack_bf16(own[0], own[1]), p1 = pack_bf16(own[2], own[3]);
      asm volatile("movmatrix.sync.aligned.m8n8.trans.b16 %0, %0;" : "+r"(p0));
      asm volatile("movmatrix.sync.aligned.m8n8.trans.b16 %0, %0;" : "+r"(p1));
      const uint32_t r2 = __shfl_xor_sync(0xffffffffu, lane & 2 ? p0 : p1, 2);
      if (lane & 2) p0 = r2; else p1 = r2;
      const uint32_t r1 = __shfl_xor_sync(0xffffffffu, lane & 1 ? p0 : p1, 1);
      if (lane & 1) p0 = r1; else p1 = r1;
      if (!(YP & 256) || p0 == 0x12345678)
        *((uint2*)(out + (size_t)(seg * 32 + (ks & 3) * 8 + (lane >> 2)) * DM + mt * 64 + w * 16) + (lane & 3)) = make_uint2(p0, p1);
      SSTAMP(seg, 7);
    };
    float acc[16];
#pragma unroll
    for (int i = 0; i < 16; i++) acc[i] = 0.f;
    int pend = -1, sl = wide ? 0 : wg, ph = 0;
    if (PING && wg) bar_arrive(1, 256);
    CDECL;
    auto run = [&](auto extra) {
#pragma unroll 1
    for (int seg = 0; seg <= ((XP & 2048) ? -1 : NSEG); seg++) {
      CSTAMP(0);
      const bool fin = pend >= 0 && (seg - pend >= 2 || seg == NSEG);
      if (seg < NSEG) mbar_wait(full3 + 8 * sl, ph);
      if (fin) fetch(pend);
      CSTAMP(1);
      if (seg < NSEG) {
      if (wg) SSTAMP(seg, 5);
      if (seg < PING) bar_sync(1 + wg, 256);
      CSTAMP(7);
      const uint64_t db = make_desc(sb + sl * XT, 16, 1024, 1);
      WG_FENCE();
#pragma unroll
      for (int k = 0; k < ((XP & 1024) ? 1 : 36); k++) wgmma_n32_rs(acc, wa[k][0], wa[k][1], wa[k][2], wa[k][3], db + (k >> 2) * 256 + (k & 3) * 2, k);
      if (decltype(extra)::value) wgmma_n32_rs(acc, wa[36][0], wa[36][1], wa[36][2], wa[36][3], make_desc(sb + A_XT + sl * 1024, 16, 256, 3), 1);
      WG_COMMIT();
      if (seg < PING) bar_arrive(2 - wg, 256);
      CSTAMP(2);
      CSTAMP(3);
      WG_WAIT(0);
      CSTAMP(4);
      if (wg) SSTAMP(seg, 6);
      if (lane == 0) mbar_arrive(empty3 + 8 * sl);
      sl += wide ? 1 : 2;
      if (sl >= (wide ? 3 : 4)) { sl -= wide ? 3 : 4; ph ^= 1; }
      uint2* dst = g_part + (((seg & 7) * 9 + mt) * 32 + ks) * 128 + (tid & 127);
      uint32_t q[8];
#pragma unroll
      for (int j = 0; j < 8; j++) q[j] = j & 1 ? pack_bf16(acc[2 * j], acc[2 * j + 1]) : (pack_bf16(acc[2 * j], acc[2 * j + 1]) & ~1u) | ((~seg >> 3) & 1);
      if (QM & 32) tick_wait(pace, seg + (QM >> 4 & 1) + 2);
      if (!(YP & 1025) || q[0] == 0x12345678)
      asm volatile("st.relaxed.gpu.global.v2.b32 [%0], {%1,%2};\nst.relaxed.gpu.global.v2.b32 [%0 + 8192], {%3,%4};\n"
                   "st.relaxed.gpu.global.v2.b32 [%0 + 16384], {%5,%6};\nst.relaxed.gpu.global.v2.b32 [%0 + 24576], {%7,%8};"
                   :: "l"(dst), "r"(q[0]), "r"(q[1]), "r"(q[2]), "r"(q[3]), "r"(q[4]), "r"(q[5]), "r"(q[6]), "r"(q[7]) : "memory");
      }
      CSTAMP(5);
      if (fin) { finish(pend); pend = -1; }
      CSTAMP(6);
      if ((seg & 1) == ks >> 2 && !(YP & 1)) pend = seg;
      if (wg && (seg & 7) == 6) ASTAMP(5 + (seg >> 3));
    }
    };
    if (ks >= 4) run(BoolC<true>()); else run(BoolC<false>());
    if (PING && !wg) bar_sync(1, 256);
    CDUMP;
    ASTAMP(13);
    bar_sync(6, 288);
  }
}

typedef CUresult (*EncodeFn)(CUtensorMap*, CUtensorMapDataType, cuuint32_t, void*, const cuuint64_t*, const cuuint64_t*,
                             const cuuint32_t*, const cuuint32_t*, CUtensorMapInterleave, CUtensorMapSwizzle,
                             CUtensorMapL2promotion, CUtensorMapFloatOOBfill);
static void make_map(EncodeFn enc, CUtensorMap* m, const void* p, int rows, int cols, int box_rows) {
  cuuint64_t dims[2] = {(cuuint64_t)cols, (cuuint64_t)rows};
  cuuint64_t strides[1] = {(cuuint64_t)cols * 2};
  cuuint32_t box[2] = {64, (cuuint32_t)box_rows};
  cuuint32_t es[2] = {1, 1};
  enc(m, CU_TENSOR_MAP_DATA_TYPE_BFLOAT16, 2, (void*)p, dims, strides, box, es, CU_TENSOR_MAP_INTERLEAVE_NONE,
      CU_TENSOR_MAP_SWIZZLE_128B, CU_TENSOR_MAP_L2_PROMOTION_L2_128B, CU_TENSOR_MAP_FLOAT_OOB_FILL_NONE);
}

constexpr int g_poll = POLL_NS;
extern "C" void kernel_launch(void* const* d_in, const int* in_sizes, int n_in, void* d_out, int out_size) {
  const bf16* x = (const bf16*)d_in[0];
  const bf16* wqkvA = (const bf16*)d_in[1];
  const bf16* woA = (const bf16*)d_in[2];
  const bf16* mem0 = (const bf16*)d_in[4];
  const bf16* Wq = (const bf16*)d_in[5];
  const bf16* Wk = (const bf16*)d_in[6];
  const bf16* Wv = (const bf16*)d_in[7];
  const bf16* Wo = (const bf16*)d_in[8];
  const bf16* gate_w = (const bf16*)d_in[10];
  static EncodeFn enc = nullptr;
  static void *pO = nullptr, *pR = nullptr, *pF = nullptr;
  if (!enc) {
    cudaDriverEntryPointQueryResult qr;
    cudaGetDriverEntryPoint("cuTensorMapEncodeTiled", (void**)&enc, cudaEnableDefault, &qr);
    cudaGetSymbolAddress(&pO, g_Ocat);
    cudaGetSymbolAddress(&pR, g_red_raw);
    cudaGetSymbolAddress(&pF, g_cflag);
    cudaFuncSetAttribute(rec_kernel, cudaFuncAttributeMaxDynamicSharedMemorySize, SM_TOTAL);
    cudaFuncSetAttribute(aux_kernel, cudaFuncAttributeMaxDynamicSharedMemorySize, A_TOTAL);
  }
  RMaps rm;
  rm.poll = g_poll;
  rm.oflag = (const unsigned char*)pF;
  rm.red = (unsigned char*)(((uintptr_t)pR + 262143) & ~(uintptr_t)262143);
  {
    cuuint64_t dims[3] = {64, S_LEN, 9}, strides[2] = {DM * 2, 128};
    cuuint32_t box[3] = {64, 32, 9}, es[3] = {1, 1, 1};
    enc(&rm.x, CU_TENSOR_MAP_DATA_TYPE_BFLOAT16, 3, (void*)x, dims, strides, box, es, CU_TENSOR_MAP_INTERLEAVE_NONE,
        CU_TENSOR_MAP_SWIZZLE_128B, CU_TENSOR_MAP_L2_PROMOTION_L2_128B, CU_TENSOR_MAP_FLOAT_OOB_FILL_NONE);
  }
  make_map(enc, &rm.wq, Wq, DM, 4096, 192);
  make_map(enc, &rm.wk, Wk, DM, 4096, 192);
  make_map(enc, &rm.wv, Wv, DM, 4096, 192);
  make_map(enc, &rm.wo, Wo, 4096, DM, 128);
  AMaps am;
  am.red = rm.red; am.poll = rm.poll;
  {
    cuuint64_t dims[3] = {DM, S_LEN / 2, 2}, strides[2] = {DM * 4, DM * 2};
    cuuint32_t box[3] = {32, 64, 2}, es[3] = {1, 1, 1};
    enc(&am.x, CU_TENSOR_MAP_DATA_TYPE_BFLOAT16, 3, (void*)x, dims, strides, box, es, CU_TENSOR_MAP_INTERLEAVE_NONE,
        CU_TENSOR_MAP_SWIZZLE_64B, CU_TENSOR_MAP_L2_PROMOTION_L2_128B, CU_TENSOR_MAP_FLOAT_OOB_FILL_NONE);
    cuuint64_t wdims[3] = {DM, DM, 3}, wstrides[2] = {DM * 6, DM * 2};
    cuuint32_t wbox[3] = {64, 32, 3}, wbox8[3] = {8, 32, 3};
    enc(&am.wa, CU_TENSOR_MAP_DATA_TYPE_BFLOAT16, 3, (void*)wqkvA, wdims, wstrides, wbox, es, CU_TENSOR_MAP_INTERLEAVE_NONE,
        CU_TENSOR_MAP_SWIZZLE_128B, CU_TENSOR_MAP_L2_PROMOTION_L2_128B, CU_TENSOR_MAP_FLOAT_OOB_FILL_NONE);
    enc(&am.wa8, CU_TENSOR_MAP_DATA_TYPE_BFLOAT16, 3, (void*)wqkvA, wdims, wstrides, wbox8, es, CU_TENSOR_MAP_INTERLEAVE_NONE,
        CU_TENSOR_MAP_SWIZZLE_NONE, CU_TENSOR_MAP_L2_PROMOTION_NONE, CU_TENSOR_MAP_FLOAT_OOB_FILL_NONE);
  }
  {
    cuuint64_t dims[3] = {64, S_LEN, KCAT / 64}, strides[2] = {KCAT * 2, 128};
    cuuint32_t box[3] = {64, 32, 9}, es[3] = {1, 1, 1};
    make_map(enc, &am.o, pO, S_LEN, KCAT, 32);
    enc(&am.o3, CU_TENSOR_MAP_DATA_TYPE_BFLOAT16, 3, pO, dims, strides, box, es, CU_TENSOR_MAP_INTERLEAVE_NONE,
        CU_TENSOR_MAP_SWIZZLE_128B, CU_TENSOR_MAP_L2_PROMOTION_L2_128B, CU_TENSOR_MAP_FLOAT_OOB_FILL_NONE);
  }
  make_map(enc, &am.wob, Wo, 4096, DM, 64);
  make_map(enc, &am.woa, woA, DM, DM, 64);
  make_map(enc, &am.woa16, woA, DM, DM, 16);
  {
    cuuint64_t dims[2] = {KCAT, S_LEN}, strides[1] = {KCAT * 2};
    cuuint32_t box[2] = {16, 32}, es[2] = {1, 1};
    enc(&am.o16, CU_TENSOR_MAP_DATA_TYPE_BFLOAT16, 2, pO, dims, strides, box, es, CU_TENSOR_MAP_INTERLEAVE_NONE,
        CU_TENSOR_MAP_SWIZZLE_32B, CU_TENSOR_MAP_L2_PROMOTION_NONE, CU_TENSOR_MAP_FLOAT_OOB_FILL_NONE);
  }

  rec_kernel<<<96, 384, SM_TOTAL, cudaStreamPerThread>>>(rm, x, mem0);
  cudaLaunchConfig_t cfg = {};
  cfg.gridDim = dim3(NAUX); cfg.blockDim = dim3(512); cfg.dynamicSmemBytes = A_TOTAL; cfg.stream = cudaStreamPerThread;
  cudaLaunchAttribute at[1];
  at[0].id = cudaLaunchAttributeProgrammaticStreamSerialization; at[0].val.programmaticStreamSerializationAllowed = 1;
  cfg.attrs = at; cfg.numAttrs = 1;
  if (XP & 16) cfg.numAttrs = 0;
  if (!(XP & 64)) cudaLaunchKernelEx(&cfg, aux_kernel, am, x, gate_w, (bf16*)d_out);
}
```

```cpp
#include <cuda_runtime.h>
#include <cuda_bf16.h>
#include <cuda_fp16.h>
#include <cuda.h>
#include <stdint.h>

typedef __nv_bfloat16 bf16;

constexpr int S_LEN = 2048, DM = 576, NH = 32, DH = 128, NSEG = 64, KCAT = 4096 + 576;
#define RED_LINE(i) (((i) >> 2) * 4096 + ((i) & 1) * 256 + ((i) & 2) * 512)
#define RED_SLOT(s) (((s) & 1) * 128 + ((s) & 2) * 256)

#define POLL_NS 896
#define QM 60
constexpr int NUP = 4;
#define N5 224
#define KP(i) (((i) >> 1) + 4 * ((i) & 1))
#define SPIN_LIMIT (1 << 14)
#define XP 0
#define YP 0

__device__ __align__(1024) bf16 g_Ocat[S_LEN * KCAT];
__device__ __align__(1024) unsigned char g_red_raw[2 * 262144];
constexpr int HINT_OFF = 2048;
__device__ __align__(16) float g_gate[S_LEN];
__device__ __align__(128) uint4 g_stats[96 * 2];
__device__ unsigned g_epoch;
__device__ unsigned g_epoch2;
__device__ __align__(128) unsigned g_oflag[NH * 32];
__device__ unsigned g_abar[3 * 32];
__device__ __align__(128) unsigned g_cflag[96 * 32];
__device__ uint2 g_sflag[96 * 4];
__device__ __align__(1024) unsigned char g_seg[NSEG * 96 * 8192];
__device__ __align__(1024) unsigned char g_km[NSEG * NH * 4096];
__device__ __align__(1024) uint2 g_part[8 * 9 * 4 * 8 * 128];
__device__ int g_err;
#define SSTAMP(seg, idx)
#define TSTAMP(idx)
#define QSTAMP(idx)
#define PROF(idx)
#define PROFP(idx)
#define STAMP(idx)
#define ASTAMP(idx)
#define WSTAMP(idx)

#define CSTAMP(idx)
#define CDECL
#define CDUMP
#define DI __device__ __forceinline__
DI uint32_t smem_u32(const void* p) { return (uint32_t)__cvta_generic_to_shared(p); }
DI uint32_t clock32() { uint32_t c; asm volatile("mov.u32 %0, %%clock;" : "=r"(c) :: "memory"); return c; }
DI uint32_t gtime() { uint32_t c; asm volatile("mov.u32 %0, %%globaltimer_lo;" : "=r"(c) :: "memory"); return c; }
DI uint32_t ldg_relaxed32(const void* p) { uint32_t v; asm volatile("ld.relaxed.gpu.global.b32 %0, [%1];" : "=r"(v) : "l"(p) : "memory"); return v; }
DI uint32_t ldg_acquire32(const void* p) { uint32_t v; asm volatile("ld.acquire.gpu.global.b32 %0, [%1];" : "=r"(v) : "l"(p) : "memory"); return v; }
DI void stg_relaxed32(void* p, uint32_t v) { asm volatile("st.relaxed.gpu.global.b32 [%0], %1;" :: "l"(p), "r"(v) : "memory"); }
DI uint32_t mapa(uint32_t a, uint32_t r) { uint32_t o; asm("mapa.shared::cluster.u32 %0, %1, %2;" : "=r"(o) : "r"(a), "r"(r)); return o; }
DI void cluster_arrive() { asm volatile("barrier.cluster.arrive.relaxed.aligned;" ::: "memory"); }
DI void cluster_wait() { asm volatile("barrier.cluster.wait.aligned;" ::: "memory"); }
DI void cluster_sync() { asm volatile("barrier.cluster.arrive.release.aligned;\nbarrier.cluster.wait.acquire.aligned;" ::: "memory"); }
DI void mbar_init(uint32_t b, uint32_t c) { asm volatile("mbarrier.init.shared::cta.b64 [%0], %1;" :: "r"(b), "r"(c) : "memory"); }
DI void mbar_expect(uint32_t b, uint32_t tx) { asm volatile("mbarrier.arrive.expect_tx.shared::cta.b64 _, [%0], %1;" :: "r"(b), "r"(tx) : "memory"); }
DI void mbar_arrive(uint32_t b) { asm volatile("mbarrier.arrive.shared::cta.b64 _, [%0];" :: "r"(b) : "memory"); }
DI void mbar_wait(uint32_t b, uint32_t par) {
  asm volatile("{\n.reg .pred p;\n.reg .u32 n, q;\nmov.u32 n, 0;\n"
               "WL: add.u32 n, n, 1;\nshr.u32 q, n, 12;\nxor.b32 q, q, %1;\n"
               "mbarrier.try_wait.parity.shared::cta.b64 p, [%0], q;\n@!p bra.uni WL;\n}"
               :: "r"(b), "r"(par) : "memory");
}
DI void wait_until(uint32_t t) {
  const uint32_t now = gtime();
  t = min(t, now + 8192);
  asm volatile("{\n.reg .pred p;\n.reg .u32 c;\nTL: mov.u32 c, %%globaltimer_lo;\nsetp.lt.u32 p, c, %0;\n@p bra.uni TL;\n}" :: "r"(t) : "memory");
}
#define PIN(v) v = __shfl_xor_sync(0xffffffffu, v, 0)
#define SCHED_FENCE(k) asm volatile("{\n.reg .pred p;\nsetp.eq.u32 p, %0, %1;\n@p exit;\n}" :: "r"(fence_reg), "r"(k) : "memory")
DI void bar_sync(int id, int n) { asm volatile("bar.sync %0, %1;" :: "r"(id), "r"(n) : "memory"); }
DI void bar_arrive(int id, int n) { asm volatile("bar.arrive %0, %1;" :: "r"(id), "r"(n) : "memory"); }
DI void fence_async() { asm volatile("fence.proxy.async.shared::cta;" ::: "memory"); }
DI void st_async4(uint32_t a, uint32_t x, uint32_t y, uint32_t z, uint32_t w, uint32_t mb) {
  asm volatile("st.async.weak.shared::cluster.mbarrier::complete_tx::bytes.v4.b32 [%0], {%1,%2,%3,%4}, [%5];"
               :: "r"(a), "r"(x), "r"(y), "r"(z), "r"(w), "r"(mb) : "memory");
}
DI void sts32(uint32_t a, uint32_t x) { asm volatile("st.shared.b32 [%0], %1;" :: "r"(a), "r"(x) : "memory"); }
DI void sts64(uint32_t a, uint32_t x, uint32_t y) { asm volatile("st.shared.v2.b32 [%0], {%1,%2};" :: "r"(a), "r"(x), "r"(y) : "memory"); }
DI void sts128(uint32_t a, uint32_t x, uint32_t y, uint32_t z, uint32_t w) {
  asm volatile("st.shared.v4.b32 [%0], {%1,%2,%3,%4};" :: "r"(a), "r"(x), "r"(y), "r"(z), "r"(w) : "memory");
}
DI uint32_t lds32(uint32_t a) { uint32_t x; asm volatile("ld.shared.b32 %0, [%1];" : "=r"(x) : "r"(a) : "memory"); return x; }
DI uint32_t lds32v(uint32_t a) { uint32_t x; asm volatile("ld.volatile.shared.b32 %0, [%1];" : "=r"(x) : "r"(a) : "memory"); return x; }
DI void lds64(uint32_t a, uint32_t& x, uint32_t& y) { asm volatile("ld.shared.v2.b32 {%0,%1}, [%2];" : "=r"(x), "=r"(y) : "r"(a) : "memory"); }
DI void lds128(uint32_t a, uint32_t* r) {
  asm volatile("ld.shared.v4.b32 {%0,%1,%2,%3}, [%4];" : "=r"(r[0]), "=r"(r[1]), "=r"(r[2]), "=r"(r[3]) : "r"(a) : "memory");
}
DI void lds128f(uint32_t a, float* r) {
  asm volatile("ld.shared.v4.f32 {%0,%1,%2,%3}, [%4];" : "=f"(r[0]), "=f"(r[1]), "=f"(r[2]), "=f"(r[3]) : "r"(a) : "memory");
}
DI void ldsm4t(uint32_t* r, uint32_t a) {
  asm volatile("ldmatrix.sync.aligned.m8n8.x4.trans.shared.b16 {%0,%1,%2,%3}, [%4];"
               : "=r"(r[0]), "=r"(r[1]), "=r"(r[2]), "=r"(r[3]) : "r"(a) : "memory");
}
DI void ldsm4t_in(uint32_t* r, uint32_t a, uint32_t t) {
  asm volatile("{\n.reg .pred p;\nsetp.ne.u32 p, %5, 0;\n@p ldmatrix.sync.aligned.m8n8.x4.trans.shared.b16 {%0,%1,%2,%3}, [%4];\n}"
               : "+r"(r[0]), "+r"(r[1]), "+r"(r[2]), "+r"(r[3]) : "r"(a), "r"(t) : "memory");
}
DI void lds128_in(uint32_t* r, uint32_t a, uint32_t t) {
  asm volatile("{\n.reg .pred p;\nsetp.ne.u32 p, %5, 0;\n@p ld.shared.v4.b32 {%0,%1,%2,%3}, [%4];\n}"
               : "+r"(r[0]), "+r"(r[1]), "+r"(r[2]), "+r"(r[3]) : "r"(a), "r"(t) : "memory");
}
DI void ldsm2t_in(uint32_t* r, uint32_t a, uint32_t t) {
  asm volatile("{\n.reg .pred p;\nsetp.ne.u32 p, %3, 0;\n@p ldmatrix.sync.aligned.m8n8.x2.trans.shared.b16 {%0,%1}, [%2];\n}" : "+r"(r[0]), "+r"(r[1]) : "r"(a), "r"(t) : "memory");
}
DI void reserve2(uint32_t* r) { asm volatile("{\n.reg .u64 t;\nmov.u64 t, %%clock64;\nmov.b64 {%0, %1}, t;\n}" : "=r"(r[0]), "=r"(r[1])); }
DI void scale_sum(float& x, float& y, float s, uint32_t t) {
  asm volatile("{\n.reg .pred p;\nsetp.ne.u32 p, %2, 0;\n@p mul.f32 %0, %0, %1;\n}" : "+f"(y) : "f"(s), "r"(t));
  asm volatile("{\n.reg .pred p;\nsetp.ne.u32 p, %3, 1;\n@p fma.rn.f32 %0, %0, %1, %2;\n}" : "+f"(x) : "f"(s), "f"(y), "r"(t));
}
DI void ldsm4(uint32_t* r, uint32_t a) {
  asm volatile("ldmatrix.sync.aligned.m8n8.x4.shared.b16 {%0,%1,%2,%3}, [%4];"
               : "=r"(r[0]), "=r"(r[1]), "=r"(r[2]), "=r"(r[3]) : "r"(a) : "memory");
}
DI void st_async1(uint32_t a, uint32_t x, uint32_t mb) {
  asm volatile("st.async.weak.shared::cluster.mbarrier::complete_tx::bytes.b32 [%0], %1, [%2];" :: "r"(a), "r"(x), "r"(mb) : "memory");
}
DI void stsm4(uint32_t a, uint32_t x, uint32_t y, uint32_t z, uint32_t w) {
  asm volatile("stmatrix.sync.aligned.m8n8.x4.shared.b16 [%0], {%1,%2,%3,%4};" :: "r"(a), "r"(x), "r"(y), "r"(z), "r"(w) : "memory");
}
DI void stsm4t(uint32_t a, uint32_t x, uint32_t y, uint32_t z, uint32_t w) {
  asm volatile("stmatrix.sync.aligned.m8n8.x4.trans.shared.b16 [%0], {%1,%2,%3,%4};" :: "r"(a), "r"(x), "r"(y), "r"(z), "r"(w) : "memory");
}
DI uint32_t pack_bf16(float lo, float hi) { uint32_t r; asm("cvt.rn.bf16x2.f32 %0, %1, %2;" : "=r"(r) : "f"(hi), "f"(lo)); return r; }
DI uint32_t pack_f16(float lo, float hi) { uint32_t r; asm("cvt.rn.f16x2.f32 %0, %1, %2;" : "=r"(r) : "f"(hi), "f"(lo)); return r; }
DI float ex2(float x) { float y; asm("ex2.approx.ftz.f32 %0, %1;" : "=f"(y) : "f"(x)); return y; }
DI float rcp(float x) { float y; asm("rcp.approx.ftz.f32 %0, %1;" : "=f"(y) : "f"(x)); return y; }
DI float bf_lo(uint32_t x) { return __uint_as_float(x << 16); }
DI float bf_hi(uint32_t x) { return __uint_as_float(x & 0xffff0000u); }
DI void mma16816(float* d, const uint32_t* a, uint32_t b0, uint32_t b1) {
  asm volatile("mma.sync.aligned.m16n8k16.row.col.f32.bf16.bf16.f32 {%0,%1,%2,%3}, {%4,%5,%6,%7}, {%8,%9}, {%0,%1,%2,%3};"
               : "+f"(d[0]), "+f"(d[1]), "+f"(d[2]), "+f"(d[3]) : "r"(a[0]), "r"(a[1]), "r"(a[2]), "r"(a[3]), "r"(b0), "r"(b1));
}
DI void mma16816z(float* d, const uint32_t* a, uint32_t b0, uint32_t b1) {
  asm volatile("mma.sync.aligned.m16n8k16.row.col.f32.bf16.bf16.f32 {%0,%1,%2,%3}, {%4,%5,%6,%7}, {%8,%9}, {%10,%10,%10,%10};"
               : "=f"(d[0]), "=f"(d[1]), "=f"(d[2]), "=f"(d[3]) : "r"(a[0]), "r"(a[1]), "r"(a[2]), "r"(a[3]), "r"(b0), "r"(b1), "f"(0.f));
}
DI void mma1688(float* d, uint32_t a0, uint32_t a1, uint32_t b0) {
  asm volatile("mma.sync.aligned.m16n8k8.row.col.f32.bf16.bf16.f32 {%0,%1,%2,%3}, {%4,%5}, {%6}, {%0,%1,%2,%3};"
               : "+f"(d[0]), "+f"(d[1]), "+f"(d[2]), "+f"(d[3]) : "r"(a0), "r"(a1), "r"(b0));
}
DI uint32_t add_bf16(uint32_t a, uint32_t b) { uint32_t r; asm("add.rn.bf16x2 %0, %1, %2;" : "=r"(r) : "r"(a), "r"(b)); return r; }
DI uint32_t mul_bf16(uint32_t a, uint32_t b) { uint32_t r; asm("mul.rn.bf16x2 %0, %1, %2;" : "=r"(r) : "r"(a), "r"(b)); return r; }
DI uint64_t make_desc(uint32_t addr, uint32_t lbo, uint32_t sbo, uint32_t swz) {
  return (uint64_t)((addr & 0x3FFFF) >> 4) | ((uint64_t)(lbo >> 4) << 16) | ((uint64_t)(sbo >> 4) << 32) | ((uint64_t)swz << 62);
}
#define WG_FENCE() asm volatile("wgmma.fence.sync.aligned;" ::: "memory")
#define WG_COMMIT() asm volatile("wgmma.commit_group.sync.aligned;" ::: "memory")
#define WG_WAIT(n) asm volatile("wgmma.wait_group.sync.aligned %0;" :: "n"(n) : "memory")
#define ACC8(d, o) "+f"(d[o]), "+f"(d[o + 1]), "+f"(d[o + 2]), "+f"(d[o + 3]), "+f"(d[o + 4]), "+f"(d[o + 5]), "+f"(d[o + 6]), "+f"(d[o + 7])
DI void wgmma_n32_rs(float* d, uint32_t a0, uint32_t a1, uint32_t a2, uint32_t a3, uint64_t db, int acc) {
  asm volatile("{\n.reg .pred p;\nsetp.ne.b32 p, %21, 0;\n"
               "wgmma.mma_async.sync.aligned.m64n32k16.f32.bf16.bf16 {%0,%1,%2,%3,%4,%5,%6,%7,%8,%9,%10,%11,%12,%13,%14,%15}, "
               "{%16,%17,%18,%19}, %20, p, 1, 1, 0;\n}\n"
               : ACC8(d, 0), ACC8(d, 8) : "r"(a0), "r"(a1), "r"(a2), "r"(a3), "l"(db), "r"(acc));
}
template <int TA>
DI void wgmma_n32_ss(float* d, uint64_t da, uint64_t db, int acc) {
  asm volatile("{\n.reg .pred p;\nsetp.ne.b32 p, %18, 0;\n"
               "wgmma.mma_async.sync.aligned.m64n32k16.f32.bf16.bf16 {%0,%1,%2,%3,%4,%5,%6,%7,%8,%9,%10,%11,%12,%13,%14,%15}, "
               "%16, %17, p, 1, 1, %19, 1;\n}\n"
               : ACC8(d, 0), ACC8(d, 8) : "l"(da), "l"(db), "r"(acc), "n"(TA));
}
DI void tma_load(uint32_t dst, const CUtensorMap* m, int c0, int c1, uint32_t mb) {
  asm volatile("cp.async.bulk.tensor.2d.shared::cluster.global.mbarrier::complete_tx::bytes [%0], [%1, {%3, %4}], [%2];"
               :: "r"(dst), "l"(m), "r"(mb), "r"(c0), "r"(c1) : "memory");
}
DI void tma_load3(uint32_t dst, const CUtensorMap* m, int row, uint32_t mb) {
  asm volatile("cp.async.bulk.tensor.3d.shared::cluster.global.mbarrier::complete_tx::bytes [%0], [%1, {%3, %4, %3}], [%2];"
               :: "r"(dst), "l"(m), "r"(mb), "r"(0), "r"(row) : "memory");
}
DI bool elect_one() {
  uint32_t p;
  asm volatile("{\n.reg .pred p;\nelect.sync _|p, 0xffffffff;\nselp.u32 %0, 1, 0, p;\n}" : "=r"(p));
  return p;
}
DI void bulk_s2s(uint32_t dst, uint32_t src, uint32_t bytes, uint32_t mb) {
  asm volatile("cp.async.bulk.shared::cluster.shared::cta.mbarrier::complete_tx::bytes [%0], [%1], %2, [%3];"
               :: "r"(dst), "r"(src), "r"(bytes), "r"(mb) : "memory");
}
DI void bulk_load(uint32_t dst, const void* src, uint32_t bytes, uint32_t mb) {
  asm volatile("cp.async.bulk.shared::cluster.global.mbarrier::complete_tx::bytes [%0], [%1], %2, [%3];" :: "r"(dst), "l"(src), "r"(bytes), "r"(mb) : "memory");
}
#define EVICT_FIRST ".reg .b64 pol;\ncreatepolicy.fractional.L2::evict_first.b64 pol, 1.0;\n"
DI void tma_load_ef(uint32_t dst, const CUtensorMap* m, int c0, int c1, uint32_t mb) {
  asm volatile("{\n" EVICT_FIRST "cp.async.bulk.tensor.2d.shared::cluster.global.mbarrier::complete_tx::bytes.L2::cache_hint [%0], [%1, {%3, %4}], [%2], pol;\n}"
               :: "r"(dst), "l"(m), "r"(mb), "r"(c0), "r"(c1) : "memory");
}
DI void tma_prefetch(const CUtensorMap* m, int c0, int c1) {
  asm volatile("cp.async.bulk.prefetch.tensor.2d.L2.global.tile [%0, {%1, %2}];" :: "l"(m), "r"(c0), "r"(c1) : "memory");
}
DI void tma_store(const CUtensorMap* m, uint32_t src, int c0, int c1) {
  asm volatile("cp.async.bulk.tensor.2d.global.shared::cta.bulk_group [%0, {%2, %3}], [%1];" :: "l"(m), "r"(src), "r"(c0), "r"(c1) : "memory");
}
DI uint4 ldg_relaxed(const void* p) {
  uint4 v;
  asm volatile("ld.relaxed.gpu.global.v4.b32 {%0,%1,%2,%3}, [%4];" : "=r"(v.x), "=r"(v.y), "=r"(v.z), "=r"(v.w) : "l"(p) : "memory");
  return v;
}
DI void stg_relaxed(void* p, uint32_t x, uint32_t y, uint32_t z, uint32_t w) {
  asm volatile("st.relaxed.gpu.global.v4.b32 [%0], {%1,%2,%3,%4};" :: "l"(p), "r"(x), "r"(y), "r"(z), "r"(w) : "memory");
}
DI void red_f16x8(void* p, uint32_t x, uint32_t y, uint32_t z, uint32_t w) {
  asm volatile("red.relaxed.gpu.global.add.noftz.v4.f16x2 [%0], {%1,%2,%3,%4};" :: "l"(p), "r"(x), "r"(y), "r"(z), "r"(w) : "memory");
}
DI void sq_acc(uint32_t& a, uint32_t x) { asm("fma.rn.bf16x2 %0, %1, %1, %0;" : "+r"(a) : "r"(x)); }
DI __half2 amax4(__half2 h, const uint32_t* v) {
  h = __hmax2_nan(__hmax2_nan(h, __habs2(*(const __half2*)&v[0])), __habs2(*(const __half2*)&v[1]));
  return __hmax2_nan(__hmax2_nan(h, __habs2(*(const __half2*)&v[2])), __habs2(*(const __half2*)&v[3]));
}
DI uint32_t wexp(__half2 h) { const uint32_t u = *(const uint32_t*)&h; return __reduce_max_sync(0xffffffffu, max((u >> 16) & 0x7fffu, u & 0x7fffu)) >> 7; }
DI float warp_sum(float v) {
#pragma unroll
  for (int o = 16; o; o >>= 1) v += __shfl_xor_sync(0xffffffffu, v, o);
  return v;
}

constexpr int SM_WO3 = 0;
constexpr int SM_X = 16384;
constexpr int XT = 36864;
constexpr int SM_EXP = 126976;
constexpr int SEGB = 10240;
constexpr int SM_BLK = SM_EXP + 8192;
constexpr int SM_VC = SM_BLK + 4 * SEGB;
constexpr int SM_PART = SM_VC + 16384;
constexpr int SM_QM = SM_PART + 4096;
constexpr int SM_E = SM_QM + 1024;
constexpr int SM_VM = SM_E + 1536;
constexpr int SM_OB = SM_VM + 2048;
constexpr int SM_FB = SM_OB + 2048;
constexpr int SM_STAGE = SM_X + XT;
constexpr int SM_M0 = SM_STAGE + 3 * 49152;
constexpr int SM_MISC = 210944;
constexpr int SM_WOST = 212992;
constexpr int SM_MEM = SM_WOST;
constexpr int SM_MAX = SM_MEM + 11264;
#define MEM_BLK(q) ((q) / 3 * 4096 + (q) % 3 * 1024)
constexpr int SM_TOTAL = 229376;
constexpr int MB_W = SM_MISC;
constexpr int MB_WO = SM_MISC + 24;
constexpr int MB_WO3 = SM_MISC + 32;
constexpr int MB_X = SM_MISC + 40;
constexpr int MB_S = SM_MISC + 64;
constexpr int MB_F = SM_MISC + 72;
constexpr int MB_VX = SM_MISC + 80;
constexpr int SC_FPAR = SM_MISC + 136;
constexpr int SC_DEAD = SM_MISC + 96;
constexpr int SC_UNSC = SM_MISC + 112;
constexpr int SC_OFL = SM_MISC + 1024;
constexpr int SC_EXPW = SM_MISC + 132;
constexpr int SC_ONES = SM_MISC + 144;
constexpr int SC_SS = SM_MISC + 160;
constexpr int SC_LAT = SM_MISC + 224;
constexpr int SC_TAG = SM_MISC + 232;
constexpr int SC_EPO = SM_MISC + 240;
constexpr int MB_XS = SM_MISC + 248;
constexpr int SC_XMAX = SM_MISC + 256;
constexpr int SC_PROF = 229376;

constexpr float SM_SCALE = 0.08838834764831845f;
constexpr float LOG2E = 1.4426950408889634f;
constexpr float E_LIM = 20.f;

template <bool B> struct BoolC { static constexpr bool value = B; };
template <int I> struct IntC { static constexpr int value = I; };
struct RMaps { CUtensorMap x, wq, wk, wv, wo; unsigned char* red; uint32_t poll; const unsigned char* oflag; };

DI uint32_t latest_hint(uint32_t h, uint32_t d, int s) {
  const uint32_t x = (((h | 0xc0c0c0c0u) - ((d >> 5) & 63) * 0x01010101u) & 0x3f3f3f3fu) | ((h ^ (((s >> 2) + 1) & 3) * 0x40404040u) & 0xc0c0c0c0u);
  const uint32_t y = __vmaxu2(x & 0x00ff00ffu, (x >> 8) & 0x00ff00ffu);
  return __reduce_max_sync(0xffffffffu, max(y & 0xffffu, y >> 16));
}
DI uint32_t near_half(uint32_t sb) {
  uint32_t a, b; lds64(sb + SC_LAT, a, b);
  return a > b;
}

template <int RT, int K0, int K1, bool D32 = false>
DI void xproj(float* acc, const uint32_t (&wa)[2][18][4], uint64_t xd) {
  if (XP & 1) return;
  WG_FENCE();
#pragma unroll
  for (int k = K0; k < ((XP & 128) ? K0 + 1 : K1); k++)
  {
    uint64_t d = xd + (uint64_t)(((k >> 1) * 4096 + (k & 1) * 32) >> 4);
    if (D32) asm("mov.b64 %0, {%1, %2};" : "=l"(d) : "r"((uint32_t)xd + (((k >> 1) * 4096 + (k & 1) * 32) >> 4)), "r"((uint32_t)(xd >> 32)));
    wgmma_n32_rs(acc, wa[RT][k][0], wa[RT][k][1], wa[RT][k][2], wa[RT][k][3], d, k != 0);
  }
  WG_COMMIT();
}

DI void load_w(uint32_t sb, const RMaps& tm, uint32_t rank, int c) {
  const int h = blockIdx.x / 3;
  mbar_expect(sb + MB_W + 8 * c, 49152);
  tma_load_ef(sb + SM_STAGE + c * 49152, rank < 2 ? &tm.wk : &tm.wv, h * DH + (rank == 1 ? 64 : 0), c * 192, sb + MB_W + 8 * c);
  tma_load_ef(sb + SM_STAGE + c * 49152 + 24576, rank < 2 ? &tm.wq : &tm.wv, h * DH + (rank == 0 ? 0 : 64), c * 192, sb + MB_W + 8 * c);
}
DI void seg_store(int seg, uint32_t slot, uint32_t sb) {
  asm volatile("cp.async.bulk.global.shared::cta.bulk_group [%0], [%1], 8192;"
               :: "l"(g_seg + ((size_t)slot * 96 + blockIdx.x) * 8192), "r"(sb + SM_BLK + (seg & 3) * SEGB) : "memory");
  asm volatile("cp.async.bulk.commit_group;" ::: "memory");
}
DI void seg_publish(int seg, uint32_t sb) {
  uint32_t v, own;
  lds64(sb + SC_EPO, v, own);
  asm volatile("cp.async.bulk.wait_group 0;" ::: "memory");
  asm volatile("st.relaxed.gpu.global.v2.b32 [%0], {%1,%2};" :: "l"(&g_sflag[blockIdx.x * 4]), "r"(v + seg), "r"(own) : "memory");
}

DI void proj_role(const uint32_t sb, const RMaps& tm, const bf16* __restrict__ x, const uint32_t rank, const int wg, const int w, const int lane) {
  const bool qk = rank < 2;
  uint32_t wa[2][18][4];
  float acc[16];
  const uint64_t xd0 = make_desc(sb + SM_X + wg * 64, 16, 1024, 1);
  {
    const int rr = (lane & 7) + ((lane >> 4) << 3);
    const uint32_t col = ((2 * w + ((lane >> 3) & 1)) ^ (lane & 7)) << 4;
    float ss = 0.f;
    bar_sync(3, 256);
    mbar_wait(sb + MB_X, 0);
    auto chunk = [&](auto cc) {
      constexpr int c = decltype(cc)::value;
      QSTAMP(2 + 2 * c);
      mbar_wait(sb + MB_W + 8 * c, 0);
      QSTAMP(3 + 2 * c);
#pragma unroll
      for (int rt = 1; rt >= 0; rt--)
#pragma unroll
        for (int k = 0; k < 6; k++)
          ldsm4t(wa[rt][c * 6 + k], sb + SM_STAGE + c * 49152 + (rt ^ wg) * 24576 + (64 * (k >> 1) + 32 * wg + 16 * (k & 1) + rr) * 128 + col);
      fence_async();
      if (c < 2) {
        bar_sync(3, 256);
        QSTAMP(17 + c);
        if (threadIdx.x == 0) {
          if (c == 0) tma_load(sb + SM_X + XT, &tm.wo, rank * 192, (blockIdx.x / 3) * DH, sb + MB_WO);
          else if (blockIdx.x < NSEG) bulk_load(sb + SM_X + 2 * XT, x + blockIdx.x * 32 * DM, XT, sb + MB_XS);
          else tma_load3(sb + SM_X + 2 * XT, &tm.x, 64, sb + MB_X + 16);
        }
        __syncwarp();
      } else {
        cluster_arrive();
      }
      xproj<1, 6 * c, 6 * c + 6>(acc, wa, xd0);
      if (!qk) {
        uint32_t q[4] = {0, 0, 0, 0};
#pragma unroll
        for (int rt = 0; rt < 2; rt++)
#pragma unroll
          for (int k = 0; k < 6; k++)
#pragma unroll
            for (int i = 0; i < 4; i++) sq_acc(q[i], wa[rt][c * 6 + k][i]);
#pragma unroll
        for (int i = 0; i < 4; i++) ss += bf_lo(q[i]) + bf_hi(q[i]);
      }
    };
    chunk(IntC<0>()); chunk(IntC<1>()); chunk(IntC<2>());
    ss = warp_sum(ss);
    if (lane == 0) sts32(sb + SC_SS + 4 * (wg * 4 + w), __float_as_uint(ss));
    bar_arrive(11, 384);
  }
  STAMP(1);
  QSTAMP(8);
  STAMP(2);

  uint32_t t16 = sb + (w * 32 + lane) * 16;
  uint32_t mem_a = sb + SM_MEM + wg * 512 + lane * 16;
  uint32_t fin_a = sb + (lane & 7) * 16 + SM_BLK + (qk ? (wg ^ 1) * 4096 + w * 256 + (lane & 8) * 16 + (lane & 16) * 64
                                              : wg * 4096 + w * 1024 + (lane & 8) * 64 + (lane & 16) * 8);
  PIN(t16); PIN(mem_a); PIN(fin_a);
  const uint32_t fence_reg = mem_a;
  const uint32_t fin2 = qk ? 2048 : 256;
  auto do_export = [&](auto retire, uint32_t always) {
    WG_WAIT(0);
    uint32_t p[2];
#pragma unroll
    for (int i = 0; i < 2; i++) {
      p[i] = pack_bf16(acc[8 * i], acc[8 * i + 1]);
      sts128(t16 + SM_EXP + wg * 4096 + i * 2048, p[i], pack_bf16(acc[8 * i + 2], acc[8 * i + 3]),
             pack_bf16(acc[8 * i + 4], acc[8 * i + 5]), pack_bf16(acc[8 * i + 6], acc[8 * i + 7]));
    }
    if (decltype(retire)::value)
      asm volatile("{\n.reg .pred p, q;\nsetp.ne.u32 p, %2, 0;\nsetp.ne.u32 q, %2, 1;\n@p ld.shared.b32 %0, [%3];\n@q ld.shared.b32 %1, [%3 + 4];\n"
                   "setp.ne.u32 p, %0, %1;\n@p exit;\n}" : "+r"(p[0]), "+r"(p[1]) : "r"(always), "r"(sb + SC_DEAD) : "memory");
  };
  uint32_t o[8];
  auto import = [&]() { lds128(t16 + SM_EXP + (wg ^ 1) * 4096, o); lds128(t16 + SM_EXP + (wg ^ 1) * 4096 + 2048, o + 4); };
  auto finish_from = [&](int seg, const float* d) {
    const uint32_t a = fin_a + (seg & 3) * SEGB;
#pragma unroll
    for (int i = 0; i < 8; i++) o[i] = add_bf16(pack_bf16(d[2 * i], d[2 * i + 1]), o[i]);
    stsm4(a, o[0], o[1], o[2], o[3]);
    stsm4(a + fin2, o[4], o[5], o[6], o[7]);
    fence_async();
  };
  auto finish = [&](int seg) { WG_WAIT(0); finish_from(seg, acc); };
  auto send_v = [&](int seg, int dst) {
    if (seg < NSEG - 1 && !(XP & 2) && elect_one())
      bulk_s2s(mapa(sb + SM_VC + (seg & 1) * 8192, dst), sb + SM_BLK + (seg & 3) * SEGB, 8192, mapa(sb + MB_VX + (seg & 1) * 8, dst));
    __syncwarp();
  };
  auto wait_v = [&](int seg) {
    if (seg < NSEG - 1 && !(XP & 2)) {
      mbar_wait(sb + MB_VX + (seg & 1) * 8, (seg >> 1) & 1);
      if (elect_one()) mbar_expect(sb + MB_VX + (seg & 1) * 8, 8192);
      __syncwarp();
    }
  };
  auto export_seg = [&](int seg, uint32_t slot) { if (!(XP & (4 | 8192)) && elect_one()) seg_store(seg, slot, sb); __syncwarp(); };
  auto publish = [&](int seg) { if (!(XP & (4 | 16384)) && elect_one()) seg_publish(seg, sb); __syncwarp(); };
  do_export(BoolC<false>(), 0);
  QSTAMP(9);
  SCHED_FENCE(11);
  xproj<0, 0, 18>(acc, wa, xd0);
  bar_sync(3, 256);
  QSTAMP(10);
  cluster_wait();
  QSTAMP(11);
  mbar_wait(sb + MB_X + 8, 0);
  QSTAMP(12);
  import();
  finish(0);
  SCHED_FENCE(12);
  uint64_t dA = xd0 + (XT >> 4);
  xproj<1, 0, 18>(acc, wa, dA);
  bar_sync(3, 256);
  if (!qk && wg == 0 && w < 2) send_v(0, w);
  if (wg == 0 && w == 3) export_seg(0, 0);
  QSTAMP(13);
  if (qk && wg == 0 && w == 0) wait_v(0);
  QSTAMP(14);
  bar_arrive(13, 384);
  if (!qk) {
    do_export(BoolC<false>(), 0);
    SCHED_FENCE(15);
    xproj<0, 0, 18>(acc, wa, dA);
    if (threadIdx.x == 0 && !(XP & 8)) { mbar_expect(sb + MB_X, XT); tma_load3(sb + SM_X, &tm.x, 96, sb + MB_X); }
    bar_sync(3, 256);
    mbar_wait(sb + MB_X + 16, 0);
    import();
    finish(1);
    SCHED_FENCE(16);
    dA += XT >> 4;
    xproj<1, 0, 18>(acc, wa, dA);
  }
  QSTAMP(15);
  WG_WAIT(0);
  bar_sync(0, 384);
  if (wg == 0 && w == 3) publish(0);
  QSTAMP(16);
  const int ro = __shfl_sync(0xffffffffu, near_half(sb) ^ wg, 0);
  STAMP(5);
  const uint32_t always = __shfl_sync(0xffffffffu, lds32(sb + SC_DEAD + 12), 0);
  const int ah = qk ? 1 : 2;
  int b2 = qk ? 2 : 0;
  int s = 0;
  uint32_t hint_lo = (uint32_t)(uint64_t)tm.red + HINT_OFF + blockIdx.x + (lane & 1) * 4096 + (lane >> 1) * 16384;
  PIN(hint_lo);
  auto post_hint = [&]() {
    uint32_t t;
    asm volatile("{\n.reg .u64 g;\nmov.u64 g, %%globaltimer;\ncvt.u32.u64 %0, g;\n}" : "=r"(t) :: "memory");
    asm volatile("{\n.reg .pred p;\n.reg .b64 a;\n.reg .u32 t;\nsetp.lt.u32 p, %0, %1;\nmov.b64 a, {%2, %3};\n"
                 "bfe.u32 t, %5, 5, 6;\nor.b32 t, t, %4;\n@p st.relaxed.gpu.global.u8 [a], t;\n}"
                 :: "r"(t16), "r"(sb + 160), "r"(hint_lo + RED_SLOT(s)), "r"((uint32_t)((uint64_t)tm.red >> 32)), "r"(((s >> 2) + 1) << 6), "r"(t) : "memory");
  };
  auto memproj = [&](auto second, int id, uint32_t dep, float u0, float u1, float* r) {
    constexpr bool R1 = decltype(second)::value;
    uint32_t b[NUP][4], b0[4];
    if (R1) asm volatile("{\n.reg .pred p;\nsetp.eq.u32 p, %0, %1;\n@p exit;\n}" :: "r"(dep), "r"(id) : "memory");
    bar_sync(R1 ? 2 : 1, 256);
    PROF(0);
    ldsm4t(b0, mem_a);
#pragma unroll
    for (int q = 0; q < NUP; q++) {
      if (R1 && q == 2) {
        bar_sync(11, 256);
        SCHED_FENCE(id + 1);
      }
      ldsm4t(b[q], mem_a + MEM_BLK(q + 1));
    }
    mma16816z(&acc[0], wa[0][0], b0[0], b0[1]);
    mma16816z(&acc[4], wa[1][0], b0[0], b0[1]);
    mma16816z(&acc[8], wa[0][1], b0[2], b0[3]);
    mma16816z(&acc[12], wa[1][1], b0[2], b0[3]);
#pragma unroll
    for (int q = 1; q < 9; q++) {
      uint32_t* const c = b[(q - 1) % NUP];
      mma16816(&acc[0], wa[0][2 * q], c[0], c[1]);
      mma16816(&acc[4], wa[1][2 * q], c[0], c[1]);
      mma16816(&acc[8], wa[0][2 * q + 1], c[2], c[3]);
      mma16816(&acc[12], wa[1][2 * q + 1], c[2], c[3]);
      if (R1 && q + NUP == 9) bar_sync(3, 256);
      if (q + NUP < 9) ldsm4t_in(c, mem_a + MEM_BLK(q + NUP), always);
      else if (R1 && q + NUP < 11) lds128_in(c, t16 + SM_PART + (10 - q - NUP) * 2048, always);
      else if (!R1 && q == 8) { bar_arrive(11, 256); lds128_in(c, sb + SC_DEAD, always); u0 = u1 = __uint_as_float(c[3]); }
    }
#pragma unroll
    for (int i = 0; i < 8; i++) {
      const float u = i < 4 ? u0 : u1;
      r[i] = R1 ? fmaf(acc[8 + i], u, (acc[i] + __uint_as_float(b[(8 + i / 4) % NUP][i & 3])) * u) : fmaf(acc[i], u, acc[8 + i]);
    }
  };
  if (ro == 0) {
#pragma unroll 1
    while (true) {
      do_export(BoolC<true>(), always);
      PROFP(3);
      if (s == 8) STAMP(6);
      float r[8];
      memproj(BoolC<false>(), 30, 0, 0.f, 0.f, r);
      sts128(t16 + SM_PART, __float_as_uint(r[0]), __float_as_uint(r[1]), __float_as_uint(r[2]), __float_as_uint(r[3]));
      sts128(t16 + SM_PART + 2048, __float_as_uint(r[4]), __float_as_uint(r[5]), __float_as_uint(r[6]), __float_as_uint(r[7]));
      bar_arrive(3, 256);
      PROF(1);
      bar_sync(9, 256);
      post_hint();
      if (w == 3 && s) publish(s);
      if (s == NSEG - 1) break;
      if (w == 1) {
        uint32_t m[8];
        lds128(t16 + SM_MAX - 512, m); lds128(t16 + SM_MAX, m + 4);
        const int em = (wexp(amax4(amax4(*(const __half2*)&m[0], m), m + 4)) >> 3) + (int)(lds32(sb + SC_UNSC + (s & 1) * 8) >> 23) - 15;
        const int ex = max(s ? em : 0, (int)lds32(sb + SC_XMAX + 4 * s)) - 127 + (int)lds32(sb + SC_EXPW);
        sts32(sb + SC_UNSC + (~s & 1) * 8, (127 + min(max(ex, -120), 120)) << 23);
        __syncwarp();
        if (elect_one()) mbar_arrive(sb + MB_S);
      }
      SCHED_FENCE(9);
      bar_sync(5, qk ? N5 : 256);
      PROF(2);
      import();
      xproj<0, 0, 18>(acc, wa, dA);
      WG_WAIT(0);
      bar_sync(10, 256);
      SCHED_FENCE(17);
      dA += (int64_t)(b2 ? XT >> 4 : -(XT >> 3));
      finish(s + ah);
      if (w != 3) bar_arrive(13, 384);
      PROF(6);
      SCHED_FENCE(14);
      bar_sync(12, 256);
      PROF(7);
      xproj<1, 0, 18, true>(acc, wa, dA);
      bar_arrive(14, 256);
      b2 = b2 == 2 ? 0 : b2 + 1;
      s++;
      if (w == 3) {
        const uint32_t slot = s < lds32(sb + SC_EPO + 4) ? s & 7 : s;
        bar_sync(13, 384);
        export_seg(s, slot);
      }
      PROFP(8);
    }
    if (!qk) bar_arrive(5, 256);
  } else {
    uint32_t km[4];
    auto send_km = [&]() {
      if (XP & (4 | 4096)) return;
      uint32_t t, u;
      lds64(sb + SC_TAG, t, u);
      t |= km[0] & ~1u; u += s * (NH * 4096);
      if (qk)
        asm volatile("{\n.reg .u32 o;\n.reg .u64 a;\nshr.u32 o, %0, 1;\nadd.u32 o, o, %1;\nmad.wide.u32 a, o, 1, %2;\nst.relaxed.gpu.global.v2.b32 [a], {%3,%4};\n}"
                     :: "r"(t16), "r"(u), "l"(g_km), "r"(t), "r"(km[1]) : "memory");
      else
        asm volatile("{\n.reg .u32 o;\n.reg .u64 a;\nadd.u32 o, %0, %1;\nmad.wide.u32 a, o, 1, %2;\nst.relaxed.gpu.global.v4.b32 [a], {%3,%4,%5,%6};\n}"
                     :: "r"(t16), "r"(u), "l"(g_km), "r"(t), "r"(km[1]), "r"(km[2]), "r"(km[3]) : "memory");
    };
#pragma unroll 1
    while (true) {
      do_export(BoolC<true>(), always);
      if (!qk && w == 2) send_v(s + 1, 0);
      PROFP(3);
      if (s == 8) STAMP(6);
      const uint32_t tl = ((t16 >> 8) ^ wg) & 1, am = (t16 & ~256u) - w * 256;
      const float un = __uint_as_float(lds32(sb + SC_UNSC + (s & 1) * 8));
      float r[8];
      if (qk) {
        uint32_t a0 = am + (tl ? SM_QM : SM_BLK + 8192 + (s & 3) * SEGB);
        float u0 = wg ? un * (SM_SCALE * LOG2E) : un, u1 = wg ? un : un * (SM_SCALE * LOG2E);
        PIN(a0); PIN(u0); PIN(u1);
        memproj(BoolC<true>(), 32, a0, u0, u1, r);
        const uint32_t p0 = pack_bf16(r[0], r[1]), p1 = pack_bf16(r[2], r[3]), p2 = pack_bf16(r[4], r[5]), p3 = pack_bf16(r[6], r[7]);
        stsm4(a0, p0, p1, p2, p3);
        bar_arrive(4, 256);
        km[0] = wg ? p2 : p0; km[1] = wg ? p3 : p1;
      } else {
        const uint32_t d0 = s < NSEG - 1 ? 0 : 2, d1 = s < NSEG - 1 ? 1 : 2;
        uint32_t r0 = mapa(t16 + SM_VM, d0), r1 = mapa(t16 + SM_VM, d1);
        PIN(r0); PIN(r1);
        memproj(BoolC<true>(), 34, r0 | r1, un, un, r);
        const uint32_t p0 = pack_bf16(r[0], r[1]), p1 = pack_bf16(r[2], r[3]), p2 = pack_bf16(r[4], r[5]), p3 = pack_bf16(r[6], r[7]);
        const uint32_t v0 = wg ? p2 : p0, v1 = wg ? p3 : p1, v2 = wg ? p0 : p2, v3 = wg ? p1 : p3;
        st_async4(r0, v0, v1, v2, v3, mapa(sb + MB_S, d0));
        st_async4(r1, v0, v1, v2, v3, mapa(sb + MB_S, d1));
        bar_arrive(5, 256);
        sts128(t16 + SM_VM, v0, v1, v2, v3);
        __syncwarp();
        if (elect_one()) mbar_arrive(sb + MB_S);
        km[0] = v0; km[1] = v1; km[2] = v2; km[3] = v3;
      }
      PROF(1);
      auto rearm = [&]() { mbar_wait(sb + MB_S, s & 1); if (elect_one()) mbar_expect(sb + MB_S, qk ? 640 + 2048 : 1280); __syncwarp(); };
      if (s == NSEG - 1 && w != 1) {
      } else if (w == 1) {
        if ((t16 & 384) == 0) stg_relaxed(tm.red + (RED_SLOT(s + 2) + RED_LINE(blockIdx.x)) + (t16 & 112), 0, 0, 0, 0);
        uint32_t base, own;
        lds64(sb + SC_EPO, base, own);
        if ((int)(lds32v(sb + SC_OFL) - base) < s - 7) sts32(sb + SC_EPO + 4, min(own, s + 1));
        if (elect_one()) bulk_load(sb + SC_OFL, tm.oflag + blockIdx.x * 128, 16, sb + MB_XS);
      } else if (w == 0) {
        const int tn = s + ah + 1;
        if (tn + 1 < NSEG && !(XP & 8) && elect_one()) {
          const int b0 = b2 == 2 ? 0 : b2 + 1;
          mbar_expect(sb + MB_X + 8 * b0, XT);
          tma_load3(sb + SM_X + b0 * XT, &tm.x, (tn + 1) * 32, sb + MB_X + 8 * b0);
        }
        if (tn < NSEG && (!(XP & 8) || tn < 3)) mbar_wait(sb + MB_X + 8 * b2, (tn / 3) & 1);
      } else if (w == 2) {
        if (!qk) send_v(s + 1, 1);
      } else {
        rearm();
      }
      __syncwarp();
      send_km();
      if (s == NSEG - 1) break;
      import();
      PROF(4);
      SCHED_FENCE(10);
      bar_sync(7, 256);
      xproj<0, 0, 18>(acc, wa, dA);
      bar_arrive(12, 256);
      dA += (int64_t)(b2 ? XT >> 4 : -(XT >> 3));
      finish(s + ah);
      if (qk && w == 0) wait_v(s + 1);
      bar_arrive(13, 384);
      PROF(6);
      SCHED_FENCE(13);
      bar_sync(14, 256);
      PROF(7);
      xproj<1, 0, 18>(acc, wa, dA);
      b2 = b2 == 2 ? 0 : b2 + 1;
      s++;
      PROFP(8);
    }
  }
  bar_arrive(0, 384);
  STAMP(3);
  cluster_sync();
  STAMP(4);
}

DI void attn_role(const uint32_t sb, unsigned char* smem_raw, const RMaps& tm, const uint32_t RANK, const bf16* __restrict__ x, const bf16* __restrict__ mem0,
                  const int w, const int lane) {
  const int t2 = w * 32 + lane;
  uint32_t wo[8][4], w1[8][4];
  const uint32_t wo_lane = sb + ((lane & 7) + ((lane >> 4) << 3)) * 128 + (((w + 4 * ((lane >> 3) & 1)) ^ (lane & 7)) << 4);
  unsigned char* const g_red = tm.red;
  {
    const uint32_t tag = *(volatile unsigned*)&g_epoch + 1;
    QSTAMP(0);
    bar_sync(0, 160);
    QSTAMP(1);
    cluster_arrive();
    __half2 hx = __float2half2_rn(0.f);
    if (t2 == 0) { sts32(sb + SC_OFL, (tag - 1) * NSEG); sts64(sb + SC_EPO, (tag - 1) * NSEG + 1, NSEG); sts64(sb + SC_TAG, tag & 1, blockIdx.x / 3 * 4096 + (RANK < 2 ? RANK * 1024 - (sb >> 1) : 2048 - sb)); sts32(sb + SC_UNSC, __float_as_uint(1.f)); sts128(sb + SC_DEAD, 0, 0, 0, 0x3f800000u); sts64(sb + SC_FPAR, 0, 0); sts128(sb + SC_ONES, 0x3f803f80u, 0x3f803f80u, 0x3f803f80u, 0x3f803f80u); }
    WSTAMP(27);
    uint32_t q[8] = {0, 0, 0, 0, 0, 0, 0, 0};
    QSTAMP(2);
    mbar_wait(sb + MB_WO3, 0);
    QSTAMP(3);
    uint32_t mv[5][4];
#pragma unroll
    for (int i = 0; i < 5; i++) {
      ldsm4(mv[i], sb + SM_M0 + (lane & 7) * (DM * 2) + min(w + 4 * i, 17) * 64 + (lane >> 3) * 16);
      if (blockIdx.x == 0) hx = amax4(hx, mv[i]);
    }
#pragma unroll
    for (int k = 0; k < 8; k++) {
      ldsm4t(wo[k], wo_lane + SM_WO3 + k * 2048); ldsm4t(w1[k], wo_lane + SM_WOST + k * 2048);
#pragma unroll
      for (int i = 0; i < 4; i++) { sq_acc(q[i], wo[k][i]); sq_acc(q[i], w1[k][i]); }
    }
    bar_sync(6, 128);
#pragma unroll
    for (int k = 0; k < 8; k++) sts128(sb + SM_WO3 + t2 * 16 + k * 2048, wo[k][0], wo[k][1], wo[k][2], wo[k][3]);
#pragma unroll
    for (int i = 0; i < 5; i++) {
      const int c = (w + 4 * i) * 32;
      if (c < DM) stsm4t(sb + SM_MEM + (c + c / 192 * 64 + lane) * 16, mv[i][0], mv[i][1], mv[i][2], mv[i][3]);
    }
    bar_arrive(1, 256); bar_arrive(2, 256); bar_arrive(9, 256);
    QSTAMP(4);
    mbar_wait(sb + MB_WO, 0);
    QSTAMP(5);
#pragma unroll
    for (int k = 0; k < 8; k++) ldsm4t(wo[k], wo_lane + SM_X + XT + k * 2048);
    fence_async();
    bar_sync(6, 128);
    if (t2 == 32) tma_load3(sb + SM_X + XT, &tm.x, 32, sb + MB_X + 8);
    __syncwarp();
#pragma unroll
    for (int k = 0; k < 8; k++)
#pragma unroll
      for (int i = 0; i < 4; i++) sq_acc(q[4 + i], wo[k][i]);
    float ss = 0.f;
#pragma unroll
    for (int i = 0; i < 8; i++) ss += bf_lo(q[i]) + bf_hi(q[i]);
    ss = warp_sum(ss);
    if (lane == 0) sts32(sb + SC_SS + 4 * (8 + w), __float_as_uint(ss));
    if (blockIdx.x < NSEG) {
      mbar_wait(sb + MB_XS, 0);
#pragma unroll
      for (int i = 0; i < 18; i++) { uint32_t v[4]; lds128(sb + SM_X + 2 * XT + t2 * 16 + i * 2048, v); hx = amax4(hx, v); }
      fence_async();
      bar_sync(6, 128);
      if (t2 == 32) tma_load3(sb + SM_X + 2 * XT, &tm.x, 64, sb + MB_X + 16);
      __syncwarp();
    }
    sts32(sb + SC_SS + 4 * (12 + w), wexp(hx));
    QSTAMP(6);
    bar_sync(11, 384);
    QSTAMP(7);
    if (t2 == 0) {
      float a[16];
#pragma unroll
      for (int i = 0; i < 4; i++) lds128f(sb + SC_SS + 16 * i, &a[4 * i]);
      stg_relaxed(&g_stats[blockIdx.x * 2], __float_as_uint(((a[0] + a[1]) + (a[2] + a[3])) + ((a[4] + a[5]) + (a[6] + a[7]))),
                  __float_as_uint((a[8] + a[9]) + (a[10] + a[11])),
                  max(max(__float_as_uint(a[12]), __float_as_uint(a[13])), max(__float_as_uint(a[14]), __float_as_uint(a[15]))), tag);
    }
    __syncwarp();
    WSTAMP(24);
    QSTAMP(8);
    cluster_wait();
    QSTAMP(9);
    if (w == 0) {
      uint4 v[3];
      int n = 0;
      while (true) {
#pragma unroll
        for (int i = 0; i < 3; i++) v[i] = ldg_relaxed(&g_stats[(i * 32 + lane) * 2]);
        if (__all_sync(0xffffffffu, v[0].w == tag && v[1].w == tag && v[2].w == tag) || ++n > SPIN_LIMIT) break;
        __nanosleep(100);
      }
      WSTAMP(25);
      QSTAMP(10);
      const float sv = warp_sum(__uint_as_float(v[0].x) + __uint_as_float(v[1].x) + __uint_as_float(v[2].x));
      const float so = warp_sum(__uint_as_float(v[0].y) + __uint_as_float(v[1].y) + __uint_as_float(v[2].y));
      const int expW = ((int)(__float_as_uint(sv) >> 23) + (int)(__float_as_uint(so) >> 23) - 254 + 2 + 10 + 1) >> 1;
      sts32(sb + SC_XMAX + 4 * lane, v[0].z); sts32(sb + SC_XMAX + 128 + 4 * lane, v[1].z);
      sts32(sb + SC_EXPW, expW + 1 - 15);
      if (blockIdx.x == 0 && lane == 0) *(volatile unsigned*)&g_epoch = tag;
      sts32(sb + SC_FPAR + 4, 1);
    } else if (w < 3) {
      const uint32_t u = blockIdx.x >> 4;
      unsigned char* const z = g_red + 98304 + (blockIdx.x & 15) * 128 + (u & 1) * 2048 + (u & 6) * 4096 + (((u >> 1) ^ w) & 1) * 4096 + lane * 4;
      stg_relaxed32(z, 0);
      uint32_t best = 0xffffffffu;
#pragma unroll 1
      for (int i = 0; i < 64; i++) {
        uint32_t dt;
        asm volatile("{\n.reg .pred p;\n.reg .u32 c, v;\nmov.u32 c, %%clock;\n"
                     "atom.relaxed.gpu.global.exch.b32 v, [%1], 0;\nsetp.eq.u32 p, v, 0;\nmov.u32 %0, 0;\n@p mov.u32 %0, %%clock;\nsub.u32 %0, %0, c;\n}"
                     : "=r"(dt) : "l"(z) : "memory");
        best = min(best, dt);
        if (lds32v(sb + SC_FPAR + 4) && i >= 1) break;
      }
      sts32(sb + SC_LAT + (w - 1) * 4, best);
    }
    QSTAMP(11);
    bar_sync(13, 384);
    bar_arrive(0, 384);
    QSTAMP(12);
    WSTAMP(26);
  }

  const uint32_t nh = __shfl_sync(0xffffffffu, near_half(sb), 0);
  uint32_t l16 = sb + lane * 16;
  PIN(l16);
#define LV ((l16 >> 4) & 31)
#define fence_reg l16
  const uint32_t red_lo = (uint32_t)(uint64_t)g_red, red_hi = (uint32_t)((uint64_t)g_red >> 32);
  uint32_t lp;
  auto slot = [&](int s, uint32_t c, uint32_t ofs) {
    const uint32_t lo = lp | (red_lo + ((w >> 1) * 4 + (w & 1) * 2 + ((w ^ c) & 1)) * 4096 + RED_SLOT(s) + ofs);
    uint64_t a; asm("mov.b64 %0, {%1, %2};" : "=l"(a) : "r"(lo), "r"(red_hi));
    return (unsigned char*)a;
  };
  const uint32_t always = __shfl_sync(0xffffffffu, lds32(sb + SC_DEAD + 12), 0);
  const int mode0 = RANK < 2 ? w : w | 4;
  auto hint_addr = [&](int s) { return min(LV, 23u) * 4 + (red_lo + HINT_OFF + nh * 4096 + w * 16384 + RED_SLOT(s)); };
  auto load_hints = [&](uint32_t lo) {
    uint64_t a; asm("mov.b64 %0, {%1, %2};" : "=l"(a) : "r"(lo), "r"(red_hi));
    return ldg_relaxed32((const void*)a);
  };
  int s = 0;
  bool bad = false;
#pragma unroll 1
  while (true) {
    const uint32_t par = s & 1;
    uint32_t vx[4][4], hints;
    auto load_vx = [&]() {
      const uint32_t va = l16 + (RANK < 2 ? SM_VC + par * 8192 : SM_BLK + (s & 3) * SEGB) + w * 1024 + ((LV >> 3) & 1) * 384 - (LV >> 4) * 128;
#pragma unroll
      for (int i = 0; i < 4; i++) ldsm4(vx[i], va + (i & 1) * 4096 + (i >> 1) * 256);
    };
    auto retire = [&](uint32_t x) {
      asm volatile("{\n.reg .pred p;\nsetp.eq.u32 p, %0, 0;\n@p exit;\n}" :: "r"(vx[0][0] | vx[1][0] | vx[2][0] | vx[3][0] | x) : "memory");
    };
    auto scores = [&](auto memkeys, auto first, float* sc) {
      constexpr bool MK = decltype(memkeys)::value, FIRST = decltype(first)::value;
      uint32_t kb[4][4], qb[2][4];
      const uint32_t m = LV >> 3;
      uint32_t kaddr = l16 + SM_BLK + 4096 + (s & 3) * SEGB + w * 2048 + (m & 1) * (MK ? 128 : 896) - (m >> 1) * 128;
      if (MK) { PIN(kaddr); }
      else {
#pragma unroll
        for (int k = 0; k < 4; k++) ldsm4t(kb[k], kaddr + k * 256);
      }
      if (FIRST) { load_vx(); retire(MK ? kaddr : kb[0][0] | kb[1][0] | kb[2][0] | kb[3][0] | l16); bar_sync(4, 256); PROF(4); }
      ldsm4t(qb[0], l16 + SM_QM);
      if (MK) ldsm4t(kb[0], kaddr);
      ldsm4t(qb[1], l16 + SM_QM + 512);
      if (MK) ldsm4t(kb[2], kaddr + 512);
      float c[4][4];
      mma16816z(c[0], kb[0], qb[0][0], qb[0][1]); mma16816z(c[1], kb[MK ? 0 : 1], qb[0][2], qb[0][3]);
      mma16816z(c[2], kb[2], qb[1][0], qb[1][1]); mma16816z(c[3], kb[MK ? 2 : 3], qb[1][2], qb[1][3]);
      if (FIRST) bar_arrive(5, N5);
#pragma unroll
      for (int i = 0; i < (MK ? 2 : 4); i++) sc[i] = ((c[0][i] + c[1][MK ? i + 2 : i]) + c[2][i]) + c[3][MK ? i + 2 : i];
    };
    auto send = [&](auto memkeys) {
      constexpr bool MK = decltype(memkeys)::value;
      constexpr int N = MK ? 1 : 2;
      const uint32_t sa = sb + LV * 4 + SM_E + (MK ? 1024 + RANK * 128 : RANK * 512 + w * 256);
      uint32_t ra[N][2], mb[N][2];
#pragma unroll
      for (int i = 0; i < N; i++)
#pragma unroll
        for (int j = 0; j < 2; j++) {
          ra[i][j] = mapa(sa + i * 128, j ? 2 : RANK ^ 1); mb[i][j] = mapa(sb + MB_S, j ? 2 : RANK ^ 1);
          PIN(ra[i][j]);
        }
      float sc[4];
      scores(memkeys, BoolC<true>(), sc);
      uint32_t e[N];
#pragma unroll
      for (int i = 0; i < N; i++) {
        e[i] = pack_bf16(ex2(sc[2 * i]), ex2(sc[2 * i + 1]));
        if (!(fmaxf(fabsf(sc[2 * i]), fabsf(sc[2 * i + 1])) <= E_LIM)) e[i] = 0x7fff7fffu;
        st_async1(ra[i][0], e[i], mb[i][0]);
        st_async1(ra[i][1], e[i], mb[i][1]);
      }
#pragma unroll
      for (int i = 0; i < N; i++) sts32(sa + i * 128, e[i]);
      __syncwarp();
      if (l16 == sb) mbar_arrive(sb + MB_S);
      PROF(5);
    };
    const int mode = bad ? 8 : mode0;
    if (mode < 2) {
      send(BoolC<false>());
    } else if (mode == 2) {
      send(BoolC<true>());
    } else if (mode == 8) {
      load_vx();
      retire(l16);
      const uint32_t fp = lds32(sb + SC_FPAR);
      bar_sync(6, 128);
      if (w == 0 && l16 == sb) { sts32(sb + SC_FPAR, fp ^ 1); mbar_expect(sb + MB_F, 3072); }
      if (RANK < 2 && w < 3) {
        float sc[4] = {0.f, 0.f, 0.f, 0.f};
        if (w < 2) scores(BoolC<false>(), BoolC<false>(), sc); else scores(BoolC<true>(), BoolC<false>(), sc);
#pragma unroll 1
        for (int r = 0; r < 3; r++)
          st_async4(mapa(l16 + SM_FB + RANK * 1536 + w * 512, r), __float_as_uint(sc[0]), __float_as_uint(sc[1]), __float_as_uint(sc[2]), __float_as_uint(sc[3]), mapa(sb + MB_F, r));
      }
      mbar_wait(sb + MB_F, fp);
      float a[12];
#pragma unroll
      for (int j = 0; j < 3; j++) {
        float b[4];
        lds128f(l16 + SM_FB + j * 512, a + 4 * j); lds128f(l16 + SM_FB + 1536 + j * 512, b);
#pragma unroll
        for (int i = 0; i < 4; i++) a[4 * j + i] += b[i];
      }
      float m0 = fmaxf(fmaxf(fmaxf(a[0], a[2]), fmaxf(a[4], a[6])), a[8]), m1 = fmaxf(fmaxf(fmaxf(a[1], a[3]), fmaxf(a[5], a[7])), a[9]);
#pragma unroll
      for (int o = 4; o < 32; o <<= 1) { m0 = fmaxf(m0, __shfl_xor_sync(0xffffffffu, m0, o)); m1 = fmaxf(m1, __shfl_xor_sync(0xffffffffu, m1, o)); }
#pragma unroll
      for (int i = 0; i < 5; i++) {
        const uint32_t ea = sb + SM_E + LV * 4 + (i < 4 ? i * 128 : 1024);
        sts32(ea, pack_bf16(ex2(a[2 * i] - m0), ex2(a[2 * i + 1] - m1)));
        sts32(ea + (i < 4 ? 512 : 128), 0x3f803f80u);
      }
      __syncwarp();
    } else {
      load_vx();
      if (mode == 3) bar_arrive(4, 256);
      retire(l16 + 1);
    }
    {
      uint32_t wa[4], wb[4], oc[4];
      constexpr int WS = 2048;
      const uint32_t w3a = l16 + SM_WO3 + w * 512;
      lds128(w3a + KP(0) * WS, wa); lds128(w3a + KP(1) * WS, wb); lds128(sb + SC_ONES, oc);
      uint32_t e[10], p[5], vm[4], ob[4];
      float o0[4], o1[4], f[3][2][4], rs[4];
      reserve2(vm); reserve2(vm + 2); reserve2(e + 8);
      hints = hint_addr(s);
      PIN(hints);
      mbar_wait(sb + MB_S, par);
      PROF(6);
      ldsm4t(e, l16 + SM_E); ldsm2t_in(e + 8, l16 + SM_E + 1024, always); ldsm4t(e + 4, l16 + SM_E + 512);
      lds128_in(vm, l16 + w * 512 + SM_VM, always);
      const float scl = __uint_as_float(lds32(sb + SC_UNSC + 8 - par * 8));
      hints = load_hints(hints);
#pragma unroll
      for (int i = 0; i < 4; i++) p[i] = mul_bf16(e[i], e[4 + i]);
      p[4] = mul_bf16(e[8], e[9]);
      mma16816z(o0, vx[0], p[0], p[1]); mma16816z(o1, vx[1], p[0], p[1]); mma16816z(rs, oc, p[0], p[1]);
      mma16816(o0, vx[2], p[2], p[3]); lds128_in(vx[2], w3a + KP(2) * WS, always);
      mma16816(o1, vx[3], p[2], p[3]); lds128_in(vx[3], w3a + KP(3) * WS, always);
      mma16816(rs, oc, p[2], p[3]);
      mma1688(o0, vm[0], vm[1], p[4]); mma1688(o1, vm[2], vm[3], p[4]); mma1688(rs, oc[0], oc[1], p[4]);
      stsm4(l16 + w * 512 + SM_OB, pack_bf16(o0[0], o0[1]), pack_bf16(o0[2], o0[3]), pack_bf16(o1[0], o1[1]), pack_bf16(o1[2], o1[3]));
      bar_sync(6, 128);
      PROF(7);
      ldsm4t_in(oc, l16 + SM_OB, always);
      bad = __any_sync(0xffffffffu, !(rs[0] + rs[1] > 0.f) && !bad);
      rs[0] *= scl; rs[1] *= scl;
      asm volatile("{\n.reg .pred p;\nsetp.ne.u32 p, %1, 0;\n@p rcp.approx.ftz.f32 %0, %0;\n}" : "+f"(rs[0]) : "r"(always));
      asm volatile("{\n.reg .pred p;\nsetp.ne.u32 p, %1, 1;\n@p rcp.approx.ftz.f32 %0, %0;\n}" : "+f"(rs[1]) : "r"(always));
      asm volatile("lop3.b32 %0, %1, %2, %3, 0xfe;" : "=r"(lp) : "r"((l16 & 128) * 2), "r"((l16 & 256) * 4), "r"(l16 & 112));
      if (bad) continue;
      ldsm4t(ob, l16 + SM_OB + 512);
      mma16816z(f[2][0], wa, oc[0], oc[1]); mma16816z(f[2][1], wb, oc[2], oc[3]);
      mma16816z(f[0][0], wo[0], oc[0], oc[1]); mma16816z(f[0][1], wo[4], oc[2], oc[3]);
      mma16816z(f[1][0], w1[0], oc[0], oc[1]); mma16816z(f[1][1], w1[4], oc[2], oc[3]);
      ldsm4t_in(oc, l16 + SM_OB + 1024, always);
      mma16816(f[2][0], vx[2], ob[0], ob[1]); lds128_in(vx[2], w3a + KP(4) * WS, always);
      mma16816(f[2][1], vx[3], ob[2], ob[3]); lds128_in(vx[3], w3a + KP(5) * WS, always);
      mma16816(f[0][0], wo[1], ob[0], ob[1]); mma16816(f[0][1], wo[5], ob[2], ob[3]);
      mma16816(f[1][0], w1[1], ob[0], ob[1]); mma16816(f[1][1], w1[5], ob[2], ob[3]);
      ldsm4t_in(ob, l16 + SM_OB + 1536, always);
      mma16816(f[0][0], wo[2], oc[0], oc[1]); mma16816(f[0][1], wo[6], oc[2], oc[3]);
      mma16816(f[2][0], vx[2], oc[0], oc[1]); lds128_in(vx[2], w3a + KP(6) * WS, always);
      mma16816(f[2][1], vx[3], oc[2], oc[3]); lds128_in(vx[3], w3a + KP(7) * WS, always);
      mma16816(f[1][0], w1[2], oc[0], oc[1]); mma16816(f[1][1], w1[6], oc[2], oc[3]);
      mma16816(f[0][0], wo[3], ob[0], ob[1]); mma16816(f[0][1], wo[7], ob[2], ob[3]);
      mma16816(f[1][0], w1[3], ob[0], ob[1]); mma16816(f[1][1], w1[7], ob[2], ob[3]);
      mma16816(f[2][0], vx[2], ob[0], ob[1]); mma16816(f[2][1], vx[3], ob[2], ob[3]);
      bar_arrive(7, 256);
      lds128_in(ob, sb + SC_DEAD, always);
      uint32_t h[3][2];
#pragma unroll
      for (int j = 0; j < 3; j++)
#pragma unroll
        for (int i = 0; i < 2; i++)
        {
          scale_sum(f[j][1][2 * i], f[j][0][2 * i], rs[0], always); scale_sum(f[j][1][2 * i + 1], f[j][0][2 * i + 1], rs[1], always);
          h[j][i] = pack_f16(f[j][1][2 * i], f[j][1][2 * i + 1]);
        }
      const uint32_t rofs = RANK * 32768;
      red_f16x8(slot(s, RANK >> 1, rofs), h[0][0], h[1][0], h[2][0], 0x3c00u);
      red_f16x8(slot(s, (RANK >> 1) ^ 1, rofs), h[0][1], h[1][1], h[2][1], 0x3c00u);
      bar_arrive(10, 256);
      SCHED_FENCE(5);
      l16 += ob[1];
    }
    {
    PROF(8);
    const uint32_t ma0 = l16 + SM_MEM + w * 128 + (LV >> 3) * 896 + nh * 512;
    const unsigned char* const sl[2] = {slot(s, nh, 0), slot(s, nh ^ 1, 0)};
    uint32_t dl = gtime() - 1984;
    uint32_t late = latest_hint(hints, dl, s);
    if (late >= 64) {
      int n = 0;
#pragma unroll 1
      do {
        hints = load_hints(hint_addr(s));
        dl = gtime() - 1984;
        late = latest_hint(hints, dl, s);
      } while (late >= 64 && ++n < SPIN_LIMIT);
    }
    dl += late * 32 + tm.poll;
    PROF(9);
    {
      auto wait_until = [&](uint32_t t) {
        asm volatile("{\n.reg .pred p;\n.reg .s32 c;\n.reg .u64 t;\nTL: mov.u64 t, %%globaltimer;\ncvt.u32.u64 c, t;\nsub.s32 c, c, %0;\nsetp.lt.s32 p, c, 0;\n@p bra.uni TL;\n}" :: "r"(t + (l16 & 15)) : "memory");
      };
      uint4 v[2][3];
      auto load = [&](int c) {
#pragma unroll
        for (int r = 0; r < 3; r++) v[c][r] = ldg_relaxed(sl[c ^ (r >> 1)] + r * 32768);
      };
      auto decode = [&](int c, int n) {
        uint32_t q[9];
        __half2 hm;
        const uint32_t ma = ma0 ^ (c * 512);
#pragma unroll
        for (int i = 0; i < 9; i++) {
          const uint32_t h = i % 3 == 0 ? v[c][i / 3].x : (i % 3 == 1 ? v[c][i / 3].y : v[c][i / 3].z);
          const float2 f = __half22float2(*(const __half2*)&h);
          q[i] = pack_bf16(f.x, f.y);
          hm = i ? __hmax2(hm, __habs2(*(const __half2*)&h)) : __habs2(*(const __half2*)&h);
        }
#pragma unroll
        for (int r = 0; r < 3; r++) stsm4(ma + r * 4096, q[3 * r], q[3 * r + 1], q[3 * r + 2], r < 2 ? v[c][r].w : *(const uint32_t*)&hm);
        const bool done = __all_sync(0xffffffffu, v[c][0].w == 0x5000u && v[c][1].w == 0x5000u && v[c][2].w == 0x5000u) || n > SPIN_LIMIT;
        asm volatile("{\n.reg .pred p;\nsetp.ne.u32 p, %0, 0;\n@p bar.arrive %1, 256;\n}" :: "r"((int)done), "r"(1 + c) : "memory");
        return done;
      };
      int n = 0;
      wait_until(dl);
      PROF(10);
#pragma unroll 1
      do {
        load(0);
        load(1);
        asm volatile("{\n.reg .pred p;\nsetp.eq.u32 p, %0, 0;\n@p bar.sync 13, 384;\n}" :: "r"(n) : "memory");
      } while (!decode(0, n++));
      PROF(11);
#pragma unroll 1
      while (!decode(1, n++)) load(1);
      bar_arrive(9, 256);
      PROF(12);
    }
    PROF(13);
    if (++s == NSEG - 1) break;
    }
  }
#undef fence_reg
  if (RANK < 2) bar_arrive(4, 256);
  bar_sync(0, 384);
  cluster_sync();
}

__global__ void __cluster_dims__(3, 1, 1) __launch_bounds__(384, 1)
rec_kernel(const __grid_constant__ RMaps tm, const bf16* __restrict__ x, const bf16* __restrict__ mem0) {
  extern __shared__ __align__(1024) unsigned char smem_raw[];
  const uint32_t sb = smem_u32(smem_raw);
  const int tid = threadIdx.x, lane = tid & 31;
  const int wg = __shfl_sync(0xffffffffu, tid >> 7, 0);
  const int w = __shfl_sync(0xffffffffu, (tid >> 5) & 3, 0);
  uint32_t rank; asm("mov.u32 %0, %%cluster_ctarank;" : "=r"(rank));
  STAMP(0);
  asm volatile("griddepcontrol.launch_dependents;" ::: "memory");
    if (tid == 0) {
      const int h = blockIdx.x / 3;
      mbar_init(sb + MB_XS, 1);
      for (int i = 0; i < 3; i++) { mbar_init(sb + MB_W + 8 * i, 1); mbar_init(sb + MB_X + 8 * i, 1); }
      mbar_init(sb + MB_WO3, 1);
      fence_async();
      load_w(sb, tm, rank, 0);
      mbar_expect(sb + MB_X, XT);
      tma_load3(sb + SM_X, &tm.x, 0, sb + MB_X);
      mbar_expect(sb + MB_WO3, 32768 + 8 * DM * 2);
      tma_load(sb + SM_WOST, &tm.wo, rank * 192 + 64, h * DH, sb + MB_WO3);
      tma_load(sb + SM_WO3, &tm.wo, rank * 192 + 128, h * DH, sb + MB_WO3);
      bulk_load(sb + SM_M0, mem0, 8 * DM * 2, sb + MB_WO3);
      load_w(sb, tm, rank, 1);
      load_w(sb, tm, rank, 2);
      mbar_init(sb + MB_WO, 1);
      mbar_init(sb + MB_S, rank < 2 ? 5 : 6);
      mbar_init(sb + MB_F, 1);
      mbar_init(sb + MB_VX, 1); mbar_init(sb + MB_VX + 8, 1);
      asm volatile("fence.mbarrier_init.release.cluster;" ::: "memory");
      fence_async();
      mbar_expect(sb + MB_X + 8, XT); mbar_expect(sb + MB_X + 16, XT);
      mbar_expect(sb + MB_WO, 16384); mbar_expect(sb + MB_XS, XT);
      mbar_expect(sb + MB_S, rank < 2 ? 640 + 2048 : 1280);
      mbar_expect(sb + MB_VX, 8192); mbar_expect(sb + MB_VX + 8, 8192);
    }
  __syncwarp();
  if (wg < 2) {
    asm volatile("setmaxnreg.inc.sync.aligned.u32 192;");
    __syncwarp();
    QSTAMP(0);
    if (tid < 32) bar_arrive(0, 160);
    QSTAMP(1);
    proj_role(sb, tm, x, rank, wg, w, lane);
  } else {
    asm volatile("setmaxnreg.dec.sync.aligned.u32 120;");
    attn_role(sb, smem_raw, tm, rank, x, mem0, w, lane);
  }
}

constexpr int NAUX = 36;
constexpr int A_ST = 6, A_STAGE = 8192 + 12288, A_W8 = A_ST * A_STAGE, A_EXC = A_W8 + A_ST * 1536, A_ROWS = 57;
constexpr int A_IN = A_EXC + 8 * 2304, A_INB = 3 * SEGB, A_OST = A_IN + 2 * A_INB, A_P = A_OST + 8192, A_G = A_P + 3072;
constexpr int A_BAR = A_G + 1024;
constexpr int A_XT = A_BAR + 1024, A_XW = A_XT;
constexpr int A_TOTAL = A_XT + 4096;
static_assert(A_IN % 1024 == 0 && A_XT % 1024 == 0 && A_IN >= 4 * XT && A_IN + 64 * DM * 2 <= A_BAR && A_TOTAL <= 232448, "side kernel shared memory");
struct AMaps { CUtensorMap x, wa, wa8, o, o3, o16, wob, woa, woa16; const unsigned char* red; uint32_t poll; };

DI void wgmma_n192_ss_nt(float* d, uint64_t da, uint64_t db, int acc) {
  asm volatile("{\n.reg .pred p;\nsetp.ne.b32 p, %98, 0;\n"
               "wgmma.mma_async.sync.aligned.m64n192k16.f32.bf16.bf16 {"
               "%0,%1,%2,%3,%4,%5,%6,%7,%8,%9,%10,%11,%12,%13,%14,%15,%16,%17,%18,%19,%20,%21,%22,%23,%24,%25,%26,%27,%28,%29,%30,%31,"
               "%32,%33,%34,%35,%36,%37,%38,%39,%40,%41,%42,%43,%44,%45,%46,%47,%48,%49,%50,%51,%52,%53,%54,%55,%56,%57,%58,%59,%60,%61,%62,%63,"
               "%64,%65,%66,%67,%68,%69,%70,%71,%72,%73,%74,%75,%76,%77,%78,%79,%80,%81,%82,%83,%84,%85,%86,%87,%88,%89,%90,%91,%92,%93,%94,%95"
               "}, %96, %97, p, 1, 1, 0, 1;\n}\n"
               : ACC8(d, 0), ACC8(d, 8), ACC8(d, 16), ACC8(d, 24), ACC8(d, 32), ACC8(d, 40), ACC8(d, 48), ACC8(d, 56),
                 ACC8(d, 64), ACC8(d, 72), ACC8(d, 80), ACC8(d, 88) : "l"(da), "l"(db), "r"(acc));
}
DI void wgmma_n24_ss_nt(float* d, uint64_t da, uint64_t db, int acc) {
  asm volatile("{\n.reg .pred p;\nsetp.ne.b32 p, %14, 0;\n"
               "wgmma.mma_async.sync.aligned.m64n24k16.f32.bf16.bf16 {%0,%1,%2,%3,%4,%5,%6,%7,%8,%9,%10,%11}, %12, %13, p, 1, 1, 0, 1;\n}\n"
               : ACC8(d, 0), "+f"(d[8]), "+f"(d[9]), "+f"(d[10]), "+f"(d[11]) : "l"(da), "l"(db), "r"(acc));
}
DI void tma_load3d(uint32_t dst, const CUtensorMap* m, int c0, int c1, int c2, uint32_t mb) {
  asm volatile("cp.async.bulk.tensor.3d.shared::cluster.global.mbarrier::complete_tx::bytes [%0], [%1, {%3, %4, %5}], [%2];"
               :: "r"(dst), "l"(m), "r"(mb), "r"(c0), "r"(c1), "r"(c2) : "memory");
}
DI uint32_t trans8(uint32_t x) { uint32_t r; asm("movmatrix.sync.aligned.m8n8.trans.b16 %0, %1;" : "=r"(r) : "r"(x)); return r; }
DI void wgmma_n40_ss(float* d, uint64_t da, uint64_t db, int acc) {
  asm volatile("{\n.reg .pred p;\nsetp.ne.b32 p, %22, 0;\n"
               "wgmma.mma_async.sync.aligned.m64n40k16.f32.bf16.bf16 {%0,%1,%2,%3,%4,%5,%6,%7,%8,%9,%10,%11,%12,%13,%14,%15,%16,%17,%18,%19}, "
               "%20, %21, p, 1, 1, 1, 1;\n}\n"
               : ACC8(d, 0), ACC8(d, 8), "+f"(d[16]), "+f"(d[17]), "+f"(d[18]), "+f"(d[19]) : "l"(da), "l"(db), "r"(acc));
}
template <int ST> DI void ldg8x64(uint32_t* m, const void* p) {
  asm volatile("ld.relaxed.gpu.global.v2.b32 {%0,%1}, [%16];\nld.relaxed.gpu.global.v2.b32 {%2,%3}, [%16 + %17];\n"
               "ld.relaxed.gpu.global.v2.b32 {%4,%5}, [%16 + %18];\nld.relaxed.gpu.global.v2.b32 {%6,%7}, [%16 + %19];\n"
               "ld.relaxed.gpu.global.v2.b32 {%8,%9}, [%16 + %20];\nld.relaxed.gpu.global.v2.b32 {%10,%11}, [%16 + %21];\n"
               "ld.relaxed.gpu.global.v2.b32 {%12,%13}, [%16 + %22];\nld.relaxed.gpu.global.v2.b32 {%14,%15}, [%16 + %23];"
               : "=r"(m[0]), "=r"(m[1]), "=r"(m[2]), "=r"(m[3]), "=r"(m[4]), "=r"(m[5]), "=r"(m[6]), "=r"(m[7]),
                 "=r"(m[8]), "=r"(m[9]), "=r"(m[10]), "=r"(m[11]), "=r"(m[12]), "=r"(m[13]), "=r"(m[14]), "=r"(m[15])
               : "l"(p), "n"(ST), "n"(2 * ST), "n"(3 * ST), "n"(4 * ST), "n"(5 * ST), "n"(6 * ST), "n"(7 * ST) : "memory");
}
template <int ST> DI void ldg4x128(uint32_t* m, const void* p) {
  asm volatile("ld.relaxed.gpu.global.v4.b32 {%0,%1,%2,%3}, [%16];\nld.relaxed.gpu.global.v4.b32 {%4,%5,%6,%7}, [%16 + %17];\n"
               "ld.relaxed.gpu.global.v4.b32 {%8,%9,%10,%11}, [%16 + %18];\nld.relaxed.gpu.global.v4.b32 {%12,%13,%14,%15}, [%16 + %19];"
               : "=r"(m[0]), "=r"(m[1]), "=r"(m[2]), "=r"(m[3]), "=r"(m[4]), "=r"(m[5]), "=r"(m[6]), "=r"(m[7]),
                 "=r"(m[8]), "=r"(m[9]), "=r"(m[10]), "=r"(m[11]), "=r"(m[12]), "=r"(m[13]), "=r"(m[14]), "=r"(m[15])
               : "l"(p), "n"(ST), "n"(2 * ST), "n"(3 * ST) : "memory");
}
template <int N, int ST> DI bool stale(const uint32_t* m, uint32_t tag) {
  uint32_t x = m[0] ^ tag;
#pragma unroll
  for (int i = 1; i < N; i++) asm("lop3.b32 %0, %0, %1, %2, 0xf6;" : "+r"(x) : "r"(m[i * ST]), "r"(tag));
  return __any_sync(0xffffffffu, x & 1);
}
DI int wait_flags(const unsigned* p, bool active, unsigned base, int seg) {
  int n = 0, m;
  while (true) {
    m = __reduce_min_sync(0xffffffffu, active ? (int)(ldg_acquire32(p) - base) : NSEG);
    if (m > seg || ++n > SPIN_LIMIT) break;
    __nanosleep((YP & 32) ? 400 : 40);
  }
  return max(m, seg + 1);
}
DI void wait_count(const unsigned* p, unsigned target) {
  int n = 0;
  unsigned v;
  while (true) {
    asm volatile("ld.acquire.gpu.global.b32 %0, [%1];" : "=r"(v) : "l"(p) : "memory");
    if ((int)(v - target) >= 0 || ++n > SPIN_LIMIT) break;
    __nanosleep(64);
  }
}
#define PACE_NEXT 1024
#define PING 60
DI bool tick_wait(uint32_t pace, int step) {
  const int n = lds32v(pace);
  if (n <= step) mbar_wait(pace + 8, n & 1);
  return n <= step;
}
DI void sleep_until(uint32_t t) {
  for (int n = 0; n < 64; n++) {
    const int r = t - gtime();
    if (r <= 0) break;
    __nanosleep(r >> 1);
  }
}
DI void aux_barrier(int i, unsigned epoch) {
  asm volatile("fence.proxy.async;" ::: "memory");
  asm volatile("red.release.gpu.global.add.u32 [%0], 1;" :: "l"(&g_abar[i * 32]) : "memory");
  wait_count(&g_abar[i * 32], NAUX * (epoch + 1));
  asm volatile("fence.proxy.async;" ::: "memory");
}

__global__ void __launch_bounds__(512, 1)
aux_kernel(const __grid_constant__ AMaps tm, const bf16* __restrict__ x, const bf16* __restrict__ gate_w, bf16* __restrict__ out) {
  extern __shared__ __align__(1024) unsigned char smem_raw[];
  const uint32_t sb = smem_u32(smem_raw);
  const uint32_t full1 = sb + A_BAR, empty1 = full1 + 8 * A_ST, fullw = empty1 + 8 * A_ST, full3 = fullw + 16, empty3 = full3 + 32,
                 fulla = empty3 + 32, emptya = fulla + 32, fullg = emptya + 16, pace = fullg + 8;
  const int tid = threadIdx.x, lane = tid & 31, cta = blockIdx.x;
  const int wg = __shfl_sync(0xffffffffu, tid >> 7, 0), w = __shfl_sync(0xffffffffu, (tid >> 5) & 3, 0);
  ASTAMP(14);
  const unsigned epoch = *(volatile unsigned*)&g_epoch2;
  if (tid == 0) {
    for (int i = 0; i < A_ST; i++) { mbar_init(full1 + 8 * i, 1); mbar_init(empty1 + 8 * i, 8); }
    mbar_init(fullw, 1); mbar_init(fullw + 8, 1); mbar_init(fullg, 1);
    for (int i = 0; i < 2; i++) { mbar_init(fulla + 16 * i, 2); mbar_init(fulla + 16 * i + 8, 1); mbar_init(emptya + 8 * i, 4); }
    sts64(pace, 0, 0); mbar_init(pace + 8, 1); sts32(pace + 16, 0); sts64(pace + 24, 65536, 0xffff0000u);
    for (int i = 0; i < 4; i++) { mbar_init(full3 + 8 * i, 1); mbar_init(empty3 + 8 * i, cta < NH ? 8 : 4); }
    fence_async();
  }
  auto load_a = [&](int st, int k, int col) {
    mbar_expect(full1 + 8 * st, A_STAGE + 1536);
    tma_load3d(sb + st * A_STAGE, &tm.x, k, (cta >> 1) * A_ROWS - 7, 0, full1 + 8 * st);
    tma_load3d(sb + st * A_STAGE + 8192, &tm.wa, col, k, 0, full1 + 8 * st);
    tma_load3d(sb + A_W8 + st * 1536, &tm.wa8, col + 64, k, 0, full1 + 8 * st);
  };
  __syncthreads();
  ASTAMP(0);
  const bool wide = cta < NH;
  auto p3_ks = [&](int g) { return wide ? cta >> 2 : 2 * (cta - NH) + g; };
  auto p3_mt = [&](int g) { return wide ? 2 * (cta & 3) + g : 8; };
  const unsigned fbase = epoch * NSEG;
  if (wg == 3) {
    asm volatile("setmaxnreg.dec.sync.aligned.u32 48;");
    if (w == 1 && cta < NH) {
      if (lane < 3) stg_relaxed32(&g_cflag[(cta * 3 + lane) * 32], fbase);
      bar_arrive(5, 160);
#pragma unroll 1
      for (int seg = 0; seg < ((XP & 2048) ? 0 : NSEG); seg++) {
        bar_sync(4, 160);
        if (QM & 16) tick_wait(pace, seg + 1);
        if (elect_one()) {
          fence_async();
          if (!(YP & 2)) {
            tma_store(&tm.o, sb + A_OST, cta * DH, seg * 32);
            tma_store(&tm.o, sb + A_OST + 4096, cta * DH + 64, seg * 32);
          }
          asm volatile("cp.async.bulk.commit_group;" ::: "memory");
          asm volatile("cp.async.bulk.wait_group.read 0;" ::: "memory");
        }
        __syncwarp();
        if (seg < NSEG - 1) bar_arrive(5, 160);
        if (elect_one()) {
          asm volatile("cp.async.bulk.wait_group 0;" ::: "memory");
          TSTAMP(2);
          stg_relaxed32(&g_oflag[cta * 32], fbase + seg + 1);
        }
        __syncwarp();
        if (lane < 3) stg_relaxed32(&g_cflag[(cta * 3 + lane) * 32], fbase + seg + 1);
      }
    }
    if (w == 2 && cta < NH) {
      const uint32_t ktag = (epoch + 1) & 1, ma = sb + A_IN + 8192 + lane * 16;
      int avail = 0;
      int own = 0;
      bar_sync(10, 64);
#pragma unroll 1
      for (int seg = 0; seg < ((XP & 2048) ? 0 : NSEG); seg++) {
        if (avail <= seg) {
          int n = 0;
          while (true) {
            asm volatile("ld.acquire.gpu.global.v2.b32 {%0,%1}, [%2];" : "=r"(avail), "=r"(own) : "l"(&g_sflag[(cta * 3 + min(lane, 2)) * 4]) : "memory");
            avail = __reduce_min_sync(0xffffffffu, (int)(avail - fbase));
            if (avail > seg || ++n > SPIN_LIMIT) break;
            __nanosleep(40);
          }
        }
        if (QM & 8) tick_wait(pace, seg);
        TSTAMP(0);
        const unsigned char* km = g_km + (size_t)(seg * NH + cta) * 4096 + lane * 8;
        uint32_t m[16];
        const float g = __ldcg(&g_gate[seg * 32 + lane]);
        ldg8x64<256>(m, km);
        const uint32_t b = seg & 1, full = fulla + 16 * b, mb = ma + b * A_INB;
        mbar_wait(emptya + 8 * b, (~seg >> 1) & 1);
        if (lane < 2) mbar_expect(full + 8 * lane, (YP & 8) ? 0 : 16384 >> lane);
        __syncwarp();
        const int slot = seg < own ? seg & 7 : seg;
        if (lane < 3 && !(YP & 8)) bulk_load(sb + A_IN + b * A_INB + lane * SEGB, g_seg + ((size_t)slot * 96 + cta * 3 + lane) * 8192, 8192, full + (lane & 2) * 4);
        int n = 0;
#pragma unroll 1
        while (stale<8, 2>(m, ktag) && ++n < SPIN_LIMIT) { if (seg < NSEG - 1) __nanosleep(200); ldg8x64<256>(m, km); }
        TSTAMP(1);
#pragma unroll
        for (int i = 0; i < 4; i++) stsm4(mb + (i >> 1) * SEGB + (i & 1) * 512, m[4 * i], m[4 * i + 1], m[4 * i + 2], m[4 * i + 3]);
        sts32(sb + A_G + b * 128 + lane * 4, __float_as_uint(1.f - g));
        fence_async();
        __syncwarp();
        if (lane == 0) mbar_arrive(full);
      }
    }
    if (w == 3 && QM) {
      const unsigned char* const hp = tm.red + HINT_OFF + 65536 + (cta & 1) * 4096 + min(lane, 23) * 4;
      uint32_t d = 0;
      int s = 0, n = 0;
#pragma unroll 1
      while (s < NSEG - 1) {
        const uint32_t h = ldg_relaxed32(hp + RED_SLOT(s)), t = (gtime() - 1984) & ~31u, late = latest_hint(h, t, s);
        if (late < 64) {
          d = t + late * 32 + tm.poll;
          sleep_until(d);
          s++; n = 0;
          if (lane == 0) { mbar_arrive(pace + 8); sts64(pace, s < NSEG - 1 ? s : 2 * NSEG, d); }
          sleep_until(d + PACE_NEXT);
        } else {
          if (++n > (s ? 16 : 256) || lds32v(pace + 16)) break;
          if (!s) __nanosleep(100);
        }
      }
      if (s < NSEG - 1 && lane == 0) { mbar_arrive(pace + 8); sts64(pace, 2 * NSEG, d); }
    }
    if (w != 0) return;
    const bool lead = lane == 0;
#pragma unroll 1
    for (int it = 0, st = 0, ph = 1, k = 0, col = (cta & 1) * (DM / 2); it < ((XP & 256) ? 0 : 72); it++) {
      mbar_wait(empty1 + 8 * st, ph);
      if (elect_one()) load_a(st, k, col);
      __syncwarp();
      if (++st == A_ST) { st = 0; ph ^= 1; }
      k += 32;
      if (k == DM) { k = 0; col += 72; }
    }
    auto load_wo = [&](uint32_t dst, int g, int kb, uint32_t mb) {
      if (kb < 64) tma_load(dst, &tm.wob, p3_mt(g) * 64, kb * 64, mb);
      else tma_load(dst, &tm.woa, p3_mt(g) * 64, (kb - 64) * 64, mb);
    };
    if (lead) mbar_expect(fullw, 16 * 8192);
#pragma unroll 1
    for (int st = 0; st < A_ST; st++) {
      if (!(XP & 256)) mbar_wait(empty1 + 8 * st, 1);
      if (lane < 16 && min(((lane + 1) * 8192 - 1) / A_STAGE, A_ST - 1) == st) load_wo(sb + lane * 8192, lane >> 3, p3_ks(lane >> 3) * 9 + (lane & 7), fullw);
      __syncwarp();
    }
    __syncwarp(); bar_sync(6, 288);
    if (lead) mbar_expect(fullw + 8, 2 * 8192 + (p3_ks(0) >= 4 ? 4096 : 0));
    __syncwarp();
    if (lane < 2) {
      load_wo(sb + (16 + lane) * 8192, lane, p3_ks(lane) * 9 + 8, fullw + 8);
      if (p3_ks(0) >= 4) tma_load(sb + A_XW + lane * 2048, &tm.woa16, p3_mt(lane) * 64, 448 + p3_ks(lane) * 16, fullw + 8);
    }
    __syncwarp();
    if (lead) aux_barrier(1, epoch);
    __syncwarp(); bar_sync(6, 288);
    {
      int avail = 0, sl = 0, ph = 1;
      const int h = (9 * p3_ks(0) >> 1) + lane;
#pragma unroll 1
      for (int seg = 0; seg < ((XP & 2048) ? 0 : NSEG); seg++) {
        if (avail <= seg) avail = wait_flags(&g_oflag[min(h, NH - 1) * 32], lane < (wide ? 5 : 9), fbase, seg);
        SSTAMP(seg, 4);
        for (int g = 0; g < (wide ? 1 : 2); g++) {
          const int ks = p3_ks(g);
          mbar_wait(empty3 + 8 * sl, ph);
          if ((QM & 4) && tick_wait(pace, seg + (QM >> 4 & 1) + 1)) __nanosleep(100);
          if (YP & 4) { if (lead) mbar_arrive(full3 + 8 * sl); }
          else if (elect_one()) {
            mbar_expect(full3 + 8 * sl, XT + (ks >= 4 ? 1024 : 0));
            tma_load3d(sb + sl * XT, &tm.o3, 0, seg * 32, ks * 9, full3 + 8 * sl);
            if (ks >= 4) tma_load(sb + A_XT + sl * 1024, &tm.o16, 72 * 64 - 64 + ks * 16, seg * 32, full3 + 8 * sl);
          }
          __syncwarp();
          if (++sl == (wide ? 3 : 4)) { sl = 0; ph ^= 1; }
        }
      }
    }
    sts32(pace + 16, 1);
    asm volatile("griddepcontrol.wait;" ::: "memory");
  } else if (wg == 2) {
    asm volatile("setmaxnreg.dec.sync.aligned.u32 64;");
    if (cta < NH) {
      if (tid == 256) { mbar_expect(fullg, 64 * DM * 2); bulk_load(sb + A_IN, x + cta * 64 * DM, 64 * DM * 2, fullg); }
      uint32_t gw[9];
#pragma unroll
      for (int j = 0; j < 9; j++) gw[j] = ((const uint32_t*)gate_w)[j * 32 + lane];
      mbar_wait(fullg, 0);
      float mine = 0.f;
#pragma unroll 4
      for (int u = 0; u < 16; u++) {
        float d0 = 0.f, d1 = 0.f;
#pragma unroll
        for (int j = 0; j < 9; j++) {
          const uint32_t a = lds32(sb + A_IN + (w * 16 + u) * (DM * 2) + j * 128 + lane * 4);
          d0 = fmaf(bf_lo(a), bf_lo(gw[j]), d0); d1 = fmaf(bf_hi(a), bf_hi(gw[j]), d1);
        }
        d0 = warp_sum(d0 + d1);
        if (lane == u) mine = d0;
      }
      if (lane < 16) g_gate[cta * 64 + w * 16 + lane] = 1.f / (1.f + __expf(-mine));
      fence_async();
    }
    bar_sync(3, 128);
    if (tid == 256) { aux_barrier(0, epoch); if (cta == 0) *(volatile unsigned*)&g_epoch2 = epoch + 1; }
    __syncwarp();
    bar_sync(3, 128);
    if (w == 0) bar_arrive(8, 288);
    if (w == 1 && cta < NH) bar_arrive(10, 64);
    if (cta < NH) {
      CDECL;
#pragma unroll 1
      for (int seg = 0; seg < ((XP & 2048) ? 0 : NSEG); seg++) {
        CSTAMP(0);
        const uint32_t in = sb + A_IN + (seg & 1) * A_INB;
        const uint64_t qd = make_desc(in, 128, 1024, 0);
        mbar_wait(fulla + 16 * (seg & 1), (seg >> 1) & 1);
        CSTAMP(3);
        SSTAMP(seg, 0);
        float d[2][16];
        {
          float a[20];
          uint32_t vm[16];
          const unsigned char* vp = g_km + (size_t)(seg * NH + cta) * 4096 + 2048 + lane * 16;
          if (w == 3) ldg4x128<512>(vm, vp);
          WG_FENCE();
#pragma unroll
          for (int k = 0; k < ((YP & 16) ? 1 : 8); k++) wgmma_n40_ss(a, qd + ((k >> 2) * SEGB + (k & 3) * 256 >> 4), qd + ((k >> 2) * SEGB + (k & 3) * 256 + 4096 >> 4), k > 0);
          const uint32_t ga = sb + A_G + (seg & 1) * 128 + (w & 1) * 64 + (lane >> 2) * 4;
          const float f0 = __uint_as_float(lds32(ga)), f1 = __uint_as_float(lds32(ga + 32));
          WG_COMMIT();
          WG_WAIT(0);
          CSTAMP(5);
          SSTAMP(seg, 1);
          if (w < 2) {
            const int lim = w * 16 + (lane >> 2) - 2 * (lane & 3);
            float m0 = -3.0e38f, m1 = -3.0e38f;
#pragma unroll
            for (int i = 0; i < 20; i++) {
              if (i < 16 && (i >> 2) * 8 + (i & 1) - (i & 2) * 4 > lim) a[i] = -1.0e9f / SM_SCALE;
              if (i & 2) m1 = fmaxf(m1, a[i]); else m0 = fmaxf(m0, a[i]);
            }
#pragma unroll
            for (int o = 1; o < 4; o <<= 1) { m0 = fmaxf(m0, __shfl_xor_sync(0xffffffffu, m0, o)); m1 = fmaxf(m1, __shfl_xor_sync(0xffffffffu, m1, o)); }
#pragma unroll
            for (int i = 0; i < 20; i++) a[i] = ex2((a[i] - (i & 2 ? m1 : m0)) * (SM_SCALE * LOG2E));
            float s0 = ((a[0] + a[1]) + (a[4] + a[5])) + ((a[8] + a[9]) + (a[12] + a[13])) + (a[16] + a[17]);
            float s1 = ((a[2] + a[3]) + (a[6] + a[7])) + ((a[10] + a[11]) + (a[14] + a[15])) + (a[18] + a[19]);
#pragma unroll
            for (int o = 1; o < 4; o <<= 1) { s0 += __shfl_xor_sync(0xffffffffu, s0, o); s1 += __shfl_xor_sync(0xffffffffu, s1, o); }
            s0 = f0 * rcp(s0); s1 = f1 * rcp(s1);
            uint32_t p[10];
#pragma unroll
            for (int i = 0; i < 10; i++) p[i] = pack_bf16(a[2 * i] * (i & 1 ? s1 : s0), a[2 * i + 1] * (i & 1 ? s1 : s0));
            const uint32_t pa = sb + A_P + (2 * w + ((lane >> 3) & 1)) * 768 + (lane >> 4) * 128 + (lane & 7) * 16;
            stsm4t(pa, p[0], p[1], p[2], p[3]); stsm4t(pa + 256, p[4], p[5], p[6], p[7]); stsm4t(pa + 512, p[8], p[9], 0, 0);
            CSTAMP(6);
            fence_async();
            CSTAMP(7);
          } else if (w == 3) {
            int n = 0;
#pragma unroll 1
            while (stale<4, 4>(vm, (epoch + 1) & 1) && ++n < SPIN_LIMIT) ldg4x128<512>(vm, vp);
#pragma unroll
            for (int i = 0; i < 4; i++) stsm4(in + 2 * SEGB + 8192 + (lane >> 4) * 1024 + (lane & 15) * 16 + i * 256, vm[4 * i], vm[4 * i + 1], vm[4 * i + 2], vm[4 * i + 3]);
            fence_async();
            mbar_wait(fulla + 16 * (seg & 1) + 8, (seg >> 1) & 1);
          }
        }
        CSTAMP(8);

        bar_sync(5, 160);
        CSTAMP(10);
        SSTAMP(seg, 2);
        const uint64_t pd = make_desc(sb + A_P, 128, 768, 0), vd = make_desc(in + 2 * SEGB, 128, 512, 0), md = make_desc(in + 2 * SEGB + 8192, 0, 128, 0);
        WG_FENCE();
#pragma unroll
        for (int i = 0; i < 2; i++) {
          wgmma_n32_ss<0>(d[i], vd + i * 256, pd, 0);
          wgmma_n32_ss<0>(d[i], vd + i * 256 + 16, pd + 16, 1);
          wgmma_n32_ss<0>(d[i], md + i * 64, pd + 32, 1);
        }
        WG_COMMIT();
        WG_WAIT(0);
        CSTAMP(11);
        if (lane == 0) mbar_arrive(emptya + 8 * (seg & 1));
#pragma unroll
        for (int i = 0; i < 2; i++) {
          const uint32_t oa = sb + A_OST + i * 4096 + ((lane & 7) + ((lane >> 4) << 3)) * 128 + (((2 * w + ((lane >> 3) & 1)) ^ (lane & 7)) << 4);
          stsm4t(oa, pack_bf16(d[i][0], d[i][1]), pack_bf16(d[i][2], d[i][3]), pack_bf16(d[i][4], d[i][5]), pack_bf16(d[i][6], d[i][7]));
          stsm4t(oa + 2048, pack_bf16(d[i][8], d[i][9]), pack_bf16(d[i][10], d[i][11]), pack_bf16(d[i][12], d[i][13]), pack_bf16(d[i][14], d[i][15]));
        }
        CSTAMP(12);
        bar_sync(4, 160);
        SSTAMP(seg, 3);
      }
      CDUMP;
    }
  } else {
    asm volatile("setmaxnreg.inc.sync.aligned.u32 200;");
    {
      const int g = lane >> 2, t = lane & 3, r0 = (cta >> 1) * A_ROWS - 7 + w * 16;
      const uint32_t prev = (2 * t > g ? 0xffffu : 0u) | (2 * t + 1 > g ? 0xffff0000u : 0u);
      const int k0 = r0 + 2 * t - (2 * t > g ? 8 : 0), k1 = r0 + 2 * t + 1 - (2 * t + 1 > g ? 8 : 0);
      const uint32_t slot = sb + A_EXC + (wg * 4 + w) * 2304;
      float gl = 0.f, gh = 0.f;
      int st = 0, ph = 0;
#pragma unroll 1
      for (int p = 0; p < ((XP & 256) ? 0 : 4); p++) {
        float big[96], sml[12];
        if (p == 3 && tid < 18) {
          const int kb = p3_ks(tid >= 9) * 9 + tid % 9;
          tma_prefetch(kb < 64 ? &tm.wob : &tm.woa, p3_mt(tid >= 9) * 64, (kb & 63) * 64);
        }
        __syncwarp();
#pragma unroll
        for (int i = 0; i < 96; i++) big[i] = 0.f;
#pragma unroll
        for (int i = 0; i < 12; i++) sml[i] = 0.f;
#pragma unroll 1
        for (int k = 0; k < 18; k++) {
          mbar_wait(full1 + 8 * st, ph);
          const uint64_t da = make_desc(sb + st * A_STAGE + wg * 4096, 16, 512, 2);
          const uint64_t db = make_desc(sb + st * A_STAGE + 8192, 4096, 1024, 1), dc = make_desc(sb + A_W8 + st * 1536, 128, 512, 0);
          WG_FENCE();
#pragma unroll
          for (int j = 0; j < 2; j++) { wgmma_n192_ss_nt(big, da + j * 2, db + j * 128, 1); wgmma_n24_ss_nt(sml, da + j * 2, dc + j * 16, 1); }
          WG_COMMIT();
          WG_WAIT(1);
          if (k > 0 && lane == 0) mbar_arrive(empty1 + 8 * (st ? st - 1 : A_ST - 1));
          if (++st == A_ST) { st = 0; ph ^= 1; }
        }
        WG_WAIT(0);
        ASTAMP(16 + p + wg * 16);
        if (lane == 0) mbar_arrive(empty1 + 8 * (st ? st - 1 : A_ST - 1));
        uint32_t f[3][9][2];
#pragma unroll
        for (int c = 0; c < 3; c++)
#pragma unroll
          for (int j = 0; j < 9; j++)
#pragma unroll
            for (int i = 0; i < 2; i++) {
              const float* a = j < 8 ? &big[(c * 8 + j) * 4 + 2 * i] : &sml[c * 4 + 2 * i];
              f[c][j][i] = c < 2 ? pack_bf16(a[0], a[1]) : trans8(pack_bf16(a[0], a[1]));
            }
        if (p == 0) {
          bar_sync(8, 288);
          gl = __ldcg(&g_gate[min(max(r0 + g, 0), S_LEN / 2 - 1) * 2 + wg]); gh = __ldcg(&g_gate[min(max(r0 + g + 8, 0), S_LEN / 2 - 1) * 2 + wg]);
        }
        asm volatile("cp.async.bulk.wait_group.read 0;" ::: "memory");
        __syncwarp();
#pragma unroll
        for (int j = 0; j < 8; j += 2) sts128(slot + j * 256 + lane * 16, f[1][j][1], f[2][j][1], f[1][j + 1][1], f[2][j + 1][1]);
        sts64(slot + 2048 + lane * 8, f[1][8][1], f[2][8][1]);
        bar_sync(1 + wg, 128);
        ASTAMP(24 + p + wg * 16);
        uint32_t pv[9][2];
#pragma unroll
        for (int j = 0; j < 9; j++) pv[j][0] = pv[j][1] = 0;
        if (w) {
#pragma unroll
          for (int j = 0; j < 8; j += 2) lds128(slot - 2304 + j * 256 + lane * 16, pv[j]);
          lds64(slot - 256 + lane * 8, pv[8][0], pv[8][1]);
        }
        float a[4][4], m[4][2];
#pragma unroll
        for (int h = 0; h < 4; h++) {
          const int j = 2 * h;
          const uint32_t qa[4] = {t >= h ? f[0][j][0] : 0, t >= h ? f[0][j][1] : 0, f[0][j + 1][0], f[0][j + 1][1]};
          const uint32_t qb0 = t <= h ? f[0][j + 2][0] : 0, qb1 = t <= h ? f[0][j + 2][1] : 0;
          float s0[4], s1[4], s2[4];
          mma16816z(s1, qa, f[1][j][0], f[1][j + 1][0]); mma16816z(s2, qa, f[1][j][1], f[1][j + 1][1]); mma16816z(s0, qa, pv[j][0], pv[j + 1][0]);
          mma1688(s1, qb0, qb1, f[1][j + 2][0]); mma1688(s2, qb0, qb1, f[1][j + 2][1]); mma1688(s0, qb0, qb1, pv[j + 2][0]);
          a[h][0] = 2 * t > g ? s0[0] : s1[0]; a[h][1] = 2 * t + 1 > g ? s0[1] : s1[1]; a[h][2] = 2 * t > g ? s1[2] : s2[2]; a[h][3] = 2 * t + 1 > g ? s1[3] : s2[3];
        }
#pragma unroll
        for (int h = 0; h < 4; h++) {
#pragma unroll
          for (int i = 0; i < 4; i++) a[h][i] = (i & 1 ? k1 : k0) + (i & 2) * 4 >= 0 ? a[h][i] * (0.23570226039551584f * LOG2E) : -1.0e9f * LOG2E;
          m[h][0] = fmaxf(a[h][0], a[h][1]); m[h][1] = fmaxf(a[h][2], a[h][3]);
        }
#pragma unroll
        for (int x = 1; x < 4; x <<= 1)
#pragma unroll
          for (int i = 0; i < 8; i++) m[i >> 1][i & 1] = fmaxf(m[i >> 1][i & 1], __shfl_xor_sync(0xffffffffu, m[i >> 1][i & 1], x));
#pragma unroll
        for (int h = 0; h < 4; h++) {
#pragma unroll
          for (int i = 0; i < 4; i++) a[h][i] = ex2(a[h][i] - m[h][i >> 1]);
          m[h][0] = a[h][0] + a[h][1]; m[h][1] = a[h][2] + a[h][3];
        }
#pragma unroll
        for (int x = 1; x < 4; x <<= 1)
#pragma unroll
          for (int i = 0; i < 8; i++) m[i >> 1][i & 1] += __shfl_xor_sync(0xffffffffu, m[i >> 1][i & 1], x);
        uint32_t o[9][2];
#pragma unroll
        for (int h = 0; h < 4; h++) {
          const int j = 2 * h;
          const float z0 = gl * rcp(m[h][0]), z1 = gh * rcp(m[h][1]);
          const uint32_t pl = pack_bf16(a[h][0] * z0, a[h][1] * z0), pu = pack_bf16(a[h][2] * z1, a[h][3] * z1);
          const uint32_t pa[4] = {pl & prev, 0, pl & ~prev, pu & prev};
          float d[3][4];
#pragma unroll
          for (int i = 0; i < 3; i++) mma16816z(d[i], pa, pv[j + i][1], f[2][j + i][0]);
#pragma unroll
          for (int i = 0; i < 3; i++) mma1688(d[i], 0, pu & ~prev, f[2][j + i][1]);
#pragma unroll
          for (int i = 0; i < 3; i++) {
            const uint32_t d0 = pack_bf16(d[i][0], d[i][1]), d1 = pack_bf16(d[i][2], d[i][3]);
            o[j + i][0] = i == 0 && h > 0 && t < h ? o[j][0] : d0;
            o[j + i][1] = i == 0 && h > 0 && t < h ? o[j][1] : d1;
          }
        }
        ASTAMP(28 + p + wg * 16);
        bar_sync(1 + wg, 128);
        const uint32_t oa = slot + (lane & 15) * 144 + (lane >> 4) * 16;
#pragma unroll
        for (int j = 0; j < 8; j += 2) stsm4(oa + j * 16, o[j][0], o[j][1], o[j + 1][0], o[j + 1][1]);
        asm volatile("stmatrix.sync.aligned.m8n8.x2.shared.b16 [%0], {%1,%2};" :: "r"(oa + 128), "r"(o[8][0]), "r"(o[8][1]) : "memory");
        fence_async();
        __syncwarp();
        if (lane < 16 && w * 16 + lane >= 7 && r0 + lane < S_LEN / 2)
          asm volatile("cp.async.bulk.global.shared::cta.bulk_group [%0], [%1], 144;"
                       :: "l"(g_Ocat + (size_t)((r0 + lane) * 2 + wg) * KCAT + 4096 + (cta & 1) * (DM / 2) + p * 72), "r"(slot + lane * 144) : "memory");
        asm volatile("cp.async.bulk.commit_group;" ::: "memory");
        ASTAMP(20 + p + wg * 16);
      }
      if (XP & 256) bar_sync(8, 288);
      asm volatile("cp.async.bulk.wait_group 0;" ::: "memory");
    }
    ASTAMP(3);
    bar_arrive(6, 288);
    uint32_t wa[37][4];
    mbar_wait(fullw, 0);
    const uint32_t la = sb + ((lane & 7) + ((lane >> 4) << 3)) * 128 + (((2 * w + ((lane >> 3) & 1)) ^ (lane & 7)) << 4);
#pragma unroll
    for (int k = 0; k < 32; k++) ldsm4t(wa[k], la + wg * 65536 + k * 2048);
    mbar_wait(fullw + 8, 0);
#pragma unroll
    for (int k = 32; k < 36; k++) ldsm4t(wa[k], la + wg * 8192 + 65536 + k * 2048);
    ldsm4t(wa[36], la + A_XW + wg * 2048);
    fence_async();
    bar_arrive(6, 288);
    ASTAMP(4);
    const int ks = p3_ks(wg), mt = p3_mt(wg);
    uint32_t v[16];
    auto fetch = [&](int seg) { ldg8x64<1024>(v, g_part + (((seg & 7) * 9 + mt) * 4 + (ks & 3)) * 1024 + (tid & 127)); };
    auto finish = [&](int seg) {
      const uint32_t tagv = (~seg >> 3) & 1;
      int n = 0;
#pragma unroll 1
      while (!(YP & 512) && stale<8, 2>(v, tagv) && ++n < SPIN_LIMIT) {
        if (seg < NSEG - 2) __nanosleep(100);
        fetch(seg);
      }
      float own[4] = {bf_lo(v[0]), bf_hi(v[0]), bf_lo(v[1]), bf_hi(v[1])};
#pragma unroll
      for (int j = 1; j < 8; j++) { own[0] += bf_lo(v[2 * j]); own[1] += bf_hi(v[2 * j]); own[2] += bf_lo(v[2 * j + 1]); own[3] += bf_hi(v[2 * j + 1]); }
      uint32_t p0 = pack_bf16(own[0], own[1]), p1 = pack_bf16(own[2], own[3]);
      asm volatile("movmatrix.sync.aligned.m8n8.trans.b16 %0, %0;" : "+r"(p0));
      asm volatile("movmatrix.sync.aligned.m8n8.trans.b16 %0, %0;" : "+r"(p1));
      const uint32_t r2 = __shfl_xor_sync(0xffffffffu, lane & 2 ? p0 : p1, 2);
      if (lane & 2) p0 = r2; else p1 = r2;
      const uint32_t r1 = __shfl_xor_sync(0xffffffffu, lane & 1 ? p0 : p1, 1);
      if (lane & 1) p0 = r1; else p1 = r1;
      if (!(YP & 256) || p0 == 0x12345678)
        *((uint2*)(out + (size_t)(seg * 32 + (ks & 3) * 8 + (lane >> 2)) * DM + mt * 64 + w * 16) + (lane & 3)) = make_uint2(p0, p1);
      SSTAMP(seg, 7);
    };
    float acc[16];
#pragma unroll
    for (int i = 0; i < 16; i++) acc[i] = 0.f;
    int pend = -1, sl = wide ? 0 : wg, ph = 0;
    if (PING && wg) bar_arrive(1, 256);
    CDECL;
    auto run = [&](auto extra) {
#pragma unroll 1
    for (int seg = 0; seg <= ((XP & 2048) ? -1 : NSEG); seg++) {
      CSTAMP(0);
      const bool fin = pend >= 0 && (seg - pend >= 2 || seg == NSEG);
      if (seg < NSEG) mbar_wait(full3 + 8 * sl, ph);
      if (fin) fetch(pend);
      CSTAMP(1);
      if (seg < NSEG) {
      if (wg) SSTAMP(seg, 5);
      if (seg < PING) bar_sync(1 + wg, 256);
      CSTAMP(7);
      const uint64_t db = make_desc(sb + sl * XT, 16, 1024, 1);
      WG_FENCE();
#pragma unroll
      for (int k = 0; k < ((XP & 1024) ? 1 : 36); k++) wgmma_n32_rs(acc, wa[k][0], wa[k][1], wa[k][2], wa[k][3], db + (k >> 2) * 256 + (k & 3) * 2, k);
      if (decltype(extra)::value) wgmma_n32_rs(acc, wa[36][0], wa[36][1], wa[36][2], wa[36][3], make_desc(sb + A_XT + sl * 1024, 16, 256, 3), 1);
      WG_COMMIT();
      if (seg < PING) bar_arrive(2 - wg, 256);
      CSTAMP(2);
      CSTAMP(3);
      WG_WAIT(0);
      CSTAMP(4);
      if (wg) SSTAMP(seg, 6);
      if (lane == 0) mbar_arrive(empty3 + 8 * sl);
      sl += wide ? 1 : 2;
      if (sl >= (wide ? 3 : 4)) { sl -= wide ? 3 : 4; ph ^= 1; }
      uint2* dst = g_part + (((seg & 7) * 9 + mt) * 32 + ks) * 128 + (tid & 127);
      uint32_t q[8];
#pragma unroll
      for (int j = 0; j < 8; j++) q[j] = j & 1 ? pack_bf16(acc[2 * j], acc[2 * j + 1]) : (pack_bf16(acc[2 * j], acc[2 * j + 1]) & ~1u) | ((~seg >> 3) & 1);
      if (QM & 32) tick_wait(pace, seg + (QM >> 4 & 1) + 2);
      if (!(YP & 1025) || q[0] == 0x12345678)
      asm volatile("st.relaxed.gpu.global.v2.b32 [%0], {%1,%2};\nst.relaxed.gpu.global.v2.b32 [%0 + 8192], {%3,%4};\n"
                   "st.relaxed.gpu.global.v2.b32 [%0 + 16384], {%5,%6};\nst.relaxed.gpu.global.v2.b32 [%0 + 24576], {%7,%8};"
                   :: "l"(dst), "r"(q[0]), "r"(q[1]), "r"(q[2]), "r"(q[3]), "r"(q[4]), "r"(q[5]), "r"(q[6]), "r"(q[7]) : "memory");
      }
      CSTAMP(5);
      if (fin) { finish(pend); pend = -1; }
      CSTAMP(6);
      if ((seg & 1) == ks >> 2 && !(YP & 1)) pend = seg;
      if (wg && (seg & 7) == 6) ASTAMP(5 + (seg >> 3));
    }
    };
    if (ks >= 4) run(BoolC<true>()); else run(BoolC<false>());
    if (PING && !wg) bar_sync(1, 256);
    CDUMP;
    ASTAMP(13);
  }
}

typedef CUresult (*EncodeFn)(CUtensorMap*, CUtensorMapDataType, cuuint32_t, void*, const cuuint64_t*, const cuuint64_t*,
                             const cuuint32_t*, const cuuint32_t*, CUtensorMapInterleave, CUtensorMapSwizzle,
                             CUtensorMapL2promotion, CUtensorMapFloatOOBfill);
static void make_map(EncodeFn enc, CUtensorMap* m, const void* p, int rows, int cols, int box_rows) {
  cuuint64_t dims[2] = {(cuuint64_t)cols, (cuuint64_t)rows};
  cuuint64_t strides[1] = {(cuuint64_t)cols * 2};
  cuuint32_t box[2] = {64, (cuuint32_t)box_rows};
  cuuint32_t es[2] = {1, 1};
  enc(m, CU_TENSOR_MAP_DATA_TYPE_BFLOAT16, 2, (void*)p, dims, strides, box, es, CU_TENSOR_MAP_INTERLEAVE_NONE,
      CU_TENSOR_MAP_SWIZZLE_128B, CU_TENSOR_MAP_L2_PROMOTION_L2_128B, CU_TENSOR_MAP_FLOAT_OOB_FILL_NONE);
}

constexpr int g_poll = POLL_NS;
extern "C" void kernel_launch(void* const* d_in, const int* in_sizes, int n_in, void* d_out, int out_size) {
  const bf16* x = (const bf16*)d_in[0];
  const bf16* wqkvA = (const bf16*)d_in[1];
  const bf16* woA = (const bf16*)d_in[2];
  const bf16* mem0 = (const bf16*)d_in[4];
  const bf16* Wq = (const bf16*)d_in[5];
  const bf16* Wk = (const bf16*)d_in[6];
  const bf16* Wv = (const bf16*)d_in[7];
  const bf16* Wo = (const bf16*)d_in[8];
  const bf16* gate_w = (const bf16*)d_in[10];
  static EncodeFn enc = nullptr;
  static void *pO = nullptr, *pR = nullptr, *pF = nullptr;
  if (!enc) {
    cudaDriverEntryPointQueryResult qr;
    cudaGetDriverEntryPoint("cuTensorMapEncodeTiled", (void**)&enc, cudaEnableDefault, &qr);
    cudaGetSymbolAddress(&pO, g_Ocat);
    cudaGetSymbolAddress(&pR, g_red_raw);
    cudaGetSymbolAddress(&pF, g_cflag);
    cudaFuncSetAttribute(rec_kernel, cudaFuncAttributeMaxDynamicSharedMemorySize, SM_TOTAL);
    cudaFuncSetAttribute(aux_kernel, cudaFuncAttributeMaxDynamicSharedMemorySize, A_TOTAL);
  }
  RMaps rm;
  rm.poll = g_poll;
  rm.oflag = (const unsigned char*)pF;
  rm.red = (unsigned char*)(((uintptr_t)pR + 262143) & ~(uintptr_t)262143);
  {
    cuuint64_t dims[3] = {64, S_LEN, 9}, strides[2] = {DM * 2, 128};
    cuuint32_t box[3] = {64, 32, 9}, es[3] = {1, 1, 1};
    enc(&rm.x, CU_TENSOR_MAP_DATA_TYPE_BFLOAT16, 3, (void*)x, dims, strides, box, es, CU_TENSOR_MAP_INTERLEAVE_NONE,
        CU_TENSOR_MAP_SWIZZLE_128B, CU_TENSOR_MAP_L2_PROMOTION_L2_128B, CU_TENSOR_MAP_FLOAT_OOB_FILL_NONE);
  }
  make_map(enc, &rm.wq, Wq, DM, 4096, 192);
  make_map(enc, &rm.wk, Wk, DM, 4096, 192);
  make_map(enc, &rm.wv, Wv, DM, 4096, 192);
  make_map(enc, &rm.wo, Wo, 4096, DM, 128);
  AMaps am;
  am.red = rm.red; am.poll = rm.poll;
  {
    cuuint64_t dims[3] = {DM, S_LEN / 2, 2}, strides[2] = {DM * 4, DM * 2};
    cuuint32_t box[3] = {32, 64, 2}, es[3] = {1, 1, 1};
    enc(&am.x, CU_TENSOR_MAP_DATA_TYPE_BFLOAT16, 3, (void*)x, dims, strides, box, es, CU_TENSOR_MAP_INTERLEAVE_NONE,
        CU_TENSOR_MAP_SWIZZLE_64B, CU_TENSOR_MAP_L2_PROMOTION_L2_128B, CU_TENSOR_MAP_FLOAT_OOB_FILL_NONE);
    cuuint64_t wdims[3] = {DM, DM, 3}, wstrides[2] = {DM * 6, DM * 2};
    cuuint32_t wbox[3] = {64, 32, 3}, wbox8[3] = {8, 32, 3};
    enc(&am.wa, CU_TENSOR_MAP_DATA_TYPE_BFLOAT16, 3, (void*)wqkvA, wdims, wstrides, wbox, es, CU_TENSOR_MAP_INTERLEAVE_NONE,
        CU_TENSOR_MAP_SWIZZLE_128B, CU_TENSOR_MAP_L2_PROMOTION_L2_128B, CU_TENSOR_MAP_FLOAT_OOB_FILL_NONE);
    enc(&am.wa8, CU_TENSOR_MAP_DATA_TYPE_BFLOAT16, 3, (void*)wqkvA, wdims, wstrides, wbox8, es, CU_TENSOR_MAP_INTERLEAVE_NONE,
        CU_TENSOR_MAP_SWIZZLE_NONE, CU_TENSOR_MAP_L2_PROMOTION_NONE, CU_TENSOR_MAP_FLOAT_OOB_FILL_NONE);
  }
  {
    cuuint64_t dims[3] = {64, S_LEN, KCAT / 64}, strides[2] = {KCAT * 2, 128};
    cuuint32_t box[3] = {64, 32, 9}, es[3] = {1, 1, 1};
    make_map(enc, &am.o, pO, S_LEN, KCAT, 32);
    enc(&am.o3, CU_TENSOR_MAP_DATA_TYPE_BFLOAT16, 3, pO, dims, strides, box, es, CU_TENSOR_MAP_INTERLEAVE_NONE,
        CU_TENSOR_MAP_SWIZZLE_128B, CU_TENSOR_MAP_L2_PROMOTION_L2_128B, CU_TENSOR_MAP_FLOAT_OOB_FILL_NONE);
  }
  make_map(enc, &am.wob, Wo, 4096, DM, 64);
  make_map(enc, &am.woa, woA, DM, DM, 64);
  make_map(enc, &am.woa16, woA, DM, DM, 16);
  {
    cuuint64_t dims[2] = {KCAT, S_LEN}, strides[1] = {KCAT * 2};
    cuuint32_t box[2] = {16, 32}, es[2] = {1, 1};
    enc(&am.o16, CU_TENSOR_MAP_DATA_TYPE_BFLOAT16, 2, pO, dims, strides, box, es, CU_TENSOR_MAP_INTERLEAVE_NONE,
        CU_TENSOR_MAP_SWIZZLE_32B, CU_TENSOR_MAP_L2_PROMOTION_NONE, CU_TENSOR_MAP_FLOAT_OOB_FILL_NONE);
  }

  rec_kernel<<<96, 384, SM_TOTAL, cudaStreamPerThread>>>(rm, x, mem0);
  cudaLaunchConfig_t cfg = {};
  cfg.gridDim = dim3(NAUX); cfg.blockDim = dim3(512); cfg.dynamicSmemBytes = A_TOTAL; cfg.stream = cudaStreamPerThread;
  cudaLaunchAttribute at[1];
  at[0].id = cudaLaunchAttributeProgrammaticStreamSerialization; at[0].val.programmaticStreamSerializationAllowed = 1;
  cfg.attrs = at; cfg.numAttrs = 1;
  if (XP & 16) cfg.numAttrs = 0;
  if (!(XP & 64)) cudaLaunchKernelEx(&cfg, aux_kernel, am, x, gate_w, (bf16*)d_out);
}
```

```cpp
#include <cuda_runtime.h>
#include <cuda_bf16.h>
#include <cuda_fp16.h>
#include <cuda.h>
#include <stdint.h>

typedef __nv_bfloat16 bf16;

constexpr int S_LEN = 2048, DM = 576, NH = 32, DH = 128, NSEG = 64, KCAT = 4096 + 576;
#define RED_LINE(i) (((i) >> 2) * 4096 + ((i) & 1) * 256 + ((i) & 2) * 512)
#define RED_SLOT(s) (((s) & 1) * 128 + ((s) & 2) * 256)

#define POLL_NS 896
#define QM 60
constexpr int NUP = 4;
#define N5 224
#define KP(i) (((i) >> 1) + 4 * ((i) & 1))
#define SPIN_LIMIT (1 << 14)
#define XP 0
#define YP 0

__device__ __align__(1024) bf16 g_Ocat[S_LEN * KCAT];
__device__ __align__(1024) unsigned char g_red_raw[2 * 262144];
constexpr int HINT_OFF = 2048;
__device__ __align__(16) float g_gate[S_LEN];
__device__ __align__(128) uint4 g_stats[96 * 2];
__device__ unsigned g_epoch;
__device__ unsigned g_epoch2;
__device__ __align__(128) unsigned g_oflag[NH * 32];
__device__ unsigned g_abar[3 * 32];
__device__ __align__(128) unsigned g_cflag[96 * 32];
__device__ uint2 g_sflag[96 * 4];
__device__ __align__(1024) unsigned char g_seg[NSEG * 96 * 8192];
__device__ __align__(1024) unsigned char g_km[NSEG * NH * 4096];
__device__ __align__(1024) uint2 g_part[8 * 9 * 4 * 8 * 128];
__device__ int g_err;
#define SSTAMP(seg, idx)
#define TSTAMP(idx)
#define QSTAMP(idx)
#define PROF(idx)
#define PROFP(idx)
#define STAMP(idx)
#define ASTAMP(idx)
#define WSTAMP(idx)

#define CSTAMP(idx)
#define CDECL
#define CDUMP
#define DI __device__ __forceinline__
DI uint32_t smem_u32(const void* p) { return (uint32_t)__cvta_generic_to_shared(p); }
DI uint32_t clock32() { uint32_t c; asm volatile("mov.u32 %0, %%clock;" : "=r"(c) :: "memory"); return c; }
DI uint32_t gtime() { uint32_t c; asm volatile("mov.u32 %0, %%globaltimer_lo;" : "=r"(c) :: "memory"); return c; }
DI uint32_t ldg_relaxed32(const void* p) { uint32_t v; asm volatile("ld.relaxed.gpu.global.b32 %0, [%1];" : "=r"(v) : "l"(p) : "memory"); return v; }
DI uint32_t ldg_acquire32(const void* p) { uint32_t v; asm volatile("ld.acquire.gpu.global.b32 %0, [%1];" : "=r"(v) : "l"(p) : "memory"); return v; }
DI void stg_relaxed32(void* p, uint32_t v) { asm volatile("st.relaxed.gpu.global.b32 [%0], %1;" :: "l"(p), "r"(v) : "memory"); }
DI uint32_t mapa(uint32_t a, uint32_t r) { uint32_t o; asm("mapa.shared::cluster.u32 %0, %1, %2;" : "=r"(o) : "r"(a), "r"(r)); return o; }
DI void cluster_arrive() { asm volatile("barrier.cluster.arrive.relaxed.aligned;" ::: "memory"); }
DI void cluster_wait() { asm volatile("barrier.cluster.wait.aligned;" ::: "memory"); }
DI void cluster_sync() { asm volatile("barrier.cluster.arrive.release.aligned;\nbarrier.cluster.wait.acquire.aligned;" ::: "memory"); }
DI void mbar_init(uint32_t b, uint32_t c) { asm volatile("mbarrier.init.shared::cta.b64 [%0], %1;" :: "r"(b), "r"(c) : "memory"); }
DI void mbar_expect(uint32_t b, uint32_t tx) { asm volatile("mbarrier.arrive.expect_tx.shared::cta.b64 _, [%0], %1;" :: "r"(b), "r"(tx) : "memory"); }
DI void mbar_arrive(uint32_t b) { asm volatile("mbarrier.arrive.shared::cta.b64 _, [%0];" :: "r"(b) : "memory"); }
DI void mbar_wait(uint32_t b, uint32_t par) {
  asm volatile("{\n.reg .pred p;\n.reg .u32 n, q;\nmov.u32 n, 0;\n"
               "WL: add.u32 n, n, 1;\nshr.u32 q, n, 12;\nxor.b32 q, q, %1;\n"
               "mbarrier.try_wait.parity.shared::cta.b64 p, [%0], q;\n@!p bra.uni WL;\n}"
               :: "r"(b), "r"(par) : "memory");
}
DI void wait_until(uint32_t t) {
  const uint32_t now = gtime();
  t = min(t, now + 8192);
  asm volatile("{\n.reg .pred p;\n.reg .u32 c;\nTL: mov.u32 c, %%globaltimer_lo;\nsetp.lt.u32 p, c, %0;\n@p bra.uni TL;\n}" :: "r"(t) : "memory");
}
#define PIN(v) v = __shfl_xor_sync(0xffffffffu, v, 0)
#define SCHED_FENCE(k) asm volatile("{\n.reg .pred p;\nsetp.eq.u32 p, %0, %1;\n@p exit;\n}" :: "r"(fence_reg), "r"(k) : "memory")
DI void bar_sync(int id, int n) { asm volatile("bar.sync %0, %1;" :: "r"(id), "r"(n) : "memory"); }
DI void bar_arrive(int id, int n) { asm volatile("bar.arrive %0, %1;" :: "r"(id), "r"(n) : "memory"); }
DI void fence_async() { asm volatile("fence.proxy.async.shared::cta;" ::: "memory"); }
DI void st_async4(uint32_t a, uint32_t x, uint32_t y, uint32_t z, uint32_t w, uint32_t mb) {
  asm volatile("st.async.weak.shared::cluster.mbarrier::complete_tx::bytes.v4.b32 [%0], {%1,%2,%3,%4}, [%5];"
               :: "r"(a), "r"(x), "r"(y), "r"(z), "r"(w), "r"(mb) : "memory");
}
DI void sts32(uint32_t a, uint32_t x) { asm volatile("st.shared.b32 [%0], %1;" :: "r"(a), "r"(x) : "memory"); }
DI void sts64(uint32_t a, uint32_t x, uint32_t y) { asm volatile("st.shared.v2.b32 [%0], {%1,%2};" :: "r"(a), "r"(x), "r"(y) : "memory"); }
DI void sts128(uint32_t a, uint32_t x, uint32_t y, uint32_t z, uint32_t w) {
  asm volatile("st.shared.v4.b32 [%0], {%1,%2,%3,%4};" :: "r"(a), "r"(x), "r"(y), "r"(z), "r"(w) : "memory");
}
DI uint32_t lds32(uint32_t a) { uint32_t x; asm volatile("ld.shared.b32 %0, [%1];" : "=r"(x) : "r"(a) : "memory"); return x; }
DI uint32_t lds32v(uint32_t a) { uint32_t x; asm volatile("ld.volatile.shared.b32 %0, [%1];" : "=r"(x) : "r"(a) : "memory"); return x; }
DI void lds64(uint32_t a, uint32_t& x, uint32_t& y) { asm volatile("ld.shared.v2.b32 {%0,%1}, [%2];" : "=r"(x), "=r"(y) : "r"(a) : "memory"); }
DI void lds128(uint32_t a, uint32_t* r) {
  asm volatile("ld.shared.v4.b32 {%0,%1,%2,%3}, [%4];" : "=r"(r[0]), "=r"(r[1]), "=r"(r[2]), "=r"(r[3]) : "r"(a) : "memory");
}
DI void lds128f(uint32_t a, float* r) {
  asm volatile("ld.shared.v4.f32 {%0,%1,%2,%3}, [%4];" : "=f"(r[0]), "=f"(r[1]), "=f"(r[2]), "=f"(r[3]) : "r"(a) : "memory");
}
DI void ldsm4t(uint32_t* r, uint32_t a) {
  asm volatile("ldmatrix.sync.aligned.m8n8.x4.trans.shared.b16 {%0,%1,%2,%3}, [%4];"
               : "=r"(r[0]), "=r"(r[1]), "=r"(r[2]), "=r"(r[3]) : "r"(a) : "memory");
}
DI void ldsm4t_in(uint32_t* r, uint32_t a, uint32_t t) {
  asm volatile("{\n.reg .pred p;\nsetp.ne.u32 p, %5, 0;\n@p ldmatrix.sync.aligned.m8n8.x4.trans.shared.b16 {%0,%1,%2,%3}, [%4];\n}"
               : "+r"(r[0]), "+r"(r[1]), "+r"(r[2]), "+r"(r[3]) : "r"(a), "r"(t) : "memory");
}
DI void lds128_in(uint32_t* r, uint32_t a, uint32_t t) {
  asm volatile("{\n.reg .pred p;\nsetp.ne.u32 p, %5, 0;\n@p ld.shared.v4.b32 {%0,%1,%2,%3}, [%4];\n}"
               : "+r"(r[0]), "+r"(r[1]), "+r"(r[2]), "+r"(r[3]) : "r"(a), "r"(t) : "memory");
}
DI void ldsm2t_in(uint32_t* r, uint32_t a, uint32_t t) {
  asm volatile("{\n.reg .pred p;\nsetp.ne.u32 p, %3, 0;\n@p ldmatrix.sync.aligned.m8n8.x2.trans.shared.b16 {%0,%1}, [%2];\n}" : "+r"(r[0]), "+r"(r[1]) : "r"(a), "r"(t) : "memory");
}
DI void reserve2(uint32_t* r) { asm volatile("{\n.reg .u64 t;\nmov.u64 t, %%clock64;\nmov.b64 {%0, %1}, t;\n}" : "=r"(r[0]), "=r"(r[1])); }
DI void scale_sum(float& x, float& y, float s, uint32_t t) {
  asm volatile("{\n.reg .pred p;\nsetp.ne.u32 p, %2, 0;\n@p mul.f32 %0, %0, %1;\n}" : "+f"(y) : "f"(s), "r"(t));
  asm volatile("{\n.reg .pred p;\nsetp.ne.u32 p, %3, 1;\n@p fma.rn.f32 %0, %0, %1, %2;\n}" : "+f"(x) : "f"(s), "f"(y), "r"(t));
}
DI void ldsm4(uint32_t* r, uint32_t a) {
  asm volatile("ldmatrix.sync.aligned.m8n8.x4.shared.b16 {%0,%1,%2,%3}, [%4];"
               : "=r"(r[0]), "=r"(r[1]), "=r"(r[2]), "=r"(r[3]) : "r"(a) : "memory");
}
DI void st_async1(uint32_t a, uint32_t x, uint32_t mb) {
  asm volatile("st.async.weak.shared::cluster.mbarrier::complete_tx::bytes.b32 [%0], %1, [%2];" :: "r"(a), "r"(x), "r"(mb) : "memory");
}
DI void stsm4(uint32_t a, uint32_t x, uint32_t y, uint32_t z, uint32_t w) {
  asm volatile("stmatrix.sync.aligned.m8n8.x4.shared.b16 [%0], {%1,%2,%3,%4};" :: "r"(a), "r"(x), "r"(y), "r"(z), "r"(w) : "memory");
}
DI void stsm4t(uint32_t a, uint32_t x, uint32_t y, uint32_t z, uint32_t w) {
  asm volatile("stmatrix.sync.aligned.m8n8.x4.trans.shared.b16 [%0], {%1,%2,%3,%4};" :: "r"(a), "r"(x), "r"(y), "r"(z), "r"(w) : "memory");
}
DI uint32_t pack_bf16(float lo, float hi) { uint32_t r; asm("cvt.rn.bf16x2.f32 %0, %1, %2;" : "=r"(r) : "f"(hi), "f"(lo)); return r; }
DI uint32_t pack_f16(float lo, float hi) { uint32_t r; asm("cvt.rn.f16x2.f32 %0, %1, %2;" : "=r"(r) : "f"(hi), "f"(lo)); return r; }
DI float ex2(float x) { float y; asm("ex2.approx.ftz.f32 %0, %1;" : "=f"(y) : "f"(x)); return y; }
DI float rcp(float x) { float y; asm("rcp.approx.ftz.f32 %0, %1;" : "=f"(y) : "f"(x)); return y; }
DI float bf_lo(uint32_t x) { return __uint_as_float(x << 16); }
DI float bf_hi(uint32_t x) { return __uint_as_float(x & 0xffff0000u); }
DI void mma16816(float* d, const uint32_t* a, uint32_t b0, uint32_t b1) {
  asm volatile("mma.sync.aligned.m16n8k16.row.col.f32.bf16.bf16.f32 {%0,%1,%2,%3}, {%4,%5,%6,%7}, {%8,%9}, {%0,%1,%2,%3};"
               : "+f"(d[0]), "+f"(d[1]), "+f"(d[2]), "+f"(d[3]) : "r"(a[0]), "r"(a[1]), "r"(a[2]), "r"(a[3]), "r"(b0), "r"(b1));
}
DI void mma16816z(float* d, const uint32_t* a, uint32_t b0, uint32_t b1) {
  asm volatile("mma.sync.aligned.m16n8k16.row.col.f32.bf16.bf16.f32 {%0,%1,%2,%3}, {%4,%5,%6,%7}, {%8,%9}, {%10,%10,%10,%10};"
               : "=f"(d[0]), "=f"(d[1]), "=f"(d[2]), "=f"(d[3]) : "r"(a[0]), "r"(a[1]), "r"(a[2]), "r"(a[3]), "r"(b0), "r"(b1), "f"(0.f));
}
DI void mma1688(float* d, uint32_t a0, uint32_t a1, uint32_t b0) {
  asm volatile("mma.sync.aligned.m16n8k8.row.col.f32.bf16.bf16.f32 {%0,%1,%2,%3}, {%4,%5}, {%6}, {%0,%1,%2,%3};"
               : "+f"(d[0]), "+f"(d[1]), "+f"(d[2]), "+f"(d[3]) : "r"(a0), "r"(a1), "r"(b0));
}
DI uint32_t add_bf16(uint32_t a, uint32_t b) { uint32_t r; asm("add.rn.bf16x2 %0, %1, %2;" : "=r"(r) : "r"(a), "r"(b)); return r; }
DI uint32_t mul_bf16(uint32_t a, uint32_t b) { uint32_t r; asm("mul.rn.bf16x2 %0, %1, %2;" : "=r"(r) : "r"(a), "r"(b)); return r; }
DI uint64_t make_desc(uint32_t addr, uint32_t lbo, uint32_t sbo, uint32_t swz) {
  return (uint64_t)((addr & 0x3FFFF) >> 4) | ((uint64_t)(lbo >> 4) << 16) | ((uint64_t)(sbo >> 4) << 32) | ((uint64_t)swz << 62);
}
#define WG_FENCE() asm volatile("wgmma.fence.sync.aligned;" ::: "memory")
#define WG_COMMIT() asm volatile("wgmma.commit_group.sync.aligned;" ::: "memory")
#define WG_WAIT(n) asm volatile("wgmma.wait_group.sync.aligned %0;" :: "n"(n) : "memory")
#define ACC8(d, o) "+f"(d[o]), "+f"(d[o + 1]), "+f"(d[o + 2]), "+f"(d[o + 3]), "+f"(d[o + 4]), "+f"(d[o + 5]), "+f"(d[o + 6]), "+f"(d[o + 7])
DI void wgmma_n32_rs(float* d, uint32_t a0, uint32_t a1, uint32_t a2, uint32_t a3, uint64_t db, int acc) {
  asm volatile("{\n.reg .pred p;\nsetp.ne.b32 p, %21, 0;\n"
               "wgmma.mma_async.sync.aligned.m64n32k16.f32.bf16.bf16 {%0,%1,%2,%3,%4,%5,%6,%7,%8,%9,%10,%11,%12,%13,%14,%15}, "
               "{%16,%17,%18,%19}, %20, p, 1, 1, 0;\n}\n"
               : ACC8(d, 0), ACC8(d, 8) : "r"(a0), "r"(a1), "r"(a2), "r"(a3), "l"(db), "r"(acc));
}
template <int TA>
DI void wgmma_n32_ss(float* d, uint64_t da, uint64_t db, int acc) {
  asm volatile("{\n.reg .pred p;\nsetp.ne.b32 p, %18, 0;\n"
               "wgmma.mma_async.sync.aligned.m64n32k16.f32.bf16.bf16 {%0,%1,%2,%3,%4,%5,%6,%7,%8,%9,%10,%11,%12,%13,%14,%15}, "
               "%16, %17, p, 1, 1, %19, 1;\n}\n"
               : ACC8(d, 0), ACC8(d, 8) : "l"(da), "l"(db), "r"(acc), "n"(TA));
}
DI void tma_load(uint32_t dst, const CUtensorMap* m, int c0, int c1, uint32_t mb) {
  asm volatile("cp.async.bulk.tensor.2d.shared::cluster.global.mbarrier::complete_tx::bytes [%0], [%1, {%3, %4}], [%2];"
               :: "r"(dst), "l"(m), "r"(mb), "r"(c0), "r"(c1) : "memory");
}
DI void tma_load3(uint32_t dst, const CUtensorMap* m, int row, uint32_t mb) {
  asm volatile("cp.async.bulk.tensor.3d.shared::cluster.global.mbarrier::complete_tx::bytes [%0], [%1, {%3, %4, %3}], [%2];"
               :: "r"(dst), "l"(m), "r"(mb), "r"(0), "r"(row) : "memory");
}
DI bool elect_one() {
  uint32_t p;
  asm volatile("{\n.reg .pred p;\nelect.sync _|p, 0xffffffff;\nselp.u32 %0, 1, 0, p;\n}" : "=r"(p));
  return p;
}
DI void bulk_s2s(uint32_t dst, uint32_t src, uint32_t bytes, uint32_t mb) {
  asm volatile("cp.async.bulk.shared::cluster.shared::cta.mbarrier::complete_tx::bytes [%0], [%1], %2, [%3];"
               :: "r"(dst), "r"(src), "r"(bytes), "r"(mb) : "memory");
}
DI void bulk_load(uint32_t dst, const void* src, uint32_t bytes, uint32_t mb) {
  asm volatile("cp.async.bulk.shared::cluster.global.mbarrier::complete_tx::bytes [%0], [%1], %2, [%3];" :: "r"(dst), "l"(src), "r"(bytes), "r"(mb) : "memory");
}
#define EVICT_FIRST ".reg .b64 pol;\ncreatepolicy.fractional.L2::evict_first.b64 pol, 1.0;\n"
DI void tma_load_ef(uint32_t dst, const CUtensorMap* m, int c0, int c1, uint32_t mb) {
  asm volatile("{\n" EVICT_FIRST "cp.async.bulk.tensor.2d.shared::cluster.global.mbarrier::complete_tx::bytes.L2::cache_hint [%0], [%1, {%3, %4}], [%2], pol;\n}"
               :: "r"(dst), "l"(m), "r"(mb), "r"(c0), "r"(c1) : "memory");
}
DI void tma_prefetch(const CUtensorMap* m, int c0, int c1) {
  asm volatile("cp.async.bulk.prefetch.tensor.2d.L2.global.tile [%0, {%1, %2}];" :: "l"(m), "r"(c0), "r"(c1) : "memory");
}
DI void tma_store(const CUtensorMap* m, uint32_t src, int c0, int c1) {
  asm volatile("cp.async.bulk.tensor.2d.global.shared::cta.bulk_group [%0, {%2, %3}], [%1];" :: "l"(m), "r"(src), "r"(c0), "r"(c1) : "memory");
}
DI uint4 ldg_relaxed(const void* p) {
  uint4 v;
  asm volatile("ld.relaxed.gpu.global.v4.b32 {%0,%1,%2,%3}, [%4];" : "=r"(v.x), "=r"(v.y), "=r"(v.z), "=r"(v.w) : "l"(p) : "memory");
  return v;
}
DI void stg_relaxed(void* p, uint32_t x, uint32_t y, uint32_t z, uint32_t w) {
  asm volatile("st.relaxed.gpu.global.v4.b32 [%0], {%1,%2,%3,%4};" :: "l"(p), "r"(x), "r"(y), "r"(z), "r"(w) : "memory");
}
DI void red_f16x8(void* p, uint32_t x, uint32_t y, uint32_t z, uint32_t w) {
  asm volatile("red.relaxed.gpu.global.add.noftz.v4.f16x2 [%0], {%1,%2,%3,%4};" :: "l"(p), "r"(x), "r"(y), "r"(z), "r"(w) : "memory");
}
DI void sq_acc(uint32_t& a, uint32_t x) { asm("fma.rn.bf16x2 %0, %1, %1, %0;" : "+r"(a) : "r"(x)); }
DI __half2 amax4(__half2 h, const uint32_t* v) {
  h = __hmax2_nan(__hmax2_nan(h, __habs2(*(const __half2*)&v[0])), __habs2(*(const __half2*)&v[1]));
  return __hmax2_nan(__hmax2_nan(h, __habs2(*(const __half2*)&v[2])), __habs2(*(const __half2*)&v[3]));
}
DI uint32_t wexp(__half2 h) { const uint32_t u = *(const uint32_t*)&h; return __reduce_max_sync(0xffffffffu, max((u >> 16) & 0x7fffu, u & 0x7fffu)) >> 7; }
DI float warp_sum(float v) {
#pragma unroll
  for (int o = 16; o; o >>= 1) v += __shfl_xor_sync(0xffffffffu, v, o);
  return v;
}

constexpr int SM_WO3 = 0;
constexpr int SM_X = 16384;
constexpr int XT = 36864;
constexpr int SM_EXP = 126976;
constexpr int SEGB = 10240;
constexpr int SM_BLK = SM_EXP + 8192;
constexpr int SM_VC = SM_BLK + 4 * SEGB;
constexpr int SM_PART = SM_VC + 16384;
constexpr int SM_QM = SM_PART + 4096;
constexpr int SM_E = SM_QM + 1024;
constexpr int SM_VM = SM_E + 1536;
constexpr int SM_OB = SM_VM + 2048;
constexpr int SM_FB = SM_OB + 2048;
constexpr int SM_STAGE = SM_X + XT;
constexpr int SM_M0 = SM_STAGE + 3 * 49152;
constexpr int SM_MISC = 210944;
constexpr int SM_WOST = 212992;
constexpr int SM_MEM = SM_WOST;
constexpr int SM_MAX = SM_MEM + 11264;
#define MEM_BLK(q) ((q) / 3 * 4096 + (q) % 3 * 1024)
constexpr int SM_TOTAL = 229376;
constexpr int MB_W = SM_MISC;
constexpr int MB_WO = SM_MISC + 24;
constexpr int MB_WO3 = SM_MISC + 32;
constexpr int MB_X = SM_MISC + 40;
constexpr int MB_S = SM_MISC + 64;
constexpr int MB_F = SM_MISC + 72;
constexpr int MB_VX = SM_MISC + 80;
constexpr int SC_FPAR = SM_MISC + 136;
constexpr int SC_DEAD = SM_MISC + 96;
constexpr int SC_UNSC = SM_MISC + 112;
constexpr int SC_OFL = SM_MISC + 1024;
constexpr int SC_EXPW = SM_MISC + 132;
constexpr int SC_ONES = SM_MISC + 144;
constexpr int SC_SS = SM_MISC + 160;
constexpr int SC_LAT = SM_MISC + 224;
constexpr int SC_TAG = SM_MISC + 232;
constexpr int SC_EPO = SM_MISC + 240;
constexpr int MB_XS = SM_MISC + 248;
constexpr int SC_XMAX = SM_MISC + 256;
constexpr int SC_PROF = 229376;

constexpr float SM_SCALE = 0.08838834764831845f;
constexpr float LOG2E = 1.4426950408889634f;
constexpr float E_LIM = 20.f;

template <bool B> struct BoolC { static constexpr bool value = B; };
template <int I> struct IntC { static constexpr int value = I; };
struct RMaps { CUtensorMap x, wq, wk, wv, wo; unsigned char* red; uint32_t poll; const unsigned char* oflag; };

DI uint32_t latest_hint(uint32_t h, uint32_t d, int s) {
  const uint32_t x = (((h | 0xc0c0c0c0u) - ((d >> 5) & 63) * 0x01010101u) & 0x3f3f3f3fu) | ((h ^ (((s >> 2) + 1) & 3) * 0x40404040u) & 0xc0c0c0c0u);
  const uint32_t y = __vmaxu2(x & 0x00ff00ffu, (x >> 8) & 0x00ff00ffu);
  return __reduce_max_sync(0xffffffffu, max(y & 0xffffu, y >> 16));
}
DI uint32_t near_half(uint32_t sb) {
  uint32_t a, b; lds64(sb + SC_LAT, a, b);
  return a > b;
}

template <int RT, int K0, int K1, bool D32 = false>
DI void xproj(float* acc, const uint32_t (&wa)[2][18][4], uint64_t xd) {
  if (XP & 1) return;
  WG_FENCE();
#pragma unroll
  for (int k = K0; k < ((XP & 128) ? K0 + 1 : K1); k++)
  {
    uint64_t d = xd + (uint64_t)(((k >> 1) * 4096 + (k & 1) * 32) >> 4);
    if (D32) asm("mov.b64 %0, {%1, %2};" : "=l"(d) : "r"((uint32_t)xd + (((k >> 1) * 4096 + (k & 1) * 32) >> 4)), "r"((uint32_t)(xd >> 32)));
    wgmma_n32_rs(acc, wa[RT][k][0], wa[RT][k][1], wa[RT][k][2], wa[RT][k][3], d, k != 0);
  }
  WG_COMMIT();
}

DI void load_w(uint32_t sb, const RMaps& tm, uint32_t rank, int c) {
  const int h = blockIdx.x / 3;
  mbar_expect(sb + MB_W + 8 * c, 49152);
  tma_load_ef(sb + SM_STAGE + c * 49152, rank < 2 ? &tm.wk : &tm.wv, h * DH + (rank == 1 ? 64 : 0), c * 192, sb + MB_W + 8 * c);
  tma_load_ef(sb + SM_STAGE + c * 49152 + 24576, rank < 2 ? &tm.wq : &tm.wv, h * DH + (rank == 0 ? 0 : 64), c * 192, sb + MB_W + 8 * c);
}
DI void seg_store(int seg, uint32_t slot, uint32_t sb) {
  asm volatile("cp.async.bulk.global.shared::cta.bulk_group [%0], [%1], 8192;"
               :: "l"(g_seg + ((size_t)slot * 96 + blockIdx.x) * 8192), "r"(sb + SM_BLK + (seg & 3) * SEGB) : "memory");
  asm volatile("cp.async.bulk.commit_group;" ::: "memory");
}
DI void seg_publish(int seg, uint32_t sb) {
  uint32_t v, own;
  lds64(sb + SC_EPO, v, own);
  asm volatile("cp.async.bulk.wait_group 0;" ::: "memory");
  asm volatile("st.relaxed.gpu.global.v2.b32 [%0], {%1,%2};" :: "l"(&g_sflag[blockIdx.x * 4]), "r"(v + seg), "r"(own) : "memory");
}

DI void proj_role(const uint32_t sb, const RMaps& tm, const bf16* __restrict__ x, const uint32_t rank, const int wg, const int w, const int lane) {
  const bool qk = rank < 2;
  uint32_t wa[2][18][4];
  float acc[16];
  const uint64_t xd0 = make_desc(sb + SM_X + wg * 64, 16, 1024, 1);
  {
    const int rr = (lane & 7) + ((lane >> 4) << 3);
    const uint32_t col = ((2 * w + ((lane >> 3) & 1)) ^ (lane & 7)) << 4;
    float ss = 0.f;
    bar_sync(3, 256);
    mbar_wait(sb + MB_X, 0);
    auto chunk = [&](auto cc) {
      constexpr int c = decltype(cc)::value;
      QSTAMP(2 + 2 * c);
      mbar_wait(sb + MB_W + 8 * c, 0);
      QSTAMP(3 + 2 * c);
#pragma unroll
      for (int rt = 1; rt >= 0; rt--)
#pragma unroll
        for (int k = 0; k < 6; k++)
          ldsm4t(wa[rt][c * 6 + k], sb + SM_STAGE + c * 49152 + (rt ^ wg) * 24576 + (64 * (k >> 1) + 32 * wg + 16 * (k & 1) + rr) * 128 + col);
      fence_async();
      if (c < 2) {
        bar_sync(3, 256);
        QSTAMP(17 + c);
        if (threadIdx.x == 0) {
          if (c == 0) tma_load(sb + SM_X + XT, &tm.wo, rank * 192, (blockIdx.x / 3) * DH, sb + MB_WO);
          else if (blockIdx.x < NSEG) bulk_load(sb + SM_X + 2 * XT, x + blockIdx.x * 32 * DM, XT, sb + MB_XS);
          else tma_load3(sb + SM_X + 2 * XT, &tm.x, 64, sb + MB_X + 16);
        }
        __syncwarp();
      } else {
        cluster_arrive();
      }
      xproj<1, 6 * c, 6 * c + 6>(acc, wa, xd0);
      if (!qk) {
        uint32_t q[4] = {0, 0, 0, 0};
#pragma unroll
        for (int rt = 0; rt < 2; rt++)
#pragma unroll
          for (int k = 0; k < 6; k++)
#pragma unroll
            for (int i = 0; i < 4; i++) sq_acc(q[i], wa[rt][c * 6 + k][i]);
#pragma unroll
        for (int i = 0; i < 4; i++) ss += bf_lo(q[i]) + bf_hi(q[i]);
      }
    };
    chunk(IntC<0>()); chunk(IntC<1>()); chunk(IntC<2>());
    ss = warp_sum(ss);
    if (lane == 0) sts32(sb + SC_SS + 4 * (wg * 4 + w), __float_as_uint(ss));
    bar_arrive(11, 384);
  }
  STAMP(1);
  QSTAMP(8);
  STAMP(2);

  uint32_t t16 = sb + (w * 32 + lane) * 16;
  uint32_t mem_a = sb + SM_MEM + wg * 512 + lane * 16;
  uint32_t fin_a = sb + (lane & 7) * 16 + SM_BLK + (qk ? (wg ^ 1) * 4096 + w * 256 + (lane & 8) * 16 + (lane & 16) * 64
                                              : wg * 4096 + w * 1024 + (lane & 8) * 64 + (lane & 16) * 8);
  PIN(t16); PIN(mem_a); PIN(fin_a);
  const uint32_t fence_reg = mem_a;
  const uint32_t fin2 = qk ? 2048 : 256;
  auto do_export = [&](auto retire, uint32_t always) {
    WG_WAIT(0);
    uint32_t p[2];
#pragma unroll
    for (int i = 0; i < 2; i++) {
      p[i] = pack_bf16(acc[8 * i], acc[8 * i + 1]);
      sts128(t16 + SM_EXP + wg * 4096 + i * 2048, p[i], pack_bf16(acc[8 * i + 2], acc[8 * i + 3]),
             pack_bf16(acc[8 * i + 4], acc[8 * i + 5]), pack_bf16(acc[8 * i + 6], acc[8 * i + 7]));
    }
    if (decltype(retire)::value)
      asm volatile("{\n.reg .pred p, q;\nsetp.ne.u32 p, %2, 0;\nsetp.ne.u32 q, %2, 1;\n@p ld.shared.b32 %0, [%3];\n@q ld.shared.b32 %1, [%3 + 4];\n"
                   "setp.ne.u32 p, %0, %1;\n@p exit;\n}" : "+r"(p[0]), "+r"(p[1]) : "r"(always), "r"(sb + SC_DEAD) : "memory");
  };
  uint32_t o[8];
  auto import = [&]() { lds128(t16 + SM_EXP + (wg ^ 1) * 4096, o); lds128(t16 + SM_EXP + (wg ^ 1) * 4096 + 2048, o + 4); };
  auto finish_from = [&](int seg, const float* d) {
    const uint32_t a = fin_a + (seg & 3) * SEGB;
#pragma unroll
    for (int i = 0; i < 8; i++) o[i] = add_bf16(pack_bf16(d[2 * i], d[2 * i + 1]), o[i]);
    stsm4(a, o[0], o[1], o[2], o[3]);
    stsm4(a + fin2, o[4], o[5], o[6], o[7]);
    fence_async();
  };
  auto finish = [&](int seg) { WG_WAIT(0); finish_from(seg, acc); };
  auto send_v = [&](int seg, int dst) {
    if (seg < NSEG - 1 && !(XP & 2) && elect_one())
      bulk_s2s(mapa(sb + SM_VC + (seg & 1) * 8192, dst), sb + SM_BLK + (seg & 3) * SEGB, 8192, mapa(sb + MB_VX + (seg & 1) * 8, dst));
    __syncwarp();
  };
  auto wait_v = [&](int seg) {
    if (seg < NSEG - 1 && !(XP & 2)) {
      mbar_wait(sb + MB_VX + (seg & 1) * 8, (seg >> 1) & 1);
      if (elect_one()) mbar_expect(sb + MB_VX + (seg & 1) * 8, 8192);
      __syncwarp();
    }
  };
  auto export_seg = [&](int seg, uint32_t slot) { if (!(XP & (4 | 8192)) && elect_one()) seg_store(seg, slot, sb); __syncwarp(); };
  auto publish = [&](int seg) { if (!(XP & (4 | 16384)) && elect_one()) seg_publish(seg, sb); __syncwarp(); };
  do_export(BoolC<false>(), 0);
  QSTAMP(9);
  SCHED_FENCE(11);
  xproj<0, 0, 18>(acc, wa, xd0);
  bar_sync(3, 256);
  QSTAMP(10);
  cluster_wait();
  QSTAMP(11);
  mbar_wait(sb + MB_X + 8, 0);
  QSTAMP(12);
  import();
  finish(0);
  SCHED_FENCE(12);
  uint64_t dA = xd0 + (XT >> 4);
  xproj<1, 0, 18>(acc, wa, dA);
  bar_sync(3, 256);
  if (!qk && wg == 0 && w < 2) send_v(0, w);
  if (wg == 0 && w == 3) export_seg(0, 0);
  QSTAMP(13);
  if (qk && wg == 0 && w == 0) wait_v(0);
  QSTAMP(14);
  bar_arrive(13, 384);
  if (!qk) {
    do_export(BoolC<false>(), 0);
    SCHED_FENCE(15);
    xproj<0, 0, 18>(acc, wa, dA);
    if (threadIdx.x == 0 && !(XP & 8)) { mbar_expect(sb + MB_X, XT); tma_load3(sb + SM_X, &tm.x, 96, sb + MB_X); }
    bar_sync(3, 256);
    mbar_wait(sb + MB_X + 16, 0);
    import();
    finish(1);
    SCHED_FENCE(16);
    dA += XT >> 4;
    xproj<1, 0, 18>(acc, wa, dA);
  }
  QSTAMP(15);
  WG_WAIT(0);
  bar_sync(0, 384);
  if (wg == 0 && w == 3) publish(0);
  QSTAMP(16);
  const int ro = __shfl_sync(0xffffffffu, near_half(sb) ^ wg, 0);
  STAMP(5);
  const uint32_t always = __shfl_sync(0xffffffffu, lds32(sb + SC_DEAD + 12), 0);
  const int ah = qk ? 1 : 2;
  int b2 = qk ? 2 : 0;
  int s = 0;
  uint32_t hint_lo = (uint32_t)(uint64_t)tm.red + HINT_OFF + blockIdx.x + (lane & 1) * 4096 + (lane >> 1) * 16384;
  PIN(hint_lo);
  auto post_hint = [&]() {
    uint32_t t;
    asm volatile("{\n.reg .u64 g;\nmov.u64 g, %%globaltimer;\ncvt.u32.u64 %0, g;\n}" : "=r"(t) :: "memory");
    asm volatile("{\n.reg .pred p;\n.reg .b64 a;\n.reg .u32 t;\nsetp.lt.u32 p, %0, %1;\nmov.b64 a, {%2, %3};\n"
                 "bfe.u32 t, %5, 5, 6;\nor.b32 t, t, %4;\n@p st.relaxed.gpu.global.u8 [a], t;\n}"
                 :: "r"(t16), "r"(sb + 160), "r"(hint_lo + RED_SLOT(s)), "r"((uint32_t)((uint64_t)tm.red >> 32)), "r"(((s >> 2) + 1) << 6), "r"(t) : "memory");
  };
  auto memproj = [&](auto second, int id, uint32_t dep, float u0, float u1, float* r) {
    constexpr bool R1 = decltype(second)::value;
    uint32_t b[NUP][4], b0[4];
    if (R1) asm volatile("{\n.reg .pred p;\nsetp.eq.u32 p, %0, %1;\n@p exit;\n}" :: "r"(dep), "r"(id) : "memory");
    bar_sync(R1 ? 2 : 1, 256);
    PROF(0);
    ldsm4t(b0, mem_a);
#pragma unroll
    for (int q = 0; q < NUP; q++) {
      if (R1 && q == 2) {
        bar_sync(11, 256);
        SCHED_FENCE(id + 1);
      }
      ldsm4t(b[q], mem_a + MEM_BLK(q + 1));
    }
    mma16816z(&acc[0], wa[0][0], b0[0], b0[1]);
    mma16816z(&acc[4], wa[1][0], b0[0], b0[1]);
    mma16816z(&acc[8], wa[0][1], b0[2], b0[3]);
    mma16816z(&acc[12], wa[1][1], b0[2], b0[3]);
#pragma unroll
    for (int q = 1; q < 9; q++) {
      uint32_t* const c = b[(q - 1) % NUP];
      mma16816(&acc[0], wa[0][2 * q], c[0], c[1]);
      mma16816(&acc[4], wa[1][2 * q], c[0], c[1]);
      mma16816(&acc[8], wa[0][2 * q + 1], c[2], c[3]);
      mma16816(&acc[12], wa[1][2 * q + 1], c[2], c[3]);
      if (R1 && q + NUP == 9) bar_sync(3, 256);
      if (q + NUP < 9) ldsm4t_in(c, mem_a + MEM_BLK(q + NUP), always);
      else if (R1 && q + NUP < 11) lds128_in(c, t16 + SM_PART + (10 - q - NUP) * 2048, always);
      else if (!R1 && q == 8) { bar_arrive(11, 256); lds128_in(c, sb + SC_DEAD, always); u0 = u1 = __uint_as_float(c[3]); }
    }
#pragma unroll
    for (int i = 0; i < 8; i++) {
      const float u = i < 4 ? u0 : u1;
      r[i] = R1 ? fmaf(acc[8 + i], u, (acc[i] + __uint_as_float(b[(8 + i / 4) % NUP][i & 3])) * u) : fmaf(acc[i], u, acc[8 + i]);
    }
  };
  if (ro == 0) {
#pragma unroll 1
    while (true) {
      do_export(BoolC<true>(), always);
      PROFP(3);
      if (s == 8) STAMP(6);
      float r[8];
      memproj(BoolC<false>(), 30, 0, 0.f, 0.f, r);
      sts128(t16 + SM_PART, __float_as_uint(r[0]), __float_as_uint(r[1]), __float_as_uint(r[2]), __float_as_uint(r[3]));
      sts128(t16 + SM_PART + 2048, __float_as_uint(r[4]), __float_as_uint(r[5]), __float_as_uint(r[6]), __float_as_uint(r[7]));
      bar_arrive(3, 256);
      PROF(1);
      bar_sync(9, 256);
      post_hint();
      if (w == 3 && s) publish(s);
      if (s == NSEG - 1) break;
      if (w == 1) {
        uint32_t m[8];
        lds128(t16 + SM_MAX - 512, m); lds128(t16 + SM_MAX, m + 4);
        const int em = (wexp(amax4(amax4(*(const __half2*)&m[0], m), m + 4)) >> 3) + (int)(lds32(sb + SC_UNSC + (s & 1) * 8) >> 23) - 15;
        const int ex = max(s ? em : 0, (int)lds32(sb + SC_XMAX + 4 * s)) - 127 + (int)lds32(sb + SC_EXPW);
        sts32(sb + SC_UNSC + (~s & 1) * 8, (127 + min(max(ex, -120), 120)) << 23);
        __syncwarp();
        if (elect_one()) mbar_arrive(sb + MB_S);
      }
      SCHED_FENCE(9);
      bar_sync(5, qk ? N5 : 256);
      PROF(2);
      import();
      xproj<0, 0, 18>(acc, wa, dA);
      WG_WAIT(0);
      bar_sync(10, 256);
      SCHED_FENCE(17);
      dA += (int64_t)(b2 ? XT >> 4 : -(XT >> 3));
      finish(s + ah);
      if (w != 3) bar_arrive(13, 384);
      PROF(6);
      SCHED_FENCE(14);
      bar_sync(12, 256);
      PROF(7);
      xproj<1, 0, 18, true>(acc, wa, dA);
      bar_arrive(14, 256);
      b2 = b2 == 2 ? 0 : b2 + 1;
      s++;
      if (w == 3) {
        const uint32_t slot = s < lds32(sb + SC_EPO + 4) ? s & 7 : s;
        bar_sync(13, 384);
        export_seg(s, slot);
      }
      PROFP(8);
    }
    if (!qk) bar_arrive(5, 256);
  } else {
    uint32_t km[4];
    auto send_km = [&]() {
      if (XP & (4 | 4096)) return;
      uint32_t t, u;
      lds64(sb + SC_TAG, t, u);
      t |= km[0] & ~1u; u += s * (NH * 4096);
      if (qk)
        asm volatile("{\n.reg .u32 o;\n.reg .u64 a;\nshr.u32 o, %0, 1;\nadd.u32 o, o, %1;\nmad.wide.u32 a, o, 1, %2;\nst.relaxed.gpu.global.v2.b32 [a], {%3,%4};\n}"
                     :: "r"(t16), "r"(u), "l"(g_km), "r"(t), "r"(km[1]) : "memory");
      else
        asm volatile("{\n.reg .u32 o;\n.reg .u64 a;\nadd.u32 o, %0, %1;\nmad.wide.u32 a, o, 1, %2;\nst.relaxed.gpu.global.v4.b32 [a], {%3,%4,%5,%6};\n}"
                     :: "r"(t16), "r"(u), "l"(g_km), "r"(t), "r"(km[1]), "r"(km[2]), "r"(km[3]) : "memory");
    };
#pragma unroll 1
    while (true) {
      do_export(BoolC<true>(), always);
      if (!qk && w == 2) send_v(s + 1, 0);
      PROFP(3);
      if (s == 8) STAMP(6);
      const uint32_t tl = ((t16 >> 8) ^ wg) & 1, am = (t16 & ~256u) - w * 256;
      const float un = __uint_as_float(lds32(sb + SC_UNSC + (s & 1) * 8));
      float r[8];
      if (qk) {
        uint32_t a0 = am + (tl ? SM_QM : SM_BLK + 8192 + (s & 3) * SEGB);
        float u0 = wg ? un * (SM_SCALE * LOG2E) : un, u1 = wg ? un : un * (SM_SCALE * LOG2E);
        PIN(a0); PIN(u0); PIN(u1);
        memproj(BoolC<true>(), 32, a0, u0, u1, r);
        const uint32_t p0 = pack_bf16(r[0], r[1]), p1 = pack_bf16(r[2], r[3]), p2 = pack_bf16(r[4], r[5]), p3 = pack_bf16(r[6], r[7]);
        stsm4(a0, p0, p1, p2, p3);
        bar_arrive(4, 256);
        km[0] = wg ? p2 : p0; km[1] = wg ? p3 : p1;
      } else {
        const uint32_t d0 = s < NSEG - 1 ? 0 : 2, d1 = s < NSEG - 1 ? 1 : 2;
        uint32_t r0 = mapa(t16 + SM_VM, d0), r1 = mapa(t16 + SM_VM, d1);
        PIN(r0); PIN(r1);
        memproj(BoolC<true>(), 34, r0 | r1, un, un, r);
        const uint32_t p0 = pack_bf16(r[0], r[1]), p1 = pack_bf16(r[2], r[3]), p2 = pack_bf16(r[4], r[5]), p3 = pack_bf16(r[6], r[7]);
        const uint32_t v0 = wg ? p2 : p0, v1 = wg ? p3 : p1, v2 = wg ? p0 : p2, v3 = wg ? p1 : p3;
        st_async4(r0, v0, v1, v2, v3, mapa(sb + MB_S, d0));
        st_async4(r1, v0, v1, v2, v3, mapa(sb + MB_S, d1));
        bar_arrive(5, 256);
        sts128(t16 + SM_VM, v0, v1, v2, v3);
        __syncwarp();
        if (elect_one()) mbar_arrive(sb + MB_S);
        km[0] = v0; km[1] = v1; km[2] = v2; km[3] = v3;
      }
      PROF(1);
      auto rearm = [&]() { mbar_wait(sb + MB_S, s & 1); if (elect_one()) mbar_expect(sb + MB_S, qk ? 640 + 2048 : 1280); __syncwarp(); };
      if (s == NSEG - 1 && w != 1) {
      } else if (w == 1) {
        if ((t16 & 384) == 0) stg_relaxed(tm.red + (RED_SLOT(s + 2) + RED_LINE(blockIdx.x)) + (t16 & 112), 0, 0, 0, 0);
        uint32_t base, own;
        lds64(sb + SC_EPO, base, own);
        if ((int)(lds32v(sb + SC_OFL) - base) < s - 7) sts32(sb + SC_EPO + 4, min(own, s + 1));
        if (elect_one()) bulk_load(sb + SC_OFL, tm.oflag + blockIdx.x * 128, 16, sb + MB_XS);
      } else if (w == 0) {
        const int tn = s + ah + 1;
        if (tn + 1 < NSEG && !(XP & 8) && elect_one()) {
          const int b0 = b2 == 2 ? 0 : b2 + 1;
          mbar_expect(sb + MB_X + 8 * b0, XT);
          tma_load3(sb + SM_X + b0 * XT, &tm.x, (tn + 1) * 32, sb + MB_X + 8 * b0);
        }
        if (tn < NSEG && (!(XP & 8) || tn < 3)) mbar_wait(sb + MB_X + 8 * b2, (tn / 3) & 1);
      } else if (w == 2) {
        if (!qk) send_v(s + 1, 1);
      } else {
        rearm();
      }
      __syncwarp();
      send_km();
      if (s == NSEG - 1) break;
      import();
      PROF(4);
      SCHED_FENCE(10);
      bar_sync(7, 256);
      xproj<0, 0, 18>(acc, wa, dA);
      bar_arrive(12, 256);
      dA += (int64_t)(b2 ? XT >> 4 : -(XT >> 3));
      finish(s + ah);
      if (qk && w == 0) wait_v(s + 1);
      bar_arrive(13, 384);
      PROF(6);
      SCHED_FENCE(13);
      bar_sync(14, 256);
      PROF(7);
      xproj<1, 0, 18>(acc, wa, dA);
      b2 = b2 == 2 ? 0 : b2 + 1;
      s++;
      PROFP(8);
    }
  }
  bar_arrive(0, 384);
  STAMP(3);
  cluster_sync();
  STAMP(4);
}

DI void attn_role(const uint32_t sb, unsigned char* smem_raw, const RMaps& tm, const uint32_t RANK, const bf16* __restrict__ x, const bf16* __restrict__ mem0,
                  const int w, const int lane) {
  const int t2 = w * 32 + lane;
  uint32_t wo[8][4], w1[8][4];
  const uint32_t wo_lane = sb + ((lane & 7) + ((lane >> 4) << 3)) * 128 + (((w + 4 * ((lane >> 3) & 1)) ^ (lane & 7)) << 4);
  unsigned char* const g_red = tm.red;
  {
    const uint32_t tag = *(volatile unsigned*)&g_epoch + 1;
    QSTAMP(0);
    bar_sync(0, 160);
    QSTAMP(1);
    cluster_arrive();
    __half2 hx = __float2half2_rn(0.f);
    if (t2 == 0) { sts32(sb + SC_OFL, (tag - 1) * NSEG); sts64(sb + SC_EPO, (tag - 1) * NSEG + 1, NSEG); sts64(sb + SC_TAG, tag & 1, blockIdx.x / 3 * 4096 + (RANK < 2 ? RANK * 1024 - (sb >> 1) : 2048 - sb)); sts32(sb + SC_UNSC, __float_as_uint(1.f)); sts128(sb + SC_DEAD, 0, 0, 0, 0x3f800000u); sts64(sb + SC_FPAR, 0, 0); sts128(sb + SC_ONES, 0x3f803f80u, 0x3f803f80u, 0x3f803f80u, 0x3f803f80u); }
    WSTAMP(27);
    uint32_t q[8] = {0, 0, 0, 0, 0, 0, 0, 0};
    QSTAMP(2);
    mbar_wait(sb + MB_WO3, 0);
    QSTAMP(3);
    uint32_t mv[5][4];
#pragma unroll
    for (int i = 0; i < 5; i++) {
      ldsm4(mv[i], sb + SM_M0 + (lane & 7) * (DM * 2) + min(w + 4 * i, 17) * 64 + (lane >> 3) * 16);
      if (blockIdx.x == 0) hx = amax4(hx, mv[i]);
    }
#pragma unroll
    for (int k = 0; k < 8; k++) {
      ldsm4t(wo[k], wo_lane + SM_WO3 + k * 2048); ldsm4t(w1[k], wo_lane + SM_WOST + k * 2048);
#pragma unroll
      for (int i = 0; i < 4; i++) { sq_acc(q[i], wo[k][i]); sq_acc(q[i], w1[k][i]); }
    }
    bar_sync(6, 128);
#pragma unroll
    for (int k = 0; k < 8; k++) sts128(sb + SM_WO3 + t2 * 16 + k * 2048, wo[k][0], wo[k][1], wo[k][2], wo[k][3]);
#pragma unroll
    for (int i = 0; i < 5; i++) {
      const int c = (w + 4 * i) * 32;
      if (c < DM) stsm4t(sb + SM_MEM + (c + c / 192 * 64 + lane) * 16, mv[i][0], mv[i][1], mv[i][2], mv[i][3]);
    }
    bar_arrive(1, 256); bar_arrive(2, 256); bar_arrive(9, 256);
    QSTAMP(4);
    mbar_wait(sb + MB_WO, 0);
    QSTAMP(5);
#pragma unroll
    for (int k = 0; k < 8; k++) ldsm4t(wo[k], wo_lane + SM_X + XT + k * 2048);
    fence_async();
    bar_sync(6, 128);
    if (t2 == 32) tma_load3(sb + SM_X + XT, &tm.x, 32, sb + MB_X + 8);
    __syncwarp();
#pragma unroll
    for (int k = 0; k < 8; k++)
#pragma unroll
      for (int i = 0; i < 4; i++) sq_acc(q[4 + i], wo[k][i]);
    float ss = 0.f;
#pragma unroll
    for (int i = 0; i < 8; i++) ss += bf_lo(q[i]) + bf_hi(q[i]);
    ss = warp_sum(ss);
    if (lane == 0) sts32(sb + SC_SS + 4 * (8 + w), __float_as_uint(ss));
    if (blockIdx.x < NSEG) {
      mbar_wait(sb + MB_XS, 0);
#pragma unroll
      for (int i = 0; i < 18; i++) { uint32_t v[4]; lds128(sb + SM_X + 2 * XT + t2 * 16 + i * 2048, v); hx = amax4(hx, v); }
      fence_async();
      bar_sync(6, 128);
      if (t2 == 32) tma_load3(sb + SM_X + 2 * XT, &tm.x, 64, sb + MB_X + 16);
      __syncwarp();
    }
    sts32(sb + SC_SS + 4 * (12 + w), wexp(hx));
    QSTAMP(6);
    bar_sync(11, 384);
    QSTAMP(7);
    if (t2 == 0) {
      float a[16];
#pragma unroll
      for (int i = 0; i < 4; i++) lds128f(sb + SC_SS + 16 * i, &a[4 * i]);
      stg_relaxed(&g_stats[blockIdx.x * 2], __float_as_uint(((a[0] + a[1]) + (a[2] + a[3])) + ((a[4] + a[5]) + (a[6] + a[7]))),
                  __float_as_uint((a[8] + a[9]) + (a[10] + a[11])),
                  max(max(__float_as_uint(a[12]), __float_as_uint(a[13])), max(__float_as_uint(a[14]), __float_as_uint(a[15]))), tag);
    }
    __syncwarp();
    WSTAMP(24);
    QSTAMP(8);
    cluster_wait();
    QSTAMP(9);
    if (w == 0) {
      uint4 v[3];
      int n = 0;
      while (true) {
#pragma unroll
        for (int i = 0; i < 3; i++) v[i] = ldg_relaxed(&g_stats[(i * 32 + lane) * 2]);
        if (__all_sync(0xffffffffu, v[0].w == tag && v[1].w == tag && v[2].w == tag) || ++n > SPIN_LIMIT) break;
        __nanosleep(100);
      }
      WSTAMP(25);
      QSTAMP(10);
      const float sv = warp_sum(__uint_as_float(v[0].x) + __uint_as_float(v[1].x) + __uint_as_float(v[2].x));
      const float so = warp_sum(__uint_as_float(v[0].y) + __uint_as_float(v[1].y) + __uint_as_float(v[2].y));
      const int expW = ((int)(__float_as_uint(sv) >> 23) + (int)(__float_as_uint(so) >> 23) - 254 + 2 + 10 + 1) >> 1;
      sts32(sb + SC_XMAX + 4 * lane, v[0].z); sts32(sb + SC_XMAX + 128 + 4 * lane, v[1].z);
      sts32(sb + SC_EXPW, expW + 1 - 15);
      if (blockIdx.x == 0 && lane == 0) *(volatile unsigned*)&g_epoch = tag;
      sts32(sb + SC_FPAR + 4, 1);
    } else if (w < 3) {
      const uint32_t u = blockIdx.x >> 4;
      unsigned char* const z = g_red + 98304 + (blockIdx.x & 15) * 128 + (u & 1) * 2048 + (u & 6) * 4096 + (((u >> 1) ^ w) & 1) * 4096 + lane * 4;
      stg_relaxed32(z, 0);
      uint32_t best = 0xffffffffu;
#pragma unroll 1
      for (int i = 0; i < 64; i++) {
        uint32_t dt;
        asm volatile("{\n.reg .pred p;\n.reg .u32 c, v;\nmov.u32 c, %%clock;\n"
                     "atom.relaxed.gpu.global.exch.b32 v, [%1], 0;\nsetp.eq.u32 p, v, 0;\nmov.u32 %0, 0;\n@p mov.u32 %0, %%clock;\nsub.u32 %0, %0, c;\n}"
                     : "=r"(dt) : "l"(z) : "memory");
        best = min(best, dt);
        if (lds32v(sb + SC_FPAR + 4) && i >= 1) break;
      }
      sts32(sb + SC_LAT + (w - 1) * 4, best);
    }
    QSTAMP(11);
    bar_sync(13, 384);
    bar_arrive(0, 384);
    QSTAMP(12);
    WSTAMP(26);
  }

  const uint32_t nh = __shfl_sync(0xffffffffu, near_half(sb), 0);
  uint32_t l16 = sb + lane * 16;
  PIN(l16);
#define LV ((l16 >> 4) & 31)
#define fence_reg l16
  const uint32_t red_lo = (uint32_t)(uint64_t)g_red, red_hi = (uint32_t)((uint64_t)g_red >> 32);
  uint32_t lp;
  auto slot = [&](int s, uint32_t c, uint32_t ofs) {
    const uint32_t lo = lp | (red_lo + ((w >> 1) * 4 + (w & 1) * 2 + ((w ^ c) & 1)) * 4096 + RED_SLOT(s) + ofs);
    uint64_t a; asm("mov.b64 %0, {%1, %2};" : "=l"(a) : "r"(lo), "r"(red_hi));
    return (unsigned char*)a;
  };
  const uint32_t always = __shfl_sync(0xffffffffu, lds32(sb + SC_DEAD + 12), 0);
  const int mode0 = RANK < 2 ? w : w | 4;
  auto hint_addr = [&](int s) { return min(LV, 23u) * 4 + (red_lo + HINT_OFF + nh * 4096 + w * 16384 + RED_SLOT(s)); };
  auto load_hints = [&](uint32_t lo) {
    uint64_t a; asm("mov.b64 %0, {%1, %2};" : "=l"(a) : "r"(lo), "r"(red_hi));
    return ldg_relaxed32((const void*)a);
  };
  int s = 0;
  bool bad = false;
#pragma unroll 1
  while (true) {
    const uint32_t par = s & 1;
    uint32_t vx[4][4], hints;
    auto load_vx = [&]() {
      const uint32_t va = l16 + (RANK < 2 ? SM_VC + par * 8192 : SM_BLK + (s & 3) * SEGB) + w * 1024 + ((LV >> 3) & 1) * 384 - (LV >> 4) * 128;
#pragma unroll
      for (int i = 0; i < 4; i++) ldsm4(vx[i], va + (i & 1) * 4096 + (i >> 1) * 256);
    };
    auto retire = [&](uint32_t x) {
      asm volatile("{\n.reg .pred p;\nsetp.eq.u32 p, %0, 0;\n@p exit;\n}" :: "r"(vx[0][0] | vx[1][0] | vx[2][0] | vx[3][0] | x) : "memory");
    };
    auto scores = [&](auto memkeys, auto first, float* sc) {
      constexpr bool MK = decltype(memkeys)::value, FIRST = decltype(first)::value;
      uint32_t kb[4][4], qb[2][4];
      const uint32_t m = LV >> 3;
      uint32_t kaddr = l16 + SM_BLK + 4096 + (s & 3) * SEGB + w * 2048 + (m & 1) * (MK ? 128 : 896) - (m >> 1) * 128;
      if (MK) { PIN(kaddr); }
      else {
#pragma unroll
        for (int k = 0; k < 4; k++) ldsm4t(kb[k], kaddr + k * 256);
      }
      if (FIRST) { load_vx(); retire(MK ? kaddr : kb[0][0] | kb[1][0] | kb[2][0] | kb[3][0] | l16); bar_sync(4, 256); PROF(4); }
      ldsm4t(qb[0], l16 + SM_QM);
      if (MK) ldsm4t(kb[0], kaddr);
      ldsm4t(qb[1], l16 + SM_QM + 512);
      if (MK) ldsm4t(kb[2], kaddr + 512);
      float c[4][4];
      mma16816z(c[0], kb[0], qb[0][0], qb[0][1]); mma16816z(c[1], kb[MK ? 0 : 1], qb[0][2], qb[0][3]);
      mma16816z(c[2], kb[2], qb[1][0], qb[1][1]); mma16816z(c[3], kb[MK ? 2 : 3], qb[1][2], qb[1][3]);
      if (FIRST) bar_arrive(5, N5);
#pragma unroll
      for (int i = 0; i < (MK ? 2 : 4); i++) sc[i] = ((c[0][i] + c[1][MK ? i + 2 : i]) + c[2][i]) + c[3][MK ? i + 2 : i];
    };
    auto send = [&](auto memkeys) {
      constexpr bool MK = decltype(memkeys)::value;
      constexpr int N = MK ? 1 : 2;
      const uint32_t sa = sb + LV * 4 + SM_E + (MK ? 1024 + RANK * 128 : RANK * 512 + w * 256);
      uint32_t ra[N][2], mb[N][2];
#pragma unroll
      for (int i = 0; i < N; i++)
#pragma unroll
        for (int j = 0; j < 2; j++) {
          ra[i][j] = mapa(sa + i * 128, j ? 2 : RANK ^ 1); mb[i][j] = mapa(sb + MB_S, j ? 2 : RANK ^ 1);
          PIN(ra[i][j]);
        }
      float sc[4];
      scores(memkeys, BoolC<true>(), sc);
      uint32_t e[N];
#pragma unroll
      for (int i = 0; i < N; i++) {
        e[i] = pack_bf16(ex2(sc[2 * i]), ex2(sc[2 * i + 1]));
        if (!(fmaxf(fabsf(sc[2 * i]), fabsf(sc[2 * i + 1])) <= E_LIM)) e[i] = 0x7fff7fffu;
        st_async1(ra[i][0], e[i], mb[i][0]);
        st_async1(ra[i][1], e[i], mb[i][1]);
      }
#pragma unroll
      for (int i = 0; i < N; i++) sts32(sa + i * 128, e[i]);
      __syncwarp();
      if (l16 == sb) mbar_arrive(sb + MB_S);
      PROF(5);
    };
    const int mode = bad ? 8 : mode0;
    if (mode < 2) {
      send(BoolC<false>());
    } else if (mode == 2) {
      send(BoolC<true>());
    } else if (mode == 8) {
      load_vx();
      retire(l16);
      const uint32_t fp = lds32(sb + SC_FPAR);
      bar_sync(6, 128);
      if (w == 0 && l16 == sb) { sts32(sb + SC_FPAR, fp ^ 1); mbar_expect(sb + MB_F, 3072); }
      if (RANK < 2 && w < 3) {
        float sc[4] = {0.f, 0.f, 0.f, 0.f};
        if (w < 2) scores(BoolC<false>(), BoolC<false>(), sc); else scores(BoolC<true>(), BoolC<false>(), sc);
#pragma unroll 1
        for (int r = 0; r < 3; r++)
          st_async4(mapa(l16 + SM_FB + RANK * 1536 + w * 512, r), __float_as_uint(sc[0]), __float_as_uint(sc[1]), __float_as_uint(sc[2]), __float_as_uint(sc[3]), mapa(sb + MB_F, r));
      }
      mbar_wait(sb + MB_F, fp);
      float a[12];
#pragma unroll
      for (int j = 0; j < 3; j++) {
        float b[4];
        lds128f(l16 + SM_FB + j * 512, a + 4 * j); lds128f(l16 + SM_FB + 1536 + j * 512, b);
#pragma unroll
        for (int i = 0; i < 4; i++) a[4 * j + i] += b[i];
      }
      float m0 = fmaxf(fmaxf(fmaxf(a[0], a[2]), fmaxf(a[4], a[6])), a[8]), m1 = fmaxf(fmaxf(fmaxf(a[1], a[3]), fmaxf(a[5], a[7])), a[9]);
#pragma unroll
      for (int o = 4; o < 32; o <<= 1) { m0 = fmaxf(m0, __shfl_xor_sync(0xffffffffu, m0, o)); m1 = fmaxf(m1, __shfl_xor_sync(0xffffffffu, m1, o)); }
#pragma unroll
      for (int i = 0; i < 5; i++) {
        const uint32_t ea = sb + SM_E + LV * 4 + (i < 4 ? i * 128 : 1024);
        sts32(ea, pack_bf16(ex2(a[2 * i] - m0), ex2(a[2 * i + 1] - m1)));
        sts32(ea + (i < 4 ? 512 : 128), 0x3f803f80u);
      }
      __syncwarp();
    } else {
      load_vx();
      if (mode == 3) bar_arrive(4, 256);
      retire(l16 + 1);
    }
    {
      uint32_t wa[4], wb[4], oc[4];
      constexpr int WS = 2048;
      const uint32_t w3a = l16 + SM_WO3 + w * 512;
      lds128(w3a + KP(0) * WS, wa); lds128(w3a + KP(1) * WS, wb); lds128(sb + SC_ONES, oc);
      uint32_t e[10], p[5], vm[4], ob[4];
      float o0[4], o1[4], f[3][2][4], rs[4];
      reserve2(vm); reserve2(vm + 2); reserve2(e + 8);
      hints = hint_addr(s);
      PIN(hints);
      mbar_wait(sb + MB_S, par);
      PROF(6);
      ldsm4t(e, l16 + SM_E); ldsm2t_in(e + 8, l16 + SM_E + 1024, always); ldsm4t(e + 4, l16 + SM_E + 512);
      lds128_in(vm, l16 + w * 512 + SM_VM, always);
      const float scl = __uint_as_float(lds32(sb + SC_UNSC + 8 - par * 8));
      hints = load_hints(hints);
#pragma unroll
      for (int i = 0; i < 4; i++) p[i] = mul_bf16(e[i], e[4 + i]);
      p[4] = mul_bf16(e[8], e[9]);
      mma16816z(o0, vx[0], p[0], p[1]); mma16816z(o1, vx[1], p[0], p[1]); mma16816z(rs, oc, p[0], p[1]);
      mma16816(o0, vx[2], p[2], p[3]); lds128_in(vx[2], w3a + KP(2) * WS, always);
      mma16816(o1, vx[3], p[2], p[3]); lds128_in(vx[3], w3a + KP(3) * WS, always);
      mma16816(rs, oc, p[2], p[3]);
      mma1688(o0, vm[0], vm[1], p[4]); mma1688(o1, vm[2], vm[3], p[4]); mma1688(rs, oc[0], oc[1], p[4]);
      stsm4(l16 + w * 512 + SM_OB, pack_bf16(o0[0], o0[1]), pack_bf16(o0[2], o0[3]), pack_bf16(o1[0], o1[1]), pack_bf16(o1[2], o1[3]));
      bar_sync(6, 128);
      PROF(7);
      ldsm4t_in(oc, l16 + SM_OB, always);
      bad = __any_sync(0xffffffffu, !(rs[0] + rs[1] > 0.f) && !bad);
      rs[0] *= scl; rs[1] *= scl;
      asm volatile("{\n.reg .pred p;\nsetp.ne.u32 p, %1, 0;\n@p rcp.approx.ftz.f32 %0, %0;\n}" : "+f"(rs[0]) : "r"(always));
      asm volatile("{\n.reg .pred p;\nsetp.ne.u32 p, %1, 1;\n@p rcp.approx.ftz.f32 %0, %0;\n}" : "+f"(rs[1]) : "r"(always));
      asm volatile("lop3.b32 %0, %1, %2, %3, 0xfe;" : "=r"(lp) : "r"((l16 & 128) * 2), "r"((l16 & 256) * 4), "r"(l16 & 112));
      if (bad) continue;
      ldsm4t(ob, l16 + SM_OB + 512);
      mma16816z(f[2][0], wa, oc[0], oc[1]); mma16816z(f[2][1], wb, oc[2], oc[3]);
      mma16816z(f[0][0], wo[0], oc[0], oc[1]); mma16816z(f[0][1], wo[4], oc[2], oc[3]);
      mma16816z(f[1][0], w1[0], oc[0], oc[1]); mma16816z(f[1][1], w1[4], oc[2], oc[3]);
      ldsm4t_in(oc, l16 + SM_OB + 1024, always);
      mma16816(f[2][0], vx[2], ob[0], ob[1]); lds128_in(vx[2], w3a + KP(4) * WS, always);
      mma16816(f[2][1], vx[3], ob[2], ob[3]); lds128_in(vx[3], w3a + KP(5) * WS, always);
      mma16816(f[0][0], wo[1], ob[0], ob[1]); mma16816(f[0][1], wo[5], ob[2], ob[3]);
      mma16816(f[1][0], w1[1], ob[0], ob[1]); mma16816(f[1][1], w1[5], ob[2], ob[3]);
      ldsm4t_in(ob, l16 + SM_OB + 1536, always);
      mma16816(f[0][0], wo[2], oc[0], oc[1]); mma16816(f[0][1], wo[6], oc[2], oc[3]);
      mma16816(f[2][0], vx[2], oc[0], oc[1]); lds128_in(vx[2], w3a + KP(6) * WS, always);
      mma16816(f[2][1], vx[3], oc[2], oc[3]); lds128_in(vx[3], w3a + KP(7) * WS, always);
      mma16816(f[1][0], w1[2], oc[0], oc[1]); mma16816(f[1][1], w1[6], oc[2], oc[3]);
      mma16816(f[0][0], wo[3], ob[0], ob[1]); mma16816(f[0][1], wo[7], ob[2], ob[3]);
      mma16816(f[1][0], w1[3], ob[0], ob[1]); mma16816(f[1][1], w1[7], ob[2], ob[3]);
      mma16816(f[2][0], vx[2], ob[0], ob[1]); mma16816(f[2][1], vx[3], ob[2], ob[3]);
      bar_arrive(7, 256);
      lds128_in(ob, sb + SC_DEAD, always);
      uint32_t h[3][2];
#pragma unroll
      for (int j = 0; j < 3; j++)
#pragma unroll
        for (int i = 0; i < 2; i++)
        {
          scale_sum(f[j][1][2 * i], f[j][0][2 * i], rs[0], always); scale_sum(f[j][1][2 * i + 1], f[j][0][2 * i + 1], rs[1], always);
          h[j][i] = pack_f16(f[j][1][2 * i], f[j][1][2 * i + 1]);
        }
      const uint32_t rofs = RANK * 32768;
      red_f16x8(slot(s, RANK >> 1, rofs), h[0][0], h[1][0], h[2][0], 0x3c00u);
      red_f16x8(slot(s, (RANK >> 1) ^ 1, rofs), h[0][1], h[1][1], h[2][1], 0x3c00u);
      bar_arrive(10, 256);
      SCHED_FENCE(5);
      l16 += ob[1];
    }
    {
    PROF(8);
    const uint32_t ma0 = l16 + SM_MEM + w * 128 + (LV >> 3) * 896 + nh * 512;
    const unsigned char* const sl[2] = {slot(s, nh, 0), slot(s, nh ^ 1, 0)};
    uint32_t dl = gtime() - 1984;
    uint32_t late = latest_hint(hints, dl, s);
    if (late >= 64) {
      int n = 0;
#pragma unroll 1
      do {
        hints = load_hints(hint_addr(s));
        dl = gtime() - 1984;
        late = latest_hint(hints, dl, s);
      } while (late >= 64 && ++n < SPIN_LIMIT);
    }
    dl += late * 32 + tm.poll;
    PROF(9);
    {
      auto wait_until = [&](uint32_t t) {
        asm volatile("{\n.reg .pred p;\n.reg .s32 c;\n.reg .u64 t;\nTL: mov.u64 t, %%globaltimer;\ncvt.u32.u64 c, t;\nsub.s32 c, c, %0;\nsetp.lt.s32 p, c, 0;\n@p bra.uni TL;\n}" :: "r"(t + (l16 & 15)) : "memory");
      };
      uint4 v[2][3];
      auto load = [&](int c) {
#pragma unroll
        for (int r = 0; r < 3; r++) v[c][r] = ldg_relaxed(sl[c ^ (r >> 1)] + r * 32768);
      };
      auto decode = [&](int c, int n) {
        uint32_t q[9];
        __half2 hm;
        const uint32_t ma = ma0 ^ (c * 512);
#pragma unroll
        for (int i = 0; i < 9; i++) {
          const uint32_t h = i % 3 == 0 ? v[c][i / 3].x : (i % 3 == 1 ? v[c][i / 3].y : v[c][i / 3].z);
          const float2 f = __half22float2(*(const __half2*)&h);
          q[i] = pack_bf16(f.x, f.y);
          hm = i ? __hmax2(hm, __habs2(*(const __half2*)&h)) : __habs2(*(const __half2*)&h);
        }
#pragma unroll
        for (int r = 0; r < 3; r++) stsm4(ma + r * 4096, q[3 * r], q[3 * r + 1], q[3 * r + 2], r < 2 ? v[c][r].w : *(const uint32_t*)&hm);
        const bool done = __all_sync(0xffffffffu, v[c][0].w == 0x5000u && v[c][1].w == 0x5000u && v[c][2].w == 0x5000u) || n > SPIN_LIMIT;
        asm volatile("{\n.reg .pred p;\nsetp.ne.u32 p, %0, 0;\n@p bar.arrive %1, 256;\n}" :: "r"((int)done), "r"(1 + c) : "memory");
        return done;
      };
      int n = 0;
      wait_until(dl);
      PROF(10);
#pragma unroll 1
      do {
        load(0);
        load(1);
        asm volatile("{\n.reg .pred p;\nsetp.eq.u32 p, %0, 0;\n@p bar.sync 13, 384;\n}" :: "r"(n) : "memory");
      } while (!decode(0, n++));
      PROF(11);
#pragma unroll 1
      while (!decode(1, n++)) load(1);
      bar_arrive(9, 256);
      PROF(12);
    }
    PROF(13);
    if (++s == NSEG - 1) break;
    }
  }
#undef fence_reg
  if (RANK < 2) bar_arrive(4, 256);
  bar_sync(0, 384);
  cluster_sync();
}

__global__ void __cluster_dims__(3, 1, 1) __launch_bounds__(384, 1)
rec_kernel(const __grid_constant__ RMaps tm, const bf16* __restrict__ x, const bf16* __restrict__ mem0) {
  extern __shared__ __align__(1024) unsigned char smem_raw[];
  const uint32_t sb = smem_u32(smem_raw);
  const int tid = threadIdx.x, lane = tid & 31;
  const int wg = __shfl_sync(0xffffffffu, tid >> 7, 0);
  const int w = __shfl_sync(0xffffffffu, (tid >> 5) & 3, 0);
  uint32_t rank; asm("mov.u32 %0, %%cluster_ctarank;" : "=r"(rank));
  STAMP(0);
  asm volatile("griddepcontrol.launch_dependents;" ::: "memory");
    if (tid == 0) {
      const int h = blockIdx.x / 3;
      mbar_init(sb + MB_XS, 1);
      for (int i = 0; i < 3; i++) { mbar_init(sb + MB_W + 8 * i, 1); mbar_init(sb + MB_X + 8 * i, 1); }
      mbar_init(sb + MB_WO3, 1);
      fence_async();
      load_w(sb, tm, rank, 0);
      mbar_expect(sb + MB_X, XT);
      tma_load3(sb + SM_X, &tm.x, 0, sb + MB_X);
      mbar_expect(sb + MB_WO3, 32768 + 8 * DM * 2);
      tma_load(sb + SM_WOST, &tm.wo, rank * 192 + 64, h * DH, sb + MB_WO3);
      tma_load(sb + SM_WO3, &tm.wo, rank * 192 + 128, h * DH, sb + MB_WO3);
      bulk_load(sb + SM_M0, mem0, 8 * DM * 2, sb + MB_WO3);
      load_w(sb, tm, rank, 1);
      load_w(sb, tm, rank, 2);
      mbar_init(sb + MB_WO, 1);
      mbar_init(sb + MB_S, rank < 2 ? 5 : 6);
      mbar_init(sb + MB_F, 1);
      mbar_init(sb + MB_VX, 1); mbar_init(sb + MB_VX + 8, 1);
      asm volatile("fence.mbarrier_init.release.cluster;" ::: "memory");
      fence_async();
      mbar_expect(sb + MB_X + 8, XT); mbar_expect(sb + MB_X + 16, XT);
      mbar_expect(sb + MB_WO, 16384); mbar_expect(sb + MB_XS, XT);
      mbar_expect(sb + MB_S, rank < 2 ? 640 + 2048 : 1280);
      mbar_expect(sb + MB_VX, 8192); mbar_expect(sb + MB_VX + 8, 8192);
    }
  __syncwarp();
  if (wg < 2) {
    asm volatile("setmaxnreg.inc.sync.aligned.u32 192;");
    __syncwarp();
    QSTAMP(0);
    if (tid < 32) bar_arrive(0, 160);
    QSTAMP(1);
    proj_role(sb, tm, x, rank, wg, w, lane);
  } else {
    asm volatile("setmaxnreg.dec.sync.aligned.u32 120;");
    attn_role(sb, smem_raw, tm, rank, x, mem0, w, lane);
  }
}

constexpr int NAUX = 36;
constexpr int A_ST = 6, A_STAGE = 8192 + 12288, A_W8 = A_ST * A_STAGE, A_EXC = A_W8 + A_ST * 1536, A_ROWS = 57;
constexpr int A_IN = A_EXC + 8 * 2304, A_INB = 3 * SEGB, A_OST = A_IN + 2 * A_INB, A_P = A_OST + 8192, A_G = A_P + 3072;
constexpr int A_BAR = A_G + 1024;
constexpr int A_XT = A_BAR + 1024, A_XW = A_XT;
constexpr int A_TOTAL = A_XT + 4096;
static_assert(A_IN % 1024 == 0 && A_XT % 1024 == 0 && A_IN >= 4 * XT && A_IN + 64 * DM * 2 <= A_BAR && A_TOTAL <= 232448, "side kernel shared memory");
struct AMaps { CUtensorMap x, wa, wa8, o, o3, o16, wob, woa, woa16; const unsigned char* red; uint32_t poll; };

DI void wgmma_n192_ss_nt(float* d, uint64_t da, uint64_t db, int acc) {
  asm volatile("{\n.reg .pred p;\nsetp.ne.b32 p, %98, 0;\n"
               "wgmma.mma_async.sync.aligned.m64n192k16.f32.bf16.bf16 {"
               "%0,%1,%2,%3,%4,%5,%6,%7,%8,%9,%10,%11,%12,%13,%14,%15,%16,%17,%18,%19,%20,%21,%22,%23,%24,%25,%26,%27,%28,%29,%30,%31,"
               "%32,%33,%34,%35,%36,%37,%38,%39,%40,%41,%42,%43,%44,%45,%46,%47,%48,%49,%50,%51,%52,%53,%54,%55,%56,%57,%58,%59,%60,%61,%62,%63,"
               "%64,%65,%66,%67,%68,%69,%70,%71,%72,%73,%74,%75,%76,%77,%78,%79,%80,%81,%82,%83,%84,%85,%86,%87,%88,%89,%90,%91,%92,%93,%94,%95"
               "}, %96, %97, p, 1, 1, 0, 1;\n}\n"
               : ACC8(d, 0), ACC8(d, 8), ACC8(d, 16), ACC8(d, 24), ACC8(d, 32), ACC8(d, 40), ACC8(d, 48), ACC8(d, 56),
                 ACC8(d, 64), ACC8(d, 72), ACC8(d, 80), ACC8(d, 88) : "l"(da), "l"(db), "r"(acc));
}
DI void wgmma_n24_ss_nt(float* d, uint64_t da, uint64_t db, int acc) {
  asm volatile("{\n.reg .pred p;\nsetp.ne.b32 p, %14, 0;\n"
               "wgmma.mma_async.sync.aligned.m64n24k16.f32.bf16.bf16 {%0,%1,%2,%3,%4,%5,%6,%7,%8,%9,%10,%11}, %12, %13, p, 1, 1, 0, 1;\n}\n"
               : ACC8(d, 0), "+f"(d[8]), "+f"(d[9]), "+f"(d[10]), "+f"(d[11]) : "l"(da), "l"(db), "r"(acc));
}
DI void tma_load3d(uint32_t dst, const CUtensorMap* m, int c0, int c1, int c2, uint32_t mb) {
  asm volatile("cp.async.bulk.tensor.3d.shared::cluster.global.mbarrier::complete_tx::bytes [%0], [%1, {%3, %4, %5}], [%2];"
               :: "r"(dst), "l"(m), "r"(mb), "r"(c0), "r"(c1), "r"(c2) : "memory");
}
DI uint32_t trans8(uint32_t x) { uint32_t r; asm("movmatrix.sync.aligned.m8n8.trans.b16 %0, %1;" : "=r"(r) : "r"(x)); return r; }
DI void wgmma_n40_ss(float* d, uint64_t da, uint64_t db, int acc) {
  asm volatile("{\n.reg .pred p;\nsetp.ne.b32 p, %22, 0;\n"
               "wgmma.mma_async.sync.aligned.m64n40k16.f32.bf16.bf16 {%0,%1,%2,%3,%4,%5,%6,%7,%8,%9,%10,%11,%12,%13,%14,%15,%16,%17,%18,%19}, "
               "%20, %21, p, 1, 1, 1, 1;\n}\n"
               : ACC8(d, 0), ACC8(d, 8), "+f"(d[16]), "+f"(d[17]), "+f"(d[18]), "+f"(d[19]) : "l"(da), "l"(db), "r"(acc));
}
template <int ST> DI void ldg8x64(uint32_t* m, const void* p) {
  asm volatile("ld.relaxed.gpu.global.v2.b32 {%0,%1}, [%16];\nld.relaxed.gpu.global.v2.b32 {%2,%3}, [%16 + %17];\n"
               "ld.relaxed.gpu.global.v2.b32 {%4,%5}, [%16 + %18];\nld.relaxed.gpu.global.v2.b32 {%6,%7}, [%16 + %19];\n"
               "ld.relaxed.gpu.global.v2.b32 {%8,%9}, [%16 + %20];\nld.relaxed.gpu.global.v2.b32 {%10,%11}, [%16 + %21];\n"
               "ld.relaxed.gpu.global.v2.b32 {%12,%13}, [%16 + %22];\nld.relaxed.gpu.global.v2.b32 {%14,%15}, [%16 + %23];"
               : "=r"(m[0]), "=r"(m[1]), "=r"(m[2]), "=r"(m[3]), "=r"(m[4]), "=r"(m[5]), "=r"(m[6]), "=r"(m[7]),
                 "=r"(m[8]), "=r"(m[9]), "=r"(m[10]), "=r"(m[11]), "=r"(m[12]), "=r"(m[13]), "=r"(m[14]), "=r"(m[15])
               : "l"(p), "n"(ST), "n"(2 * ST), "n"(3 * ST), "n"(4 * ST), "n"(5 * ST), "n"(6 * ST), "n"(7 * ST) : "memory");
}
template <int ST> DI void ldg4x128(uint32_t* m, const void* p) {
  asm volatile("ld.relaxed.gpu.global.v4.b32 {%0,%1,%2,%3}, [%16];\nld.relaxed.gpu.global.v4.b32 {%4,%5,%6,%7}, [%16 + %17];\n"
               "ld.relaxed.gpu.global.v4.b32 {%8,%9,%10,%11}, [%16 + %18];\nld.relaxed.gpu.global.v4.b32 {%12,%13,%14,%15}, [%16 + %19];"
               : "=r"(m[0]), "=r"(m[1]), "=r"(m[2]), "=r"(m[3]), "=r"(m[4]), "=r"(m[5]), "=r"(m[6]), "=r"(m[7]),
                 "=r"(m[8]), "=r"(m[9]), "=r"(m[10]), "=r"(m[11]), "=r"(m[12]), "=r"(m[13]), "=r"(m[14]), "=r"(m[15])
               : "l"(p), "n"(ST), "n"(2 * ST), "n"(3 * ST) : "memory");
}
template <int N, int ST> DI bool stale(const uint32_t* m, uint32_t tag) {
  uint32_t x = m[0] ^ tag;
#pragma unroll
  for (int i = 1; i < N; i++) asm("lop3.b32 %0, %0, %1, %2, 0xf6;" : "+r"(x) : "r"(m[i * ST]), "r"(tag));
  return __any_sync(0xffffffffu, x & 1);
}
DI int wait_flags(const unsigned* p, bool active, unsigned base, int seg) {
  int n = 0, m;
  while (true) {
    m = __reduce_min_sync(0xffffffffu, active ? (int)(ldg_acquire32(p) - base) : NSEG);
    if (m > seg || ++n > SPIN_LIMIT) break;
    if (seg < NSEG - 2) __nanosleep(40);
  }
  return max(m, seg + 1);
}
DI void wait_count(const unsigned* p, unsigned target) {
  int n = 0;
  unsigned v;
  while (true) {
    asm volatile("ld.acquire.gpu.global.b32 %0, [%1];" : "=r"(v) : "l"(p) : "memory");
    if ((int)(v - target) >= 0 || ++n > SPIN_LIMIT) break;
    __nanosleep(64);
  }
}
#define PACE_NEXT 1024
#define FD 192
#define OD 96
#define PING 60
DI bool tick_wait(uint32_t pace, int step) {
  const int n = lds32v(pace);
  if (n <= step) mbar_wait(pace + 8, n & 1);
  return n <= step;
}
DI void sleep_until(uint32_t t) {
  for (int n = 0; n < 64; n++) {
    const int r = t - gtime();
    if (r <= 0) break;
    __nanosleep(r >> 1);
  }
}
DI void aux_barrier(int i, unsigned epoch) {
  asm volatile("fence.proxy.async;" ::: "memory");
  asm volatile("red.release.gpu.global.add.u32 [%0], 1;" :: "l"(&g_abar[i * 32]) : "memory");
  wait_count(&g_abar[i * 32], NAUX * (epoch + 1));
  asm volatile("fence.proxy.async;" ::: "memory");
}

__global__ void __launch_bounds__(512, 1)
aux_kernel(const __grid_constant__ AMaps tm, const bf16* __restrict__ x, const bf16* __restrict__ gate_w, bf16* __restrict__ out) {
  extern __shared__ __align__(1024) unsigned char smem_raw[];
  const uint32_t sb = smem_u32(smem_raw);
  const uint32_t full1 = sb + A_BAR, empty1 = full1 + 8 * A_ST, fullw = empty1 + 8 * A_ST, full3 = fullw + 16, empty3 = full3 + 32,
                 fulla = empty3 + 32, emptya = fulla + 32, fullg = emptya + 16, pace = fullg + 8;
  const int tid = threadIdx.x, lane = tid & 31, cta = blockIdx.x;
  const int wg = __shfl_sync(0xffffffffu, tid >> 7, 0), w = __shfl_sync(0xffffffffu, (tid >> 5) & 3, 0);
  ASTAMP(14);
  const unsigned epoch = *(volatile unsigned*)&g_epoch2;
  if (tid == 0) {
    for (int i = 0; i < A_ST; i++) { mbar_init(full1 + 8 * i, 1); mbar_init(empty1 + 8 * i, 8); }
    mbar_init(fullw, 1); mbar_init(fullw + 8, 1); mbar_init(fullg, 1);
    for (int i = 0; i < 2; i++) { mbar_init(fulla + 16 * i, 2); mbar_init(fulla + 16 * i + 8, 1); mbar_init(emptya + 8 * i, 4); }
    sts64(pace, 0, 0); mbar_init(pace + 8, 1); sts32(pace + 16, 0); sts64(pace + 24, 65536, 0xffff0000u);
    for (int i = 0; i < 4; i++) { mbar_init(full3 + 8 * i, 1); mbar_init(empty3 + 8 * i, cta < NH ? 8 : 4); }
    fence_async();
  }
  auto load_a = [&](int st, int k, int col) {
    mbar_expect(full1 + 8 * st, A_STAGE + 1536);
    tma_load3d(sb + st * A_STAGE, &tm.x, k, (cta >> 1) * A_ROWS - 7, 0, full1 + 8 * st);
    tma_load3d(sb + st * A_STAGE + 8192, &tm.wa, col, k, 0, full1 + 8 * st);
    tma_load3d(sb + A_W8 + st * 1536, &tm.wa8, col + 64, k, 0, full1 + 8 * st);
  };
  __syncthreads();
  ASTAMP(0);
  const bool wide = cta < NH;
  auto p3_ks = [&](int g) { return wide ? cta >> 2 : 2 * (cta - NH) + g; };
  auto p3_mt = [&](int g) { return wide ? 2 * (cta & 3) + g : 8; };
  const unsigned fbase = epoch * NSEG;
  if (wg == 3) {
    asm volatile("setmaxnreg.dec.sync.aligned.u32 48;");
    if (w == 1 && cta < NH) {
      if (lane < 3) stg_relaxed32(&g_cflag[(cta * 3 + lane) * 32], fbase);
      bar_arrive(5, 160);
#pragma unroll 1
      for (int seg = 0; seg < ((XP & 2048) ? 0 : NSEG); seg++) {
        bar_sync(4, 160);
        if (QM & 16) tick_wait(pace, seg + 1);
        if (elect_one()) {
          fence_async();
          if (!(YP & 2)) {
            tma_store(&tm.o, sb + A_OST, cta * DH, seg * 32);
            tma_store(&tm.o, sb + A_OST + 4096, cta * DH + 64, seg * 32);
          }
          asm volatile("cp.async.bulk.commit_group;" ::: "memory");
          asm volatile("cp.async.bulk.wait_group.read 0;" ::: "memory");
        }
        __syncwarp();
        if (seg < NSEG - 1) bar_arrive(5, 160);
        if (elect_one()) {
          asm volatile("cp.async.bulk.wait_group 0;" ::: "memory");
          TSTAMP(2);
          stg_relaxed32(&g_oflag[cta * 32], fbase + seg + 1);
        }
        __syncwarp();
        if (lane < 3) stg_relaxed32(&g_cflag[(cta * 3 + lane) * 32], fbase + seg + 1);
      }
    }
    if (w == 2 && cta < NH) {
      const uint32_t ktag = (epoch + 1) & 1, ma = sb + A_IN + 8192 + lane * 16;
      int avail = 0;
      int own = 0;
      bar_sync(10, 64);
#pragma unroll 1
      for (int seg = 0; seg < ((XP & 2048) ? 0 : NSEG); seg++) {
        const uint32_t b = seg & 1, full = fulla + 16 * b, mb = ma + b * A_INB;
        mbar_wait(emptya + 8 * b, (~seg >> 1) & 1);
        if (lane < 2) mbar_expect(full + 8 * lane, (YP & 8) ? 0 : 16384 >> lane);
        if (avail <= seg) {
          int n = 0;
          while (true) {
            asm volatile("ld.acquire.gpu.global.v2.b32 {%0,%1}, [%2];" : "=r"(avail), "=r"(own) : "l"(&g_sflag[(cta * 3 + min(lane, 2)) * 4]) : "memory");
            avail = __reduce_min_sync(0xffffffffu, (int)(avail - fbase));
            if (avail > seg || ++n > SPIN_LIMIT) break;
            if (seg < NSEG - 1) __nanosleep(40);
          }
        }
        const int slot = seg < own ? seg & 7 : seg;
        const int s0 = __shfl_sync(0xffffffffu, slot, 0), s1 = __shfl_sync(0xffffffffu, slot, 1), s2 = __shfl_sync(0xffffffffu, slot, 2);
        if ((QM & 8) && tick_wait(pace, seg) && FD && seg < NSEG - 2) sleep_until(gtime() + FD);
        TSTAMP(0);
        if (!(YP & 8) && elect_one()) {
          const unsigned char* src = g_seg + cta * (3 * 8192);
          const uint32_t dst = sb + A_IN + b * A_INB;
          bulk_load(dst, src + (size_t)s0 * (96 * 8192), 8192, full);
          bulk_load(dst + SEGB, src + (size_t)s1 * (96 * 8192) + 8192, 8192, full);
          bulk_load(dst + 2 * SEGB, src + (size_t)s2 * (96 * 8192) + 16384, 8192, full + 8);
        }
        __syncwarp();
        const unsigned char* km = g_km + (size_t)(seg * NH + cta) * 4096 + lane * 8;
        uint32_t m[16];
        const float g = __ldcg(&g_gate[seg * 32 + lane]);
        ldg8x64<256>(m, km);
        int n = 0;
#pragma unroll 1
        while (stale<8, 2>(m, ktag) && ++n < SPIN_LIMIT) { if (seg < NSEG - 1) __nanosleep(200); ldg8x64<256>(m, km); }
        TSTAMP(1);
#pragma unroll
        for (int i = 0; i < 4; i++) stsm4(mb + (i >> 1) * SEGB + (i & 1) * 512, m[4 * i], m[4 * i + 1], m[4 * i + 2], m[4 * i + 3]);
        sts32(sb + A_G + b * 128 + lane * 4, __float_as_uint(1.f - g));
        fence_async();
        __syncwarp();
        if (lane == 0) mbar_arrive(full);
      }
    }
    if (w == 3 && QM) {
      const unsigned char* const hp = tm.red + HINT_OFF + 65536 + (cta & 1) * 4096 + min(lane, 23) * 4;
      uint32_t d = 0;
      int s = 0, n = 0;
#pragma unroll 1
      while (s < NSEG - 1) {
        const uint32_t h = ldg_relaxed32(hp + RED_SLOT(s)), t = (gtime() - 1984) & ~31u, late = latest_hint(h, t, s);
        if (late < 64) {
          d = t + late * 32 + tm.poll;
          sleep_until(d);
          s++; n = 0;
          if (lane == 0) { mbar_arrive(pace + 8); sts64(pace, s < NSEG - 1 ? s : 2 * NSEG, d); }
          sleep_until(d + PACE_NEXT);
        } else {
          if (++n > (s ? 16 : 256) || lds32v(pace + 16)) break;
          if (!s) __nanosleep(100);
        }
      }
      if (s < NSEG - 1 && lane == 0) { mbar_arrive(pace + 8); sts64(pace, 2 * NSEG, d); }
    }
    if (w != 0) return;
    const bool lead = lane == 0;
#pragma unroll 1
    for (int it = 0, st = 0, ph = 1, k = 0, col = (cta & 1) * (DM / 2); it < ((XP & 256) ? 0 : 72); it++) {
      mbar_wait(empty1 + 8 * st, ph);
      if (elect_one()) load_a(st, k, col);
      __syncwarp();
      if (++st == A_ST) { st = 0; ph ^= 1; }
      k += 32;
      if (k == DM) { k = 0; col += 72; }
    }
    auto load_wo = [&](uint32_t dst, int g, int kb, uint32_t mb) {
      if (kb < 64) tma_load(dst, &tm.wob, p3_mt(g) * 64, kb * 64, mb);
      else tma_load(dst, &tm.woa, p3_mt(g) * 64, (kb - 64) * 64, mb);
    };
    if (lead) mbar_expect(fullw, 16 * 8192);
#pragma unroll 1
    for (int st = 0; st < A_ST; st++) {
      if (!(XP & 256)) mbar_wait(empty1 + 8 * st, 1);
      if (lane < 16 && min(((lane + 1) * 8192 - 1) / A_STAGE, A_ST - 1) == st) load_wo(sb + lane * 8192, lane >> 3, p3_ks(lane >> 3) * 9 + (lane & 7), fullw);
      __syncwarp();
    }
    __syncwarp(); bar_sync(6, 288);
    if (lead) mbar_expect(fullw + 8, 2 * 8192 + (p3_ks(0) >= 4 ? 4096 : 0));
    __syncwarp();
    if (lane < 2) {
      load_wo(sb + (16 + lane) * 8192, lane, p3_ks(lane) * 9 + 8, fullw + 8);
      if (p3_ks(0) >= 4) tma_load(sb + A_XW + lane * 2048, &tm.woa16, p3_mt(lane) * 64, 448 + p3_ks(lane) * 16, fullw + 8);
    }
    __syncwarp();
    if (lead) aux_barrier(1, epoch);
    __syncwarp(); bar_sync(6, 288);
    {
      int avail = 0, sl = 0, ph = 1;
      const int h = (9 * p3_ks(0) >> 1) + lane;
#pragma unroll 1
      for (int seg = 0; seg < ((XP & 2048) ? 0 : NSEG); seg++) {
        if (avail <= seg) avail = wait_flags(&g_oflag[min(h, NH - 1) * 32], lane < (wide ? 5 : 9), fbase, seg);
        SSTAMP(seg, 4);
        for (int g = 0; g < (wide ? 1 : 2); g++) {
          const int ks = p3_ks(g);
          mbar_wait(empty3 + 8 * sl, ph);
          if ((QM & 4) && tick_wait(pace, seg + (QM >> 4 & 1) + 1)) sleep_until(gtime() + OD);
          if (YP & 4) { if (lead) mbar_arrive(full3 + 8 * sl); }
          else if (elect_one()) {
            mbar_expect(full3 + 8 * sl, XT + (ks >= 4 ? 1024 : 0));
            tma_load3d(sb + sl * XT, &tm.o3, 0, seg * 32, ks * 9, full3 + 8 * sl);
            if (ks >= 4) tma_load(sb + A_XT + sl * 1024, &tm.o16, 72 * 64 - 64 + ks * 16, seg * 32, full3 + 8 * sl);
          }
          __syncwarp();
          if (++sl == (wide ? 3 : 4)) { sl = 0; ph ^= 1; }
        }
      }
    }
    sts32(pace + 16, 1);
    asm volatile("griddepcontrol.wait;" ::: "memory");
  } else if (wg == 2) {
    asm volatile("setmaxnreg.dec.sync.aligned.u32 64;");
    if (cta < NH) {
      if (tid == 256) { mbar_expect(fullg, 64 * DM * 2); bulk_load(sb + A_IN, x + cta * 64 * DM, 64 * DM * 2, fullg); }
      uint32_t gw[9];
#pragma unroll
      for (int j = 0; j < 9; j++) gw[j] = ((const uint32_t*)gate_w)[j * 32 + lane];
      mbar_wait(fullg, 0);
      float mine = 0.f;
#pragma unroll 4
      for (int u = 0; u < 16; u++) {
        float d0 = 0.f, d1 = 0.f;
#pragma unroll
        for (int j = 0; j < 9; j++) {
          const uint32_t a = lds32(sb + A_IN + (w * 16 + u) * (DM * 2) + j * 128 + lane * 4);
          d0 = fmaf(bf_lo(a), bf_lo(gw[j]), d0); d1 = fmaf(bf_hi(a), bf_hi(gw[j]), d1);
        }
        d0 = warp_sum(d0 + d1);
        if (lane == u) mine = d0;
      }
      if (lane < 16) g_gate[cta * 64 + w * 16 + lane] = 1.f / (1.f + __expf(-mine));
      fence_async();
    }
    bar_sync(3, 128);
    if (tid == 256) { aux_barrier(0, epoch); if (cta == 0) *(volatile unsigned*)&g_epoch2 = epoch + 1; }
    __syncwarp();
    bar_sync(3, 128);
    if (w == 0) bar_arrive(8, 288);
    if (w == 1 && cta < NH) bar_arrive(10, 64);
    if (cta < NH) {
      CDECL;
#pragma unroll 1
      for (int seg = 0; seg < ((XP & 2048) ? 0 : NSEG); seg++) {
        CSTAMP(0);
        const uint32_t in = sb + A_IN + (seg & 1) * A_INB;
        const uint64_t qd = make_desc(in, 128, 1024, 0);
        mbar_wait(fulla + 16 * (seg & 1), (seg >> 1) & 1);
        CSTAMP(3);
        SSTAMP(seg, 0);
        float d[2][16];
        {
          float a[20];
          uint32_t vm[16];
          const unsigned char* vp = g_km + (size_t)(seg * NH + cta) * 4096 + 2048 + lane * 16;
          if (w == 3) ldg4x128<512>(vm, vp);
          WG_FENCE();
#pragma unroll
          for (int k = 0; k < ((YP & 16) ? 1 : 8); k++) wgmma_n40_ss(a, qd + ((k >> 2) * SEGB + (k & 3) * 256 >> 4), qd + ((k >> 2) * SEGB + (k & 3) * 256 + 4096 >> 4), k > 0);
          const uint32_t ga = sb + A_G + (seg & 1) * 128 + (w & 1) * 64 + (lane >> 2) * 4;
          const float f0 = __uint_as_float(lds32(ga)), f1 = __uint_as_float(lds32(ga + 32));
          WG_COMMIT();
          WG_WAIT(0);
          CSTAMP(5);
          SSTAMP(seg, 1);
          if (w < 2) {
            const int lim = w * 16 + (lane >> 2) - 2 * (lane & 3);
            float m0 = -3.0e38f, m1 = -3.0e38f;
#pragma unroll
            for (int i = 0; i < 20; i++) {
              if (i < 16 && (i >> 2) * 8 + (i & 1) - (i & 2) * 4 > lim) a[i] = -1.0e9f / SM_SCALE;
              if (i & 2) m1 = fmaxf(m1, a[i]); else m0 = fmaxf(m0, a[i]);
            }
#pragma unroll
            for (int o = 1; o < 4; o <<= 1) { m0 = fmaxf(m0, __shfl_xor_sync(0xffffffffu, m0, o)); m1 = fmaxf(m1, __shfl_xor_sync(0xffffffffu, m1, o)); }
#pragma unroll
            for (int i = 0; i < 20; i++) a[i] = ex2((a[i] - (i & 2 ? m1 : m0)) * (SM_SCALE * LOG2E));
            float s0 = ((a[0] + a[1]) + (a[4] + a[5])) + ((a[8] + a[9]) + (a[12] + a[13])) + (a[16] + a[17]);
            float s1 = ((a[2] + a[3]) + (a[6] + a[7])) + ((a[10] + a[11]) + (a[14] + a[15])) + (a[18] + a[19]);
#pragma unroll
            for (int o = 1; o < 4; o <<= 1) { s0 += __shfl_xor_sync(0xffffffffu, s0, o); s1 += __shfl_xor_sync(0xffffffffu, s1, o); }
            s0 = f0 * rcp(s0); s1 = f1 * rcp(s1);
            uint32_t p[10];
#pragma unroll
            for (int i = 0; i < 10; i++) p[i] = pack_bf16(a[2 * i] * (i & 1 ? s1 : s0), a[2 * i + 1] * (i & 1 ? s1 : s0));
            const uint32_t pa = sb + A_P + (2 * w + ((lane >> 3) & 1)) * 768 + (lane >> 4) * 128 + (lane & 7) * 16;
            stsm4t(pa, p[0], p[1], p[2], p[3]); stsm4t(pa + 256, p[4], p[5], p[6], p[7]); stsm4t(pa + 512, p[8], p[9], 0, 0);
            CSTAMP(6);
            fence_async();
            CSTAMP(7);
          } else if (w == 3) {
            int n = 0;
#pragma unroll 1
            while (stale<4, 4>(vm, (epoch + 1) & 1) && ++n < SPIN_LIMIT) ldg4x128<512>(vm, vp);
#pragma unroll
            for (int i = 0; i < 4; i++) stsm4(in + 2 * SEGB + 8192 + (lane >> 4) * 1024 + (lane & 15) * 16 + i * 256, vm[4 * i], vm[4 * i + 1], vm[4 * i + 2], vm[4 * i + 3]);
            fence_async();
            mbar_wait(fulla + 16 * (seg & 1) + 8, (seg >> 1) & 1);
          }
        }
        CSTAMP(8);

        bar_sync(5, 160);
        CSTAMP(10);
        SSTAMP(seg, 2);
        const uint64_t pd = make_desc(sb + A_P, 128, 768, 0), vd = make_desc(in + 2 * SEGB, 128, 512, 0), md = make_desc(in + 2 * SEGB + 8192, 0, 128, 0);
        WG_FENCE();
#pragma unroll
        for (int i = 0; i < 2; i++) {
          wgmma_n32_ss<0>(d[i], vd + i * 256, pd, 0);
          wgmma_n32_ss<0>(d[i], vd + i * 256 + 16, pd + 16, 1);
          wgmma_n32_ss<0>(d[i], md + i * 64, pd + 32, 1);
        }
        WG_COMMIT();
        WG_WAIT(0);
        CSTAMP(11);
        if (lane == 0) mbar_arrive(emptya + 8 * (seg & 1));
#pragma unroll
        for (int i = 0; i < 2; i++) {
          const uint32_t oa = sb + A_OST + i * 4096 + ((lane & 7) + ((lane >> 4) << 3)) * 128 + (((2 * w + ((lane >> 3) & 1)) ^ (lane & 7)) << 4);
          stsm4t(oa, pack_bf16(d[i][0], d[i][1]), pack_bf16(d[i][2], d[i][3]), pack_bf16(d[i][4], d[i][5]), pack_bf16(d[i][6], d[i][7]));
          stsm4t(oa + 2048, pack_bf16(d[i][8], d[i][9]), pack_bf16(d[i][10], d[i][11]), pack_bf16(d[i][12], d[i][13]), pack_bf16(d[i][14], d[i][15]));
        }
        CSTAMP(12);
        bar_sync(4, 160);
        SSTAMP(seg, 3);
      }
      CDUMP;
    }
  } else {
    asm volatile("setmaxnreg.inc.sync.aligned.u32 200;");
    {
      const int g = lane >> 2, t = lane & 3, r0 = (cta >> 1) * A_ROWS - 7 + w * 16;
      const uint32_t prev = (2 * t > g ? 0xffffu : 0u) | (2 * t + 1 > g ? 0xffff0000u : 0u);
      const int k0 = r0 + 2 * t - (2 * t > g ? 8 : 0), k1 = r0 + 2 * t + 1 - (2 * t + 1 > g ? 8 : 0);
      const uint32_t slot = sb + A_EXC + (wg * 4 + w) * 2304;
      float gl = 0.f, gh = 0.f;
      int st = 0, ph = 0;
#pragma unroll 1
      for (int p = 0; p < ((XP & 256) ? 0 : 4); p++) {
        float big[96], sml[12];
        if (p == 3 && tid < 18) {
          const int kb = p3_ks(tid >= 9) * 9 + tid % 9;
          tma_prefetch(kb < 64 ? &tm.wob : &tm.woa, p3_mt(tid >= 9) * 64, (kb & 63) * 64);
        }
        __syncwarp();
#pragma unroll
        for (int i = 0; i < 96; i++) big[i] = 0.f;
#pragma unroll
        for (int i = 0; i < 12; i++) sml[i] = 0.f;
#pragma unroll 1
        for (int k = 0; k < 18; k++) {
          mbar_wait(full1 + 8 * st, ph);
          const uint64_t da = make_desc(sb + st * A_STAGE + wg * 4096, 16, 512, 2);
          const uint64_t db = make_desc(sb + st * A_STAGE + 8192, 4096, 1024, 1), dc = make_desc(sb + A_W8 + st * 1536, 128, 512, 0);
          WG_FENCE();
#pragma unroll
          for (int j = 0; j < 2; j++) { wgmma_n192_ss_nt(big, da + j * 2, db + j * 128, 1); wgmma_n24_ss_nt(sml, da + j * 2, dc + j * 16, 1); }
          WG_COMMIT();
          WG_WAIT(1);
          if (k > 0 && lane == 0) mbar_arrive(empty1 + 8 * (st ? st - 1 : A_ST - 1));
          if (++st == A_ST) { st = 0; ph ^= 1; }
        }
        WG_WAIT(0);
        ASTAMP(16 + p + wg * 16);
        if (lane == 0) mbar_arrive(empty1 + 8 * (st ? st - 1 : A_ST - 1));
        uint32_t f[3][9][2];
#pragma unroll
        for (int c = 0; c < 3; c++)
#pragma unroll
          for (int j = 0; j < 9; j++)
#pragma unroll
            for (int i = 0; i < 2; i++) {
              const float* a = j < 8 ? &big[(c * 8 + j) * 4 + 2 * i] : &sml[c * 4 + 2 * i];
              f[c][j][i] = c < 2 ? pack_bf16(a[0], a[1]) : trans8(pack_bf16(a[0], a[1]));
            }
        if (p == 0) {
          bar_sync(8, 288);
          gl = __ldcg(&g_gate[min(max(r0 + g, 0), S_LEN / 2 - 1) * 2 + wg]); gh = __ldcg(&g_gate[min(max(r0 + g + 8, 0), S_LEN / 2 - 1) * 2 + wg]);
        }
        asm volatile("cp.async.bulk.wait_group.read 0;" ::: "memory");
        __syncwarp();
#pragma unroll
        for (int j = 0; j < 8; j += 2) sts128(slot + j * 256 + lane * 16, f[1][j][1], f[2][j][1], f[1][j + 1][1], f[2][j + 1][1]);
        sts64(slot + 2048 + lane * 8, f[1][8][1], f[2][8][1]);
        bar_sync(1 + wg, 128);
        ASTAMP(24 + p + wg * 16);
        uint32_t pv[9][2];
#pragma unroll
        for (int j = 0; j < 9; j++) pv[j][0] = pv[j][1] = 0;
        if (w) {
#pragma unroll
          for (int j = 0; j < 8; j += 2) lds128(slot - 2304 + j * 256 + lane * 16, pv[j]);
          lds64(slot - 256 + lane * 8, pv[8][0], pv[8][1]);
        }
        float a[4][4], m[4][2];
#pragma unroll
        for (int h = 0; h < 4; h++) {
          const int j = 2 * h;
          const uint32_t qa[4] = {t >= h ? f[0][j][0] : 0, t >= h ? f[0][j][1] : 0, f[0][j + 1][0], f[0][j + 1][1]};
          const uint32_t qb0 = t <= h ? f[0][j + 2][0] : 0, qb1 = t <= h ? f[0][j + 2][1] : 0;
          float s0[4], s1[4], s2[4];
          mma16816z(s1, qa, f[1][j][0], f[1][j + 1][0]); mma16816z(s2, qa, f[1][j][1], f[1][j + 1][1]); mma16816z(s0, qa, pv[j][0], pv[j + 1][0]);
          mma1688(s1, qb0, qb1, f[1][j + 2][0]); mma1688(s2, qb0, qb1, f[1][j + 2][1]); mma1688(s0, qb0, qb1, pv[j + 2][0]);
          a[h][0] = 2 * t > g ? s0[0] : s1[0]; a[h][1] = 2 * t + 1 > g ? s0[1] : s1[1]; a[h][2] = 2 * t > g ? s1[2] : s2[2]; a[h][3] = 2 * t + 1 > g ? s1[3] : s2[3];
        }
#pragma unroll
        for (int h = 0; h < 4; h++) {
#pragma unroll
          for (int i = 0; i < 4; i++) a[h][i] = (i & 1 ? k1 : k0) + (i & 2) * 4 >= 0 ? a[h][i] * (0.23570226039551584f * LOG2E) : -1.0e9f * LOG2E;
          m[h][0] = fmaxf(a[h][0], a[h][1]); m[h][1] = fmaxf(a[h][2], a[h][3]);
        }
#pragma unroll
        for (int x = 1; x < 4; x <<= 1)
#pragma unroll
          for (int i = 0; i < 8; i++) m[i >> 1][i & 1] = fmaxf(m[i >> 1][i & 1], __shfl_xor_sync(0xffffffffu, m[i >> 1][i & 1], x));
#pragma unroll
        for (int h = 0; h < 4; h++) {
#pragma unroll
          for (int i = 0; i < 4; i++) a[h][i] = ex2(a[h][i] - m[h][i >> 1]);
          m[h][0] = a[h][0] + a[h][1]; m[h][1] = a[h][2] + a[h][3];
        }
#pragma unroll
        for (int x = 1; x < 4; x <<= 1)
#pragma unroll
          for (int i = 0; i < 8; i++) m[i >> 1][i & 1] += __shfl_xor_sync(0xffffffffu, m[i >> 1][i & 1], x);
        uint32_t o[9][2];
#pragma unroll
        for (int h = 0; h < 4; h++) {
          const int j = 2 * h;
          const float z0 = gl * rcp(m[h][0]), z1 = gh * rcp(m[h][1]);
          const uint32_t pl = pack_bf16(a[h][0] * z0, a[h][1] * z0), pu = pack_bf16(a[h][2] * z1, a[h][3] * z1);
          const uint32_t pa[4] = {pl & prev, 0, pl & ~prev, pu & prev};
          float d[3][4];
#pragma unroll
          for (int i = 0; i < 3; i++) mma16816z(d[i], pa, pv[j + i][1], f[2][j + i][0]);
#pragma unroll
          for (int i = 0; i < 3; i++) mma1688(d[i], 0, pu & ~prev, f[2][j + i][1]);
#pragma unroll
          for (int i = 0; i < 3; i++) {
            const uint32_t d0 = pack_bf16(d[i][0], d[i][1]), d1 = pack_bf16(d[i][2], d[i][3]);
            o[j + i][0] = i == 0 && h > 0 && t < h ? o[j][0] : d0;
            o[j + i][1] = i == 0 && h > 0 && t < h ? o[j][1] : d1;
          }
        }
        ASTAMP(28 + p + wg * 16);
        bar_sync(1 + wg, 128);
        const uint32_t oa = slot + (lane & 15) * 144 + (lane >> 4) * 16;
#pragma unroll
        for (int j = 0; j < 8; j += 2) stsm4(oa + j * 16, o[j][0], o[j][1], o[j + 1][0], o[j + 1][1]);
        asm volatile("stmatrix.sync.aligned.m8n8.x2.shared.b16 [%0], {%1,%2};" :: "r"(oa + 128), "r"(o[8][0]), "r"(o[8][1]) : "memory");
        fence_async();
        __syncwarp();
        if (lane < 16 && w * 16 + lane >= 7 && r0 + lane < S_LEN / 2)
          asm volatile("cp.async.bulk.global.shared::cta.bulk_group [%0], [%1], 144;"
                       :: "l"(g_Ocat + (size_t)((r0 + lane) * 2 + wg) * KCAT + 4096 + (cta & 1) * (DM / 2) + p * 72), "r"(slot + lane * 144) : "memory");
        asm volatile("cp.async.bulk.commit_group;" ::: "memory");
        ASTAMP(20 + p + wg * 16);
      }
      if (XP & 256) bar_sync(8, 288);
      asm volatile("cp.async.bulk.wait_group 0;" ::: "memory");
    }
    ASTAMP(3);
    bar_arrive(6, 288);
    uint32_t wa[37][4];
    mbar_wait(fullw, 0);
    const uint32_t la = sb + ((lane & 7) + ((lane >> 4) << 3)) * 128 + (((2 * w + ((lane >> 3) & 1)) ^ (lane & 7)) << 4);
#pragma unroll
    for (int k = 0; k < 32; k++) ldsm4t(wa[k], la + wg * 65536 + k * 2048);
    mbar_wait(fullw + 8, 0);
#pragma unroll
    for (int k = 32; k < 36; k++) ldsm4t(wa[k], la + wg * 8192 + 65536 + k * 2048);
    ldsm4t(wa[36], la + A_XW + wg * 2048);
    fence_async();
    bar_arrive(6, 288);
    ASTAMP(4);
    const int ks = p3_ks(wg), mt = p3_mt(wg);
    uint32_t v[16];
    auto fetch = [&](int seg) { ldg8x64<1024>(v, g_part + (((seg & 7) * 9 + mt) * 4 + (ks & 3)) * 1024 + (tid & 127)); };
    auto finish = [&](int seg) {
      const uint32_t tagv = (~seg >> 3) & 1;
      int n = 0;
#pragma unroll 1
      while (!(YP & 512) && stale<8, 2>(v, tagv) && ++n < SPIN_LIMIT) {
        if (seg < NSEG - 2) __nanosleep(100);
        fetch(seg);
      }
      float own[4] = {bf_lo(v[0]), bf_hi(v[0]), bf_lo(v[1]), bf_hi(v[1])};
#pragma unroll
      for (int j = 1; j < 8; j++) { own[0] += bf_lo(v[2 * j]); own[1] += bf_hi(v[2 * j]); own[2] += bf_lo(v[2 * j + 1]); own[3] += bf_hi(v[2 * j + 1]); }
      uint32_t p0 = pack_bf16(own[0], own[1]), p1 = pack_bf16(own[2], own[3]);
      asm volatile("movmatrix.sync.aligned.m8n8.trans.b16 %0, %0;" : "+r"(p0));
      asm volatile("movmatrix.sync.aligned.m8n8.trans.b16 %0, %0;" : "+r"(p1));
      const uint32_t r2 = __shfl_xor_sync(0xffffffffu, lane & 2 ? p0 : p1, 2);
      if (lane & 2) p0 = r2; else p1 = r2;
      const uint32_t r1 = __shfl_xor_sync(0xffffffffu, lane & 1 ? p0 : p1, 1);
      if (lane & 1) p0 = r1; else p1 = r1;
      if (!(YP & 256) || p0 == 0x12345678)
        *((uint2*)(out + (size_t)(seg * 32 + (ks & 3) * 8 + (lane >> 2)) * DM + mt * 64 + w * 16) + (lane & 3)) = make_uint2(p0, p1);
      SSTAMP(seg, 7);
    };
    float acc[16];
#pragma unroll
    for (int i = 0; i < 16; i++) acc[i] = 0.f;
    int pend = -1, sl = wide ? 0 : wg, ph = 0;
    if (PING && wg) bar_arrive(1, 256);
    CDECL;
    auto run = [&](auto extra) {
#pragma unroll 1
    for (int seg = 0; seg <= ((XP & 2048) ? -1 : NSEG); seg++) {
      CSTAMP(0);
      const bool fin = pend >= 0 && (seg - pend >= 2 || seg == NSEG);
      if (seg < NSEG) mbar_wait(full3 + 8 * sl, ph);
      if (fin) fetch(pend);
      CSTAMP(1);
      if (seg < NSEG) {
      if (wg) SSTAMP(seg, 5);
      if (seg < PING) bar_sync(1 + wg, 256);
      CSTAMP(7);
      const uint64_t db = make_desc(sb + sl * XT, 16, 1024, 1);
      WG_FENCE();
#pragma unroll
      for (int k = 0; k < ((XP & 1024) ? 1 : 36); k++) wgmma_n32_rs(acc, wa[k][0], wa[k][1], wa[k][2], wa[k][3], db + (k >> 2) * 256 + (k & 3) * 2, k);
      if (decltype(extra)::value) wgmma_n32_rs(acc, wa[36][0], wa[36][1], wa[36][2], wa[36][3], make_desc(sb + A_XT + sl * 1024, 16, 256, 3), 1);
      WG_COMMIT();
      if (seg < PING) bar_arrive(2 - wg, 256);
      CSTAMP(2);
      CSTAMP(3);
      WG_WAIT(0);
      CSTAMP(4);
      if (wg) SSTAMP(seg, 6);
      if (lane == 0) mbar_arrive(empty3 + 8 * sl);
      sl += wide ? 1 : 2;
      if (sl >= (wide ? 3 : 4)) { sl -= wide ? 3 : 4; ph ^= 1; }
      uint2* dst = g_part + (((seg & 7) * 9 + mt) * 32 + ks) * 128 + (tid & 127);
      uint32_t q[8];
#pragma unroll
      for (int j = 0; j < 8; j++) q[j] = j & 1 ? pack_bf16(acc[2 * j], acc[2 * j + 1]) : (pack_bf16(acc[2 * j], acc[2 * j + 1]) & ~1u) | ((~seg >> 3) & 1);
      if (QM & 32) tick_wait(pace, seg + (QM >> 4 & 1) + 2);
      if (!(YP & 1025) || q[0] == 0x12345678)
      asm volatile("st.relaxed.gpu.global.v2.b32 [%0], {%1,%2};\nst.relaxed.gpu.global.v2.b32 [%0 + 8192], {%3,%4};\n"
                   "st.relaxed.gpu.global.v2.b32 [%0 + 16384], {%5,%6};\nst.relaxed.gpu.global.v2.b32 [%0 + 24576], {%7,%8};"
                   :: "l"(dst), "r"(q[0]), "r"(q[1]), "r"(q[2]), "r"(q[3]), "r"(q[4]), "r"(q[5]), "r"(q[6]), "r"(q[7]) : "memory");
      }
      CSTAMP(5);
      if (fin) { finish(pend); pend = -1; }
      CSTAMP(6);
      if ((seg & 1) == ks >> 2 && !(YP & 1)) pend = seg;
      if (wg && (seg & 7) == 6) ASTAMP(5 + (seg >> 3));
    }
    };
    if (ks >= 4) run(BoolC<true>()); else run(BoolC<false>());
    if (PING && !wg) bar_sync(1, 256);
    CDUMP;
    ASTAMP(13);
  }
}

typedef CUresult (*EncodeFn)(CUtensorMap*, CUtensorMapDataType, cuuint32_t, void*, const cuuint64_t*, const cuuint64_t*,
                             const cuuint32_t*, const cuuint32_t*, CUtensorMapInterleave, CUtensorMapSwizzle,
                             CUtensorMapL2promotion, CUtensorMapFloatOOBfill);
static void make_map(EncodeFn enc, CUtensorMap* m, const void* p, int rows, int cols, int box_rows) {
  cuuint64_t dims[2] = {(cuuint64_t)cols, (cuuint64_t)rows};
  cuuint64_t strides[1] = {(cuuint64_t)cols * 2};
  cuuint32_t box[2] = {64, (cuuint32_t)box_rows};
  cuuint32_t es[2] = {1, 1};
  enc(m, CU_TENSOR_MAP_DATA_TYPE_BFLOAT16, 2, (void*)p, dims, strides, box, es, CU_TENSOR_MAP_INTERLEAVE_NONE,
      CU_TENSOR_MAP_SWIZZLE_128B, CU_TENSOR_MAP_L2_PROMOTION_L2_128B, CU_TENSOR_MAP_FLOAT_OOB_FILL_NONE);
}

constexpr int g_poll = POLL_NS;
extern "C" void kernel_launch(void* const* d_in, const int* in_sizes, int n_in, void* d_out, int out_size) {
  const bf16* x = (const bf16*)d_in[0];
  const bf16* wqkvA = (const bf16*)d_in[1];
  const bf16* woA = (const bf16*)d_in[2];
  const bf16* mem0 = (const bf16*)d_in[4];
  const bf16* Wq = (const bf16*)d_in[5];
  const bf16* Wk = (const bf16*)d_in[6];
  const bf16* Wv = (const bf16*)d_in[7];
  const bf16* Wo = (const bf16*)d_in[8];
  const bf16* gate_w = (const bf16*)d_in[10];
  static EncodeFn enc = nullptr;
  static void *pO = nullptr, *pR = nullptr, *pF = nullptr;
  if (!enc) {
    cudaDriverEntryPointQueryResult qr;
    cudaGetDriverEntryPoint("cuTensorMapEncodeTiled", (void**)&enc, cudaEnableDefault, &qr);
    cudaGetSymbolAddress(&pO, g_Ocat);
    cudaGetSymbolAddress(&pR, g_red_raw);
    cudaGetSymbolAddress(&pF, g_cflag);
    cudaFuncSetAttribute(rec_kernel, cudaFuncAttributeMaxDynamicSharedMemorySize, SM_TOTAL);
    cudaFuncSetAttribute(aux_kernel, cudaFuncAttributeMaxDynamicSharedMemorySize, A_TOTAL);
  }
  RMaps rm;
  rm.poll = g_poll;
  rm.oflag = (const unsigned char*)pF;
  rm.red = (unsigned char*)(((uintptr_t)pR + 262143) & ~(uintptr_t)262143);
  {
    cuuint64_t dims[3] = {64, S_LEN, 9}, strides[2] = {DM * 2, 128};
    cuuint32_t box[3] = {64, 32, 9}, es[3] = {1, 1, 1};
    enc(&rm.x, CU_TENSOR_MAP_DATA_TYPE_BFLOAT16, 3, (void*)x, dims, strides, box, es, CU_TENSOR_MAP_INTERLEAVE_NONE,
        CU_TENSOR_MAP_SWIZZLE_128B, CU_TENSOR_MAP_L2_PROMOTION_L2_128B, CU_TENSOR_MAP_FLOAT_OOB_FILL_NONE);
  }
  make_map(enc, &rm.wq, Wq, DM, 4096, 192);
  make_map(enc, &rm.wk, Wk, DM, 4096, 192);
  make_map(enc, &rm.wv, Wv, DM, 4096, 192);
  make_map(enc, &rm.wo, Wo, 4096, DM, 128);
  AMaps am;
  am.red = rm.red; am.poll = rm.poll;
  {
    cuuint64_t dims[3] = {DM, S_LEN / 2, 2}, strides[2] = {DM * 4, DM * 2};
    cuuint32_t box[3] = {32, 64, 2}, es[3] = {1, 1, 1};
    enc(&am.x, CU_TENSOR_MAP_DATA_TYPE_BFLOAT16, 3, (void*)x, dims, strides, box, es, CU_TENSOR_MAP_INTERLEAVE_NONE,
        CU_TENSOR_MAP_SWIZZLE_64B, CU_TENSOR_MAP_L2_PROMOTION_L2_128B, CU_TENSOR_MAP_FLOAT_OOB_FILL_NONE);
    cuuint64_t wdims[3] = {DM, DM, 3}, wstrides[2] = {DM * 6, DM * 2};
    cuuint32_t wbox[3] = {64, 32, 3}, wbox8[3] = {8, 32, 3};
    enc(&am.wa, CU_TENSOR_MAP_DATA_TYPE_BFLOAT16, 3, (void*)wqkvA, wdims, wstrides, wbox, es, CU_TENSOR_MAP_INTERLEAVE_NONE,
        CU_TENSOR_MAP_SWIZZLE_128B, CU_TENSOR_MAP_L2_PROMOTION_L2_128B, CU_TENSOR_MAP_FLOAT_OOB_FILL_NONE);
    enc(&am.wa8, CU_TENSOR_MAP_DATA_TYPE_BFLOAT16, 3, (void*)wqkvA, wdims, wstrides, wbox8, es, CU_TENSOR_MAP_INTERLEAVE_NONE,
        CU_TENSOR_MAP_SWIZZLE_NONE, CU_TENSOR_MAP_L2_PROMOTION_NONE, CU_TENSOR_MAP_FLOAT_OOB_FILL_NONE);
  }
  {
    cuuint64_t dims[3] = {64, S_LEN, KCAT / 64}, strides[2] = {KCAT * 2, 128};
    cuuint32_t box[3] = {64, 32, 9}, es[3] = {1, 1, 1};
    make_map(enc, &am.o, pO, S_LEN, KCAT, 32);
    enc(&am.o3, CU_TENSOR_MAP_DATA_TYPE_BFLOAT16, 3, pO, dims, strides, box, es, CU_TENSOR_MAP_INTERLEAVE_NONE,
        CU_TENSOR_MAP_SWIZZLE_128B, CU_TENSOR_MAP_L2_PROMOTION_L2_128B, CU_TENSOR_MAP_FLOAT_OOB_FILL_NONE);
  }
  make_map(enc, &am.wob, Wo, 4096, DM, 64);
  make_map(enc, &am.woa, woA, DM, DM, 64);
  make_map(enc, &am.woa16, woA, DM, DM, 16);
  {
    cuuint64_t dims[2] = {KCAT, S_LEN}, strides[1] = {KCAT * 2};
    cuuint32_t box[2] = {16, 32}, es[2] = {1, 1};
    enc(&am.o16, CU_TENSOR_MAP_DATA_TYPE_BFLOAT16, 2, pO, dims, strides, box, es, CU_TENSOR_MAP_INTERLEAVE_NONE,
        CU_TENSOR_MAP_SWIZZLE_32B, CU_TENSOR_MAP_L2_PROMOTION_NONE, CU_TENSOR_MAP_FLOAT_OOB_FILL_NONE);
  }

  rec_kernel<<<96, 384, SM_TOTAL, cudaStreamPerThread>>>(rm, x, mem0);
  cudaLaunchConfig_t cfg = {};
  cfg.gridDim = dim3(NAUX); cfg.blockDim = dim3(512); cfg.dynamicSmemBytes = A_TOTAL; cfg.stream = cudaStreamPerThread;
  cudaLaunchAttribute at[1];
  at[0].id = cudaLaunchAttributeProgrammaticStreamSerialization; at[0].val.programmaticStreamSerializationAllowed = 1;
  cfg.attrs = at; cfg.numAttrs = 1;
  if (XP & 16) cfg.numAttrs = 0;
  if (!(XP & 64)) cudaLaunchKernelEx(&cfg, aux_kernel, am, x, gate_w, (bf16*)d_out);
}
```

```cpp
#include <cuda_runtime.h>
#include <cuda_bf16.h>
#include <cuda_fp16.h>
#include <cuda.h>
#include <stdint.h>

typedef __nv_bfloat16 bf16;

constexpr int S_LEN = 2048, DM = 576, NH = 32, DH = 128, NSEG = 64, KCAT = 4096 + 576;
#define RED_LINE(i) (((i) >> 2) * 4096 + ((i) & 1) * 256 + ((i) & 2) * 512)
#define RED_SLOT(s) (((s) & 1) * 128 + ((s) & 2) * 256)

#define POLL_NS 896
#define QM 60
constexpr int NUP = 4;
#define N0 18
#define N7 (N0 < 18 ? 384 : 256)
#define N5 224
#define KP(i) (((i) >> 1) + 4 * ((i) & 1))
#define SPIN_LIMIT (1 << 14)
#define JN 7
#define FS 0
#define XP 0
#define YP 0

__device__ __align__(1024) bf16 g_Ocat[S_LEN * KCAT];
__device__ __align__(1024) unsigned char g_red_raw[2 * 262144];
constexpr int HINT_OFF = 2048;
__device__ __align__(16) float g_gate[S_LEN];
__device__ __align__(128) uint4 g_stats[96 * 2];
__device__ unsigned g_epoch;
__device__ unsigned g_epoch2;
__device__ __align__(128) unsigned g_oflag[NH * 32];
__device__ unsigned g_abar[3 * 32];
__device__ __align__(128) unsigned g_cflag[96 * 32];
__device__ uint2 g_sflag[96 * 4];
__device__ __align__(1024) unsigned char g_seg[NSEG * 96 * 8192];
__device__ __align__(1024) unsigned char g_km[NSEG * NH * 4096];
__device__ __align__(1024) uint2 g_part[8 * 9 * 4 * 8 * 128];
__device__ int g_err;
#define SSTAMP(seg, idx)
#define TSTAMP(idx)
#define QSTAMP(idx)
#define PROF(idx)
#define PROFP(idx)
#define STAMP(idx)
#define ASTAMP(idx)
#define WSTAMP(idx)

#define CSTAMP(idx)
#define CDECL
#define CDUMP
#define DI __device__ __forceinline__
DI uint32_t smem_u32(const void* p) { return (uint32_t)__cvta_generic_to_shared(p); }
DI uint32_t clock32() { uint32_t c; asm volatile("mov.u32 %0, %%clock;" : "=r"(c) :: "memory"); return c; }
DI uint32_t gtime() { uint32_t c; asm volatile("mov.u32 %0, %%globaltimer_lo;" : "=r"(c) :: "memory"); return c; }
DI uint32_t ldg_relaxed32(const void* p) { uint32_t v; asm volatile("ld.relaxed.gpu.global.b32 %0, [%1];" : "=r"(v) : "l"(p) : "memory"); return v; }
DI uint32_t ldg_acquire32(const void* p) { uint32_t v; asm volatile("ld.acquire.gpu.global.b32 %0, [%1];" : "=r"(v) : "l"(p) : "memory"); return v; }
DI void stg_relaxed32(void* p, uint32_t v) { asm volatile("st.relaxed.gpu.global.b32 [%0], %1;" :: "l"(p), "r"(v) : "memory"); }
DI uint32_t mapa(uint32_t a, uint32_t r) { uint32_t o; asm("mapa.shared::cluster.u32 %0, %1, %2;" : "=r"(o) : "r"(a), "r"(r)); return o; }
DI void cluster_arrive() { asm volatile("barrier.cluster.arrive.relaxed.aligned;" ::: "memory"); }
DI void cluster_wait() { asm volatile("barrier.cluster.wait.aligned;" ::: "memory"); }
DI void cluster_sync() { asm volatile("barrier.cluster.arrive.release.aligned;\nbarrier.cluster.wait.acquire.aligned;" ::: "memory"); }
DI void mbar_init(uint32_t b, uint32_t c) { asm volatile("mbarrier.init.shared::cta.b64 [%0], %1;" :: "r"(b), "r"(c) : "memory"); }
DI void mbar_expect(uint32_t b, uint32_t tx) { asm volatile("mbarrier.arrive.expect_tx.shared::cta.b64 _, [%0], %1;" :: "r"(b), "r"(tx) : "memory"); }
DI void mbar_arrive(uint32_t b) { asm volatile("mbarrier.arrive.shared::cta.b64 _, [%0];" :: "r"(b) : "memory"); }
DI void mbar_wait(uint32_t b, uint32_t par) {
  asm volatile("{\n.reg .pred p;\n.reg .u32 n, q;\nmov.u32 n, 0;\n"
               "WL: add.u32 n, n, 1;\nshr.u32 q, n, 12;\nxor.b32 q, q, %1;\n"
               "mbarrier.try_wait.parity.shared::cta.b64 p, [%0], q;\n@!p bra.uni WL;\n}"
               :: "r"(b), "r"(par) : "memory");
}
DI void wait_until(uint32_t t) {
  const uint32_t now = gtime();
  t = min(t, now + 8192);
  asm volatile("{\n.reg .pred p;\n.reg .u32 c;\nTL: mov.u32 c, %%globaltimer_lo;\nsetp.lt.u32 p, c, %0;\n@p bra.uni TL;\n}" :: "r"(t) : "memory");
}
#define PIN(v) v = __shfl_xor_sync(0xffffffffu, v, 0)
#define SCHED_FENCE(k) asm volatile("{\n.reg .pred p;\nsetp.eq.u32 p, %0, %1;\n@p exit;\n}" :: "r"(fence_reg), "r"(k) : "memory")
DI void bar_sync(int id, int n) { asm volatile("bar.sync %0, %1;" :: "r"(id), "r"(n) : "memory"); }
DI void bar_arrive(int id, int n) { asm volatile("bar.arrive %0, %1;" :: "r"(id), "r"(n) : "memory"); }
DI void fence_async() { asm volatile("fence.proxy.async.shared::cta;" ::: "memory"); }
DI void st_async4(uint32_t a, uint32_t x, uint32_t y, uint32_t z, uint32_t w, uint32_t mb) {
  asm volatile("st.async.weak.shared::cluster.mbarrier::complete_tx::bytes.v4.b32 [%0], {%1,%2,%3,%4}, [%5];"
               :: "r"(a), "r"(x), "r"(y), "r"(z), "r"(w), "r"(mb) : "memory");
}
DI void sts32(uint32_t a, uint32_t x) { asm volatile("st.shared.b32 [%0], %1;" :: "r"(a), "r"(x) : "memory"); }
DI void sts64(uint32_t a, uint32_t x, uint32_t y) { asm volatile("st.shared.v2.b32 [%0], {%1,%2};" :: "r"(a), "r"(x), "r"(y) : "memory"); }
DI void sts128(uint32_t a, uint32_t x, uint32_t y, uint32_t z, uint32_t w) {
  asm volatile("st.shared.v4.b32 [%0], {%1,%2,%3,%4};" :: "r"(a), "r"(x), "r"(y), "r"(z), "r"(w) : "memory");
}
DI uint32_t lds32(uint32_t a) { uint32_t x; asm volatile("ld.shared.b32 %0, [%1];" : "=r"(x) : "r"(a) : "memory"); return x; }
DI uint32_t lds32v(uint32_t a) { uint32_t x; asm volatile("ld.volatile.shared.b32 %0, [%1];" : "=r"(x) : "r"(a) : "memory"); return x; }
DI void lds64(uint32_t a, uint32_t& x, uint32_t& y) { asm volatile("ld.shared.v2.b32 {%0,%1}, [%2];" : "=r"(x), "=r"(y) : "r"(a) : "memory"); }
DI void lds128(uint32_t a, uint32_t* r) {
  asm volatile("ld.shared.v4.b32 {%0,%1,%2,%3}, [%4];" : "=r"(r[0]), "=r"(r[1]), "=r"(r[2]), "=r"(r[3]) : "r"(a) : "memory");
}
DI void lds128f(uint32_t a, float* r) {
  asm volatile("ld.shared.v4.f32 {%0,%1,%2,%3}, [%4];" : "=f"(r[0]), "=f"(r[1]), "=f"(r[2]), "=f"(r[3]) : "r"(a) : "memory");
}
DI void ldsm4t(uint32_t* r, uint32_t a) {
  asm volatile("ldmatrix.sync.aligned.m8n8.x4.trans.shared.b16 {%0,%1,%2,%3}, [%4];"
               : "=r"(r[0]), "=r"(r[1]), "=r"(r[2]), "=r"(r[3]) : "r"(a) : "memory");
}
DI void ldsm4t_in(uint32_t* r, uint32_t a, uint32_t t) {
  asm volatile("{\n.reg .pred p;\nsetp.ne.u32 p, %5, 0;\n@p ldmatrix.sync.aligned.m8n8.x4.trans.shared.b16 {%0,%1,%2,%3}, [%4];\n}"
               : "+r"(r[0]), "+r"(r[1]), "+r"(r[2]), "+r"(r[3]) : "r"(a), "r"(t) : "memory");
}
DI void lds128_in(uint32_t* r, uint32_t a, uint32_t t) {
  asm volatile("{\n.reg .pred p;\nsetp.ne.u32 p, %5, 0;\n@p ld.shared.v4.b32 {%0,%1,%2,%3}, [%4];\n}"
               : "+r"(r[0]), "+r"(r[1]), "+r"(r[2]), "+r"(r[3]) : "r"(a), "r"(t) : "memory");
}
DI void ldsm2t_in(uint32_t* r, uint32_t a, uint32_t t) {
  asm volatile("{\n.reg .pred p;\nsetp.ne.u32 p, %3, 0;\n@p ldmatrix.sync.aligned.m8n8.x2.trans.shared.b16 {%0,%1}, [%2];\n}" : "+r"(r[0]), "+r"(r[1]) : "r"(a), "r"(t) : "memory");
}
DI void reserve2(uint32_t* r) { asm volatile("{\n.reg .u64 t;\nmov.u64 t, %%clock64;\nmov.b64 {%0, %1}, t;\n}" : "=r"(r[0]), "=r"(r[1])); }
DI void scale_sum(float& x, float& y, float s, uint32_t t) {
  asm volatile("{\n.reg .pred p;\nsetp.ne.u32 p, %2, 0;\n@p mul.f32 %0, %0, %1;\n}" : "+f"(y) : "f"(s), "r"(t));
  asm volatile("{\n.reg .pred p;\nsetp.ne.u32 p, %3, 1;\n@p fma.rn.f32 %0, %0, %1, %2;\n}" : "+f"(x) : "f"(s), "f"(y), "r"(t));
}
DI void ldsm4(uint32_t* r, uint32_t a) {
  asm volatile("ldmatrix.sync.aligned.m8n8.x4.shared.b16 {%0,%1,%2,%3}, [%4];"
               : "=r"(r[0]), "=r"(r[1]), "=r"(r[2]), "=r"(r[3]) : "r"(a) : "memory");
}
DI void st_async1(uint32_t a, uint32_t x, uint32_t mb) {
  asm volatile("st.async.weak.shared::cluster.mbarrier::complete_tx::bytes.b32 [%0], %1, [%2];" :: "r"(a), "r"(x), "r"(mb) : "memory");
}
DI void stsm4(uint32_t a, uint32_t x, uint32_t y, uint32_t z, uint32_t w) {
  asm volatile("stmatrix.sync.aligned.m8n8.x4.shared.b16 [%0], {%1,%2,%3,%4};" :: "r"(a), "r"(x), "r"(y), "r"(z), "r"(w) : "memory");
}
DI void stsm4t(uint32_t a, uint32_t x, uint32_t y, uint32_t z, uint32_t w) {
  asm volatile("stmatrix.sync.aligned.m8n8.x4.trans.shared.b16 [%0], {%1,%2,%3,%4};" :: "r"(a), "r"(x), "r"(y), "r"(z), "r"(w) : "memory");
}
DI uint32_t pack_bf16(float lo, float hi) { uint32_t r; asm("cvt.rn.bf16x2.f32 %0, %1, %2;" : "=r"(r) : "f"(hi), "f"(lo)); return r; }
DI uint32_t pack_f16(float lo, float hi) { uint32_t r; asm("cvt.rn.f16x2.f32 %0, %1, %2;" : "=r"(r) : "f"(hi), "f"(lo)); return r; }
DI float ex2(float x) { float y; asm("ex2.approx.ftz.f32 %0, %1;" : "=f"(y) : "f"(x)); return y; }
DI float rcp(float x) { float y; asm("rcp.approx.ftz.f32 %0, %1;" : "=f"(y) : "f"(x)); return y; }
DI float bf_lo(uint32_t x) { return __uint_as_float(x << 16); }
DI float bf_hi(uint32_t x) { return __uint_as_float(x & 0xffff0000u); }
DI void mma16816(float* d, const uint32_t* a, uint32_t b0, uint32_t b1) {
  asm volatile("mma.sync.aligned.m16n8k16.row.col.f32.bf16.bf16.f32 {%0,%1,%2,%3}, {%4,%5,%6,%7}, {%8,%9}, {%0,%1,%2,%3};"
               : "+f"(d[0]), "+f"(d[1]), "+f"(d[2]), "+f"(d[3]) : "r"(a[0]), "r"(a[1]), "r"(a[2]), "r"(a[3]), "r"(b0), "r"(b1));
}
DI void mma16816z(float* d, const uint32_t* a, uint32_t b0, uint32_t b1) {
  asm volatile("mma.sync.aligned.m16n8k16.row.col.f32.bf16.bf16.f32 {%0,%1,%2,%3}, {%4,%5,%6,%7}, {%8,%9}, {%10,%10,%10,%10};"
               : "=f"(d[0]), "=f"(d[1]), "=f"(d[2]), "=f"(d[3]) : "r"(a[0]), "r"(a[1]), "r"(a[2]), "r"(a[3]), "r"(b0), "r"(b1), "f"(0.f));
}
DI void mma1688(float* d, uint32_t a0, uint32_t a1, uint32_t b0) {
  asm volatile("mma.sync.aligned.m16n8k8.row.col.f32.bf16.bf16.f32 {%0,%1,%2,%3}, {%4,%5}, {%6}, {%0,%1,%2,%3};"
               : "+f"(d[0]), "+f"(d[1]), "+f"(d[2]), "+f"(d[3]) : "r"(a0), "r"(a1), "r"(b0));
}
DI uint32_t add_bf16(uint32_t a, uint32_t b) { uint32_t r; asm("add.rn.bf16x2 %0, %1, %2;" : "=r"(r) : "r"(a), "r"(b)); return r; }
DI uint32_t mul_bf16(uint32_t a, uint32_t b) { uint32_t r; asm("mul.rn.bf16x2 %0, %1, %2;" : "=r"(r) : "r"(a), "r"(b)); return r; }
DI uint64_t make_desc(uint32_t addr, uint32_t lbo, uint32_t sbo, uint32_t swz) {
  return (uint64_t)((addr & 0x3FFFF) >> 4) | ((uint64_t)(lbo >> 4) << 16) | ((uint64_t)(sbo >> 4) << 32) | ((uint64_t)swz << 62);
}
#define WG_FENCE() asm volatile("wgmma.fence.sync.aligned;" ::: "memory")
#define WG_COMMIT() asm volatile("wgmma.commit_group.sync.aligned;" ::: "memory")
#define WG_WAIT(n) asm volatile("wgmma.wait_group.sync.aligned %0;" :: "n"(n) : "memory")
#define ACC8(d, o) "+f"(d[o]), "+f"(d[o + 1]), "+f"(d[o + 2]), "+f"(d[o + 3]), "+f"(d[o + 4]), "+f"(d[o + 5]), "+f"(d[o + 6]), "+f"(d[o + 7])
DI void wgmma_n32_rs(float* d, uint32_t a0, uint32_t a1, uint32_t a2, uint32_t a3, uint64_t db, int acc) {
  asm volatile("{\n.reg .pred p;\nsetp.ne.b32 p, %21, 0;\n"
               "wgmma.mma_async.sync.aligned.m64n32k16.f32.bf16.bf16 {%0,%1,%2,%3,%4,%5,%6,%7,%8,%9,%10,%11,%12,%13,%14,%15}, "
               "{%16,%17,%18,%19}, %20, p, 1, 1, 0;\n}\n"
               : ACC8(d, 0), ACC8(d, 8) : "r"(a0), "r"(a1), "r"(a2), "r"(a3), "l"(db), "r"(acc));
}
template <int TA>
DI void wgmma_n32_ss(float* d, uint64_t da, uint64_t db, int acc) {
  asm volatile("{\n.reg .pred p;\nsetp.ne.b32 p, %18, 0;\n"
               "wgmma.mma_async.sync.aligned.m64n32k16.f32.bf16.bf16 {%0,%1,%2,%3,%4,%5,%6,%7,%8,%9,%10,%11,%12,%13,%14,%15}, "
               "%16, %17, p, 1, 1, %19, 1;\n}\n"
               : ACC8(d, 0), ACC8(d, 8) : "l"(da), "l"(db), "r"(acc), "n"(TA));
}
DI void tma_load(uint32_t dst, const CUtensorMap* m, int c0, int c1, uint32_t mb) {
  asm volatile("cp.async.bulk.tensor.2d.shared::cluster.global.mbarrier::complete_tx::bytes [%0], [%1, {%3, %4}], [%2];"
               :: "r"(dst), "l"(m), "r"(mb), "r"(c0), "r"(c1) : "memory");
}
DI void tma_load3(uint32_t dst, const CUtensorMap* m, int row, uint32_t mb) {
  asm volatile("cp.async.bulk.tensor.3d.shared::cluster.global.mbarrier::complete_tx::bytes [%0], [%1, {%3, %4, %3}], [%2];"
               :: "r"(dst), "l"(m), "r"(mb), "r"(0), "r"(row) : "memory");
}
DI bool elect_one() {
  uint32_t p;
  asm volatile("{\n.reg .pred p;\nelect.sync _|p, 0xffffffff;\nselp.u32 %0, 1, 0, p;\n}" : "=r"(p));
  return p;
}
DI void bulk_s2s(uint32_t dst, uint32_t src, uint32_t bytes, uint32_t mb) {
  asm volatile("cp.async.bulk.shared::cluster.shared::cta.mbarrier::complete_tx::bytes [%0], [%1], %2, [%3];"
               :: "r"(dst), "r"(src), "r"(bytes), "r"(mb) : "memory");
}
DI void bulk_load(uint32_t dst, const void* src, uint32_t bytes, uint32_t mb) {
  asm volatile("cp.async.bulk.shared::cluster.global.mbarrier::complete_tx::bytes [%0], [%1], %2, [%3];" :: "r"(dst), "l"(src), "r"(bytes), "r"(mb) : "memory");
}
#define EVICT_FIRST ".reg .b64 pol;\ncreatepolicy.fractional.L2::evict_first.b64 pol, 1.0;\n"
DI void tma_load_ef(uint32_t dst, const CUtensorMap* m, int c0, int c1, uint32_t mb) {
  asm volatile("{\n" EVICT_FIRST "cp.async.bulk.tensor.2d.shared::cluster.global.mbarrier::complete_tx::bytes.L2::cache_hint [%0], [%1, {%3, %4}], [%2], pol;\n}"
               :: "r"(dst), "l"(m), "r"(mb), "r"(c0), "r"(c1) : "memory");
}
DI void tma_prefetch(const CUtensorMap* m, int c0, int c1) {
  asm volatile("cp.async.bulk.prefetch.tensor.2d.L2.global.tile [%0, {%1, %2}];" :: "l"(m), "r"(c0), "r"(c1) : "memory");
}
DI void tma_store(const CUtensorMap* m, uint32_t src, int c0, int c1) {
  asm volatile("cp.async.bulk.tensor.2d.global.shared::cta.bulk_group [%0, {%2, %3}], [%1];" :: "l"(m), "r"(src), "r"(c0), "r"(c1) : "memory");
}
DI uint4 ldg_relaxed(const void* p) {
  uint4 v;
  asm volatile("ld.relaxed.gpu.global.v4.b32 {%0,%1,%2,%3}, [%4];" : "=r"(v.x), "=r"(v.y), "=r"(v.z), "=r"(v.w) : "l"(p) : "memory");
  return v;
}
DI void stg_relaxed(void* p, uint32_t x, uint32_t y, uint32_t z, uint32_t w) {
  asm volatile("st.relaxed.gpu.global.v4.b32 [%0], {%1,%2,%3,%4};" :: "l"(p), "r"(x), "r"(y), "r"(z), "r"(w) : "memory");
}
DI void red_f16x8(void* p, uint32_t x, uint32_t y, uint32_t z, uint32_t w) {
  asm volatile("red.relaxed.gpu.global.add.noftz.v4.f16x2 [%0], {%1,%2,%3,%4};" :: "l"(p), "r"(x), "r"(y), "r"(z), "r"(w) : "memory");
}
DI void sq_acc(uint32_t& a, uint32_t x) { asm("fma.rn.bf16x2 %0, %1, %1, %0;" : "+r"(a) : "r"(x)); }
DI __half2 amax4(__half2 h, const uint32_t* v) {
  h = __hmax2_nan(__hmax2_nan(h, __habs2(*(const __half2*)&v[0])), __habs2(*(const __half2*)&v[1]));
  return __hmax2_nan(__hmax2_nan(h, __habs2(*(const __half2*)&v[2])), __habs2(*(const __half2*)&v[3]));
}
DI uint32_t wexp(__half2 h) { const uint32_t u = *(const uint32_t*)&h; return __reduce_max_sync(0xffffffffu, max((u >> 16) & 0x7fffu, u & 0x7fffu)) >> 7; }
DI float warp_sum(float v) {
#pragma unroll
  for (int o = 16; o; o >>= 1) v += __shfl_xor_sync(0xffffffffu, v, o);
  return v;
}

constexpr int SM_WO3 = 0;
constexpr int SM_X = 16384;
constexpr int XT = 36864;
constexpr int SM_EXP = 126976;
constexpr int SEGB = 10240;
constexpr int SM_BLK = SM_EXP + 8192;
constexpr int SM_VC = SM_BLK + 4 * SEGB;
constexpr int SM_PART = SM_VC + 16384;
constexpr int SM_QM = SM_PART + 4096;
constexpr int SM_E = SM_QM + 1024;
constexpr int SM_VM = SM_E + 1536;
constexpr int SM_OB = SM_VM + 2048;
constexpr int SM_FB = SM_OB + 2048;
constexpr int SM_STAGE = SM_X + XT;
constexpr int SM_M0 = SM_STAGE + 3 * 49152;
constexpr int SM_MISC = 210944;
constexpr int SM_WOST = 212992;
constexpr int SM_MEM = SM_WOST;
constexpr int SM_MAX = SM_MEM + 11264;
#define MEM_BLK(q) ((q) / 3 * 4096 + (q) % 3 * 1024)
constexpr int SM_TOTAL = 229376;
constexpr int MB_W = SM_MISC;
constexpr int MB_WO = SM_MISC + 24;
constexpr int MB_WO3 = SM_MISC + 32;
constexpr int MB_X = SM_MISC + 40;
constexpr int MB_S = SM_MISC + 64;
constexpr int MB_F = SM_MISC + 72;
constexpr int MB_VX = SM_MISC + 80;
constexpr int SC_FPAR = SM_MISC + 136;
constexpr int SC_DEAD = SM_MISC + 96;
constexpr int SC_UNSC = SM_MISC + 112;
constexpr int SC_OFL = SM_MISC + 1024;
constexpr int SC_EXPW = SM_MISC + 132;
constexpr int SC_ONES = SM_MISC + 144;
constexpr int SC_SS = SM_MISC + 160;
constexpr int SC_LAT = SM_MISC + 224;
constexpr int SC_TAG = SM_MISC + 232;
constexpr int SC_EPO = SM_MISC + 240;
constexpr int MB_XS = SM_MISC + 248;
constexpr int SC_XMAX = SM_MISC + 256;
constexpr int SC_PROF = 229376;

constexpr float SM_SCALE = 0.08838834764831845f;
constexpr float LOG2E = 1.4426950408889634f;
constexpr float E_LIM = 20.f;

template <bool B> struct BoolC { static constexpr bool value = B; };
template <int I> struct IntC { static constexpr int value = I; };
struct RMaps { CUtensorMap x, wq, wk, wv, wo; unsigned char* red; uint32_t poll; const unsigned char* oflag; };

DI uint32_t latest_hint(uint32_t h, uint32_t d, int s) {
  const uint32_t x = (((h | 0xc0c0c0c0u) - ((d >> 5) & 63) * 0x01010101u) & 0x3f3f3f3fu) | ((h ^ (((s >> 2) + 1) & 3) * 0x40404040u) & 0xc0c0c0c0u);
  const uint32_t y = __vmaxu2(x & 0x00ff00ffu, (x >> 8) & 0x00ff00ffu);
  return __reduce_max_sync(0xffffffffu, max(y & 0xffffu, y >> 16));
}
DI uint32_t near_half(uint32_t sb) {
  uint32_t a, b; lds64(sb + SC_LAT, a, b);
  return a > b;
}

template <int RT, int K0, int K1, bool D32 = false>
DI void xproj(float* acc, const uint32_t (&wa)[2][18][4], uint64_t xd) {
  if (XP & 1) return;
  WG_FENCE();
#pragma unroll
  for (int k = K0; k < ((XP & 128) ? K0 + 1 : K1); k++)
  {
    uint64_t d = xd + (uint64_t)(((k >> 1) * 4096 + (k & 1) * 32) >> 4);
    if (D32) asm("mov.b64 %0, {%1, %2};" : "=l"(d) : "r"((uint32_t)xd + (((k >> 1) * 4096 + (k & 1) * 32) >> 4)), "r"((uint32_t)(xd >> 32)));
    wgmma_n32_rs(acc, wa[RT][k][0], wa[RT][k][1], wa[RT][k][2], wa[RT][k][3], d, k != 0);
  }
  WG_COMMIT();
}

DI void load_w(uint32_t sb, const RMaps& tm, uint32_t rank, int c) {
  const int h = blockIdx.x / 3;
  mbar_expect(sb + MB_W + 8 * c, 49152);
  tma_load_ef(sb + SM_STAGE + c * 49152, rank < 2 ? &tm.wk : &tm.wv, h * DH + (rank == 1 ? 64 : 0), c * 192, sb + MB_W + 8 * c);
  tma_load_ef(sb + SM_STAGE + c * 49152 + 24576, rank < 2 ? &tm.wq : &tm.wv, h * DH + (rank == 0 ? 0 : 64), c * 192, sb + MB_W + 8 * c);
}
DI void seg_store(int seg, uint32_t slot, uint32_t sb) {
  asm volatile("cp.async.bulk.global.shared::cta.bulk_group [%0], [%1], 8192;"
               :: "l"(g_seg + ((size_t)slot * 96 + blockIdx.x) * 8192), "r"(sb + SM_BLK + (seg & 3) * SEGB) : "memory");
  asm volatile("cp.async.bulk.commit_group;" ::: "memory");
}
DI void seg_publish(int seg, uint32_t sb) {
  uint32_t v, own;
  lds64(sb + SC_EPO, v, own);
  asm volatile("cp.async.bulk.wait_group 0;" ::: "memory");
  asm volatile("st.relaxed.gpu.global.v2.b32 [%0], {%1,%2};" :: "l"(&g_sflag[blockIdx.x * 4]), "r"(v + seg), "r"(own) : "memory");
}

DI void proj_role(const uint32_t sb, const RMaps& tm, const bf16* __restrict__ x, const uint32_t rank, const int wg, const int w, const int lane) {
  const bool qk = rank < 2;
  uint32_t wa[2][18][4];
  float acc[16];
  const uint64_t xd0 = make_desc(sb + SM_X + wg * 64, 16, 1024, 1);
  {
    const int rr = (lane & 7) + ((lane >> 4) << 3);
    const uint32_t col = ((2 * w + ((lane >> 3) & 1)) ^ (lane & 7)) << 4;
    float ss = 0.f;
    bar_sync(3, 256);
    mbar_wait(sb + MB_X, 0);
    auto chunk = [&](auto cc) {
      constexpr int c = decltype(cc)::value;
      QSTAMP(2 + 2 * c);
      mbar_wait(sb + MB_W + 8 * c, 0);
      QSTAMP(3 + 2 * c);
#pragma unroll
      for (int rt = 1; rt >= 0; rt--)
#pragma unroll
        for (int k = 0; k < 6; k++)
          ldsm4t(wa[rt][c * 6 + k], sb + SM_STAGE + c * 49152 + (rt ^ wg) * 24576 + (64 * (k >> 1) + 32 * wg + 16 * (k & 1) + rr) * 128 + col);
      fence_async();
      if (c < 2) {
        bar_sync(3, 256);
        QSTAMP(17 + c);
        if (threadIdx.x == 0) {
          if (c == 0) tma_load(sb + SM_X + XT, &tm.wo, rank * 192, (blockIdx.x / 3) * DH, sb + MB_WO);
          else if (blockIdx.x < NSEG) bulk_load(sb + SM_X + 2 * XT, x + blockIdx.x * 32 * DM, XT, sb + MB_XS);
          else tma_load3(sb + SM_X + 2 * XT, &tm.x, 64, sb + MB_X + 16);
        }
        __syncwarp();
      } else {
        cluster_arrive();
      }
      xproj<1, 6 * c, 6 * c + 6>(acc, wa, xd0);
      if (!qk) {
        uint32_t q[4] = {0, 0, 0, 0};
#pragma unroll
        for (int rt = 0; rt < 2; rt++)
#pragma unroll
          for (int k = 0; k < 6; k++)
#pragma unroll
            for (int i = 0; i < 4; i++) sq_acc(q[i], wa[rt][c * 6 + k][i]);
#pragma unroll
        for (int i = 0; i < 4; i++) ss += bf_lo(q[i]) + bf_hi(q[i]);
      }
    };
    chunk(IntC<0>()); chunk(IntC<1>()); chunk(IntC<2>());
    ss = warp_sum(ss);
    if (lane == 0) sts32(sb + SC_SS + 4 * (wg * 4 + w), __float_as_uint(ss));
    bar_arrive(11, 384);
  }
  STAMP(1);
  QSTAMP(8);
  STAMP(2);

  uint32_t t16 = sb + (w * 32 + lane) * 16;
  uint32_t mem_a = sb + SM_MEM + wg * 512 + lane * 16;
  uint32_t fin_a = sb + (lane & 7) * 16 + SM_BLK + (qk ? (wg ^ 1) * 4096 + w * 256 + (lane & 8) * 16 + (lane & 16) * 64
                                              : wg * 4096 + w * 1024 + (lane & 8) * 64 + (lane & 16) * 8);
  PIN(t16); PIN(mem_a); PIN(fin_a);
  const uint32_t fence_reg = mem_a;
  const uint32_t fin2 = qk ? 2048 : 256;
  auto do_export = [&](auto retire, uint32_t always) {
    WG_WAIT(0);
    uint32_t p[2];
#pragma unroll
    for (int i = 0; i < 2; i++) {
      p[i] = pack_bf16(acc[8 * i], acc[8 * i + 1]);
      sts128(t16 + SM_EXP + wg * 4096 + i * 2048, p[i], pack_bf16(acc[8 * i + 2], acc[8 * i + 3]),
             pack_bf16(acc[8 * i + 4], acc[8 * i + 5]), pack_bf16(acc[8 * i + 6], acc[8 * i + 7]));
    }
    if (decltype(retire)::value)
      asm volatile("{\n.reg .pred p, q;\nsetp.ne.u32 p, %2, 0;\nsetp.ne.u32 q, %2, 1;\n@p ld.shared.b32 %0, [%3];\n@q ld.shared.b32 %1, [%3 + 4];\n"
                   "setp.ne.u32 p, %0, %1;\n@p exit;\n}" : "+r"(p[0]), "+r"(p[1]) : "r"(always), "r"(sb + SC_DEAD) : "memory");
  };
  uint32_t o[8];
  auto import = [&]() { lds128(t16 + SM_EXP + (wg ^ 1) * 4096, o); lds128(t16 + SM_EXP + (wg ^ 1) * 4096 + 2048, o + 4); };
  auto fin_pack = [&]() {
    WG_WAIT(0);
#pragma unroll
    for (int i = 0; i < 8; i++) o[i] = add_bf16(pack_bf16(acc[2 * i], acc[2 * i + 1]), o[i]);
  };
  auto fin_store = [&](int seg) {
    const uint32_t a = fin_a + (seg & 3) * SEGB;
    stsm4(a, o[0], o[1], o[2], o[3]);
    stsm4(a + fin2, o[4], o[5], o[6], o[7]);
    fence_async();
  };
  auto finish = [&](int seg) { fin_pack(); fin_store(seg); };
  auto send_v = [&](int seg, int dst) {
    if (seg < NSEG - 1 && !(XP & 2) && elect_one())
      bulk_s2s(mapa(sb + SM_VC + (seg & 1) * 8192, dst), sb + SM_BLK + (seg & 3) * SEGB, 8192, mapa(sb + MB_VX + (seg & 1) * 8, dst));
    __syncwarp();
  };
  auto wait_v = [&](int seg) {
    if (seg < NSEG - 1 && !(XP & 2)) {
      mbar_wait(sb + MB_VX + (seg & 1) * 8, (seg >> 1) & 1);
      if (elect_one()) mbar_expect(sb + MB_VX + (seg & 1) * 8, 8192);
      __syncwarp();
    }
  };
  auto export_seg = [&](int seg, uint32_t slot) { if (!(XP & (4 | 8192)) && elect_one()) seg_store(seg, slot, sb); __syncwarp(); };
  auto publish = [&](int seg) { if (!(XP & (4 | 16384)) && elect_one()) seg_publish(seg, sb); __syncwarp(); };
  do_export(BoolC<false>(), 0);
  QSTAMP(9);
  SCHED_FENCE(11);
  xproj<0, 0, 18>(acc, wa, xd0);
  bar_sync(3, 256);
  QSTAMP(10);
  cluster_wait();
  QSTAMP(11);
  mbar_wait(sb + MB_X + 8, 0);
  QSTAMP(12);
  import();
  finish(0);
  SCHED_FENCE(12);
  uint64_t dA = xd0 + (XT >> 4);
  xproj<1, 0, 18>(acc, wa, dA);
  bar_sync(3, 256);
  if (!qk && wg == 0 && w < 2) send_v(0, w);
  if (wg == 0 && w == 3) export_seg(0, 0);
  QSTAMP(13);
  if (qk && wg == 0 && w == 0) wait_v(0);
  QSTAMP(14);
  bar_arrive(13, 384);
  if (!qk) {
    do_export(BoolC<false>(), 0);
    SCHED_FENCE(15);
    xproj<0, 0, 18>(acc, wa, dA);
    if (threadIdx.x == 0 && !(XP & 8)) { mbar_expect(sb + MB_X, XT); tma_load3(sb + SM_X, &tm.x, 96, sb + MB_X); }
    bar_sync(3, 256);
    mbar_wait(sb + MB_X + 16, 0);
    import();
    finish(1);
    SCHED_FENCE(16);
    dA += XT >> 4;
    xproj<1, 0, 18>(acc, wa, dA);
  }
  QSTAMP(15);
  WG_WAIT(0);
  bar_sync(0, 384);
  if (wg == 0 && w == 3) publish(0);
  QSTAMP(16);
  const int ro = __shfl_sync(0xffffffffu, near_half(sb) ^ wg, 0);
  STAMP(5);
  const uint32_t always = __shfl_sync(0xffffffffu, lds32(sb + SC_DEAD + 12), 0);
  const int ah = qk ? 1 : 2;
  int b2 = qk ? 2 : 0;
  int s = 0;
  uint32_t hint_lo = (uint32_t)(uint64_t)tm.red + HINT_OFF + blockIdx.x + (lane & 1) * 4096 + (lane >> 1) * 16384;
  PIN(hint_lo);
  auto post_hint = [&]() {
    uint32_t t;
    asm volatile("{\n.reg .u64 g;\nmov.u64 g, %%globaltimer;\ncvt.u32.u64 %0, g;\n}" : "=r"(t) :: "memory");
    asm volatile("{\n.reg .pred p;\n.reg .b64 a;\n.reg .u32 t;\nsetp.lt.u32 p, %0, %1;\nmov.b64 a, {%2, %3};\n"
                 "bfe.u32 t, %5, 5, 6;\nor.b32 t, t, %4;\n@p st.relaxed.gpu.global.u8 [a], t;\n}"
                 :: "r"(t16), "r"(sb + 160), "r"(hint_lo + RED_SLOT(s)), "r"((uint32_t)((uint64_t)tm.red >> 32)), "r"(((s >> 2) + 1) << 6), "r"(t) : "memory");
  };
  auto memproj = [&](auto second, int id, uint32_t dep, float u0, float u1, float* r) {
    constexpr bool R1 = decltype(second)::value;
    uint32_t b[NUP][4], b0[4];
    if (R1) asm volatile("{\n.reg .pred p;\nsetp.eq.u32 p, %0, %1;\n@p exit;\n}" :: "r"(dep), "r"(id) : "memory");
    bar_sync(R1 ? 2 : 1, 256);
    PROF(0);
    ldsm4t(b0, mem_a);
#pragma unroll
    for (int q = 0; q < NUP; q++) {
      if (R1 && q == 2) {
        bar_sync(11, 256);
        SCHED_FENCE(id + 1);
      }
      ldsm4t(b[q], mem_a + MEM_BLK(q + 1));
    }
    mma16816z(&acc[0], wa[0][0], b0[0], b0[1]);
    mma16816z(&acc[4], wa[1][0], b0[0], b0[1]);
    mma16816z(&acc[8], wa[0][1], b0[2], b0[3]);
    mma16816z(&acc[12], wa[1][1], b0[2], b0[3]);
#pragma unroll
    for (int q = 1; q < 9; q++) {
      uint32_t* const c = b[(q - 1) % NUP];
      mma16816(&acc[0], wa[0][2 * q], c[0], c[1]);
      mma16816(&acc[4], wa[1][2 * q], c[0], c[1]);
      mma16816(&acc[8], wa[0][2 * q + 1], c[2], c[3]);
      mma16816(&acc[12], wa[1][2 * q + 1], c[2], c[3]);
      if (R1 && q + NUP == 9) bar_sync(3, 256);
      if (q + NUP < 9) ldsm4t_in(c, mem_a + MEM_BLK(q + NUP), always);
      else if (R1 && q + NUP < 11) lds128_in(c, t16 + SM_PART + (10 - q - NUP) * 2048, always);
      else if (!R1 && q == 8) { bar_arrive(11, 256); lds128_in(c, sb + SC_DEAD, always); u0 = u1 = __uint_as_float(c[3]); }
    }
#pragma unroll
    for (int i = 0; i < 8; i++) {
      const float u = i < 4 ? u0 : u1;
      r[i] = R1 ? fmaf(acc[8 + i], u, (acc[i] + __uint_as_float(b[(8 + i / 4) % NUP][i & 3])) * u) : fmaf(acc[i], u, acc[8 + i]);
    }
  };
  if (ro == 0) {
#pragma unroll 1
    while (true) {
      do_export(BoolC<true>(), always);
      PROFP(3);
      if (s == 8) STAMP(6);
      float r[8];
      memproj(BoolC<false>(), 30, 0, 0.f, 0.f, r);
      sts128(t16 + SM_PART, __float_as_uint(r[0]), __float_as_uint(r[1]), __float_as_uint(r[2]), __float_as_uint(r[3]));
      sts128(t16 + SM_PART + 2048, __float_as_uint(r[4]), __float_as_uint(r[5]), __float_as_uint(r[6]), __float_as_uint(r[7]));
      bar_arrive(3, 256);
      PROF(1);
      bar_sync(9, 256);
      post_hint();
      if (w == 3 && s) publish(s);
      if (s == NSEG - 1) break;
      if (w == 1) {
        uint32_t m[8];
        lds128(t16 + SM_MAX - 512, m); lds128(t16 + SM_MAX, m + 4);
        const int em = (wexp(amax4(amax4(*(const __half2*)&m[0], m), m + 4)) >> 3) + (int)(lds32(sb + SC_UNSC + (s & 1) * 8) >> 23) - 15;
        const int ex = max(s ? em : 0, (int)lds32(sb + SC_XMAX + 4 * s)) - 127 + (int)lds32(sb + SC_EXPW);
        sts32(sb + SC_UNSC + (~s & 1) * 8, (127 + min(max(ex, -120), 120)) << 23);
        __syncwarp();
        if (elect_one()) mbar_arrive(sb + MB_S);
      }
      SCHED_FENCE(9);
      bar_sync(5, qk ? N5 : 256);
      PROF(2);
      import();
      xproj<0, 0, N0>(acc, wa, dA);
      if (N0 < 18) { bar_sync(7, N7); xproj<0, N0, 18>(acc, wa, dA); }
      if (FS & 1) { fin_pack(); SCHED_FENCE(18); } else WG_WAIT(0);
      bar_sync(10, 256);
      SCHED_FENCE(17);
      dA += (int64_t)(b2 ? XT >> 4 : -(XT >> 3));
      if (!(FS & 1)) fin_pack();
      if (FS & 2) bar_arrive(14, 256);
      if (!(FS & 4)) { fin_store(s + ah); if (w != 3) bar_arrive(13, 384); }
      PROF(6);
      SCHED_FENCE(14);
      bar_sync(12, 256);
      PROF(7);
      xproj<1, 0, 18, true>(acc, wa, dA);
      if (!(FS & 2)) bar_arrive(14, 256);
      if (FS & 4) { fin_store(s + ah); if (w != 3) bar_arrive(13, 384); }
      b2 = b2 == 2 ? 0 : b2 + 1;
      s++;
      if (w == 3) {
        const uint32_t slot = s < lds32(sb + SC_EPO + 4) ? s & 7 : s;
        bar_sync(13, 384);
        export_seg(s, slot);
      }
      PROFP(8);
    }
    if (!qk) bar_arrive(5, 256);
  } else {
    uint32_t km[4];
    auto send_km = [&]() {
      if (XP & (4 | 4096)) return;
      uint32_t t, u;
      lds64(sb + SC_TAG, t, u);
      t |= km[0] & ~1u; u += s * (NH * 4096);
      if (qk)
        asm volatile("{\n.reg .u32 o;\n.reg .u64 a;\nshr.u32 o, %0, 1;\nadd.u32 o, o, %1;\nmad.wide.u32 a, o, 1, %2;\nst.relaxed.gpu.global.v2.b32 [a], {%3,%4};\n}"
                     :: "r"(t16), "r"(u), "l"(g_km), "r"(t), "r"(km[1]) : "memory");
      else
        asm volatile("{\n.reg .u32 o;\n.reg .u64 a;\nadd.u32 o, %0, %1;\nmad.wide.u32 a, o, 1, %2;\nst.relaxed.gpu.global.v4.b32 [a], {%3,%4,%5,%6};\n}"
                     :: "r"(t16), "r"(u), "l"(g_km), "r"(t), "r"(km[1]), "r"(km[2]), "r"(km[3]) : "memory");
    };
#pragma unroll 1
    while (true) {
      do_export(BoolC<true>(), always);
      if (!qk && w == 2) send_v(s + 1, 0);
      PROFP(3);
      if (s == 8) STAMP(6);
      const uint32_t tl = ((t16 >> 8) ^ wg) & 1, am = (t16 & ~256u) - w * 256;
      const float un = __uint_as_float(lds32(sb + SC_UNSC + (s & 1) * 8));
      float r[8];
      if (qk) {
        uint32_t a0 = am + (tl ? SM_QM : SM_BLK + 8192 + (s & 3) * SEGB);
        float u0 = wg ? un * (SM_SCALE * LOG2E) : un, u1 = wg ? un : un * (SM_SCALE * LOG2E);
        PIN(a0); PIN(u0); PIN(u1);
        memproj(BoolC<true>(), 32, a0, u0, u1, r);
        const uint32_t p0 = pack_bf16(r[0], r[1]), p1 = pack_bf16(r[2], r[3]), p2 = pack_bf16(r[4], r[5]), p3 = pack_bf16(r[6], r[7]);
        stsm4(a0, p0, p1, p2, p3);
        bar_arrive(4, 256);
        km[0] = wg ? p2 : p0; km[1] = wg ? p3 : p1;
      } else {
        const uint32_t d0 = s < NSEG - 1 ? 0 : 2, d1 = s < NSEG - 1 ? 1 : 2;
        uint32_t r0 = mapa(t16 + SM_VM, d0), r1 = mapa(t16 + SM_VM, d1);
        PIN(r0); PIN(r1);
        memproj(BoolC<true>(), 34, r0 | r1, un, un, r);
        const uint32_t p0 = pack_bf16(r[0], r[1]), p1 = pack_bf16(r[2], r[3]), p2 = pack_bf16(r[4], r[5]), p3 = pack_bf16(r[6], r[7]);
        const uint32_t v0 = wg ? p2 : p0, v1 = wg ? p3 : p1, v2 = wg ? p0 : p2, v3 = wg ? p1 : p3;
        st_async4(r0, v0, v1, v2, v3, mapa(sb + MB_S, d0));
        st_async4(r1, v0, v1, v2, v3, mapa(sb + MB_S, d1));
        bar_arrive(5, 256);
        sts128(t16 + SM_VM, v0, v1, v2, v3);
        __syncwarp();
        if (elect_one()) mbar_arrive(sb + MB_S);
        km[0] = v0; km[1] = v1; km[2] = v2; km[3] = v3;
      }
      PROF(1);
      auto rearm = [&]() { mbar_wait(sb + MB_S, s & 1); if (elect_one()) mbar_expect(sb + MB_S, qk ? 640 + 2048 : 1280); __syncwarp(); };
      if (s == NSEG - 1 && w != 1) {
      } else if (w == 1) {
        if ((t16 & 384) == 0) stg_relaxed(tm.red + (RED_SLOT(s + 2) + RED_LINE(blockIdx.x)) + (t16 & 112), 0, 0, 0, 0);
        uint32_t base, own;
        lds64(sb + SC_EPO, base, own);
        if ((int)(lds32v(sb + SC_OFL) - base) < s - 7) sts32(sb + SC_EPO + 4, min(own, s + 1));
        if (elect_one()) bulk_load(sb + SC_OFL, tm.oflag + blockIdx.x * 128, 16, sb + MB_XS);
      } else if (w == 0) {
        const int tn = s + ah + 1;
        if (tn + 1 < NSEG && !(XP & 8) && elect_one()) {
          const int b0 = b2 == 2 ? 0 : b2 + 1;
          mbar_expect(sb + MB_X + 8 * b0, XT);
          tma_load3(sb + SM_X + b0 * XT, &tm.x, (tn + 1) * 32, sb + MB_X + 8 * b0);
        }
        if (tn < NSEG && (!(XP & 8) || tn < 3)) mbar_wait(sb + MB_X + 8 * b2, (tn / 3) & 1);
      } else if (w == 2) {
        if (!qk) send_v(s + 1, 1);
      } else {
        rearm();
      }
      __syncwarp();
      send_km();
      if (s == NSEG - 1) break;
      import();
      PROF(4);
      SCHED_FENCE(10);
      bar_sync(7, N7);
      if (FS & 16) bar_arrive(12, 256);
      xproj<0, 0, 18>(acc, wa, dA);
      if (!(FS & 16)) bar_arrive(12, 256);
      dA += (int64_t)(b2 ? XT >> 4 : -(XT >> 3));
      fin_pack();
      if (!(FS & 8)) {
        fin_store(s + ah);
        if (qk && w == 0) wait_v(s + 1);
        bar_arrive(13, 384);
      }
      PROF(6);
      SCHED_FENCE(13);
      bar_sync(14, 256);
      PROF(7);
      xproj<1, 0, 18>(acc, wa, dA);
      if (FS & 8) {
        fin_store(s + ah);
        if (qk && w == 0) wait_v(s + 1);
        bar_arrive(13, 384);
      }
      b2 = b2 == 2 ? 0 : b2 + 1;
      s++;
      PROFP(8);
    }
  }
  bar_arrive(0, 384);
  STAMP(3);
  cluster_sync();
  STAMP(4);
}

DI void attn_role(const uint32_t sb, unsigned char* smem_raw, const RMaps& tm, const uint32_t RANK, const bf16* __restrict__ x, const bf16* __restrict__ mem0,
                  const int w, const int lane) {
  const int t2 = w * 32 + lane;
  uint32_t wo[8][4], w1[8][4];
  const uint32_t wo_lane = sb + ((lane & 7) + ((lane >> 4) << 3)) * 128 + (((w + 4 * ((lane >> 3) & 1)) ^ (lane & 7)) << 4);
  unsigned char* const g_red = tm.red;
  {
    const uint32_t tag = *(volatile unsigned*)&g_epoch + 1;
    QSTAMP(0);
    bar_sync(0, 160);
    QSTAMP(1);
    cluster_arrive();
    __half2 hx = __float2half2_rn(0.f);
    if (t2 == 0) { sts32(sb + SC_OFL, (tag - 1) * NSEG); sts64(sb + SC_EPO, (tag - 1) * NSEG + 1, NSEG); sts64(sb + SC_TAG, tag & 1, blockIdx.x / 3 * 4096 + (RANK < 2 ? RANK * 1024 - (sb >> 1) : 2048 - sb)); sts32(sb + SC_UNSC, __float_as_uint(1.f)); sts128(sb + SC_DEAD, 0, 0, 0, 0x3f800000u); sts64(sb + SC_FPAR, 0, 0); sts128(sb + SC_ONES, 0x3f803f80u, 0x3f803f80u, 0x3f803f80u, 0x3f803f80u); }
    WSTAMP(27);
    uint32_t q[8] = {0, 0, 0, 0, 0, 0, 0, 0};
    QSTAMP(2);
    mbar_wait(sb + MB_WO3, 0);
    QSTAMP(3);
    uint32_t mv[5][4];
#pragma unroll
    for (int i = 0; i < 5; i++) {
      ldsm4(mv[i], sb + SM_M0 + (lane & 7) * (DM * 2) + min(w + 4 * i, 17) * 64 + (lane >> 3) * 16);
      if (blockIdx.x == 0) hx = amax4(hx, mv[i]);
    }
#pragma unroll
    for (int k = 0; k < 8; k++) {
      ldsm4t(wo[k], wo_lane + SM_WO3 + k * 2048); ldsm4t(w1[k], wo_lane + SM_WOST + k * 2048);
#pragma unroll
      for (int i = 0; i < 4; i++) { sq_acc(q[i], wo[k][i]); sq_acc(q[i], w1[k][i]); }
    }
    bar_sync(6, 128);
#pragma unroll
    for (int k = 0; k < 8; k++) sts128(sb + SM_WO3 + t2 * 16 + k * 2048, wo[k][0], wo[k][1], wo[k][2], wo[k][3]);
#pragma unroll
    for (int i = 0; i < 5; i++) {
      const int c = (w + 4 * i) * 32;
      if (c < DM) stsm4t(sb + SM_MEM + (c + c / 192 * 64 + lane) * 16, mv[i][0], mv[i][1], mv[i][2], mv[i][3]);
    }
    bar_arrive(1, 256); bar_arrive(2, 256); bar_arrive(9, 256);
    QSTAMP(4);
    mbar_wait(sb + MB_WO, 0);
    QSTAMP(5);
#pragma unroll
    for (int k = 0; k < 8; k++) ldsm4t(wo[k], wo_lane + SM_X + XT + k * 2048);
    fence_async();
    bar_sync(6, 128);
    if (t2 == 32) tma_load3(sb + SM_X + XT, &tm.x, 32, sb + MB_X + 8);
    __syncwarp();
#pragma unroll
    for (int k = 0; k < 8; k++)
#pragma unroll
      for (int i = 0; i < 4; i++) sq_acc(q[4 + i], wo[k][i]);
    float ss = 0.f;
#pragma unroll
    for (int i = 0; i < 8; i++) ss += bf_lo(q[i]) + bf_hi(q[i]);
    ss = warp_sum(ss);
    if (lane == 0) sts32(sb + SC_SS + 4 * (8 + w), __float_as_uint(ss));
    if (blockIdx.x < NSEG) {
      mbar_wait(sb + MB_XS, 0);
#pragma unroll
      for (int i = 0; i < 18; i++) { uint32_t v[4]; lds128(sb + SM_X + 2 * XT + t2 * 16 + i * 2048, v); hx = amax4(hx, v); }
      fence_async();
      bar_sync(6, 128);
      if (t2 == 32) tma_load3(sb + SM_X + 2 * XT, &tm.x, 64, sb + MB_X + 16);
      __syncwarp();
    }
    sts32(sb + SC_SS + 4 * (12 + w), wexp(hx));
    QSTAMP(6);
    bar_sync(11, 384);
    QSTAMP(7);
    if (t2 == 0) {
      float a[16];
#pragma unroll
      for (int i = 0; i < 4; i++) lds128f(sb + SC_SS + 16 * i, &a[4 * i]);
      stg_relaxed(&g_stats[blockIdx.x * 2], __float_as_uint(((a[0] + a[1]) + (a[2] + a[3])) + ((a[4] + a[5]) + (a[6] + a[7]))),
                  __float_as_uint((a[8] + a[9]) + (a[10] + a[11])),
                  max(max(__float_as_uint(a[12]), __float_as_uint(a[13])), max(__float_as_uint(a[14]), __float_as_uint(a[15]))), tag);
    }
    __syncwarp();
    WSTAMP(24);
    QSTAMP(8);
    cluster_wait();
    QSTAMP(9);
    if (w == 0) {
      uint4 v[3];
      int n = 0;
      while (true) {
#pragma unroll
        for (int i = 0; i < 3; i++) v[i] = ldg_relaxed(&g_stats[(i * 32 + lane) * 2]);
        if (__all_sync(0xffffffffu, v[0].w == tag && v[1].w == tag && v[2].w == tag) || ++n > SPIN_LIMIT) break;
        __nanosleep(100);
      }
      WSTAMP(25);
      QSTAMP(10);
      const float sv = warp_sum(__uint_as_float(v[0].x) + __uint_as_float(v[1].x) + __uint_as_float(v[2].x));
      const float so = warp_sum(__uint_as_float(v[0].y) + __uint_as_float(v[1].y) + __uint_as_float(v[2].y));
      const int expW = ((int)(__float_as_uint(sv) >> 23) + (int)(__float_as_uint(so) >> 23) - 254 + 2 + 10 + 1) >> 1;
      sts32(sb + SC_XMAX + 4 * lane, v[0].z); sts32(sb + SC_XMAX + 128 + 4 * lane, v[1].z);
      sts32(sb + SC_EXPW, expW + 1 - 15);
      if (blockIdx.x == 0 && lane == 0) *(volatile unsigned*)&g_epoch = tag;
      sts32(sb + SC_FPAR + 4, 1);
    } else if (w < 3) {
      const uint32_t u = blockIdx.x >> 4;
      unsigned char* const z = g_red + 98304 + (blockIdx.x & 15) * 128 + (u & 1) * 2048 + (u & 6) * 4096 + (((u >> 1) ^ w) & 1) * 4096 + lane * 4;
      stg_relaxed32(z, 0);
      uint32_t best = 0xffffffffu;
#pragma unroll 1
      for (int i = 0; i < 64; i++) {
        uint32_t dt;
        asm volatile("{\n.reg .pred p;\n.reg .u32 c, v;\nmov.u32 c, %%clock;\n"
                     "atom.relaxed.gpu.global.exch.b32 v, [%1], 0;\nsetp.eq.u32 p, v, 0;\nmov.u32 %0, 0;\n@p mov.u32 %0, %%clock;\nsub.u32 %0, %0, c;\n}"
                     : "=r"(dt) : "l"(z) : "memory");
        best = min(best, dt);
        if (lds32v(sb + SC_FPAR + 4) && i >= 1) break;
      }
      sts32(sb + SC_LAT + (w - 1) * 4, best);
    }
    QSTAMP(11);
    bar_sync(13, 384);
    bar_arrive(0, 384);
    QSTAMP(12);
    WSTAMP(26);
  }

  const uint32_t nh = __shfl_sync(0xffffffffu, near_half(sb), 0);
  uint32_t l16 = sb + lane * 16;
  PIN(l16);
#define LV ((l16 >> 4) & 31)
#define fence_reg l16
  const uint32_t red_lo = (uint32_t)(uint64_t)g_red, red_hi = (uint32_t)((uint64_t)g_red >> 32);
  uint32_t lp;
  auto slot = [&](int s, uint32_t c, uint32_t ofs) {
    const uint32_t lo = lp | (red_lo + ((w >> 1) * 4 + (w & 1) * 2 + ((w ^ c) & 1)) * 4096 + RED_SLOT(s) + ofs);
    uint64_t a; asm("mov.b64 %0, {%1, %2};" : "=l"(a) : "r"(lo), "r"(red_hi));
    return (unsigned char*)a;
  };
  const uint32_t always = __shfl_sync(0xffffffffu, lds32(sb + SC_DEAD + 12), 0);
  const int mode0 = RANK < 2 ? w : w | 4;
  auto hint_addr = [&](int s) { return min(LV, 23u) * 4 + (red_lo + HINT_OFF + nh * 4096 + w * 16384 + RED_SLOT(s)); };
  auto load_hints = [&](uint32_t lo) {
    uint64_t a; asm("mov.b64 %0, {%1, %2};" : "=l"(a) : "r"(lo), "r"(red_hi));
    return ldg_relaxed32((const void*)a);
  };
  int s = 0;
  bool bad = false;
#pragma unroll 1
  while (true) {
    const uint32_t par = s & 1;
    uint32_t vx[4][4], hints;
    if (JN) { hints = hint_addr(s); PIN(hints); }
    auto load_vx = [&]() {
      const uint32_t va = l16 + (RANK < 2 ? SM_VC + par * 8192 : SM_BLK + (s & 3) * SEGB) + w * 1024 + ((LV >> 3) & 1) * 384 - (LV >> 4) * 128;
#pragma unroll
      for (int i = 0; i < 4; i++) ldsm4(vx[i], va + (i & 1) * 4096 + (i >> 1) * 256);
    };
    auto retire = [&](uint32_t x) {
      asm volatile("{\n.reg .pred p;\nsetp.eq.u32 p, %0, 0;\n@p exit;\n}" :: "r"(vx[0][0] | vx[1][0] | vx[2][0] | vx[3][0] | x) : "memory");
    };
    auto scores = [&](auto memkeys, auto first, float* sc) {
      constexpr bool MK = decltype(memkeys)::value, FIRST = decltype(first)::value;
      uint32_t kb[4][4], qb[2][4];
      const uint32_t m = LV >> 3;
      uint32_t kaddr = l16 + SM_BLK + 4096 + (s & 3) * SEGB + w * 2048 + (m & 1) * (MK ? 128 : 896) - (m >> 1) * 128;
      if (MK) { PIN(kaddr); }
      else {
#pragma unroll
        for (int k = 0; k < 4; k++) ldsm4t(kb[k], kaddr + k * 256);
      }
      if (FIRST) { load_vx(); retire(MK ? kaddr : kb[0][0] | kb[1][0] | kb[2][0] | kb[3][0] | l16); bar_sync(4, 256); PROF(4); }
      ldsm4t(qb[0], l16 + SM_QM);
      if (MK) ldsm4t(kb[0], kaddr);
      ldsm4t(qb[1], l16 + SM_QM + 512);
      if (MK) ldsm4t(kb[2], kaddr + 512);
      float c[4][4];
      mma16816z(c[0], kb[0], qb[0][0], qb[0][1]); mma16816z(c[1], kb[MK ? 0 : 1], qb[0][2], qb[0][3]);
      mma16816z(c[2], kb[2], qb[1][0], qb[1][1]); mma16816z(c[3], kb[MK ? 2 : 3], qb[1][2], qb[1][3]);
      if (FIRST) bar_arrive(5, N5);
#pragma unroll
      for (int i = 0; i < (MK ? 2 : 4); i++) sc[i] = ((c[0][i] + c[1][MK ? i + 2 : i]) + c[2][i]) + c[3][MK ? i + 2 : i];
    };
    auto send = [&](auto memkeys) {
      constexpr bool MK = decltype(memkeys)::value;
      constexpr int N = MK ? 1 : 2;
      const uint32_t sa = sb + LV * 4 + SM_E + (MK ? 1024 + RANK * 128 : RANK * 512 + w * 256);
      uint32_t ra[N][2], mb[N][2];
#pragma unroll
      for (int i = 0; i < N; i++)
#pragma unroll
        for (int j = 0; j < 2; j++) {
          ra[i][j] = mapa(sa + i * 128, j ? 2 : RANK ^ 1); mb[i][j] = mapa(sb + MB_S, j ? 2 : RANK ^ 1);
          PIN(ra[i][j]);
        }
      float sc[4];
      scores(memkeys, BoolC<true>(), sc);
      uint32_t e[N];
#pragma unroll
      for (int i = 0; i < N; i++) {
        e[i] = pack_bf16(ex2(sc[2 * i]), ex2(sc[2 * i + 1]));
        if (!(fmaxf(fabsf(sc[2 * i]), fabsf(sc[2 * i + 1])) <= E_LIM)) e[i] = 0x7fff7fffu;
        st_async1(ra[i][0], e[i], mb[i][0]);
        st_async1(ra[i][1], e[i], mb[i][1]);
      }
#pragma unroll
      for (int i = 0; i < N; i++) sts32(sa + i * 128, e[i]);
      __syncwarp();
      if (l16 == sb) mbar_arrive(sb + MB_S);
      PROF(5);
    };
    const int mode = bad ? 8 : mode0;
    if (mode < 2) {
      send(BoolC<false>());
    } else if (mode == 2) {
      send(BoolC<true>());
    } else if (mode == 8) {
      load_vx();
      retire(l16);
      const uint32_t fp = lds32(sb + SC_FPAR);
      bar_sync(6, 128);
      if (w == 0 && l16 == sb) { sts32(sb + SC_FPAR, fp ^ 1); mbar_expect(sb + MB_F, 3072); }
      if (RANK < 2 && w < 3) {
        float sc[4] = {0.f, 0.f, 0.f, 0.f};
        if (w < 2) scores(BoolC<false>(), BoolC<false>(), sc); else scores(BoolC<true>(), BoolC<false>(), sc);
#pragma unroll 1
        for (int r = 0; r < 3; r++)
          st_async4(mapa(l16 + SM_FB + RANK * 1536 + w * 512, r), __float_as_uint(sc[0]), __float_as_uint(sc[1]), __float_as_uint(sc[2]), __float_as_uint(sc[3]), mapa(sb + MB_F, r));
      }
      mbar_wait(sb + MB_F, fp);
      float a[12];
#pragma unroll
      for (int j = 0; j < 3; j++) {
        float b[4];
        lds128f(l16 + SM_FB + j * 512, a + 4 * j); lds128f(l16 + SM_FB + 1536 + j * 512, b);
#pragma unroll
        for (int i = 0; i < 4; i++) a[4 * j + i] += b[i];
      }
      float m0 = fmaxf(fmaxf(fmaxf(a[0], a[2]), fmaxf(a[4], a[6])), a[8]), m1 = fmaxf(fmaxf(fmaxf(a[1], a[3]), fmaxf(a[5], a[7])), a[9]);
#pragma unroll
      for (int o = 4; o < 32; o <<= 1) { m0 = fmaxf(m0, __shfl_xor_sync(0xffffffffu, m0, o)); m1 = fmaxf(m1, __shfl_xor_sync(0xffffffffu, m1, o)); }
#pragma unroll
      for (int i = 0; i < 5; i++) {
        const uint32_t ea = sb + SM_E + LV * 4 + (i < 4 ? i * 128 : 1024);
        sts32(ea, pack_bf16(ex2(a[2 * i] - m0), ex2(a[2 * i + 1] - m1)));
        sts32(ea + (i < 4 ? 512 : 128), 0x3f803f80u);
      }
      __syncwarp();
    } else {
      load_vx();
      if (mode == 3) bar_arrive(4, 256);
      retire(l16 + 1);
    }
    {
      uint32_t wa[4], wb[4], oc[4];
      constexpr int WS = 2048;
      const uint32_t w3a = l16 + SM_WO3 + w * 512;
      if (!JN) { lds128(w3a + KP(0) * WS, wa); lds128(w3a + KP(1) * WS, wb); lds128(sb + SC_ONES, oc); }
      uint32_t e[10], p[5], vm[4], ob[4];
      float o0[4], o1[4], f[3][2][4], rs[4];
      if (!JN) {
        reserve2(vm); reserve2(vm + 2); reserve2(e + 8);
        hints = hint_addr(s);
        PIN(hints);
      }
      mbar_wait(sb + MB_S, par);
      PROF(6);
      if (JN) {
        ldsm4t(e, l16 + SM_E); ldsm4t(e + 4, l16 + SM_E + 512);
        asm volatile("ldmatrix.sync.aligned.m8n8.x2.trans.shared.b16 {%0,%1}, [%2];" : "=r"(e[8]), "=r"(e[9]) : "r"(l16 + SM_E + 1024) : "memory");
        lds128(l16 + w * 512 + SM_VM, vm);
        if (JN & 2) oc[0] = oc[1] = oc[2] = oc[3] = always | (always >> 16); else lds128(sb + SC_ONES, oc);
        if (!(JN & 4)) { lds128(w3a + KP(0) * WS, wa); lds128(w3a + KP(1) * WS, wb); }
      } else {
      ldsm4t(e, l16 + SM_E); ldsm2t_in(e + 8, l16 + SM_E + 1024, always); ldsm4t(e + 4, l16 + SM_E + 512);
      lds128_in(vm, l16 + w * 512 + SM_VM, always);
      }
      const float scl = __uint_as_float(lds32(sb + SC_UNSC + 8 - par * 8));
      hints = load_hints(hints);
#pragma unroll
      for (int i = 0; i < 4; i++) p[i] = mul_bf16(e[i], e[4 + i]);
      p[4] = mul_bf16(e[8], e[9]);
      mma16816z(o0, vx[0], p[0], p[1]); if (JN & 4) lds128_in(vx[0], w3a + KP(0) * WS, always);
      mma16816z(o1, vx[1], p[0], p[1]); if (JN & 4) lds128_in(vx[1], w3a + KP(1) * WS, always);
      mma16816z(rs, oc, p[0], p[1]);
      mma16816(o0, vx[2], p[2], p[3]); lds128_in(vx[2], w3a + KP(2) * WS, always);
      mma16816(o1, vx[3], p[2], p[3]); lds128_in(vx[3], w3a + KP(3) * WS, always);
      mma16816(rs, oc, p[2], p[3]);
      mma1688(o0, vm[0], vm[1], p[4]); mma1688(o1, vm[2], vm[3], p[4]); mma1688(rs, oc[0], oc[1], p[4]);
      stsm4(l16 + w * 512 + SM_OB, pack_bf16(o0[0], o0[1]), pack_bf16(o0[2], o0[3]), pack_bf16(o1[0], o1[1]), pack_bf16(o1[2], o1[3]));
      bar_sync(6, 128);
      PROF(7);
      ldsm4t_in(oc, l16 + SM_OB, always);
      bad = __any_sync(0xffffffffu, !(rs[0] + rs[1] > 0.f) && !bad);
      rs[0] *= scl; rs[1] *= scl;
      asm volatile("{\n.reg .pred p;\nsetp.ne.u32 p, %1, 0;\n@p rcp.approx.ftz.f32 %0, %0;\n}" : "+f"(rs[0]) : "r"(always));
      asm volatile("{\n.reg .pred p;\nsetp.ne.u32 p, %1, 1;\n@p rcp.approx.ftz.f32 %0, %0;\n}" : "+f"(rs[1]) : "r"(always));
      asm volatile("lop3.b32 %0, %1, %2, %3, 0xfe;" : "=r"(lp) : "r"((l16 & 128) * 2), "r"((l16 & 256) * 4), "r"(l16 & 112));
      if (bad) continue;
      ldsm4t(ob, l16 + SM_OB + 512);
      mma16816z(f[2][0], JN & 4 ? vx[0] : wa, oc[0], oc[1]); mma16816z(f[2][1], JN & 4 ? vx[1] : wb, oc[2], oc[3]);
      mma16816z(f[0][0], wo[0], oc[0], oc[1]); mma16816z(f[0][1], wo[4], oc[2], oc[3]);
      mma16816z(f[1][0], w1[0], oc[0], oc[1]); mma16816z(f[1][1], w1[4], oc[2], oc[3]);
      ldsm4t_in(oc, l16 + SM_OB + 1024, always);
      mma16816(f[2][0], vx[2], ob[0], ob[1]); lds128_in(vx[2], w3a + KP(4) * WS, always);
      mma16816(f[2][1], vx[3], ob[2], ob[3]); lds128_in(vx[3], w3a + KP(5) * WS, always);
      mma16816(f[0][0], wo[1], ob[0], ob[1]); mma16816(f[0][1], wo[5], ob[2], ob[3]);
      mma16816(f[1][0], w1[1], ob[0], ob[1]); mma16816(f[1][1], w1[5], ob[2], ob[3]);
      ldsm4t_in(ob, l16 + SM_OB + 1536, always);
      mma16816(f[0][0], wo[2], oc[0], oc[1]); mma16816(f[0][1], wo[6], oc[2], oc[3]);
      mma16816(f[2][0], vx[2], oc[0], oc[1]); lds128_in(vx[2], w3a + KP(6) * WS, always);
      mma16816(f[2][1], vx[3], oc[2], oc[3]); lds128_in(vx[3], w3a + KP(7) * WS, always);
      mma16816(f[1][0], w1[2], oc[0], oc[1]); mma16816(f[1][1], w1[6], oc[2], oc[3]);
      mma16816(f[0][0], wo[3], ob[0], ob[1]); mma16816(f[0][1], wo[7], ob[2], ob[3]);
      mma16816(f[1][0], w1[3], ob[0], ob[1]); mma16816(f[1][1], w1[7], ob[2], ob[3]);
      mma16816(f[2][0], vx[2], ob[0], ob[1]); mma16816(f[2][1], vx[3], ob[2], ob[3]);
      bar_arrive(7, N7);
      lds128_in(ob, sb + SC_DEAD, always);
      uint32_t h[3][2];
#pragma unroll
      for (int j = 0; j < 3; j++)
#pragma unroll
        for (int i = 0; i < 2; i++)
        {
          scale_sum(f[j][1][2 * i], f[j][0][2 * i], rs[0], always); scale_sum(f[j][1][2 * i + 1], f[j][0][2 * i + 1], rs[1], always);
          h[j][i] = pack_f16(f[j][1][2 * i], f[j][1][2 * i + 1]);
        }
      const uint32_t rofs = RANK * 32768;
      red_f16x8(slot(s, RANK >> 1, rofs), h[0][0], h[1][0], h[2][0], 0x3c00u);
      red_f16x8(slot(s, (RANK >> 1) ^ 1, rofs), h[0][1], h[1][1], h[2][1], 0x3c00u);
      bar_arrive(10, 256);
      SCHED_FENCE(5);
      l16 += ob[1];
    }
    {
    PROF(8);
    const uint32_t ma0 = l16 + SM_MEM + w * 128 + (LV >> 3) * 896 + nh * 512;
    const unsigned char* const sl[2] = {slot(s, nh, 0), slot(s, nh ^ 1, 0)};
    uint32_t dl = gtime() - 1984;
    uint32_t late = latest_hint(hints, dl, s);
    if (late >= 64) {
      int n = 0;
#pragma unroll 1
      do {
        hints = load_hints(hint_addr(s));
        dl = gtime() - 1984;
        late = latest_hint(hints, dl, s);
      } while (late >= 64 && ++n < SPIN_LIMIT);
    }
    dl += late * 32 + tm.poll;
    PROF(9);
    {
      auto wait_until = [&](uint32_t t) {
        asm volatile("{\n.reg .pred p;\n.reg .s32 c;\n.reg .u64 t;\nTL: mov.u64 t, %%globaltimer;\ncvt.u32.u64 c, t;\nsub.s32 c, c, %0;\nsetp.lt.s32 p, c, 0;\n@p bra.uni TL;\n}" :: "r"(t + (l16 & 15)) : "memory");
      };
      uint4 v[2][3];
      auto load = [&](int c) {
#pragma unroll
        for (int r = 0; r < 3; r++) v[c][r] = ldg_relaxed(sl[c ^ (r >> 1)] + r * 32768);
      };
      auto decode = [&](int c, int n) {
        uint32_t q[9];
        __half2 hm;
        const uint32_t ma = ma0 ^ (c * 512);
#pragma unroll
        for (int i = 0; i < 9; i++) {
          const uint32_t h = i % 3 == 0 ? v[c][i / 3].x : (i % 3 == 1 ? v[c][i / 3].y : v[c][i / 3].z);
          const float2 f = __half22float2(*(const __half2*)&h);
          q[i] = pack_bf16(f.x, f.y);
          hm = i ? __hmax2(hm, __habs2(*(const __half2*)&h)) : __habs2(*(const __half2*)&h);
        }
#pragma unroll
        for (int r = 0; r < 3; r++) stsm4(ma + r * 4096, q[3 * r], q[3 * r + 1], q[3 * r + 2], r < 2 ? v[c][r].w : *(const uint32_t*)&hm);
        const bool done = __all_sync(0xffffffffu, v[c][0].w == 0x5000u && v[c][1].w == 0x5000u && v[c][2].w == 0x5000u) || n > SPIN_LIMIT;
        asm volatile("{\n.reg .pred p;\nsetp.ne.u32 p, %0, 0;\n@p bar.arrive %1, 256;\n}" :: "r"((int)done), "r"(1 + c) : "memory");
        return done;
      };
      int n = 0;
      wait_until(dl);
      PROF(10);
#pragma unroll 1
      do {
        load(0);
        load(1);
        asm volatile("{\n.reg .pred p;\nsetp.eq.u32 p, %0, 0;\n@p bar.sync 13, 384;\n}" :: "r"(n) : "memory");
      } while (!decode(0, n++));
      PROF(11);
#pragma unroll 1
      while (!decode(1, n++)) load(1);
      bar_arrive(9, 256);
      PROF(12);
    }
    PROF(13);
    if (++s == NSEG - 1) break;
    }
  }
#undef fence_reg
  if (RANK < 2) bar_arrive(4, 256);
  bar_sync(0, 384);
  cluster_sync();
}

__global__ void __cluster_dims__(3, 1, 1) __launch_bounds__(384, 1)
rec_kernel(const __grid_constant__ RMaps tm, const bf16* __restrict__ x, const bf16* __restrict__ mem0) {
  extern __shared__ __align__(1024) unsigned char smem_raw[];
  const uint32_t sb = smem_u32(smem_raw);
  const int tid = threadIdx.x, lane = tid & 31;
  const int wg = __shfl_sync(0xffffffffu, tid >> 7, 0);
  const int w = __shfl_sync(0xffffffffu, (tid >> 5) & 3, 0);
  uint32_t rank; asm("mov.u32 %0, %%cluster_ctarank;" : "=r"(rank));
  STAMP(0);
  asm volatile("griddepcontrol.launch_dependents;" ::: "memory");
    if (tid == 0) {
      const int h = blockIdx.x / 3;
      mbar_init(sb + MB_XS, 1);
      for (int i = 0; i < 3; i++) { mbar_init(sb + MB_W + 8 * i, 1); mbar_init(sb + MB_X + 8 * i, 1); }
      mbar_init(sb + MB_WO3, 1);
      fence_async();
      load_w(sb, tm, rank, 0);
      mbar_expect(sb + MB_X, XT);
      tma_load3(sb + SM_X, &tm.x, 0, sb + MB_X);
      mbar_expect(sb + MB_WO3, 32768 + 8 * DM * 2);
      tma_load(sb + SM_WOST, &tm.wo, rank * 192 + 64, h * DH, sb + MB_WO3);
      tma_load(sb + SM_WO3, &tm.wo, rank * 192 + 128, h * DH, sb + MB_WO3);
      bulk_load(sb + SM_M0, mem0, 8 * DM * 2, sb + MB_WO3);
      load_w(sb, tm, rank, 1);
      load_w(sb, tm, rank, 2);
      mbar_init(sb + MB_WO, 1);
      mbar_init(sb + MB_S, rank < 2 ? 5 : 6);
      mbar_init(sb + MB_F, 1);
      mbar_init(sb + MB_VX, 1); mbar_init(sb + MB_VX + 8, 1);
      asm volatile("fence.mbarrier_init.release.cluster;" ::: "memory");
      fence_async();
      mbar_expect(sb + MB_X + 8, XT); mbar_expect(sb + MB_X + 16, XT);
      mbar_expect(sb + MB_WO, 16384); mbar_expect(sb + MB_XS, XT);
      mbar_expect(sb + MB_S, rank < 2 ? 640 + 2048 : 1280);
      mbar_expect(sb + MB_VX, 8192); mbar_expect(sb + MB_VX + 8, 8192);
    }
  __syncwarp();
  if (wg < 2) {
    asm volatile("setmaxnreg.inc.sync.aligned.u32 192;");
    __syncwarp();
    QSTAMP(0);
    if (tid < 32) bar_arrive(0, 160);
    QSTAMP(1);
    proj_role(sb, tm, x, rank, wg, w, lane);
  } else {
    asm volatile("setmaxnreg.dec.sync.aligned.u32 120;");
    attn_role(sb, smem_raw, tm, rank, x, mem0, w, lane);
  }
}

constexpr int NAUX = 36;
constexpr int A_ST = 6, A_STAGE = 8192 + 12288, A_W8 = A_ST * A_STAGE, A_EXC = A_W8 + A_ST * 1536, A_ROWS = 57;
constexpr int A_IN = A_EXC + 8 * 2304, A_INB = 3 * SEGB, A_OST = A_IN + 2 * A_INB, A_P = A_OST + 8192, A_G = A_P + 3072;
constexpr int A_BAR = A_G + 1024;
constexpr int A_XT = A_BAR + 1024, A_XW = A_XT;
constexpr int A_TOTAL = A_XT + 4096;
static_assert(A_IN % 1024 == 0 && A_XT % 1024 == 0 && A_IN >= 4 * XT && A_IN + 64 * DM * 2 <= A_BAR && A_TOTAL <= 232448, "side kernel shared memory");
struct AMaps { CUtensorMap x, wa, wa8, o, o3, o16, wob, woa, woa16; const unsigned char* red; uint32_t poll; };

DI void wgmma_n192_ss_nt(float* d, uint64_t da, uint64_t db, int acc) {
  asm volatile("{\n.reg .pred p;\nsetp.ne.b32 p, %98, 0;\n"
               "wgmma.mma_async.sync.aligned.m64n192k16.f32.bf16.bf16 {"
               "%0,%1,%2,%3,%4,%5,%6,%7,%8,%9,%10,%11,%12,%13,%14,%15,%16,%17,%18,%19,%20,%21,%22,%23,%24,%25,%26,%27,%28,%29,%30,%31,"
               "%32,%33,%34,%35,%36,%37,%38,%39,%40,%41,%42,%43,%44,%45,%46,%47,%48,%49,%50,%51,%52,%53,%54,%55,%56,%57,%58,%59,%60,%61,%62,%63,"
               "%64,%65,%66,%67,%68,%69,%70,%71,%72,%73,%74,%75,%76,%77,%78,%79,%80,%81,%82,%83,%84,%85,%86,%87,%88,%89,%90,%91,%92,%93,%94,%95"
               "}, %96, %97, p, 1, 1, 0, 1;\n}\n"
               : ACC8(d, 0), ACC8(d, 8), ACC8(d, 16), ACC8(d, 24), ACC8(d, 32), ACC8(d, 40), ACC8(d, 48), ACC8(d, 56),
                 ACC8(d, 64), ACC8(d, 72), ACC8(d, 80), ACC8(d, 88) : "l"(da), "l"(db), "r"(acc));
}
DI void wgmma_n24_ss_nt(float* d, uint64_t da, uint64_t db, int acc) {
  asm volatile("{\n.reg .pred p;\nsetp.ne.b32 p, %14, 0;\n"
               "wgmma.mma_async.sync.aligned.m64n24k16.f32.bf16.bf16 {%0,%1,%2,%3,%4,%5,%6,%7,%8,%9,%10,%11}, %12, %13, p, 1, 1, 0, 1;\n}\n"
               : ACC8(d, 0), "+f"(d[8]), "+f"(d[9]), "+f"(d[10]), "+f"(d[11]) : "l"(da), "l"(db), "r"(acc));
}
DI void tma_load3d(uint32_t dst, const CUtensorMap* m, int c0, int c1, int c2, uint32_t mb) {
  asm volatile("cp.async.bulk.tensor.3d.shared::cluster.global.mbarrier::complete_tx::bytes [%0], [%1, {%3, %4, %5}], [%2];"
               :: "r"(dst), "l"(m), "r"(mb), "r"(c0), "r"(c1), "r"(c2) : "memory");
}
DI uint32_t trans8(uint32_t x) { uint32_t r; asm("movmatrix.sync.aligned.m8n8.trans.b16 %0, %1;" : "=r"(r) : "r"(x)); return r; }
DI void wgmma_n40_ss(float* d, uint64_t da, uint64_t db, int acc) {
  asm volatile("{\n.reg .pred p;\nsetp.ne.b32 p, %22, 0;\n"
               "wgmma.mma_async.sync.aligned.m64n40k16.f32.bf16.bf16 {%0,%1,%2,%3,%4,%5,%6,%7,%8,%9,%10,%11,%12,%13,%14,%15,%16,%17,%18,%19}, "
               "%20, %21, p, 1, 1, 1, 1;\n}\n"
               : ACC8(d, 0), ACC8(d, 8), "+f"(d[16]), "+f"(d[17]), "+f"(d[18]), "+f"(d[19]) : "l"(da), "l"(db), "r"(acc));
}
template <int ST> DI void ldg8x64(uint32_t* m, const void* p) {
  asm volatile("ld.relaxed.gpu.global.v2.b32 {%0,%1}, [%16];\nld.relaxed.gpu.global.v2.b32 {%2,%3}, [%16 + %17];\n"
               "ld.relaxed.gpu.global.v2.b32 {%4,%5}, [%16 + %18];\nld.relaxed.gpu.global.v2.b32 {%6,%7}, [%16 + %19];\n"
               "ld.relaxed.gpu.global.v2.b32 {%8,%9}, [%16 + %20];\nld.relaxed.gpu.global.v2.b32 {%10,%11}, [%16 + %21];\n"
               "ld.relaxed.gpu.global.v2.b32 {%12,%13}, [%16 + %22];\nld.relaxed.gpu.global.v2.b32 {%14,%15}, [%16 + %23];"
               : "=r"(m[0]), "=r"(m[1]), "=r"(m[2]), "=r"(m[3]), "=r"(m[4]), "=r"(m[5]), "=r"(m[6]), "=r"(m[7]),
                 "=r"(m[8]), "=r"(m[9]), "=r"(m[10]), "=r"(m[11]), "=r"(m[12]), "=r"(m[13]), "=r"(m[14]), "=r"(m[15])
               : "l"(p), "n"(ST), "n"(2 * ST), "n"(3 * ST), "n"(4 * ST), "n"(5 * ST), "n"(6 * ST), "n"(7 * ST) : "memory");
}
template <int ST> DI void ldg4x128(uint32_t* m, const void* p) {
  asm volatile("ld.relaxed.gpu.global.v4.b32 {%0,%1,%2,%3}, [%16];\nld.relaxed.gpu.global.v4.b32 {%4,%5,%6,%7}, [%16 + %17];\n"
               "ld.relaxed.gpu.global.v4.b32 {%8,%9,%10,%11}, [%16 + %18];\nld.relaxed.gpu.global.v4.b32 {%12,%13,%14,%15}, [%16 + %19];"
               : "=r"(m[0]), "=r"(m[1]), "=r"(m[2]), "=r"(m[3]), "=r"(m[4]), "=r"(m[5]), "=r"(m[6]), "=r"(m[7]),
                 "=r"(m[8]), "=r"(m[9]), "=r"(m[10]), "=r"(m[11]), "=r"(m[12]), "=r"(m[13]), "=r"(m[14]), "=r"(m[15])
               : "l"(p), "n"(ST), "n"(2 * ST), "n"(3 * ST) : "memory");
}
template <int N, int ST> DI bool stale(const uint32_t* m, uint32_t tag) {
  uint32_t x = m[0] ^ tag;
#pragma unroll
  for (int i = 1; i < N; i++) asm("lop3.b32 %0, %0, %1, %2, 0xf6;" : "+r"(x) : "r"(m[i * ST]), "r"(tag));
  return __any_sync(0xffffffffu, x & 1);
}
DI int wait_flags(const unsigned* p, bool active, unsigned base, int seg) {
  int n = 0, m;
  while (true) {
    m = __reduce_min_sync(0xffffffffu, active ? (int)(ldg_acquire32(p) - base) : NSEG);
    if (m > seg || ++n > SPIN_LIMIT) break;
    if (seg < NSEG - 2) __nanosleep(40);
  }
  return max(m, seg + 1);
}
DI void wait_count(const unsigned* p, unsigned target) {
  int n = 0;
  unsigned v;
  while (true) {
    asm volatile("ld.acquire.gpu.global.b32 %0, [%1];" : "=r"(v) : "l"(p) : "memory");
    if ((int)(v - target) >= 0 || ++n > SPIN_LIMIT) break;
    __nanosleep(64);
  }
}
#define PACE_NEXT 1024
#define FD 192
#define OD 96
#define PING 60
DI bool tick_wait(uint32_t pace, int step) {
  const int n = lds32v(pace);
  if (n <= step) mbar_wait(pace + 8, n & 1);
  return n <= step;
}
DI void sleep_until(uint32_t t) {
  for (int n = 0; n < 64; n++) {
    const int r = t - gtime();
    if (r <= 0) break;
    __nanosleep(r >> 1);
  }
}
DI void aux_barrier(int i, unsigned epoch) {
  asm volatile("fence.proxy.async;" ::: "memory");
  asm volatile("red.release.gpu.global.add.u32 [%0], 1;" :: "l"(&g_abar[i * 32]) : "memory");
  wait_count(&g_abar[i * 32], NAUX * (epoch + 1));
  asm volatile("fence.proxy.async;" ::: "memory");
}

__global__ void __launch_bounds__(512, 1)
aux_kernel(const __grid_constant__ AMaps tm, const bf16* __restrict__ x, const bf16* __restrict__ gate_w, bf16* __restrict__ out) {
  extern __shared__ __align__(1024) unsigned char smem_raw[];
  const uint32_t sb = smem_u32(smem_raw);
  const uint32_t full1 = sb + A_BAR, empty1 = full1 + 8 * A_ST, fullw = empty1 + 8 * A_ST, full3 = fullw + 16, empty3 = full3 + 32,
                 fulla = empty3 + 32, emptya = fulla + 32, fullg = emptya + 16, pace = fullg + 8;
  const int tid = threadIdx.x, lane = tid & 31, cta = blockIdx.x;
  const int wg = __shfl_sync(0xffffffffu, tid >> 7, 0), w = __shfl_sync(0xffffffffu, (tid >> 5) & 3, 0);
  ASTAMP(14);
  const unsigned epoch = *(volatile unsigned*)&g_epoch2;
  if (tid == 0) {
    for (int i = 0; i < A_ST; i++) { mbar_init(full1 + 8 * i, 1); mbar_init(empty1 + 8 * i, 8); }
    mbar_init(fullw, 1); mbar_init(fullw + 8, 1); mbar_init(fullg, 1);
    for (int i = 0; i < 2; i++) { mbar_init(fulla + 16 * i, 2); mbar_init(fulla + 16 * i + 8, 1); mbar_init(emptya + 8 * i, 4); }
    sts64(pace, 0, 0); mbar_init(pace + 8, 1); sts32(pace + 16, 0); sts64(pace + 24, 65536, 0xffff0000u);
    for (int i = 0; i < 4; i++) { mbar_init(full3 + 8 * i, 1); mbar_init(empty3 + 8 * i, cta < NH ? 8 : 4); }
    fence_async();
  }
  auto load_a = [&](int st, int k, int col) {
    mbar_expect(full1 + 8 * st, A_STAGE + 1536);
    tma_load3d(sb + st * A_STAGE, &tm.x, k, (cta >> 1) * A_ROWS - 7, 0, full1 + 8 * st);
    tma_load3d(sb + st * A_STAGE + 8192, &tm.wa, col, k, 0, full1 + 8 * st);
    tma_load3d(sb + A_W8 + st * 1536, &tm.wa8, col + 64, k, 0, full1 + 8 * st);
  };
  __syncthreads();
  ASTAMP(0);
  const bool wide = cta < NH;
  auto p3_ks = [&](int g) { return wide ? cta >> 2 : 2 * (cta - NH) + g; };
  auto p3_mt = [&](int g) { return wide ? 2 * (cta & 3) + g : 8; };
  const unsigned fbase = epoch * NSEG;
  if (wg == 3) {
    asm volatile("setmaxnreg.dec.sync.aligned.u32 48;");
    if (w == 1 && cta < NH) {
      if (lane < 3) stg_relaxed32(&g_cflag[(cta * 3 + lane) * 32], fbase);
      bar_arrive(5, 160);
#pragma unroll 1
      for (int seg = 0; seg < ((XP & 2048) ? 0 : NSEG); seg++) {
        bar_sync(4, 160);
        if (QM & 16) tick_wait(pace, seg + 1);
        if (elect_one()) {
          fence_async();
          if (!(YP & 2)) {
            tma_store(&tm.o, sb + A_OST, cta * DH, seg * 32);
            tma_store(&tm.o, sb + A_OST + 4096, cta * DH + 64, seg * 32);
          }
          asm volatile("cp.async.bulk.commit_group;" ::: "memory");
          asm volatile("cp.async.bulk.wait_group.read 0;" ::: "memory");
        }
        __syncwarp();
        if (seg < NSEG - 1) bar_arrive(5, 160);
        if (elect_one()) {
          asm volatile("cp.async.bulk.wait_group 0;" ::: "memory");
          TSTAMP(2);
          stg_relaxed32(&g_oflag[cta * 32], fbase + seg + 1);
        }
        __syncwarp();
        if (lane < 3) stg_relaxed32(&g_cflag[(cta * 3 + lane) * 32], fbase + seg + 1);
      }
    }
    if (w == 2 && cta < NH) {
      const uint32_t ktag = (epoch + 1) & 1, ma = sb + A_IN + 8192 + lane * 16;
      int avail = 0;
      int own = 0;
      bar_sync(10, 64);
#pragma unroll 1
      for (int seg = 0; seg < ((XP & 2048) ? 0 : NSEG); seg++) {
        const uint32_t b = seg & 1, full = fulla + 16 * b, mb = ma + b * A_INB;
        mbar_wait(emptya + 8 * b, (~seg >> 1) & 1);
        if (lane < 2) mbar_expect(full + 8 * lane, (YP & 8) ? 0 : 16384 >> lane);
        if (avail <= seg) {
          int n = 0;
          while (true) {
            asm volatile("ld.acquire.gpu.global.v2.b32 {%0,%1}, [%2];" : "=r"(avail), "=r"(own) : "l"(&g_sflag[(cta * 3 + min(lane, 2)) * 4]) : "memory");
            avail = __reduce_min_sync(0xffffffffu, (int)(avail - fbase));
            if (avail > seg || ++n > SPIN_LIMIT) break;
            if (seg < NSEG - 1) __nanosleep(40);
          }
        }
        const int slot = seg < own ? seg & 7 : seg;
        const int s0 = __shfl_sync(0xffffffffu, slot, 0), s1 = __shfl_sync(0xffffffffu, slot, 1), s2 = __shfl_sync(0xffffffffu, slot, 2);
        if ((QM & 8) && tick_wait(pace, seg) && FD && seg < NSEG - 2) sleep_until(gtime() + FD);
        TSTAMP(0);
        if (!(YP & 8) && elect_one()) {
          const unsigned char* src = g_seg + cta * (3 * 8192);
          const uint32_t dst = sb + A_IN + b * A_INB;
          bulk_load(dst, src + (size_t)s0 * (96 * 8192), 8192, full);
          bulk_load(dst + SEGB, src + (size_t)s1 * (96 * 8192) + 8192, 8192, full);
          bulk_load(dst + 2 * SEGB, src + (size_t)s2 * (96 * 8192) + 16384, 8192, full + 8);
        }
        __syncwarp();
        const unsigned char* km = g_km + (size_t)(seg * NH + cta) * 4096 + lane * 8;
        uint32_t m[16];
        const float g = __ldcg(&g_gate[seg * 32 + lane]);
        ldg8x64<256>(m, km);
        int n = 0;
#pragma unroll 1
        while (stale<8, 2>(m, ktag) && ++n < SPIN_LIMIT) { if (seg < NSEG - 1) __nanosleep(200); ldg8x64<256>(m, km); }
        TSTAMP(1);
#pragma unroll
        for (int i = 0; i < 4; i++) stsm4(mb + (i >> 1) * SEGB + (i & 1) * 512, m[4 * i], m[4 * i + 1], m[4 * i + 2], m[4 * i + 3]);
        sts32(sb + A_G + b * 128 + lane * 4, __float_as_uint(1.f - g));
        fence_async();
        __syncwarp();
        if (lane == 0) mbar_arrive(full);
      }
    }
    if (w == 3 && QM) {
      const unsigned char* const hp = tm.red + HINT_OFF + 65536 + (cta & 1) * 4096 + min(lane, 23) * 4;
      uint32_t d = 0;
      int s = 0, n = 0;
#pragma unroll 1
      while (s < NSEG - 1) {
        const uint32_t h = ldg_relaxed32(hp + RED_SLOT(s)), t = (gtime() - 1984) & ~31u, late = latest_hint(h, t, s);
        if (late < 64) {
          d = t + late * 32 + tm.poll;
          sleep_until(d);
          s++; n = 0;
          if (lane == 0) { mbar_arrive(pace + 8); sts64(pace, s < NSEG - 1 ? s : 2 * NSEG, d); }
          sleep_until(d + PACE_NEXT);
        } else {
          if (++n > (s ? 16 : 256) || lds32v(pace + 16)) break;
          if (!s) __nanosleep(100);
        }
      }
      if (s < NSEG - 1 && lane == 0) { mbar_arrive(pace + 8); sts64(pace, 2 * NSEG, d); }
    }
    if (w != 0) return;
    const bool lead = lane == 0;
#pragma unroll 1
    for (int it = 0, st = 0, ph = 1, k = 0, col = (cta & 1) * (DM / 2); it < ((XP & 256) ? 0 : 72); it++) {
      mbar_wait(empty1 + 8 * st, ph);
      if (elect_one()) load_a(st, k, col);
      __syncwarp();
      if (++st == A_ST) { st = 0; ph ^= 1; }
      k += 32;
      if (k == DM) { k = 0; col += 72; }
    }
    auto load_wo = [&](uint32_t dst, int g, int kb, uint32_t mb) {
      if (kb < 64) tma_load(dst, &tm.wob, p3_mt(g) * 64, kb * 64, mb);
      else tma_load(dst, &tm.woa, p3_mt(g) * 64, (kb - 64) * 64, mb);
    };
    if (lead) mbar_expect(fullw, 16 * 8192);
#pragma unroll 1
    for (int st = 0; st < A_ST; st++) {
      if (!(XP & 256)) mbar_wait(empty1 + 8 * st, 1);
      if (lane < 16 && min(((lane + 1) * 8192 - 1) / A_STAGE, A_ST - 1) == st) load_wo(sb + lane * 8192, lane >> 3, p3_ks(lane >> 3) * 9 + (lane & 7), fullw);
      __syncwarp();
    }
    __syncwarp(); bar_sync(6, 288);
    if (lead) mbar_expect(fullw + 8, 2 * 8192 + (p3_ks(0) >= 4 ? 4096 : 0));
    __syncwarp();
    if (lane < 2) {
      load_wo(sb + (16 + lane) * 8192, lane, p3_ks(lane) * 9 + 8, fullw + 8);
      if (p3_ks(0) >= 4) tma_load(sb + A_XW + lane * 2048, &tm.woa16, p3_mt(lane) * 64, 448 + p3_ks(lane) * 16, fullw + 8);
    }
    __syncwarp();
    if (lead) aux_barrier(1, epoch);
    __syncwarp(); bar_sync(6, 288);
    {
      int avail = 0, sl = 0, ph = 1;
      const int h = (9 * p3_ks(0) >> 1) + lane;
#pragma unroll 1
      for (int seg = 0; seg < ((XP & 2048) ? 0 : NSEG); seg++) {
        if (avail <= seg) avail = wait_flags(&g_oflag[min(h, NH - 1) * 32], lane < (wide ? 5 : 9), fbase, seg);
        SSTAMP(seg, 4);
        for (int g = 0; g < (wide ? 1 : 2); g++) {
          const int ks = p3_ks(g);
          mbar_wait(empty3 + 8 * sl, ph);
          if ((QM & 4) && tick_wait(pace, seg + (QM >> 4 & 1) + 1)) sleep_until(gtime() + OD);
          if (YP & 4) { if (lead) mbar_arrive(full3 + 8 * sl); }
          else if (elect_one()) {
            mbar_expect(full3 + 8 * sl, XT + (ks >= 4 ? 1024 : 0));
            tma_load3d(sb + sl * XT, &tm.o3, 0, seg * 32, ks * 9, full3 + 8 * sl);
            if (ks >= 4) tma_load(sb + A_XT + sl * 1024, &tm.o16, 72 * 64 - 64 + ks * 16, seg * 32, full3 + 8 * sl);
          }
          __syncwarp();
          if (++sl == (wide ? 3 : 4)) { sl = 0; ph ^= 1; }
        }
      }
    }
    sts32(pace + 16, 1);
    asm volatile("griddepcontrol.wait;" ::: "memory");
  } else if (wg == 2) {
    asm volatile("setmaxnreg.dec.sync.aligned.u32 64;");
    if (cta < NH) {
      if (tid == 256) { mbar_expect(fullg, 64 * DM * 2); bulk_load(sb + A_IN, x + cta * 64 * DM, 64 * DM * 2, fullg); }
      uint32_t gw[9];
#pragma unroll
      for (int j = 0; j < 9; j++) gw[j] = ((const uint32_t*)gate_w)[j * 32 + lane];
      mbar_wait(fullg, 0);
      float mine = 0.f;
#pragma unroll 4
      for (int u = 0; u < 16; u++) {
        float d0 = 0.f, d1 = 0.f;
#pragma unroll
        for (int j = 0; j < 9; j++) {
          const uint32_t a = lds32(sb + A_IN + (w * 16 + u) * (DM * 2) + j * 128 + lane * 4);
          d0 = fmaf(bf_lo(a), bf_lo(gw[j]), d0); d1 = fmaf(bf_hi(a), bf_hi(gw[j]), d1);
        }
        d0 = warp_sum(d0 + d1);
        if (lane == u) mine = d0;
      }
      if (lane < 16) g_gate[cta * 64 + w * 16 + lane] = 1.f / (1.f + __expf(-mine));
      fence_async();
    }
    bar_sync(3, 128);
    if (tid == 256) { aux_barrier(0, epoch); if (cta == 0) *(volatile unsigned*)&g_epoch2 = epoch + 1; }
    __syncwarp();
    bar_sync(3, 128);
    if (w == 0) bar_arrive(8, 288);
    if (w == 1 && cta < NH) bar_arrive(10, 64);
    if (cta < NH) {
      CDECL;
#pragma unroll 1
      for (int seg = 0; seg < ((XP & 2048) ? 0 : NSEG); seg++) {
        CSTAMP(0);
        const uint32_t in = sb + A_IN + (seg & 1) * A_INB;
        const uint64_t qd = make_desc(in, 128, 1024, 0);
        mbar_wait(fulla + 16 * (seg & 1), (seg >> 1) & 1);
        CSTAMP(3);
        SSTAMP(seg, 0);
        float d[2][16];
        {
          float a[20];
          uint32_t vm[16];
          const unsigned char* vp = g_km + (size_t)(seg * NH + cta) * 4096 + 2048 + lane * 16;
          if (w == 3) ldg4x128<512>(vm, vp);
          WG_FENCE();
#pragma unroll
          for (int k = 0; k < ((YP & 16) ? 1 : 8); k++) wgmma_n40_ss(a, qd + ((k >> 2) * SEGB + (k & 3) * 256 >> 4), qd + ((k >> 2) * SEGB + (k & 3) * 256 + 4096 >> 4), k > 0);
          const uint32_t ga = sb + A_G + (seg & 1) * 128 + (w & 1) * 64 + (lane >> 2) * 4;
          const float f0 = __uint_as_float(lds32(ga)), f1 = __uint_as_float(lds32(ga + 32));
          WG_COMMIT();
          WG_WAIT(0);
          CSTAMP(5);
          SSTAMP(seg, 1);
          if (w < 2) {
            const int lim = w * 16 + (lane >> 2) - 2 * (lane & 3);
            float m0 = -3.0e38f, m1 = -3.0e38f;
#pragma unroll
            for (int i = 0; i < 20; i++) {
              if (i < 16 && (i >> 2) * 8 + (i & 1) - (i & 2) * 4 > lim) a[i] = -1.0e9f / SM_SCALE;
              if (i & 2) m1 = fmaxf(m1, a[i]); else m0 = fmaxf(m0, a[i]);
            }
#pragma unroll
            for (int o = 1; o < 4; o <<= 1) { m0 = fmaxf(m0, __shfl_xor_sync(0xffffffffu, m0, o)); m1 = fmaxf(m1, __shfl_xor_sync(0xffffffffu, m1, o)); }
#pragma unroll
            for (int i = 0; i < 20; i++) a[i] = ex2((a[i] - (i & 2 ? m1 : m0)) * (SM_SCALE * LOG2E));
            float s0 = ((a[0] + a[1]) + (a[4] + a[5])) + ((a[8] + a[9]) + (a[12] + a[13])) + (a[16] + a[17]);
            float s1 = ((a[2] + a[3]) + (a[6] + a[7])) + ((a[10] + a[11]) + (a[14] + a[15])) + (a[18] + a[19]);
#pragma unroll
            for (int o = 1; o < 4; o <<= 1) { s0 += __shfl_xor_sync(0xffffffffu, s0, o); s1 += __shfl_xor_sync(0xffffffffu, s1, o); }
            s0 = f0 * rcp(s0); s1 = f1 * rcp(s1);
            uint32_t p[10];
#pragma unroll
            for (int i = 0; i < 10; i++) p[i] = pack_bf16(a[2 * i] * (i & 1 ? s1 : s0), a[2 * i + 1] * (i & 1 ? s1 : s0));
            const uint32_t pa = sb + A_P + (2 * w + ((lane >> 3) & 1)) * 768 + (lane >> 4) * 128 + (lane & 7) * 16;
            stsm4t(pa, p[0], p[1], p[2], p[3]); stsm4t(pa + 256, p[4], p[5], p[6], p[7]); stsm4t(pa + 512, p[8], p[9], 0, 0);
            CSTAMP(6);
            fence_async();
            CSTAMP(7);
          } else if (w == 3) {
            int n = 0;
#pragma unroll 1
            while (stale<4, 4>(vm, (epoch + 1) & 1) && ++n < SPIN_LIMIT) ldg4x128<512>(vm, vp);
#pragma unroll
            for (int i = 0; i < 4; i++) stsm4(in + 2 * SEGB + 8192 + (lane >> 4) * 1024 + (lane & 15) * 16 + i * 256, vm[4 * i], vm[4 * i + 1], vm[4 * i + 2], vm[4 * i + 3]);
            fence_async();
            mbar_wait(fulla + 16 * (seg & 1) + 8, (seg >> 1) & 1);
          }
        }
        CSTAMP(8);

        bar_sync(5, 160);
        CSTAMP(10);
        SSTAMP(seg, 2);
        const uint64_t pd = make_desc(sb + A_P, 128, 768, 0), vd = make_desc(in + 2 * SEGB, 128, 512, 0), md = make_desc(in + 2 * SEGB + 8192, 0, 128, 0);
        WG_FENCE();
#pragma unroll
        for (int i = 0; i < 2; i++) {
          wgmma_n32_ss<0>(d[i], vd + i * 256, pd, 0);
          wgmma_n32_ss<0>(d[i], vd + i * 256 + 16, pd + 16, 1);
          wgmma_n32_ss<0>(d[i], md + i * 64, pd + 32, 1);
        }
        WG_COMMIT();
        WG_WAIT(0);
        CSTAMP(11);
        if (lane == 0) mbar_arrive(emptya + 8 * (seg & 1));
#pragma unroll
        for (int i = 0; i < 2; i++) {
          const uint32_t oa = sb + A_OST + i * 4096 + ((lane & 7) + ((lane >> 4) << 3)) * 128 + (((2 * w + ((lane >> 3) & 1)) ^ (lane & 7)) << 4);
          stsm4t(oa, pack_bf16(d[i][0], d[i][1]), pack_bf16(d[i][2], d[i][3]), pack_bf16(d[i][4], d[i][5]), pack_bf16(d[i][6], d[i][7]));
          stsm4t(oa + 2048, pack_bf16(d[i][8], d[i][9]), pack_bf16(d[i][10], d[i][11]), pack_bf16(d[i][12], d[i][13]), pack_bf16(d[i][14], d[i][15]));
        }
        CSTAMP(12);
        bar_sync(4, 160);
        SSTAMP(seg, 3);
      }
      CDUMP;
    }
  } else {
    asm volatile("setmaxnreg.inc.sync.aligned.u32 200;");
    {
      const int g = lane >> 2, t = lane & 3, r0 = (cta >> 1) * A_ROWS - 7 + w * 16;
      const uint32_t prev = (2 * t > g ? 0xffffu : 0u) | (2 * t + 1 > g ? 0xffff0000u : 0u);
      const int k0 = r0 + 2 * t - (2 * t > g ? 8 : 0), k1 = r0 + 2 * t + 1 - (2 * t + 1 > g ? 8 : 0);
      const uint32_t slot = sb + A_EXC + (wg * 4 + w) * 2304;
      float gl = 0.f, gh = 0.f;
      int st = 0, ph = 0;
#pragma unroll 1
      for (int p = 0; p < ((XP & 256) ? 0 : 4); p++) {
        float big[96], sml[12];
        if (p == 3 && tid < 18) {
          const int kb = p3_ks(tid >= 9) * 9 + tid % 9;
          tma_prefetch(kb < 64 ? &tm.wob : &tm.woa, p3_mt(tid >= 9) * 64, (kb & 63) * 64);
        }
        __syncwarp();
#pragma unroll
        for (int i = 0; i < 96; i++) big[i] = 0.f;
#pragma unroll
        for (int i = 0; i < 12; i++) sml[i] = 0.f;
#pragma unroll 1
        for (int k = 0; k < 18; k++) {
          mbar_wait(full1 + 8 * st, ph);
          const uint64_t da = make_desc(sb + st * A_STAGE + wg * 4096, 16, 512, 2);
          const uint64_t db = make_desc(sb + st * A_STAGE + 8192, 4096, 1024, 1), dc = make_desc(sb + A_W8 + st * 1536, 128, 512, 0);
          WG_FENCE();
#pragma unroll
          for (int j = 0; j < 2; j++) { wgmma_n192_ss_nt(big, da + j * 2, db + j * 128, 1); wgmma_n24_ss_nt(sml, da + j * 2, dc + j * 16, 1); }
          WG_COMMIT();
          WG_WAIT(1);
          if (k > 0 && lane == 0) mbar_arrive(empty1 + 8 * (st ? st - 1 : A_ST - 1));
          if (++st == A_ST) { st = 0; ph ^= 1; }
        }
        WG_WAIT(0);
        ASTAMP(16 + p + wg * 16);
        if (lane == 0) mbar_arrive(empty1 + 8 * (st ? st - 1 : A_ST - 1));
        uint32_t f[3][9][2];
#pragma unroll
        for (int c = 0; c < 3; c++)
#pragma unroll
          for (int j = 0; j < 9; j++)
#pragma unroll
            for (int i = 0; i < 2; i++) {
              const float* a = j < 8 ? &big[(c * 8 + j) * 4 + 2 * i] : &sml[c * 4 + 2 * i];
              f[c][j][i] = c < 2 ? pack_bf16(a[0], a[1]) : trans8(pack_bf16(a[0], a[1]));
            }
        if (p == 0) {
          bar_sync(8, 288);
          gl = __ldcg(&g_gate[min(max(r0 + g, 0), S_LEN / 2 - 1) * 2 + wg]); gh = __ldcg(&g_gate[min(max(r0 + g + 8, 0), S_LEN / 2 - 1) * 2 + wg]);
        }
        asm volatile("cp.async.bulk.wait_group.read 0;" ::: "memory");
        __syncwarp();
#pragma unroll
        for (int j = 0; j < 8; j += 2) sts128(slot + j * 256 + lane * 16, f[1][j][1], f[2][j][1], f[1][j + 1][1], f[2][j + 1][1]);
        sts64(slot + 2048 + lane * 8, f[1][8][1], f[2][8][1]);
        bar_sync(1 + wg, 128);
        ASTAMP(24 + p + wg * 16);
        uint32_t pv[9][2];
#pragma unroll
        for (int j = 0; j < 9; j++) pv[j][0] = pv[j][1] = 0;
        if (w) {
#pragma unroll
          for (int j = 0; j < 8; j += 2) lds128(slot - 2304 + j * 256 + lane * 16, pv[j]);
          lds64(slot - 256 + lane * 8, pv[8][0], pv[8][1]);
        }
        float a[4][4], m[4][2];
#pragma unroll
        for (int h = 0; h < 4; h++) {
          const int j = 2 * h;
          const uint32_t qa[4] = {t >= h ? f[0][j][0] : 0, t >= h ? f[0][j][1] : 0, f[0][j + 1][0], f[0][j + 1][1]};
          const uint32_t qb0 = t <= h ? f[0][j + 2][0] : 0, qb1 = t <= h ? f[0][j + 2][1] : 0;
          float s0[4], s1[4], s2[4];
          mma16816z(s1, qa, f[1][j][0], f[1][j + 1][0]); mma16816z(s2, qa, f[1][j][1], f[1][j + 1][1]); mma16816z(s0, qa, pv[j][0], pv[j + 1][0]);
          mma1688(s1, qb0, qb1, f[1][j + 2][0]); mma1688(s2, qb0, qb1, f[1][j + 2][1]); mma1688(s0, qb0, qb1, pv[j + 2][0]);
          a[h][0] = 2 * t > g ? s0[0] : s1[0]; a[h][1] = 2 * t + 1 > g ? s0[1] : s1[1]; a[h][2] = 2 * t > g ? s1[2] : s2[2]; a[h][3] = 2 * t + 1 > g ? s1[3] : s2[3];
        }
#pragma unroll
        for (int h = 0; h < 4; h++) {
#pragma unroll
          for (int i = 0; i < 4; i++) a[h][i] = (i & 1 ? k1 : k0) + (i & 2) * 4 >= 0 ? a[h][i] * (0.23570226039551584f * LOG2E) : -1.0e9f * LOG2E;
          m[h][0] = fmaxf(a[h][0], a[h][1]); m[h][1] = fmaxf(a[h][2], a[h][3]);
        }
#pragma unroll
        for (int x = 1; x < 4; x <<= 1)
#pragma unroll
          for (int i = 0; i < 8; i++) m[i >> 1][i & 1] = fmaxf(m[i >> 1][i & 1], __shfl_xor_sync(0xffffffffu, m[i >> 1][i & 1], x));
#pragma unroll
        for (int h = 0; h < 4; h++) {
#pragma unroll
          for (int i = 0; i < 4; i++) a[h][i] = ex2(a[h][i] - m[h][i >> 1]);
          m[h][0] = a[h][0] + a[h][1]; m[h][1] = a[h][2] + a[h][3];
        }
#pragma unroll
        for (int x = 1; x < 4; x <<= 1)
#pragma unroll
          for (int i = 0; i < 8; i++) m[i >> 1][i & 1] += __shfl_xor_sync(0xffffffffu, m[i >> 1][i & 1], x);
        uint32_t o[9][2];
#pragma unroll
        for (int h = 0; h < 4; h++) {
          const int j = 2 * h;
          const float z0 = gl * rcp(m[h][0]), z1 = gh * rcp(m[h][1]);
          const uint32_t pl = pack_bf16(a[h][0] * z0, a[h][1] * z0), pu = pack_bf16(a[h][2] * z1, a[h][3] * z1);
          const uint32_t pa[4] = {pl & prev, 0, pl & ~prev, pu & prev};
          float d[3][4];
#pragma unroll
          for (int i = 0; i < 3; i++) mma16816z(d[i], pa, pv[j + i][1], f[2][j + i][0]);
#pragma unroll
          for (int i = 0; i < 3; i++) mma1688(d[i], 0, pu & ~prev, f[2][j + i][1]);
#pragma unroll
          for (int i = 0; i < 3; i++) {
            const uint32_t d0 = pack_bf16(d[i][0], d[i][1]), d1 = pack_bf16(d[i][2], d[i][3]);
            o[j + i][0] = i == 0 && h > 0 && t < h ? o[j][0] : d0;
            o[j + i][1] = i == 0 && h > 0 && t < h ? o[j][1] : d1;
          }
        }
        ASTAMP(28 + p + wg * 16);
        bar_sync(1 + wg, 128);
        const uint32_t oa = slot + (lane & 15) * 144 + (lane >> 4) * 16;
#pragma unroll
        for (int j = 0; j < 8; j += 2) stsm4(oa + j * 16, o[j][0], o[j][1], o[j + 1][0], o[j + 1][1]);
        asm volatile("stmatrix.sync.aligned.m8n8.x2.shared.b16 [%0], {%1,%2};" :: "r"(oa + 128), "r"(o[8][0]), "r"(o[8][1]) : "memory");
        fence_async();
        __syncwarp();
        if (lane < 16 && w * 16 + lane >= 7 && r0 + lane < S_LEN / 2)
          asm volatile("cp.async.bulk.global.shared::cta.bulk_group [%0], [%1], 144;"
                       :: "l"(g_Ocat + (size_t)((r0 + lane) * 2 + wg) * KCAT + 4096 + (cta & 1) * (DM / 2) + p * 72), "r"(slot + lane * 144) : "memory");
        asm volatile("cp.async.bulk.commit_group;" ::: "memory");
        ASTAMP(20 + p + wg * 16);
      }
      if (XP & 256) bar_sync(8, 288);
      asm volatile("cp.async.bulk.wait_group 0;" ::: "memory");
    }
    ASTAMP(3);
    bar_arrive(6, 288);
    uint32_t wa[37][4];
    mbar_wait(fullw, 0);
    const uint32_t la = sb + ((lane & 7) + ((lane >> 4) << 3)) * 128 + (((2 * w + ((lane >> 3) & 1)) ^ (lane & 7)) << 4);
#pragma unroll
    for (int k = 0; k < 32; k++) ldsm4t(wa[k], la + wg * 65536 + k * 2048);
    mbar_wait(fullw + 8, 0);
#pragma unroll
    for (int k = 32; k < 36; k++) ldsm4t(wa[k], la + wg * 8192 + 65536 + k * 2048);
    ldsm4t(wa[36], la + A_XW + wg * 2048);
    fence_async();
    bar_arrive(6, 288);
    ASTAMP(4);
    const int ks = p3_ks(wg), mt = p3_mt(wg);
    uint32_t v[16];
    auto fetch = [&](int seg) { ldg8x64<1024>(v, g_part + (((seg & 7) * 9 + mt) * 4 + (ks & 3)) * 1024 + (tid & 127)); };
    auto finish = [&](int seg) {
      const uint32_t tagv = (~seg >> 3) & 1;
      int n = 0;
#pragma unroll 1
      while (!(YP & 512) && stale<8, 2>(v, tagv) && ++n < SPIN_LIMIT) {
        if (seg < NSEG - 2) __nanosleep(100);
        fetch(seg);
      }
      float own[4] = {bf_lo(v[0]), bf_hi(v[0]), bf_lo(v[1]), bf_hi(v[1])};
#pragma unroll
      for (int j = 1; j < 8; j++) { own[0] += bf_lo(v[2 * j]); own[1] += bf_hi(v[2 * j]); own[2] += bf_lo(v[2 * j + 1]); own[3] += bf_hi(v[2 * j + 1]); }
      uint32_t p0 = pack_bf16(own[0], own[1]), p1 = pack_bf16(own[2], own[3]);
      asm volatile("movmatrix.sync.aligned.m8n8.trans.b16 %0, %0;" : "+r"(p0));
      asm volatile("movmatrix.sync.aligned.m8n8.trans.b16 %0, %0;" : "+r"(p1));
      const uint32_t r2 = __shfl_xor_sync(0xffffffffu, lane & 2 ? p0 : p1, 2);
      if (lane & 2) p0 = r2; else p1 = r2;
      const uint32_t r1 = __shfl_xor_sync(0xffffffffu, lane & 1 ? p0 : p1, 1);
      if (lane & 1) p0 = r1; else p1 = r1;
      if (!(YP & 256) || p0 == 0x12345678)
        *((uint2*)(out + (size_t)(seg * 32 + (ks & 3) * 8 + (lane >> 2)) * DM + mt * 64 + w * 16) + (lane & 3)) = make_uint2(p0, p1);
      SSTAMP(seg, 7);
    };
    float acc[16];
#pragma unroll
    for (int i = 0; i < 16; i++) acc[i] = 0.f;
    int pend = -1, sl = wide ? 0 : wg, ph = 0;
    if (PING && wg) bar_arrive(1, 256);
    CDECL;
    auto run = [&](auto extra) {
#pragma unroll 1
    for (int seg = 0; seg <= ((XP & 2048) ? -1 : NSEG); seg++) {
      CSTAMP(0);
      const bool fin = pend >= 0 && (seg - pend >= 2 || seg == NSEG);
      if (seg < NSEG) mbar_wait(full3 + 8 * sl, ph);
      if (fin) fetch(pend);
      CSTAMP(1);
      if (seg < NSEG) {
      if (wg) SSTAMP(seg, 5);
      if (seg < PING) bar_sync(1 + wg, 256);
      CSTAMP(7);
      const uint64_t db = make_desc(sb + sl * XT, 16, 1024, 1);
      WG_FENCE();
#pragma unroll
      for (int k = 0; k < ((XP & 1024) ? 1 : 36); k++) wgmma_n32_rs(acc, wa[k][0], wa[k][1], wa[k][2], wa[k][3], db + (k >> 2) * 256 + (k & 3) * 2, k);
      if (decltype(extra)::value) wgmma_n32_rs(acc, wa[36][0], wa[36][1], wa[36][2], wa[36][3], make_desc(sb + A_XT + sl * 1024, 16, 256, 3), 1);
      WG_COMMIT();
      if (seg < PING) bar_arrive(2 - wg, 256);
      CSTAMP(2);
      CSTAMP(3);
      WG_WAIT(0);
      CSTAMP(4);
      if (wg) SSTAMP(seg, 6);
      if (lane == 0) mbar_arrive(empty3 + 8 * sl);
      sl += wide ? 1 : 2;
      if (sl >= (wide ? 3 : 4)) { sl -= wide ? 3 : 4; ph ^= 1; }
      uint2* dst = g_part + (((seg & 7) * 9 + mt) * 32 + ks) * 128 + (tid & 127);
      uint32_t q[8];
#pragma unroll
      for (int j = 0; j < 8; j++) q[j] = j & 1 ? pack_bf16(acc[2 * j], acc[2 * j + 1]) : (pack_bf16(acc[2 * j], acc[2 * j + 1]) & ~1u) | ((~seg >> 3) & 1);
      if (QM & 32) tick_wait(pace, seg + (QM >> 4 & 1) + 2);
      if (!(YP & 1025) || q[0] == 0x12345678)
      asm volatile("st.relaxed.gpu.global.v2.b32 [%0], {%1,%2};\nst.relaxed.gpu.global.v2.b32 [%0 + 8192], {%3,%4};\n"
                   "st.relaxed.gpu.global.v2.b32 [%0 + 16384], {%5,%6};\nst.relaxed.gpu.global.v2.b32 [%0 + 24576], {%7,%8};"
                   :: "l"(dst), "r"(q[0]), "r"(q[1]), "r"(q[2]), "r"(q[3]), "r"(q[4]), "r"(q[5]), "r"(q[6]), "r"(q[7]) : "memory");
      }
      CSTAMP(5);
      if (fin) { finish(pend); pend = -1; }
      CSTAMP(6);
      if ((seg & 1) == ks >> 2 && !(YP & 1)) pend = seg;
      if (wg && (seg & 7) == 6) ASTAMP(5 + (seg >> 3));
    }
    };
    if (ks >= 4) run(BoolC<true>()); else run(BoolC<false>());
    if (PING && !wg) bar_sync(1, 256);
    CDUMP;
    ASTAMP(13);
  }
}

typedef CUresult (*EncodeFn)(CUtensorMap*, CUtensorMapDataType, cuuint32_t, void*, const cuuint64_t*, const cuuint64_t*,
                             const cuuint32_t*, const cuuint32_t*, CUtensorMapInterleave, CUtensorMapSwizzle,
                             CUtensorMapL2promotion, CUtensorMapFloatOOBfill);
static void make_map(EncodeFn enc, CUtensorMap* m, const void* p, int rows, int cols, int box_rows) {
  cuuint64_t dims[2] = {(cuuint64_t)cols, (cuuint64_t)rows};
  cuuint64_t strides[1] = {(cuuint64_t)cols * 2};
  cuuint32_t box[2] = {64, (cuuint32_t)box_rows};
  cuuint32_t es[2] = {1, 1};
  enc(m, CU_TENSOR_MAP_DATA_TYPE_BFLOAT16, 2, (void*)p, dims, strides, box, es, CU_TENSOR_MAP_INTERLEAVE_NONE,
      CU_TENSOR_MAP_SWIZZLE_128B, CU_TENSOR_MAP_L2_PROMOTION_L2_128B, CU_TENSOR_MAP_FLOAT_OOB_FILL_NONE);
}

constexpr int g_poll = POLL_NS;
extern "C" void kernel_launch(void* const* d_in, const int* in_sizes, int n_in, void* d_out, int out_size) {
  const bf16* x = (const bf16*)d_in[0];
  const bf16* wqkvA = (const bf16*)d_in[1];
  const bf16* woA = (const bf16*)d_in[2];
  const bf16* mem0 = (const bf16*)d_in[4];
  const bf16* Wq = (const bf16*)d_in[5];
  const bf16* Wk = (const bf16*)d_in[6];
  const bf16* Wv = (const bf16*)d_in[7];
  const bf16* Wo = (const bf16*)d_in[8];
  const bf16* gate_w = (const bf16*)d_in[10];
  static EncodeFn enc = nullptr;
  static void *pO = nullptr, *pR = nullptr, *pF = nullptr;
  if (!enc) {
    cudaDriverEntryPointQueryResult qr;
    cudaGetDriverEntryPoint("cuTensorMapEncodeTiled", (void**)&enc, cudaEnableDefault, &qr);
    cudaGetSymbolAddress(&pO, g_Ocat);
    cudaGetSymbolAddress(&pR, g_red_raw);
    cudaGetSymbolAddress(&pF, g_cflag);
    cudaFuncSetAttribute(rec_kernel, cudaFuncAttributeMaxDynamicSharedMemorySize, SM_TOTAL);
    cudaFuncSetAttribute(aux_kernel, cudaFuncAttributeMaxDynamicSharedMemorySize, A_TOTAL);
  }
  RMaps rm;
  rm.poll = g_poll;
  rm.oflag = (const unsigned char*)pF;
  rm.red = (unsigned char*)(((uintptr_t)pR + 262143) & ~(uintptr_t)262143);
  {
    cuuint64_t dims[3] = {64, S_LEN, 9}, strides[2] = {DM * 2, 128};
    cuuint32_t box[3] = {64, 32, 9}, es[3] = {1, 1, 1};
    enc(&rm.x, CU_TENSOR_MAP_DATA_TYPE_BFLOAT16, 3, (void*)x, dims, strides, box, es, CU_TENSOR_MAP_INTERLEAVE_NONE,
        CU_TENSOR_MAP_SWIZZLE_128B, CU_TENSOR_MAP_L2_PROMOTION_L2_128B, CU_TENSOR_MAP_FLOAT_OOB_FILL_NONE);
  }
  make_map(enc, &rm.wq, Wq, DM, 4096, 192);
  make_map(enc, &rm.wk, Wk, DM, 4096, 192);
  make_map(enc, &rm.wv, Wv, DM, 4096, 192);
  make_map(enc, &rm.wo, Wo, 4096, DM, 128);
  AMaps am;
  am.red = rm.red; am.poll = rm.poll;
  {
    cuuint64_t dims[3] = {DM, S_LEN / 2, 2}, strides[2] = {DM * 4, DM * 2};
    cuuint32_t box[3] = {32, 64, 2}, es[3] = {1, 1, 1};
    enc(&am.x, CU_TENSOR_MAP_DATA_TYPE_BFLOAT16, 3, (void*)x, dims, strides, box, es, CU_TENSOR_MAP_INTERLEAVE_NONE,
        CU_TENSOR_MAP_SWIZZLE_64B, CU_TENSOR_MAP_L2_PROMOTION_L2_128B, CU_TENSOR_MAP_FLOAT_OOB_FILL_NONE);
    cuuint64_t wdims[3] = {DM, DM, 3}, wstrides[2] = {DM * 6, DM * 2};
    cuuint32_t wbox[3] = {64, 32, 3}, wbox8[3] = {8, 32, 3};
    enc(&am.wa, CU_TENSOR_MAP_DATA_TYPE_BFLOAT16, 3, (void*)wqkvA, wdims, wstrides, wbox, es, CU_TENSOR_MAP_INTERLEAVE_NONE,
        CU_TENSOR_MAP_SWIZZLE_128B, CU_TENSOR_MAP_L2_PROMOTION_L2_128B, CU_TENSOR_MAP_FLOAT_OOB_FILL_NONE);
    enc(&am.wa8, CU_TENSOR_MAP_DATA_TYPE_BFLOAT16, 3, (void*)wqkvA, wdims, wstrides, wbox8, es, CU_TENSOR_MAP_INTERLEAVE_NONE,
        CU_TENSOR_MAP_SWIZZLE_NONE, CU_TENSOR_MAP_L2_PROMOTION_NONE, CU_TENSOR_MAP_FLOAT_OOB_FILL_NONE);
  }
  {
    cuuint64_t dims[3] = {64, S_LEN, KCAT / 64}, strides[2] = {KCAT * 2, 128};
    cuuint32_t box[3] = {64, 32, 9}, es[3] = {1, 1, 1};
    make_map(enc, &am.o, pO, S_LEN, KCAT, 32);
    enc(&am.o3, CU_TENSOR_MAP_DATA_TYPE_BFLOAT16, 3, pO, dims, strides, box, es, CU_TENSOR_MAP_INTERLEAVE_NONE,
        CU_TENSOR_MAP_SWIZZLE_128B, CU_TENSOR_MAP_L2_PROMOTION_L2_128B, CU_TENSOR_MAP_FLOAT_OOB_FILL_NONE);
  }
  make_map(enc, &am.wob, Wo, 4096, DM, 64);
  make_map(enc, &am.woa, woA, DM, DM, 64);
  make_map(enc, &am.woa16, woA, DM, DM, 16);
  {
    cuuint64_t dims[2] = {KCAT, S_LEN}, strides[1] = {KCAT * 2};
    cuuint32_t box[2] = {16, 32}, es[2] = {1, 1};
    enc(&am.o16, CU_TENSOR_MAP_DATA_TYPE_BFLOAT16, 2, pO, dims, strides, box, es, CU_TENSOR_MAP_INTERLEAVE_NONE,
        CU_TENSOR_MAP_SWIZZLE_32B, CU_TENSOR_MAP_L2_PROMOTION_NONE, CU_TENSOR_MAP_FLOAT_OOB_FILL_NONE);
  }

  rec_kernel<<<96, 384, SM_TOTAL, cudaStreamPerThread>>>(rm, x, mem0);
  cudaLaunchConfig_t cfg = {};
  cfg.gridDim = dim3(NAUX); cfg.blockDim = dim3(512); cfg.dynamicSmemBytes = A_TOTAL; cfg.stream = cudaStreamPerThread;
  cudaLaunchAttribute at[1];
  at[0].id = cudaLaunchAttributeProgrammaticStreamSerialization; at[0].val.programmaticStreamSerializationAllowed = 1;
  cfg.attrs = at; cfg.numAttrs = 1;
  if (XP & 16) cfg.numAttrs = 0;
  if (!(XP & 64)) cudaLaunchKernelEx(&cfg, aux_kernel, am, x, gate_w, (bf16*)d_out);
}
```
